```python
import torch

def _softmax(x, axis=-1):
    return torch.softmax(x, dim=axis)

def _gelu(x):
    return torch.nn.functional.gelu(x, approximate='tanh')

def _silu(x):
    return torch.nn.functional.silu(x)

def _sigmoid(x):
    return torch.sigmoid(x)

def _layernorm(x, axis=-1, eps=1e-05):
    m = x.mean(dim=axis, keepdim=True)
    v = x.var(dim=axis, keepdim=True, unbiased=False)
    return (x - m) / torch.sqrt(v + eps)

def _scatter_add(tgt, idx, src, axis=0):
    return tgt.clone().index_add_(axis, idx, src)

def _segment_sum(src, seg, n):
    out = torch.zeros((n,) + src.shape[1:], dtype=src.dtype)
    return out.index_add_(0, seg, src)

def _pad(x, pw):
    flat = tuple((v for pair in reversed(pw) for v in pair))
    return torch.nn.functional.pad(x, flat)
kernel_name = 'adaLN_cond__compressed_kv_cla__glu_gated_geglu__decode'

def setup_inputs():

    _w = lambda a: (lambda t: t.to(torch.bfloat16) if t.is_floating_point() else t)(torch.as_tensor(a))

    def _A_setup():
        B, H, Sq, Sk, D, M = (1, 32, 1, 32768, 128, 512)
        Dc = 4 * D
        return {'x': _w((lambda *s: torch.randn(*s, dtype=torch.bfloat16) * 0.1)(B, Sq, M)), 'c_kv': _w((lambda *s: torch.randn(*s, dtype=torch.bfloat16) * 3.2)(B, Sk, Dc)), 'w_q': _w((lambda *s: torch.randn(*s, dtype=torch.bfloat16) * 0.8)(M, H, D) * M ** (-0.5)), 'w_uk': _w((lambda *s: torch.randn(*s, dtype=torch.bfloat16) * 0.8)(Dc, H, D) * Dc ** (-0.5)), 'w_uv': _w((lambda *s: torch.randn(*s, dtype=torch.bfloat16) * 3.2)(Dc, H, D) * Dc ** (-0.5)), 'w_o': _w((lambda *s: torch.randn(*s, dtype=torch.bfloat16) * 3.2)(H, D, M) * (H * D) ** (-0.5))}
    _A_in = _A_setup()

    def _B_setup():
        B, S, Dm, Df = (1, 1, 512, 1792)
        return {'x': _w((lambda *s: torch.randn(*s, dtype=torch.bfloat16) * 0.1)(B, S, Dm)), 'w_gate': _w((lambda *s: torch.randn(*s, dtype=torch.bfloat16) * 1.6)(Dm, Df) * Dm ** (-0.5)), 'w_up': _w((lambda *s: torch.randn(*s, dtype=torch.bfloat16) * 1.6)(Dm, Df) * Dm ** (-0.5)), 'w_down': _w((lambda *s: torch.randn(*s, dtype=torch.bfloat16) * 1.6)(Df, Dm) * Df ** (-0.5))}
    _B_in = _B_setup()
    return {'A_x': _A_in['x'], 'A_c_kv': _A_in['c_kv'], 'A_w_q': _A_in['w_q'], 'A_w_uk': _A_in['w_uk'], 'A_w_uv': _A_in['w_uv'], 'A_w_o': _A_in['w_o'], 'B_x': _B_in['x'], 'B_w_gate': _B_in['w_gate'], 'B_w_up': _B_in['w_up'], 'B_w_down': _B_in['w_down'], 'c': _w((lambda *s: torch.randn(*s, dtype=torch.bfloat16) * 0.1)(1, 512) * 8.0), 'w_mod': _w((lambda *s: torch.randn(*s, dtype=torch.bfloat16) * 0.1)(512, 6 * 512) * 512 ** (-0.5) * 8.0)}

def reference(A_x, A_c_kv, A_w_q, A_w_uk, A_w_uv, A_w_o, B_x, B_w_gate, B_w_up, B_w_down, c, w_mod):

    def _A_ref(x, c_kv, w_q, w_uk, w_uv, w_o):
        B, Sq, M = (x.shape[0], x.shape[1], x.shape[2])
        Sk = c_kv.shape[1]
        H, D = (w_q.shape[1], w_q.shape[2])
        q = torch.einsum('bqm,mhd->bhqd', x, w_q)
        k = torch.einsum('bkc,chd->bhkd', c_kv, w_uk)
        v = torch.einsum('bkc,chd->bhkd', c_kv, w_uv)
        scores = torch.einsum('bhqd,bhkd->bhqk', q, k) * D ** (-0.5)
        off = Sk - Sq
        qi = torch.arange(Sq)[:, None]
        kj = torch.arange(Sk)[None, :]
        cmask = kj <= qi + off
        scores = torch.where(cmask[None, None], scores, -1000000000.0)
        p = _softmax(scores, axis=-1)
        ctx = torch.einsum('bhqk,bhkd->bhqd', p, v)
        return torch.einsum('bhqd,hdm->bqm', ctx, w_o)

    def _B_ref(x, w_gate, w_up, w_down):
        g = torch.einsum('bsd,df->bsf', x, w_gate)
        u = torch.einsum('bsd,df->bsf', x, w_up)
        h = _gelu(g) * u
        return torch.einsum('bsf,fd->bsd', h, w_down)
    x = A_x
    mod = (_silu(c) @ w_mod).reshape(c.shape[0], 6, 1, -1)
    sa, ca, ga, sb, cb, gb = (mod[:, 0].clone(), mod[:, 1].clone(), mod[:, 2].clone(), mod[:, 3].clone(), mod[:, 4].clone(), mod[:, 5].clone())
    h = _layernorm(x, axis=-1) * (1 + ca) + sa
    x = x + ga * _A_ref(h, A_c_kv, A_w_q, A_w_uk, A_w_uv, A_w_o)
    h = _layernorm(x, axis=-1) * (1 + cb) + sb
    x = x + gb * _B_ref(h, B_w_gate, B_w_up, B_w_down)
    return x
```

```cpp
#include <cuda_runtime.h>
#include <cuda_bf16.h>
#include <cuda.h>
#include <stdint.h>
#include <stdio.h>
#include <stdlib.h>

typedef CUresult (*EncFn)(CUtensorMap*, CUtensorMapDataType, cuuint32_t, void*, const cuuint64_t*, const cuuint64_t*,
                          const cuuint32_t*, const cuuint32_t*, CUtensorMapInterleave, CUtensorMapSwizzle,
                          CUtensorMapL2promotion, CUtensorMapFloatOOBfill);

static void enc3d(EncFn fn, CUtensorMap* tm, void* p, uint64_t d0, uint64_t d1, uint64_t d2, uint64_t s1, uint64_t s2, uint32_t b0,
                  uint32_t b1, uint32_t b2, CUtensorMapSwizzle sw, CUtensorMapL2promotion pr) {
  cuuint64_t gd[3] = {d0, d1, d2}, gs[2] = {s1, s2};
  cuuint32_t bx[3] = {b0, b1, b2}, es[3] = {1, 1, 1};
  fn(tm, CU_TENSOR_MAP_DATA_TYPE_BFLOAT16, 3, p, gd, gs, bx, es, CU_TENSOR_MAP_INTERLEAVE_NONE, sw, pr, CU_TENSOR_MAP_FLOAT_OOB_FILL_NONE);
}

namespace v9 {
typedef __nv_bfloat16 bf16;
#define SK 32768
#define SPIN_MAX (1 << 20)
template <int N> struct IC { static constexpr int value = N; };

__device__ __forceinline__ uint32_t s2u(const void* p) { return (uint32_t)__cvta_generic_to_shared(p); }
__device__ __forceinline__ float bflo(uint32_t u) { return __uint_as_float(u << 16); }
__device__ __forceinline__ float bfhi(uint32_t u) { return __uint_as_float(u & 0xffff0000u); }
__device__ __forceinline__ float u2f(uint32_t u) { return __uint_as_float(u); }
__device__ __forceinline__ void fma8(float* acc, uint4 v, float s) {
  acc[0] += s * bflo(v.x); acc[1] += s * bfhi(v.x); acc[2] += s * bflo(v.y); acc[3] += s * bfhi(v.y);
  acc[4] += s * bflo(v.z); acc[5] += s * bfhi(v.z); acc[6] += s * bflo(v.w); acc[7] += s * bfhi(v.w);
}
__device__ __forceinline__ uint32_t pack2(float a, float b) {
  __nv_bfloat162 p = __floats2bfloat162_rn(a, b); return *(uint32_t*)&p;
}
__device__ __forceinline__ float bfr(float v) { return bfhi(pack2(v, v)); }
__device__ __forceinline__ float silu_bf(float c) { return bfr(__fdividef(c, 1.f + __expf(-c))); }
#define fbits(v) ((__float_as_uint(v) & ~1u) | par)
__device__ __forceinline__ uint32_t pack2t(float a, float b, unsigned par) {
  const uint32_t ua = ((__float_as_uint(a) + ((par ^ 1) << 16)) & 0xFFFE0000u) | (par << 16);
  return __byte_perm(ua, pack2(b, b), 0x7632);
}
__device__ __forceinline__ void nbar(int id, int n) { asm volatile("bar.sync %0, %1;" ::"r"(id), "r"(n) : "memory"); }
__device__ __forceinline__ void nbar_arrive(int id, int n) { asm volatile("bar.arrive %0, %1;" ::"r"(id), "r"(n) : "memory"); }
__device__ __forceinline__ uint4 ldc16(const void* p) {
  uint4 v; asm volatile("ld.relaxed.cta.global.v4.u32 {%0,%1,%2,%3}, [%4];" : "=r"(v.x), "=r"(v.y), "=r"(v.z), "=r"(v.w) : "l"(p) : "memory"); return v;
}
__device__ __forceinline__ unsigned ldc4(const void* p) {
  unsigned v; asm volatile("ld.relaxed.cta.global.u32 %0, [%1];" : "=r"(v) : "l"(p) : "memory"); return v;
}
__device__ __forceinline__ uint4 ldx16(const void* p) {
  uint4 v; asm volatile("ld.relaxed.gpu.global.v4.u32 {%0,%1,%2,%3}, [%4];" : "=r"(v.x), "=r"(v.y), "=r"(v.z), "=r"(v.w) : "l"(p) : "memory"); return v;
}
__device__ __forceinline__ unsigned ldx4(const void* p) {
  unsigned v; asm volatile("ld.relaxed.gpu.global.u32 %0, [%1];" : "=r"(v) : "l"(p) : "memory"); return v;
}
__device__ __forceinline__ unsigned long long ldx64(const void* p) {
  unsigned long long v; asm volatile("ld.relaxed.gpu.global.u64 %0, [%1];" : "=l"(v) : "l"(p) : "memory"); return v;
}
__device__ __forceinline__ void stx16(void* p, uint4 v) {
  asm volatile("st.relaxed.gpu.global.v4.u32 [%0], {%1,%2,%3,%4};" ::"l"(p), "r"(v.x), "r"(v.y), "r"(v.z), "r"(v.w) : "memory");
}
__device__ __forceinline__ void stx8(void* p, uint2 v) { asm volatile("st.relaxed.gpu.global.v2.u32 [%0], {%1,%2};" ::"l"(p), "r"(v.x), "r"(v.y) : "memory"); }
__device__ __forceinline__ void stx4(void* p, unsigned v) { asm volatile("st.relaxed.gpu.global.u32 [%0], %1;" ::"l"(p), "r"(v) : "memory"); }
__device__ __forceinline__ void pub4(void* p, unsigned v) { asm volatile("red.relaxed.gpu.global.xor.b32 [%0], %1;" ::"l"(p), "r"(v) : "memory"); }
__device__ __forceinline__ void pub8(void* p, unsigned lo, unsigned hi) {
  asm volatile("{.reg .b64 t; mov.b64 t, {%1, %2}; red.relaxed.gpu.global.xor.b64 [%0], t;}" ::"l"(p), "r"(lo), "r"(hi) : "memory");
}
__device__ __forceinline__ unsigned lop_x3(unsigned a, unsigned b, unsigned c) {
  unsigned d; asm("lop3.b32 %0, %1, %2, %3, 0x7E;" : "=r"(d) : "r"(a), "r"(b), "r"(c)); return d; }
__device__ __forceinline__ unsigned or3(unsigned a, unsigned b, unsigned c) {
  unsigned d; asm("lop3.b32 %0, %1, %2, %3, 0xFE;" : "=r"(d) : "r"(a), "r"(b), "r"(c)); return d; }
__device__ __forceinline__ unsigned and3(unsigned a, unsigned b, unsigned c) {
  unsigned d; asm("lop3.b32 %0, %1, %2, %3, 0x80;" : "=r"(d) : "r"(a), "r"(b), "r"(c)); return d; }
__device__ __forceinline__ uint2 ldx8(const void* p) {
  uint2 v; asm volatile("{.reg .b64 t; ld.relaxed.gpu.global.b64 t, [%2]; mov.b64 {%0, %1}, t;}" : "=r"(v.x), "=r"(v.y) : "l"(p) : "memory"); return v;
}
__device__ __forceinline__ float lds4(uint32_t a) { float v; asm volatile("ld.shared.f32 %0, [%1];" : "=f"(v) : "r"(a) : "memory"); return v; }
__device__ __forceinline__ float shx(float v, int m) {
  float r; asm volatile("shfl.sync.bfly.b32 %0, %1, %2, 0x1f, 0xffffffff;" : "=f"(r) : "f"(v), "r"(m)); return r;
}
__device__ __forceinline__ uint32_t mbar_test(uint32_t bar, uint32_t ph) {
  uint32_t ok;
  asm volatile("{.reg .pred p; mbarrier.test_wait.parity.shared::cta.b64 p, [%1], %2; vote.sync.all.pred p, p, 0xffffffff; selp.u32 %0, 1, 0, p;}"
               : "=r"(ok) : "r"(bar), "r"(ph) : "memory");
  return ok;
}
#define X16(v) (lop_x3(v.x, v.y, par) | lop_x3(v.z, v.w, par))
#define RETRY(bad) if (!__any_sync(~0u, (bad) & 1) || ++it_ >= SPIN_MAX) break;
#define POLL _Pragma("unroll 1") for (int it_ = 0;;)
__device__ __forceinline__ void mbar_wait(uint32_t bar, uint32_t ph = 0) {
  asm volatile("{.reg .pred p; .reg .u32 n; mov.u32 n, 0;\n"
               "W%=: mbarrier.try_wait.parity.shared::cta.b64 p, [%0], %1; add.u32 n, n, 1; setp.lt.and.u32 p, n, 0x100000, !p; @p bra W%=;}"
               ::"r"(bar), "r"(ph) : "memory");
}
__device__ __forceinline__ float ex2(float v) { float r; asm("ex2.approx.ftz.f32 %0, %1;" : "=f"(r) : "f"(v)); return r; }
__device__ __forceinline__ float rcp(float v) { float r; asm("rcp.approx.ftz.f32 %0, %1;" : "=f"(r) : "f"(v)); return r; }
__device__ __forceinline__ void mma16(float* d, const uint32_t* a, uint32_t b0, uint32_t b1) {
  asm volatile("mma.sync.aligned.m16n8k16.row.col.f32.bf16.bf16.f32 {%0,%1,%2,%3}, {%4,%5,%6,%7}, {%8,%9}, {%0,%1,%2,%3};"
               : "+f"(d[0]), "+f"(d[1]), "+f"(d[2]), "+f"(d[3]) : "r"(a[0]), "r"(a[1]), "r"(a[2]), "r"(a[3]), "r"(b0), "r"(b1));
}
__device__ __forceinline__ float4 lds16(uint32_t a) {
  float4 v; asm volatile("ld.shared.v4.f32 {%0,%1,%2,%3}, [%4];" : "=f"(v.x), "=f"(v.y), "=f"(v.z), "=f"(v.w) : "r"(a) : "memory"); return v;
}
__device__ __forceinline__ uint4 ldsv16(uint32_t a) {
  uint4 v; asm volatile("ld.relaxed.cluster.shared.v4.u32 {%0,%1,%2,%3}, [%4];" : "=r"(v.x), "=r"(v.y), "=r"(v.z), "=r"(v.w) : "r"(a) : "memory"); return v;
}
__device__ __forceinline__ void sts4(uint32_t a, float v) { asm volatile("st.shared.f32 [%0], %1;" ::"r"(a), "f"(v) : "memory"); }
__device__ __forceinline__ void sts16(uint32_t a, uint4 v) {
  asm volatile("st.shared.v4.b32 [%0], {%1,%2,%3,%4};" ::"r"(a), "r"(v.x), "r"(v.y), "r"(v.z), "r"(v.w) : "memory");
}
__device__ __forceinline__ void ldsm_t(uint32_t* r, uint32_t a) {
  asm volatile("ldmatrix.sync.aligned.m8n8.x4.trans.shared.b16 {%0,%1,%2,%3}, [%4];" : "=r"(r[0]), "=r"(r[1]), "=r"(r[2]), "=r"(r[3]) : "r"(a) : "memory");
}
__device__ __forceinline__ void ldsm(uint32_t* r, uint32_t a) {
  asm volatile("ldmatrix.sync.aligned.m8n8.x4.shared.b16 {%0,%1,%2,%3}, [%4];" : "=r"(r[0]), "=r"(r[1]), "=r"(r[2]), "=r"(r[3]) : "r"(a) : "memory");
}
__device__ __forceinline__ uint32_t mapa(uint32_t a, uint32_t r) {
  uint32_t v; asm volatile("mapa.shared::cluster.u32 %0, %1, %2;" : "=r"(v) : "r"(a), "r"(r)); return v;
}
__device__ __forceinline__ unsigned long long mapg(uint32_t a, uint32_t r) {
  unsigned long long v;
  asm volatile("{.reg .u32 t; .reg .u64 u; mapa.shared::cluster.u32 t, %1, %2; cvt.u64.u32 u, t; cvta.shared::cluster.u64 %0, u;}" : "=l"(v) : "r"(a), "r"(r));
  return v;
}
template <int N>
__device__ __forceinline__ void tred(float* a, int lane, int m) {
  const bool hi = lane & m;
#pragma unroll
  for (int i = 0; i < N; i++) {
    float send = hi ? a[i] : a[i + N], keep = hi ? a[i + N] : a[i];
    a[i] = keep + __shfl_xor_sync(~0u, send, m);
  }
}
template <int N>
__device__ __forceinline__ void tmax(float* a, int lane, int m) {
  const bool hi = lane & m;
#pragma unroll
  for (int i = 0; i < N; i++) {
    float send = hi ? a[i] : a[i + N], keep = hi ? a[i + N] : a[i];
    a[i] = fmaxf(keep, __shfl_xor_sync(~0u, send, m));
  }
}
__device__ __forceinline__ void arrive_n(uint32_t bar, bool on, int cnt) {
  asm volatile("{.reg .pred p; setp.ne.s32 p, %1, 0; @p mbarrier.arrive.shared::cta.b64 _, [%0], %2;}" ::"r"(bar), "r"((int)on), "r"(cnt) : "memory");
}
__device__ __forceinline__ unsigned long long stream_policy() {
  unsigned long long p;
  asm volatile("createpolicy.fractional.L2::evict_first.b64 %0, 1.0;" : "=l"(p));
  return p;
}
__device__ __forceinline__ void tma3d(uint32_t dst, const CUtensorMap* tm, uint32_t bar, int c0, int c1, int c2) {
  asm volatile("cp.async.bulk.tensor.3d.shared::cluster.global.mbarrier::complete_tx::bytes.L2::cache_hint [%0], [%1, {%3, %4, %5}], [%2], %6;"
               ::"r"(dst), "l"(tm), "r"(bar), "r"(c0), "r"(c1), "r"(c2), "l"(stream_policy()) : "memory");
}
__device__ __forceinline__ void spin_until(unsigned t) { while ((int)((unsigned)clock() - t) < 0) {} }
__device__ __forceinline__ void wait_until(unsigned t) {
  unsigned now;
  do { asm volatile("mov.u32 %0, %%globaltimer_lo;" : "=r"(now)); } while ((int)(now - t) < 0);
}
__device__ __forceinline__ void sleep_until(unsigned t) {
  unsigned now;
  for (;;) {
    asm volatile("mov.u32 %0, %%globaltimer_lo;" : "=r"(now));
    if ((int)(now - t) >= 0) break;
    __nanosleep(min(t - now, 1000u) >> 1);
  }
}
#define PIN(x) asm volatile("" : "+r"(x))
#define PINL(x) asm volatile("" : "+l"(x))
#define BAR_ARRIVE(i) asm volatile("mbarrier.arrive.shared::cta.b64 _, [%0];" ::"r"(bar0 + 8 * (i)) : "memory")
#define CNT_ADD(c) asm volatile("red.relaxed.gpu.global.add.u32 [%0], 1;" ::"l"(scr->cnt + (c)) : "memory")
#define BAR_INIT(i, cnt) asm volatile("mbarrier.init.shared::cta.b64 [%0], %1;" ::"r"(bar0 + 8 * (i)), "r"(cnt) : "memory")
#define BAR_ARM(i, bytes) asm volatile("mbarrier.arrive.expect_tx.shared::cta.b64 _, [%0], %1;" ::"r"(bar0 + 8 * (i)), "r"(bytes) : "memory")
struct TMaps { CUtensorMap m[9]; };

#define NCTA9 120
#define TAU 32.f
#define NSL 100
#define NPO 3
#define VDLY 150
#define HWIN 6
#define O_Q 131072
#define O_LZ 163840
#define O_CTX 196608
#define O_HZ 198656
#define O_X 199680
#define O_P 216064
#define O_B 220160
#define O_R 222464
#define O_SILU 226560
#define O_SM 227584
#define O_BAR 229376
#define O_EP (O_BAR + 256)
#define O_DBG (O_EP + 16)
#define SMEM9 (O_DBG + 128)
#define B_FULL 0
#define B_FM 8
#define B_EMPTY 10
#define B_EM 18
#define B_Q2 19
#define B_H 20
#define B_QF 21
#define B_TAB 22
#define B_W 23
#define B_ST 24
#define B_HZ 25
#define B_WZ 26
#define B_G2 28
#define B_G 27
enum { T_WQ, T_WUK, T_KV, T_MOD, T_UV, T_WO, T_GU, T_DN = 8 };
#define NBIG 40
struct Sched { unsigned t0, dth; uint2 r[3][8]; unsigned nr[3], nt[3], dt, t4, d7, d4, d6; };

struct __align__(128) Scratch {
  unsigned cnt[8 * 32];
  uint2 rec[32 * 4 * 8 * 64];
  uint2 hdr[32 * 16];
  unsigned h[8 * 256];
  uint4 qa[2048];
  unsigned xao[8 * 512];
  unsigned xf[32 * 56 * 16];
  unsigned xm[2048];
};
__device__ Scratch g_scr;
#define SMEM_BASE 1024u
#define DSC ((SMEM_BASE >> 4) | (1u << 16))
#define HI128 (64u | (1u << 30))
#define HI64 (32u | (2u << 30))
template <int TA, int TB, unsigned HIA, unsigned HIB>
__device__ __forceinline__ void wgmma32(float* d, uint32_t da, uint32_t db, int acc) {
  asm volatile("{.reg .pred p; .reg .b64 da, db; setp.ne.b32 p, %18, 0; mov.b64 da, {%16, %21}; mov.b64 db, {%17, %22};\n"
               "wgmma.mma_async.sync.aligned.m64n32k16.f32.bf16.bf16 "
               "{%0,%1,%2,%3,%4,%5,%6,%7,%8,%9,%10,%11,%12,%13,%14,%15}, da, db, p, 1, 1, %19, %20;}"
               : "+f"(d[0]), "+f"(d[1]), "+f"(d[2]), "+f"(d[3]), "+f"(d[4]), "+f"(d[5]), "+f"(d[6]), "+f"(d[7]),
                 "+f"(d[8]), "+f"(d[9]), "+f"(d[10]), "+f"(d[11]), "+f"(d[12]), "+f"(d[13]), "+f"(d[14]), "+f"(d[15])
               : "r"(da), "r"(db), "r"(acc), "n"(TA), "n"(TB), "n"(HIA), "n"(HIB));
}
__device__ __forceinline__ void wgmma32r(float* d, const uint32_t* a, uint32_t db) {
  asm volatile("{.reg .b64 db; mov.b64 db, {%20, %21};\n"
               "wgmma.mma_async.sync.aligned.m64n32k16.f32.bf16.bf16 "
               "{%0,%1,%2,%3,%4,%5,%6,%7,%8,%9,%10,%11,%12,%13,%14,%15}, {%16,%17,%18,%19}, db, 1, 1, 1, 1;}"
               : "+f"(d[0]), "+f"(d[1]), "+f"(d[2]), "+f"(d[3]), "+f"(d[4]), "+f"(d[5]), "+f"(d[6]), "+f"(d[7]),
                 "+f"(d[8]), "+f"(d[9]), "+f"(d[10]), "+f"(d[11]), "+f"(d[12]), "+f"(d[13]), "+f"(d[14]), "+f"(d[15])
               : "r"(a[0]), "r"(a[1]), "r"(a[2]), "r"(a[3]), "r"(db), "n"(HI64));
}
template <int N> __device__ __forceinline__ void wg_wait(float* a) {
  asm volatile("wgmma.wait_group.sync.aligned %16;"
               : "+f"(a[0]), "+f"(a[1]), "+f"(a[2]), "+f"(a[3]), "+f"(a[4]), "+f"(a[5]), "+f"(a[6]), "+f"(a[7]), "+f"(a[8]), "+f"(a[9]), "+f"(a[10]),
                 "+f"(a[11]), "+f"(a[12]), "+f"(a[13]), "+f"(a[14]), "+f"(a[15]) : "n"(N) : "memory");
}
__device__ __forceinline__ float sum8(uint32_t a) {
  const float4 p = lds16(a), q = lds16(a + 1024);
  return ((p.x + p.y) + (p.z + p.w)) + ((q.x + q.y) + (q.z + q.w));
}
__device__ __forceinline__ int posof(int c) { return (c & ~14) + 2 * (c & 6) + ((c >> 2) & 2); }

__global__ void __cluster_dims__(8, 1, 1) __launch_bounds__(384, 1)
fused_kernel(const bf16* __restrict__ x, const bf16* __restrict__ cvec, const bf16* __restrict__ w_mod, bf16* __restrict__ out,
             Scratch* __restrict__ scr, const __grid_constant__ Sched sch, const __grid_constant__ TMaps tms) {
  extern __shared__ __align__(1024) unsigned char smem[];
  const int tid = threadIdx.x, warp = __shfl_sync(~0u, tid >> 5, 0), lane = tid & 31;
  const int b = blockIdx.x, cl = b >> 3, rn = b & 7, rk = b & 1, hd = b >> 1, f = b - 64;
  const bool isA = b < 64;
  uint32_t sb = s2u(smem), bar0 = sb + O_BAR;
  unsigned gt_start;
  asm volatile("mov.u32 %0, %%globaltimer_lo;" : "=r"(gt_start));
  const int g = lane >> 2, tq = lane & 3;
  const int arow = 64 * rn + ((tid & 255) >> 4);
  uint4 wm[4];
  uint32_t cw;
  if (warp < 8 && isA) {
    const bf16* wa = w_mod + (size_t)arow * 3072 + (lane & 8) * 64 + 64 * cl + 8 * (lane & 7);
#pragma unroll
    for (int i = 0; i < 4; i++) wm[i] = ldx16(wa + i * 16 * 3072);
    cw = ldc4(cvec + (arow & ~1) + 16 * tq);
  }
  if (warp == 11) {
    if (lane == 0) {
#pragma unroll
      for (int i = 0; i < B_EMPTY; i++) BAR_INIT(i, 1);
    }
    __syncwarp();
    asm volatile("fence.mbarrier_init.release.cluster;" ::: "memory");
    asm volatile("barrier.cluster.arrive.relaxed.aligned;" ::: "memory");
    if (isA) {
#pragma unroll 1
      for (int i = 0; i < 8; i++) {
        if (i >= HWIN) mbar_wait(bar0 + 8 * (i - HWIN));
        wait_until(gt_start + sch.t0 + ((64 * i + b) * sch.dth >> 8));
        if (lane == 0) {
          BAR_ARM(i, 16384);
          tma3d(sb + i * 16384, &tms.m[i >> 2], bar0 + 8 * i, 0, i < 4 ? 128 * i : 256 * rk + 64 * (i - 4), i < 4 ? b : b & ~1);
        }
        __syncwarp();
      }
    }
  }
  if (warp == 10) {
    const unsigned ep = ldc4(&scr->cnt[0]);
    if (isA) {
      const uint4 xa = ldc16(x + 16 * lane), xb = ldc16(x + 16 * lane + 8);
      float xv[16] = {bflo(xa.x), bfhi(xa.x), bflo(xa.y), bfhi(xa.y), bflo(xa.z), bfhi(xa.z), bflo(xa.w), bfhi(xa.w),
                      bflo(xb.x), bfhi(xb.x), bflo(xb.y), bfhi(xb.y), bflo(xb.z), bfhi(xb.z), bflo(xb.w), bfhi(xb.w)};
      float s = 0;
#pragma unroll
      for (int i = 0; i < 16; i++) s += xv[i];
#pragma unroll
      for (int o = 16; o; o >>= 1) s += __shfl_xor_sync(~0u, s, o);
      const float mean = s * (1.f / 512.f);
      s = 0;
#pragma unroll
      for (int i = 0; i < 16; i++) { xv[i] -= mean; s += xv[i] * xv[i]; }
#pragma unroll
      for (int o = 16; o; o >>= 1) s += __shfl_xor_sync(~0u, s, o);
      const float rstd = rsqrtf(s * (1.f / 512.f) + 1e-5f);
      if (g == cl)
#pragma unroll
        for (int i = 0; i < 4; i++)
          *(float4*)(smem + O_SM + (256 + tq * 16 + 4 * i) * 4) = make_float4(xv[4 * i] * rstd, xv[4 * i + 1] * rstd, xv[4 * i + 2] * rstd, xv[4 * i + 3] * rstd);
    }
    if (lane == 0) *(volatile unsigned*)(smem + O_EP) = ep;
    nbar_arrive(1, 288);
  }
  const int cls = isA ? (b >= NBIG) : 2, v0 = isA ? 2 : 0;
  if (warp >= 8) {
    asm volatile("setmaxnreg.dec.sync.aligned.u32 72;");
    if (warp == 8) {
      if (lane < 8) asm volatile("prefetch.tensormap [%0];" ::"l"(&tms.m[lane + 1]) : "memory");
#pragma unroll 4
      for (int i = 0; i < 70; i++) sts16(sb + O_LZ + i * 512 + lane * 16, make_uint4(0, 0, 0, 0));
      asm volatile("fence.acq_rel.cluster;" ::: "memory");
      if ((sb & 0xFFFFFF) != SMEM_BASE) __trap();
    } else if (warp == 9) {
      if (lane == 0) {
#pragma unroll
        for (int i = B_EMPTY; i < B_EM; i++) BAR_INIT(i, 8);
        BAR_INIT(B_Q2, 9); BAR_ARM(B_Q2, 1024);
        BAR_INIT(B_H, 1); BAR_INIT(B_QF, 1); BAR_ARM(B_QF, 32768);
        BAR_INIT(B_TAB, 1); BAR_INIT(B_W, 1); BAR_INIT(B_ST, 8); BAR_INIT(B_HZ, 1); BAR_ARM(B_HZ, 256); BAR_INIT(B_WZ, 1); BAR_INIT(B_G, 1); BAR_INIT(B_G2, 1);
      }

    }
    if (warp != 11) {
      __syncwarp();
      asm volatile("fence.mbarrier_init.release.cluster;" ::: "memory");
      __threadfence_block();
      asm volatile("barrier.cluster.arrive.relaxed.aligned;" ::: "memory");
    }
    asm volatile("barrier.cluster.wait.acquire.aligned;" ::: "memory");
    if (warp == 8) {
      const int nr = sch.nr[cls], vl = v0 + sch.nt[cls] - 1;
      unsigned long long hist = 0;
      int v = v0;
#pragma unroll 1
      for (int rd = 0; rd < nr; rd++) {
        const uint2 e = sch.r[cls][rd];
        const int type = e.y & 15, win = (e.y >> 4) & 15, pos = b + 64 - (int)((e.y >> 8) & 255), tile = e.y >> 16;
        const bool mod = type == T_MOD;
        const int ni = mod ? 1 : type == T_DN ? 2 : 4;
        unsigned t = gt_start + (e.x & 0xffff) + (pos * sch.dt >> 8);
        const int c0 = mod ? 1024 + 32 * b : type == T_WO ? 64 * rn : type == T_GU ? 32 * f : 0;
        int c1 = type == T_KV ? 64 * (tile + pos) : type == T_DN ? 32 * f : 0;
        int c2 = mod ? tile : type == T_WO ? 4 * cl : type == T_UV ? b : 0;
        const int i1 = type == T_DN ? 16 : type == T_UV ? 128 : 0;
#pragma unroll 1
        for (int j = 0; j < ni; j++) {
          const int slot = mod ? B_FM + tile : (v & 1) * 4 + j;
          if (mod ? tile : v >= 2) mbar_wait(bar0 + 8 * (B_EMPTY + (mod ? (vl & 1) * 4 : slot)), mod ? (vl >> 1) & 1 : ((v >> 1) - 1) & 1);
          const int hw = (int)(hist >> (6 * (win - 1))) & 63;
          if (hw) mbar_wait(bar0 + 8 * (hw & 15), (hw >> 4) & 1);
          wait_until(t);
          if (lane == 0) {
            BAR_ARM(slot, 16384);
            tma3d(sb + (mod ? (tile ? O_Q : O_X) : slot * 16384), &tms.m[type == T_GU ? type + (j & 1) : type], bar0 + 8 * slot, c0, c1, c2);
          }
          __syncwarp();
          hist = hist << 6 | (32 | (mod ? 0 : (v & 2) << 3) | slot);
          t += e.x >> 16; c1 += i1;
          c2 += type == T_KV ? 2 : type == T_WO ? 1 : type == T_GU ? j & 1 : 0;
        }
        v += !mod;
      }
      return;
    }
    const unsigned epoch = *(volatile unsigned*)(smem + O_EP), par = (epoch + 1) & 1;
    if (warp == 10) {
      if (isA) {
        for (int it = 0; ldx4(scr->cnt + 1) != (epoch + 1) * 128 && it < SPIN_MAX; it++) {}
        if (lane == 0) BAR_ARRIVE(B_H);
      } else mbar_wait(bar0);
      for (int it = 0; ldx4(scr->cnt + 32 + 32 * (rn >> 2)) != (epoch + 1) * 32 && it < SPIN_MAX; it++) {}
      if (lane == 0)
        asm volatile("cp.async.bulk.shared::cluster.global.mbarrier::complete_tx::bytes.multicast::cluster [%0], [%1], 4096, [%2], %3;"
                     ::"r"(sb + O_Q + rn * 4096), "l"(scr->qa + rn * 256), "r"(bar0 + 8 * B_QF), "h"((unsigned short)0xff) : "memory");
      const unsigned dl = isA ? sch.d4 : sch.d6;
      if (isA) sleep_until(gt_start + sch.t4);
      else {
        const int nt = sch.nt[2];
#pragma unroll 1
        for (int t = 0; t < nt; t++) mbar_wait(bar0 + (t & 1) * 32 + 24, (t >> 1) & 1);
        unsigned long long now;
        asm volatile("mov.u64 %0, %%globaltimer;" : "=l"(now));
        if (lane == 0) { asm volatile("red.relaxed.gpu.global.max.u64 [%0], %1;" ::"l"(scr->cnt + 130), "l"(now) : "memory"); CNT_ADD(128); }
        sleep_until((unsigned)now + 2000);
      }
      uint4 an;
      for (int it = 0; an = ldx16(scr->cnt + 128), an.x != (epoch + 1) * 56 && it < SPIN_MAX; it++) {}
      wait_until(an.z + (dl >> 16));
      if (lane == 0) BAR_ARRIVE(B_G2);
      wait_until(an.z + (dl & 0xffff));
      if (lane == 0) BAR_ARRIVE(B_G);
    } else if (warp == 11) {
      {
        uint2* ph = scr->hdr + (16 * (rn >> 2) + 2 * (rn & 3) + (g & 1) + 4 * (g & 2)) * 16 + cl;
        if (lane < 16 && (tq == 0 || (tq == 1 && cl == 14))) stx8(ph + tq, make_uint2(par ^ 1, 0));
        uint32_t a_w = sb + O_HZ + 256 + (lane & 7) * 8 + ((lane >> 1) & 4);
        PIN(a_w); PINL(ph);
        mbar_wait(bar0 + 8 * B_HZ);
        float4 hz[4];
#pragma unroll
        for (int u = 0; u < 4; u++) hz[u] = lds16(sb + O_HZ + (g & 3) * 64 + ((u ^ tq) << 4));
        float M = fmaxf(fmaxf(fmaxf(hz[0].x, hz[0].z), fmaxf(hz[1].x, hz[1].z)), fmaxf(fmaxf(hz[2].x, hz[2].z), fmaxf(hz[3].x, hz[3].z)));
        M = u2f(fbits(M));
        float L = 0.f;
#pragma unroll
        for (int u = 0; u < 4; u++) {
          const uint32_t wp = pack2(ex2(hz[u].x - M), ex2(hz[u].z - M));
          if (u == 0) sts4(a_w, u2f(wp));
          L += bflo(wp) * hz[u].y + bfhi(wp) * hz[u].w;
        }
        if (lane < 16 && tq == 0) pub8(ph, __float_as_uint(M) | 1u, __float_as_uint(L));
        __syncwarp();
        if (lane == 0) BAR_ARRIVE(B_WZ);
      }
      if (isA) {
        mbar_wait(bar0 + 8 * B_G2);
        unsigned long long hh;
        POLL { hh = ldx64(scr->hdr + hd * 16 + (lane & 15)); RETRY((lane & 15) == 15 ? 0u : (unsigned)hh ^ par) }
        const float m = (lane & 15) == 15 ? -1e30f : u2f((unsigned)hh);
        int mi = __float_as_int(m);
        mi ^= (mi >> 31) & 0x7fffffff;
        mi = __reduce_max_sync(~0u, mi);
        mi ^= (mi >> 31) & 0x7fffffff;
        const float w = ex2(m - __int_as_float(mi));
        float L = w * u2f(hh >> 32);
#pragma unroll
        for (int o2 = 8; o2; o2 >>= 1) L += __shfl_xor_sync(~0u, L, o2);
        sts4(sb + O_SM + (384 + 2 * (lane & 6) + ((lane >> 2) & 2) + (lane & 1)) * 4, w * rcp(L));
        __syncwarp();
        if (lane == 0) BAR_ARRIVE(B_W);
      }
    } else {
      if (isA) {
        mbar_wait(bar0 + 8 * B_QF);
#pragma unroll 2
        for (int k = 0; k < 8; k++) {
          const uint32_t cp = ldc4(cvec + 2 * (lane + 32 * k));
          *(uint32_t*)(smem + O_SILU + (lane + 32 * k) * 4) = pack2(silu_bf(bflo(cp)), silu_bf(bfhi(cp)));
        }
        __syncwarp();
        uint32_t ab = sb + O_X + (8 * (lane >> 4) + (lane & 7)) * 64 + ((((lane >> 3) & 1) ^ ((lane >> 1) & 3)) << 4);
        float d[4][4] = {};
#pragma unroll 1
        for (int jm = 0; jm < 2; jm++) {
          mbar_wait(bar0 + 8 * (B_FM + jm));
#pragma unroll 2
          for (int s2 = 0; s2 < 8; s2++)
#pragma unroll
            for (int s = 0; s < 2; s++) {
              uint32_t a0[4], a1[4];
              const uint32_t* ps = (const uint32_t*)(smem + O_SILU) + 128 * jm + 16 * s2 + 8 * s + tq;
              ldsm_t(a0, ab + (2 * s2 + s) * 1024); ldsm_t(a1, (ab + (2 * s2 + s) * 1024) ^ 32);
              mma16(d[s], a0, ps[0], ps[4]); mma16(d[2 + s], a1, ps[0], ps[4]);
            }
          ab -= O_X - O_Q;
        }
        const float t0 = (tq & 1) ? d[0][2] + d[1][2] : d[0][0] + d[1][0], t1 = (tq & 1) ? d[2][2] + d[3][2] : d[2][0] + d[3][0];
        stx4(scr->xm + b * 32 + posof(8 * tq + g), fbits(bfr(bfr((tq & 2) ? t1 : t0) + ((b >> 4) == 2 ? 1.f : 0.f))));
        __syncwarp();
        if (lane == 0) CNT_ADD(96);
      } else sleep_until(gt_start + sch.t4);
      for (int it = 0; ldx4(scr->cnt + 96) != (epoch + 1) * 64 && it < SPIN_MAX; it++) __nanosleep(NSL);
      if (isA) {
        unsigned long long ga;
        POLL { ga = ldx64(scr->xm + 64 * rn + 2 * lane); RETRY(lop_x3((unsigned)ga, ga >> 32, par)) }
        *(float2*)(smem + O_SM + (320 + 2 * lane) * 4) = make_float2(bfhi((unsigned)ga), bfhi(ga >> 32));
      }
      __syncwarp();
      if (lane == 0) BAR_ARRIVE(B_TAB);
    }
    return;
  }

  float* s_sm = (float*)(smem + O_SM);
  unsigned par, epoch;
  asm volatile("barrier.cluster.arrive.relaxed.aligned;" ::: "memory");
  if (isA) {
    float* s_r = (float*)(smem + O_R);
    float acc[8] = {0, 0, 0, 0, 0, 0, 0, 0};
    const float sl = silu_bf((arow & 1) ? bfhi(cw) : bflo(cw));
#pragma unroll
    for (int i = 0; i < 4; i++) fma8(acc, wm[i], __shfl_sync(~0u, sl, i, 4));
    tred<4>(acc, lane, 16);
    *(float4*)(s_r + warp * 128 + 8 * (lane & 15) + ((lane >> 2) & 4)) = make_float4(acc[0], acc[1], acc[2], acc[3]);
    nbar(1, 288);
    epoch = *(volatile unsigned*)(smem + O_EP);
    par = (epoch + 1) & 1;
    if (warp < 2) {
      float t = 0.f, ca = rn == 0 ? 1.f : 0.f;
#pragma unroll
      for (int w = 0; w < 8; w++) { t += s_r[w * 128 + tid]; ca += s_r[w * 128 + 64 + tid]; }
      t += ca * s_sm[256 + tid];
      const float nb = __shfl_down_sync(~0u, t, 1);
      const uint32_t w0 = lane < 8 ? pack2t(t, nb, par) : pack2(t, nb);
      const uint32_t w1 = __shfl_down_sync(~0u, w0, 8), w2 = __shfl_down_sync(~0u, w0, 16), w3 = __shfl_down_sync(~0u, w0, 24);
      if (lane < 8 && !(lane & 1)) stx16(scr->h + (rn >> 1) * 512 + (2 * cl + warp) * 32 + rk * 16 + 2 * lane, make_uint4(w0, w1, w2, w3));
      __syncwarp();
      if (lane == 0) CNT_ADD(1);
    }
    asm volatile("barrier.cluster.wait.acquire.aligned;" ::: "memory");
    const uint32_t rsb = mapa(sb, rn ^ 1);
    {
      uint32_t a[4][4][4];
      mbar_wait(bar0 + 8 * (warp >> 1));
      const uint32_t ab = sb + (64 * warp + 8 * (lane >> 4) + (lane & 7)) * 128;
#pragma unroll
      for (int s = 0; s < 4; s++)
#pragma unroll
        for (int mt = 0; mt < 4; mt++) ldsm_t(a[s][mt], ab + s * 2048 + (((2 * mt + ((lane >> 3) & 1)) ^ (lane & 7)) << 4));
      uint4 v0, v1;
      const unsigned* ph = scr->h + (g >> 1) * 512 + 64 * warp + 4 * (lane & 7);
      uint32_t off = O_B + warp * 272 + (32 * rk + 8 * tq + (lane & 4)) * 4;
      PIN(off); PINL(ph);
      mbar_wait(bar0 + 8 * B_H);
      POLL { v0 = ldx16(ph); v1 = ldx16(ph + 32); RETRY(lop_x3(v0.x, v1.x, par)) }
      float d[4][4] = {};
#pragma unroll
      for (int mt = 0; mt < 4; mt++) {
        mma16(d[mt], a[0][mt], v0.x, v0.y); mma16(d[mt], a[1][mt], v0.z, v0.w);
        mma16(d[mt], a[2][mt], v1.x, v1.y); mma16(d[mt], a[3][mt], v1.z, v1.w);
      }
      float r[8];
#pragma unroll
      for (int mt = 0; mt < 4; mt++) { r[2 * mt] = d[mt][0] + d[mt][1]; r[2 * mt + 1] = d[mt][2] + d[mt][3]; }
      tred<4>(r, lane, 2); tred<2>(r, lane, 1);
      const float rc = __shfl_xor_sync(~0u, (lane & 4) ? r[0] : r[1], 4);
      const uint32_t wd = (lane & 4) ? pack2(rc, r[1]) : pack2(r[0], rc);
      const uint32_t w1 = __shfl_down_sync(~0u, wd, 8), w2 = __shfl_down_sync(~0u, wd, 16), w3 = __shfl_down_sync(~0u, wd, 24);
      asm volatile("{.reg .pred p; setp.lt.s32 p, %7, 8; @p st.shared.v4.b32 [%0], {%2,%3,%4,%5};\n"
                   "@p st.async.shared::cluster.mbarrier::complete_tx::bytes.v4.b32 [%1], {%2,%3,%4,%5}, [%6];}"
                   ::"r"(sb + off), "r"(rsb + off), "r"(wd), "r"(w1), "r"(w2), "r"(w3), "r"(rsb + O_BAR + 8 * B_Q2), "r"(lane) : "memory");
      __syncwarp();
      arrive_n(bar0 + 8 * B_Q2, lane == 0, 1);
      arrive_n(bar0 + 8 * (B_EMPTY + (warp >> 1)), lane == 0, 4);
    }
    {
      uint32_t a[2][8][4];
      uint32_t a_bq = sb + O_B + (lane & 7) * 272 + (lane >> 3) * 16;
      uint4* p_qa = scr->qa + (4 * rk + (warp >> 1)) * 256 + hd * 8 + ((4 * (warp & 1) + tq) ^ (hd & 7));
      PIN(a_bq); PINL(p_qa);
      mbar_wait(bar0 + 8 * (4 + (warp >> 1)));
      const uint32_t ab = sb + 65536 + (warp >> 1) * 16384 + (32 * (warp & 1) + (lane & 15)) * 128;
#pragma unroll
      for (int i = 0; i < 16; i++) ldsm(a[i >> 3][i & 7], ab + (i >> 3) * 2048 + ((i >> 2) & 1) * 8192 + (((2 * (i & 3) + (lane >> 4)) ^ (lane & 7)) << 4));
      mbar_wait(bar0 + 8 * B_Q2);
      float d[4][4] = {};
#pragma unroll
      for (int y = 0; y < 4; y++) {
        uint32_t bq[4];
        ldsm(bq, a_bq + 64 * y);
#pragma unroll
        for (int mt = 0; mt < 2; mt++) { mma16(d[2 * mt], a[mt][2 * y], bq[0], bq[1]); mma16(d[2 * mt + 1], a[mt][2 * y + 1], bq[2], bq[3]); }
      }
      float r[4];
#pragma unroll
      for (int i = 0; i < 4; i++) r[i] = (d[i & 2][2 * (i & 1)] + d[i & 2][2 * (i & 1) + 1]) + (d[(i & 2) + 1][2 * (i & 1)] + d[(i & 2) + 1][2 * (i & 1) + 1]);
      tred<2>(r, lane, 2); tred<1>(r, lane, 1);
      const float nb = __shfl_xor_sync(~0u, r[0], 4);
      const uint32_t w0 = lane < 8 ? pack2t(r[0], nb, par) : pack2(r[0], nb);
      const uint32_t w1 = __shfl_down_sync(~0u, w0, 8), w2 = __shfl_down_sync(~0u, w0, 16), w3 = __shfl_down_sync(~0u, w0, 24);
      if (lane < 4) stx16(p_qa, make_uint4(w0, w1, w2, w3));
      arrive_n(bar0 + 8 * (B_EMPTY + 4 + (warp >> 1)), lane == 0, 4);
      if (warp) nbar_arrive(3, 256); else { nbar(3, 256); if (lane == 0) CNT_ADD(32 + 32 * rk); }
    }
  } else {
    nbar(1, 288);
    epoch = *(volatile unsigned*)(smem + O_EP);
    par = (epoch + 1) & 1;
    asm volatile("barrier.cluster.wait.acquire.aligned;" ::: "memory");
    mbar_wait(bar0);
  }
  asm volatile("setmaxnreg.inc.sync.aligned.u32 216;");
  uint2* p_rec = scr->rec + ((16 * (rn >> 2) + 2 * (rn & 3) + (g & 1) + 4 * (tq & 2)) * 32 + 16 * (warp >> 2) + 2 * (warp & 3) + (tq & 1)) * 64 + cl * 4 + (g >> 1);
  PINL(p_rec);
  {
    const unsigned inv = par ^ 1;
#pragma unroll
    for (int q = 0; q < 2; q++) { stx8(p_rec + q * 512, make_uint2(inv, 0)); if (cl == 14) stx8(p_rec + q * 512 + 4, make_uint2(0, 0)); }
    if (isA) { if (warp < 2) stx4(scr->xao + b * 64 + tid, inv); }
    else stx8(scr->xf + ((4 * warp + tq) * 56 + f) * 16 + 2 * g, make_uint2(inv, 0));
  }
  {
    mbar_wait(bar0 + 8 * B_QF);
    unsigned bad = 0;
#pragma unroll
    for (int k = 0; k < 8; k++) bad |= *(volatile unsigned*)(smem + O_Q + k * 4096 + tid * 16) ^ par;
    if (__builtin_expect(__any_sync(~0u, bad & 1), 0)) {
#pragma unroll 1
      for (int k = 0; k < 8; k++) {
        uint4 v;
        POLL { v = ldx16(scr->qa + k * 256 + tid); RETRY(v.x ^ par) }
        sts16(sb + O_Q + k * 4096 + tid * 16, v);
      }
      asm volatile("fence.proxy.async.shared::cta;" ::: "memory");
    }
    if (warp >= 4) nbar_arrive(1, 256); else nbar(1, 256);
  }
  sb = __shfl_sync(~0u, sb, 0); bar0 = sb + O_BAR;
  const int nt = sch.nt[cls], wg = warp >> 2;
  uint32_t a_z = sb + O_LZ + (lane & 7) * 4096 + wg * 2048 + (warp & 3) * 256 + (((lane >> 3) ^ (lane & 7)) << 4);
  PIN(a_z);
  uint32_t z[4][4];
  {
    const float sc = 0.08838834764831845f * 1.4426950408889634f;
    const uint32_t a_pm = sb + O_SM + lane * 16;
    float mrun = -1e30f;
    float o[4][16], sx[16], mref[8];
#pragma unroll
    for (int k = 0; k < 16; k++) { o[0][k] = o[1][k] = o[2][k] = o[3][k] = sx[k] = 0.f; mref[k >> 1] = -1e30f; }
    const int key = 16 * warp + (lane & 15);
    uint32_t a_p = sb + O_P + key * 64 + (((lane >> 4) ^ ((key >> 1) & 3)) << 4);
    uint32_t a_v = sb + wg * 32768 + (8 * (lane >> 4) + (lane & 7)) * 128 + (((2 * (warp & 3) + ((lane >> 3) & 1)) ^ (lane & 7)) << 4);
    unsigned long long dst[2];
#pragma unroll
    for (int j = 0; j < 2; j++) { dst[j] = mapg(sb + O_LZ + rn * 4096 + wg * 2048 + (warp & 3) * 128 + (g ^ rn) * 16, 4 * j + tq); PINL(dst[j]); }
    const uint32_t rb = mapa(sb, 4 * (lane >> 4) + tq);
    uint32_t a_h = rb + O_HZ + ((lane >> 2) & 3) * 64 + rn * 8, a_hb = rb + O_BAR + 8 * B_HZ;
    PIN(a_p); PIN(a_v); PIN(a_h); PIN(a_hb);
    uint32_t ones[4] = {0x3F803F80u, 0x3F803F80u, 0x3F803F80u, 0x3F803F80u};
    PIN(ones[0]); PIN(ones[1]); PIN(ones[2]); PIN(ones[3]);
#pragma unroll 1
    for (int t = 0; t < nt; t++) {
      const int v = v0 + t;
      const uint32_t fb = bar0 + (v & 1) * 32, ph = (v >> 1) & 1, av = a_v + (v & 1) * 65536;
      uint32_t vf[4][4][4];
      if (wg == 0) {
        const uint32_t da = DSC + (v & 1) * 4096, db = DSC + O_Q / 16;
#pragma unroll
        for (int jj = 0; jj < 2; jj++) {
#pragma unroll 1
          for (int j = 2 * jj; j < 2 * jj + 2; j++) {
            mbar_wait(fb + 8 * j, ph);
            asm volatile("wgmma.fence.sync.aligned;" ::: "memory");
#pragma unroll
            for (int k = 0; k < 8; k++)
              wgmma32<0, 0, HI128, HI128>(sx, da + j * 1024 + (k >> 2) * 512 + (k & 3) * 2, db + j * 512 + (k >> 2) * 256 + (k & 3) * 2, jj | k | j);
            asm volatile("wgmma.commit_group.sync.aligned;" ::: "memory");
          }
          if (jj == 0) {
#pragma unroll
            for (int i = 0; i < 16; i++) ldsm_t(vf[i >> 2][i & 3], av + i * 2048);
            nbar(5, 256);
          }
        }
        wg_wait<0>(sx);
      } else {
        nbar_arrive(5, 256);
#pragma unroll
        for (int j = 0; j < 2; j++) {
          mbar_wait(fb + 16 + 8 * j, ph);
          if (j) spin_until(clock() + VDLY);
#pragma unroll
          for (int i = 0; i < 8; i++) ldsm_t(vf[2 * j + (i >> 2)][i & 3], av + j * 16384 + i * 2048);
        }
      }
#pragma unroll 1
      for (int pass = 0;; pass++) {
        int ex = 0;
        if (wg == 0) {
          float mx = -1e30f;
#pragma unroll
          for (int i = 0; i < 8; i++) mx = fmaxf(mx, fmaxf(sx[2 * (i & 6) + (i & 1)], sx[2 * (i & 6) + (i & 1) + 2]) * sc - mref[i]);
          ex = mx > TAU;
          uint32_t pk[8];
#pragma unroll
          for (int i = 0; i < 8; i++) pk[i] = pack2(ex2(sx[2 * i] * sc - mref[i & 6]), ex2(sx[2 * i + 1] * sc - mref[(i & 6) + 1]));
#pragma unroll
          for (int u = 0; u < 2; u++)
            asm volatile("stmatrix.sync.aligned.m8n8.x4.shared.b16 [%0], {%1,%2,%3,%4};"
                         ::"r"(a_p ^ (u << 5)), "r"(pk[4 * u]), "r"(pk[4 * u + 1]), "r"(pk[4 * u + 2]), "r"(pk[4 * u + 3]) : "memory");
          asm volatile("fence.proxy.async.shared::cta;" ::: "memory");
        }
        asm volatile("{.reg .pred p, q; setp.ne.s32 q, %0, 0; bar.red.or.pred p, 4, 256, q; selp.s32 %0, 1, 0, p;}" : "+r"(ex)::"memory");
        if (!ex || pass) break;
        if (wg == 0) {
          float cm[8];
#pragma unroll
          for (int i = 0; i < 8; i++) cm[i] = fmaxf(sx[2 * (i & 6) + (i & 1)], sx[2 * (i & 6) + (i & 1) + 2]);
          tmax<4>(cm, lane, 16); tmax<2>(cm, lane, 8); tmax<1>(cm, lane, 4);
          sts4(a_pm + warp * 4, cm[0] * sc);
        }
        nbar(4, 256);
        const float4 pm = lds16(a_pm);
        const float mn = fmaxf(fmaxf(fmaxf(pm.x, pm.y), fmaxf(pm.z, pm.w)), mrun), al = ex2(mrun - mn);
        mrun = mn;
#pragma unroll
        for (int i = 0; i < 8; i++) {
          const float a = __shfl_sync(~0u, al, 4 * i + tq), aw = wg ? a : 1.f;
          mref[i] = __shfl_sync(~0u, mn, 4 * i + tq);
#pragma unroll
          for (int e = 0; e < 2; e++) {
            const int k = 2 * (i & 6) + (i & 1) + 2 * e;
            o[0][k] *= a; o[1][k] *= a; o[2][k] *= a; o[3][k] *= a; sx[k] *= aw;
          }
        }
      }
      if (wg) {
        asm volatile("wgmma.fence.sync.aligned;" ::: "memory");
#pragma unroll
        for (int k = 0; k < 4; k++) wgmma32r(sx, ones, DSC + O_P / 16 + k * 64);
        asm volatile("wgmma.commit_group.sync.aligned;" ::: "memory");
        wg_wait<0>(sx);
        if (t == nt - 1 && warp == 4) {
          float lv[4];
#pragma unroll
          for (int j = 0; j < 4; j++) lv[j] = (lane & 4) ? sx[4 * j + 1] : sx[4 * j];
          asm volatile("st.async.shared::cluster.mbarrier::complete_tx::bytes.v2.f32 [%0], {%1, %2}, [%3];"
                       ::"r"(a_h), "f"(mrun), "f"((lane & 16) ? ((lane & 8) ? lv[3] : lv[2]) : ((lane & 8) ? lv[1] : lv[0])), "r"(a_hb) : "memory");
        }
      }
#pragma unroll
      for (int q = 0; q < 4; q++) {
        asm volatile("wgmma.fence.sync.aligned;" ::: "memory");
#pragma unroll
        for (int k = 0; k < 4; k++) wgmma32r(o[q], vf[q][k], DSC + O_P / 16 + k * 64);
        asm volatile("wgmma.commit_group.sync.aligned;" ::: "memory");
        if (q == 3) {
          arrive_n(fb + 8 * B_EMPTY + 8 * tq, lane < 4 && lane >= 2 * wg, 2 - (tq >> 1));
#pragma unroll
          for (int u = 0; u < 4; u++) ldsm_t(z[u], (a_z + (u >> 1) * 128) ^ ((u & 1) << 6));
        }
        wg_wait<0>(o[q]);
#pragma unroll
        for (int j = 0; j < 2; j++)
          asm volatile("{.reg .pred p; setp.eq.s32 p, %5, %6; @p st.relaxed.cluster.v4.b32 [%0], {%1,%2,%3,%4};}"
                       ::"l"(dst[j] + q * 512), "r"(pack2t(o[q][8 * j], o[q][8 * j + 1], 1)), "r"(pack2(o[q][8 * j + 2], o[q][8 * j + 3])),
                         "r"(pack2(o[q][8 * j + 4], o[q][8 * j + 5])), "r"(pack2(o[q][8 * j + 6], o[q][8 * j + 7])), "r"(t), "r"(nt - 1) : "memory");
      }
    }
  }
  {
    uint32_t wx[2][4];
    mbar_wait(bar0 + 8 * B_WZ);
    uint2 wp;
    asm volatile("ld.shared.v2.u32 {%0, %1}, [%2];" : "=r"(wp.x), "=r"(wp.y) : "r"(sb + O_HZ + 256 + (lane & 7) * 8) : "memory");
#pragma unroll
    for (int c = 0; c < 4; c++) { wx[c >> 1][2 * (c & 1)] = (g >> 1) == c ? wp.x : 0u; wx[c >> 1][2 * (c & 1) + 1] = (g >> 1) == c ? wp.y : 0u; }
    int q = 0;
#pragma unroll 1
    for (int it = 0; it < SPIN_MAX; it++) {
      float d[4][4] = {}, r[4];
      unsigned ok[4];
#pragma unroll
      for (int e = 0; e < 2; e++)
#pragma unroll
        for (int u = 0; u < 4; u++) mma16(d[u], wx[e], z[u][2 * e], z[u][2 * e + 1]);
#pragma unroll
      for (int u = 0; u < 4; u++) ok[u] = (z[u][0] & z[u][1]) & (z[u][2] & z[u][3]);
      const int go = __all_sync(~0u, g || ((ok[0] & ok[1]) & (ok[2] & ok[3]) & 0x10001u) == 0x10001u);
      a_z += go << 10;
#pragma unroll
      for (int u = 0; u < 4; u++) ldsm_t(z[u], (a_z + (u >> 1) * 128) ^ ((u & 1) << 6));
#pragma unroll
      for (int u = 0; u < 4; u++) r[u] = (tq & 2) ? ((g & 1) ? d[u][3] : d[u][2]) : ((g & 1) ? d[u][1] : d[u][0]);
      asm volatile("{.reg .pred p; .reg .b64 t; setp.ne.u32 p, %3, 0; mov.b64 t, {%1, %2}; @p red.relaxed.gpu.global.xor.b64 [%0], t;}"
                   ::"l"(p_rec + q * 512), "r"(pack2t(r[0], r[1], par) | 1u), "r"(pack2(r[2], r[3])), "r"(go) : "memory");
      q += go;
      if (q == 2) break;
    }
  }
  const int vt = v0 + nt;
  const uint32_t bufa = sb + (vt & 1) * 65536, fulla = bar0 + (vt & 1) * 32, pha = (vt >> 1) & 1, phb = ((vt + 1) >> 1) & 1;
  const uint32_t bufo = sb + ((vt + 1) & 1) * 65536, fullb = bar0 + ((vt + 1) & 1) * 32;
  uint32_t a_rs = sb + O_R + (warp >> 2) * 1024 + (16 * tq + g) * 16 + ((warp + tq) & 3) * 4;
  if (isA) {
    const int row = 16 * (warp & 6) + 8 * (warp & 1) + (lane & 16) + ((lane & 7) >> 1) + 4 * (lane & 1);
    uint32_t ab = bufa + row * 128 + ((((lane >> 3) & 1) ^ (row & 7)) << 4);
    const uint2* pr = scr->rec + (hd * 32 + warp) * 64 + lane;
    unsigned long long a_c0 = mapg(sb + O_CTX + (64 * rn + 32 * (warp & 1) + posof(lane)) * 4, warp & 6);
    unsigned long long a_c1 = mapg(sb + O_CTX + (64 * rn + 32 * (warp & 1) + posof(lane)) * 4, warp | 1);
    uint32_t a_rl = sb + O_R + (32 * (warp & 1) + lane) * 16;
    uint32_t ao = bufo + (16 * warp + 8 * (lane >> 4) + (lane & 7)) * 128 + ((((lane >> 3) & 1) ^ (lane & 7)) << 4);
    uint32_t a_cx = sb + O_CTX + (16 * warp + 4 * tq) * 4, a_ga = sb + O_SM + (320 + posof(tid & 63)) * 4;
    unsigned* p_ao = scr->xao + b * 64 + posof(tid & 63);
    float xv = cl == 0 ? __bfloat162float(x[64 * rn + (tid & 63)]) : 0.f;
    unsigned p2 = lane >= 28 ? 0 : par;
    PIN(ab); PINL(pr); PINL(a_c0); PINL(a_c1); PIN(a_rl); PIN(a_rs); PIN(ao); PIN(a_cx); PIN(a_ga); PINL(p_ao); PIN(p2);
    asm volatile("" : "+f"(xv));
    {
      uint32_t a[4][4][4];
      uint2 z[4], y[4];
      float d[4][4] = {}, r[8];
      mbar_wait(fulla, pha);
      POLL {
#pragma unroll
        for (int q = 0; q < 4; q++) z[q] = ldx8(pr + q * 512);
        RETRY(lop_x3(z[0].x, z[1].x, par) | lop_x3(z[2].x, z[3].x, par))
      }
#pragma unroll
      for (int q = 0; q < 4; q++) {
        if (q == 3) {
          mbar_wait(bar0 + 8 * B_G);
#pragma unroll
          for (int u = 0; u < 4; u++) y[u] = ldx8(pr + u * 512 + 32);
        }
        mbar_wait(fulla + 8 * q, pha);
#pragma unroll
        for (int mt = 0; mt < 4; mt++) ldsm_t(a[q][mt], (ab + q * 16384) ^ (mt << 5));
#pragma unroll
        for (int mt = 0; mt < 4; mt++) mma16(d[mt], a[q][mt], z[q].x, z[q].y);
      }
      mbar_wait(bar0 + 8 * B_W);
      const float4 W = lds16(sb + O_SM + (384 + 4 * tq) * 4);
#pragma unroll
      for (int i = 0; i < 8; i++) { r[i] = W.x * d[i >> 1][2 * (i & 1)] + W.y * d[i >> 1][2 * (i & 1) + 1]; asm volatile("" : "+f"(r[i])); }
      POLL {
#pragma unroll
        for (int mt = 0; mt < 4; mt++) d[mt][0] = d[mt][1] = d[mt][2] = d[mt][3] = 0.f;
#pragma unroll
        for (int q = 0; q < 4; q++)
#pragma unroll
          for (int mt = 0; mt < 4; mt++) mma16(d[mt], a[q][mt], y[q].x, y[q].y);
        if (__builtin_expect(!__any_sync(~0u, or3(lop_x3(y[0].x, y[1].x, p2), lop_x3(y[2].x, y[3].x, p2), 0) & 1) || ++it_ >= SPIN_MAX, 1)) break;
#pragma unroll
        for (int u = 0; u < 4; u++) y[u] = ldx8(pr + u * 512 + 32);
      }
#pragma unroll
      for (int i = 0; i < 8; i++) r[i] = W.w * d[i >> 1][2 * (i & 1) + 1] + (W.z * d[i >> 1][2 * (i & 1)] + r[i]);
      tred<4>(r, lane, 2); tred<2>(r, lane, 1);
      sts4(a_rs, r[0]); sts4(a_rs + 128, r[1]);
      nbar(1, 256);
      const uint32_t cv = __float_as_uint(sum8(a_rl)) | 1u;
      asm volatile("st.relaxed.cluster.b32 [%0], %2; st.relaxed.cluster.b32 [%1], %2;" ::"l"(a_c0), "l"(a_c1), "r"(cv) : "memory");
    }
    {
      uint32_t a[4][4][4];
#pragma unroll
      for (int j = 0; j < NPO; j++) {
        mbar_wait(fullb + 8 * j, phb);
#pragma unroll
        for (int mt = 0; mt < 4; mt++) ldsm_t(a[j][mt], (ao + j * 16384) ^ (mt << 5));
      }
      uint4 c[4];
      POLL {
#pragma unroll
        for (int j = 0; j < 4; j++) c[j] = ldsv16(a_cx + j * 512);
        RETRY(~and3(and3(and3(c[0].x, c[0].y, c[0].z), and3(c[1].x, c[1].y, c[1].z), and3(c[0].w, c[1].w, c[2].x)),
                    and3(and3(c[2].y, c[2].z, c[2].w), and3(c[3].x, c[3].y, c[3].z), c[3].w), ~0u))
      }
      float d[4][4] = {};
#pragma unroll
      for (int j = 0; j < 4; j++) {
        if (j + 1 >= NPO && j < 3) {
          mbar_wait(fullb + 8 * (j + 1), phb);
#pragma unroll
          for (int mt = 0; mt < 4; mt++) ldsm_t(a[j + 1][mt], (ao + (j + 1) * 16384) ^ (mt << 5));
        }
        const uint32_t b0 = pack2(u2f(c[j].x), u2f(c[j].y)), b1 = pack2(u2f(c[j].z), u2f(c[j].w));
#pragma unroll
        for (int mt = 0; mt < 4; mt++) mma16(d[mt], a[j][mt], b0, b1);
      }
      const float r0 = (tq & 2) ? ((tq & 1) ? d[3][0] : d[2][0]) : ((tq & 1) ? d[1][0] : d[0][0]);
      const float r1 = (tq & 2) ? ((tq & 1) ? d[3][2] : d[2][2]) : ((tq & 1) ? d[1][2] : d[0][2]);
      sts4(a_rs + 2048, r0); sts4(a_rs + 2048 + 128, r1);
      if (warp >= 2) nbar_arrive(2, 256);
      else {
        mbar_wait(bar0 + 8 * B_TAB);
        const float gav = lds4(a_ga);
        nbar(2, 256);
        pub4(p_ao, __float_as_uint(gav * sum8(a_rl + 2048) + xv) | 1u);
      }
    }
  } else {
    uint32_t af[4][4][4], ad[2][4][4];
    uint32_t ab = bufa + (32 * warp + 8 * (lane >> 4) + (lane & 7)) * 64 + ((((lane >> 3) & 1) ^ ((lane >> 1) & 3)) << 4);
    uint32_t a_d = bufo + warp * 2048 + (8 * (lane >> 4) + (lane & 7)) * 128 + ((((lane >> 3) & 1) ^ (lane & 7)) << 4);
    uint32_t a_rl = sb + O_R + lane * 16, a_st = sb + O_SM + (352 + 2 * warp) * 4;
    unsigned* p_f = scr->xf + ((4 * warp + tq) * 56 + f) * 16 + 2 * g;
    const unsigned* pa = scr->xao + (g >> 1) * 512 + 32 * warp + 4 * (lane & 7);
    const unsigned* pf = scr->xf + f * 896 + 4 * tid;
    const int col = ((tid >> 1) & 7) + 8 * (tid & 1);
    bf16* po = out + 16 * f + col;
    uint32_t a_q = sb + O_SM + (warp * 16 + 4 * tq + (lane >> 3)) * 4, one = g == 0 ? 0x3F803F80u : 0u;
    unsigned d7 = sch.d7;
    PIN(ab); PIN(a_d); PIN(a_rl); PINL(p_f); PINL(pa); PIN(a_rs); PIN(a_st); PINL(pf); PINL(po); PIN(a_q); PIN(one); PIN(d7);
    mbar_wait(bar0 + 8 * B_TAB);
    uint4 cf[2];
    uint2 bb[4];
    unsigned gbw;
    POLL {
      unsigned bad = 0;
#pragma unroll
      for (int h = 0; h < 2; h++) cf[h] = ldx16(scr->xm + 1024 + 256 * h + 32 * warp + 4 * (lane & 7));
#pragma unroll
      for (int s = 0; s < 4; s++) {
        const uint4 w = ldx16(scr->xm + 1024 - (g & 1) * 512 + 256 * (s >> 1) + 32 * warp + 16 * (s & 1) + 4 * tq);
        bb[s] = make_uint2(__byte_perm(w.x, w.y, 0x7632), __byte_perm(w.z, w.w, 0x7632));
        bad = or3(bad, lop_x3(w.x, w.y, par), lop_x3(w.z, w.w, par));
      }
      gbw = ldx4(scr->xm + 1536 + 16 * (f & 31) + posof(col));
      RETRY(or3(bad, X16(cf[0]), X16(cf[1])) | (gbw ^ par))
    }
    const float gbv = bfhi(gbw);
    float e[4][4] = {};
    uint4 v[2][2];
    auto item = [&](const int it) {
      mbar_wait(fulla + 8 * it, pha);
#pragma unroll
      for (int i = 0; i < 4; i++) ldsm_t(af[it][i], (ab + it * 16384 + (i >> 1) * 1024) ^ ((i & 1) << 5));
    };
    auto item_mma = [&](const int it) {
#pragma unroll
      for (int i = 0; i < 4; i++) mma16(e[2 * (it & 1) + (i & 1)], af[it][i], bb[(it & 2) + (i >> 1)].x, bb[(it & 2) + (i >> 1)].y);
    };
    item(0); item_mma(0); item(1); item_mma(1);
    mbar_wait(bar0 + 8 * B_G);
#pragma unroll
    for (int i = 0; i < 4; i++) v[i >> 1][i & 1] = ldx16(pa + (i >> 1) * 256 + (i & 1) * 2048);
    item(2); item_mma(2);
    float y[2][4], df[4][4] = {}, dg[4];
    uint32_t have0;
    uint32_t zb[2][2];
    POLL {
      dg[0] = dg[1] = dg[2] = dg[3] = 0.f;
#pragma unroll
      for (int h = 0; h < 2; h++) {
        y[h][0] = u2f(v[h][0].x) + u2f(v[h][1].x); y[h][1] = u2f(v[h][0].y) + u2f(v[h][1].y);
        y[h][2] = u2f(v[h][0].z) + u2f(v[h][1].z); y[h][3] = u2f(v[h][0].w) + u2f(v[h][1].w);
        const uint32_t y0 = pack2(y[h][0], y[h][1]), y1 = pack2(y[h][2], y[h][3]);
        const uint32_t ya[4] = {y0, one, y1, one};
        mma16(dg, ya, y0, y1);
        zb[h][0] = pack2(y[h][0] * u2f(cf[h].x), y[h][1] * u2f(cf[h].y)); zb[h][1] = pack2(y[h][2] * u2f(cf[h].z), y[h][3] * u2f(cf[h].w));
      }
      const unsigned bad = or3(or3(lop_x3(v[0][0].x, v[0][0].y, par), lop_x3(v[0][0].z, v[0][0].w, par), lop_x3(v[0][1].x, v[0][1].y, par)),
                               or3(lop_x3(v[0][1].z, v[0][1].w, par), lop_x3(v[1][0].x, v[1][0].y, par), lop_x3(v[1][0].z, v[1][0].w, par)),
                               or3(lop_x3(v[1][1].x, v[1][1].y, par), lop_x3(v[1][1].z, v[1][1].w, par), 0));
      if (__builtin_expect(!__any_sync(~0u, bad & 1) || ++it_ >= SPIN_MAX, 1)) break;
#pragma unroll
      for (int i = 0; i < 4; i++) v[i >> 1][i & 1] = ldx16(pa + (i >> 1) * 256 + (i & 1) * 2048);
    }
    {
      uint32_t bz[4][2];
#pragma unroll
      for (int s = 0; s < 4; s++) { bz[s][0] = (g & 1) == (s & 1) ? zb[s >> 1][0] : 0u; bz[s][1] = (g & 1) == (s & 1) ? zb[s >> 1][1] : 0u; }
      auto mm = [&](const int it, const int i) { mma16(df[2 * (it & 1) + (i & 1)], af[it][i], bz[(it & 2) + (i >> 1)][0], bz[(it & 2) + (i >> 1)][1]); };
      mm(0, 0); mm(0, 1); mm(1, 0);
      float s0 = dg[2] + dg[3], s1 = (g & 1) ? dg[1] : dg[0];
      s1 += shx(s1, 16); s0 += shx(s0, 1);
      mm(1, 1); mm(0, 2);
      s1 += shx(s1, 8); s0 += shx(s0, 2);
      mm(0, 3); mm(1, 2);
      s1 += shx(s1, 4);
      mm(1, 3); mm(2, 0);
      s1 += shx(s1, 2);
      mm(2, 1); mm(2, 2);
      s1 += shx(s1, 1);
      mm(2, 3);
      asm volatile("{.reg .pred p; setp.eq.s32 p, %3, 0; @p st.shared.v2.f32 [%0], {%1, %2}; @p mbarrier.arrive.shared::cta.b64 _, [%4];}"
                   ::"r"(a_st), "f"(s0), "f"(s1), "r"(lane), "r"(bar0 + 8 * B_ST) : "memory");
      item(3);
      have0 = mbar_test(fullb, phb);
#pragma unroll
      for (int mt = 0; mt < 4; mt++) ldsm_t(ad[0][mt], a_d ^ (mt << 5));
      mm(3, 0); mm(3, 1); mm(3, 2); mm(3, 3);
      item_mma(3);
    }
    mbar_wait(bar0 + 8 * B_ST);
    float mean, rstd;
    {
      float4 u[4];
#pragma unroll
      for (int i = 0; i < 4; i++) u[i] = lds16(sb + O_SM + (352 + 4 * i) * 4);
      mean = (((u[0].x + u[0].z) + (u[1].x + u[1].z)) + ((u[2].x + u[2].z) + (u[3].x + u[3].z))) * (1.f / 512.f);
      const float sq = (((u[0].y + u[0].w) + (u[1].y + u[1].w)) + ((u[2].y + u[2].w) + (u[3].y + u[3].w))) * (1.f / 512.f);
      asm("rsqrt.approx.ftz.f32 %0, %1;" : "=f"(rstd) : "f"(fmaxf(sq - mean * mean, 0.f) + 1e-5f));
    }
    float r[8];
#pragma unroll
    for (int i = 0; i < 8; i++) r[i] = df[i >> 1][2 * (i & 1)] + df[i >> 1][2 * (i & 1) + 1];
    tred<4>(r, lane, 2); tred<2>(r, lane, 1);
    float A[4];
#pragma unroll
    for (int i = 0; i < 4; i++) A[i] = (tq & 2) ? ((tq & 1) ? e[3][i] : e[2][i]) : ((tq & 1) ? e[1][i] : e[0][i]);
    sts4(a_rs, rstd * r[0] + (A[1] - rstd * mean * A[0])); sts4(a_rs + 128, rstd * r[1] + (A[3] - rstd * mean * A[2]));
    const uint32_t have1 = mbar_test(fullb + 8, phb);
    nbar(1, 256);
    {
      const float4 g0 = lds16(a_rl), g1 = lds16(a_rl + 1024), u0 = lds16(a_rl + 512), u1 = lds16(a_rl + 1536);
#pragma unroll
      for (int mt = 0; mt < 4; mt++) ldsm_t(ad[1][mt], (a_d + 16384) ^ (mt << 5));
      const float gg = bfr(((g0.x + g0.y) + (g0.z + g0.w)) + ((g1.x + g1.y) + (g1.z + g1.w)));
      const float uu = bfr(((u0.x + u0.y) + (u0.z + u0.w)) + ((u1.x + u1.y) + (u1.z + u1.w)));
      const float hh = bfr(gg * rcp(1.f + ex2(gg * (-2.302208198f - 0.1029432397f * gg * gg)))) * uu;
      const uint32_t hw = pack2(hh, __shfl_down_sync(~0u, hh, 1));
      uint32_t hb[4];
#pragma unroll
      for (int i = 0; i < 4; i++) hb[i] = __shfl_sync(~0u, hw, 8 * i + 2 * tq);
      float dd[4][4] = {};
#pragma unroll
      for (int j = 0; j < 2; j++)
        if (!(j ? have1 : have0)) {
          mbar_wait(fullb + 8 * j, phb);
#pragma unroll
          for (int mt = 0; mt < 4; mt++) ldsm_t(ad[j][mt], (a_d + j * 16384) ^ (mt << 5));
        }
#pragma unroll
      for (int j = 0; j < 2; j++)
#pragma unroll
        for (int mt = 0; mt < 4; mt++) mma16(dd[mt], ad[j][mt], hb[2 * j], hb[2 * j + 1]);
      const float f0 = (tq & 2) ? ((tq & 1) ? dd[3][0] : dd[2][0]) : ((tq & 1) ? dd[1][0] : dd[0][0]);
      const float f1 = (tq & 2) ? ((tq & 1) ? dd[3][2] : dd[2][2]) : ((tq & 1) ? dd[1][2] : dd[0][2]);
      pub8(p_f, __float_as_uint(f0) | 1u, __float_as_uint(f1));
    }
    const unsigned tpub = clock();
    if (f < 32) {
      if (warp == ((f & 15) >> 1)) {
        float a4[4];
#pragma unroll
        for (int i = 0; i < 4; i++) a4[i] = (f & 16) ? y[1][i] : y[0][i];
        tred<2>(a4, lane, 16); tred<1>(a4, lane, 8);
        if ((g & 1) == (f & 1)) sts4(sb + O_SM + (112 + 4 * tq + ((lane >> 2) & 2) + (lane >> 4)) * 4, a4[0]);
      }
      if (warp == 7) nbar_arrive(2, 256);
      else {
        uint4 u;
        float q4[4];
        spin_until(tpub + d7);
        POLL {
          u = ldx16(pf);
          q4[0] = u2f(u.x); q4[1] = u2f(u.y); q4[2] = u2f(u.z); q4[3] = u2f(u.w);
          tred<2>(q4, lane, 16); tred<1>(q4, lane, 8);
          q4[0] += __shfl_xor_sync(~0u, q4[0], 4);
          RETRY(lop_x3(u.x, u.z, par))
        }
        sts4(a_q, q4[0]);
        nbar(2, 256);
        if (tid < 16) {
          float q[8];
#pragma unroll
          for (int i = 0; i < 8; i++) q[i] = lds4(sb + O_SM + (tid + 16 * i) * 4);
          const float t = ((q[0] + q[1]) + (q[2] + q[3])) + ((q[4] + q[5]) + q[6]);
          *po = __float2bfloat16(q[7] + bfr(gbv * bfr(t)));
          if (f == 0 && tid == 0) stx4(&scr->cnt[0], epoch + 1);
        }
      }
    }
  }
}

static void make_sched(Sched& s) {
  const char* order = "FAFABCFmmvog..d";
  const double dt = 5150 * 1e-3, dth = 5100 * 1e-3, dtt = 5150 * 1e-3;
  const int nbig = NBIG;
  s.t0 = 200; s.dth = (unsigned)(dth * 256 + 0.5);
  double t = s.t0 + 512 * dth + 150;
  int tile = 0, jm = 0;
  for (int i = 0; i < 3; i++) s.nr[i] = s.nt[i] = 0;
  auto add = [&](int c, int type, double step, int win, int b0, int tl) {
    s.r[c][s.nr[c]++] = make_uint2((unsigned)(t + 0.5) | (unsigned)(step + 0.5) << 16, type | win << 4 | (b0 + 64) << 8 | tl << 16);
    if (type == T_KV) s.nt[c]++;
  };
  const int w1 = 6, w2 = 4;
  for (const char* p = order; *p; p++) {
    const char c = *p;
    if (c == 'v' || c == 'o' || c == 'm') {
      const int ty = c == 'v' ? T_UV : c == 'o' ? T_WO : T_MOD;
      const double d = c == 'm' ? dt : dtt;
      add(0, ty, 64 * d, w1, 0, c == 'm' ? jm : 0); add(1, ty, 64 * d, w1, 0, c == 'm' ? jm : 0);
      t += (c == 'm' ? 64 : 256) * d; jm += c == 'm';
    } else if (c == 'g' || c == 'd') {
      add(2, c == 'g' ? T_GU : T_DN, 56 * dtt, c == 'g' ? w1 : 6, 64, 0);
      t += (c == 'g' ? 224 : 112) * dtt;
    } else if (c == '.') t += 100;
    else if (c == '-') t -= 100;
    else {
      const int na = c == 'F' ? 0 : c == 'C' ? nbig : 64, nf = c == 'A' ? 0 : 56, n = na + nf;
      const int w = na && nf ? w2 : w1;
      if (na) add(0, T_KV, n * dt, w, 0, tile);
      if (na == 64) add(1, T_KV, n * dt, w, 0, tile);
      if (nf) add(2, T_KV, n * dt, w, 64 - na, tile);
      tile += n; t += 4 * n * dt;
      s.t4 = (unsigned)t + 600;
    }
  }
  s.dt = (unsigned)(dt * 256 + 0.5); s.d7 = 300; s.d4 = 2150 | 1350 << 16; s.d6 = 3550;
}

static void launch(void* const* d_in, void* d_out) {
  static TMaps tms;
  static Sched sch;
  static bool init = false;
  static void* scr = nullptr;
  if (!init) {
    void* fn = nullptr; cudaDriverEntryPointQueryResult qr;
    cudaGetDriverEntryPoint("cuTensorMapEncodeTiled", &fn, cudaEnableDefault, &qr);
    EncFn f = (EncFn)fn;
    const CUtensorMapSwizzle S64 = CU_TENSOR_MAP_SWIZZLE_64B, S128 = CU_TENSOR_MAP_SWIZZLE_128B;
    const CUtensorMapL2promotion P128 = CU_TENSOR_MAP_L2_PROMOTION_L2_128B, P256 = CU_TENSOR_MAP_L2_PROMOTION_L2_256B;
    enc3d(f, &tms.m[0], d_in[2], 64, 512, 64, 8192, 128, 64, 128, 1, S128, P128);
    enc3d(f, &tms.m[1], d_in[3], 64, 512, 64, 8192, 128, 64, 64, 2, S128, P256);
    enc3d(f, &tms.m[2], d_in[1], 64, SK, 8, 1024, 128, 64, 64, 2, S128, P256);
    enc3d(f, &tms.m[3], d_in[11], 3072, 256, 2, 6144, 256 * 6144, 32, 256, 1, S64, P128);
    enc3d(f, &tms.m[4], d_in[4], 64, 512, 64, 8192, 128, 64, 128, 1, S128, P128);
    enc3d(f, &tms.m[5], d_in[5], 512, 128, 32, 1024, 128 * 1024, 64, 128, 1, S128, P128);
    enc3d(f, &tms.m[6], d_in[7], 1792, 256, 2, 3584, 256 * 3584, 32, 256, 1, S64, P128);
    enc3d(f, &tms.m[7], d_in[8], 1792, 256, 2, 3584, 256 * 3584, 32, 256, 1, S64, P128);
    enc3d(f, &tms.m[8], d_in[9], 64, 1792, 8, 1024, 128, 64, 16, 8, S128, P256);
    cudaFuncSetAttribute(fused_kernel, cudaFuncAttributeMaxDynamicSharedMemorySize, SMEM9);
    cudaGetSymbolAddress(&scr, g_scr);
    make_sched(sch);
    init = true;
  }
  fused_kernel<<<NCTA9, 384, SMEM9>>>((const bf16*)d_in[0], (const bf16*)d_in[10], (const bf16*)d_in[11], (bf16*)d_out, (Scratch*)scr, sch, tms);
}

static bool fits() {
  cudaFuncSetAttribute(fused_kernel, cudaFuncAttributeMaxDynamicSharedMemorySize, SMEM9);
  cudaLaunchConfig_t cfg = {};
  cfg.gridDim = dim3(NCTA9); cfg.blockDim = dim3(384); cfg.dynamicSmemBytes = SMEM9;
  cudaLaunchAttribute at[1];
  at[0].id = cudaLaunchAttributeClusterDimension; at[0].val.clusterDim.x = 8; at[0].val.clusterDim.y = 1; at[0].val.clusterDim.z = 1;
  cfg.attrs = at; cfg.numAttrs = 1;
  int n = 0;
  if (cudaOccupancyMaxActiveClusters(&n, fused_kernel, &cfg) != cudaSuccess) { (void)cudaGetLastError(); return false; }
  return n >= NCTA9 / 8;
}
}
#undef BAR_ARM
#undef BAR_ARRIVE
#undef BAR_INIT
#undef B_EM
#undef B_EMPTY
#undef B_FM
#undef B_FULL
#undef B_G
#undef B_G2
#undef B_H
#undef B_HZ
#undef B_Q2
#undef B_QF
#undef B_ST
#undef B_TAB
#undef B_W
#undef B_WZ
#undef CNT_ADD
#undef DSC
#undef HI128
#undef HI64
#undef HWIN
#undef NBIG
#undef NCTA9
#undef NPO
#undef NSL
#undef O_B
#undef O_BAR
#undef O_CTX
#undef O_DBG
#undef O_EP
#undef O_HZ
#undef O_LZ
#undef O_P
#undef O_Q
#undef O_R
#undef O_SILU
#undef O_SM
#undef O_X
#undef PIN
#undef PINL
#undef POLL
#undef RETRY
#undef SK
#undef SMEM9
#undef SMEM_BASE
#undef SPIN_MAX
#undef TAU
#undef VDLY
#undef X16
#undef fbits

namespace v8 {
typedef __nv_bfloat16 bf16;
#define NCTA 128
#define SK 32768
#define SLOT 32768
#define NSLOT 6
#define OFF_WQ (2 * SLOT)
#define OFF_WUK (4 * SLOT)
#define OFF_Q 196608
#define OFF_P (OFF_Q + 16384)
#define OFF_B (OFF_P + 4096)
#define OFF_R4 (OFF_B + 2304)
#define OFF_SILU (OFF_R4 + 4096)
#define OFF_RA (OFF_SILU + 1024)
#define OFF_SM (OFF_RA + 1024)
#define OFF_BP (OFF_SM + 1792)
#define OFF_CO (OFF_BP + 1024)
#define OFF_BAR (OFF_CO + 1280)
#define OFF_MASK (OFF_BAR + 512)
#define OFF_DBG (OFF_MASK + 16)
#define SMEM_BYTES (OFF_DBG + 128)
#define OFF_MOD OFF_Q
#define OFF_UV (4 * SLOT)
#define OFF_O (5 * SLOT)
#define OFF_G 0
#define OFF_U 16384
#define OFF_D SLOT
#define OFF_XO (OFF_D + 16384)
#define FB_UK 4
#define FB_KV 6
#define FB_MOD 22
#define FB_UV 23
#define FB_O 25
#define FB_G 27
#define FB_D 29
#define EB 30
#define QB 50
#define XB 51
#define SPIN_MAX (1 << 20)
#define BACKOFF 40
#define RATE_NS 652
#define RATE_T0 200
#define RATE_TL 300
#define WINS 0x3222333
#define KVWIN 4
#define RATE_H 650
#define RATE_E 650
#define SMUL 9
#define NPRE0 1
#define NPRE1 3
#define HWIN 4
#define EWIN 3
#define WTEST 450
#define DLY5 650
#define DLY6 600
#define DLY7 600
#define P12(a, b, c, d, e, f, g, h, i, j, k, l) ((unsigned long long)(a) | (b) << 5 | (c) << 10 | (d) << 15 | (e) << 20 | (f) << 25 | \
  (unsigned long long)(g) << 30 | (unsigned long long)(h) << 35 | (unsigned long long)(i) << 40 | (unsigned long long)(j) << 45 | \
  (unsigned long long)(k) << 50 | (unsigned long long)(l) << 55)
#define ORDER0 P12(0, 1, 2, 3, 4, 5, 16, 6, 7, 8, 9, 10)
#define ORDER1 P12(11, 12, 13, 14, 15, 17, 18, 19, 20, 23, 21, 22)
#define TAIL_K 17
#define RS 16
template <int N> struct IC { static constexpr int value = N; };
struct TMaps { CUtensorMap m[9]; };

struct __align__(128) Scratch {
  uint4 xo[128 * 64 * RS];
  uint2 ml[32 * 64];
  unsigned h[8 * 256];
  unsigned qa[32 * 256];
  unsigned xc[128 * 64];
  unsigned xao[8 * 512];
  unsigned xf[112 * 512];
  unsigned xm[2048];
  unsigned cnt[5 * 32];
};
__device__ Scratch g_scr;
#define g_xo scr->xo
#define g_ml scr->ml
#define g_h scr->h
#define g_qa scr->qa
#define g_xc scr->xc
#define g_xao scr->xao
#define g_xf scr->xf
#define g_xm scr->xm
#define g_epoch scr->cnt[0]

__device__ __forceinline__ uint32_t s2u(const void* p) { return (uint32_t)__cvta_generic_to_shared(p); }
__device__ __forceinline__ float bflo(uint32_t u) { return __uint_as_float(u << 16); }
__device__ __forceinline__ float bfhi(uint32_t u) { return __uint_as_float(u & 0xffff0000u); }
__device__ __forceinline__ float u2f(uint32_t u) { return __uint_as_float(u); }
__device__ __forceinline__ void fma8(float* acc, uint4 v, float s) {
  acc[0] += s * bflo(v.x); acc[1] += s * bfhi(v.x); acc[2] += s * bflo(v.y); acc[3] += s * bfhi(v.y);
  acc[4] += s * bflo(v.z); acc[5] += s * bfhi(v.z); acc[6] += s * bflo(v.w); acc[7] += s * bfhi(v.w);
}
__device__ __forceinline__ uint32_t pack2(float a, float b) {
  __nv_bfloat162 p = __floats2bfloat162_rn(a, b); return *(uint32_t*)&p;
}
__device__ __forceinline__ float bfr(float v) { return bfhi(pack2(v, v)); }
__device__ __forceinline__ float silu_bf(float c) { return bfr(__fdividef(c, 1.f + __expf(-c))); }
#define fbits(v) ((__float_as_uint(v) & ~1u) | par)
__device__ __forceinline__ uint32_t pack2t(float a, float b, unsigned par) {
  const uint32_t ua = ((__float_as_uint(a) + ((par ^ 1) << 16)) & 0xFFFE0000u) | (par << 16);
  return __byte_perm(ua, pack2(b, b), 0x7632);
}
__device__ __forceinline__ void nbar(int id, int n) { asm volatile("bar.sync %0, %1;" ::"r"(id), "r"(n) : "memory"); }
__device__ __forceinline__ void nbar_arrive(int id, int n) { asm volatile("bar.arrive %0, %1;" ::"r"(id), "r"(n) : "memory"); }
__device__ __forceinline__ uint4 ldc16(const void* p) {
  uint4 v; asm volatile("ld.relaxed.cta.global.v4.u32 {%0,%1,%2,%3}, [%4];" : "=r"(v.x), "=r"(v.y), "=r"(v.z), "=r"(v.w) : "l"(p) : "memory"); return v;
}
__device__ __forceinline__ unsigned ldc4(const void* p) {
  unsigned v; asm volatile("ld.relaxed.cta.global.u32 %0, [%1];" : "=r"(v) : "l"(p) : "memory"); return v;
}
__device__ __forceinline__ uint4 ldx16(const void* p) {
  uint4 v; asm volatile("ld.relaxed.gpu.global.v4.u32 {%0,%1,%2,%3}, [%4];" : "=r"(v.x), "=r"(v.y), "=r"(v.z), "=r"(v.w) : "l"(p) : "memory"); return v;
}
__device__ __forceinline__ unsigned ldx4(const void* p) {
  unsigned v; asm volatile("ld.relaxed.gpu.global.u32 %0, [%1];" : "=r"(v) : "l"(p) : "memory"); return v;
}
__device__ __forceinline__ unsigned long long ldx64(const void* p) {
  unsigned long long v; asm volatile("ld.relaxed.gpu.global.u64 %0, [%1];" : "=l"(v) : "l"(p) : "memory"); return v;
}
__device__ __forceinline__ void stx16(void* p, uint4 v) {
  asm volatile("st.relaxed.gpu.global.v4.u32 [%0], {%1,%2,%3,%4};" ::"l"(p), "r"(v.x), "r"(v.y), "r"(v.z), "r"(v.w) : "memory");
}
__device__ __forceinline__ void stx8(void* p, uint2 v) { asm volatile("st.relaxed.gpu.global.v2.u32 [%0], {%1,%2};" ::"l"(p), "r"(v.x), "r"(v.y) : "memory"); }
__device__ __forceinline__ void stx4(void* p, unsigned v) { asm volatile("st.relaxed.gpu.global.u32 [%0], %1;" ::"l"(p), "r"(v) : "memory"); }
__device__ __forceinline__ unsigned lop_x3(unsigned a, unsigned b, unsigned c) {
  unsigned d; asm("lop3.b32 %0, %1, %2, %3, 0x7E;" : "=r"(d) : "r"(a), "r"(b), "r"(c)); return d; }
#define X16(v) (lop_x3(v.x, v.y, par) | lop_x3(v.z, v.w, par))
#define X8(v) lop_x3(v.x, v.y, par)
#define RETRY(bad) if (!__any_sync(~0u, (bad) & 1) || ++it_ >= SPIN_MAX) break; __nanosleep(BACKOFF);
#define POLL _Pragma("unroll 1") for (int it_ = 0;;)
__device__ __forceinline__ void mbar_wait(uint32_t bar) {
  uint32_t ok; int it = 0;
  do {
    asm volatile("{.reg .pred p; mbarrier.try_wait.parity.shared::cta.b64 p, [%1], 0; selp.u32 %0,1,0,p;}"
                 : "=r"(ok) : "r"(bar) : "memory");
  } while (!ok && ++it < SPIN_MAX);
}
__device__ __forceinline__ float ex2(float v) { float r; asm("ex2.approx.ftz.f32 %0, %1;" : "=f"(r) : "f"(v)); return r; }
__device__ __forceinline__ float rcp(float v) { float r; asm("rcp.approx.ftz.f32 %0, %1;" : "=f"(r) : "f"(v)); return r; }
__device__ __forceinline__ void mma16(float* d, const uint32_t* a, uint32_t b0, uint32_t b1) {
  asm volatile("mma.sync.aligned.m16n8k16.row.col.f32.bf16.bf16.f32 {%0,%1,%2,%3}, {%4,%5,%6,%7}, {%8,%9}, {%0,%1,%2,%3};"
               : "+f"(d[0]), "+f"(d[1]), "+f"(d[2]), "+f"(d[3]) : "r"(a[0]), "r"(a[1]), "r"(a[2]), "r"(a[3]), "r"(b0), "r"(b1));
}
__device__ __forceinline__ float4 lds16(uint32_t a) {
  float4 v; asm volatile("ld.shared.v4.f32 {%0,%1,%2,%3}, [%4];" : "=f"(v.x), "=f"(v.y), "=f"(v.z), "=f"(v.w) : "r"(a) : "memory"); return v;
}
__device__ __forceinline__ void ldsm_t(uint32_t* r, uint32_t a) {
  asm volatile("ldmatrix.sync.aligned.m8n8.x4.trans.shared.b16 {%0,%1,%2,%3}, [%4];" : "=r"(r[0]), "=r"(r[1]), "=r"(r[2]), "=r"(r[3]) : "r"(a) : "memory");
}
__device__ __forceinline__ void ldsm(uint32_t* r, uint32_t a) {
  asm volatile("ldmatrix.sync.aligned.m8n8.x4.shared.b16 {%0,%1,%2,%3}, [%4];" : "=r"(r[0]), "=r"(r[1]), "=r"(r[2]), "=r"(r[3]) : "r"(a) : "memory");
}
template <int N>
__device__ __forceinline__ void tred(float* a, int lane, int m) {
  const bool hi = lane & m;
#pragma unroll
  for (int i = 0; i < N; i++) {
    float send = hi ? a[i] : a[i + N], keep = hi ? a[i + N] : a[i];
    a[i] = keep + __shfl_xor_sync(~0u, send, m);
  }
}
template <int N>
__device__ __forceinline__ void tmax(float* a, int lane, int m) {
  const bool hi = lane & m;
#pragma unroll
  for (int i = 0; i < N; i++) {
    float send = hi ? a[i] : a[i + N], keep = hi ? a[i + N] : a[i];
    a[i] = fmaxf(keep, __shfl_xor_sync(~0u, send, m));
  }
}
__device__ __forceinline__ void arrive2(uint32_t bar, uint32_t rbar, bool local, bool remote) {
  asm volatile("{.reg .pred p, q; setp.ne.s32 p, %2, 0; setp.ne.s32 q, %3, 0; @p mbarrier.arrive.shared::cta.b64 _, [%0];\n"
               "@q mbarrier.arrive.relaxed.cluster.shared::cluster.b64 _, [%1];}" ::"r"(bar), "r"(rbar), "r"((int)local), "r"((int)remote) : "memory");
}
__device__ __forceinline__ unsigned long long stream_policy() {
  unsigned long long p;
  asm volatile("createpolicy.fractional.L2::evict_first.b64 %0, 1.0;" : "=l"(p));
  return p;
}
__device__ __forceinline__ void tma3d(uint32_t dst, const CUtensorMap* tm, uint32_t bar, int c0, int c1, int c2) {
  asm volatile("cp.async.bulk.tensor.3d.shared::cluster.global.mbarrier::complete_tx::bytes.L2::cache_hint [%0], [%1, {%3, %4, %5}], [%2], %6;"
               ::"r"(dst), "l"(tm), "r"(bar), "r"(c0), "r"(c1), "r"(c2), "l"(stream_policy()) : "memory");
}
__device__ __forceinline__ void st_async2(uint32_t dst, uint32_t bar, float v0, float v1) {
  asm volatile("st.async.shared::cluster.mbarrier::complete_tx::bytes.v2.f32 [%0], {%1, %2}, [%3];" ::"r"(dst), "f"(v0), "f"(v1), "r"(bar) : "memory");
}
__device__ __forceinline__ void st_pair(int mode, uint32_t dst, uint32_t bar, float v0, float v1) {
  asm volatile("{.reg .pred p, q; setp.eq.s32 p, %4, 1; setp.eq.s32 q, %4, 2; @p st.shared.v2.f32 [%0], {%1, %2};\n"
               "@q st.async.shared::cluster.mbarrier::complete_tx::bytes.v2.f32 [%0], {%1, %2}, [%3];}"
               ::"r"(dst), "f"(v0), "f"(v1), "r"(bar), "r"(mode) : "memory");
}
__device__ __forceinline__ void spin_until(unsigned t) { while ((int)((unsigned)clock() - t) < 0) {} }
__device__ __forceinline__ unsigned wait_until(unsigned t) {
  unsigned now;
  for (;;) {
    asm volatile("mov.u32 %0, %%globaltimer_lo;" : "=r"(now));
    if ((int)(now - t) >= 0) break;
  }
  return now;
}
#define PIN(x) asm volatile("" : "+r"(x))
#define PINL(x) asm volatile("" : "+l"(x))
#define BAR_ARRIVE(i) asm volatile("mbarrier.arrive.shared::cta.b64 _, [%0];" ::"r"(bar0 + 8 * (i)) : "memory")
#define CNT_ADD(c) asm volatile("red.relaxed.gpu.global.add.u32 [%0], 1;" ::"l"(scr->cnt + (c)) : "memory")
#define BAR_INIT(i, cnt) asm volatile("mbarrier.init.shared::cta.b64 [%0], %1;" ::"r"(bar0 + 8 * (i)), "r"(cnt) : "memory")
#define BAR_ARM(i, bytes) asm volatile("mbarrier.arrive.expect_tx.shared::cta.b64 _, [%0], %1;" ::"r"(bar0 + 8 * (i)), "r"(bytes) : "memory")

__device__ __forceinline__ void tail(unsigned char* smem, Scratch* __restrict__ scr, const bf16* __restrict__ x, bf16* __restrict__ out,
                                     const unsigned par, const unsigned epoch, const int warp) {
  int tid, b;
  asm volatile("mov.u32 %0, %%tid.x;" : "=r"(tid));
  asm volatile("mov.u32 %0, %%ctaid.x;" : "=r"(b));
  const int lane = tid & 31, g = lane >> 2, tq = lane & 3;
  const uint32_t sb = __shfl_sync(~0u, s2u(smem), 0), bar0 = sb + OFF_BAR;
  float* s_sm = (float*)(smem + OFF_SM);
  const int prow = 4 * (lane >> 4) + ((lane & 7) >> 1) + 8 * (lane & 1);
  const float* s_co = (const float*)(smem + OFF_CO);
  const int opos = (b & 15) * 32 + (lane & 16) + 2 * (lane & 6) + ((lane >> 2) & 2) + (lane & 1);
  const float xv = b < 16 ? __bfloat162float(x[(b & 15) * 32 + lane]) : 0.f;
  const int rk = b & 1, ob = 32 * rk + ((b >> 1) & 31);
  uint32_t psb;
  asm volatile("mapa.shared::cluster.u32 %0, %1, %2;" : "=r"(psb) : "r"(sb), "r"(rk ^ 1));
  {
    uint32_t a[8][4];
    {
      const int rg = tid >> 4;
      const uint4* src = g_xo + ((size_t)b * 64 + rg) * RS;
      const uint32_t dst = sb + OFF_XO + rg * 256 + (((tid & 15) ^ (rg & 7)) << 4);
      unsigned long long todo = 0x0001000100010001ull;
#pragma unroll 1
      for (int it = 0; it < SPIN_MAX * 16; it++) {
        unsigned long long mk = *(volatile unsigned long long*)(smem + OFF_MASK);
        const unsigned long long nw = (mk >> rg) & todo;
        todo ^= nw;
#pragma unroll
        for (int i = 0; i < 4; i++)
          if (nw >> (16 * i) & 1)
            asm volatile("cp.async.cg.shared.global [%0], [%1], 16;" ::"r"(dst + i * 4096), "l"(src + i * 16 * RS + (tid & 15)) : "memory");
        if (!__any_sync(~0u, todo != 0)) break;
      }
      asm volatile("cp.async.mbarrier.arrive.noinc.shared::cta.b64 [%0];" ::"r"(bar0 + 8 * (XB + 2)) : "memory");
    }
    mbar_wait(bar0 + 8 * FB_UV); mbar_wait(bar0 + 8 * (FB_UV + 1));
    const uint32_t ab = sb + OFF_UV + (warp >> 2) * 8192 + (8 * (lane >> 4) + (lane & 7)) * 128 + (((2 * (warp & 3) + ((lane >> 3) & 1)) ^ (lane & 7)) << 4);
#pragma unroll
    for (int s = 0; s < 8; s++) ldsm_t(a[s], ab + (s >> 2) * 16384 + (s & 3) * 2048);
    const int chn = 2 * warp + (tq & 1);
    uint32_t a_b = sb + OFF_B + (tq >> 1) * 272 + (32 * (chn >> 2) + 8 * (g >> 1) + 2 * (chn & 3) + (g & 1)) * 2;
    uint32_t a_bq = sb + OFF_B + (lane & 1) * 272 + (lane >> 3) * 16;
    unsigned* p_c = g_xc + (b >> 2) * 256 + warp * 32 + (b & 3) * 8 + (g & 3) * 2 + (g >> 2);
    PIN(a_b); PIN(a_bq); PINL(p_c);
    mbar_wait(bar0 + 8 * (XB + 6));
    uint32_t wb[8];
#pragma unroll
    for (int s = 0; s < 8; s++) wb[s] = *(const uint32_t*)(smem + OFF_RA + (4 * s + tq) * 4);
    const float invL = *(const float*)(smem + OFF_RA + 128);
    float ov;
    POLL {
      mbar_wait(bar0 + 8 * (XB + 2));
      uint32_t ao[4][4];
#pragma unroll
      for (int s = 0; s < 4; s++)
        ldsm_t(ao[s], sb + OFF_XO + (16 * s + 8 * (lane >> 4) + (lane & 7)) * 256 + (((2 * warp + ((lane >> 3) & 1)) ^ (lane & 7)) << 4));
      float d[4][4] = {};
#pragma unroll
      for (int s = 0; s < 4; s++) mma16(d[s], ao[s], wb[2 * s], wb[2 * s + 1]);
      const unsigned p2 = par * 0x10001u;
      unsigned bad = 0;
#pragma unroll
      for (int s = 0; s < 4; s++) bad |= lop_x3(ao[s][0], ao[s][1], p2) | lop_x3(ao[s][2], ao[s][3], p2);
      bad = g == 0 ? bad | (bad >> 16) : 0u;
      ov = (tq & 1) ? (d[0][2] + d[1][2]) + (d[2][2] + d[3][2]) : (d[0][0] + d[1][0]) + (d[2][0] + d[3][0]);
      if (__builtin_expect(!__any_sync(~0u, bad & 1) || ++it_ >= SPIN_MAX, 1)) break;
#pragma unroll
      for (int i = 0; i < 4; i++)
        asm volatile("cp.async.cg.shared.global [%0], [%1], 16;"
                     ::"r"(sb + OFF_XO + ((lane >> 1) + 16 * i) * 256 + (((2 * warp + (lane & 1)) ^ ((lane >> 1) & 7)) << 4)),
                       "l"(g_xo + ((size_t)b * 64 + (lane >> 1) + 16 * i) * RS + 2 * warp + (lane & 1)) : "memory");
      asm volatile("cp.async.wait_all;" ::: "memory");
      __syncwarp();
    }
    {
      const float lo = ov - bfhi(__float_as_uint(ov));
      asm volatile("st.shared.u16 [%0], %1;" ::"r"(a_b), "h"((unsigned short)((tq & 2) ? pack2(lo, lo) : __float_as_uint(ov) >> 16)) : "memory");
    }
    nbar(1, 256);
    float d[4][4] = {};
#pragma unroll
    for (int y = 0; y < 4; y++) {
      uint32_t bq[4];
      ldsm(bq, a_bq + 64 * y);
      mma16(d[(2 * y) & 3], a[2 * y], bq[0], bq[1]); mma16(d[(2 * y + 1) & 3], a[2 * y + 1], bq[2], bq[3]);
    }
    const float r0 = ((d[0][0] + d[0][1]) + (d[1][0] + d[1][1])) + ((d[2][0] + d[2][1]) + (d[3][0] + d[3][1]));
    const float r1 = ((d[0][2] + d[0][3]) + (d[1][2] + d[1][3])) + ((d[2][2] + d[2][3]) + (d[3][2] + d[3][3]));
    if (tq == 0) stx4(p_c, pack2t(r0 * invL, r1 * invL, par));
  }
  unsigned tpub = clock();
  mbar_wait(bar0 + 8 * (XB + 4));
  const float gav = s_co[256 + (opos & 31)];
  const float gbv = s_co[288 + (lane & 4) + 2 * (lane & 1) + ((lane >> 1) & 1)];
  float4 cf[2];
#pragma unroll
  for (int s = 0; s < 2; s++) cf[s] = *(const float4*)(s_co + 32 * warp + 16 * s + 4 * tq);
  {
    uint32_t a[2][4][4];
    mbar_wait(bar0 + 8 * (FB_O + (warp >> 2)));
    const uint32_t ab = sb + OFF_O + (32 * warp + prow) * 128 + ((((lane >> 3) & 1) ^ (prow & 7)) << 4);
#pragma unroll
    for (int i = 0; i < 8; i++) ldsm_t(a[i >> 2][i & 3], (ab + (i >> 2) * 2048) ^ ((i & 3) << 5));
    uint4 v;
    const unsigned* pc = g_xc + (4 * (b >> 4) + 2 * rk + (warp >> 2)) * 256 + 64 * (warp & 3) + 2 * lane;
    uint32_t ro = ((tq >> 1) == rk ? sb : psb) + OFF_P + (8 * (tq & 1) + g) * 144 + (8 * rk + warp) * 8;
    uint32_t a_q = sb + OFF_P + (8 * (lane >> 4) + (lane & 7)) * 144;
    unsigned* p_ao = g_xao + (b >> 5) * 1024 + (opos >> 4) * 32 + (b & 16) + (opos & 15);
    PIN(ro); PIN(a_q); PINL(p_ao); PINL(pc);
    spin_until(tpub + DLY5);
    POLL {
      const unsigned long long u0 = ldx64(pc);
      v.x = (unsigned)u0; v.y = u0 >> 32;
      RETRY(X8(v))
    }
    v.z = lane & 16 ? v.x : 0u; v.w = lane & 16 ? v.y : 0u;
    if (lane & 16) v.x = v.y = 0u;
    float d[4][4] = {};
#pragma unroll
    for (int mt = 0; mt < 4; mt++) mma16(d[mt], a[0][mt], v.x, v.y);
#pragma unroll
    for (int mt = 0; mt < 4; mt++) mma16(d[mt], a[1][mt], v.z, v.w);
    float r[8];
#pragma unroll
    for (int i = 0; i < 8; i++) r[i] = d[i >> 1][2 * (i & 1)] + d[i >> 1][2 * (i & 1) + 1];
    tred<4>(r, lane, 2); tred<2>(r, lane, 1);
    st_pair((tq >> 1) == rk ? 1 : 2, ro, psb + OFF_BAR + 8 * (XB + 3), r[0], r[1]);
    __syncwarp();
    if (lane == 0) BAR_ARRIVE(XB + 3);
    if (warp == 0) {
      mbar_wait(bar0 + 8 * (XB + 3));
      float p[8];
#pragma unroll
      for (int i = 0; i < 8; i++) {
        const float4 q = lds16(a_q + i * 16);
        p[i] = (lane & 8) ? q.y + q.w : q.x + q.z;
      }
      const float t = ((p[0] + p[1]) + (p[2] + p[3])) + ((p[4] + p[5]) + (p[6] + p[7]));
      stx4(p_ao, fbits(gav * t + xv));
    }
  }
  tpub = clock();
  if (b < 112) {
    uint32_t af[2][4][4], ad[4][4];
    const uint32_t ab = sb + (32 * warp + 8 * (lane >> 4) + (lane & 7)) * 64 + ((((lane >> 3) & 1) ^ ((lane >> 1) & 3)) << 4);
    uint32_t ro = ((tq & 1) == rk ? sb : psb) + OFF_R4 + (8 * (tq >> 1) + g) * 176 + (10 * rk + warp) * 8;
    uint32_t a_q = sb + OFF_R4 + (8 * (lane >> 4) + (lane & 7)) * 176 + (lane & 8) * 10;
    uint32_t a_d = sb + OFF_D + warp * 2048 + (8 * (lane >> 4) + (lane & 7)) * 128 + ((((lane >> 3) & 1) ^ (lane & 7)) << 4);
    unsigned* p_f = g_xf + b * 512 + 64 * warp + 16 * tq + 2 * g;
    const unsigned* pa = g_xao + (g >> 1) * 1024 + 512 * rk + 64 * warp + 4 * (lane & 7);
    PIN(ro); PIN(a_q); PIN(a_d); PINL(p_f); PINL(pa);
    spin_until(tpub + DLY6);
    uint4 v[2];
    {
      bool have = false;
      POLL {
        v[0] = ldx16(pa); v[1] = ldx16(pa + 32);
        const unsigned t1 = (unsigned)clock() + WTEST;
        while (!have && (int)((unsigned)clock() - t1) < 0) {
          uint32_t ok;
          asm volatile("{.reg .pred p, q; mbarrier.test_wait.parity.shared::cta.b64 p, [%1], 0; mbarrier.test_wait.parity.shared::cta.b64 q, [%1+8], 0;\n"
                       "and.pred p, p, q; vote.sync.all.pred p, p, 0xffffffff; selp.u32 %0, 1, 0, p;}" : "=r"(ok) : "r"(bar0 + 8 * FB_G) : "memory");
          if (ok) {
#pragma unroll
            for (int i = 0; i < 8; i++) ldsm_t(af[i >> 2][i & 3], (ab + ((i & 2) ? OFF_U : OFF_G) + (i >> 2) * 1024) ^ ((i & 1) << 5));
            have = true;
          }
        }
        if (!__any_sync(~0u, (X16(v[0]) | X16(v[1])) & 1) || ++it_ >= SPIN_MAX) break;
      }
      float df[4][4] = {}, dg[2][4] = {};
      uint32_t zb[4];
      const uint32_t one = g == 0 ? 0x3F803F80u : 0u;
#pragma unroll
      for (int s = 0; s < 2; s++) {
        const uint32_t y0 = pack2(u2f(v[s].x), u2f(v[s].y)), y1 = pack2(u2f(v[s].z), u2f(v[s].w));
        const uint32_t ya[4] = {y0, one, y1, one};
        mma16(dg[s], ya, y0, y1);
        zb[2 * s] = pack2(u2f(v[s].x) * cf[s].x, u2f(v[s].y) * cf[s].y); zb[2 * s + 1] = pack2(u2f(v[s].z) * cf[s].z, u2f(v[s].w) * cf[s].w);
      }
      float st[2] = {(dg[0][2] + dg[0][3]) + (dg[1][2] + dg[1][3]), (dg[0][0] + dg[0][1]) + (dg[1][0] + dg[1][1])};
      if (!have) {
        mbar_wait(bar0 + 8 * FB_G); mbar_wait(bar0 + 8 * (FB_G + 1));
#pragma unroll
        for (int i = 0; i < 8; i++) ldsm_t(af[i >> 2][i & 3], (ab + ((i & 2) ? OFF_U : OFF_G) + (i >> 2) * 1024) ^ ((i & 1) << 5));
      }
#pragma unroll
      for (int i = 0; i < 8; i++) mma16(df[i & 3], af[i >> 2][i & 3], zb[2 * (i >> 2)], zb[2 * (i >> 2) + 1]);
#pragma unroll
      for (int o2 = 1; o2 < 4; o2 <<= 1) { st[0] += __shfl_xor_sync(~0u, st[0], o2); st[1] += __shfl_xor_sync(~0u, st[1], o2); }
#pragma unroll
      for (int o2 = 4; o2 < 32; o2 <<= 1) st[1] += __shfl_xor_sync(~0u, st[1], o2);
      float r[8];
#pragma unroll
      for (int i = 0; i < 8; i++) r[i] = df[i >> 1][2 * (i & 1)] + df[i >> 1][2 * (i & 1) + 1];
      tred<4>(r, lane, 2); tred<2>(r, lane, 1);
      const int md = (tq & 1) == rk ? 1 : 2;
      st_pair(md, ro, psb + OFF_BAR + 8 * (XB + 5), r[0], r[1]);
      st_pair(lane < 2 ? md : 0, ro + 16 * 176, psb + OFF_BAR + 8 * (XB + 5), st[0], st[1]);
      __syncwarp();
      if (lane == 0) BAR_ARRIVE(XB + 5);
      mbar_wait(bar0 + 8 * FB_D);
#pragma unroll
      for (int mt = 0; mt < 4; mt++)
        ldsm_t(ad[mt], a_d ^ (mt << 5));
    }
    mbar_wait(bar0 + 8 * (XB + 5));
    {
      float4 q[5], u[8];
#pragma unroll
      for (int i = 0; i < 5; i++) q[i] = lds16(a_q + i * 16);
#pragma unroll
      for (int i = 0; i < 8; i++) u[i] = *(const float4*)(smem + OFF_R4 + 16 * 176 + (i >> 2) * 80 + (i & 3) * 16);
      float p[6] = {((q[0].x + q[0].z) + (q[1].x + q[1].z)) + ((q[2].x + q[2].z) + (q[3].x + q[3].z)), q[4].x, q[4].z,
                    ((q[0].y + q[0].w) + (q[1].y + q[1].w)) + ((q[2].y + q[2].w) + (q[3].y + q[3].w)), q[4].y, q[4].w};
      tred<3>(p, lane, 8);
      const float P = p[0], A1 = p[1], A2 = p[2];
      const float mean = (((u[0].x + u[0].z) + (u[1].x + u[1].z)) + ((u[2].x + u[2].z) + (u[3].x + u[3].z)) +
                          ((u[4].x + u[4].z) + (u[5].x + u[5].z)) + ((u[6].x + u[6].z) + (u[7].x + u[7].z))) * (1.f / 512.f);
      const float sq = (((u[0].y + u[0].w) + (u[1].y + u[1].w)) + ((u[2].y + u[2].w) + (u[3].y + u[3].w)) +
                         ((u[4].y + u[4].w) + (u[5].y + u[5].w)) + ((u[6].y + u[6].w) + (u[7].y + u[7].w))) * (1.f / 512.f);
      float rstd;
      asm("rsqrt.approx.ftz.f32 %0, %1;" : "=f"(rstd) : "f"(fmaxf(sq - mean * mean, 0.f) + 1e-5f));
      const float gg = bfr(rstd * (P - mean * A1) + A2);
      const float uu = __shfl_xor_sync(~0u, gg, 16);
      const float hh = bfr(gg * rcp(1.f + ex2(gg * (-2.302208198f - 0.1029432397f * gg * gg)))) * uu;
      const uint32_t hw = pack2(hh, __shfl_down_sync(~0u, hh, 1));
      const uint32_t b0 = __shfl_sync(~0u, hw, 2 * tq), b1 = __shfl_sync(~0u, hw, 2 * tq + 8);
      float f0 = 0, f1 = 0;
#pragma unroll
      for (int mt = 0; mt < 4; mt++) {
        float dd[4] = {0, 0, 0, 0};
        mma16(dd, ad[mt], b0, b1);
        if (tq == mt) { f0 = dd[0]; f1 = dd[2]; }
      }
      stx8(p_f, make_uint2(fbits(f0), fbits(f1)));
    }
    tpub = clock();
    if (b < 64 && warp == (b >> 3)) {
      const uint4 y = (b & 4) ? v[1] : v[0];
      float a4[4] = {u2f(y.x), u2f(y.y), u2f(y.z), u2f(y.w)};
      tred<2>(a4, lane, 16); tred<1>(a4, lane, 8);
      a4[0] += __shfl_xor_sync(~0u, a4[0], 4);
      if (!(lane & 4)) s_sm[416 + 8 * (lane >> 4) + 2 * tq + ((lane >> 3) & 1)] = a4[0];
      if (warp == 7) nbar_arrive(2, 256);
    } else if (b < 64 && warp == 7) nbar_arrive(2, 256);
    if (b < 64 && warp < 7) {
      uint4 v;
      const unsigned* pf = g_xf + (tid >> 1) * 512 + 8 * ob + 4 * (tid & 1);
      const int col = 16 * (ob >> 1) + 4 * (ob & 1) + ((tid >> 1) & 3) + 8 * (tid & 1);
      bf16* po = out + col;
      PINL(po); PINL(pf);
      spin_until(tpub + DLY7);
      POLL { v = ldx16(pf); RETRY(X16(v)) }
      float f[4] = {u2f(v.x), u2f(v.y), u2f(v.z), u2f(v.w)};
      tred<2>(f, lane, 16); tred<1>(f, lane, 8);
      f[0] += __shfl_xor_sync(~0u, f[0], 4); f[0] += __shfl_xor_sync(~0u, f[0], 2);
      if (!(lane & 6)) s_sm[352 + warp * 8 + 4 * (lane & 1) + (lane >> 3)] = f[0];
      nbar(2, 256);
      if (tid < 8) {
        const float* q = s_sm + 352 + tid;
        const float t = ((q[0] + q[8]) + (q[16] + q[24])) + ((q[32] + q[40]) + q[48]);
        *po = __float2bfloat16(s_sm[416 + (col & 15)] + bfr(gbv * bfr(t)));
        if (b == 0 && tid == 0) stx4(&g_epoch, epoch + 1);
      }
    }
  }
}

__global__ void __cluster_dims__(2, 1, 1) __launch_bounds__(384, 1)
fused_kernel(const bf16* __restrict__ x, const bf16* __restrict__ cvec, const bf16* __restrict__ w_mod, bf16* __restrict__ out,
             Scratch* __restrict__ scr, const __grid_constant__ TMaps tms) {
  extern __shared__ __align__(1024) unsigned char smem[];
  const int tid = threadIdx.x, warp = __shfl_sync(~0u, tid >> 5, 0), lane = tid & 31;
  const int b = blockIdx.x, rk = b & 1, pr = b >> 1, hd = b >> 2;
  uint32_t sb = s2u(smem), bar0 = sb + OFF_BAR;

  unsigned gt_start;
  asm volatile("mov.u32 %0, %%globaltimer_lo;" : "=r"(gt_start));
  const int g = lane >> 2, tq = lane & 3;
  const int arow = 64 * (b >> 4) + ((tid & 255) >> 3);
  uint4 wm0, wm1;
  uint32_t c0w, c1w;
  if (warp < 8) {
    const bf16* wa = w_mod + (size_t)arow * 3072 + (lane & 4) * 128 + 32 * (b & 15) + 8 * tq;
    wm0 = ldx16(wa); wm1 = ldx16(wa + 32 * 3072);
    c0w = ldc4(cvec + (arow & ~1)); c1w = ldc4(cvec + (arow & ~1) + 32);
  }
  const unsigned t_off = gt_start + RATE_T0;
  if (warp == 11) {
    if (lane == 0) {
#pragma unroll
      for (int i = 0; i < FB_KV; i++) { BAR_INIT(i, 1); BAR_ARM(i, 16384); }
    }
    __syncwarp();
    asm volatile("fence.mbarrier_init.release.cluster;" ::: "memory");
    asm volatile("barrier.cluster.arrive.relaxed.aligned;" ::: "memory");
#pragma unroll 1
    for (int i = 0; i < FB_KV; i++) {
      if (i >= HWIN) mbar_wait(bar0 + 8 * (i - HWIN));
      wait_until(t_off + (i < 4 ? 2 * i + ((b >> 1) & 1) : 4 * i - 8 + (b & 3)) * (RATE_H / 4));
      if (lane == 0) {
        if (i < 4) tma3d(sb + OFF_WQ + i * 16384, &tms.m[0], bar0 + 8 * i, 0, i * 128, 2 * hd + rk);
        else tma3d(sb + OFF_WQ + i * 16384, &tms.m[1], bar0 + 8 * i, 0, (b & 3) * 128 + (i - 4) * 64, 2 * hd);
      }
      __syncwarp();
    }
  }
  if (warp == 10) {
    const uint4 xa = ldc16(x + 16 * lane), xb = ldc16(x + 16 * lane + 8);
    const unsigned ep = ldc4(&g_epoch);
    float xv[16] = {bflo(xa.x), bfhi(xa.x), bflo(xa.y), bfhi(xa.y), bflo(xa.z), bfhi(xa.z), bflo(xa.w), bfhi(xa.w),
                    bflo(xb.x), bfhi(xb.x), bflo(xb.y), bfhi(xb.y), bflo(xb.z), bfhi(xb.z), bflo(xb.w), bfhi(xb.w)};
    float s = 0;
#pragma unroll
    for (int i = 0; i < 16; i++) s += xv[i];
#pragma unroll
    for (int o = 16; o; o >>= 1) s += __shfl_xor_sync(~0u, s, o);
    const float mean = s * (1.f / 512.f);
    s = 0;
#pragma unroll
    for (int i = 0; i < 16; i++) { xv[i] -= mean; s += xv[i] * xv[i]; }
#pragma unroll
    for (int o = 16; o; o >>= 1) s += __shfl_xor_sync(~0u, s, o);
    const float rstd = rsqrtf(s * (1.f / 512.f) + 1e-5f);
    if ((lane >> 1) == (b & 15))
#pragma unroll
      for (int i = 0; i < 4; i++)
        *(float4*)(smem + OFF_SM + (256 + (lane & 1) * 16 + 4 * i) * 4) = make_float4(xv[4 * i] * rstd, xv[4 * i + 1] * rstd, xv[4 * i + 2] * rstd, xv[4 * i + 3] * rstd);
    if (lane == 0) *(volatile unsigned*)(smem + OFF_MASK + 8) = ep;
    nbar_arrive(1, 288);
  }
  if (warp >= 8) {
    asm volatile("setmaxnreg.dec.sync.aligned.u32 72;");
    if (tid == 288) {
#pragma unroll
      for (int q = FB_KV; q < FB_KV + 16; q++) { BAR_INIT(q, 1); BAR_ARM(q, 32768); }
    }
    if (tid == 320) {
#pragma unroll
      for (int q = 0; q <= 13 + NSLOT; q++) BAR_INIT(EB + q, q == 0 ? 4 : q < 5 ? 16 : q < 16 ? 12 : 6);
    }
    if (tid == 256) {
#pragma unroll
      for (int q = FB_MOD; q <= FB_D; q++) { BAR_INIT(q, 1); BAR_ARM(q, 16384); }
      BAR_INIT(QB, 9); BAR_ARM(QB, 1024);
#pragma unroll
      for (int q = 0; q < 7; q++) BAR_INIT(XB + q, q == 2 ? 256 : q == 5 || q == 3 ? 9 : 1);
      BAR_ARM(XB + 3, 1024);
      BAR_ARM(XB + 5, 1024 + 64 + 512);
      *(volatile unsigned long long*)(smem + OFF_MASK) = 0;
    }
    if (warp != 11) {
      __syncwarp();
      asm volatile("fence.mbarrier_init.release.cluster;" ::: "memory");
      __threadfence_block();
      asm volatile("barrier.cluster.arrive.relaxed.aligned;" ::: "memory");
    }
    if (warp == 11) {
      asm volatile("barrier.cluster.wait.acquire.aligned;" ::: "memory");
      const unsigned epoch = *(volatile unsigned*)(smem + OFF_MASK + 8), par = (epoch + 1) & 1;
      mbar_wait(bar0 + 8 * (FB_KV + 15));
      for (int it = 0; ldx4(scr->cnt + 96 + 32 * (b >> 6)) != (epoch + 1) * 64 && it < SPIN_MAX; it++) {}
      uint4 hh;
      POLL { hh = ldx16(g_ml + (b >> 2) * 64 + 2 * lane); RETRY(X16(hh)) }
      int mi = __float_as_int(fmaxf(u2f(hh.x), u2f(hh.z)));
      mi ^= (mi >> 31) & 0x7fffffff;
      mi = __reduce_max_sync(~0u, mi);
      mi ^= (mi >> 31) & 0x7fffffff;
      const float M = __int_as_float(mi);
      const uint32_t wp = pack2(ex2(u2f(hh.x) - M), ex2(u2f(hh.z) - M));
      float L = bflo(wp) * u2f(hh.y) + bfhi(wp) * u2f(hh.w);
#pragma unroll
      for (int o2 = 16; o2; o2 >>= 1) L += __shfl_xor_sync(~0u, L, o2);
      *(uint32_t*)(smem + OFF_RA + lane * 4) = wp;
      if (lane == 0) *(float*)(smem + OFF_RA + 128) = rcp(L);
      __syncwarp();
      if (lane == 0) BAR_ARRIVE(XB + 6);
    }
    if (warp == 10) {
      if (lane < 8) asm volatile("prefetch.tensormap [%0];" ::"l"(&tms.m[lane + 1]) : "memory");
      asm volatile("barrier.cluster.wait.acquire.aligned;" ::: "memory");
      const unsigned epoch = *(volatile unsigned*)(smem + OFF_MASK + 8);
#pragma unroll 1
      for (int e = 0; e < 2; e++) {
        for (int it = 0; ldx4(scr->cnt + (e ? 2 + rk : 1)) != (epoch + 1) * (e ? 64 : 128) && it < SPIN_MAX; it++) {}
        if (lane == 0) BAR_ARRIVE(XB + e);
      }
      mbar_wait(bar0 + 8 * (FB_KV + 14));
      unsigned long long m = 0;
#pragma unroll 1
      for (int it = 0; ~m && it < SPIN_MAX; it++) {
        m = ldx64(scr->cnt + 32 + 32 * (b >> 6)) ^ ((epoch & 1) ? ~0ull : 0ull);
        if (lane == 0) *(volatile unsigned long long*)(smem + OFF_MASK) = m;
      }
    }
    if (warp == 9) {
      asm volatile("barrier.cluster.wait.acquire.aligned;" ::: "memory");
      const unsigned epoch = *(volatile unsigned*)(smem + OFF_MASK + 8);
      const unsigned par = (epoch + 1) & 1, inv = par ^ 1;
      const uint4 inv4 = make_uint4(inv, inv, inv, inv);
      mbar_wait(bar0 + 8 * FB_KV);
#pragma unroll 2
      for (int k = 0; k < 8; k++) {
        const uint32_t cp = ldc4(cvec + 2 * (lane + 32 * k));
        *(uint32_t*)(smem + OFF_SILU + (lane + 32 * k) * 4) = pack2(silu_bf(bflo(cp)), silu_bf(bfhi(cp)));
      }
      __syncwarp();
      mbar_wait(bar0 + 8 * FB_MOD);
      const uint32_t ab = sb + OFF_MOD + (8 * (lane >> 4) + (lane & 7)) * 32 + ((((lane >> 3) ^ (lane >> 2)) & 1) << 4);
      float d[4][4] = {};
#pragma unroll 2
      for (int s4 = 0; s4 < 8; s4++)
#pragma unroll
        for (int s = 0; s < 4; s++) {
          uint32_t a[4];
          const uint32_t* ps = (const uint32_t*)(smem + OFF_SILU) + 32 * s4 + 8 * s + tq;
          ldsm_t(a, ab + (4 * s4 + s) * 512); mma16(d[s], a, ps[0], ps[4]);
        }
      const float t = (tq & 1) ? (d[0][2] + d[1][2]) + (d[2][2] + d[3][2]) : (d[0][0] + d[1][0]) + (d[2][0] + d[3][0]);
      if (tq < 2) stx4(g_xm + b * 16 + 2 * (g & 6) + 2 * tq + (g & 1), fbits(bfr(t)));
      __syncwarp();
      if (lane == 0) CNT_ADD(6);
      mbar_wait(bar0 + 8 * (FB_KV + 8));
      if (lane < 16) stx16(g_xc + (b >> 2) * 256 + (lane >> 1) * 32 + (b & 3) * 8 + (lane & 1) * 4, inv4);
      if (lane < 8) stx16(g_xao + (b >> 5) * 1024 + (b & 15) * 64 + (lane & 4) * 8 + (b & 16) + (lane & 3) * 4, inv4);
      if (b < 112)
#pragma unroll 1
        for (int k = 0; k < 4; k++) stx16(g_xf + b * 512 + (lane + 32 * k) * 4, inv4);
      nbar_arrive(2, 288);
      for (int it = 0; ldx4(scr->cnt + 6) != (epoch + 1) * 128 && it < SPIN_MAX; it++) __nanosleep(100);
      {
        uint4 sv[2], cb[2];
        unsigned ga, gb;
        POLL {
#pragma unroll
          for (int k = 0; k < 2; k++) { sv[k] = ldx16(g_xm + 512 + 256 * rk + 4 * (lane + 32 * k)); cb[k] = ldx16(g_xm + 1024 + 256 * rk + 4 * (lane + 32 * k)); }
          ga = ldx4(g_xm + (b & 15) * 32 + lane); gb = ldx4(g_xm + 1536 + 256 * rk + 8 * (pr & 31) + (lane & 7));
          RETRY(X16(sv[0]) | X16(sv[1]) | X16(cb[0]) | X16(cb[1]) | lop_x3(ga, gb, par))
        }
#pragma unroll
        for (int k = 0; k < 2; k++) {
          const float c0 = bfr(1.f + bfhi(cb[k].x)), c1 = bfr(1.f + bfhi(cb[k].y)), c2 = bfr(1.f + bfhi(cb[k].z)), c3 = bfr(1.f + bfhi(cb[k].w));
          *(float4*)(smem + OFF_CO + (lane + 32 * k) * 16) = make_float4(c0, c1, c2, c3);
          uint2* pb = (uint2*)(smem + OFF_BP) + lane + 32 * k;
          pb[0] = make_uint2(pack2(c0, c1), pack2(c2, c3));
          pb[64] = make_uint2(__byte_perm(sv[k].x, sv[k].y, 0x7632), __byte_perm(sv[k].z, sv[k].w, 0x7632));
        }
        *(float*)(smem + OFF_CO + 1024 + lane * 4) = bfhi(ga);
        *(float*)(smem + OFF_CO + 1152 + lane * 4) = bfhi(gb);
      }
      __syncwarp();
      if (lane == 0) BAR_ARRIVE(XB + 4);
    }
    if (warp == 8) {
      const unsigned stag = ((pr * SMUL) & 63) * RATE_NS >> 6;
      unsigned tnext = t_off + 4 * RATE_H;
      asm volatile("barrier.cluster.wait.acquire.aligned;" ::: "memory");
#pragma unroll 1
      for (int k = 0; k < 24; k++) {
        const int code = (k < 12 ? ORDER0 >> (5 * k) : ORDER1 >> (5 * (k - 12))) & 31;
        const bool kv = code < 16;
        const int n = code, w = code - 16;
        if (!kv && w >= 5 && b >= 112) break;
        if (kv) mbar_wait(bar0 + 8 * (FB_KV + n - (n < 6 ? EWIN : KVWIN)));
        if (k >= TAIL_K) mbar_wait(bar0 + 8 * (FB_KV + (int)((ORDER1 >> (5 * (k - 12 - ((WINS >> (4 * (k - TAIL_K))) & 15)))) & 31)));
        const int e = kv ? (n == 3 ? 2 : n == 5 ? 1 : n) : w == 0 ? 0 : w < 5 ? 16 + ((w - 1) >> 1) : w == 7 ? 19 : 18;
        if (e != 1 && k) mbar_wait(bar0 + 8 * (EB + e));
        wait_until(tnext + stag);
        tnext += k > TAIL_K ? RATE_TL : k < 4 ? RATE_E : RATE_NS;
        if (lane == 0) {
          if (kv)
            asm volatile("cp.async.bulk.tensor.3d.shared::cluster.global.mbarrier::complete_tx::bytes.multicast::cluster.L2::cache_hint [%0], [%1, {%3, %4, %5}], [%2], %6, %7;"
                         ::"r"(sb + (n % NSLOT) * SLOT + rk * 16384), "l"(&tms.m[2]), "r"(bar0 + 8 * (FB_KV + n)), "r"(0), "r"(((n >> 1) * 64 + pr) * 64),
                           "r"(4 * (n & 1) + 2 * rk), "h"((unsigned short)3), "l"(stream_policy()) : "memory");
          else {
            tma3d(sb + (w == 0 ? OFF_MOD : w < 5 ? OFF_UV + (w - 1) * 16384 : w == 5 ? OFF_G : w == 6 ? OFF_U : OFF_D),
                  &tms.m[w == 0 ? 3 : w < 3 ? 4 : w < 5 ? 5 : w + 1], bar0 + 8 * (FB_MOD + w),
                  w == 0 ? 1024 + b * 16 : w < 3 || w == 7 ? 0 : w < 5 ? (pr & 7) * 64 : pr * 32, w == 7 ? b * 16 : w == 1 || w == 2 ? (b & 3) * 128 + (w - 1) * 64 : 0,
                  w == 1 || w == 2 ? 2 * hd : w == 3 || w == 4 ? (b >> 4) * 4 + 2 * rk + w - 3 : w == 5 || w == 6 ? rk : 0);
          }
        }
        __syncwarp();
      }
    }
    if (b < 112) {
      const int mt = warp & 1, dd = (warp >> 1) & 1;
      mbar_wait(bar0 + 8 * (XB + 4));
      const uint32_t ab = sb + (mt ? OFF_U : OFF_G) + (8 * (lane >> 4) + (lane & 7)) * 64 + (((2 * dd + ((lane >> 3) & 1)) ^ ((lane >> 1) & 3)) << 4);
      uint32_t base;
      asm volatile("mapa.shared::cluster.u32 %0, %1, %2;" : "=r"(base) : "r"(sb), "r"(dd));
      uint2 bb[16];
#pragma unroll
      for (int s = 0; s < 16; s++) bb[s] = *(const uint2*)(smem + OFF_BP + (g & 1) * 512 + (4 * s + tq) * 8);
      mbar_wait(bar0 + 8 * (FB_G + mt));
      float e[4][4] = {};
#pragma unroll
      for (int s = 0; s < 16; s++) { uint32_t a[4]; ldsm_t(a, ab + s * 1024); mma16(e[s & 3], a, bb[s].x, bb[s].y); }
      float r[4];
#pragma unroll
      for (int i = 0; i < 4; i++) r[i] = (e[0][i] + e[1][i]) + (e[2][i] + e[3][i]);
      if (tq < 2) st_async2(base + OFF_R4 + (8 * mt + g) * 176 + (10 * rk + 8 + tq) * 8, base + OFF_BAR + 8 * (XB + 5), tq ? r[1] : r[0], tq ? r[3] : r[2]);
    }
    return;
  }

  float* s_sm = (float*)(smem + OFF_SM);
  unsigned par, epoch;
  uint32_t rsb;
  {
    float* s_r4 = (float*)(smem + OFF_R4);
    asm volatile("barrier.cluster.arrive.relaxed.aligned;" ::: "memory");
    asm volatile("mapa.shared::cluster.u32 %0, %1, %2;" : "=r"(rsb) : "r"(sb), "r"(rk ^ 1));
    const float c0 = (arow & 1) ? bfhi(c0w) : bflo(c0w), c1 = (arow & 1) ? bfhi(c1w) : bflo(c1w);
    float acc[8] = {0, 0, 0, 0, 0, 0, 0, 0};
    fma8(acc, wm0, silu_bf(c0)); fma8(acc, wm1, silu_bf(c1));
    tred<4>(acc, lane, 8); tred<2>(acc, lane, 16);
    *(float2*)(s_r4 + warp * 64 + 8 * (lane & 7) + ((lane >> 1) & 4) + ((lane >> 3) & 2)) = make_float2(acc[0], acc[1]);
    nbar(1, 288);
    epoch = *(volatile unsigned*)(smem + OFF_MASK + 8);
    par = (epoch + 1) & 1;
    if (warp == 0) {
      float t = 0.f, ca = b < 16 ? 1.f : 0.f;
#pragma unroll
      for (int w = 0; w < 8; w++) { t += s_r4[w * 64 + lane]; ca += s_r4[w * 64 + 32 + lane]; }
      t += ca * s_sm[256 + lane];
      const float nb = __shfl_down_sync(~0u, t, 1);
      const uint32_t w0 = lane < 8 ? pack2t(t, nb, par) : pack2(t, nb);
      const uint32_t w1 = __shfl_down_sync(~0u, w0, 8), w2 = __shfl_down_sync(~0u, w0, 16), w3 = __shfl_down_sync(~0u, w0, 24);
      if (lane < 8 && !(lane & 1)) stx16(g_h + (b >> 5) * 512 + (b & 15) * 32 + (b & 16) + 2 * lane, make_uint4(w0, w1, w2, w3));
      __syncwarp();
      if (lane == 0) CNT_ADD(1);
    }
  }
  asm volatile("barrier.cluster.wait.acquire.aligned;" ::: "memory");
  {
    uint32_t a[4][4][4];
    mbar_wait(bar0 + 8 * (warp >> 1));
    const uint32_t ab = sb + OFF_WQ + (64 * warp + 8 * (lane >> 4) + (lane & 7)) * 128;
#pragma unroll
    for (int s = 0; s < 4; s++)
#pragma unroll
      for (int mt = 0; mt < 4; mt++) ldsm_t(a[s][mt], ab + s * 2048 + (((2 * mt + ((lane >> 3) & 1)) ^ (lane & 7)) << 4));
    uint4 v0, v1;
    const unsigned* ph = g_h + (g >> 1) * 512 + 64 * warp + 4 * (lane & 7);
    uint32_t off = OFF_B + warp * 272 + (32 * rk + 8 * tq + (lane & 4)) * 4;
    PIN(off); PINL(ph);
    mbar_wait(bar0 + 8 * XB);
    POLL { v0 = ldx16(ph); v1 = ldx16(ph + 32); RETRY(lop_x3(v0.x, v1.x, par)) }
    float d[4][4] = {};
#pragma unroll
    for (int mt = 0; mt < 4; mt++) {
      mma16(d[mt], a[0][mt], v0.x, v0.y); mma16(d[mt], a[1][mt], v0.z, v0.w);
      mma16(d[mt], a[2][mt], v1.x, v1.y); mma16(d[mt], a[3][mt], v1.z, v1.w);
    }
    float r[8];
#pragma unroll
    for (int mt = 0; mt < 4; mt++) { r[2 * mt] = d[mt][0] + d[mt][1]; r[2 * mt + 1] = d[mt][2] + d[mt][3]; }
    tred<4>(r, lane, 2); tred<2>(r, lane, 1);
    const float rc = __shfl_xor_sync(~0u, (lane & 4) ? r[0] : r[1], 4);
    const uint32_t wd = (lane & 4) ? pack2(rc, r[1]) : pack2(r[0], rc);
    const uint32_t w1 = __shfl_down_sync(~0u, wd, 8), w2 = __shfl_down_sync(~0u, wd, 16), w3 = __shfl_down_sync(~0u, wd, 24);
    asm volatile("{.reg .pred p; setp.lt.s32 p, %7, 8; @p st.shared.v4.b32 [%0], {%2,%3,%4,%5};\n"
                 "@p st.async.shared::cluster.mbarrier::complete_tx::bytes.v4.b32 [%1], {%2,%3,%4,%5}, [%6];}"
                 ::"r"(sb + off), "r"(rsb + off), "r"(wd), "r"(w1), "r"(w2), "r"(w3), "r"(rsb + OFF_BAR + 8 * QB), "r"(lane) : "memory");
    __syncwarp();
    arrive2(bar0 + 8 * QB, 0, lane == 0, false);
    arrive2(bar0 + 8 * (EB + 2), rsb + OFF_BAR + 8 * (EB + 2), lane == 0, lane == 0);
  }
  {
    uint32_t a[8][4];
    uint32_t a_bq = sb + OFF_B + (lane & 7) * 272 + (lane >> 3) * 16;
    unsigned* p_qa = g_qa + b * 64 + 8 * warp + 4 * lane;
    PIN(a_bq); PINL(p_qa);
    mbar_wait(bar0 + 8 * (FB_UK + (warp >> 2)));
    const uint32_t ab = sb + OFF_WUK + (warp >> 2) * 16384 + (16 * (warp & 3) + (lane & 15)) * 128;
#pragma unroll
    for (int s = 0; s < 8; s++) ldsm(a[s], ab + (s >> 2) * 8192 + (((2 * (s & 3) + (lane >> 4)) ^ (lane & 7)) << 4));
    mbar_wait(bar0 + 8 * QB);
    float d[4][4] = {};
#pragma unroll
    for (int y = 0; y < 4; y++) {
      uint32_t bq[4];
      ldsm(bq, a_bq + 64 * y);
      mma16(d[(2 * y) & 3], a[2 * y], bq[0], bq[1]); mma16(d[(2 * y + 1) & 3], a[2 * y + 1], bq[2], bq[3]);
    }
    float r[2] = {((d[0][0] + d[0][1]) + (d[1][0] + d[1][1])) + ((d[2][0] + d[2][1]) + (d[3][0] + d[3][1])),
                  ((d[0][2] + d[0][3]) + (d[1][2] + d[1][3])) + ((d[2][2] + d[2][3]) + (d[3][2] + d[3][3]))};
    tred<1>(r, lane, 1);
    r[0] += __shfl_xor_sync(~0u, r[0], 2);
    const float nb = __shfl_xor_sync(~0u, r[0], 4);
    const uint32_t w0 = lane < 8 ? pack2t(r[0], nb, par) : pack2(r[0], nb);
    const uint32_t w1 = __shfl_down_sync(~0u, w0, 8), w2 = __shfl_down_sync(~0u, w0, 16), w3 = __shfl_down_sync(~0u, w0, 24);
    if (lane < 2) stx16(p_qa, make_uint4(w0, w1, w2, w3));
    arrive2(bar0 + 8 * (EB + 4), rsb + OFF_BAR + 8 * (EB + 4), lane == 0, lane == 0);
  }
  {
    if (warp) nbar_arrive(3, 256); else { nbar(3, 256); if (lane == 0) CNT_ADD(2 + (b >> 6)); }
    asm volatile("setmaxnreg.inc.sync.aligned.u32 216;");
    const unsigned* pq = g_qa + rk * 4096 + tid * 4;
    uint32_t a_q = sb + OFF_Q + ((tid & 63) >> 3) * 2048 + (tid >> 6) * 128 + (((tid & 7) ^ (tid >> 6)) << 4);
    PINL(pq); PIN(a_q);
    mbar_wait(bar0 + 8 * (XB + 1));
    uint4 v[4];
    POLL {
#pragma unroll
      for (int k = 0; k < 4; k++) v[k] = ldx16(pq + 1024 * k);
      RETRY(lop_x3(v[0].x, v[1].x, par) | lop_x3(v[2].x, v[3].x, par))
    }
#pragma unroll
    for (int k = 0; k < 4; k++)
      asm volatile("st.shared.v4.b32 [%0], {%1,%2,%3,%4};" ::"r"((a_q + k * 512) ^ ((k & 1) << 6)), "r"(v[k].x), "r"(v[k].y), "r"(v[k].z), "r"(v[k].w) : "memory");
    if (warp >= 4) nbar_arrive(1, 256); else nbar(1, 256);
  }
  sb = __shfl_sync(~0u, sb, 0); bar0 = sb + OFF_BAR;
  if (warp < 4) {
    uint32_t qf[32][4];
#pragma unroll
    for (int s = 0; s < 32; s++) ldsm(qf[s], sb + OFF_Q + (s >> 2) * 2048 + (lane & 15) * 128 + (((2 * (s & 3) + (lane >> 4)) ^ (lane & 7)) << 4));
    float l0 = 0.f, l1 = 0.f, m0 = -1e30f, m1 = -1e30f;
    const float sc = 0.08838834764831845f * 1.4426950408889634f;
    const uint32_t kofs = (16 * warp + 8 * (lane >> 4) + (lane & 7)) * 128 + ((((lane >> 3) & 1) ^ (lane & 7)) << 4);
    uint32_t st = sb;
#pragma unroll 1
    for (int t = 0; t < 8; t++) {
      float sa[4][4] = {};
#pragma unroll
      for (int hf = 0; hf < 2; hf++) {
        const int n = 2 * t + hf;
        mbar_wait(bar0 + 8 * (FB_KV + n));
        uint32_t kf[16][4];
#pragma unroll
        for (int y = 0; y < 16; y++) ldsm(kf[y], st + (y >> 2) * 8192 + (kofs ^ ((y & 3) << 5)));
#pragma unroll
        for (int y = 0; y < 16; y++) {
          mma16(sa[(2 * y) & 3], qf[16 * hf + y], kf[y][0], kf[y][1]); mma16(sa[((2 * y) & 3) + 1], qf[16 * hf + y], kf[y][2], kf[y][3]);
        }
        __syncwarp();
        arrive2(bar0 + 8 * (EB + NSLOT + n), rsb + OFF_BAR + 8 * (EB + NSLOT + n), lane == 0 && n < 14, lane == 0 && n < 16 - NSLOT);
        if (hf == 0) arrive2(bar0 + 8 * EB, 0, lane == 0 && t == 0, false);
        st = st + SLOT == sb + NSLOT * SLOT ? sb : st + SLOT;
      }
#pragma unroll
      for (int i = 0; i < 4; i++) { sa[0][i] = (sa[0][i] + sa[2][i]) * sc; sa[1][i] = (sa[1][i] + sa[3][i]) * sc; }
      float cm[2] = {fmaxf(fmaxf(sa[0][0], sa[0][1]), fmaxf(sa[1][0], sa[1][1])), fmaxf(fmaxf(sa[0][2], sa[0][3]), fmaxf(sa[1][2], sa[1][3]))};
      tmax<1>(cm, lane, 1);
      cm[0] = fmaxf(cm[0], __shfl_xor_sync(~0u, cm[0], 2));
      float* pm = s_sm + (t & 1) * 64;
      if (tq < 2) pm[(g + 8 * tq) * 4 + warp] = cm[0];
      if (t >= 2) nbar(6 + (t & 1), 256); else nbar(3, 128);
      const float4 a0 = *(const float4*)(pm + g * 4), b0 = *(const float4*)(pm + g * 4 + 32);
      const float n0 = fmaxf(fmaxf(fmaxf(a0.x, a0.y), fmaxf(a0.z, a0.w)), m0), n1 = fmaxf(fmaxf(fmaxf(b0.x, b0.y), fmaxf(b0.z, b0.w)), m1);
      uint32_t pk[4];
#pragma unroll
      for (int i = 0; i < 2; i++) { pk[2 * i] = pack2(ex2(sa[i][0] - n0), ex2(sa[i][1] - n0)); pk[2 * i + 1] = pack2(ex2(sa[i][2] - n1), ex2(sa[i][3] - n1)); }
      *(uint4*)(smem + OFF_P + (t & 1) * 2048 + tid * 16) = make_uint4(pk[0], pk[1], pk[2], pk[3]);
      const float al0 = ex2(m0 - n0), al1 = ex2(m1 - n1);
      if (tid < 32 && tq == 0) *(float2*)(s_sm + 192 + (t & 1) * 16 + 2 * g) = make_float2(al0, al1);
      nbar_arrive(4 + (t & 1), 256);
      m0 = n0; m1 = n1;
      l0 = l0 * al0 + (bflo(pk[0]) + bfhi(pk[0])) + (bflo(pk[2]) + bfhi(pk[2]));
      l1 = l1 * al1 + (bflo(pk[1]) + bfhi(pk[1])) + (bflo(pk[3]) + bfhi(pk[3]));
    }
    float lr[2] = {l0, l1};
    tred<1>(lr, lane, 1);
    lr[0] += __shfl_xor_sync(~0u, lr[0], 2);
    if (tq < 2) s_sm[128 + (g + 8 * tq) * 4 + warp] = lr[0];
    nbar(3, 128);
    if (warp == 0 && tq < 2) {
      const float4 a0 = *(const float4*)(s_sm + 128 + (g + 8 * tq) * 4);
      stx8(g_ml + (16 * rk + g + 8 * tq) * 64 + pr, make_uint2(fbits(tq ? m1 : m0), fbits((a0.x + a0.y) + (a0.z + a0.w))));
    }
    if (warp == 0) { __syncwarp(); if (lane == 0) CNT_ADD(96 + 32 * rk); }
    nbar(2, 288);
    if (tid == 0) asm volatile("red.relaxed.gpu.global.xor.b64 [%0], %1;" ::"l"(scr->cnt + 32 + 32 * rk), "l"(1ull << pr) : "memory");
  } else {
    float o[16][4] = {};
    const uint32_t vofs = (warp & 1) * 16384 + (lane & 15) * 128 + (((lane >> 4) ^ (lane & 7)) << 4);
    const int hf = (warp >> 1) & 1;
    uint32_t st = sb + hf * SLOT;
    auto pv = [&](const int t, auto np) {
      constexpr int npre = decltype(np)::value;
      uint32_t vf[4][8][4];
      const int n = 2 * t + hf;
      mbar_wait(bar0 + 8 * (FB_KV + n));
#pragma unroll
      for (int s = 0; s < npre; s++)
#pragma unroll
        for (int y = 0; y < 8; y++) ldsm_t(vf[s][y], st + (y >> 2) * 8192 + s * 2048 + (vofs ^ ((y & 3) << 5)));
      nbar(4 + (t & 1), 256);
      const float2 al = *(const float2*)(s_sm + 192 + (t & 1) * 16 + 2 * g);
      uint4 pf[4];
#pragma unroll
      for (int s = 0; s < 4; s++) pf[s] = *(const uint4*)(smem + OFF_P + (t & 1) * 2048 + s * 512 + lane * 16);
      if (t < 6) nbar_arrive(6 + (t & 1), 256);
#pragma unroll
      for (int s = npre; s < 4; s++)
#pragma unroll
        for (int y = 0; y < 8; y++) ldsm_t(vf[s][y], st + (y >> 2) * 8192 + s * 2048 + (vofs ^ ((y & 3) << 5)));
#pragma unroll
      for (int nt = 0; nt < 16; nt++) { o[nt][0] *= al.x; o[nt][1] *= al.x; o[nt][2] *= al.y; o[nt][3] *= al.y; }
#pragma unroll
      for (int s = 0; s < 4; s++) {
        const uint32_t pa[4] = {pf[s].x, pf[s].y, pf[s].z, pf[s].w};
#pragma unroll
        for (int y = 0; y < 8; y++) { mma16(o[2 * y], pa, vf[s][y][0], vf[s][y][1]); mma16(o[2 * y + 1], pa, vf[s][y][2], vf[s][y][3]); }
      }
      __syncwarp();
      arrive2(bar0 + 8 * (EB + NSLOT + n), rsb + OFF_BAR + 8 * (EB + NSLOT + n), lane == 0 && n < 14, lane == 0 && n < 16 - NSLOT);
      st = st + 2 * SLOT >= sb + NSLOT * SLOT ? st - (NSLOT - 2) * SLOT : st + 2 * SLOT;
    };
#pragma unroll 1
    for (int t = 0; t < 7; t++) pv(t, IC<NPRE0>());
    pv(7, IC<NPRE1>());
    uint4* po = g_xo + ((size_t)((16 * rk + (g & 6)) * 4 + warp - 4) * 64 + pr) * RS + (lane & 7);
    const bool odd = lane & 4;
#pragma unroll
    for (int e = 0; e < 2; e++)
#pragma unroll
      for (int j2 = 0; j2 < 2; j2++) {
        uint32_t c0[4], c1[4];
#pragma unroll
        for (int i = 0; i < 4; i++) {
          c0[i] = i ? pack2(o[8 * j2 + i][2 * e], o[8 * j2 + i][2 * e + 1]) : pack2t(o[8 * j2][2 * e], o[8 * j2][2 * e + 1], par);
          c1[i] = i ? pack2(o[8 * j2 + 4 + i][2 * e], o[8 * j2 + 4 + i][2 * e + 1]) : pack2t(o[8 * j2 + 4][2 * e], o[8 * j2 + 4][2 * e + 1], par);
          const uint32_t r = __shfl_xor_sync(~0u, odd ? c0[i] : c1[i], 4);
          if (odd) c0[i] = r; else c1[i] = r;
        }
        stx16(po + e * 8 * 4 * 64 * RS + 8 * j2, make_uint4(c0[0], c0[1], c0[2], c0[3]));
        stx16(po + (e * 8 + 1) * 4 * 64 * RS + 8 * j2, make_uint4(c1[0], c1[1], c1[2], c1[3]));
      }
    nbar_arrive(2, 288);
  }
  tail(smem, scr, x, out, par, epoch, warp);
}

static void launch(void* const* d_in, void* d_out) {
  static TMaps tms;
  static bool init = false;
  static void* scr = nullptr;
  if (!init) {
    void* fn = nullptr; cudaDriverEntryPointQueryResult qr;
    cudaGetDriverEntryPoint("cuTensorMapEncodeTiled", &fn, cudaEnableDefault, &qr);
    EncFn f = (EncFn)fn;
    const CUtensorMapSwizzle S32 = CU_TENSOR_MAP_SWIZZLE_32B, S64 = CU_TENSOR_MAP_SWIZZLE_64B, S128 = CU_TENSOR_MAP_SWIZZLE_128B;
    const CUtensorMapL2promotion P128 = CU_TENSOR_MAP_L2_PROMOTION_L2_128B, P256 = CU_TENSOR_MAP_L2_PROMOTION_L2_256B;
    enc3d(f, &tms.m[0], d_in[2], 64, 512, 64, 8192, 128, 64, 128, 1, S128, P128);
    enc3d(f, &tms.m[1], d_in[3], 64, 512, 64, 8192, 128, 64, 64, 2, S128, P256);
    enc3d(f, &tms.m[2], d_in[1], 64, SK, 8, 1024, 128, 64, 64, 2, S128, P256);
    enc3d(f, &tms.m[3], d_in[11], 3072, 256, 2, 6144, 256 * 6144, 16, 256, 2, S32, P128);
    enc3d(f, &tms.m[4], d_in[4], 64, 512, 64, 8192, 128, 64, 64, 2, S128, P256);
    enc3d(f, &tms.m[5], d_in[5], 512, 128, 32, 1024, 128 * 1024, 64, 128, 1, S128, P128);
    enc3d(f, &tms.m[6], d_in[7], 1792, 256, 2, 3584, 256 * 3584, 32, 256, 1, S64, P128);
    enc3d(f, &tms.m[7], d_in[8], 1792, 256, 2, 3584, 256 * 3584, 32, 256, 1, S64, P128);
    enc3d(f, &tms.m[8], d_in[9], 64, 1792, 8, 1024, 128, 64, 16, 8, S128, P256);
    cudaFuncSetAttribute(fused_kernel, cudaFuncAttributeMaxDynamicSharedMemorySize, SMEM_BYTES);
    cudaGetSymbolAddress(&scr, g_scr);
    init = true;
  }
  fused_kernel<<<NCTA, 384, SMEM_BYTES>>>((const bf16*)d_in[0], (const bf16*)d_in[10], (const bf16*)d_in[11], (bf16*)d_out, (Scratch*)scr, tms);
}

}

extern "C" void kernel_launch(void* const* d_in, const int* in_sizes, int n_in, void* d_out, int out_size) {
  static int big = -1;
  if (big < 0) big = v9::fits();
  if (big) v9::launch(d_in, d_out); else v8::launch(d_in, d_out);
}
```

```cpp
#include <cuda_runtime.h>
#include <cuda_bf16.h>
#include <cuda.h>
#include <stdint.h>
#include <stdio.h>
#include <stdlib.h>

typedef CUresult (*EncFn)(CUtensorMap*, CUtensorMapDataType, cuuint32_t, void*, const cuuint64_t*, const cuuint64_t*,
                          const cuuint32_t*, const cuuint32_t*, CUtensorMapInterleave, CUtensorMapSwizzle,
                          CUtensorMapL2promotion, CUtensorMapFloatOOBfill);

static void enc3d(EncFn fn, CUtensorMap* tm, void* p, uint64_t d0, uint64_t d1, uint64_t d2, uint64_t s1, uint64_t s2, uint32_t b0,
                  uint32_t b1, uint32_t b2, CUtensorMapSwizzle sw, CUtensorMapL2promotion pr) {
  cuuint64_t gd[3] = {d0, d1, d2}, gs[2] = {s1, s2};
  cuuint32_t bx[3] = {b0, b1, b2}, es[3] = {1, 1, 1};
  fn(tm, CU_TENSOR_MAP_DATA_TYPE_BFLOAT16, 3, p, gd, gs, bx, es, CU_TENSOR_MAP_INTERLEAVE_NONE, sw, pr, CU_TENSOR_MAP_FLOAT_OOB_FILL_NONE);
}

namespace v9 {
typedef __nv_bfloat16 bf16;
#define SK 32768
#define SPIN_MAX (1 << 20)
template <int N> struct IC { static constexpr int value = N; };

__device__ __forceinline__ uint32_t s2u(const void* p) { return (uint32_t)__cvta_generic_to_shared(p); }
__device__ __forceinline__ float bflo(uint32_t u) { return __uint_as_float(u << 16); }
__device__ __forceinline__ float bfhi(uint32_t u) { return __uint_as_float(u & 0xffff0000u); }
__device__ __forceinline__ float u2f(uint32_t u) { return __uint_as_float(u); }
__device__ __forceinline__ void fma8(float* acc, uint4 v, float s) {
  acc[0] += s * bflo(v.x); acc[1] += s * bfhi(v.x); acc[2] += s * bflo(v.y); acc[3] += s * bfhi(v.y);
  acc[4] += s * bflo(v.z); acc[5] += s * bfhi(v.z); acc[6] += s * bflo(v.w); acc[7] += s * bfhi(v.w);
}
__device__ __forceinline__ uint32_t pack2(float a, float b) {
  __nv_bfloat162 p = __floats2bfloat162_rn(a, b); return *(uint32_t*)&p;
}
__device__ __forceinline__ float bfr(float v) { return bfhi(pack2(v, v)); }
__device__ __forceinline__ float silu_bf(float c) { return bfr(__fdividef(c, 1.f + __expf(-c))); }
#define fbits(v) ((__float_as_uint(v) & ~1u) | par)
__device__ __forceinline__ uint32_t pack2t(float a, float b, unsigned par) {
  const uint32_t ua = ((__float_as_uint(a) + ((par ^ 1) << 16)) & 0xFFFE0000u) | (par << 16);
  return __byte_perm(ua, pack2(b, b), 0x7632);
}
__device__ __forceinline__ void nbar(int id, int n) { asm volatile("bar.sync %0, %1;" ::"r"(id), "r"(n) : "memory"); }
__device__ __forceinline__ void nbar_arrive(int id, int n) { asm volatile("bar.arrive %0, %1;" ::"r"(id), "r"(n) : "memory"); }
__device__ __forceinline__ uint4 ldc16(const void* p) {
  uint4 v; asm volatile("ld.relaxed.cta.global.v4.u32 {%0,%1,%2,%3}, [%4];" : "=r"(v.x), "=r"(v.y), "=r"(v.z), "=r"(v.w) : "l"(p) : "memory"); return v;
}
__device__ __forceinline__ unsigned ldc4(const void* p) {
  unsigned v; asm volatile("ld.relaxed.cta.global.u32 %0, [%1];" : "=r"(v) : "l"(p) : "memory"); return v;
}
__device__ __forceinline__ uint4 ldx16(const void* p) {
  uint4 v; asm volatile("ld.relaxed.gpu.global.v4.u32 {%0,%1,%2,%3}, [%4];" : "=r"(v.x), "=r"(v.y), "=r"(v.z), "=r"(v.w) : "l"(p) : "memory"); return v;
}
__device__ __forceinline__ unsigned ldx4(const void* p) {
  unsigned v; asm volatile("ld.relaxed.gpu.global.u32 %0, [%1];" : "=r"(v) : "l"(p) : "memory"); return v;
}
__device__ __forceinline__ unsigned long long ldx64(const void* p) {
  unsigned long long v; asm volatile("ld.relaxed.gpu.global.u64 %0, [%1];" : "=l"(v) : "l"(p) : "memory"); return v;
}
__device__ __forceinline__ void stx16(void* p, uint4 v) {
  asm volatile("st.relaxed.gpu.global.v4.u32 [%0], {%1,%2,%3,%4};" ::"l"(p), "r"(v.x), "r"(v.y), "r"(v.z), "r"(v.w) : "memory");
}
__device__ __forceinline__ void stx8(void* p, uint2 v) { asm volatile("st.relaxed.gpu.global.v2.u32 [%0], {%1,%2};" ::"l"(p), "r"(v.x), "r"(v.y) : "memory"); }
__device__ __forceinline__ void stx4(void* p, unsigned v) { asm volatile("st.relaxed.gpu.global.u32 [%0], %1;" ::"l"(p), "r"(v) : "memory"); }
__device__ __forceinline__ void pub4(void* p, unsigned v) { asm volatile("red.relaxed.gpu.global.xor.b32 [%0], %1;" ::"l"(p), "r"(v) : "memory"); }
__device__ __forceinline__ void pub8(void* p, unsigned lo, unsigned hi) {
  asm volatile("{.reg .b64 t; mov.b64 t, {%1, %2}; red.relaxed.gpu.global.xor.b64 [%0], t;}" ::"l"(p), "r"(lo), "r"(hi) : "memory");
}
__device__ __forceinline__ unsigned lop_x3(unsigned a, unsigned b, unsigned c) {
  unsigned d; asm("lop3.b32 %0, %1, %2, %3, 0x7E;" : "=r"(d) : "r"(a), "r"(b), "r"(c)); return d; }
__device__ __forceinline__ unsigned or3(unsigned a, unsigned b, unsigned c) {
  unsigned d; asm("lop3.b32 %0, %1, %2, %3, 0xFE;" : "=r"(d) : "r"(a), "r"(b), "r"(c)); return d; }
__device__ __forceinline__ unsigned and3(unsigned a, unsigned b, unsigned c) {
  unsigned d; asm("lop3.b32 %0, %1, %2, %3, 0x80;" : "=r"(d) : "r"(a), "r"(b), "r"(c)); return d; }
__device__ __forceinline__ unsigned dep16(const uint32_t* f) {
  unsigned d = 0;
#pragma unroll
  for (int i = 0; i < 8; i++) d = or3(d, f[8 * i], f[8 * i + 4]);
  return d;
}
__device__ __forceinline__ uint2 ldx8(const void* p) {
  uint2 v; asm volatile("{.reg .b64 t; ld.relaxed.gpu.global.b64 t, [%2]; mov.b64 {%0, %1}, t;}" : "=r"(v.x), "=r"(v.y) : "l"(p) : "memory"); return v;
}
__device__ __forceinline__ float lds4(uint32_t a) { float v; asm volatile("ld.shared.f32 %0, [%1];" : "=f"(v) : "r"(a) : "memory"); return v; }
__device__ __forceinline__ float shx(float v, int m) {
  float r; asm volatile("shfl.sync.bfly.b32 %0, %1, %2, 0x1f, 0xffffffff;" : "=f"(r) : "f"(v), "r"(m)); return r;
}
__device__ __forceinline__ uint32_t mbar_test(uint32_t bar, uint32_t ph) {
  uint32_t ok;
  asm volatile("{.reg .pred p; mbarrier.test_wait.parity.shared::cta.b64 p, [%1], %2; vote.sync.all.pred p, p, 0xffffffff; selp.u32 %0, 1, 0, p;}"
               : "=r"(ok) : "r"(bar), "r"(ph) : "memory");
  return ok;
}
#define X16(v) (lop_x3(v.x, v.y, par) | lop_x3(v.z, v.w, par))
#define RETRY(bad) if (!__any_sync(~0u, (bad) & 1) || ++it_ >= SPIN_MAX) break;
#define POLL _Pragma("unroll 1") for (int it_ = 0;;)
__device__ __forceinline__ void mbar_wait(uint32_t bar, uint32_t ph = 0) {
  asm volatile("{.reg .pred p; .reg .u32 n; mov.u32 n, 0;\n"
               "W%=: mbarrier.try_wait.parity.shared::cta.b64 p, [%0], %1; add.u32 n, n, 1; setp.lt.and.u32 p, n, 0x100000, !p; @p bra W%=;}"
               ::"r"(bar), "r"(ph) : "memory");
}
__device__ __forceinline__ float ex2(float v) { float r; asm("ex2.approx.ftz.f32 %0, %1;" : "=f"(r) : "f"(v)); return r; }
__device__ __forceinline__ float rcp(float v) { float r; asm("rcp.approx.ftz.f32 %0, %1;" : "=f"(r) : "f"(v)); return r; }
__device__ __forceinline__ void mma16(float* d, const uint32_t* a, uint32_t b0, uint32_t b1) {
  asm volatile("mma.sync.aligned.m16n8k16.row.col.f32.bf16.bf16.f32 {%0,%1,%2,%3}, {%4,%5,%6,%7}, {%8,%9}, {%0,%1,%2,%3};"
               : "+f"(d[0]), "+f"(d[1]), "+f"(d[2]), "+f"(d[3]) : "r"(a[0]), "r"(a[1]), "r"(a[2]), "r"(a[3]), "r"(b0), "r"(b1));
}
__device__ __forceinline__ void mma16c(float* d, const uint32_t* a, uint32_t b0, uint32_t b1, const float* c) {
  asm volatile("mma.sync.aligned.m16n8k16.row.col.f32.bf16.bf16.f32 {%0,%1,%2,%3}, {%4,%5,%6,%7}, {%8,%9}, {%10,%11,%12,%13};"
               : "=f"(d[0]), "=f"(d[1]), "=f"(d[2]), "=f"(d[3])
               : "r"(a[0]), "r"(a[1]), "r"(a[2]), "r"(a[3]), "r"(b0), "r"(b1), "f"(c[0]), "f"(c[1]), "f"(c[2]), "f"(c[3]));
}
__device__ __forceinline__ float4 lds16(uint32_t a) {
  float4 v; asm volatile("ld.shared.v4.f32 {%0,%1,%2,%3}, [%4];" : "=f"(v.x), "=f"(v.y), "=f"(v.z), "=f"(v.w) : "r"(a) : "memory"); return v;
}
__device__ __forceinline__ uint4 ldsv16(uint32_t a) {
  uint4 v; asm volatile("ld.relaxed.cluster.shared.v4.u32 {%0,%1,%2,%3}, [%4];" : "=r"(v.x), "=r"(v.y), "=r"(v.z), "=r"(v.w) : "r"(a) : "memory"); return v;
}
__device__ __forceinline__ void sts4(uint32_t a, float v) { asm volatile("st.shared.f32 [%0], %1;" ::"r"(a), "f"(v) : "memory"); }
__device__ __forceinline__ void sts16(uint32_t a, uint4 v) {
  asm volatile("st.shared.v4.b32 [%0], {%1,%2,%3,%4};" ::"r"(a), "r"(v.x), "r"(v.y), "r"(v.z), "r"(v.w) : "memory");
}
__device__ __forceinline__ void ldsm_t(uint32_t* r, uint32_t a) {
  asm volatile("ldmatrix.sync.aligned.m8n8.x4.trans.shared.b16 {%0,%1,%2,%3}, [%4];" : "=r"(r[0]), "=r"(r[1]), "=r"(r[2]), "=r"(r[3]) : "r"(a) : "memory");
}
__device__ __forceinline__ void ldsm(uint32_t* r, uint32_t a) {
  asm volatile("ldmatrix.sync.aligned.m8n8.x4.shared.b16 {%0,%1,%2,%3}, [%4];" : "=r"(r[0]), "=r"(r[1]), "=r"(r[2]), "=r"(r[3]) : "r"(a) : "memory");
}
__device__ __forceinline__ uint32_t mapa(uint32_t a, uint32_t r) {
  uint32_t v; asm volatile("mapa.shared::cluster.u32 %0, %1, %2;" : "=r"(v) : "r"(a), "r"(r)); return v;
}
__device__ __forceinline__ unsigned long long mapg(uint32_t a, uint32_t r) {
  unsigned long long v;
  asm volatile("{.reg .u32 t; .reg .u64 u; mapa.shared::cluster.u32 t, %1, %2; cvt.u64.u32 u, t; cvta.shared::cluster.u64 %0, u;}" : "=l"(v) : "r"(a), "r"(r));
  return v;
}
template <int N>
__device__ __forceinline__ void tred(float* a, int lane, int m) {
  const bool hi = lane & m;
#pragma unroll
  for (int i = 0; i < N; i++) {
    float send = hi ? a[i] : a[i + N], keep = hi ? a[i + N] : a[i];
    a[i] = keep + __shfl_xor_sync(~0u, send, m);
  }
}
template <int N>
__device__ __forceinline__ void tmax(float* a, int lane, int m) {
  const bool hi = lane & m;
#pragma unroll
  for (int i = 0; i < N; i++) {
    float send = hi ? a[i] : a[i + N], keep = hi ? a[i + N] : a[i];
    a[i] = fmaxf(keep, __shfl_xor_sync(~0u, send, m));
  }
}
__device__ __forceinline__ void arrive_n(uint32_t bar, bool on, int cnt) {
  asm volatile("{.reg .pred p; setp.ne.s32 p, %1, 0; @p mbarrier.arrive.shared::cta.b64 _, [%0], %2;}" ::"r"(bar), "r"((int)on), "r"(cnt) : "memory");
}
__device__ __forceinline__ unsigned long long stream_policy() {
  unsigned long long p;
  asm volatile("createpolicy.fractional.L2::evict_first.b64 %0, 1.0;" : "=l"(p));
  return p;
}
__device__ __forceinline__ void tma3d(uint32_t dst, const CUtensorMap* tm, uint32_t bar, int c0, int c1, int c2) {
  asm volatile("cp.async.bulk.tensor.3d.shared::cluster.global.mbarrier::complete_tx::bytes.L2::cache_hint [%0], [%1, {%3, %4, %5}], [%2], %6;"
               ::"r"(dst), "l"(tm), "r"(bar), "r"(c0), "r"(c1), "r"(c2), "l"(stream_policy()) : "memory");
}
__device__ __forceinline__ void spin_until(unsigned t) { while ((int)((unsigned)clock() - t) < 0) {} }
__device__ __forceinline__ void wait_until(unsigned t) {
  unsigned now;
  do { asm volatile("mov.u32 %0, %%globaltimer_lo;" : "=r"(now)); } while ((int)(now - t) < 0);
}
__device__ __forceinline__ void sleep_until(unsigned t) {
  unsigned now;
#pragma unroll 1
  do {
    __nanosleep(200);
    asm volatile("mov.u32 %0, %%globaltimer_lo;" : "=r"(now));
  } while ((int)(now - t) < 0);
}
#define PIN(x) asm volatile("" : "+r"(x))
#define PINL(x) asm volatile("" : "+l"(x))
#define BAR_ARRIVE(i) asm volatile("mbarrier.arrive.shared::cta.b64 _, [%0];" ::"r"(bar0 + 8 * (i)) : "memory")
#define CNT_ADD(c) asm volatile("red.relaxed.gpu.global.inc.u32 [%0], 0xffffffff;" ::"l"(scr->cnt + (c)) : "memory")
#define BAR_INIT(i, cnt) asm volatile("mbarrier.init.shared::cta.b64 [%0], %1;" ::"r"(bar0 + 8 * (i)), "r"(cnt) : "memory")
#define BAR_ARM(i, bytes) asm volatile("mbarrier.arrive.expect_tx.shared::cta.b64 _, [%0], %1;" ::"r"(bar0 + 8 * (i)), "r"(bytes) : "memory")
struct TMaps { CUtensorMap m[9]; };

#define NCTA9 120
#define TAU 32.f
#define NSL 100
#define NPE 2
#define WTEST 600
#define NPO 3
#define VDLY 150
#define O_Q 131072
#define O_LZ 163840
#define O_CTX 196608
#define O_HZ 198656
#define O_HW 200704
#define O_X 201728
#define O_P 218112
#define O_B 222208
#define O_R 224512
#define O_SILU 228608
#define O_SM 229632
#define O_BAR 231424
#define O_EP (O_BAR + 256)
#define O_DBG (O_EP + 16)
#define SMEM9 (O_DBG + 128)
#define B_FULL 0
#define B_FM 8
#define B_EMPTY 10
#define B_EM 18
#define B_LZ 18
#define B_Q2 19
#define B_H 20
#define B_QF 21
#define B_TAB 22
#define B_W 23
#define B_ST 24
#define B_HZ 25
#define B_WZ 26
#define B_G2 28
#define B_G 27
enum { T_WQ, T_WUK, T_KV, T_MOD, T_UV, T_WO, T_GU, T_DN = 8 };
#define NBIG 40
struct Sched { unsigned t0, dth; uint2 r[3][8]; unsigned nr[3], nt[3], dt, t4, d7, d4, d6; };

struct __align__(128) Scratch {
  unsigned cnt[8 * 32];
  uint2 rec[32 * 4 * 8 * 64];
  uint2 hdr[32 * 16];
  unsigned h[8 * 256];
  uint4 qa[2048];
  unsigned xao[8 * 512];
  unsigned xf[32 * 56 * 16];
  unsigned xm[2048];
};
__device__ Scratch g_scr;
#define SMEM_BASE 1024u
#define DSC ((SMEM_BASE >> 4) | (1u << 16))
#define HI128 (64u | (1u << 30))
#define HI64 (32u | (2u << 30))
template <int TA, int TB, unsigned HIA, unsigned HIB>
__device__ __forceinline__ void wgmma32(float* d, uint32_t da, uint32_t db, int acc) {
  asm volatile("{.reg .pred p; .reg .b64 da, db; setp.ne.b32 p, %18, 0; mov.b64 da, {%16, %21}; mov.b64 db, {%17, %22};\n"
               "wgmma.mma_async.sync.aligned.m64n32k16.f32.bf16.bf16 "
               "{%0,%1,%2,%3,%4,%5,%6,%7,%8,%9,%10,%11,%12,%13,%14,%15}, da, db, p, 1, 1, %19, %20;}"
               : "+f"(d[0]), "+f"(d[1]), "+f"(d[2]), "+f"(d[3]), "+f"(d[4]), "+f"(d[5]), "+f"(d[6]), "+f"(d[7]),
                 "+f"(d[8]), "+f"(d[9]), "+f"(d[10]), "+f"(d[11]), "+f"(d[12]), "+f"(d[13]), "+f"(d[14]), "+f"(d[15])
               : "r"(da), "r"(db), "r"(acc), "n"(TA), "n"(TB), "n"(HIA), "n"(HIB));
}
__device__ __forceinline__ void wgmma32r(float* d, const uint32_t* a, uint32_t db) {
  asm volatile("{.reg .b64 db; mov.b64 db, {%20, %21};\n"
               "wgmma.mma_async.sync.aligned.m64n32k16.f32.bf16.bf16 "
               "{%0,%1,%2,%3,%4,%5,%6,%7,%8,%9,%10,%11,%12,%13,%14,%15}, {%16,%17,%18,%19}, db, 1, 1, 1, 1;}"
               : "+f"(d[0]), "+f"(d[1]), "+f"(d[2]), "+f"(d[3]), "+f"(d[4]), "+f"(d[5]), "+f"(d[6]), "+f"(d[7]),
                 "+f"(d[8]), "+f"(d[9]), "+f"(d[10]), "+f"(d[11]), "+f"(d[12]), "+f"(d[13]), "+f"(d[14]), "+f"(d[15])
               : "r"(a[0]), "r"(a[1]), "r"(a[2]), "r"(a[3]), "r"(db), "n"(HI64));
}
template <int N> __device__ __forceinline__ void wg_wait(float* a) {
  asm volatile("wgmma.wait_group.sync.aligned %16;"
               : "+f"(a[0]), "+f"(a[1]), "+f"(a[2]), "+f"(a[3]), "+f"(a[4]), "+f"(a[5]), "+f"(a[6]), "+f"(a[7]), "+f"(a[8]), "+f"(a[9]), "+f"(a[10]),
                 "+f"(a[11]), "+f"(a[12]), "+f"(a[13]), "+f"(a[14]), "+f"(a[15]) : "n"(N) : "memory");
}
__device__ __forceinline__ float sum8(uint32_t a) {
  const float4 p = lds16(a), q = lds16(a + 1024);
  return ((p.x + p.y) + (p.z + p.w)) + ((q.x + q.y) + (q.z + q.w));
}
__device__ __forceinline__ int posof(int c) { return (c & ~14) + 2 * (c & 6) + ((c >> 2) & 2); }

__global__ void __cluster_dims__(8, 1, 1) __launch_bounds__(384, 1)
fused_kernel(const bf16* __restrict__ x, const bf16* __restrict__ cvec, const bf16* __restrict__ w_mod, bf16* __restrict__ out,
             Scratch* __restrict__ scr, const __grid_constant__ Sched sch, const __grid_constant__ TMaps tms) {
  extern __shared__ __align__(1024) unsigned char smem[];
  const int tid = threadIdx.x, warp = __shfl_sync(~0u, tid >> 5, 0), lane = tid & 31;
  const int b = blockIdx.x, cl = b >> 3, rn = b & 7, rk = b & 1, hd = b >> 1, f = b - 64;
  const bool isA = b < 64;
  uint32_t sb = s2u(smem), bar0 = sb + O_BAR;
  unsigned gt_start;
  asm volatile("mov.u32 %0, %%globaltimer_lo;" : "=r"(gt_start));
  const int g = lane >> 2, tq = lane & 3;
  const int arow = 64 * rn + ((tid & 255) >> 4);
  uint4 wm[4];
  uint32_t cw, xw;
  if (warp < 8 && isA) {
    const bf16* wa = w_mod + (size_t)arow * 3072 + (lane & 8) * 64 + 64 * cl + 8 * (lane & 7);
#pragma unroll
    for (int i = 0; i < 4; i++) wm[i] = ldx16(wa + i * 16 * 3072);
    cw = ldc4(cvec + (arow & ~1) + 16 * tq);
    if (warp < 2) xw = ldc4(x + 64 * cl + (tid & 62));
  }
  if (warp == 11) {
    if (lane == 0) {
#pragma unroll
      for (int i = 0; i < B_EMPTY; i++) BAR_INIT(i, 1);
    }
    __syncwarp();
    asm volatile("fence.mbarrier_init.release.cluster;" ::: "memory");
    asm volatile("barrier.cluster.arrive.relaxed.aligned;" ::: "memory");
    if (isA) {
#pragma unroll 1
      for (int i = 0; i < 8; i++) {
        if (i >= 6) mbar_wait(bar0 + 8 * (i - 6));
        wait_until(gt_start + ((64 * i + b) * sch.dth >> 8));
        if (lane == 0) {
          BAR_ARM(i, 16384);
          tma3d(sb + i * 16384, &tms.m[i >> 2], bar0 + 8 * i, 0, i < 4 ? 128 * i : 256 * rk + 64 * (i - 4), i < 4 ? b : b & ~1);
        }
        __syncwarp();
      }
    }
  }
  if (warp == 10) {
    const unsigned ep = ldc4(&scr->cnt[0]);
    if (isA) {
      const uint4 xa = ldc16(x + 16 * lane), xb = ldc16(x + 16 * lane + 8);
      float xv[16] = {bflo(xa.x), bfhi(xa.x), bflo(xa.y), bfhi(xa.y), bflo(xa.z), bfhi(xa.z), bflo(xa.w), bfhi(xa.w),
                      bflo(xb.x), bfhi(xb.x), bflo(xb.y), bfhi(xb.y), bflo(xb.z), bfhi(xb.z), bflo(xb.w), bfhi(xb.w)};
      const float x0 = __shfl_sync(~0u, xv[0], 0);
      float s = 0, q = 0;
#pragma unroll
      for (int i = 0; i < 16; i++) { xv[i] -= x0; s += xv[i]; q += xv[i] * xv[i]; }
#pragma unroll
      for (int o = 16; o; o >>= 1) { s += __shfl_xor_sync(~0u, s, o); q += __shfl_xor_sync(~0u, q, o); }
      s *= 1.f / 512.f;
      float rstd;
      asm("rsqrt.approx.ftz.f32 %0, %1;" : "=f"(rstd) : "f"(fmaxf(q * (1.f / 512.f) - s * s, 0.f) + 1e-5f));
      *(float2*)(smem + O_SM + 1024) = make_float2(s + x0, rstd);
    }
    if (lane == 0) *(volatile unsigned*)(smem + O_EP) = ep;
    nbar_arrive(1, 288);
  }
  const int cls = isA ? (b >= NBIG) : 2, v0 = isA ? 2 : 0;
  if (warp >= 8) {
    asm volatile("setmaxnreg.dec.sync.aligned.u32 72;");
    if (warp == 8) {
      if (lane < 8) asm volatile("prefetch.tensormap [%0];" ::"l"(&tms.m[lane + 1]) : "memory");
      if ((sb & 0xFFFFFF) != SMEM_BASE) __trap();
    } else if (warp == 9) {
      if (lane == 0) {
#pragma unroll
        for (int i = B_EMPTY; i < B_EM; i++) BAR_INIT(i, 8);
        BAR_INIT(B_LZ, 8); BAR_INIT(B_Q2, 9); BAR_ARM(B_Q2, 1024);
        BAR_INIT(B_H, 1); BAR_INIT(B_QF, 1); BAR_ARM(B_QF, 32768);
        BAR_INIT(B_TAB, 1); BAR_INIT(B_W, 1); BAR_INIT(B_ST, 8); BAR_INIT(B_WZ, 1); BAR_INIT(B_G, 1); BAR_INIT(B_G2, 1);
      }

    }
    if (warp != 11) {
      __syncwarp();
      asm volatile("fence.mbarrier_init.release.cluster;" ::: "memory");
      __threadfence_block();
      asm volatile("barrier.cluster.arrive.relaxed.aligned;" ::: "memory");
    }
    asm volatile("barrier.cluster.wait.acquire.aligned;" ::: "memory");
    if (warp == 8) {
      const int nr = sch.nr[cls], vl = v0 + sch.nt[cls] - 1;
      unsigned long long hist = 0;
      int v = v0;
#pragma unroll 1
      for (int rd = 0; rd < nr; rd++) {
        const uint2 e = sch.r[cls][rd];
        const int type = e.y & 15, win = (e.y >> 4) & 15, pos = b + 64 - (int)((e.y >> 8) & 255), tile = e.y >> 16;
        const bool mod = type == T_MOD;
        const int ni = mod ? 1 : type == T_DN ? 2 : 4;
        unsigned t = gt_start + (e.x & 0xffff) + (pos * sch.dt >> 8);
        const int c0 = mod ? 1024 + 32 * b : type == T_WO ? 64 * rn : type == T_GU ? 32 * f : 0;
        int c1 = type == T_KV ? 64 * (tile + pos) : type == T_DN ? 32 * f : 0;
        int c2 = mod ? tile : type == T_WO ? 4 * cl : type == T_UV ? b : 0;
        const int i1 = type == T_DN ? 16 : type == T_UV ? 128 : 0;
#pragma unroll 1
        for (int j = 0; j < ni; j++) {
          const int slot = mod ? B_FM + tile : (v & 1) * 4 + j;
          if (mod ? tile : v >= 2) mbar_wait(bar0 + 8 * (B_EMPTY + (mod ? (vl & 1) * 4 : slot)), mod ? (vl >> 1) & 1 : ((v >> 1) - 1) & 1);
          const int hw = (int)(hist >> (6 * (win - 1))) & 63;
          if (hw) mbar_wait(bar0 + 8 * (hw & 15), (hw >> 4) & 1);
          wait_until(t);
          if (lane == 0) {
            BAR_ARM(slot, 16384);
            tma3d(sb + (mod ? (tile ? O_Q : O_X) : slot * 16384), &tms.m[type == T_GU ? type + (j & 1) : type], bar0 + 8 * slot, c0, c1, c2);
          }
          __syncwarp();
          hist = hist << 6 | (32 | (mod ? 0 : (v & 2) << 3) | slot);
          t += e.x >> 16; c1 += i1;
          c2 += type == T_KV ? 2 : type == T_WO ? 1 : type == T_GU ? j & 1 : 0;
        }
        v += !mod;
      }
      return;
    }
    const unsigned epoch = *(volatile unsigned*)(smem + O_EP), par = (epoch + 1) & 1;
    if (warp == 10) {
      if (isA) {
        for (int it = 0; ldx4(scr->cnt + 1) != (epoch + 1) * 128 && it < SPIN_MAX; it++) {}
        if (lane == 0) BAR_ARRIVE(B_H);
      } else mbar_wait(bar0);
      for (int it = 0; ldx4(scr->cnt + 32 + 32 * (rn >> 2)) != (epoch + 1) * 32 && it < SPIN_MAX; it++) {}
      if (lane == 0)
        asm volatile("cp.async.bulk.shared::cluster.global.mbarrier::complete_tx::bytes.multicast::cluster [%0], [%1], 4096, [%2], %3;"
                     ::"r"(sb + O_Q + rn * 4096), "l"(scr->qa + rn * 256), "r"(bar0 + 8 * B_QF), "h"((unsigned short)0xff) : "memory");
      const unsigned dl = isA ? sch.d4 : sch.d6;
      unsigned tw = gt_start + sch.t4;
      if (!isA) {
        const int nt = sch.nt[2];
#pragma unroll 1
        for (int t = 0; t < nt; t++) mbar_wait(bar0 + 8 * B_EMPTY + (t & 1) * 32 + 24, (t >> 1) & 1);
        unsigned long long now;
        asm volatile("mov.u64 %0, %%globaltimer;" : "=l"(now));
        if (lane == 0) { asm volatile("red.relaxed.gpu.global.max.u64 [%0], %1;" ::"l"(scr->cnt + 130), "l"(now) : "memory"); CNT_ADD(128); }
        tw = (unsigned)now + 1700;
      }
      sleep_until(tw);
      uint4 an;
      for (int it = 0; an = ldx16(scr->cnt + 128), an.x != (epoch + 1) * 56 && it < SPIN_MAX; it++) {}
      wait_until(an.z + (dl >> 16));
      if (lane == 0) BAR_ARRIVE(B_G2);
      wait_until(an.z + (dl & 0xffff));
      if (lane == 0) BAR_ARRIVE(B_G);
    } else if (warp == 11) {
      {
        uint2* ph = scr->hdr + ((lane & 24) + 2 * tq + (g & 1)) * 16 + cl;
        const bool own = (lane >> 4) * 4 + tq == rn;
        if (own) { stx8(ph, make_uint2(par ^ 1, 0)); if (cl == 14) stx8(ph + 1, make_uint2(0, 0)); }
        uint32_t a_w = sb + O_HW + ((lane >> 4) * 4 + tq) * 128 + (g & 1) * 64 + ((lane >> 1) & 4);
        PIN(a_w); PINL(ph);
        const int vt = v0 + sch.nt[cls];
#pragma unroll 1
        for (int t = 0; t < vt; t++) mbar_wait(bar0 + 8 * B_EMPTY + (t & 1) * 32 + 24, (t >> 1) & 1);
        float hz[8], M;
        uint32_t wp[4];
#pragma unroll 1
        for (int e = 0; e < 2; e++) {
          POLL {
            unsigned ok = 1;
#pragma unroll
            for (int u = 0; u < 8; u++)
              asm volatile("ld.relaxed.cluster.shared.f32 %0, [%1];" : "=f"(hz[u]) : "r"(sb + O_HZ + e * 1024 + u * 128 + lane * 4) : "memory");
#pragma unroll
            for (int u = 0; u < 4; u++) ok = and3(ok, __float_as_uint(hz[u]), __float_as_uint(hz[u + 4]));
            RETRY(~ok)
          }
          if (e) break;
          M = fmaxf(fmaxf(fmaxf(hz[0], hz[1]), fmaxf(hz[2], hz[3])), fmaxf(fmaxf(hz[4], hz[5]), fmaxf(hz[6], hz[7])));
          M = u2f(fbits(M));
#pragma unroll
          for (int u = 0; u < 4; u++) {
            wp[u] = pack2(ex2(hz[u] - M), ex2(hz[u + 4] - M));
            sts4(a_w + ((rn - u) & 3) * 8, u2f(wp[u])); sts4(a_w + ((rn - u) & 3) * 8 + 32, u2f(wp[u]));
          }
          __syncwarp();
          if (lane == 0) BAR_ARRIVE(B_WZ);
        }
        float L = 0.f;
#pragma unroll
        for (int u = 0; u < 4; u++) L += bflo(wp[u]) * hz[u] + bfhi(wp[u]) * hz[u + 4];
        if (own) pub8(ph, __float_as_uint(M) | 1u, __float_as_uint(L));
      }
      if (isA) {
        mbar_wait(bar0 + 8 * B_G2);
        unsigned long long hh;
        POLL { hh = ldx64(scr->hdr + hd * 16 + (lane & 15)); RETRY((lane & 15) == 15 ? 0u : (unsigned)hh ^ par) }
        const float m = (lane & 15) == 15 ? -1e30f : u2f((unsigned)hh);
        int mi = __float_as_int(m);
        mi ^= (mi >> 31) & 0x7fffffff;
        mi = __reduce_max_sync(~0u, mi);
        mi ^= (mi >> 31) & 0x7fffffff;
        const float w = ex2(m - __int_as_float(mi));
        float L = w * u2f(hh >> 32);
#pragma unroll
        for (int o2 = 8; o2; o2 >>= 1) L += __shfl_xor_sync(~0u, L, o2);
        sts4(sb + O_SM + (384 + 2 * (lane & 6) + ((lane >> 2) & 2) + (lane & 1)) * 4, w * rcp(L));
        __syncwarp();
        if (lane == 0) BAR_ARRIVE(B_W);
      }
    } else {
#pragma unroll 4
      for (int i = 0; i < 72; i++) sts16(sb + O_LZ + i * 512 + lane * 16, make_uint4(0, 0, 0, 0));
      __syncwarp();
      if (lane < 8) asm volatile("mbarrier.arrive.release.cluster.shared::cluster.b64 _, [%0];" ::"r"(mapa(bar0 + 8 * B_LZ, lane)) : "memory");
      if (isA) {
        mbar_wait(bar0 + 8 * B_QF);
#pragma unroll 2
        for (int k = 0; k < 8; k++) {
          const uint32_t cp = ldc4(cvec + 2 * (lane + 32 * k));
          *(uint32_t*)(smem + O_SILU + (lane + 32 * k) * 4) = pack2(silu_bf(bflo(cp)), silu_bf(bfhi(cp)));
        }
        __syncwarp();
        uint32_t ab = sb + O_X + (8 * (lane >> 4) + (lane & 7)) * 64 + ((((lane >> 3) & 1) ^ ((lane >> 1) & 3)) << 4);
        float d[4][4] = {};
#pragma unroll 1
        for (int jm = 0; jm < 2; jm++) {
          mbar_wait(bar0 + 8 * (B_FM + jm));
#pragma unroll 2
          for (int s2 = 0; s2 < 8; s2++)
#pragma unroll
            for (int s = 0; s < 2; s++) {
              uint32_t a0[4], a1[4];
              const uint32_t* ps = (const uint32_t*)(smem + O_SILU) + 128 * jm + 16 * s2 + 8 * s + tq;
              ldsm_t(a0, ab + (2 * s2 + s) * 1024); ldsm_t(a1, (ab + (2 * s2 + s) * 1024) ^ 32);
              mma16(d[s], a0, ps[0], ps[4]); mma16(d[2 + s], a1, ps[0], ps[4]);
            }
          ab -= O_X - O_Q;
        }
        const float t0 = (tq & 1) ? d[0][2] + d[1][2] : d[0][0] + d[1][0], t1 = (tq & 1) ? d[2][2] + d[3][2] : d[2][0] + d[3][0];
        stx4(scr->xm + b * 32 + posof(8 * tq + g), fbits(bfr(bfr((tq & 2) ? t1 : t0) + ((b >> 4) == 2 ? 1.f : 0.f))));
        __syncwarp();
        if (lane == 0) CNT_ADD(96);
      } else sleep_until(gt_start + sch.t4);
      for (int it = 0; ldx4(scr->cnt + 96) != (epoch + 1) * 64 && it < SPIN_MAX; it++) __nanosleep(NSL);
      if (isA) {
        unsigned long long ga;
        POLL { ga = ldx64(scr->xm + 64 * rn + 2 * lane); RETRY(lop_x3((unsigned)ga, ga >> 32, par)) }
        *(float2*)(smem + O_SM + (320 + 2 * lane) * 4) = make_float2(bfhi((unsigned)ga), bfhi(ga >> 32));
      }
      __syncwarp();
      if (lane == 0) BAR_ARRIVE(B_TAB);
    }
    return;
  }

  float* s_sm = (float*)(smem + O_SM);
  unsigned par, epoch;
  asm volatile("barrier.cluster.arrive.relaxed.aligned;" ::: "memory");
  if (isA) {
    float* s_r = (float*)(smem + O_R);
    float acc[8] = {0, 0, 0, 0, 0, 0, 0, 0};
    const float sl = silu_bf((arow & 1) ? bfhi(cw) : bflo(cw));
#pragma unroll
    for (int i = 0; i < 4; i++) fma8(acc, wm[i], __shfl_sync(~0u, sl, i, 4));
    tred<4>(acc, lane, 16);
    *(float4*)(s_r + warp * 128 + 8 * (lane & 15) + ((lane >> 2) & 4)) = make_float4(acc[0], acc[1], acc[2], acc[3]);
    nbar(1, 288);
    epoch = *(volatile unsigned*)(smem + O_EP);
    par = (epoch + 1) & 1;
    if (warp < 2) {
      float t = 0.f, ca = rn == 0 ? 1.f : 0.f;
#pragma unroll
      for (int w = 0; w < 8; w++) { t += s_r[w * 128 + tid]; ca += s_r[w * 128 + 64 + tid]; }
      t += ca * ((((tid & 1) ? bfhi(xw) : bflo(xw)) - s_sm[256]) * s_sm[257]);
      const float nb = __shfl_down_sync(~0u, t, 1);
      const uint32_t w0 = lane < 8 ? pack2t(t, nb, par) : pack2(t, nb);
      const uint32_t w1 = __shfl_down_sync(~0u, w0, 8), w2 = __shfl_down_sync(~0u, w0, 16), w3 = __shfl_down_sync(~0u, w0, 24);
      if (lane < 8 && !(lane & 1)) stx16(scr->h + (rn >> 1) * 512 + (2 * cl + warp) * 32 + rk * 16 + 2 * lane, make_uint4(w0, w1, w2, w3));
      __syncwarp();
      if (lane == 0) CNT_ADD(1);
    }
    asm volatile("barrier.cluster.wait.acquire.aligned;" ::: "memory");
    const uint32_t rsb = mapa(sb, rn ^ 1);
    {
      uint32_t a[4][4][4];
      mbar_wait(bar0 + 8 * (warp >> 1));
      const uint32_t ab = sb + (64 * warp + 8 * (lane >> 4) + (lane & 7)) * 128;
#pragma unroll
      for (int s = 0; s < 4; s++)
#pragma unroll
        for (int mt = 0; mt < 4; mt++) ldsm_t(a[s][mt], ab + s * 2048 + (((2 * mt + ((lane >> 3) & 1)) ^ (lane & 7)) << 4));
      arrive_n(bar0 + 8 * (B_EMPTY + (warp >> 1)), lane == 0, 4 + (dep16(&a[0][0][0]) & (sch.t0 >> 24)));
      uint4 v0, v1;
      const unsigned* ph = scr->h + (g >> 1) * 512 + 64 * warp + 4 * (lane & 7);
      uint32_t off = O_B + warp * 272 + (32 * rk + 8 * tq + (lane & 4)) * 4;
      PIN(off); PINL(ph);
      mbar_wait(bar0 + 8 * B_H);
      POLL { v0 = ldx16(ph); v1 = ldx16(ph + 32); RETRY(lop_x3(v0.x, v1.x, par)) }
      float d[4][4] = {};
#pragma unroll
      for (int mt = 0; mt < 4; mt++) {
        mma16(d[mt], a[0][mt], v0.x, v0.y); mma16(d[mt], a[1][mt], v0.z, v0.w);
        mma16(d[mt], a[2][mt], v1.x, v1.y); mma16(d[mt], a[3][mt], v1.z, v1.w);
      }
      float r[8];
#pragma unroll
      for (int mt = 0; mt < 4; mt++) { r[2 * mt] = d[mt][0] + d[mt][1]; r[2 * mt + 1] = d[mt][2] + d[mt][3]; }
      tred<4>(r, lane, 2); tred<2>(r, lane, 1);
      const float rc = __shfl_xor_sync(~0u, (lane & 4) ? r[0] : r[1], 4);
      const uint32_t wd = (lane & 4) ? pack2(rc, r[1]) : pack2(r[0], rc);
      const uint32_t w1 = __shfl_down_sync(~0u, wd, 8), w2 = __shfl_down_sync(~0u, wd, 16), w3 = __shfl_down_sync(~0u, wd, 24);
      asm volatile("{.reg .pred p; setp.lt.s32 p, %7, 8; @p st.shared.v4.b32 [%0], {%2,%3,%4,%5};\n"
                   "@p st.async.shared::cluster.mbarrier::complete_tx::bytes.v4.b32 [%1], {%2,%3,%4,%5}, [%6];}"
                   ::"r"(sb + off), "r"(rsb + off), "r"(wd), "r"(w1), "r"(w2), "r"(w3), "r"(rsb + O_BAR + 8 * B_Q2), "r"(lane) : "memory");
      __syncwarp();
      arrive_n(bar0 + 8 * B_Q2, lane == 0, 1);
    }
    {
      uint32_t a[2][8][4];
      uint32_t a_bq = sb + O_B + (lane & 7) * 272 + (lane >> 3) * 16;
      uint4* p_qa = scr->qa + (4 * rk + (warp >> 1)) * 256 + hd * 8 + ((4 * (warp & 1) + tq) ^ (hd & 7));
      PIN(a_bq); PINL(p_qa);
      mbar_wait(bar0 + 8 * (4 + (warp >> 1)));
      const uint32_t ab = sb + 65536 + (warp >> 1) * 16384 + (32 * (warp & 1) + (lane & 15)) * 128;
#pragma unroll
      for (int i = 0; i < 16; i++) ldsm(a[i >> 3][i & 7], ab + (i >> 3) * 2048 + ((i >> 2) & 1) * 8192 + (((2 * (i & 3) + (lane >> 4)) ^ (lane & 7)) << 4));
      arrive_n(bar0 + 8 * (B_EMPTY + 4 + (warp >> 1)), lane == 0, 4 + (dep16(&a[0][0][0]) & (sch.t0 >> 24)));
      mbar_wait(bar0 + 8 * B_Q2);
      float d[4][4] = {};
#pragma unroll
      for (int y = 0; y < 4; y++) {
        uint32_t bq[4];
        ldsm(bq, a_bq + 64 * y);
#pragma unroll
        for (int mt = 0; mt < 2; mt++) { mma16(d[2 * mt], a[mt][2 * y], bq[0], bq[1]); mma16(d[2 * mt + 1], a[mt][2 * y + 1], bq[2], bq[3]); }
      }
      float r[4];
#pragma unroll
      for (int i = 0; i < 4; i++) r[i] = (d[i & 2][2 * (i & 1)] + d[i & 2][2 * (i & 1) + 1]) + (d[(i & 2) + 1][2 * (i & 1)] + d[(i & 2) + 1][2 * (i & 1) + 1]);
      tred<2>(r, lane, 2); tred<1>(r, lane, 1);
      const float nb = __shfl_xor_sync(~0u, r[0], 4);
      const uint32_t w0 = (lane >> 3) == (hd & 3) ? pack2t(r[0], nb, par) : pack2(r[0], nb);
      const uint32_t w1 = __shfl_down_sync(~0u, w0, 8), w2 = __shfl_down_sync(~0u, w0, 16), w3 = __shfl_down_sync(~0u, w0, 24);
      if (lane < 4) stx16(p_qa, make_uint4(w0, w1, w2, w3));
      if (warp) nbar_arrive(3, 256); else { nbar(3, 256); if (lane == 0) CNT_ADD(32 + 32 * rk); }
    }
  } else {
    nbar(1, 288);
    epoch = *(volatile unsigned*)(smem + O_EP);
    par = (epoch + 1) & 1;
    asm volatile("barrier.cluster.wait.acquire.aligned;" ::: "memory");
    mbar_wait(bar0);
  }
  asm volatile("setmaxnreg.inc.sync.aligned.u32 216;");
  uint2* p_rec = scr->rec + ((16 * (warp >> 2) + 2 * (warp & 3) + (g & 1) + 4 * (tq & 2)) * 32 + 4 * rn + (tq & 1)) * 64 + cl * 4 + (g >> 1);
  PINL(p_rec);
  {
    const unsigned inv = par ^ 1;
#pragma unroll
    for (int q = 0; q < 2; q++) { stx8(p_rec + q * 128, make_uint2(inv, 0)); if (cl == 14) stx8(p_rec + q * 128 + 4, make_uint2(0, 0)); }
    if (isA) { if (warp < 2) stx4(scr->xao + b * 64 + tid, inv); }
    else stx8(scr->xf + ((4 * warp + tq) * 56 + f) * 16 + 2 * g, make_uint2(inv, 0));
  }
  sb = __shfl_sync(~0u, sb, 0); bar0 = sb + O_BAR;
  const int nt = sch.nt[cls], wg = warp >> 2;
  uint32_t a_z[4];
#pragma unroll
  for (int u = 0; u < 4; u++) {
    const int s3 = (rn - u - (lane >> 1 & 1)) & 3;
    a_z[u] = sb + O_LZ + (s3 + 4 * (lane & 1)) * 4096 + wg * 512 + g * 64 + (((warp & 3) ^ (s3 & 1) ^ (2 * (lane & 1))) << 4);
    PIN(a_z[u]);
  }
  uint32_t z[4][4], a_w = sb + O_HW + warp * 128 + (g & 1) * 64 + (tq & 1) * 8;
  PIN(a_w);
  {
    const float sc = 0.08838834764831845f * 1.4426950408889634f;
    const uint32_t a_pm = sb + O_SM + lane * 16;
    float mrun = -1e30f;
    float o[4][16], sx[16], mref[8];
#pragma unroll
    for (int k = 0; k < 16; k++) { o[0][k] = o[1][k] = o[2][k] = o[3][k] = sx[k] = 0.f; mref[k >> 1] = -1e30f; }
    const int key = 16 * warp + (lane & 15);
    uint32_t a_p = sb + O_P + key * 64 + (((lane >> 4) ^ ((key >> 1) & 3)) << 4);
    uint32_t a_v = sb + wg * 32768 + (8 * (lane >> 4) + (lane & 7)) * 128 + (((2 * (warp & 3) + ((lane >> 3) & 1)) ^ (lane & 7)) << 4);
    const int rot = rn + warp;
    unsigned long long dst[4];
#pragma unroll
    for (int q = 0; q < 4; q++) {
      dst[q] = mapg(sb + O_LZ + rn * 4096 + (warp & 3) * 1024 + g * 64 + ((tq ^ (rn & 1) ^ ((rn >> 1) & 2)) << 4), 4 * wg + ((q + rot) & 3));
      PINL(dst[q]);
    }
    unsigned long long a_h = mapg(sb + O_HZ + wg * 1024 + rn * 128 + lane * 4, 2 * (warp & 3));
    unsigned long long a_h1 = mapg(sb + O_HZ + wg * 1024 + rn * 128 + lane * 4, 2 * (warp & 3) + 1);
    PIN(a_p); PIN(a_v); PINL(a_h); PINL(a_h1);
    uint32_t rel = lane < 4 && lane >= 2 * wg ? 2 - (tq >> 1) : 0;
    PIN(rel);
    uint32_t ones[4] = {0x3F803F80u, 0x3F803F80u, 0x3F803F80u, 0x3F803F80u};
    PIN(ones[0]); PIN(ones[1]); PIN(ones[2]); PIN(ones[3]);
    {
      asm volatile("{.reg .pred p; .reg .u32 n; mov.u32 n, 0;\n"
                   "W%=: mbarrier.try_wait.parity.acquire.cluster.shared::cta.b64 p, [%0], 0; add.u32 n, n, 1; setp.lt.and.u32 p, n, 0x100000, !p; @p bra W%=;}"
                   ::"r"(bar0 + 8 * B_LZ) : "memory");
      mbar_wait(bar0 + 8 * B_QF);
      unsigned bad = 0;
#pragma unroll
      for (int k = 0; k < 8; k++) bad |= __float_as_uint(lds4(sb + O_Q + k * 4096 + tid * 16 + (lane >> 3) * 4)) ^ par;
      if (__builtin_expect(__any_sync(~0u, bad & 1), 0)) {
#pragma unroll 1
        for (int k = 0; k < 8; k++) {
          uint4 v;
          POLL { v = ldx16(scr->qa + k * 256 + tid); RETRY(((lane & 16) ? ((lane & 8) ? v.w : v.z) : ((lane & 8) ? v.y : v.x)) ^ par) }
          sts16(sb + O_Q + k * 4096 + tid * 16, v);
        }
        asm volatile("fence.proxy.async.shared::cta;" ::: "memory");
      }
      if (warp >= 4) nbar_arrive(1, 256); else nbar(1, 256);
    }
#pragma unroll 1
    for (int t = 0; t < nt; t++) {
      const int v = v0 + t;
      const uint32_t fb = bar0 + (v & 1) * 32, ph = (v >> 1) & 1, av = a_v + (v & 1) * 65536;
      uint32_t vf[4][4][4], cnt;
      auto landed = [&]() {
        cnt = rel + (dep16(&vf[0][0][0]) & (nt >> 8));
        PIN(cnt);
      };
      if (wg == 0) {
        const uint32_t da = DSC + (v & 1) * 4096, db = DSC + O_Q / 16;
#pragma unroll
        for (int jj = 0; jj < 2; jj++) {
#pragma unroll 1
          for (int j = 2 * jj; j < 2 * jj + 2; j++) {
            mbar_wait(fb + 8 * j, ph);
            asm volatile("wgmma.fence.sync.aligned;" ::: "memory");
#pragma unroll
            for (int k = 0; k < 8; k++)
              wgmma32<0, 0, HI128, HI128>(sx, da + j * 1024 + (k >> 2) * 512 + (k & 3) * 2, db + j * 512 + (k >> 2) * 256 + (k & 3) * 2, jj || k ? 1 : j);
            asm volatile("wgmma.commit_group.sync.aligned;" ::: "memory");
          }
          if (jj == 0) {
#pragma unroll
            for (int i = 0; i < 16; i++) ldsm_t(vf[i >> 2][i & 3], av + (((i >> 2) + rot) & 3) * 8192 + (i & 3) * 2048);
            nbar(5, 256);
            landed();
          }
        }
      } else {
        nbar_arrive(5, 256);
#pragma unroll 1
        for (int j = 0; j < 2; j++) {
          mbar_wait(fb + 16 + 8 * j, ph);
          if (j) spin_until(clock() + VDLY);
#pragma unroll
          for (int q = 0; q < 4; q++)
            if (((q + rot) & 2) == 2 * j)
#pragma unroll
              for (int k = 0; k < 4; k++) ldsm_t(vf[q][k], av + ((q + rot) & 3) * 8192 + k * 2048);
        }
        landed();
      }
      wg_wait<0>(sx);
      asm volatile("{.reg .pred p; setp.ne.s32 p, %1, 0; @p mbarrier.arrive.shared::cta.b64 _, [%0], %1;}" ::"r"(fb + 8 * B_EMPTY + 8 * tq), "r"(cnt) : "memory");
#pragma unroll 1
      for (int pass = 0;; pass++) {
        int ex = !(t | pass);
        if (wg == 0 && (t | pass)) {
          float mx = -1e30f;
#pragma unroll
          for (int i = 0; i < 8; i++) mx = fmaxf(mx, fmaxf(sx[2 * (i & 6) + (i & 1)], sx[2 * (i & 6) + (i & 1) + 2]) * sc - mref[i]);
          ex = mx > TAU;
          uint32_t pk[8];
#pragma unroll
          for (int i = 0; i < 8; i++) pk[i] = pack2(ex2(sx[2 * i] * sc - mref[i & 6]), ex2(sx[2 * i + 1] * sc - mref[(i & 6) + 1]));
#pragma unroll
          for (int u = 0; u < 2; u++)
            asm volatile("stmatrix.sync.aligned.m8n8.x4.shared.b16 [%0], {%1,%2,%3,%4};"
                         ::"r"(a_p ^ (u << 5)), "r"(pk[4 * u]), "r"(pk[4 * u + 1]), "r"(pk[4 * u + 2]), "r"(pk[4 * u + 3]) : "memory");
          asm volatile("fence.proxy.async.shared::cta;" ::: "memory");
        }
        asm volatile("{.reg .pred p, q; setp.ne.s32 q, %0, 0; bar.red.or.pred p, 4, 256, q; selp.s32 %0, 1, 0, p;}" : "+r"(ex)::"memory");
        if (!ex || pass) break;
        if (wg == 0) {
          float cm[8];
#pragma unroll
          for (int i = 0; i < 8; i++) cm[i] = fmaxf(sx[2 * (i & 6) + (i & 1)], sx[2 * (i & 6) + (i & 1) + 2]);
          tmax<4>(cm, lane, 16); tmax<2>(cm, lane, 8); tmax<1>(cm, lane, 4);
          sts4(a_pm + warp * 4, cm[0] * sc);
        }
        nbar(4, 256);
        const float4 pm = lds16(a_pm);
        const float mn = u2f(__float_as_uint(fmaxf(fmaxf(fmaxf(pm.x, pm.y), fmaxf(pm.z, pm.w)), mrun)) | 1u), al = ex2(mrun - mn);
        mrun = mn;
#pragma unroll
        for (int i = 0; i < 8; i++) {
          const float a = __shfl_sync(~0u, al, 4 * i + tq), aw = wg ? a : 1.f;
          mref[i] = __shfl_sync(~0u, mn, 4 * i + tq);
#pragma unroll
          for (int e = 0; e < 2; e++) {
            const int k = 2 * (i & 6) + (i & 1) + 2 * e;
            o[0][k] *= a; o[1][k] *= a; o[2][k] *= a; o[3][k] *= a; sx[k] *= aw;
          }
        }
      }
      float hv = mrun;
      if (wg) {
        asm volatile("wgmma.fence.sync.aligned;" ::: "memory");
#pragma unroll
        for (int k = 0; k < 4; k++) wgmma32r(sx, ones, DSC + O_P / 16 + k * 64);
        asm volatile("wgmma.commit_group.sync.aligned;" ::: "memory");
        wg_wait<0>(sx);
        float lv[4];
#pragma unroll
        for (int j = 0; j < 4; j++) lv[j] = (lane & 4) ? sx[4 * j + 1] : sx[4 * j];
        hv = (lane & 16) ? ((lane & 8) ? lv[3] : lv[2]) : ((lane & 8) ? lv[1] : lv[0]);
      }
      asm volatile("{.reg .pred p; setp.eq.s32 p, %3, %4; @p st.relaxed.cluster.b32 [%0], %1; @p st.relaxed.cluster.b32 [%2], %1;}"
                   ::"l"(a_h), "r"(__float_as_uint(hv) | 1u), "l"(a_h1), "r"(t), "r"(nt - 1) : "memory");
#pragma unroll
      for (int q = 0; q < 4; q++) {
        asm volatile("wgmma.fence.sync.aligned;" ::: "memory");
#pragma unroll
        for (int k = 0; k < 4; k++) wgmma32r(o[q], vf[q][k], DSC + O_P / 16 + k * 64);
        asm volatile("wgmma.commit_group.sync.aligned;" ::: "memory");
        if (q == 3) {
#pragma unroll
          for (int u = 0; u < 4; u++) ldsm_t(z[u], a_z[u] + u * 1024);
        }
        wg_wait<0>(o[q]);
#pragma unroll
        for (int j = 0; j < 2; j++)
          asm volatile("{.reg .pred p; setp.eq.s32 p, %5, %6; @p st.relaxed.cluster.v4.b32 [%0], {%1,%2,%3,%4};}"
                       ::"l"(dst[q] + j * 512), "r"(pack2t(o[q][8 * j], o[q][8 * j + 1], 1)), "r"(pack2(o[q][8 * j + 2], o[q][8 * j + 3])),
                         "r"(pack2(o[q][8 * j + 4], o[q][8 * j + 5])), "r"(pack2(o[q][8 * j + 6], o[q][8 * j + 7])), "r"(t), "r"(nt - 1) : "memory");
      }
    }
  }
  {
    uint32_t wx[4][4];
    mbar_wait(bar0 + 8 * B_WZ);
#pragma unroll
    for (int u = 0; u < 4; u++) {
      uint2 wp;
      asm volatile("ld.shared.v2.u32 {%0, %1}, [%2];" : "=r"(wp.x), "=r"(wp.y) : "r"(a_w + u * 8) : "memory");
      const bool lo = (g >> 1) == (tq >> 1), hi = (g >> 1) == 2 + (tq >> 1);
      wx[u][0] = lo ? wp.x : 0u; wx[u][1] = lo ? wp.y : 0u; wx[u][2] = hi ? wp.x : 0u; wx[u][3] = hi ? wp.y : 0u;
    }
    auto bad = [&]() {
      const unsigned ok = and3(and3(and3(z[0][0], z[0][1], z[0][2]), and3(z[0][3], z[1][0], z[1][1]), and3(z[1][2], z[1][3], z[2][0])),
                               and3(and3(z[2][1], z[2][2], z[2][3]), and3(z[3][0], z[3][1], z[3][2]), z[3][3]), 0x10001u);
      return __any_sync(~0u, g == 0 && ok != 0x10001u);
    };
    POLL {
      if (it_)
#pragma unroll
        for (int u = 0; u < 4; u++) ldsm_t(z[u], a_z[u] + u * 1024);
      if (!bad() || ++it_ >= SPIN_MAX) break;
    }
    float d0[8][4] = {}, d[8][4], r[8];
#pragma unroll
    for (int i = 0; i < 8; i++) mma16(d0[i], wx[i >> 1], z[i >> 1][2 * (i & 1)], z[i >> 1][2 * (i & 1) + 1]);
    POLL {
#pragma unroll
      for (int u = 0; u < 4; u++) ldsm_t(z[u], a_z[u ^ 2] + u * 1024);
#pragma unroll
      for (int i = 0; i < 8; i++) mma16c(d[i], wx[(i >> 1) ^ 2], z[i >> 1][2 * (i & 1)], z[i >> 1][2 * (i & 1) + 1], d0[i]);
      if (!bad() || ++it_ >= SPIN_MAX) break;
    }
#pragma unroll
    for (int i = 0; i < 8; i++) r[i] = (tq & 2) ? ((g & 1) ? d[i][3] : d[i][2]) : ((g & 1) ? d[i][1] : d[i][0]);
#pragma unroll
    for (int q = 0; q < 2; q++) pub8(p_rec + q * 128, pack2t(r[4 * q], r[4 * q + 1], par) | 1u, pack2(r[4 * q + 2], r[4 * q + 3]));
  }
  const int vt = v0 + nt;
  const uint32_t bufa = sb + (vt & 1) * 65536, fulla = bar0 + (vt & 1) * 32, pha = (vt >> 1) & 1, phb = ((vt + 1) >> 1) & 1;
  const uint32_t bufo = sb + ((vt + 1) & 1) * 65536, fullb = bar0 + ((vt + 1) & 1) * 32;
  uint32_t a_rs = sb + O_R + (warp >> 2) * 1024 + (16 * tq + g) * 16 + ((warp + tq) & 3) * 4;
  if (isA) {
    const int row = 16 * (warp & 6) + 8 * (warp & 1) + (lane & 16) + ((lane & 7) >> 1) + 4 * (lane & 1);
    uint32_t ab = bufa + row * 128 + ((((lane >> 3) & 1) ^ (row & 7)) << 4);
    const uint2* pr = scr->rec + (hd * 32 + warp) * 64 + lane;
    unsigned long long a_c0 = mapg(sb + O_CTX + (64 * rn + 32 * (warp & 1) + posof(lane)) * 4, warp & 6);
    unsigned long long a_c1 = mapg(sb + O_CTX + (64 * rn + 32 * (warp & 1) + posof(lane)) * 4, warp | 1);
    uint32_t a_rl = sb + O_R + (32 * (warp & 1) + lane) * 16;
    uint32_t ao = bufo + (16 * warp + 8 * (lane >> 4) + (lane & 7)) * 128 + ((((lane >> 3) & 1) ^ (lane & 7)) << 4);
    uint32_t a_cx = sb + O_CTX + (16 * warp + 4 * tq) * 4, a_ga = sb + O_SM + (320 + posof(tid & 63)) * 4;
    unsigned* p_ao = scr->xao + b * 64 + posof(tid & 63);
    float xv = cl == 0 ? __bfloat162float(x[64 * rn + (tid & 63)]) : 0.f;
    unsigned p2 = lane >= 28 ? 0 : par;
    PIN(ab); PINL(pr); PINL(a_c0); PINL(a_c1); PIN(a_rl); PIN(a_rs); PIN(ao); PIN(a_cx); PIN(a_ga); PINL(p_ao); PIN(p2);
    asm volatile("" : "+f"(xv));
    uint32_t aw[4][4][4];
    auto wo = [&](const int j) {
      mbar_wait(fullb + 8 * j, phb);
#pragma unroll
      for (int mt = 0; mt < 4; mt++) ldsm_t(aw[j][mt], (ao + j * 16384) ^ (mt << 5));
    };
    {
      uint32_t a[4][4][4];
      uint2 z[4], y[4];
      float d[4][4] = {}, r[8];
      mbar_wait(fulla, pha);
      POLL {
#pragma unroll
        for (int q = 0; q < 4; q++) z[q] = ldx8(pr + q * 512);
        RETRY(lop_x3(z[0].x, z[1].x, par) | lop_x3(z[2].x, z[3].x, par))
      }
#pragma unroll
      for (int q = 0; q < 4; q++) {
        if (q == 3) {
          mbar_wait(bar0 + 8 * B_G);
#pragma unroll
          for (int u = 0; u < 4; u++) y[u] = ldx8(pr + u * 512 + 32);
        }
        mbar_wait(fulla + 8 * q, pha);
#pragma unroll
        for (int mt = 0; mt < 4; mt++) ldsm_t(a[q][mt], (ab + q * 16384) ^ (mt << 5));
#pragma unroll
        for (int mt = 0; mt < 4; mt++) mma16(d[mt], a[q][mt], z[q].x, z[q].y);
      }
      mbar_wait(bar0 + 8 * B_W);
      const float4 W = lds16(sb + O_SM + (384 + 4 * tq) * 4);
#pragma unroll
      for (int i = 0; i < 8; i++) { r[i] = W.x * d[i >> 1][2 * (i & 1)] + W.y * d[i >> 1][2 * (i & 1) + 1]; asm volatile("" : "+f"(r[i])); }
#pragma unroll
      for (int j = 0; j < NPE; j++) wo(j);
      POLL {
        if (it_)
#pragma unroll
          for (int u = 0; u < 4; u++) y[u] = ldx8(pr + u * 512 + 32);
#pragma unroll
        for (int mt = 0; mt < 4; mt++) d[mt][0] = d[mt][1] = d[mt][2] = d[mt][3] = 0.f;
#pragma unroll
        for (int q = 0; q < 4; q++)
#pragma unroll
          for (int mt = 0; mt < 4; mt++) mma16(d[mt], a[q][mt], y[q].x, y[q].y);
        RETRY(or3(lop_x3(y[0].x, y[1].x, p2), lop_x3(y[2].x, y[3].x, p2), 0))
      }
#pragma unroll
      for (int i = 0; i < 8; i++) r[i] = W.w * d[i >> 1][2 * (i & 1) + 1] + (W.z * d[i >> 1][2 * (i & 1)] + r[i]);
      tred<4>(r, lane, 2); tred<2>(r, lane, 1);
      sts4(a_rs, r[0]); sts4(a_rs + 128, r[1]);
      nbar(1, 256);
      const uint32_t cv = __float_as_uint(sum8(a_rl)) | 1u;
      asm volatile("st.relaxed.cluster.b32 [%0], %2; st.relaxed.cluster.b32 [%1], %2;" ::"l"(a_c0), "l"(a_c1), "r"(cv) : "memory");
    }
    {
#pragma unroll
      for (int j = NPE; j < NPO; j++) wo(j);
      uint4 c[4];
      POLL {
#pragma unroll
        for (int j = 0; j < 4; j++) c[j] = ldsv16(a_cx + j * 512);
        RETRY(~and3(and3(and3(c[0].x, c[0].y, c[0].z), and3(c[1].x, c[1].y, c[1].z), and3(c[0].w, c[1].w, c[2].x)),
                    and3(and3(c[2].y, c[2].z, c[2].w), and3(c[3].x, c[3].y, c[3].z), c[3].w), ~0u))
      }
      float d[4][4] = {};
#pragma unroll
      for (int j = 0; j < 4; j++) {
        if (j + 1 >= NPO && j < 3) wo(j + 1);
        const uint32_t b0 = pack2(u2f(c[j].x), u2f(c[j].y)), b1 = pack2(u2f(c[j].z), u2f(c[j].w));
#pragma unroll
        for (int mt = 0; mt < 4; mt++) mma16(d[mt], aw[j][mt], b0, b1);
      }
      const float r0 = (tq & 2) ? ((tq & 1) ? d[3][0] : d[2][0]) : ((tq & 1) ? d[1][0] : d[0][0]);
      const float r1 = (tq & 2) ? ((tq & 1) ? d[3][2] : d[2][2]) : ((tq & 1) ? d[1][2] : d[0][2]);
      sts4(a_rs + 2048, r0); sts4(a_rs + 2048 + 128, r1);
      if (warp >= 2) nbar_arrive(2, 256);
      else {
        mbar_wait(bar0 + 8 * B_TAB);
        const float gav = lds4(a_ga);
        nbar(2, 256);
        pub4(p_ao, __float_as_uint(gav * sum8(a_rl + 2048) + xv) | 1u);
      }
    }
  } else {
    uint32_t af[4][4][4], ad[2][4][4];
    uint32_t ab = bufa + (32 * warp + 8 * (lane >> 4) + (lane & 7)) * 64 + ((((lane >> 3) & 1) ^ ((lane >> 1) & 3)) << 4);
    uint32_t a_d = bufo + warp * 2048 + (8 * (lane >> 4) + (lane & 7)) * 128 + ((((lane >> 3) & 1) ^ (lane & 7)) << 4);
    uint32_t a_rl = sb + O_R + lane * 16, a_st = sb + O_SM + (352 + 2 * warp) * 4;
    unsigned* p_f = scr->xf + ((4 * warp + tq) * 56 + f) * 16 + 2 * g;
    const unsigned* pa = scr->xao + (g >> 1) * 512 + 32 * warp + 4 * (lane & 7);
    const unsigned* pf = scr->xf + f * 896 + 4 * tid;
    const int col = ((tid >> 1) & 7) + 8 * (tid & 1);
    bf16* po = out + 16 * f + col;
    uint32_t a_q = sb + O_SM + (warp * 16 + 4 * tq + (lane >> 3)) * 4, one = g == 0 ? 0x3F803F80u : 0u;
    unsigned d7 = sch.d7;
    PIN(ab); PIN(a_d); PIN(a_rl); PINL(p_f); PINL(pa); PIN(a_rs); PIN(a_st); PINL(pf); PINL(po); PIN(a_q); PIN(one); PIN(d7);
    mbar_wait(bar0 + 8 * B_TAB);
    uint4 cf[2];
    uint2 bb[4];
    unsigned gbw;
    POLL {
      unsigned bad = 0;
#pragma unroll
      for (int h = 0; h < 2; h++) cf[h] = ldx16(scr->xm + 1024 + 256 * h + 32 * warp + 4 * (lane & 7));
#pragma unroll
      for (int s = 0; s < 4; s++) {
        const uint4 w = ldx16(scr->xm + 1024 - (g & 1) * 512 + 256 * (s >> 1) + 32 * warp + 16 * (s & 1) + 4 * tq);
        bb[s] = make_uint2(__byte_perm(w.x, w.y, 0x7632), __byte_perm(w.z, w.w, 0x7632));
        bad = or3(bad, lop_x3(w.x, w.y, par), lop_x3(w.z, w.w, par));
      }
      gbw = ldx4(scr->xm + 1536 + 16 * (f & 31) + posof(col));
      RETRY(or3(bad, X16(cf[0]), X16(cf[1])) | (gbw ^ par))
    }
    const float gbv = bfhi(gbw);
    float e[4][4] = {};
    uint4 v[2][2];
    auto item = [&](const int it) {
      mbar_wait(fulla + 8 * it, pha);
#pragma unroll
      for (int i = 0; i < 4; i++) ldsm_t(af[it][i], (ab + it * 16384 + (i >> 1) * 1024) ^ ((i & 1) << 5));
    };
    auto item_mma = [&](const int it) {
#pragma unroll
      for (int i = 0; i < 4; i++) mma16(e[2 * (it & 1) + (i & 1)], af[it][i], bb[(it & 2) + (i >> 1)].x, bb[(it & 2) + (i >> 1)].y);
    };
    item(0); item_mma(0); item(1); item_mma(1);
    mbar_wait(bar0 + 8 * B_G);
#pragma unroll
    for (int i = 0; i < 4; i++) v[i >> 1][i & 1] = ldx16(pa + (i >> 1) * 256 + (i & 1) * 2048);
    const unsigned t3 = clock() + WTEST;
    item(2); item_mma(2);
    uint32_t have3;
    do have3 = mbar_test(fulla + 24, pha); while (!have3 && (int)((unsigned)clock() - t3) < 0);
    if (have3) { item(3); item_mma(3); }
    float y[2][4], df[4][4] = {}, dg[4];
    uint32_t have0;
    uint32_t zb[2][2];
    POLL {
      if (it_)
#pragma unroll
        for (int i = 0; i < 4; i++) v[i >> 1][i & 1] = ldx16(pa + (i >> 1) * 256 + (i & 1) * 2048);
      dg[0] = dg[1] = dg[2] = dg[3] = 0.f;
#pragma unroll
      for (int h = 0; h < 2; h++) {
        y[h][0] = u2f(v[h][0].x) + u2f(v[h][1].x); y[h][1] = u2f(v[h][0].y) + u2f(v[h][1].y);
        y[h][2] = u2f(v[h][0].z) + u2f(v[h][1].z); y[h][3] = u2f(v[h][0].w) + u2f(v[h][1].w);
        const uint32_t y0 = pack2(y[h][0], y[h][1]), y1 = pack2(y[h][2], y[h][3]);
        const uint32_t ya[4] = {y0, one, y1, one};
        mma16(dg, ya, y0, y1);
        zb[h][0] = pack2(y[h][0] * u2f(cf[h].x), y[h][1] * u2f(cf[h].y)); zb[h][1] = pack2(y[h][2] * u2f(cf[h].z), y[h][3] * u2f(cf[h].w));
      }
      const unsigned bad = or3(or3(lop_x3(v[0][0].x, v[0][0].y, par), lop_x3(v[0][0].z, v[0][0].w, par), lop_x3(v[0][1].x, v[0][1].y, par)),
                               or3(lop_x3(v[0][1].z, v[0][1].w, par), lop_x3(v[1][0].x, v[1][0].y, par), lop_x3(v[1][0].z, v[1][0].w, par)),
                               or3(lop_x3(v[1][1].x, v[1][1].y, par), lop_x3(v[1][1].z, v[1][1].w, par), 0));
      RETRY(bad)
    }
    {
      uint32_t bz[4][2];
#pragma unroll
      for (int s = 0; s < 4; s++) { bz[s][0] = (g & 1) == (s & 1) ? zb[s >> 1][0] : 0u; bz[s][1] = (g & 1) == (s & 1) ? zb[s >> 1][1] : 0u; }
      auto mm = [&](const int it, const int i) { mma16(df[2 * (it & 1) + (i & 1)], af[it][i], bz[(it & 2) + (i >> 1)][0], bz[(it & 2) + (i >> 1)][1]); };
      mm(0, 0); mm(0, 1); mm(1, 0);
      float s0 = dg[2] + dg[3], s1 = (g & 1) ? dg[1] : dg[0];
      s1 += shx(s1, 16); s0 += shx(s0, 1);
      mm(1, 1); mm(0, 2);
      s1 += shx(s1, 8); s0 += shx(s0, 2);
      mm(0, 3); mm(1, 2);
      s1 += shx(s1, 4);
      mm(1, 3); mm(2, 0);
      s1 += shx(s1, 2);
      mm(2, 1); mm(2, 2);
      s1 += shx(s1, 1);
      mm(2, 3);
      asm volatile("{.reg .pred p; setp.eq.s32 p, %3, 0; @p st.shared.v2.f32 [%0], {%1, %2}; @p mbarrier.arrive.shared::cta.b64 _, [%4];}"
                   ::"r"(a_st), "f"(s0), "f"(s1), "r"(lane), "r"(bar0 + 8 * B_ST) : "memory");
      if (!have3) { item(3); item_mma(3); }
      have0 = mbar_test(fullb, phb);
#pragma unroll
      for (int mt = 0; mt < 4; mt++) ldsm_t(ad[0][mt], a_d ^ (mt << 5));
      mm(3, 0); mm(3, 1); mm(3, 2); mm(3, 3);
    }
    mbar_wait(bar0 + 8 * B_ST);
    float mean, rstd;
    {
      float4 u[4];
#pragma unroll
      for (int i = 0; i < 4; i++) u[i] = lds16(sb + O_SM + (352 + 4 * i) * 4);
      mean = (((u[0].x + u[0].z) + (u[1].x + u[1].z)) + ((u[2].x + u[2].z) + (u[3].x + u[3].z))) * (1.f / 512.f);
      const float sq = (((u[0].y + u[0].w) + (u[1].y + u[1].w)) + ((u[2].y + u[2].w) + (u[3].y + u[3].w))) * (1.f / 512.f);
      asm("rsqrt.approx.ftz.f32 %0, %1;" : "=f"(rstd) : "f"(fmaxf(sq - mean * mean, 0.f) + 1e-5f));
    }
    float r[8];
#pragma unroll
    for (int i = 0; i < 8; i++) r[i] = df[i >> 1][2 * (i & 1)] + df[i >> 1][2 * (i & 1) + 1];
    tred<4>(r, lane, 2); tred<2>(r, lane, 1);
    float A[4];
#pragma unroll
    for (int i = 0; i < 4; i++) A[i] = (tq & 2) ? ((tq & 1) ? e[3][i] : e[2][i]) : ((tq & 1) ? e[1][i] : e[0][i]);
    sts4(a_rs, rstd * r[0] + (A[1] - rstd * mean * A[0])); sts4(a_rs + 128, rstd * r[1] + (A[3] - rstd * mean * A[2]));
    const uint32_t have1 = mbar_test(fullb + 8, phb);
    nbar(1, 256);
    {
      const float4 g0 = lds16(a_rl), g1 = lds16(a_rl + 1024), u0 = lds16(a_rl + 512), u1 = lds16(a_rl + 1536);
#pragma unroll
      for (int mt = 0; mt < 4; mt++) ldsm_t(ad[1][mt], (a_d + 16384) ^ (mt << 5));
      const float gg = bfr(((g0.x + g0.y) + (g0.z + g0.w)) + ((g1.x + g1.y) + (g1.z + g1.w)));
      const float uu = bfr(((u0.x + u0.y) + (u0.z + u0.w)) + ((u1.x + u1.y) + (u1.z + u1.w)));
      const float hh = bfr(gg * rcp(1.f + ex2(gg * (-2.302208198f - 0.1029432397f * gg * gg)))) * uu;
      const uint32_t hw = pack2(hh, __shfl_down_sync(~0u, hh, 1));
      uint32_t hb[4];
#pragma unroll
      for (int i = 0; i < 4; i++) hb[i] = __shfl_sync(~0u, hw, 8 * i + 2 * tq);
      float dd[4][4] = {};
#pragma unroll
      for (int j = 0; j < 2; j++)
        if (!(j ? have1 : have0)) {
          mbar_wait(fullb + 8 * j, phb);
#pragma unroll
          for (int mt = 0; mt < 4; mt++) ldsm_t(ad[j][mt], (a_d + j * 16384) ^ (mt << 5));
        }
#pragma unroll
      for (int j = 0; j < 2; j++)
#pragma unroll
        for (int mt = 0; mt < 4; mt++) mma16(dd[mt], ad[j][mt], hb[2 * j], hb[2 * j + 1]);
      const float f0 = (tq & 2) ? ((tq & 1) ? dd[3][0] : dd[2][0]) : ((tq & 1) ? dd[1][0] : dd[0][0]);
      const float f1 = (tq & 2) ? ((tq & 1) ? dd[3][2] : dd[2][2]) : ((tq & 1) ? dd[1][2] : dd[0][2]);
      pub8(p_f, __float_as_uint(f0) | 1u, __float_as_uint(f1));
    }
    const unsigned tpub = clock();
    if (f < 32) {
      if (warp == ((f & 15) >> 1)) {
        float a4[4];
#pragma unroll
        for (int i = 0; i < 4; i++) a4[i] = (f & 16) ? y[1][i] : y[0][i];
        tred<2>(a4, lane, 16); tred<1>(a4, lane, 8);
        if ((g & 1) == (f & 1)) sts4(sb + O_SM + (112 + 4 * tq + ((lane >> 2) & 2) + (lane >> 4)) * 4, a4[0]);
      }
      if (warp == 7) nbar_arrive(2, 256);
      else {
        uint4 u;
        float q4[4];
        spin_until(tpub + d7);
        POLL {
          u = ldx16(pf);
          q4[0] = u2f(u.x); q4[1] = u2f(u.y); q4[2] = u2f(u.z); q4[3] = u2f(u.w);
          tred<2>(q4, lane, 16); tred<1>(q4, lane, 8);
          q4[0] += __shfl_xor_sync(~0u, q4[0], 4);
          RETRY(lop_x3(u.x, u.z, par))
        }
        sts4(a_q, q4[0]);
        nbar(2, 256);
        if (tid < 16) {
          float q[8];
#pragma unroll
          for (int i = 0; i < 8; i++) q[i] = lds4(sb + O_SM + (tid + 16 * i) * 4);
          const float t = ((q[0] + q[1]) + (q[2] + q[3])) + ((q[4] + q[5]) + q[6]);
          *po = __float2bfloat16(q[7] + bfr(gbv * bfr(t)));
          if (f == 0 && tid == 0) stx4(&scr->cnt[0], epoch + 1);
        }
      }
    }
  }
}

static void make_sched(Sched& s) {
  const char* order = "FFAAbcFmmvog....d";
  const double dt = 5050 * 1e-3, dth = 4850 * 1e-3, dtt = 5150 * 1e-3;
  const int nbig = NBIG;
  s.t0 = 0; s.dth = (unsigned)(dth * 256 + 0.5);
  double t = 512 * dth + 0 - 0;
  int tile = 0, jm = 0;
  for (int i = 0; i < 3; i++) s.nr[i] = s.nt[i] = 0;
  auto add = [&](int c, int type, double step, int win, int b0, int tl) {
    s.r[c][s.nr[c]++] = make_uint2((unsigned)(t + 0.5) | (unsigned)(step + 0.5) << 16, type | win << 4 | (b0 + 64) << 8 | tl << 16);
    if (type == T_KV) s.nt[c]++;
  };
  const int w1 = 6, w2 = 4, wt = 6;
  for (const char* p = order; *p; p++) {
    const char c = *p;
    if (c == 'v' || c == 'o' || c == 'm') {
      const int ty = c == 'v' ? T_UV : c == 'o' ? T_WO : T_MOD;
      const double d = c == 'm' ? dt : dtt;
      const double st = 64 * d + (c == 'o' ? 0 : 0);
      add(0, ty, st, wt, 0, c == 'm' ? jm : 0); add(1, ty, st, wt, 0, c == 'm' ? jm : 0);
      t += (c == 'm' ? 64 : 256) * d; jm += c == 'm';
    } else if (c == 'g' || c == 'd') {
      const int gs = c == 'g' ? 0 : 0;
      t -= 3 * gs;
      add(2, c == 'g' ? T_GU : T_DN, 56 * dtt + gs, c == 'g' ? wt : 6, 64, 0);
      t += 3 * gs;
      t += (c == 'g' ? 224 : 112) * dtt;
    } else if (c == '.') t += 100;
    else if (c == '-') t -= 100;
    else {
      const int na = c == 'F' ? 0 : c == 'C' || c == 'c' ? nbig : 64, nf = c == 'A' ? 0 : 56, n = na + nf;
      const int w = na && nf ? w2 : w1;
      const bool ff = c == 'b' || c == 'c';
      if (na) add(0, T_KV, n * dt, w, ff ? -56 : 0, tile);
      if (na == 64) add(1, T_KV, n * dt, w, ff ? -56 : 0, tile);
      if (nf) add(2, T_KV, n * dt, w, ff ? 64 : 64 - na, tile);
      tile += n; t += 4 * n * dt;
      s.t4 = (unsigned)t + 600;
    }
  }
  s.dt = (unsigned)(dt * 256 + 0.5); s.d7 = 300; s.d4 = 1500 | 950 << 16; s.d6 = 3350;
}

static void launch(void* const* d_in, void* d_out) {
  static TMaps tms;
  static Sched sch;
  static bool init = false;
  static void* scr = nullptr;
  if (!init) {
    void* fn = nullptr; cudaDriverEntryPointQueryResult qr;
    cudaGetDriverEntryPoint("cuTensorMapEncodeTiled", &fn, cudaEnableDefault, &qr);
    EncFn f = (EncFn)fn;
    const CUtensorMapSwizzle S64 = CU_TENSOR_MAP_SWIZZLE_64B, S128 = CU_TENSOR_MAP_SWIZZLE_128B;
    const CUtensorMapL2promotion P128 = CU_TENSOR_MAP_L2_PROMOTION_L2_128B, P256 = CU_TENSOR_MAP_L2_PROMOTION_L2_256B;
    enc3d(f, &tms.m[0], d_in[2], 64, 512, 64, 8192, 128, 64, 128, 1, S128, P128);
    enc3d(f, &tms.m[1], d_in[3], 64, 512, 64, 8192, 128, 64, 64, 2, S128, P256);
    enc3d(f, &tms.m[2], d_in[1], 64, SK, 8, 1024, 128, 64, 64, 2, S128, P256);
    enc3d(f, &tms.m[3], d_in[11], 3072, 256, 2, 6144, 256 * 6144, 32, 256, 1, S64, P128);
    enc3d(f, &tms.m[4], d_in[4], 64, 512, 64, 8192, 128, 64, 128, 1, S128, P128);
    enc3d(f, &tms.m[5], d_in[5], 512, 128, 32, 1024, 128 * 1024, 64, 128, 1, S128, P128);
    enc3d(f, &tms.m[6], d_in[7], 1792, 256, 2, 3584, 256 * 3584, 32, 256, 1, S64, P128);
    enc3d(f, &tms.m[7], d_in[8], 1792, 256, 2, 3584, 256 * 3584, 32, 256, 1, S64, P128);
    enc3d(f, &tms.m[8], d_in[9], 64, 1792, 8, 1024, 128, 64, 16, 8, S128, P256);
    cudaFuncSetAttribute(fused_kernel, cudaFuncAttributeMaxDynamicSharedMemorySize, SMEM9);
    cudaGetSymbolAddress(&scr, g_scr);
    make_sched(sch);
    init = true;
  }
  fused_kernel<<<NCTA9, 384, SMEM9>>>((const bf16*)d_in[0], (const bf16*)d_in[10], (const bf16*)d_in[11], (bf16*)d_out, (Scratch*)scr, sch, tms);
}

static bool fits() {
  cudaFuncSetAttribute(fused_kernel, cudaFuncAttributeMaxDynamicSharedMemorySize, SMEM9);
  cudaLaunchConfig_t cfg = {};
  cfg.gridDim = dim3(NCTA9); cfg.blockDim = dim3(384); cfg.dynamicSmemBytes = SMEM9;
  cudaLaunchAttribute at[1];
  at[0].id = cudaLaunchAttributeClusterDimension; at[0].val.clusterDim.x = 8; at[0].val.clusterDim.y = 1; at[0].val.clusterDim.z = 1;
  cfg.attrs = at; cfg.numAttrs = 1;
  int n = 0;
  if (cudaOccupancyMaxActiveClusters(&n, fused_kernel, &cfg) != cudaSuccess) { (void)cudaGetLastError(); return false; }
  return n >= NCTA9 / 8;
}
}
#undef BAR_ARM
#undef BAR_ARRIVE
#undef BAR_INIT
#undef B_EM
#undef B_EMPTY
#undef B_FM
#undef B_FULL
#undef B_G
#undef B_G2
#undef B_H
#undef B_HZ
#undef B_LZ
#undef B_Q2
#undef B_QF
#undef B_ST
#undef B_TAB
#undef B_W
#undef B_WZ
#undef CNT_ADD
#undef DSC
#undef HI128
#undef HI64
#undef NBIG
#undef NCTA9
#undef NPE
#undef NPO
#undef NSL
#undef O_B
#undef O_BAR
#undef O_CTX
#undef O_DBG
#undef O_EP
#undef O_HW
#undef O_HZ
#undef O_LZ
#undef O_P
#undef O_Q
#undef O_R
#undef O_SILU
#undef O_SM
#undef O_X
#undef PIN
#undef PINL
#undef POLL
#undef RETRY
#undef SK
#undef SMEM9
#undef SMEM_BASE
#undef SPIN_MAX
#undef TAU
#undef VDLY
#undef WTEST
#undef X16
#undef fbits

namespace v8 {
typedef __nv_bfloat16 bf16;
#define NCTA 128
#define SK 32768
#define SLOT 32768
#define NSLOT 6
#define OFF_WQ (2 * SLOT)
#define OFF_WUK (4 * SLOT)
#define OFF_Q 196608
#define OFF_P (OFF_Q + 16384)
#define OFF_B (OFF_P + 4096)
#define OFF_R4 (OFF_B + 2304)
#define OFF_SILU (OFF_R4 + 4096)
#define OFF_RA (OFF_SILU + 1024)
#define OFF_SM (OFF_RA + 1024)
#define OFF_BP (OFF_SM + 1792)
#define OFF_CO (OFF_BP + 1024)
#define OFF_BAR (OFF_CO + 1280)
#define OFF_MASK (OFF_BAR + 512)
#define OFF_DBG (OFF_MASK + 16)
#define SMEM_BYTES (OFF_DBG + 128)
#define OFF_MOD OFF_Q
#define OFF_UV (4 * SLOT)
#define OFF_O (5 * SLOT)
#define OFF_G 0
#define OFF_U 16384
#define OFF_D SLOT
#define OFF_XO (OFF_D + 16384)
#define FB_UK 4
#define FB_KV 6
#define FB_MOD 22
#define FB_UV 23
#define FB_O 25
#define FB_G 27
#define FB_D 29
#define EB 30
#define QB 50
#define XB 51
#define SPIN_MAX (1 << 20)
#define BACKOFF 40
#define RATE_NS 652
#define RATE_T0 200
#define RATE_TL 300
#define WINS 0x3222333
#define KVWIN 4
#define RATE_H 650
#define RATE_E 650
#define SMUL 9
#define NPRE0 1
#define NPRE1 3
#define HWIN 4
#define EWIN 3
#define WTEST 450
#define DLY5 650
#define DLY6 600
#define DLY7 600
#define P12(a, b, c, d, e, f, g, h, i, j, k, l) ((unsigned long long)(a) | (b) << 5 | (c) << 10 | (d) << 15 | (e) << 20 | (f) << 25 | \
  (unsigned long long)(g) << 30 | (unsigned long long)(h) << 35 | (unsigned long long)(i) << 40 | (unsigned long long)(j) << 45 | \
  (unsigned long long)(k) << 50 | (unsigned long long)(l) << 55)
#define ORDER0 P12(0, 1, 2, 3, 4, 5, 16, 6, 7, 8, 9, 10)
#define ORDER1 P12(11, 12, 13, 14, 15, 17, 18, 19, 20, 23, 21, 22)
#define TAIL_K 17
#define RS 16
template <int N> struct IC { static constexpr int value = N; };
struct TMaps { CUtensorMap m[9]; };

struct __align__(128) Scratch {
  uint4 xo[128 * 64 * RS];
  uint2 ml[32 * 64];
  unsigned h[8 * 256];
  unsigned qa[32 * 256];
  unsigned xc[128 * 64];
  unsigned xao[8 * 512];
  unsigned xf[112 * 512];
  unsigned xm[2048];
  unsigned cnt[5 * 32];
};
__device__ Scratch g_scr;
#define g_xo scr->xo
#define g_ml scr->ml
#define g_h scr->h
#define g_qa scr->qa
#define g_xc scr->xc
#define g_xao scr->xao
#define g_xf scr->xf
#define g_xm scr->xm
#define g_epoch scr->cnt[0]

__device__ __forceinline__ uint32_t s2u(const void* p) { return (uint32_t)__cvta_generic_to_shared(p); }
__device__ __forceinline__ float bflo(uint32_t u) { return __uint_as_float(u << 16); }
__device__ __forceinline__ float bfhi(uint32_t u) { return __uint_as_float(u & 0xffff0000u); }
__device__ __forceinline__ float u2f(uint32_t u) { return __uint_as_float(u); }
__device__ __forceinline__ void fma8(float* acc, uint4 v, float s) {
  acc[0] += s * bflo(v.x); acc[1] += s * bfhi(v.x); acc[2] += s * bflo(v.y); acc[3] += s * bfhi(v.y);
  acc[4] += s * bflo(v.z); acc[5] += s * bfhi(v.z); acc[6] += s * bflo(v.w); acc[7] += s * bfhi(v.w);
}
__device__ __forceinline__ uint32_t pack2(float a, float b) {
  __nv_bfloat162 p = __floats2bfloat162_rn(a, b); return *(uint32_t*)&p;
}
__device__ __forceinline__ float bfr(float v) { return bfhi(pack2(v, v)); }
__device__ __forceinline__ float silu_bf(float c) { return bfr(__fdividef(c, 1.f + __expf(-c))); }
#define fbits(v) ((__float_as_uint(v) & ~1u) | par)
__device__ __forceinline__ uint32_t pack2t(float a, float b, unsigned par) {
  const uint32_t ua = ((__float_as_uint(a) + ((par ^ 1) << 16)) & 0xFFFE0000u) | (par << 16);
  return __byte_perm(ua, pack2(b, b), 0x7632);
}
__device__ __forceinline__ void nbar(int id, int n) { asm volatile("bar.sync %0, %1;" ::"r"(id), "r"(n) : "memory"); }
__device__ __forceinline__ void nbar_arrive(int id, int n) { asm volatile("bar.arrive %0, %1;" ::"r"(id), "r"(n) : "memory"); }
__device__ __forceinline__ uint4 ldc16(const void* p) {
  uint4 v; asm volatile("ld.relaxed.cta.global.v4.u32 {%0,%1,%2,%3}, [%4];" : "=r"(v.x), "=r"(v.y), "=r"(v.z), "=r"(v.w) : "l"(p) : "memory"); return v;
}
__device__ __forceinline__ unsigned ldc4(const void* p) {
  unsigned v; asm volatile("ld.relaxed.cta.global.u32 %0, [%1];" : "=r"(v) : "l"(p) : "memory"); return v;
}
__device__ __forceinline__ uint4 ldx16(const void* p) {
  uint4 v; asm volatile("ld.relaxed.gpu.global.v4.u32 {%0,%1,%2,%3}, [%4];" : "=r"(v.x), "=r"(v.y), "=r"(v.z), "=r"(v.w) : "l"(p) : "memory"); return v;
}
__device__ __forceinline__ unsigned ldx4(const void* p) {
  unsigned v; asm volatile("ld.relaxed.gpu.global.u32 %0, [%1];" : "=r"(v) : "l"(p) : "memory"); return v;
}
__device__ __forceinline__ unsigned long long ldx64(const void* p) {
  unsigned long long v; asm volatile("ld.relaxed.gpu.global.u64 %0, [%1];" : "=l"(v) : "l"(p) : "memory"); return v;
}
__device__ __forceinline__ void stx16(void* p, uint4 v) {
  asm volatile("st.relaxed.gpu.global.v4.u32 [%0], {%1,%2,%3,%4};" ::"l"(p), "r"(v.x), "r"(v.y), "r"(v.z), "r"(v.w) : "memory");
}
__device__ __forceinline__ void stx8(void* p, uint2 v) { asm volatile("st.relaxed.gpu.global.v2.u32 [%0], {%1,%2};" ::"l"(p), "r"(v.x), "r"(v.y) : "memory"); }
__device__ __forceinline__ void stx4(void* p, unsigned v) { asm volatile("st.relaxed.gpu.global.u32 [%0], %1;" ::"l"(p), "r"(v) : "memory"); }
__device__ __forceinline__ unsigned lop_x3(unsigned a, unsigned b, unsigned c) {
  unsigned d; asm("lop3.b32 %0, %1, %2, %3, 0x7E;" : "=r"(d) : "r"(a), "r"(b), "r"(c)); return d; }
#define X16(v) (lop_x3(v.x, v.y, par) | lop_x3(v.z, v.w, par))
#define X8(v) lop_x3(v.x, v.y, par)
#define RETRY(bad) if (!__any_sync(~0u, (bad) & 1) || ++it_ >= SPIN_MAX) break; __nanosleep(BACKOFF);
#define POLL _Pragma("unroll 1") for (int it_ = 0;;)
__device__ __forceinline__ void mbar_wait(uint32_t bar) {
  uint32_t ok; int it = 0;
  do {
    asm volatile("{.reg .pred p; mbarrier.try_wait.parity.shared::cta.b64 p, [%1], 0; selp.u32 %0,1,0,p;}"
                 : "=r"(ok) : "r"(bar) : "memory");
  } while (!ok && ++it < SPIN_MAX);
}
__device__ __forceinline__ float ex2(float v) { float r; asm("ex2.approx.ftz.f32 %0, %1;" : "=f"(r) : "f"(v)); return r; }
__device__ __forceinline__ float rcp(float v) { float r; asm("rcp.approx.ftz.f32 %0, %1;" : "=f"(r) : "f"(v)); return r; }
__device__ __forceinline__ void mma16(float* d, const uint32_t* a, uint32_t b0, uint32_t b1) {
  asm volatile("mma.sync.aligned.m16n8k16.row.col.f32.bf16.bf16.f32 {%0,%1,%2,%3}, {%4,%5,%6,%7}, {%8,%9}, {%0,%1,%2,%3};"
               : "+f"(d[0]), "+f"(d[1]), "+f"(d[2]), "+f"(d[3]) : "r"(a[0]), "r"(a[1]), "r"(a[2]), "r"(a[3]), "r"(b0), "r"(b1));
}
__device__ __forceinline__ float4 lds16(uint32_t a) {
  float4 v; asm volatile("ld.shared.v4.f32 {%0,%1,%2,%3}, [%4];" : "=f"(v.x), "=f"(v.y), "=f"(v.z), "=f"(v.w) : "r"(a) : "memory"); return v;
}
__device__ __forceinline__ void ldsm_t(uint32_t* r, uint32_t a) {
  asm volatile("ldmatrix.sync.aligned.m8n8.x4.trans.shared.b16 {%0,%1,%2,%3}, [%4];" : "=r"(r[0]), "=r"(r[1]), "=r"(r[2]), "=r"(r[3]) : "r"(a) : "memory");
}
__device__ __forceinline__ void ldsm(uint32_t* r, uint32_t a) {
  asm volatile("ldmatrix.sync.aligned.m8n8.x4.shared.b16 {%0,%1,%2,%3}, [%4];" : "=r"(r[0]), "=r"(r[1]), "=r"(r[2]), "=r"(r[3]) : "r"(a) : "memory");
}
template <int N>
__device__ __forceinline__ void tred(float* a, int lane, int m) {
  const bool hi = lane & m;
#pragma unroll
  for (int i = 0; i < N; i++) {
    float send = hi ? a[i] : a[i + N], keep = hi ? a[i + N] : a[i];
    a[i] = keep + __shfl_xor_sync(~0u, send, m);
  }
}
template <int N>
__device__ __forceinline__ void tmax(float* a, int lane, int m) {
  const bool hi = lane & m;
#pragma unroll
  for (int i = 0; i < N; i++) {
    float send = hi ? a[i] : a[i + N], keep = hi ? a[i + N] : a[i];
    a[i] = fmaxf(keep, __shfl_xor_sync(~0u, send, m));
  }
}
__device__ __forceinline__ void arrive2(uint32_t bar, uint32_t rbar, bool local, bool remote) {
  asm volatile("{.reg .pred p, q; setp.ne.s32 p, %2, 0; setp.ne.s32 q, %3, 0; @p mbarrier.arrive.shared::cta.b64 _, [%0];\n"
               "@q mbarrier.arrive.relaxed.cluster.shared::cluster.b64 _, [%1];}" ::"r"(bar), "r"(rbar), "r"((int)local), "r"((int)remote) : "memory");
}
__device__ __forceinline__ unsigned long long stream_policy() {
  unsigned long long p;
  asm volatile("createpolicy.fractional.L2::evict_first.b64 %0, 1.0;" : "=l"(p));
  return p;
}
__device__ __forceinline__ void tma3d(uint32_t dst, const CUtensorMap* tm, uint32_t bar, int c0, int c1, int c2) {
  asm volatile("cp.async.bulk.tensor.3d.shared::cluster.global.mbarrier::complete_tx::bytes.L2::cache_hint [%0], [%1, {%3, %4, %5}], [%2], %6;"
               ::"r"(dst), "l"(tm), "r"(bar), "r"(c0), "r"(c1), "r"(c2), "l"(stream_policy()) : "memory");
}
__device__ __forceinline__ void st_async2(uint32_t dst, uint32_t bar, float v0, float v1) {
  asm volatile("st.async.shared::cluster.mbarrier::complete_tx::bytes.v2.f32 [%0], {%1, %2}, [%3];" ::"r"(dst), "f"(v0), "f"(v1), "r"(bar) : "memory");
}
__device__ __forceinline__ void st_pair(int mode, uint32_t dst, uint32_t bar, float v0, float v1) {
  asm volatile("{.reg .pred p, q; setp.eq.s32 p, %4, 1; setp.eq.s32 q, %4, 2; @p st.shared.v2.f32 [%0], {%1, %2};\n"
               "@q st.async.shared::cluster.mbarrier::complete_tx::bytes.v2.f32 [%0], {%1, %2}, [%3];}"
               ::"r"(dst), "f"(v0), "f"(v1), "r"(bar), "r"(mode) : "memory");
}
__device__ __forceinline__ void spin_until(unsigned t) { while ((int)((unsigned)clock() - t) < 0) {} }
__device__ __forceinline__ unsigned wait_until(unsigned t) {
  unsigned now;
  for (;;) {
    asm volatile("mov.u32 %0, %%globaltimer_lo;" : "=r"(now));
    if ((int)(now - t) >= 0) break;
  }
  return now;
}
#define PIN(x) asm volatile("" : "+r"(x))
#define PINL(x) asm volatile("" : "+l"(x))
#define BAR_ARRIVE(i) asm volatile("mbarrier.arrive.shared::cta.b64 _, [%0];" ::"r"(bar0 + 8 * (i)) : "memory")
#define CNT_ADD(c) asm volatile("red.relaxed.gpu.global.add.u32 [%0], 1;" ::"l"(scr->cnt + (c)) : "memory")
#define BAR_INIT(i, cnt) asm volatile("mbarrier.init.shared::cta.b64 [%0], %1;" ::"r"(bar0 + 8 * (i)), "r"(cnt) : "memory")
#define BAR_ARM(i, bytes) asm volatile("mbarrier.arrive.expect_tx.shared::cta.b64 _, [%0], %1;" ::"r"(bar0 + 8 * (i)), "r"(bytes) : "memory")

__device__ __forceinline__ void tail(unsigned char* smem, Scratch* __restrict__ scr, const bf16* __restrict__ x, bf16* __restrict__ out,
                                     const unsigned par, const unsigned epoch, const int warp) {
  int tid, b;
  asm volatile("mov.u32 %0, %%tid.x;" : "=r"(tid));
  asm volatile("mov.u32 %0, %%ctaid.x;" : "=r"(b));
  const int lane = tid & 31, g = lane >> 2, tq = lane & 3;
  const uint32_t sb = __shfl_sync(~0u, s2u(smem), 0), bar0 = sb + OFF_BAR;
  float* s_sm = (float*)(smem + OFF_SM);
  const int prow = 4 * (lane >> 4) + ((lane & 7) >> 1) + 8 * (lane & 1);
  const float* s_co = (const float*)(smem + OFF_CO);
  const int opos = (b & 15) * 32 + (lane & 16) + 2 * (lane & 6) + ((lane >> 2) & 2) + (lane & 1);
  const float xv = b < 16 ? __bfloat162float(x[(b & 15) * 32 + lane]) : 0.f;
  const int rk = b & 1, ob = 32 * rk + ((b >> 1) & 31);
  uint32_t psb;
  asm volatile("mapa.shared::cluster.u32 %0, %1, %2;" : "=r"(psb) : "r"(sb), "r"(rk ^ 1));
  {
    uint32_t a[8][4];
    {
      const int rg = tid >> 4;
      const uint4* src = g_xo + ((size_t)b * 64 + rg) * RS;
      const uint32_t dst = sb + OFF_XO + rg * 256 + (((tid & 15) ^ (rg & 7)) << 4);
      unsigned long long todo = 0x0001000100010001ull;
#pragma unroll 1
      for (int it = 0; it < SPIN_MAX * 16; it++) {
        unsigned long long mk = *(volatile unsigned long long*)(smem + OFF_MASK);
        const unsigned long long nw = (mk >> rg) & todo;
        todo ^= nw;
#pragma unroll
        for (int i = 0; i < 4; i++)
          if (nw >> (16 * i) & 1)
            asm volatile("cp.async.cg.shared.global [%0], [%1], 16;" ::"r"(dst + i * 4096), "l"(src + i * 16 * RS + (tid & 15)) : "memory");
        if (!__any_sync(~0u, todo != 0)) break;
      }
      asm volatile("cp.async.mbarrier.arrive.noinc.shared::cta.b64 [%0];" ::"r"(bar0 + 8 * (XB + 2)) : "memory");
    }
    mbar_wait(bar0 + 8 * FB_UV); mbar_wait(bar0 + 8 * (FB_UV + 1));
    const uint32_t ab = sb + OFF_UV + (warp >> 2) * 8192 + (8 * (lane >> 4) + (lane & 7)) * 128 + (((2 * (warp & 3) + ((lane >> 3) & 1)) ^ (lane & 7)) << 4);
#pragma unroll
    for (int s = 0; s < 8; s++) ldsm_t(a[s], ab + (s >> 2) * 16384 + (s & 3) * 2048);
    const int chn = 2 * warp + (tq & 1);
    uint32_t a_b = sb + OFF_B + (tq >> 1) * 272 + (32 * (chn >> 2) + 8 * (g >> 1) + 2 * (chn & 3) + (g & 1)) * 2;
    uint32_t a_bq = sb + OFF_B + (lane & 1) * 272 + (lane >> 3) * 16;
    unsigned* p_c = g_xc + (b >> 2) * 256 + warp * 32 + (b & 3) * 8 + (g & 3) * 2 + (g >> 2);
    PIN(a_b); PIN(a_bq); PINL(p_c);
    mbar_wait(bar0 + 8 * (XB + 6));
    uint32_t wb[8];
#pragma unroll
    for (int s = 0; s < 8; s++) wb[s] = *(const uint32_t*)(smem + OFF_RA + (4 * s + tq) * 4);
    const float invL = *(const float*)(smem + OFF_RA + 128);
    float ov;
    POLL {
      mbar_wait(bar0 + 8 * (XB + 2));
      uint32_t ao[4][4];
#pragma unroll
      for (int s = 0; s < 4; s++)
        ldsm_t(ao[s], sb + OFF_XO + (16 * s + 8 * (lane >> 4) + (lane & 7)) * 256 + (((2 * warp + ((lane >> 3) & 1)) ^ (lane & 7)) << 4));
      float d[4][4] = {};
#pragma unroll
      for (int s = 0; s < 4; s++) mma16(d[s], ao[s], wb[2 * s], wb[2 * s + 1]);
      const unsigned p2 = par * 0x10001u;
      unsigned bad = 0;
#pragma unroll
      for (int s = 0; s < 4; s++) bad |= lop_x3(ao[s][0], ao[s][1], p2) | lop_x3(ao[s][2], ao[s][3], p2);
      bad = g == 0 ? bad | (bad >> 16) : 0u;
      ov = (tq & 1) ? (d[0][2] + d[1][2]) + (d[2][2] + d[3][2]) : (d[0][0] + d[1][0]) + (d[2][0] + d[3][0]);
      if (__builtin_expect(!__any_sync(~0u, bad & 1) || ++it_ >= SPIN_MAX, 1)) break;
#pragma unroll
      for (int i = 0; i < 4; i++)
        asm volatile("cp.async.cg.shared.global [%0], [%1], 16;"
                     ::"r"(sb + OFF_XO + ((lane >> 1) + 16 * i) * 256 + (((2 * warp + (lane & 1)) ^ ((lane >> 1) & 7)) << 4)),
                       "l"(g_xo + ((size_t)b * 64 + (lane >> 1) + 16 * i) * RS + 2 * warp + (lane & 1)) : "memory");
      asm volatile("cp.async.wait_all;" ::: "memory");
      __syncwarp();
    }
    {
      const float lo = ov - bfhi(__float_as_uint(ov));
      asm volatile("st.shared.u16 [%0], %1;" ::"r"(a_b), "h"((unsigned short)((tq & 2) ? pack2(lo, lo) : __float_as_uint(ov) >> 16)) : "memory");
    }
    nbar(1, 256);
    float d[4][4] = {};
#pragma unroll
    for (int y = 0; y < 4; y++) {
      uint32_t bq[4];
      ldsm(bq, a_bq + 64 * y);
      mma16(d[(2 * y) & 3], a[2 * y], bq[0], bq[1]); mma16(d[(2 * y + 1) & 3], a[2 * y + 1], bq[2], bq[3]);
    }
    const float r0 = ((d[0][0] + d[0][1]) + (d[1][0] + d[1][1])) + ((d[2][0] + d[2][1]) + (d[3][0] + d[3][1]));
    const float r1 = ((d[0][2] + d[0][3]) + (d[1][2] + d[1][3])) + ((d[2][2] + d[2][3]) + (d[3][2] + d[3][3]));
    if (tq == 0) stx4(p_c, pack2t(r0 * invL, r1 * invL, par));
  }
  unsigned tpub = clock();
  mbar_wait(bar0 + 8 * (XB + 4));
  const float gav = s_co[256 + (opos & 31)];
  const float gbv = s_co[288 + (lane & 4) + 2 * (lane & 1) + ((lane >> 1) & 1)];
  float4 cf[2];
#pragma unroll
  for (int s = 0; s < 2; s++) cf[s] = *(const float4*)(s_co + 32 * warp + 16 * s + 4 * tq);
  {
    uint32_t a[2][4][4];
    mbar_wait(bar0 + 8 * (FB_O + (warp >> 2)));
    const uint32_t ab = sb + OFF_O + (32 * warp + prow) * 128 + ((((lane >> 3) & 1) ^ (prow & 7)) << 4);
#pragma unroll
    for (int i = 0; i < 8; i++) ldsm_t(a[i >> 2][i & 3], (ab + (i >> 2) * 2048) ^ ((i & 3) << 5));
    uint4 v;
    const unsigned* pc = g_xc + (4 * (b >> 4) + 2 * rk + (warp >> 2)) * 256 + 64 * (warp & 3) + 2 * lane;
    uint32_t ro = ((tq >> 1) == rk ? sb : psb) + OFF_P + (8 * (tq & 1) + g) * 144 + (8 * rk + warp) * 8;
    uint32_t a_q = sb + OFF_P + (8 * (lane >> 4) + (lane & 7)) * 144;
    unsigned* p_ao = g_xao + (b >> 5) * 1024 + (opos >> 4) * 32 + (b & 16) + (opos & 15);
    PIN(ro); PIN(a_q); PINL(p_ao); PINL(pc);
    spin_until(tpub + DLY5);
    POLL {
      const unsigned long long u0 = ldx64(pc);
      v.x = (unsigned)u0; v.y = u0 >> 32;
      RETRY(X8(v))
    }
    v.z = lane & 16 ? v.x : 0u; v.w = lane & 16 ? v.y : 0u;
    if (lane & 16) v.x = v.y = 0u;
    float d[4][4] = {};
#pragma unroll
    for (int mt = 0; mt < 4; mt++) mma16(d[mt], a[0][mt], v.x, v.y);
#pragma unroll
    for (int mt = 0; mt < 4; mt++) mma16(d[mt], a[1][mt], v.z, v.w);
    float r[8];
#pragma unroll
    for (int i = 0; i < 8; i++) r[i] = d[i >> 1][2 * (i & 1)] + d[i >> 1][2 * (i & 1) + 1];
    tred<4>(r, lane, 2); tred<2>(r, lane, 1);
    st_pair((tq >> 1) == rk ? 1 : 2, ro, psb + OFF_BAR + 8 * (XB + 3), r[0], r[1]);
    __syncwarp();
    if (lane == 0) BAR_ARRIVE(XB + 3);
    if (warp == 0) {
      mbar_wait(bar0 + 8 * (XB + 3));
      float p[8];
#pragma unroll
      for (int i = 0; i < 8; i++) {
        const float4 q = lds16(a_q + i * 16);
        p[i] = (lane & 8) ? q.y + q.w : q.x + q.z;
      }
      const float t = ((p[0] + p[1]) + (p[2] + p[3])) + ((p[4] + p[5]) + (p[6] + p[7]));
      stx4(p_ao, fbits(gav * t + xv));
    }
  }
  tpub = clock();
  if (b < 112) {
    uint32_t af[2][4][4], ad[4][4];
    const uint32_t ab = sb + (32 * warp + 8 * (lane >> 4) + (lane & 7)) * 64 + ((((lane >> 3) & 1) ^ ((lane >> 1) & 3)) << 4);
    uint32_t ro = ((tq & 1) == rk ? sb : psb) + OFF_R4 + (8 * (tq >> 1) + g) * 176 + (10 * rk + warp) * 8;
    uint32_t a_q = sb + OFF_R4 + (8 * (lane >> 4) + (lane & 7)) * 176 + (lane & 8) * 10;
    uint32_t a_d = sb + OFF_D + warp * 2048 + (8 * (lane >> 4) + (lane & 7)) * 128 + ((((lane >> 3) & 1) ^ (lane & 7)) << 4);
    unsigned* p_f = g_xf + b * 512 + 64 * warp + 16 * tq + 2 * g;
    const unsigned* pa = g_xao + (g >> 1) * 1024 + 512 * rk + 64 * warp + 4 * (lane & 7);
    PIN(ro); PIN(a_q); PIN(a_d); PINL(p_f); PINL(pa);
    spin_until(tpub + DLY6);
    uint4 v[2];
    {
      bool have = false;
      POLL {
        v[0] = ldx16(pa); v[1] = ldx16(pa + 32);
        const unsigned t1 = (unsigned)clock() + WTEST;
        while (!have && (int)((unsigned)clock() - t1) < 0) {
          uint32_t ok;
          asm volatile("{.reg .pred p, q; mbarrier.test_wait.parity.shared::cta.b64 p, [%1], 0; mbarrier.test_wait.parity.shared::cta.b64 q, [%1+8], 0;\n"
                       "and.pred p, p, q; vote.sync.all.pred p, p, 0xffffffff; selp.u32 %0, 1, 0, p;}" : "=r"(ok) : "r"(bar0 + 8 * FB_G) : "memory");
          if (ok) {
#pragma unroll
            for (int i = 0; i < 8; i++) ldsm_t(af[i >> 2][i & 3], (ab + ((i & 2) ? OFF_U : OFF_G) + (i >> 2) * 1024) ^ ((i & 1) << 5));
            have = true;
          }
        }
        if (!__any_sync(~0u, (X16(v[0]) | X16(v[1])) & 1) || ++it_ >= SPIN_MAX) break;
      }
      float df[4][4] = {}, dg[2][4] = {};
      uint32_t zb[4];
      const uint32_t one = g == 0 ? 0x3F803F80u : 0u;
#pragma unroll
      for (int s = 0; s < 2; s++) {
        const uint32_t y0 = pack2(u2f(v[s].x), u2f(v[s].y)), y1 = pack2(u2f(v[s].z), u2f(v[s].w));
        const uint32_t ya[4] = {y0, one, y1, one};
        mma16(dg[s], ya, y0, y1);
        zb[2 * s] = pack2(u2f(v[s].x) * cf[s].x, u2f(v[s].y) * cf[s].y); zb[2 * s + 1] = pack2(u2f(v[s].z) * cf[s].z, u2f(v[s].w) * cf[s].w);
      }
      float st[2] = {(dg[0][2] + dg[0][3]) + (dg[1][2] + dg[1][3]), (dg[0][0] + dg[0][1]) + (dg[1][0] + dg[1][1])};
      if (!have) {
        mbar_wait(bar0 + 8 * FB_G); mbar_wait(bar0 + 8 * (FB_G + 1));
#pragma unroll
        for (int i = 0; i < 8; i++) ldsm_t(af[i >> 2][i & 3], (ab + ((i & 2) ? OFF_U : OFF_G) + (i >> 2) * 1024) ^ ((i & 1) << 5));
      }
#pragma unroll
      for (int i = 0; i < 8; i++) mma16(df[i & 3], af[i >> 2][i & 3], zb[2 * (i >> 2)], zb[2 * (i >> 2) + 1]);
#pragma unroll
      for (int o2 = 1; o2 < 4; o2 <<= 1) { st[0] += __shfl_xor_sync(~0u, st[0], o2); st[1] += __shfl_xor_sync(~0u, st[1], o2); }
#pragma unroll
      for (int o2 = 4; o2 < 32; o2 <<= 1) st[1] += __shfl_xor_sync(~0u, st[1], o2);
      float r[8];
#pragma unroll
      for (int i = 0; i < 8; i++) r[i] = df[i >> 1][2 * (i & 1)] + df[i >> 1][2 * (i & 1) + 1];
      tred<4>(r, lane, 2); tred<2>(r, lane, 1);
      const int md = (tq & 1) == rk ? 1 : 2;
      st_pair(md, ro, psb + OFF_BAR + 8 * (XB + 5), r[0], r[1]);
      st_pair(lane < 2 ? md : 0, ro + 16 * 176, psb + OFF_BAR + 8 * (XB + 5), st[0], st[1]);
      __syncwarp();
      if (lane == 0) BAR_ARRIVE(XB + 5);
      mbar_wait(bar0 + 8 * FB_D);
#pragma unroll
      for (int mt = 0; mt < 4; mt++)
        ldsm_t(ad[mt], a_d ^ (mt << 5));
    }
    mbar_wait(bar0 + 8 * (XB + 5));
    {
      float4 q[5], u[8];
#pragma unroll
      for (int i = 0; i < 5; i++) q[i] = lds16(a_q + i * 16);
#pragma unroll
      for (int i = 0; i < 8; i++) u[i] = *(const float4*)(smem + OFF_R4 + 16 * 176 + (i >> 2) * 80 + (i & 3) * 16);
      float p[6] = {((q[0].x + q[0].z) + (q[1].x + q[1].z)) + ((q[2].x + q[2].z) + (q[3].x + q[3].z)), q[4].x, q[4].z,
                    ((q[0].y + q[0].w) + (q[1].y + q[1].w)) + ((q[2].y + q[2].w) + (q[3].y + q[3].w)), q[4].y, q[4].w};
      tred<3>(p, lane, 8);
      const float P = p[0], A1 = p[1], A2 = p[2];
      const float mean = (((u[0].x + u[0].z) + (u[1].x + u[1].z)) + ((u[2].x + u[2].z) + (u[3].x + u[3].z)) +
                          ((u[4].x + u[4].z) + (u[5].x + u[5].z)) + ((u[6].x + u[6].z) + (u[7].x + u[7].z))) * (1.f / 512.f);
      const float sq = (((u[0].y + u[0].w) + (u[1].y + u[1].w)) + ((u[2].y + u[2].w) + (u[3].y + u[3].w)) +
                         ((u[4].y + u[4].w) + (u[5].y + u[5].w)) + ((u[6].y + u[6].w) + (u[7].y + u[7].w))) * (1.f / 512.f);
      float rstd;
      asm("rsqrt.approx.ftz.f32 %0, %1;" : "=f"(rstd) : "f"(fmaxf(sq - mean * mean, 0.f) + 1e-5f));
      const float gg = bfr(rstd * (P - mean * A1) + A2);
      const float uu = __shfl_xor_sync(~0u, gg, 16);
      const float hh = bfr(gg * rcp(1.f + ex2(gg * (-2.302208198f - 0.1029432397f * gg * gg)))) * uu;
      const uint32_t hw = pack2(hh, __shfl_down_sync(~0u, hh, 1));
      const uint32_t b0 = __shfl_sync(~0u, hw, 2 * tq), b1 = __shfl_sync(~0u, hw, 2 * tq + 8);
      float f0 = 0, f1 = 0;
#pragma unroll
      for (int mt = 0; mt < 4; mt++) {
        float dd[4] = {0, 0, 0, 0};
        mma16(dd, ad[mt], b0, b1);
        if (tq == mt) { f0 = dd[0]; f1 = dd[2]; }
      }
      stx8(p_f, make_uint2(fbits(f0), fbits(f1)));
    }
    tpub = clock();
    if (b < 64 && warp == (b >> 3)) {
      const uint4 y = (b & 4) ? v[1] : v[0];
      float a4[4] = {u2f(y.x), u2f(y.y), u2f(y.z), u2f(y.w)};
      tred<2>(a4, lane, 16); tred<1>(a4, lane, 8);
      a4[0] += __shfl_xor_sync(~0u, a4[0], 4);
      if (!(lane & 4)) s_sm[416 + 8 * (lane >> 4) + 2 * tq + ((lane >> 3) & 1)] = a4[0];
      if (warp == 7) nbar_arrive(2, 256);
    } else if (b < 64 && warp == 7) nbar_arrive(2, 256);
    if (b < 64 && warp < 7) {
      uint4 v;
      const unsigned* pf = g_xf + (tid >> 1) * 512 + 8 * ob + 4 * (tid & 1);
      const int col = 16 * (ob >> 1) + 4 * (ob & 1) + ((tid >> 1) & 3) + 8 * (tid & 1);
      bf16* po = out + col;
      PINL(po); PINL(pf);
      spin_until(tpub + DLY7);
      POLL { v = ldx16(pf); RETRY(X16(v)) }
      float f[4] = {u2f(v.x), u2f(v.y), u2f(v.z), u2f(v.w)};
      tred<2>(f, lane, 16); tred<1>(f, lane, 8);
      f[0] += __shfl_xor_sync(~0u, f[0], 4); f[0] += __shfl_xor_sync(~0u, f[0], 2);
      if (!(lane & 6)) s_sm[352 + warp * 8 + 4 * (lane & 1) + (lane >> 3)] = f[0];
      nbar(2, 256);
      if (tid < 8) {
        const float* q = s_sm + 352 + tid;
        const float t = ((q[0] + q[8]) + (q[16] + q[24])) + ((q[32] + q[40]) + q[48]);
        *po = __float2bfloat16(s_sm[416 + (col & 15)] + bfr(gbv * bfr(t)));
        if (b == 0 && tid == 0) stx4(&g_epoch, epoch + 1);
      }
    }
  }
}

__global__ void __cluster_dims__(2, 1, 1) __launch_bounds__(384, 1)
fused_kernel(const bf16* __restrict__ x, const bf16* __restrict__ cvec, const bf16* __restrict__ w_mod, bf16* __restrict__ out,
             Scratch* __restrict__ scr, const __grid_constant__ TMaps tms) {
  extern __shared__ __align__(1024) unsigned char smem[];
  const int tid = threadIdx.x, warp = __shfl_sync(~0u, tid >> 5, 0), lane = tid & 31;
  const int b = blockIdx.x, rk = b & 1, pr = b >> 1, hd = b >> 2;
  uint32_t sb = s2u(smem), bar0 = sb + OFF_BAR;

  unsigned gt_start;
  asm volatile("mov.u32 %0, %%globaltimer_lo;" : "=r"(gt_start));
  const int g = lane >> 2, tq = lane & 3;
  const int arow = 64 * (b >> 4) + ((tid & 255) >> 3);
  uint4 wm0, wm1;
  uint32_t c0w, c1w;
  if (warp < 8) {
    const bf16* wa = w_mod + (size_t)arow * 3072 + (lane & 4) * 128 + 32 * (b & 15) + 8 * tq;
    wm0 = ldx16(wa); wm1 = ldx16(wa + 32 * 3072);
    c0w = ldc4(cvec + (arow & ~1)); c1w = ldc4(cvec + (arow & ~1) + 32);
  }
  const unsigned t_off = gt_start + RATE_T0;
  if (warp == 11) {
    if (lane == 0) {
#pragma unroll
      for (int i = 0; i < FB_KV; i++) { BAR_INIT(i, 1); BAR_ARM(i, 16384); }
    }
    __syncwarp();
    asm volatile("fence.mbarrier_init.release.cluster;" ::: "memory");
    asm volatile("barrier.cluster.arrive.relaxed.aligned;" ::: "memory");
#pragma unroll 1
    for (int i = 0; i < FB_KV; i++) {
      if (i >= HWIN) mbar_wait(bar0 + 8 * (i - HWIN));
      wait_until(t_off + (i < 4 ? 2 * i + ((b >> 1) & 1) : 4 * i - 8 + (b & 3)) * (RATE_H / 4));
      if (lane == 0) {
        if (i < 4) tma3d(sb + OFF_WQ + i * 16384, &tms.m[0], bar0 + 8 * i, 0, i * 128, 2 * hd + rk);
        else tma3d(sb + OFF_WQ + i * 16384, &tms.m[1], bar0 + 8 * i, 0, (b & 3) * 128 + (i - 4) * 64, 2 * hd);
      }
      __syncwarp();
    }
  }
  if (warp == 10) {
    const uint4 xa = ldc16(x + 16 * lane), xb = ldc16(x + 16 * lane + 8);
    const unsigned ep = ldc4(&g_epoch);
    float xv[16] = {bflo(xa.x), bfhi(xa.x), bflo(xa.y), bfhi(xa.y), bflo(xa.z), bfhi(xa.z), bflo(xa.w), bfhi(xa.w),
                    bflo(xb.x), bfhi(xb.x), bflo(xb.y), bfhi(xb.y), bflo(xb.z), bfhi(xb.z), bflo(xb.w), bfhi(xb.w)};
    float s = 0;
#pragma unroll
    for (int i = 0; i < 16; i++) s += xv[i];
#pragma unroll
    for (int o = 16; o; o >>= 1) s += __shfl_xor_sync(~0u, s, o);
    const float mean = s * (1.f / 512.f);
    s = 0;
#pragma unroll
    for (int i = 0; i < 16; i++) { xv[i] -= mean; s += xv[i] * xv[i]; }
#pragma unroll
    for (int o = 16; o; o >>= 1) s += __shfl_xor_sync(~0u, s, o);
    const float rstd = rsqrtf(s * (1.f / 512.f) + 1e-5f);
    if ((lane >> 1) == (b & 15))
#pragma unroll
      for (int i = 0; i < 4; i++)
        *(float4*)(smem + OFF_SM + (256 + (lane & 1) * 16 + 4 * i) * 4) = make_float4(xv[4 * i] * rstd, xv[4 * i + 1] * rstd, xv[4 * i + 2] * rstd, xv[4 * i + 3] * rstd);
    if (lane == 0) *(volatile unsigned*)(smem + OFF_MASK + 8) = ep;
    nbar_arrive(1, 288);
  }
  if (warp >= 8) {
    asm volatile("setmaxnreg.dec.sync.aligned.u32 72;");
    if (tid == 288) {
#pragma unroll
      for (int q = FB_KV; q < FB_KV + 16; q++) { BAR_INIT(q, 1); BAR_ARM(q, 32768); }
    }
    if (tid == 320) {
#pragma unroll
      for (int q = 0; q <= 13 + NSLOT; q++) BAR_INIT(EB + q, q == 0 ? 4 : q < 5 ? 16 : q < 16 ? 12 : 6);
    }
    if (tid == 256) {
#pragma unroll
      for (int q = FB_MOD; q <= FB_D; q++) { BAR_INIT(q, 1); BAR_ARM(q, 16384); }
      BAR_INIT(QB, 9); BAR_ARM(QB, 1024);
#pragma unroll
      for (int q = 0; q < 7; q++) BAR_INIT(XB + q, q == 2 ? 256 : q == 5 || q == 3 ? 9 : 1);
      BAR_ARM(XB + 3, 1024);
      BAR_ARM(XB + 5, 1024 + 64 + 512);
      *(volatile unsigned long long*)(smem + OFF_MASK) = 0;
    }
    if (warp != 11) {
      __syncwarp();
      asm volatile("fence.mbarrier_init.release.cluster;" ::: "memory");
      __threadfence_block();
      asm volatile("barrier.cluster.arrive.relaxed.aligned;" ::: "memory");
    }
    if (warp == 11) {
      asm volatile("barrier.cluster.wait.acquire.aligned;" ::: "memory");
      const unsigned epoch = *(volatile unsigned*)(smem + OFF_MASK + 8), par = (epoch + 1) & 1;
      mbar_wait(bar0 + 8 * (FB_KV + 15));
      for (int it = 0; ldx4(scr->cnt + 96 + 32 * (b >> 6)) != (epoch + 1) * 64 && it < SPIN_MAX; it++) {}
      uint4 hh;
      POLL { hh = ldx16(g_ml + (b >> 2) * 64 + 2 * lane); RETRY(X16(hh)) }
      int mi = __float_as_int(fmaxf(u2f(hh.x), u2f(hh.z)));
      mi ^= (mi >> 31) & 0x7fffffff;
      mi = __reduce_max_sync(~0u, mi);
      mi ^= (mi >> 31) & 0x7fffffff;
      const float M = __int_as_float(mi);
      const uint32_t wp = pack2(ex2(u2f(hh.x) - M), ex2(u2f(hh.z) - M));
      float L = bflo(wp) * u2f(hh.y) + bfhi(wp) * u2f(hh.w);
#pragma unroll
      for (int o2 = 16; o2; o2 >>= 1) L += __shfl_xor_sync(~0u, L, o2);
      *(uint32_t*)(smem + OFF_RA + lane * 4) = wp;
      if (lane == 0) *(float*)(smem + OFF_RA + 128) = rcp(L);
      __syncwarp();
      if (lane == 0) BAR_ARRIVE(XB + 6);
    }
    if (warp == 10) {
      if (lane < 8) asm volatile("prefetch.tensormap [%0];" ::"l"(&tms.m[lane + 1]) : "memory");
      asm volatile("barrier.cluster.wait.acquire.aligned;" ::: "memory");
      const unsigned epoch = *(volatile unsigned*)(smem + OFF_MASK + 8);
#pragma unroll 1
      for (int e = 0; e < 2; e++) {
        for (int it = 0; ldx4(scr->cnt + (e ? 2 + rk : 1)) != (epoch + 1) * (e ? 64 : 128) && it < SPIN_MAX; it++) {}
        if (lane == 0) BAR_ARRIVE(XB + e);
      }
      mbar_wait(bar0 + 8 * (FB_KV + 14));
      unsigned long long m = 0;
#pragma unroll 1
      for (int it = 0; ~m && it < SPIN_MAX; it++) {
        m = ldx64(scr->cnt + 32 + 32 * (b >> 6)) ^ ((epoch & 1) ? ~0ull : 0ull);
        if (lane == 0) *(volatile unsigned long long*)(smem + OFF_MASK) = m;
      }
    }
    if (warp == 9) {
      asm volatile("barrier.cluster.wait.acquire.aligned;" ::: "memory");
      const unsigned epoch = *(volatile unsigned*)(smem + OFF_MASK + 8);
      const unsigned par = (epoch + 1) & 1, inv = par ^ 1;
      const uint4 inv4 = make_uint4(inv, inv, inv, inv);
      mbar_wait(bar0 + 8 * FB_KV);
#pragma unroll 2
      for (int k = 0; k < 8; k++) {
        const uint32_t cp = ldc4(cvec + 2 * (lane + 32 * k));
        *(uint32_t*)(smem + OFF_SILU + (lane + 32 * k) * 4) = pack2(silu_bf(bflo(cp)), silu_bf(bfhi(cp)));
      }
      __syncwarp();
      mbar_wait(bar0 + 8 * FB_MOD);
      const uint32_t ab = sb + OFF_MOD + (8 * (lane >> 4) + (lane & 7)) * 32 + ((((lane >> 3) ^ (lane >> 2)) & 1) << 4);
      float d[4][4] = {};
#pragma unroll 2
      for (int s4 = 0; s4 < 8; s4++)
#pragma unroll
        for (int s = 0; s < 4; s++) {
          uint32_t a[4];
          const uint32_t* ps = (const uint32_t*)(smem + OFF_SILU) + 32 * s4 + 8 * s + tq;
          ldsm_t(a, ab + (4 * s4 + s) * 512); mma16(d[s], a, ps[0], ps[4]);
        }
      const float t = (tq & 1) ? (d[0][2] + d[1][2]) + (d[2][2] + d[3][2]) : (d[0][0] + d[1][0]) + (d[2][0] + d[3][0]);
      if (tq < 2) stx4(g_xm + b * 16 + 2 * (g & 6) + 2 * tq + (g & 1), fbits(bfr(t)));
      __syncwarp();
      if (lane == 0) CNT_ADD(6);
      mbar_wait(bar0 + 8 * (FB_KV + 8));
      if (lane < 16) stx16(g_xc + (b >> 2) * 256 + (lane >> 1) * 32 + (b & 3) * 8 + (lane & 1) * 4, inv4);
      if (lane < 8) stx16(g_xao + (b >> 5) * 1024 + (b & 15) * 64 + (lane & 4) * 8 + (b & 16) + (lane & 3) * 4, inv4);
      if (b < 112)
#pragma unroll 1
        for (int k = 0; k < 4; k++) stx16(g_xf + b * 512 + (lane + 32 * k) * 4, inv4);
      nbar_arrive(2, 288);
      for (int it = 0; ldx4(scr->cnt + 6) != (epoch + 1) * 128 && it < SPIN_MAX; it++) __nanosleep(100);
      {
        uint4 sv[2], cb[2];
        unsigned ga, gb;
        POLL {
#pragma unroll
          for (int k = 0; k < 2; k++) { sv[k] = ldx16(g_xm + 512 + 256 * rk + 4 * (lane + 32 * k)); cb[k] = ldx16(g_xm + 1024 + 256 * rk + 4 * (lane + 32 * k)); }
          ga = ldx4(g_xm + (b & 15) * 32 + lane); gb = ldx4(g_xm + 1536 + 256 * rk + 8 * (pr & 31) + (lane & 7));
          RETRY(X16(sv[0]) | X16(sv[1]) | X16(cb[0]) | X16(cb[1]) | lop_x3(ga, gb, par))
        }
#pragma unroll
        for (int k = 0; k < 2; k++) {
          const float c0 = bfr(1.f + bfhi(cb[k].x)), c1 = bfr(1.f + bfhi(cb[k].y)), c2 = bfr(1.f + bfhi(cb[k].z)), c3 = bfr(1.f + bfhi(cb[k].w));
          *(float4*)(smem + OFF_CO + (lane + 32 * k) * 16) = make_float4(c0, c1, c2, c3);
          uint2* pb = (uint2*)(smem + OFF_BP) + lane + 32 * k;
          pb[0] = make_uint2(pack2(c0, c1), pack2(c2, c3));
          pb[64] = make_uint2(__byte_perm(sv[k].x, sv[k].y, 0x7632), __byte_perm(sv[k].z, sv[k].w, 0x7632));
        }
        *(float*)(smem + OFF_CO + 1024 + lane * 4) = bfhi(ga);
        *(float*)(smem + OFF_CO + 1152 + lane * 4) = bfhi(gb);
      }
      __syncwarp();
      if (lane == 0) BAR_ARRIVE(XB + 4);
    }
    if (warp == 8) {
      const unsigned stag = ((pr * SMUL) & 63) * RATE_NS >> 6;
      unsigned tnext = t_off + 4 * RATE_H;
      asm volatile("barrier.cluster.wait.acquire.aligned;" ::: "memory");
#pragma unroll 1
      for (int k = 0; k < 24; k++) {
        const int code = (k < 12 ? ORDER0 >> (5 * k) : ORDER1 >> (5 * (k - 12))) & 31;
        const bool kv = code < 16;
        const int n = code, w = code - 16;
        if (!kv && w >= 5 && b >= 112) break;
        if (kv) mbar_wait(bar0 + 8 * (FB_KV + n - (n < 6 ? EWIN : KVWIN)));
        if (k >= TAIL_K) mbar_wait(bar0 + 8 * (FB_KV + (int)((ORDER1 >> (5 * (k - 12 - ((WINS >> (4 * (k - TAIL_K))) & 15)))) & 31)));
        const int e = kv ? (n == 3 ? 2 : n == 5 ? 1 : n) : w == 0 ? 0 : w < 5 ? 16 + ((w - 1) >> 1) : w == 7 ? 19 : 18;
        if (e != 1 && k) mbar_wait(bar0 + 8 * (EB + e));
        wait_until(tnext + stag);
        tnext += k > TAIL_K ? RATE_TL : k < 4 ? RATE_E : RATE_NS;
        if (lane == 0) {
          if (kv)
            asm volatile("cp.async.bulk.tensor.3d.shared::cluster.global.mbarrier::complete_tx::bytes.multicast::cluster.L2::cache_hint [%0], [%1, {%3, %4, %5}], [%2], %6, %7;"
                         ::"r"(sb + (n % NSLOT) * SLOT + rk * 16384), "l"(&tms.m[2]), "r"(bar0 + 8 * (FB_KV + n)), "r"(0), "r"(((n >> 1) * 64 + pr) * 64),
                           "r"(4 * (n & 1) + 2 * rk), "h"((unsigned short)3), "l"(stream_policy()) : "memory");
          else {
            tma3d(sb + (w == 0 ? OFF_MOD : w < 5 ? OFF_UV + (w - 1) * 16384 : w == 5 ? OFF_G : w == 6 ? OFF_U : OFF_D),
                  &tms.m[w == 0 ? 3 : w < 3 ? 4 : w < 5 ? 5 : w + 1], bar0 + 8 * (FB_MOD + w),
                  w == 0 ? 1024 + b * 16 : w < 3 || w == 7 ? 0 : w < 5 ? (pr & 7) * 64 : pr * 32, w == 7 ? b * 16 : w == 1 || w == 2 ? (b & 3) * 128 + (w - 1) * 64 : 0,
                  w == 1 || w == 2 ? 2 * hd : w == 3 || w == 4 ? (b >> 4) * 4 + 2 * rk + w - 3 : w == 5 || w == 6 ? rk : 0);
          }
        }
        __syncwarp();
      }
    }
    if (b < 112) {
      const int mt = warp & 1, dd = (warp >> 1) & 1;
      mbar_wait(bar0 + 8 * (XB + 4));
      const uint32_t ab = sb + (mt ? OFF_U : OFF_G) + (8 * (lane >> 4) + (lane & 7)) * 64 + (((2 * dd + ((lane >> 3) & 1)) ^ ((lane >> 1) & 3)) << 4);
      uint32_t base;
      asm volatile("mapa.shared::cluster.u32 %0, %1, %2;" : "=r"(base) : "r"(sb), "r"(dd));
      uint2 bb[16];
#pragma unroll
      for (int s = 0; s < 16; s++) bb[s] = *(const uint2*)(smem + OFF_BP + (g & 1) * 512 + (4 * s + tq) * 8);
      mbar_wait(bar0 + 8 * (FB_G + mt));
      float e[4][4] = {};
#pragma unroll
      for (int s = 0; s < 16; s++) { uint32_t a[4]; ldsm_t(a, ab + s * 1024); mma16(e[s & 3], a, bb[s].x, bb[s].y); }
      float r[4];
#pragma unroll
      for (int i = 0; i < 4; i++) r[i] = (e[0][i] + e[1][i]) + (e[2][i] + e[3][i]);
      if (tq < 2) st_async2(base + OFF_R4 + (8 * mt + g) * 176 + (10 * rk + 8 + tq) * 8, base + OFF_BAR + 8 * (XB + 5), tq ? r[1] : r[0], tq ? r[3] : r[2]);
    }
    return;
  }

  float* s_sm = (float*)(smem + OFF_SM);
  unsigned par, epoch;
  uint32_t rsb;
  {
    float* s_r4 = (float*)(smem + OFF_R4);
    asm volatile("barrier.cluster.arrive.relaxed.aligned;" ::: "memory");
    asm volatile("mapa.shared::cluster.u32 %0, %1, %2;" : "=r"(rsb) : "r"(sb), "r"(rk ^ 1));
    const float c0 = (arow & 1) ? bfhi(c0w) : bflo(c0w), c1 = (arow & 1) ? bfhi(c1w) : bflo(c1w);
    float acc[8] = {0, 0, 0, 0, 0, 0, 0, 0};
    fma8(acc, wm0, silu_bf(c0)); fma8(acc, wm1, silu_bf(c1));
    tred<4>(acc, lane, 8); tred<2>(acc, lane, 16);
    *(float2*)(s_r4 + warp * 64 + 8 * (lane & 7) + ((lane >> 1) & 4) + ((lane >> 3) & 2)) = make_float2(acc[0], acc[1]);
    nbar(1, 288);
    epoch = *(volatile unsigned*)(smem + OFF_MASK + 8);
    par = (epoch + 1) & 1;
    if (warp == 0) {
      float t = 0.f, ca = b < 16 ? 1.f : 0.f;
#pragma unroll
      for (int w = 0; w < 8; w++) { t += s_r4[w * 64 + lane]; ca += s_r4[w * 64 + 32 + lane]; }
      t += ca * s_sm[256 + lane];
      const float nb = __shfl_down_sync(~0u, t, 1);
      const uint32_t w0 = lane < 8 ? pack2t(t, nb, par) : pack2(t, nb);
      const uint32_t w1 = __shfl_down_sync(~0u, w0, 8), w2 = __shfl_down_sync(~0u, w0, 16), w3 = __shfl_down_sync(~0u, w0, 24);
      if (lane < 8 && !(lane & 1)) stx16(g_h + (b >> 5) * 512 + (b & 15) * 32 + (b & 16) + 2 * lane, make_uint4(w0, w1, w2, w3));
      __syncwarp();
      if (lane == 0) CNT_ADD(1);
    }
  }
  asm volatile("barrier.cluster.wait.acquire.aligned;" ::: "memory");
  {
    uint32_t a[4][4][4];
    mbar_wait(bar0 + 8 * (warp >> 1));
    const uint32_t ab = sb + OFF_WQ + (64 * warp + 8 * (lane >> 4) + (lane & 7)) * 128;
#pragma unroll
    for (int s = 0; s < 4; s++)
#pragma unroll
      for (int mt = 0; mt < 4; mt++) ldsm_t(a[s][mt], ab + s * 2048 + (((2 * mt + ((lane >> 3) & 1)) ^ (lane & 7)) << 4));
    uint4 v0, v1;
    const unsigned* ph = g_h + (g >> 1) * 512 + 64 * warp + 4 * (lane & 7);
    uint32_t off = OFF_B + warp * 272 + (32 * rk + 8 * tq + (lane & 4)) * 4;
    PIN(off); PINL(ph);
    mbar_wait(bar0 + 8 * XB);
    POLL { v0 = ldx16(ph); v1 = ldx16(ph + 32); RETRY(lop_x3(v0.x, v1.x, par)) }
    float d[4][4] = {};
#pragma unroll
    for (int mt = 0; mt < 4; mt++) {
      mma16(d[mt], a[0][mt], v0.x, v0.y); mma16(d[mt], a[1][mt], v0.z, v0.w);
      mma16(d[mt], a[2][mt], v1.x, v1.y); mma16(d[mt], a[3][mt], v1.z, v1.w);
    }
    float r[8];
#pragma unroll
    for (int mt = 0; mt < 4; mt++) { r[2 * mt] = d[mt][0] + d[mt][1]; r[2 * mt + 1] = d[mt][2] + d[mt][3]; }
    tred<4>(r, lane, 2); tred<2>(r, lane, 1);
    const float rc = __shfl_xor_sync(~0u, (lane & 4) ? r[0] : r[1], 4);
    const uint32_t wd = (lane & 4) ? pack2(rc, r[1]) : pack2(r[0], rc);
    const uint32_t w1 = __shfl_down_sync(~0u, wd, 8), w2 = __shfl_down_sync(~0u, wd, 16), w3 = __shfl_down_sync(~0u, wd, 24);
    asm volatile("{.reg .pred p; setp.lt.s32 p, %7, 8; @p st.shared.v4.b32 [%0], {%2,%3,%4,%5};\n"
                 "@p st.async.shared::cluster.mbarrier::complete_tx::bytes.v4.b32 [%1], {%2,%3,%4,%5}, [%6];}"
                 ::"r"(sb + off), "r"(rsb + off), "r"(wd), "r"(w1), "r"(w2), "r"(w3), "r"(rsb + OFF_BAR + 8 * QB), "r"(lane) : "memory");
    __syncwarp();
    arrive2(bar0 + 8 * QB, 0, lane == 0, false);
    arrive2(bar0 + 8 * (EB + 2), rsb + OFF_BAR + 8 * (EB + 2), lane == 0, lane == 0);
  }
  {
    uint32_t a[8][4];
    uint32_t a_bq = sb + OFF_B + (lane & 7) * 272 + (lane >> 3) * 16;
    unsigned* p_qa = g_qa + b * 64 + 8 * warp + 4 * lane;
    PIN(a_bq); PINL(p_qa);
    mbar_wait(bar0 + 8 * (FB_UK + (warp >> 2)));
    const uint32_t ab = sb + OFF_WUK + (warp >> 2) * 16384 + (16 * (warp & 3) + (lane & 15)) * 128;
#pragma unroll
    for (int s = 0; s < 8; s++) ldsm(a[s], ab + (s >> 2) * 8192 + (((2 * (s & 3) + (lane >> 4)) ^ (lane & 7)) << 4));
    mbar_wait(bar0 + 8 * QB);
    float d[4][4] = {};
#pragma unroll
    for (int y = 0; y < 4; y++) {
      uint32_t bq[4];
      ldsm(bq, a_bq + 64 * y);
      mma16(d[(2 * y) & 3], a[2 * y], bq[0], bq[1]); mma16(d[(2 * y + 1) & 3], a[2 * y + 1], bq[2], bq[3]);
    }
    float r[2] = {((d[0][0] + d[0][1]) + (d[1][0] + d[1][1])) + ((d[2][0] + d[2][1]) + (d[3][0] + d[3][1])),
                  ((d[0][2] + d[0][3]) + (d[1][2] + d[1][3])) + ((d[2][2] + d[2][3]) + (d[3][2] + d[3][3]))};
    tred<1>(r, lane, 1);
    r[0] += __shfl_xor_sync(~0u, r[0], 2);
    const float nb = __shfl_xor_sync(~0u, r[0], 4);
    const uint32_t w0 = lane < 8 ? pack2t(r[0], nb, par) : pack2(r[0], nb);
    const uint32_t w1 = __shfl_down_sync(~0u, w0, 8), w2 = __shfl_down_sync(~0u, w0, 16), w3 = __shfl_down_sync(~0u, w0, 24);
    if (lane < 2) stx16(p_qa, make_uint4(w0, w1, w2, w3));
    arrive2(bar0 + 8 * (EB + 4), rsb + OFF_BAR + 8 * (EB + 4), lane == 0, lane == 0);
  }
  {
    if (warp) nbar_arrive(3, 256); else { nbar(3, 256); if (lane == 0) CNT_ADD(2 + (b >> 6)); }
    asm volatile("setmaxnreg.inc.sync.aligned.u32 216;");
    const unsigned* pq = g_qa + rk * 4096 + tid * 4;
    uint32_t a_q = sb + OFF_Q + ((tid & 63) >> 3) * 2048 + (tid >> 6) * 128 + (((tid & 7) ^ (tid >> 6)) << 4);
    PINL(pq); PIN(a_q);
    mbar_wait(bar0 + 8 * (XB + 1));
    uint4 v[4];
    POLL {
#pragma unroll
      for (int k = 0; k < 4; k++) v[k] = ldx16(pq + 1024 * k);
      RETRY(lop_x3(v[0].x, v[1].x, par) | lop_x3(v[2].x, v[3].x, par))
    }
#pragma unroll
    for (int k = 0; k < 4; k++)
      asm volatile("st.shared.v4.b32 [%0], {%1,%2,%3,%4};" ::"r"((a_q + k * 512) ^ ((k & 1) << 6)), "r"(v[k].x), "r"(v[k].y), "r"(v[k].z), "r"(v[k].w) : "memory");
    if (warp >= 4) nbar_arrive(1, 256); else nbar(1, 256);
  }
  sb = __shfl_sync(~0u, sb, 0); bar0 = sb + OFF_BAR;
  if (warp < 4) {
    uint32_t qf[32][4];
#pragma unroll
    for (int s = 0; s < 32; s++) ldsm(qf[s], sb + OFF_Q + (s >> 2) * 2048 + (lane & 15) * 128 + (((2 * (s & 3) + (lane >> 4)) ^ (lane & 7)) << 4));
    float l0 = 0.f, l1 = 0.f, m0 = -1e30f, m1 = -1e30f;
    const float sc = 0.08838834764831845f * 1.4426950408889634f;
    const uint32_t kofs = (16 * warp + 8 * (lane >> 4) + (lane & 7)) * 128 + ((((lane >> 3) & 1) ^ (lane & 7)) << 4);
    uint32_t st = sb;
#pragma unroll 1
    for (int t = 0; t < 8; t++) {
      float sa[4][4] = {};
#pragma unroll
      for (int hf = 0; hf < 2; hf++) {
        const int n = 2 * t + hf;
        mbar_wait(bar0 + 8 * (FB_KV + n));
        uint32_t kf[16][4];
#pragma unroll
        for (int y = 0; y < 16; y++) ldsm(kf[y], st + (y >> 2) * 8192 + (kofs ^ ((y & 3) << 5)));
#pragma unroll
        for (int y = 0; y < 16; y++) {
          mma16(sa[(2 * y) & 3], qf[16 * hf + y], kf[y][0], kf[y][1]); mma16(sa[((2 * y) & 3) + 1], qf[16 * hf + y], kf[y][2], kf[y][3]);
        }
        __syncwarp();
        arrive2(bar0 + 8 * (EB + NSLOT + n), rsb + OFF_BAR + 8 * (EB + NSLOT + n), lane == 0 && n < 14, lane == 0 && n < 16 - NSLOT);
        if (hf == 0) arrive2(bar0 + 8 * EB, 0, lane == 0 && t == 0, false);
        st = st + SLOT == sb + NSLOT * SLOT ? sb : st + SLOT;
      }
#pragma unroll
      for (int i = 0; i < 4; i++) { sa[0][i] = (sa[0][i] + sa[2][i]) * sc; sa[1][i] = (sa[1][i] + sa[3][i]) * sc; }
      float cm[2] = {fmaxf(fmaxf(sa[0][0], sa[0][1]), fmaxf(sa[1][0], sa[1][1])), fmaxf(fmaxf(sa[0][2], sa[0][3]), fmaxf(sa[1][2], sa[1][3]))};
      tmax<1>(cm, lane, 1);
      cm[0] = fmaxf(cm[0], __shfl_xor_sync(~0u, cm[0], 2));
      float* pm = s_sm + (t & 1) * 64;
      if (tq < 2) pm[(g + 8 * tq) * 4 + warp] = cm[0];
      if (t >= 2) nbar(6 + (t & 1), 256); else nbar(3, 128);
      const float4 a0 = *(const float4*)(pm + g * 4), b0 = *(const float4*)(pm + g * 4 + 32);
      const float n0 = fmaxf(fmaxf(fmaxf(a0.x, a0.y), fmaxf(a0.z, a0.w)), m0), n1 = fmaxf(fmaxf(fmaxf(b0.x, b0.y), fmaxf(b0.z, b0.w)), m1);
      uint32_t pk[4];
#pragma unroll
      for (int i = 0; i < 2; i++) { pk[2 * i] = pack2(ex2(sa[i][0] - n0), ex2(sa[i][1] - n0)); pk[2 * i + 1] = pack2(ex2(sa[i][2] - n1), ex2(sa[i][3] - n1)); }
      *(uint4*)(smem + OFF_P + (t & 1) * 2048 + tid * 16) = make_uint4(pk[0], pk[1], pk[2], pk[3]);
      const float al0 = ex2(m0 - n0), al1 = ex2(m1 - n1);
      if (tid < 32 && tq == 0) *(float2*)(s_sm + 192 + (t & 1) * 16 + 2 * g) = make_float2(al0, al1);
      nbar_arrive(4 + (t & 1), 256);
      m0 = n0; m1 = n1;
      l0 = l0 * al0 + (bflo(pk[0]) + bfhi(pk[0])) + (bflo(pk[2]) + bfhi(pk[2]));
      l1 = l1 * al1 + (bflo(pk[1]) + bfhi(pk[1])) + (bflo(pk[3]) + bfhi(pk[3]));
    }
    float lr[2] = {l0, l1};
    tred<1>(lr, lane, 1);
    lr[0] += __shfl_xor_sync(~0u, lr[0], 2);
    if (tq < 2) s_sm[128 + (g + 8 * tq) * 4 + warp] = lr[0];
    nbar(3, 128);
    if (warp == 0 && tq < 2) {
      const float4 a0 = *(const float4*)(s_sm + 128 + (g + 8 * tq) * 4);
      stx8(g_ml + (16 * rk + g + 8 * tq) * 64 + pr, make_uint2(fbits(tq ? m1 : m0), fbits((a0.x + a0.y) + (a0.z + a0.w))));
    }
    if (warp == 0) { __syncwarp(); if (lane == 0) CNT_ADD(96 + 32 * rk); }
    nbar(2, 288);
    if (tid == 0) asm volatile("red.relaxed.gpu.global.xor.b64 [%0], %1;" ::"l"(scr->cnt + 32 + 32 * rk), "l"(1ull << pr) : "memory");
  } else {
    float o[16][4] = {};
    const uint32_t vofs = (warp & 1) * 16384 + (lane & 15) * 128 + (((lane >> 4) ^ (lane & 7)) << 4);
    const int hf = (warp >> 1) & 1;
    uint32_t st = sb + hf * SLOT;
    auto pv = [&](const int t, auto np) {
      constexpr int npre = decltype(np)::value;
      uint32_t vf[4][8][4];
      const int n = 2 * t + hf;
      mbar_wait(bar0 + 8 * (FB_KV + n));
#pragma unroll
      for (int s = 0; s < npre; s++)
#pragma unroll
        for (int y = 0; y < 8; y++) ldsm_t(vf[s][y], st + (y >> 2) * 8192 + s * 2048 + (vofs ^ ((y & 3) << 5)));
      nbar(4 + (t & 1), 256);
      const float2 al = *(const float2*)(s_sm + 192 + (t & 1) * 16 + 2 * g);
      uint4 pf[4];
#pragma unroll
      for (int s = 0; s < 4; s++) pf[s] = *(const uint4*)(smem + OFF_P + (t & 1) * 2048 + s * 512 + lane * 16);
      if (t < 6) nbar_arrive(6 + (t & 1), 256);
#pragma unroll
      for (int s = npre; s < 4; s++)
#pragma unroll
        for (int y = 0; y < 8; y++) ldsm_t(vf[s][y], st + (y >> 2) * 8192 + s * 2048 + (vofs ^ ((y & 3) << 5)));
#pragma unroll
      for (int nt = 0; nt < 16; nt++) { o[nt][0] *= al.x; o[nt][1] *= al.x; o[nt][2] *= al.y; o[nt][3] *= al.y; }
#pragma unroll
      for (int s = 0; s < 4; s++) {
        const uint32_t pa[4] = {pf[s].x, pf[s].y, pf[s].z, pf[s].w};
#pragma unroll
        for (int y = 0; y < 8; y++) { mma16(o[2 * y], pa, vf[s][y][0], vf[s][y][1]); mma16(o[2 * y + 1], pa, vf[s][y][2], vf[s][y][3]); }
      }
      __syncwarp();
      arrive2(bar0 + 8 * (EB + NSLOT + n), rsb + OFF_BAR + 8 * (EB + NSLOT + n), lane == 0 && n < 14, lane == 0 && n < 16 - NSLOT);
      st = st + 2 * SLOT >= sb + NSLOT * SLOT ? st - (NSLOT - 2) * SLOT : st + 2 * SLOT;
    };
#pragma unroll 1
    for (int t = 0; t < 7; t++) pv(t, IC<NPRE0>());
    pv(7, IC<NPRE1>());
    uint4* po = g_xo + ((size_t)((16 * rk + (g & 6)) * 4 + warp - 4) * 64 + pr) * RS + (lane & 7);
    const bool odd = lane & 4;
#pragma unroll
    for (int e = 0; e < 2; e++)
#pragma unroll
      for (int j2 = 0; j2 < 2; j2++) {
        uint32_t c0[4], c1[4];
#pragma unroll
        for (int i = 0; i < 4; i++) {
          c0[i] = i ? pack2(o[8 * j2 + i][2 * e], o[8 * j2 + i][2 * e + 1]) : pack2t(o[8 * j2][2 * e], o[8 * j2][2 * e + 1], par);
          c1[i] = i ? pack2(o[8 * j2 + 4 + i][2 * e], o[8 * j2 + 4 + i][2 * e + 1]) : pack2t(o[8 * j2 + 4][2 * e], o[8 * j2 + 4][2 * e + 1], par);
          const uint32_t r = __shfl_xor_sync(~0u, odd ? c0[i] : c1[i], 4);
          if (odd) c0[i] = r; else c1[i] = r;
        }
        stx16(po + e * 8 * 4 * 64 * RS + 8 * j2, make_uint4(c0[0], c0[1], c0[2], c0[3]));
        stx16(po + (e * 8 + 1) * 4 * 64 * RS + 8 * j2, make_uint4(c1[0], c1[1], c1[2], c1[3]));
      }
    nbar_arrive(2, 288);
  }
  tail(smem, scr, x, out, par, epoch, warp);
}

static void launch(void* const* d_in, void* d_out) {
  static TMaps tms;
  static bool init = false;
  static void* scr = nullptr;
  if (!init) {
    void* fn = nullptr; cudaDriverEntryPointQueryResult qr;
    cudaGetDriverEntryPoint("cuTensorMapEncodeTiled", &fn, cudaEnableDefault, &qr);
    EncFn f = (EncFn)fn;
    const CUtensorMapSwizzle S32 = CU_TENSOR_MAP_SWIZZLE_32B, S64 = CU_TENSOR_MAP_SWIZZLE_64B, S128 = CU_TENSOR_MAP_SWIZZLE_128B;
    const CUtensorMapL2promotion P128 = CU_TENSOR_MAP_L2_PROMOTION_L2_128B, P256 = CU_TENSOR_MAP_L2_PROMOTION_L2_256B;
    enc3d(f, &tms.m[0], d_in[2], 64, 512, 64, 8192, 128, 64, 128, 1, S128, P128);
    enc3d(f, &tms.m[1], d_in[3], 64, 512, 64, 8192, 128, 64, 64, 2, S128, P256);
    enc3d(f, &tms.m[2], d_in[1], 64, SK, 8, 1024, 128, 64, 64, 2, S128, P256);
    enc3d(f, &tms.m[3], d_in[11], 3072, 256, 2, 6144, 256 * 6144, 16, 256, 2, S32, P128);
    enc3d(f, &tms.m[4], d_in[4], 64, 512, 64, 8192, 128, 64, 64, 2, S128, P256);
    enc3d(f, &tms.m[5], d_in[5], 512, 128, 32, 1024, 128 * 1024, 64, 128, 1, S128, P128);
    enc3d(f, &tms.m[6], d_in[7], 1792, 256, 2, 3584, 256 * 3584, 32, 256, 1, S64, P128);
    enc3d(f, &tms.m[7], d_in[8], 1792, 256, 2, 3584, 256 * 3584, 32, 256, 1, S64, P128);
    enc3d(f, &tms.m[8], d_in[9], 64, 1792, 8, 1024, 128, 64, 16, 8, S128, P256);
    cudaFuncSetAttribute(fused_kernel, cudaFuncAttributeMaxDynamicSharedMemorySize, SMEM_BYTES);
    cudaGetSymbolAddress(&scr, g_scr);
    init = true;
  }
  fused_kernel<<<NCTA, 384, SMEM_BYTES>>>((const bf16*)d_in[0], (const bf16*)d_in[10], (const bf16*)d_in[11], (bf16*)d_out, (Scratch*)scr, tms);
}

}

extern "C" void kernel_launch(void* const* d_in, const int* in_sizes, int n_in, void* d_out, int out_size) {
  static int big = -1;
  if (big < 0) big = v9::fits();
  if (big) v9::launch(d_in, d_out); else v8::launch(d_in, d_out);
}
```

```cpp
#include <cuda_runtime.h>
#include <cuda_bf16.h>
#include <cuda.h>
#include <stdint.h>
#include <stdio.h>
#include <stdlib.h>

typedef CUresult (*EncFn)(CUtensorMap*, CUtensorMapDataType, cuuint32_t, void*, const cuuint64_t*, const cuuint64_t*,
                          const cuuint32_t*, const cuuint32_t*, CUtensorMapInterleave, CUtensorMapSwizzle,
                          CUtensorMapL2promotion, CUtensorMapFloatOOBfill);

static void enc3d(EncFn fn, CUtensorMap* tm, void* p, uint64_t d0, uint64_t d1, uint64_t d2, uint64_t s1, uint64_t s2, uint32_t b0,
                  uint32_t b1, uint32_t b2, CUtensorMapSwizzle sw, CUtensorMapL2promotion pr) {
  cuuint64_t gd[3] = {d0, d1, d2}, gs[2] = {s1, s2};
  cuuint32_t bx[3] = {b0, b1, b2}, es[3] = {1, 1, 1};
  fn(tm, CU_TENSOR_MAP_DATA_TYPE_BFLOAT16, 3, p, gd, gs, bx, es, CU_TENSOR_MAP_INTERLEAVE_NONE, sw, pr, CU_TENSOR_MAP_FLOAT_OOB_FILL_NONE);
}

namespace v9 {
typedef __nv_bfloat16 bf16;
#define SK 32768
#define SPIN_MAX (1 << 20)
template <int N> struct IC { static constexpr int value = N; };

__device__ __forceinline__ uint32_t s2u(const void* p) { return (uint32_t)__cvta_generic_to_shared(p); }
__device__ __forceinline__ float bflo(uint32_t u) { return __uint_as_float(u << 16); }
__device__ __forceinline__ float bfhi(uint32_t u) { return __uint_as_float(u & 0xffff0000u); }
__device__ __forceinline__ float u2f(uint32_t u) { return __uint_as_float(u); }
__device__ __forceinline__ void fma8(float* acc, uint4 v, float s) {
  acc[0] += s * bflo(v.x); acc[1] += s * bfhi(v.x); acc[2] += s * bflo(v.y); acc[3] += s * bfhi(v.y);
  acc[4] += s * bflo(v.z); acc[5] += s * bfhi(v.z); acc[6] += s * bflo(v.w); acc[7] += s * bfhi(v.w);
}
__device__ __forceinline__ uint32_t pack2(float a, float b) {
  __nv_bfloat162 p = __floats2bfloat162_rn(a, b); return *(uint32_t*)&p;
}
__device__ __forceinline__ float bfr(float v) { return bfhi(pack2(v, v)); }
__device__ __forceinline__ float silu_bf(float c) { return bfr(__fdividef(c, 1.f + __expf(-c))); }
#define fbits(v) ((__float_as_uint(v) & ~1u) | par)
__device__ __forceinline__ uint32_t pack2t(float a, float b, unsigned par) {
  const uint32_t ua = ((__float_as_uint(a) + ((par ^ 1) << 16)) & 0xFFFE0000u) | (par << 16);
  return __byte_perm(ua, pack2(b, b), 0x7632);
}
__device__ __forceinline__ void nbar(int id, int n) { asm volatile("bar.sync %0, %1;" ::"r"(id), "r"(n) : "memory"); }
__device__ __forceinline__ void nbar_arrive(int id, int n) { asm volatile("bar.arrive %0, %1;" ::"r"(id), "r"(n) : "memory"); }
__device__ __forceinline__ uint4 ldc16(const void* p) {
  uint4 v; asm volatile("ld.relaxed.cta.global.v4.u32 {%0,%1,%2,%3}, [%4];" : "=r"(v.x), "=r"(v.y), "=r"(v.z), "=r"(v.w) : "l"(p) : "memory"); return v;
}
__device__ __forceinline__ unsigned ldc4(const void* p) {
  unsigned v; asm volatile("ld.relaxed.cta.global.u32 %0, [%1];" : "=r"(v) : "l"(p) : "memory"); return v;
}
__device__ __forceinline__ uint4 ldx16(const void* p) {
  uint4 v; asm volatile("ld.relaxed.gpu.global.v4.u32 {%0,%1,%2,%3}, [%4];" : "=r"(v.x), "=r"(v.y), "=r"(v.z), "=r"(v.w) : "l"(p) : "memory"); return v;
}
__device__ __forceinline__ unsigned ldx4(const void* p) {
  unsigned v; asm volatile("ld.relaxed.gpu.global.u32 %0, [%1];" : "=r"(v) : "l"(p) : "memory"); return v;
}
__device__ __forceinline__ unsigned long long ldx64(const void* p) {
  unsigned long long v; asm volatile("ld.relaxed.gpu.global.u64 %0, [%1];" : "=l"(v) : "l"(p) : "memory"); return v;
}
__device__ __forceinline__ void stx16(void* p, uint4 v) {
  asm volatile("st.relaxed.gpu.global.v4.u32 [%0], {%1,%2,%3,%4};" ::"l"(p), "r"(v.x), "r"(v.y), "r"(v.z), "r"(v.w) : "memory");
}
__device__ __forceinline__ void stx8(void* p, uint2 v) { asm volatile("st.relaxed.gpu.global.v2.u32 [%0], {%1,%2};" ::"l"(p), "r"(v.x), "r"(v.y) : "memory"); }
__device__ __forceinline__ void stx4(void* p, unsigned v) { asm volatile("st.relaxed.gpu.global.u32 [%0], %1;" ::"l"(p), "r"(v) : "memory"); }
__device__ __forceinline__ void pub4(void* p, unsigned v) { asm volatile("red.relaxed.gpu.global.xor.b32 [%0], %1;" ::"l"(p), "r"(v) : "memory"); }
__device__ __forceinline__ void pub8(void* p, unsigned lo, unsigned hi) {
  asm volatile("{.reg .b64 t; mov.b64 t, {%1, %2}; red.relaxed.gpu.global.xor.b64 [%0], t;}" ::"l"(p), "r"(lo), "r"(hi) : "memory");
}
__device__ __forceinline__ unsigned lop_x3(unsigned a, unsigned b, unsigned c) {
  unsigned d; asm("lop3.b32 %0, %1, %2, %3, 0x7E;" : "=r"(d) : "r"(a), "r"(b), "r"(c)); return d; }
__device__ __forceinline__ unsigned or3(unsigned a, unsigned b, unsigned c) {
  unsigned d; asm("lop3.b32 %0, %1, %2, %3, 0xFE;" : "=r"(d) : "r"(a), "r"(b), "r"(c)); return d; }
__device__ __forceinline__ unsigned and3(unsigned a, unsigned b, unsigned c) {
  unsigned d; asm("lop3.b32 %0, %1, %2, %3, 0x80;" : "=r"(d) : "r"(a), "r"(b), "r"(c)); return d; }
__device__ __forceinline__ unsigned dep16(const uint32_t* f) {
  unsigned d = 0;
#pragma unroll
  for (int i = 0; i < 8; i++) d = or3(d, f[8 * i], f[8 * i + 4]);
  return d;
}
__device__ __forceinline__ uint2 ldx8(const void* p) {
  uint2 v; asm volatile("{.reg .b64 t; ld.relaxed.gpu.global.b64 t, [%2]; mov.b64 {%0, %1}, t;}" : "=r"(v.x), "=r"(v.y) : "l"(p) : "memory"); return v;
}
__device__ __forceinline__ float lds4(uint32_t a) { float v; asm volatile("ld.shared.f32 %0, [%1];" : "=f"(v) : "r"(a) : "memory"); return v; }
__device__ __forceinline__ float shx(float v, int m) {
  float r; asm volatile("shfl.sync.bfly.b32 %0, %1, %2, 0x1f, 0xffffffff;" : "=f"(r) : "f"(v), "r"(m)); return r;
}
__device__ __forceinline__ uint32_t mbar_test(uint32_t bar, uint32_t ph) {
  uint32_t ok;
  asm volatile("{.reg .pred p; mbarrier.test_wait.parity.shared::cta.b64 p, [%1], %2; vote.sync.all.pred p, p, 0xffffffff; selp.u32 %0, 1, 0, p;}"
               : "=r"(ok) : "r"(bar), "r"(ph) : "memory");
  return ok;
}
#define X16(v) (lop_x3(v.x, v.y, par) | lop_x3(v.z, v.w, par))
#define RETRY(bad) if (!__any_sync(~0u, (bad) & 1) || ++it_ >= SPIN_MAX) break;
#define POLL _Pragma("unroll 1") for (int it_ = 0;;)
__device__ __forceinline__ void mbar_wait(uint32_t bar, uint32_t ph = 0) {
  asm volatile("{.reg .pred p; .reg .u32 n; mov.u32 n, 0;\n"
               "W%=: mbarrier.try_wait.parity.shared::cta.b64 p, [%0], %1; add.u32 n, n, 1; setp.lt.and.u32 p, n, 0x100000, !p; @p bra W%=;}"
               ::"r"(bar), "r"(ph) : "memory");
}
__device__ __forceinline__ float ex2(float v) { float r; asm("ex2.approx.ftz.f32 %0, %1;" : "=f"(r) : "f"(v)); return r; }
__device__ __forceinline__ float rcp(float v) { float r; asm("rcp.approx.ftz.f32 %0, %1;" : "=f"(r) : "f"(v)); return r; }
__device__ __forceinline__ void mma16(float* d, const uint32_t* a, uint32_t b0, uint32_t b1) {
  asm volatile("mma.sync.aligned.m16n8k16.row.col.f32.bf16.bf16.f32 {%0,%1,%2,%3}, {%4,%5,%6,%7}, {%8,%9}, {%0,%1,%2,%3};"
               : "+f"(d[0]), "+f"(d[1]), "+f"(d[2]), "+f"(d[3]) : "r"(a[0]), "r"(a[1]), "r"(a[2]), "r"(a[3]), "r"(b0), "r"(b1));
}
__device__ __forceinline__ void mma16c(float* d, const uint32_t* a, uint32_t b0, uint32_t b1, const float* c) {
  asm volatile("mma.sync.aligned.m16n8k16.row.col.f32.bf16.bf16.f32 {%0,%1,%2,%3}, {%4,%5,%6,%7}, {%8,%9}, {%10,%11,%12,%13};"
               : "=f"(d[0]), "=f"(d[1]), "=f"(d[2]), "=f"(d[3])
               : "r"(a[0]), "r"(a[1]), "r"(a[2]), "r"(a[3]), "r"(b0), "r"(b1), "f"(c[0]), "f"(c[1]), "f"(c[2]), "f"(c[3]));
}
__device__ __forceinline__ float4 lds16(uint32_t a) {
  float4 v; asm volatile("ld.shared.v4.f32 {%0,%1,%2,%3}, [%4];" : "=f"(v.x), "=f"(v.y), "=f"(v.z), "=f"(v.w) : "r"(a) : "memory"); return v;
}
__device__ __forceinline__ uint4 ldsv16(uint32_t a) {
  uint4 v; asm volatile("ld.relaxed.cluster.shared.v4.u32 {%0,%1,%2,%3}, [%4];" : "=r"(v.x), "=r"(v.y), "=r"(v.z), "=r"(v.w) : "r"(a) : "memory"); return v;
}
__device__ __forceinline__ void sts4(uint32_t a, float v) { asm volatile("st.shared.f32 [%0], %1;" ::"r"(a), "f"(v) : "memory"); }
__device__ __forceinline__ void sts16(uint32_t a, uint4 v) {
  asm volatile("st.shared.v4.b32 [%0], {%1,%2,%3,%4};" ::"r"(a), "r"(v.x), "r"(v.y), "r"(v.z), "r"(v.w) : "memory");
}
__device__ __forceinline__ void ldsm_t(uint32_t* r, uint32_t a) {
  asm volatile("ldmatrix.sync.aligned.m8n8.x4.trans.shared.b16 {%0,%1,%2,%3}, [%4];" : "=r"(r[0]), "=r"(r[1]), "=r"(r[2]), "=r"(r[3]) : "r"(a) : "memory");
}
__device__ __forceinline__ void ldsm_tp(uint32_t* r, uint32_t a, uint32_t on) {
  asm volatile("{.reg .pred p; setp.ne.u32 p, %5, 0; @p ldmatrix.sync.aligned.m8n8.x4.trans.shared.b16 {%0,%1,%2,%3}, [%4];}"
               : "=r"(r[0]), "=r"(r[1]), "=r"(r[2]), "=r"(r[3]) : "r"(a), "r"(on) : "memory");
}
__device__ __forceinline__ void ldsm(uint32_t* r, uint32_t a) {
  asm volatile("ldmatrix.sync.aligned.m8n8.x4.shared.b16 {%0,%1,%2,%3}, [%4];" : "=r"(r[0]), "=r"(r[1]), "=r"(r[2]), "=r"(r[3]) : "r"(a) : "memory");
}
__device__ __forceinline__ uint32_t mapa(uint32_t a, uint32_t r) {
  uint32_t v; asm volatile("mapa.shared::cluster.u32 %0, %1, %2;" : "=r"(v) : "r"(a), "r"(r)); return v;
}
__device__ __forceinline__ unsigned long long mapg(uint32_t a, uint32_t r) {
  unsigned long long v;
  asm volatile("{.reg .u32 t; .reg .u64 u; mapa.shared::cluster.u32 t, %1, %2; cvt.u64.u32 u, t; cvta.shared::cluster.u64 %0, u;}" : "=l"(v) : "r"(a), "r"(r));
  return v;
}
template <int N>
__device__ __forceinline__ void tred(float* a, int lane, int m) {
  const bool hi = lane & m;
#pragma unroll
  for (int i = 0; i < N; i++) {
    float send = hi ? a[i] : a[i + N], keep = hi ? a[i + N] : a[i];
    a[i] = keep + __shfl_xor_sync(~0u, send, m);
  }
}
template <int N>
__device__ __forceinline__ void tmax(float* a, int lane, int m) {
  const bool hi = lane & m;
#pragma unroll
  for (int i = 0; i < N; i++) {
    float send = hi ? a[i] : a[i + N], keep = hi ? a[i + N] : a[i];
    a[i] = fmaxf(keep, __shfl_xor_sync(~0u, send, m));
  }
}
__device__ __forceinline__ void arrive_n(uint32_t bar, bool on, int cnt) {
  asm volatile("{.reg .pred p; setp.ne.s32 p, %1, 0; @p mbarrier.arrive.shared::cta.b64 _, [%0], %2;}" ::"r"(bar), "r"((int)on), "r"(cnt) : "memory");
}
__device__ __forceinline__ unsigned long long stream_policy() {
  unsigned long long p;
  asm volatile("createpolicy.fractional.L2::evict_first.b64 %0, 1.0;" : "=l"(p));
  return p;
}
__device__ __forceinline__ void tma3d(uint32_t dst, const CUtensorMap* tm, uint32_t bar, int c0, int c1, int c2) {
  asm volatile("cp.async.bulk.tensor.3d.shared::cluster.global.mbarrier::complete_tx::bytes.L2::cache_hint [%0], [%1, {%3, %4, %5}], [%2], %6;"
               ::"r"(dst), "l"(tm), "r"(bar), "r"(c0), "r"(c1), "r"(c2), "l"(stream_policy()) : "memory");
}
__device__ __forceinline__ void spin_until(unsigned t) { while ((int)((unsigned)clock() - t) < 0) {} }
__device__ __forceinline__ void wait_until(unsigned t) {
  unsigned now;
  do { asm volatile("mov.u32 %0, %%globaltimer_lo;" : "=r"(now)); } while ((int)(now - t) < 0);
}
__device__ __forceinline__ void sleep_until(unsigned t) {
  unsigned now;
#pragma unroll 1
  do {
    __nanosleep(200);
    asm volatile("mov.u32 %0, %%globaltimer_lo;" : "=r"(now));
  } while ((int)(now - t) < 0);
}
#define PIN(x) asm volatile("" : "+r"(x))
#define PINL(x) asm volatile("" : "+l"(x))
#define BAR_ARRIVE(i) asm volatile("mbarrier.arrive.shared::cta.b64 _, [%0];" ::"r"(bar0 + 8 * (i)) : "memory")
#define CNT_ADD(c) asm volatile("red.relaxed.gpu.global.inc.u32 [%0], 0xffffffff;" ::"l"(scr->cnt + (c)) : "memory")
#define BAR_INIT(i, cnt) asm volatile("mbarrier.init.shared::cta.b64 [%0], %1;" ::"r"(bar0 + 8 * (i)), "r"(cnt) : "memory")
#define BAR_ARM(i, bytes) asm volatile("mbarrier.arrive.expect_tx.shared::cta.b64 _, [%0], %1;" ::"r"(bar0 + 8 * (i)), "r"(bytes) : "memory")
struct TMaps { CUtensorMap m[9]; };

#define NCTA9 120
#define TAU 32.f
#define NSL 100
#define NPE 2
#define WTEST 600
#define NPO 3
#define VDLY 150
#define O_Q 131072
#define O_LZ 163840
#define O_CTX 196608
#define O_HZ 198656
#define O_HW 200704
#define O_X 201728
#define O_P 218112
#define O_B 222208
#define O_R 224512
#define O_SILU 228608
#define O_SM 229632
#define O_BAR 231424
#define O_EP (O_BAR + 256)
#define O_DBG (O_EP + 16)
#define SMEM9 (O_DBG + 128)
#define B_FULL 0
#define B_FM 8
#define B_EMPTY 10
#define B_EM 18
#define B_LZ 18
#define B_Q2 19
#define B_H 20
#define B_QF 21
#define B_TAB 22
#define B_W 23
#define B_ST 24
#define B_HZ 25
#define B_WZ 26
#define B_G2 28
#define B_G 27
enum { T_WQ, T_WUK, T_KV, T_MOD, T_UV, T_WO, T_GU, T_DN = 8 };
#define NBIG 40
struct Sched { unsigned t0, dth; uint2 r[3][8]; unsigned nr[3], nt[3], dt, t4, d7, d4, d6; };

struct __align__(128) Scratch {
  unsigned cnt[8 * 32];
  uint2 rec[32 * 4 * 8 * 64];
  uint2 hdr[32 * 16];
  unsigned h[8 * 256];
  uint4 qa[2048];
  unsigned xao[8 * 512];
  unsigned xf[32 * 56 * 16];
  unsigned xm[2048];
};
__device__ Scratch g_scr;
#define SMEM_BASE 1024u
#define DSC ((SMEM_BASE >> 4) | (1u << 16))
#define HI128 (64u | (1u << 30))
#define HI64 (32u | (2u << 30))
template <int TA, int TB, unsigned HIA, unsigned HIB>
__device__ __forceinline__ void wgmma32(float* d, uint32_t da, uint32_t db, int acc) {
  asm volatile("{.reg .pred p; .reg .b64 da, db; setp.ne.b32 p, %18, 0; mov.b64 da, {%16, %21}; mov.b64 db, {%17, %22};\n"
               "wgmma.mma_async.sync.aligned.m64n32k16.f32.bf16.bf16 "
               "{%0,%1,%2,%3,%4,%5,%6,%7,%8,%9,%10,%11,%12,%13,%14,%15}, da, db, p, 1, 1, %19, %20;}"
               : "+f"(d[0]), "+f"(d[1]), "+f"(d[2]), "+f"(d[3]), "+f"(d[4]), "+f"(d[5]), "+f"(d[6]), "+f"(d[7]),
                 "+f"(d[8]), "+f"(d[9]), "+f"(d[10]), "+f"(d[11]), "+f"(d[12]), "+f"(d[13]), "+f"(d[14]), "+f"(d[15])
               : "r"(da), "r"(db), "r"(acc), "n"(TA), "n"(TB), "n"(HIA), "n"(HIB));
}
__device__ __forceinline__ void wgmma32r(float* d, const uint32_t* a, uint32_t db) {
  asm volatile("{.reg .b64 db; mov.b64 db, {%20, %21};\n"
               "wgmma.mma_async.sync.aligned.m64n32k16.f32.bf16.bf16 "
               "{%0,%1,%2,%3,%4,%5,%6,%7,%8,%9,%10,%11,%12,%13,%14,%15}, {%16,%17,%18,%19}, db, 1, 1, 1, 1;}"
               : "+f"(d[0]), "+f"(d[1]), "+f"(d[2]), "+f"(d[3]), "+f"(d[4]), "+f"(d[5]), "+f"(d[6]), "+f"(d[7]),
                 "+f"(d[8]), "+f"(d[9]), "+f"(d[10]), "+f"(d[11]), "+f"(d[12]), "+f"(d[13]), "+f"(d[14]), "+f"(d[15])
               : "r"(a[0]), "r"(a[1]), "r"(a[2]), "r"(a[3]), "r"(db), "n"(HI64));
}
template <int N> __device__ __forceinline__ void wg_wait(float* a) {
  asm volatile("wgmma.wait_group.sync.aligned %16;"
               : "+f"(a[0]), "+f"(a[1]), "+f"(a[2]), "+f"(a[3]), "+f"(a[4]), "+f"(a[5]), "+f"(a[6]), "+f"(a[7]), "+f"(a[8]), "+f"(a[9]), "+f"(a[10]),
                 "+f"(a[11]), "+f"(a[12]), "+f"(a[13]), "+f"(a[14]), "+f"(a[15]) : "n"(N) : "memory");
}
__device__ __forceinline__ float sum8(uint32_t a) {
  const float4 p = lds16(a), q = lds16(a + 1024);
  return ((p.x + p.y) + (p.z + p.w)) + ((q.x + q.y) + (q.z + q.w));
}
__device__ __forceinline__ int posof(int c) { return (c & ~14) + 2 * (c & 6) + ((c >> 2) & 2); }

__global__ void __cluster_dims__(8, 1, 1) __launch_bounds__(384, 1)
fused_kernel(const bf16* __restrict__ x, const bf16* __restrict__ cvec, const bf16* __restrict__ w_mod, bf16* __restrict__ out,
             Scratch* __restrict__ scr, const __grid_constant__ Sched sch, const __grid_constant__ TMaps tms) {
  extern __shared__ __align__(1024) unsigned char smem[];
  const int tid = threadIdx.x, warp = __shfl_sync(~0u, tid >> 5, 0), lane = tid & 31;
  const int b = blockIdx.x, cl = b >> 3, rn = b & 7, rk = b & 1, hd = b >> 1, f = b - 64;
  const bool isA = b < 64;
  uint32_t sb = s2u(smem), bar0 = sb + O_BAR;
  unsigned gt_start;
  asm volatile("mov.u32 %0, %%globaltimer_lo;" : "=r"(gt_start));
  const int g = lane >> 2, tq = lane & 3;
  const int arow = 64 * rn + ((tid & 255) >> 4);
  uint4 wm[4];
  uint32_t cw, xw;
  if (warp < 8 && isA) {
    const bf16* wa = w_mod + (size_t)arow * 3072 + (lane & 8) * 64 + 64 * cl + 8 * (lane & 7);
#pragma unroll
    for (int i = 0; i < 4; i++) wm[i] = ldx16(wa + i * 16 * 3072);
    cw = ldc4(cvec + (arow & ~1) + 16 * tq);
    if (warp < 2) xw = ldc4(x + 64 * cl + (tid & 62));
  }
  if (warp == 11) {
    if (lane == 0) {
#pragma unroll
      for (int i = 0; i < B_EMPTY; i++) BAR_INIT(i, 1);
    }
    __syncwarp();
    asm volatile("fence.mbarrier_init.release.cluster;" ::: "memory");
    asm volatile("barrier.cluster.arrive.relaxed.aligned;" ::: "memory");
    if (isA) {
#pragma unroll 1
      for (int i = 0; i < 8; i++) {
        if (i >= 6) mbar_wait(bar0 + 8 * (i - 6));
        wait_until(gt_start + ((64 * i + b) * sch.dth >> 8));
        if (lane == 0) {
          BAR_ARM(i, 16384);
          tma3d(sb + i * 16384, &tms.m[i >> 2], bar0 + 8 * i, 0, i < 4 ? 128 * i : 256 * rk + 64 * (i - 4), i < 4 ? b : b & ~1);
        }
        __syncwarp();
      }
    }
  }
  if (warp == 10) {
    const unsigned ep = ldc4(&scr->cnt[0]);
    if (isA) {
      const uint4 xa = ldc16(x + 16 * lane), xb = ldc16(x + 16 * lane + 8);
      float xv[16] = {bflo(xa.x), bfhi(xa.x), bflo(xa.y), bfhi(xa.y), bflo(xa.z), bfhi(xa.z), bflo(xa.w), bfhi(xa.w),
                      bflo(xb.x), bfhi(xb.x), bflo(xb.y), bfhi(xb.y), bflo(xb.z), bfhi(xb.z), bflo(xb.w), bfhi(xb.w)};
      const float x0 = __shfl_sync(~0u, xv[0], 0);
      float s = 0, q = 0;
#pragma unroll
      for (int i = 0; i < 16; i++) { xv[i] -= x0; s += xv[i]; q += xv[i] * xv[i]; }
#pragma unroll
      for (int o = 16; o; o >>= 1) { s += __shfl_xor_sync(~0u, s, o); q += __shfl_xor_sync(~0u, q, o); }
      s *= 1.f / 512.f;
      float rstd;
      asm("rsqrt.approx.ftz.f32 %0, %1;" : "=f"(rstd) : "f"(fmaxf(q * (1.f / 512.f) - s * s, 0.f) + 1e-5f));
      *(float2*)(smem + O_SM + 1024) = make_float2(s + x0, rstd);
    }
    if (lane == 0) *(volatile unsigned*)(smem + O_EP) = ep;
    nbar_arrive(1, 288);
  }
  const int cls = isA ? (b >= NBIG) : 2, v0 = isA ? 2 : 0;
  if (warp >= 8) {
    asm volatile("setmaxnreg.dec.sync.aligned.u32 72;");
    if (warp == 8) {
      if (lane < 8) asm volatile("prefetch.tensormap [%0];" ::"l"(&tms.m[lane + 1]) : "memory");
      if ((sb & 0xFFFFFF) != SMEM_BASE) __trap();
    } else if (warp == 9) {
      if (lane == 0) {
#pragma unroll
        for (int i = B_EMPTY; i < B_EM; i++) BAR_INIT(i, 8);
        BAR_INIT(B_LZ, 8); BAR_INIT(B_Q2, 9); BAR_ARM(B_Q2, 1024);
        BAR_INIT(B_H, 1); BAR_INIT(B_QF, 1); BAR_ARM(B_QF, 32768);
        BAR_INIT(B_TAB, 1); BAR_INIT(B_W, 1); BAR_INIT(B_ST, 8); BAR_INIT(B_WZ, 1); BAR_INIT(B_G, 1); BAR_INIT(B_G2, 1);
      }

    }
    if (warp != 11) {
      __syncwarp();
      asm volatile("fence.mbarrier_init.release.cluster;" ::: "memory");
      __threadfence_block();
      asm volatile("barrier.cluster.arrive.relaxed.aligned;" ::: "memory");
    }
    asm volatile("barrier.cluster.wait.acquire.aligned;" ::: "memory");
    if (warp == 8) {
      const int nr = sch.nr[cls], vl = v0 + sch.nt[cls] - 1;
      unsigned long long hist = 0;
      int v = v0;
#pragma unroll 1
      for (int rd = 0; rd < nr; rd++) {
        const uint2 e = sch.r[cls][rd];
        const int type = e.y & 15, win = (e.y >> 4) & 15, pos = b + 64 - (int)((e.y >> 8) & 255), tile = e.y >> 16;
        const bool mod = type == T_MOD;
        const int ni = mod ? 1 : type == T_DN ? 2 : 4;
        unsigned t = gt_start + (e.x & 0xffff) + (pos * sch.dt >> 8);
        const int c0 = mod ? 1024 + 32 * b : type == T_WO ? 64 * rn : type == T_GU ? 32 * f : 0;
        int c1 = type == T_KV ? 64 * (tile + pos) : type == T_DN ? 32 * f : 0;
        int c2 = mod ? tile : type == T_WO ? 4 * cl : type == T_UV ? b : 0;
        const int i1 = type == T_DN ? 16 : type == T_UV ? 128 : 0;
#pragma unroll 1
        for (int j = 0; j < ni; j++) {
          const int slot = mod ? B_FM + tile : (v & 1) * 4 + j;
          if (mod ? tile : v >= 2) mbar_wait(bar0 + 8 * (B_EMPTY + (mod ? (vl & 1) * 4 : slot)), mod ? (vl >> 1) & 1 : ((v >> 1) - 1) & 1);
          const int hw = (int)(hist >> (6 * (win - 1))) & 63;
          if (hw) mbar_wait(bar0 + 8 * (hw & 15), (hw >> 4) & 1);
          wait_until(t);
          if (lane == 0) {
            BAR_ARM(slot, 16384);
            tma3d(sb + (mod ? (tile ? O_Q : O_X) : slot * 16384), &tms.m[type == T_GU ? type + (j & 1) : type], bar0 + 8 * slot, c0, c1, c2);
          }
          __syncwarp();
          hist = hist << 6 | (32 | (mod ? 0 : (v & 2) << 3) | slot);
          t += e.x >> 16; c1 += i1;
          c2 += type == T_KV ? 2 : type == T_WO ? 1 : type == T_GU ? j & 1 : 0;
        }
        v += !mod;
      }
      return;
    }
    const unsigned epoch = *(volatile unsigned*)(smem + O_EP), par = (epoch + 1) & 1;
    if (warp == 10) {
      if (isA) {
        for (int it = 0; ldx4(scr->cnt + 1) != (epoch + 1) * 128 && it < SPIN_MAX; it++) {}
        if (lane == 0) BAR_ARRIVE(B_H);
      } else mbar_wait(bar0);
      for (int it = 0; ldx4(scr->cnt + 32 + 32 * (rn >> 2)) != (epoch + 1) * 32 && it < SPIN_MAX; it++) {}
      if (lane == 0)
        asm volatile("cp.async.bulk.shared::cluster.global.mbarrier::complete_tx::bytes.multicast::cluster [%0], [%1], 4096, [%2], %3;"
                     ::"r"(sb + O_Q + rn * 4096), "l"(scr->qa + rn * 256), "r"(bar0 + 8 * B_QF), "h"((unsigned short)0xff) : "memory");
      const unsigned dl = isA ? sch.d4 : sch.d6;
      unsigned tw = gt_start + sch.t4;
      if (!isA) {
        const int nt = sch.nt[2];
#pragma unroll 1
        for (int t = 0; t < nt; t++) mbar_wait(bar0 + 8 * B_EMPTY + (t & 1) * 32 + 24, (t >> 1) & 1);
        unsigned long long now;
        asm volatile("mov.u64 %0, %%globaltimer;" : "=l"(now));
        if (lane == 0) { asm volatile("red.relaxed.gpu.global.max.u64 [%0], %1;" ::"l"(scr->cnt + 130), "l"(now) : "memory"); CNT_ADD(128); }
        tw = (unsigned)now + 1700;
      }
      sleep_until(tw);
      uint4 an;
      for (int it = 0; an = ldx16(scr->cnt + 128), an.x != (epoch + 1) * 56 && it < SPIN_MAX; it++) {}
      wait_until(an.z + (dl >> 16));
      if (lane == 0) BAR_ARRIVE(B_G2);
      wait_until(an.z + (dl & 0xffff));
      if (lane == 0) BAR_ARRIVE(B_G);
    } else if (warp == 11) {
      {
        uint2* ph = scr->hdr + ((lane & 24) + 2 * tq + (g & 1)) * 16 + cl;
        const bool own = (lane >> 4) * 4 + tq == rn;
        if (own) { stx8(ph, make_uint2(par ^ 1, 0)); if (cl == 14) stx8(ph + 1, make_uint2(0, 0)); }
        uint32_t a_w = sb + O_HW + ((lane >> 4) * 4 + tq) * 128 + (g & 1) * 64 + ((lane >> 1) & 4);
        PIN(a_w); PINL(ph);
        const int vt = v0 + sch.nt[cls];
#pragma unroll 1
        for (int t = 0; t < vt; t++) mbar_wait(bar0 + 8 * B_EMPTY + (t & 1) * 32 + 24, (t >> 1) & 1);
        float hz[8], M;
        uint32_t wp[4];
#pragma unroll 1
        for (int e = 0; e < 2; e++) {
          POLL {
            unsigned ok = 1;
#pragma unroll
            for (int u = 0; u < 8; u++)
              asm volatile("ld.relaxed.cluster.shared.f32 %0, [%1];" : "=f"(hz[u]) : "r"(sb + O_HZ + e * 1024 + u * 128 + lane * 4) : "memory");
#pragma unroll
            for (int u = 0; u < 4; u++) ok = and3(ok, __float_as_uint(hz[u]), __float_as_uint(hz[u + 4]));
            RETRY(~ok)
          }
          if (e) break;
          M = fmaxf(fmaxf(fmaxf(hz[0], hz[1]), fmaxf(hz[2], hz[3])), fmaxf(fmaxf(hz[4], hz[5]), fmaxf(hz[6], hz[7])));
          M = u2f(fbits(M));
#pragma unroll
          for (int u = 0; u < 4; u++) {
            wp[u] = pack2(ex2(hz[u] - M), ex2(hz[u + 4] - M));
            sts4(a_w + ((rn - u) & 3) * 8, u2f(wp[u])); sts4(a_w + ((rn - u) & 3) * 8 + 32, u2f(wp[u]));
          }
          __syncwarp();
          if (lane == 0) BAR_ARRIVE(B_WZ);
        }
        float L = 0.f;
#pragma unroll
        for (int u = 0; u < 4; u++) L += bflo(wp[u]) * hz[u] + bfhi(wp[u]) * hz[u + 4];
        if (own) pub8(ph, __float_as_uint(M) | 1u, __float_as_uint(L));
      }
      if (isA) {
        mbar_wait(bar0 + 8 * B_G2);
        unsigned long long hh;
        POLL { hh = ldx64(scr->hdr + hd * 16 + (lane & 15)); RETRY((lane & 15) == 15 ? 0u : (unsigned)hh ^ par) }
        const float m = (lane & 15) == 15 ? -1e30f : u2f((unsigned)hh);
        int mi = __float_as_int(m);
        mi ^= (mi >> 31) & 0x7fffffff;
        mi = __reduce_max_sync(~0u, mi);
        mi ^= (mi >> 31) & 0x7fffffff;
        const float w = ex2(m - __int_as_float(mi));
        float L = w * u2f(hh >> 32);
#pragma unroll
        for (int o2 = 8; o2; o2 >>= 1) L += __shfl_xor_sync(~0u, L, o2);
        sts4(sb + O_SM + (384 + 2 * (lane & 6) + ((lane >> 2) & 2) + (lane & 1)) * 4, w * rcp(L));
        __syncwarp();
        if (lane == 0) BAR_ARRIVE(B_W);
      }
    } else {
#pragma unroll 4
      for (int i = 0; i < 72; i++) sts16(sb + O_LZ + i * 512 + lane * 16, make_uint4(0, 0, 0, 0));
      __syncwarp();
      if (lane < 8) asm volatile("mbarrier.arrive.release.cluster.shared::cluster.b64 _, [%0];" ::"r"(mapa(bar0 + 8 * B_LZ, lane)) : "memory");
      if (isA) {
        mbar_wait(bar0 + 8 * B_QF);
#pragma unroll 2
        for (int k = 0; k < 8; k++) {
          const uint32_t cp = ldc4(cvec + 2 * (lane + 32 * k));
          *(uint32_t*)(smem + O_SILU + (lane + 32 * k) * 4) = pack2(silu_bf(bflo(cp)), silu_bf(bfhi(cp)));
        }
        __syncwarp();
        uint32_t ab = sb + O_X + (8 * (lane >> 4) + (lane & 7)) * 64 + ((((lane >> 3) & 1) ^ ((lane >> 1) & 3)) << 4);
        float d[4][4] = {};
#pragma unroll 1
        for (int jm = 0; jm < 2; jm++) {
          mbar_wait(bar0 + 8 * (B_FM + jm));
#pragma unroll 2
          for (int s2 = 0; s2 < 8; s2++)
#pragma unroll
            for (int s = 0; s < 2; s++) {
              uint32_t a0[4], a1[4];
              const uint32_t* ps = (const uint32_t*)(smem + O_SILU) + 128 * jm + 16 * s2 + 8 * s + tq;
              ldsm_t(a0, ab + (2 * s2 + s) * 1024); ldsm_t(a1, (ab + (2 * s2 + s) * 1024) ^ 32);
              mma16(d[s], a0, ps[0], ps[4]); mma16(d[2 + s], a1, ps[0], ps[4]);
            }
          ab -= O_X - O_Q;
        }
        const float t0 = (tq & 1) ? d[0][2] + d[1][2] : d[0][0] + d[1][0], t1 = (tq & 1) ? d[2][2] + d[3][2] : d[2][0] + d[3][0];
        stx4(scr->xm + b * 32 + posof(8 * tq + g), fbits(bfr(bfr((tq & 2) ? t1 : t0) + ((b >> 4) == 2 ? 1.f : 0.f))));
        __syncwarp();
        if (lane == 0) CNT_ADD(96);
      } else sleep_until(gt_start + sch.t4);
      for (int it = 0; ldx4(scr->cnt + 96) != (epoch + 1) * 64 && it < SPIN_MAX; it++) __nanosleep(NSL);
      if (isA) {
        unsigned long long ga;
        POLL { ga = ldx64(scr->xm + 64 * rn + 2 * lane); RETRY(lop_x3((unsigned)ga, ga >> 32, par)) }
        *(float2*)(smem + O_SM + (320 + 2 * lane) * 4) = make_float2(bfhi((unsigned)ga), bfhi(ga >> 32));
      }
      __syncwarp();
      if (lane == 0) BAR_ARRIVE(B_TAB);
    }
    return;
  }

  float* s_sm = (float*)(smem + O_SM);
  unsigned par, epoch;
  asm volatile("barrier.cluster.arrive.relaxed.aligned;" ::: "memory");
  if (isA) {
    float* s_r = (float*)(smem + O_R);
    float acc[8] = {0, 0, 0, 0, 0, 0, 0, 0};
    const float sl = silu_bf((arow & 1) ? bfhi(cw) : bflo(cw));
#pragma unroll
    for (int i = 0; i < 4; i++) fma8(acc, wm[i], __shfl_sync(~0u, sl, i, 4));
    tred<4>(acc, lane, 16);
    *(float4*)(s_r + warp * 128 + 8 * (lane & 15) + ((lane >> 2) & 4)) = make_float4(acc[0], acc[1], acc[2], acc[3]);
    nbar(1, 288);
    epoch = *(volatile unsigned*)(smem + O_EP);
    par = (epoch + 1) & 1;
    if (warp < 2) {
      float t = 0.f, ca = rn == 0 ? 1.f : 0.f;
#pragma unroll
      for (int w = 0; w < 8; w++) { t += s_r[w * 128 + tid]; ca += s_r[w * 128 + 64 + tid]; }
      t += ca * ((((tid & 1) ? bfhi(xw) : bflo(xw)) - s_sm[256]) * s_sm[257]);
      const float nb = __shfl_down_sync(~0u, t, 1);
      const uint32_t w0 = lane < 8 ? pack2t(t, nb, par) : pack2(t, nb);
      const uint32_t w1 = __shfl_down_sync(~0u, w0, 8), w2 = __shfl_down_sync(~0u, w0, 16), w3 = __shfl_down_sync(~0u, w0, 24);
      if (lane < 8 && !(lane & 1)) stx16(scr->h + (rn >> 1) * 512 + (2 * cl + warp) * 32 + rk * 16 + 2 * lane, make_uint4(w0, w1, w2, w3));
      __syncwarp();
      if (lane == 0) CNT_ADD(1);
    }
    asm volatile("barrier.cluster.wait.acquire.aligned;" ::: "memory");
    const uint32_t rsb = mapa(sb, rn ^ 1);
    {
      uint32_t a[4][4][4];
      mbar_wait(bar0 + 8 * (warp >> 1));
      const uint32_t ab = sb + (64 * warp + 8 * (lane >> 4) + (lane & 7)) * 128;
#pragma unroll
      for (int s = 0; s < 4; s++)
#pragma unroll
        for (int mt = 0; mt < 4; mt++) ldsm_t(a[s][mt], ab + s * 2048 + (((2 * mt + ((lane >> 3) & 1)) ^ (lane & 7)) << 4));
      arrive_n(bar0 + 8 * (B_EMPTY + (warp >> 1)), lane == 0, 4 + (dep16(&a[0][0][0]) & (sch.t0 >> 24)));
      uint4 v0, v1;
      const unsigned* ph = scr->h + (g >> 1) * 512 + 64 * warp + 4 * (lane & 7);
      uint32_t off = O_B + warp * 272 + (32 * rk + 8 * tq + (lane & 4)) * 4;
      PIN(off); PINL(ph);
      mbar_wait(bar0 + 8 * B_H);
      POLL { v0 = ldx16(ph); v1 = ldx16(ph + 32); RETRY(lop_x3(v0.x, v1.x, par)) }
      float d[4][4] = {};
#pragma unroll
      for (int mt = 0; mt < 4; mt++) {
        mma16(d[mt], a[0][mt], v0.x, v0.y); mma16(d[mt], a[1][mt], v0.z, v0.w);
        mma16(d[mt], a[2][mt], v1.x, v1.y); mma16(d[mt], a[3][mt], v1.z, v1.w);
      }
      float r[8];
#pragma unroll
      for (int mt = 0; mt < 4; mt++) { r[2 * mt] = d[mt][0] + d[mt][1]; r[2 * mt + 1] = d[mt][2] + d[mt][3]; }
      tred<4>(r, lane, 2); tred<2>(r, lane, 1);
      const float rc = __shfl_xor_sync(~0u, (lane & 4) ? r[0] : r[1], 4);
      const uint32_t wd = (lane & 4) ? pack2(rc, r[1]) : pack2(r[0], rc);
      const uint32_t w1 = __shfl_down_sync(~0u, wd, 8), w2 = __shfl_down_sync(~0u, wd, 16), w3 = __shfl_down_sync(~0u, wd, 24);
      asm volatile("{.reg .pred p; setp.lt.s32 p, %7, 8; @p st.shared.v4.b32 [%0], {%2,%3,%4,%5};\n"
                   "@p st.async.shared::cluster.mbarrier::complete_tx::bytes.v4.b32 [%1], {%2,%3,%4,%5}, [%6];}"
                   ::"r"(sb + off), "r"(rsb + off), "r"(wd), "r"(w1), "r"(w2), "r"(w3), "r"(rsb + O_BAR + 8 * B_Q2), "r"(lane) : "memory");
      __syncwarp();
      arrive_n(bar0 + 8 * B_Q2, lane == 0, 1);
    }
    {
      uint32_t a[2][8][4];
      uint32_t a_bq = sb + O_B + (lane & 7) * 272 + (lane >> 3) * 16;
      uint4* p_qa = scr->qa + (4 * rk + (warp >> 1)) * 256 + hd * 8 + ((4 * (warp & 1) + tq) ^ (hd & 7));
      PIN(a_bq); PINL(p_qa);
      mbar_wait(bar0 + 8 * (4 + (warp >> 1)));
      const uint32_t ab = sb + 65536 + (warp >> 1) * 16384 + (32 * (warp & 1) + (lane & 15)) * 128;
#pragma unroll
      for (int i = 0; i < 16; i++) ldsm(a[i >> 3][i & 7], ab + (i >> 3) * 2048 + ((i >> 2) & 1) * 8192 + (((2 * (i & 3) + (lane >> 4)) ^ (lane & 7)) << 4));
      arrive_n(bar0 + 8 * (B_EMPTY + 4 + (warp >> 1)), lane == 0, 4 + (dep16(&a[0][0][0]) & (sch.t0 >> 24)));
      mbar_wait(bar0 + 8 * B_Q2);
      float d[4][4] = {};
#pragma unroll
      for (int y = 0; y < 4; y++) {
        uint32_t bq[4];
        ldsm(bq, a_bq + 64 * y);
#pragma unroll
        for (int mt = 0; mt < 2; mt++) { mma16(d[2 * mt], a[mt][2 * y], bq[0], bq[1]); mma16(d[2 * mt + 1], a[mt][2 * y + 1], bq[2], bq[3]); }
      }
      float r[4];
#pragma unroll
      for (int i = 0; i < 4; i++) r[i] = (d[i & 2][2 * (i & 1)] + d[i & 2][2 * (i & 1) + 1]) + (d[(i & 2) + 1][2 * (i & 1)] + d[(i & 2) + 1][2 * (i & 1) + 1]);
      tred<2>(r, lane, 2); tred<1>(r, lane, 1);
      const float nb = __shfl_xor_sync(~0u, r[0], 4);
      const uint32_t w0 = (lane >> 3) == (hd & 3) ? pack2t(r[0], nb, par) : pack2(r[0], nb);
      const uint32_t w1 = __shfl_down_sync(~0u, w0, 8), w2 = __shfl_down_sync(~0u, w0, 16), w3 = __shfl_down_sync(~0u, w0, 24);
      if (lane < 4) stx16(p_qa, make_uint4(w0, w1, w2, w3));
      if (warp) nbar_arrive(3, 256); else { nbar(3, 256); if (lane == 0) CNT_ADD(32 + 32 * rk); }
    }
  } else {
    nbar(1, 288);
    epoch = *(volatile unsigned*)(smem + O_EP);
    par = (epoch + 1) & 1;
    asm volatile("barrier.cluster.wait.acquire.aligned;" ::: "memory");
    mbar_wait(bar0);
  }
  asm volatile("setmaxnreg.inc.sync.aligned.u32 216;");
  uint2* p_rec = scr->rec + ((16 * (warp >> 2) + 2 * (warp & 3) + (g & 1) + 4 * (tq & 2)) * 32 + 4 * rn + (tq & 1)) * 64 + cl * 4 + (g >> 1);
  PINL(p_rec);
  {
    const unsigned inv = par ^ 1;
#pragma unroll
    for (int q = 0; q < 2; q++) { stx8(p_rec + q * 128, make_uint2(inv, 0)); if (cl == 14) stx8(p_rec + q * 128 + 4, make_uint2(0, 0)); }
    if (isA) { if (warp < 2) stx4(scr->xao + b * 64 + tid, inv); }
    else stx8(scr->xf + ((4 * warp + tq) * 56 + f) * 16 + 2 * g, make_uint2(inv, 0));
  }
  sb = __shfl_sync(~0u, sb, 0); bar0 = sb + O_BAR;
  const int nt = sch.nt[cls], wg = warp >> 2;
  uint32_t a_z[4];
#pragma unroll
  for (int u = 0; u < 4; u++) {
    const int s3 = (rn - u - (lane >> 1 & 1)) & 3;
    a_z[u] = sb + O_LZ + (s3 + 4 * (lane & 1)) * 4096 + wg * 512 + g * 64 + (((warp & 3) ^ (s3 & 1) ^ (2 * (lane & 1))) << 4);
    PIN(a_z[u]);
  }
  uint32_t z[4][4], a_w = sb + O_HW + warp * 128 + (g & 1) * 64 + (tq & 1) * 8;
  PIN(a_w);
  {
    const float sc = 0.08838834764831845f * 1.4426950408889634f;
    const uint32_t a_pm = sb + O_SM + lane * 16;
    float mrun = -1e30f;
    float o[4][16], sx[16], mref[8];
#pragma unroll
    for (int k = 0; k < 16; k++) { o[0][k] = o[1][k] = o[2][k] = o[3][k] = sx[k] = 0.f; mref[k >> 1] = -1e30f; }
    const int key = 16 * warp + (lane & 15);
    uint32_t a_p = sb + O_P + key * 64 + (((lane >> 4) ^ ((key >> 1) & 3)) << 4);
    uint32_t a_v = sb + wg * 32768 + (8 * (lane >> 4) + (lane & 7)) * 128 + (((2 * (warp & 3) + ((lane >> 3) & 1)) ^ (lane & 7)) << 4);
    const int rot = rn + warp;
    unsigned long long dst[4];
#pragma unroll
    for (int q = 0; q < 4; q++) {
      dst[q] = mapg(sb + O_LZ + rn * 4096 + (warp & 3) * 1024 + g * 64 + ((tq ^ (rn & 1) ^ ((rn >> 1) & 2)) << 4), 4 * wg + ((q + rot) & 3));
      PINL(dst[q]);
    }
    unsigned long long a_h = mapg(sb + O_HZ + wg * 1024 + rn * 128 + lane * 4, 2 * (warp & 3));
    unsigned long long a_h1 = mapg(sb + O_HZ + wg * 1024 + rn * 128 + lane * 4, 2 * (warp & 3) + 1);
    PIN(a_p); PIN(a_v); PINL(a_h); PINL(a_h1);
    uint32_t rel = lane < 4 && lane >= 2 * wg ? 2 - (tq >> 1) : 0;
    PIN(rel);
    uint32_t ones[4] = {0x3F803F80u, 0x3F803F80u, 0x3F803F80u, 0x3F803F80u};
    PIN(ones[0]); PIN(ones[1]); PIN(ones[2]); PIN(ones[3]);
    {
      asm volatile("{.reg .pred p; .reg .u32 n; mov.u32 n, 0;\n"
                   "W%=: mbarrier.try_wait.parity.acquire.cluster.shared::cta.b64 p, [%0], 0; add.u32 n, n, 1; setp.lt.and.u32 p, n, 0x100000, !p; @p bra W%=;}"
                   ::"r"(bar0 + 8 * B_LZ) : "memory");
      mbar_wait(bar0 + 8 * B_QF);
      unsigned bad = 0;
#pragma unroll
      for (int k = 0; k < 8; k++) bad |= __float_as_uint(lds4(sb + O_Q + k * 4096 + tid * 16 + (lane >> 3) * 4)) ^ par;
      if (__builtin_expect(__any_sync(~0u, bad & 1), 0)) {
#pragma unroll 1
        for (int k = 0; k < 8; k++) {
          uint4 v;
          POLL { v = ldx16(scr->qa + k * 256 + tid); RETRY(((lane & 16) ? ((lane & 8) ? v.w : v.z) : ((lane & 8) ? v.y : v.x)) ^ par) }
          sts16(sb + O_Q + k * 4096 + tid * 16, v);
        }
        asm volatile("fence.proxy.async.shared::cta;" ::: "memory");
      }
      if (warp >= 4) nbar_arrive(1, 256); else nbar(1, 256);
    }
#pragma unroll 1
    for (int t = 0; t < nt; t++) {
      const int v = v0 + t;
      const uint32_t fb = bar0 + (v & 1) * 32, ph = (v >> 1) & 1, av = a_v + (v & 1) * 65536;
      uint32_t vf[4][4][4], cnt;
      auto landed = [&]() {
        cnt = rel + (dep16(&vf[0][0][0]) & (nt >> 8));
        PIN(cnt);
      };
      if (wg == 0) {
        const uint32_t da = DSC + (v & 1) * 4096, db = DSC + O_Q / 16;
#pragma unroll
        for (int jj = 0; jj < 2; jj++) {
#pragma unroll 1
          for (int j = 2 * jj; j < 2 * jj + 2; j++) {
            mbar_wait(fb + 8 * j, ph);
            asm volatile("wgmma.fence.sync.aligned;" ::: "memory");
#pragma unroll
            for (int k = 0; k < 8; k++)
              wgmma32<0, 0, HI128, HI128>(sx, da + j * 1024 + (k >> 2) * 512 + (k & 3) * 2, db + j * 512 + (k >> 2) * 256 + (k & 3) * 2, jj || k ? 1 : j);
            asm volatile("wgmma.commit_group.sync.aligned;" ::: "memory");
          }
          if (jj == 0) {
#pragma unroll
            for (int i = 0; i < 16; i++) ldsm_t(vf[i >> 2][i & 3], av + (((i >> 2) + rot) & 3) * 8192 + (i & 3) * 2048);
            nbar(5, 256);
            landed();
          }
        }
      } else {
        nbar_arrive(5, 256);
#pragma unroll 1
        for (int j = 0; j < 2; j++) {
          mbar_wait(fb + 16 + 8 * j, ph);
          if (j) spin_until(clock() + VDLY);
#pragma unroll
          for (int q = 0; q < 4; q++)
            if (((q + rot) & 2) == 2 * j)
#pragma unroll
              for (int k = 0; k < 4; k++) ldsm_t(vf[q][k], av + ((q + rot) & 3) * 8192 + k * 2048);
        }
        landed();
      }
      wg_wait<0>(sx);
      asm volatile("{.reg .pred p; setp.ne.s32 p, %1, 0; @p mbarrier.arrive.shared::cta.b64 _, [%0], %1;}" ::"r"(fb + 8 * B_EMPTY + 8 * tq), "r"(cnt) : "memory");
#pragma unroll 1
      for (int pass = 0;; pass++) {
        int ex = !(t | pass);
        if (wg == 0 && (t | pass)) {
          float mx = -1e30f;
#pragma unroll
          for (int i = 0; i < 8; i++) mx = fmaxf(mx, fmaxf(sx[2 * (i & 6) + (i & 1)], sx[2 * (i & 6) + (i & 1) + 2]) * sc - mref[i]);
          ex = mx > TAU;
          uint32_t pk[8];
#pragma unroll
          for (int i = 0; i < 8; i++) pk[i] = pack2(ex2(sx[2 * i] * sc - mref[i & 6]), ex2(sx[2 * i + 1] * sc - mref[(i & 6) + 1]));
#pragma unroll
          for (int u = 0; u < 2; u++)
            asm volatile("stmatrix.sync.aligned.m8n8.x4.shared.b16 [%0], {%1,%2,%3,%4};"
                         ::"r"(a_p ^ (u << 5)), "r"(pk[4 * u]), "r"(pk[4 * u + 1]), "r"(pk[4 * u + 2]), "r"(pk[4 * u + 3]) : "memory");
          asm volatile("fence.proxy.async.shared::cta;" ::: "memory");
        }
        asm volatile("{.reg .pred p, q; setp.ne.s32 q, %0, 0; bar.red.or.pred p, 4, 256, q; selp.s32 %0, 1, 0, p;}" : "+r"(ex)::"memory");
        if (!ex || pass) break;
        if (wg == 0) {
          float cm[8];
#pragma unroll
          for (int i = 0; i < 8; i++) cm[i] = fmaxf(sx[2 * (i & 6) + (i & 1)], sx[2 * (i & 6) + (i & 1) + 2]);
          tmax<4>(cm, lane, 16); tmax<2>(cm, lane, 8); tmax<1>(cm, lane, 4);
          sts4(a_pm + warp * 4, cm[0] * sc);
        }
        nbar(4, 256);
        const float4 pm = lds16(a_pm);
        const float mn = u2f(__float_as_uint(fmaxf(fmaxf(fmaxf(pm.x, pm.y), fmaxf(pm.z, pm.w)), mrun)) | 1u), al = ex2(mrun - mn);
        mrun = mn;
#pragma unroll
        for (int i = 0; i < 8; i++) {
          const float a = __shfl_sync(~0u, al, 4 * i + tq), aw = wg ? a : 1.f;
          mref[i] = __shfl_sync(~0u, mn, 4 * i + tq);
#pragma unroll
          for (int e = 0; e < 2; e++) {
            const int k = 2 * (i & 6) + (i & 1) + 2 * e;
            o[0][k] *= a; o[1][k] *= a; o[2][k] *= a; o[3][k] *= a; sx[k] *= aw;
          }
        }
      }
      float hv = mrun;
      if (wg) {
        asm volatile("wgmma.fence.sync.aligned;" ::: "memory");
#pragma unroll
        for (int k = 0; k < 4; k++) wgmma32r(sx, ones, DSC + O_P / 16 + k * 64);
        asm volatile("wgmma.commit_group.sync.aligned;" ::: "memory");
        wg_wait<0>(sx);
        float lv[4];
#pragma unroll
        for (int j = 0; j < 4; j++) lv[j] = (lane & 4) ? sx[4 * j + 1] : sx[4 * j];
        hv = (lane & 16) ? ((lane & 8) ? lv[3] : lv[2]) : ((lane & 8) ? lv[1] : lv[0]);
      }
      asm volatile("{.reg .pred p; setp.eq.s32 p, %3, %4; @p st.relaxed.cluster.b32 [%0], %1; @p st.relaxed.cluster.b32 [%2], %1;}"
                   ::"l"(a_h), "r"(__float_as_uint(hv) | 1u), "l"(a_h1), "r"(t), "r"(nt - 1) : "memory");
#pragma unroll
      for (int q = 0; q < 4; q++) {
        asm volatile("wgmma.fence.sync.aligned;" ::: "memory");
#pragma unroll
        for (int k = 0; k < 4; k++) wgmma32r(o[q], vf[q][k], DSC + O_P / 16 + k * 64);
        asm volatile("wgmma.commit_group.sync.aligned;" ::: "memory");
        if (q == 3) {
#pragma unroll
          for (int u = 0; u < 4; u++) ldsm_t(z[u], a_z[u] + u * 1024);
        }
        wg_wait<0>(o[q]);
#pragma unroll
        for (int j = 0; j < 2; j++)
          asm volatile("{.reg .pred p; setp.eq.s32 p, %5, %6; @p st.relaxed.cluster.v4.b32 [%0], {%1,%2,%3,%4};}"
                       ::"l"(dst[q] + j * 512), "r"(pack2t(o[q][8 * j], o[q][8 * j + 1], 1)), "r"(pack2(o[q][8 * j + 2], o[q][8 * j + 3])),
                         "r"(pack2(o[q][8 * j + 4], o[q][8 * j + 5])), "r"(pack2(o[q][8 * j + 6], o[q][8 * j + 7])), "r"(t), "r"(nt - 1) : "memory");
      }
    }
  }
  {
    uint32_t wx[4][4];
    mbar_wait(bar0 + 8 * B_WZ);
#pragma unroll
    for (int u = 0; u < 4; u++) {
      uint2 wp;
      asm volatile("ld.shared.v2.u32 {%0, %1}, [%2];" : "=r"(wp.x), "=r"(wp.y) : "r"(a_w + u * 8) : "memory");
      const bool lo = (g >> 1) == (tq >> 1), hi = (g >> 1) == 2 + (tq >> 1);
      wx[u][0] = lo ? wp.x : 0u; wx[u][1] = lo ? wp.y : 0u; wx[u][2] = hi ? wp.x : 0u; wx[u][3] = hi ? wp.y : 0u;
    }
    auto bad = [&]() {
      const unsigned ok = and3(and3(and3(z[0][0], z[0][1], z[0][2]), and3(z[0][3], z[1][0], z[1][1]), and3(z[1][2], z[1][3], z[2][0])),
                               and3(and3(z[2][1], z[2][2], z[2][3]), and3(z[3][0], z[3][1], z[3][2]), z[3][3]), 0x10001u);
      return __any_sync(~0u, g == 0 && ok != 0x10001u);
    };
    POLL {
      if (it_)
#pragma unroll
        for (int u = 0; u < 4; u++) ldsm_t(z[u], a_z[u] + u * 1024);
      if (!bad() || ++it_ >= SPIN_MAX) break;
    }
    float d0[8][4] = {}, d[8][4], r[8];
#pragma unroll
    for (int i = 0; i < 8; i++) mma16(d0[i], wx[i >> 1], z[i >> 1][2 * (i & 1)], z[i >> 1][2 * (i & 1) + 1]);
    POLL {
#pragma unroll
      for (int u = 0; u < 4; u++) ldsm_t(z[u], a_z[u ^ 2] + u * 1024);
#pragma unroll
      for (int i = 0; i < 8; i++) mma16c(d[i], wx[(i >> 1) ^ 2], z[i >> 1][2 * (i & 1)], z[i >> 1][2 * (i & 1) + 1], d0[i]);
      if (!bad() || ++it_ >= SPIN_MAX) break;
    }
#pragma unroll
    for (int i = 0; i < 8; i++) r[i] = (tq & 2) ? ((g & 1) ? d[i][3] : d[i][2]) : ((g & 1) ? d[i][1] : d[i][0]);
#pragma unroll
    for (int q = 0; q < 2; q++) pub8(p_rec + q * 128, pack2t(r[4 * q], r[4 * q + 1], par) | 1u, pack2(r[4 * q + 2], r[4 * q + 3]));
  }
  const int vt = v0 + nt;
  const uint32_t bufa = sb + (vt & 1) * 65536, fulla = bar0 + (vt & 1) * 32, pha = (vt >> 1) & 1, phb = ((vt + 1) >> 1) & 1;
  const uint32_t bufo = sb + ((vt + 1) & 1) * 65536, fullb = bar0 + ((vt + 1) & 1) * 32;
  uint32_t a_rs = sb + O_R + (warp >> 2) * 1024 + (16 * tq + g) * 16 + ((warp + tq) & 3) * 4;
  if (isA) {
    const int row = 16 * (warp & 6) + 8 * (warp & 1) + (lane & 16) + ((lane & 7) >> 1) + 4 * (lane & 1);
    uint32_t ab = bufa + row * 128 + ((((lane >> 3) & 1) ^ (row & 7)) << 4);
    const uint2* pr = scr->rec + (hd * 32 + warp) * 64 + lane;
    unsigned long long a_c0 = mapg(sb + O_CTX + (64 * rn + 32 * (warp & 1) + posof(lane)) * 4, warp & 6);
    unsigned long long a_c1 = mapg(sb + O_CTX + (64 * rn + 32 * (warp & 1) + posof(lane)) * 4, warp | 1);
    uint32_t a_rl = sb + O_R + (32 * (warp & 1) + lane) * 16;
    uint32_t ao = bufo + (16 * warp + 8 * (lane >> 4) + (lane & 7)) * 128 + ((((lane >> 3) & 1) ^ (lane & 7)) << 4);
    uint32_t a_cx = sb + O_CTX + (16 * warp + 4 * tq) * 4, a_ga = sb + O_SM + (320 + posof(tid & 63)) * 4;
    unsigned* p_ao = scr->xao + b * 64 + (tid & 63);
    float xv = cl == 0 ? __bfloat162float(x[64 * rn + (tid & 63)]) : 0.f;
    unsigned p2 = lane >= 28 ? 0 : par;
    PIN(ab); PINL(pr); PINL(a_c0); PINL(a_c1); PIN(a_rl); PIN(a_rs); PIN(ao); PIN(a_cx); PIN(a_ga); PINL(p_ao); PIN(p2);
    asm volatile("" : "+f"(xv));
    uint32_t aw[4][4][4];
    auto wo = [&](const int j) {
      mbar_wait(fullb + 8 * j, phb);
#pragma unroll
      for (int mt = 0; mt < 4; mt++) ldsm_t(aw[j][mt], (ao + j * 16384) ^ (mt << 5));
    };
    {
      uint32_t a[4][4][4];
      uint2 z[4], y[4];
      float d[4][4] = {}, r[8];
      mbar_wait(fulla, pha);
      POLL {
#pragma unroll
        for (int q = 0; q < 4; q++) z[q] = ldx8(pr + q * 512);
        RETRY(lop_x3(z[0].x, z[1].x, par) | lop_x3(z[2].x, z[3].x, par))
      }
#pragma unroll
      for (int q = 0; q < 4; q++) {
        if (q == 3) {
          mbar_wait(bar0 + 8 * B_G);
#pragma unroll
          for (int u = 0; u < 4; u++) y[u] = ldx8(pr + u * 512 + 32);
        }
        mbar_wait(fulla + 8 * q, pha);
#pragma unroll
        for (int mt = 0; mt < 4; mt++) ldsm_t(a[q][mt], (ab + q * 16384) ^ (mt << 5));
#pragma unroll
        for (int mt = 0; mt < 4; mt++) mma16(d[mt], a[q][mt], z[q].x, z[q].y);
      }
      mbar_wait(bar0 + 8 * B_W);
      const float4 W = lds16(sb + O_SM + (384 + 4 * tq) * 4);
#pragma unroll
      for (int i = 0; i < 8; i++) { r[i] = W.x * d[i >> 1][2 * (i & 1)] + W.y * d[i >> 1][2 * (i & 1) + 1]; asm volatile("" : "+f"(r[i])); }
#pragma unroll
      for (int j = 0; j < NPE; j++) wo(j);
      POLL {
        if (it_)
#pragma unroll
          for (int u = 0; u < 4; u++) y[u] = ldx8(pr + u * 512 + 32);
#pragma unroll
        for (int mt = 0; mt < 4; mt++) d[mt][0] = d[mt][1] = d[mt][2] = d[mt][3] = 0.f;
#pragma unroll
        for (int q = 0; q < 4; q++)
#pragma unroll
          for (int mt = 0; mt < 4; mt++) mma16(d[mt], a[q][mt], y[q].x, y[q].y);
        RETRY(or3(lop_x3(y[0].x, y[1].x, p2), lop_x3(y[2].x, y[3].x, p2), 0))
      }
#pragma unroll
      for (int i = 0; i < 8; i++) r[i] = W.w * d[i >> 1][2 * (i & 1) + 1] + (W.z * d[i >> 1][2 * (i & 1)] + r[i]);
      tred<4>(r, lane, 2); tred<2>(r, lane, 1);
      sts4(a_rs, r[0]); sts4(a_rs + 128, r[1]);
      nbar(1, 256);
      const uint32_t cv = __float_as_uint(sum8(a_rl)) | 1u;
      asm volatile("st.relaxed.cluster.b32 [%0], %2; st.relaxed.cluster.b32 [%1], %2;" ::"l"(a_c0), "l"(a_c1), "r"(cv) : "memory");
    }
    {
#pragma unroll
      for (int j = NPE; j < NPO; j++) wo(j);
      uint4 c[4];
      POLL {
#pragma unroll
        for (int j = 0; j < 4; j++) c[j] = ldsv16(a_cx + j * 512);
        RETRY(~and3(and3(and3(c[0].x, c[0].y, c[0].z), and3(c[1].x, c[1].y, c[1].z), and3(c[0].w, c[1].w, c[2].x)),
                    and3(and3(c[2].y, c[2].z, c[2].w), and3(c[3].x, c[3].y, c[3].z), c[3].w), ~0u))
      }
      float d[4][4] = {};
#pragma unroll
      for (int j = 0; j < 4; j++) {
        if (j + 1 >= NPO && j < 3) wo(j + 1);
        const uint32_t b0 = pack2(u2f(c[j].x), u2f(c[j].y)), b1 = pack2(u2f(c[j].z), u2f(c[j].w));
#pragma unroll
        for (int mt = 0; mt < 4; mt++) mma16(d[mt], aw[j][mt], b0, b1);
      }
      const float r0 = (tq & 2) ? ((tq & 1) ? d[3][0] : d[2][0]) : ((tq & 1) ? d[1][0] : d[0][0]);
      const float r1 = (tq & 2) ? ((tq & 1) ? d[3][2] : d[2][2]) : ((tq & 1) ? d[1][2] : d[0][2]);
      sts4(a_rs + 2048, r0); sts4(a_rs + 2048 + 128, r1);
      if (warp >= 2) nbar_arrive(2, 256);
      else {
        mbar_wait(bar0 + 8 * B_TAB);
        const float gav = lds4(a_ga);
        nbar(2, 256);
        pub4(p_ao, __float_as_uint(gav * sum8(a_rl + 2048) + xv) | 1u);
      }
    }
  } else {
    uint32_t af[4][4][4], ad[2][4][4];
    uint32_t ab = bufa + (32 * warp + 8 * (lane >> 4) + (lane & 7)) * 64 + ((((lane >> 3) & 1) ^ ((lane >> 1) & 3)) << 4);
    uint32_t a_d = bufo + warp * 2048 + (8 * (lane >> 4) + (lane & 7)) * 128 + ((((lane >> 3) & 1) ^ (lane & 7)) << 4);
    uint32_t a_rl = sb + O_R + lane * 16, a_st = sb + O_SM + (352 + 8 * (lane >> 4) + warp) * 4;
    unsigned* p_f = scr->xf + ((4 * warp + tq) * 56 + f) * 16 + 2 * g;
    const unsigned* pa = scr->xao + (lane & 16) * 16 + 32 * warp + 2 * (lane & 15);
    const unsigned* pf = scr->xf + f * 896 + 4 * tid;
    const int col = ((tid >> 1) & 7) + 8 * (tid & 1);
    bf16* po = out + 16 * f + col;
    uint32_t a_q = sb + O_SM + (warp * 16 + 4 * tq + (lane >> 3)) * 4;
    unsigned d7 = sch.d7;
    PIN(ab); PIN(a_d); PIN(a_rl); PINL(p_f); PINL(pa); PIN(a_rs); PIN(a_st); PINL(pf); PINL(po); PIN(a_q); PIN(d7);
    mbar_wait(bar0 + 8 * B_TAB);
    uint2 cf;
    uint2 bb[4];
    unsigned gbw;
    POLL {
      unsigned bad = 0;
      cf = ldx8(scr->xm + 1024 + (lane & 16) * 16 + 32 * warp + posof(2 * (lane & 15)));
#pragma unroll
      for (int s = 0; s < 4; s++) {
        const uint4 w = ldx16(scr->xm + 1024 - (g & 1) * 512 + 256 * (s >> 1) + 32 * warp + 16 * (s & 1) + 4 * tq);
        bb[s] = make_uint2(__byte_perm(w.x, w.y, 0x7632), __byte_perm(w.z, w.w, 0x7632));
        bad = or3(bad, lop_x3(w.x, w.y, par), lop_x3(w.z, w.w, par));
      }
      gbw = ldx4(scr->xm + 1536 + 16 * (f & 31) + posof(col));
      RETRY(or3(bad, lop_x3(cf.x, cf.y, par), gbw ^ par))
    }
    const float gbv = bfhi(gbw);
    float e[4][4] = {};
    uint2 v[8];
    auto item = [&](const int it) {
      mbar_wait(fulla + 8 * it, pha);
#pragma unroll
      for (int i = 0; i < 4; i++) ldsm_t(af[it][i], (ab + it * 16384 + (i >> 1) * 1024) ^ ((i & 1) << 5));
    };
    auto item_mma = [&](const int it) {
#pragma unroll
      for (int i = 0; i < 4; i++) mma16(e[2 * (it & 1) + (i & 1)], af[it][i], bb[(it & 2) + (i >> 1)].x, bb[(it & 2) + (i >> 1)].y);
    };
    item(0); item_mma(0); item(1); item_mma(1);
    mbar_wait(bar0 + 8 * B_G);
#pragma unroll
    for (int i = 0; i < 8; i++) v[i] = ldx8(pa + i * 512);
    const unsigned t3 = clock() + WTEST;
    item(2); item_mma(2);
    uint32_t have3;
    do have3 = mbar_test(fulla + 24, pha); while (!have3 && (int)((unsigned)clock() - t3) < 0);
    if (have3) { item(3); item_mma(3); }
    float y0, y1, df[4][4], st[2];
    uint32_t have0, bz[4][2] = {};
    auto mm = [&](const int it, const int i) { mma16(df[2 * (it & 1) + (i & 1)], af[it][i], bz[(it & 2) + (i >> 1)][0], bz[(it & 2) + (i >> 1)][1]); };
    POLL {
      if (it_)
#pragma unroll
        for (int i = 0; i < 8; i++) v[i] = ldx8(pa + i * 512);
      y0 = ((u2f(v[0].x) + u2f(v[1].x)) + (u2f(v[2].x) + u2f(v[3].x))) + ((u2f(v[4].x) + u2f(v[5].x)) + (u2f(v[6].x) + u2f(v[7].x)));
      y1 = ((u2f(v[0].y) + u2f(v[1].y)) + (u2f(v[2].y) + u2f(v[3].y))) + ((u2f(v[4].y) + u2f(v[5].y)) + (u2f(v[6].y) + u2f(v[7].y)));
      const uint32_t zb = pack2(y0 * u2f(cf.x), y1 * u2f(cf.y));
#pragma unroll
      for (int i = 0; i < 8; i++) bz[i >> 1][i & 1] = g == i ? zb : 0u;
      st[0] = y0 + y1; st[1] = y0 * y0 + y1 * y1;
      tred<1>(st, lane, 16);
#pragma unroll
      for (int i = 0; i < 4; i++) df[i][0] = df[i][1] = df[i][2] = df[i][3] = 0.f;
      mm(0, 0); mm(0, 1); mm(1, 0); mm(1, 1);
      st[0] += shx(st[0], 8);
      mm(0, 2); mm(0, 3); mm(1, 2); mm(1, 3);
      RETRY(or3(or3(lop_x3(v[0].x, v[0].y, par), lop_x3(v[1].x, v[1].y, par), lop_x3(v[2].x, v[2].y, par)),
                or3(lop_x3(v[3].x, v[3].y, par), lop_x3(v[4].x, v[4].y, par), lop_x3(v[5].x, v[5].y, par)),
                or3(lop_x3(v[6].x, v[6].y, par), lop_x3(v[7].x, v[7].y, par), 0)))
    }
    {
      st[0] += shx(st[0], 4);
      mm(2, 0); mm(2, 1);
      st[0] += shx(st[0], 2);
      mm(2, 2); mm(2, 3);
      st[0] += shx(st[0], 1);
      sts4(a_st, st[0]);
      __syncwarp();
      arrive_n(bar0 + 8 * B_ST, lane == 0, 1);
      if (!have3) { item(3); item_mma(3); }
      have0 = mbar_test(fullb, phb);
      mm(3, 0); mm(3, 1); mm(3, 2); mm(3, 3);
#pragma unroll
      for (int mt = 0; mt < 4; mt++) ldsm_tp(ad[0][mt], a_d ^ (mt << 5), have0);
    }
    mbar_wait(bar0 + 8 * B_ST);
    float mean, rstd;
    {
      float4 u[4];
#pragma unroll
      for (int i = 0; i < 4; i++) u[i] = lds16(sb + O_SM + (352 + 4 * i) * 4);
      mean = (((u[0].x + u[0].y) + (u[0].z + u[0].w)) + ((u[1].x + u[1].y) + (u[1].z + u[1].w))) * (1.f / 512.f);
      const float sq = (((u[2].x + u[2].y) + (u[2].z + u[2].w)) + ((u[3].x + u[3].y) + (u[3].z + u[3].w))) * (1.f / 512.f);
      asm("rsqrt.approx.ftz.f32 %0, %1;" : "=f"(rstd) : "f"(fmaxf(sq - mean * mean, 0.f) + 1e-5f));
    }
    float r[8];
#pragma unroll
    for (int i = 0; i < 8; i++) r[i] = df[i >> 1][2 * (i & 1)] + df[i >> 1][2 * (i & 1) + 1];
    tred<4>(r, lane, 2); tred<2>(r, lane, 1);
    float A[4];
#pragma unroll
    for (int i = 0; i < 4; i++) A[i] = (tq & 2) ? ((tq & 1) ? e[3][i] : e[2][i]) : ((tq & 1) ? e[1][i] : e[0][i]);
    sts4(a_rs, rstd * r[0] + (A[1] - rstd * mean * A[0])); sts4(a_rs + 128, rstd * r[1] + (A[3] - rstd * mean * A[2]));
    const uint32_t have1 = mbar_test(fullb + 8, phb);
    nbar(1, 256);
    {
      const float4 g0 = lds16(a_rl), g1 = lds16(a_rl + 1024), u0 = lds16(a_rl + 512), u1 = lds16(a_rl + 1536);
#pragma unroll
      for (int mt = 0; mt < 4; mt++) ldsm_tp(ad[1][mt], (a_d + 16384) ^ (mt << 5), have1);
      const float gg = bfr(((g0.x + g0.y) + (g0.z + g0.w)) + ((g1.x + g1.y) + (g1.z + g1.w)));
      const float uu = bfr(((u0.x + u0.y) + (u0.z + u0.w)) + ((u1.x + u1.y) + (u1.z + u1.w)));
      const float hh = bfr(gg * rcp(1.f + ex2(gg * (-2.302208198f - 0.1029432397f * gg * gg)))) * uu;
      const uint32_t hw = pack2(hh, __shfl_down_sync(~0u, hh, 1));
      uint32_t hb[4];
#pragma unroll
      for (int i = 0; i < 4; i++) hb[i] = __shfl_sync(~0u, hw, 8 * i + 2 * tq);
      float dd[4][4] = {};
#pragma unroll
      for (int j = 0; j < 2; j++)
        if (!(j ? have1 : have0)) {
          mbar_wait(fullb + 8 * j, phb);
#pragma unroll
          for (int mt = 0; mt < 4; mt++) ldsm_t(ad[j][mt], (a_d + j * 16384) ^ (mt << 5));
        }
#pragma unroll
      for (int j = 0; j < 2; j++)
#pragma unroll
        for (int mt = 0; mt < 4; mt++) mma16(dd[mt], ad[j][mt], hb[2 * j], hb[2 * j + 1]);
      const float f0 = (tq & 2) ? ((tq & 1) ? dd[3][0] : dd[2][0]) : ((tq & 1) ? dd[1][0] : dd[0][0]);
      const float f1 = (tq & 2) ? ((tq & 1) ? dd[3][2] : dd[2][2]) : ((tq & 1) ? dd[1][2] : dd[0][2]);
      pub8(p_f, __float_as_uint(f0) | 1u, __float_as_uint(f1));
    }
    const unsigned tpub = clock();
    if (f < 32) {
      if (warp == ((f & 15) >> 1) && (g >> 1) == ((f >> 3) & 2) + (f & 1)) {
        sts4(sb + O_SM + (112 + 4 * tq + (g & 1)) * 4, y0); sts4(sb + O_SM + (114 + 4 * tq + (g & 1)) * 4, y1);
      }
      __syncwarp();
      if (warp == 7) nbar_arrive(2, 256);
      else {
        uint4 u;
        float q4[4];
        spin_until(tpub + d7);
        POLL {
          u = ldx16(pf);
          q4[0] = u2f(u.x); q4[1] = u2f(u.y); q4[2] = u2f(u.z); q4[3] = u2f(u.w);
          tred<2>(q4, lane, 16); tred<1>(q4, lane, 8);
          q4[0] += __shfl_xor_sync(~0u, q4[0], 4);
          RETRY(lop_x3(u.x, u.z, par))
        }
        sts4(a_q, q4[0]);
        nbar(2, 256);
        if (tid < 16) {
          float q[8];
#pragma unroll
          for (int i = 0; i < 8; i++) q[i] = lds4(sb + O_SM + (tid + 16 * i) * 4);
          const float t = ((q[0] + q[1]) + (q[2] + q[3])) + ((q[4] + q[5]) + q[6]);
          *po = __float2bfloat16(q[7] + bfr(gbv * bfr(t)));
          if (f == 0 && tid == 0) stx4(&scr->cnt[0], epoch + 1);
        }
      }
    }
  }
}

static void make_sched(Sched& s) {
  const char* order = "FFAAbcFmmvog....d";
  const double dt = 5050 * 1e-3, dth = 4850 * 1e-3, dtt = 5150 * 1e-3;
  const int nbig = NBIG;
  s.t0 = 0; s.dth = (unsigned)(dth * 256 + 0.5);
  double t = 512 * dth + 0 - 0;
  int tile = 0, jm = 0;
  for (int i = 0; i < 3; i++) s.nr[i] = s.nt[i] = 0;
  auto add = [&](int c, int type, double step, int win, int b0, int tl) {
    s.r[c][s.nr[c]++] = make_uint2((unsigned)(t + 0.5) | (unsigned)(step + 0.5) << 16, type | win << 4 | (b0 + 64) << 8 | tl << 16);
    if (type == T_KV) s.nt[c]++;
  };
  const int w1 = 6, w2 = 4, wt = 6;
  for (const char* p = order; *p; p++) {
    const char c = *p;
    if (c == 'v' || c == 'o' || c == 'm') {
      const int ty = c == 'v' ? T_UV : c == 'o' ? T_WO : T_MOD;
      const double d = c == 'm' ? dt : dtt;
      const double st = 64 * d + (c == 'o' ? 0 : 0);
      add(0, ty, st, wt, 0, c == 'm' ? jm : 0); add(1, ty, st, wt, 0, c == 'm' ? jm : 0);
      t += (c == 'm' ? 64 : 256) * d; jm += c == 'm';
    } else if (c == 'g' || c == 'd') {
      const int gs = c == 'g' ? 0 : 0;
      t -= 3 * gs;
      add(2, c == 'g' ? T_GU : T_DN, 56 * dtt + gs, c == 'g' ? wt : 6, 64, 0);
      t += 3 * gs;
      t += (c == 'g' ? 224 : 112) * dtt;
    } else if (c == '.') t += 100;
    else if (c == '-') t -= 100;
    else {
      const int na = c == 'F' ? 0 : c == 'C' || c == 'c' ? nbig : 64, nf = c == 'A' ? 0 : 56, n = na + nf;
      const int w = na && nf ? w2 : w1;
      const bool ff = c == 'b' || c == 'c';
      if (na) add(0, T_KV, n * dt, w, ff ? -56 : 0, tile);
      if (na == 64) add(1, T_KV, n * dt, w, ff ? -56 : 0, tile);
      if (nf) add(2, T_KV, n * dt, w, ff ? 64 : 64 - na, tile);
      tile += n; t += 4 * n * dt;
      s.t4 = (unsigned)t + 600;
    }
  }
  s.dt = (unsigned)(dt * 256 + 0.5); s.d7 = 300; s.d4 = 1500 | 950 << 16; s.d6 = 3350;
}

static void launch(void* const* d_in, void* d_out) {
  static TMaps tms;
  static Sched sch;
  static bool init = false;
  static void* scr = nullptr;
  if (!init) {
    void* fn = nullptr; cudaDriverEntryPointQueryResult qr;
    cudaGetDriverEntryPoint("cuTensorMapEncodeTiled", &fn, cudaEnableDefault, &qr);
    EncFn f = (EncFn)fn;
    const CUtensorMapSwizzle S64 = CU_TENSOR_MAP_SWIZZLE_64B, S128 = CU_TENSOR_MAP_SWIZZLE_128B;
    const CUtensorMapL2promotion P128 = CU_TENSOR_MAP_L2_PROMOTION_L2_128B, P256 = CU_TENSOR_MAP_L2_PROMOTION_L2_256B;
    enc3d(f, &tms.m[0], d_in[2], 64, 512, 64, 8192, 128, 64, 128, 1, S128, P128);
    enc3d(f, &tms.m[1], d_in[3], 64, 512, 64, 8192, 128, 64, 64, 2, S128, P256);
    enc3d(f, &tms.m[2], d_in[1], 64, SK, 8, 1024, 128, 64, 64, 2, S128, P256);
    enc3d(f, &tms.m[3], d_in[11], 3072, 256, 2, 6144, 256 * 6144, 32, 256, 1, S64, P128);
    enc3d(f, &tms.m[4], d_in[4], 64, 512, 64, 8192, 128, 64, 128, 1, S128, P128);
    enc3d(f, &tms.m[5], d_in[5], 512, 128, 32, 1024, 128 * 1024, 64, 128, 1, S128, P128);
    enc3d(f, &tms.m[6], d_in[7], 1792, 256, 2, 3584, 256 * 3584, 32, 256, 1, S64, P128);
    enc3d(f, &tms.m[7], d_in[8], 1792, 256, 2, 3584, 256 * 3584, 32, 256, 1, S64, P128);
    enc3d(f, &tms.m[8], d_in[9], 64, 1792, 8, 1024, 128, 64, 16, 8, S128, P256);
    cudaFuncSetAttribute(fused_kernel, cudaFuncAttributeMaxDynamicSharedMemorySize, SMEM9);
    cudaGetSymbolAddress(&scr, g_scr);
    make_sched(sch);
    init = true;
  }
  fused_kernel<<<NCTA9, 384, SMEM9>>>((const bf16*)d_in[0], (const bf16*)d_in[10], (const bf16*)d_in[11], (bf16*)d_out, (Scratch*)scr, sch, tms);
}

static bool fits() {
  cudaFuncSetAttribute(fused_kernel, cudaFuncAttributeMaxDynamicSharedMemorySize, SMEM9);
  cudaLaunchConfig_t cfg = {};
  cfg.gridDim = dim3(NCTA9); cfg.blockDim = dim3(384); cfg.dynamicSmemBytes = SMEM9;
  cudaLaunchAttribute at[1];
  at[0].id = cudaLaunchAttributeClusterDimension; at[0].val.clusterDim.x = 8; at[0].val.clusterDim.y = 1; at[0].val.clusterDim.z = 1;
  cfg.attrs = at; cfg.numAttrs = 1;
  int n = 0;
  if (cudaOccupancyMaxActiveClusters(&n, fused_kernel, &cfg) != cudaSuccess) { (void)cudaGetLastError(); return false; }
  return n >= NCTA9 / 8;
}
}
#undef BAR_ARM
#undef BAR_ARRIVE
#undef BAR_INIT
#undef B_EM
#undef B_EMPTY
#undef B_FM
#undef B_FULL
#undef B_G
#undef B_G2
#undef B_H
#undef B_HZ
#undef B_LZ
#undef B_Q2
#undef B_QF
#undef B_ST
#undef B_TAB
#undef B_W
#undef B_WZ
#undef CNT_ADD
#undef DSC
#undef HI128
#undef HI64
#undef NBIG
#undef NCTA9
#undef NPE
#undef NPO
#undef NSL
#undef O_B
#undef O_BAR
#undef O_CTX
#undef O_DBG
#undef O_EP
#undef O_HW
#undef O_HZ
#undef O_LZ
#undef O_P
#undef O_Q
#undef O_R
#undef O_SILU
#undef O_SM
#undef O_X
#undef PIN
#undef PINL
#undef POLL
#undef RETRY
#undef SK
#undef SMEM9
#undef SMEM_BASE
#undef SPIN_MAX
#undef TAU
#undef VDLY
#undef WTEST
#undef X16
#undef fbits

namespace v8 {
typedef __nv_bfloat16 bf16;
#define NCTA 128
#define SK 32768
#define SLOT 32768
#define NSLOT 6
#define OFF_WQ (2 * SLOT)
#define OFF_WUK (4 * SLOT)
#define OFF_Q 196608
#define OFF_P (OFF_Q + 16384)
#define OFF_B (OFF_P + 4096)
#define OFF_R4 (OFF_B + 2304)
#define OFF_SILU (OFF_R4 + 4096)
#define OFF_RA (OFF_SILU + 1024)
#define OFF_SM (OFF_RA + 1024)
#define OFF_BP (OFF_SM + 1792)
#define OFF_CO (OFF_BP + 1024)
#define OFF_BAR (OFF_CO + 1280)
#define OFF_MASK (OFF_BAR + 512)
#define OFF_DBG (OFF_MASK + 16)
#define SMEM_BYTES (OFF_DBG + 128)
#define OFF_MOD OFF_Q
#define OFF_UV (4 * SLOT)
#define OFF_O (5 * SLOT)
#define OFF_G 0
#define OFF_U 16384
#define OFF_D SLOT
#define OFF_XO (OFF_D + 16384)
#define FB_UK 4
#define FB_KV 6
#define FB_MOD 22
#define FB_UV 23
#define FB_O 25
#define FB_G 27
#define FB_D 29
#define EB 30
#define QB 50
#define XB 51
#define SPIN_MAX (1 << 20)
#define BACKOFF 40
#define RATE_NS 652
#define RATE_T0 200
#define RATE_TL 300
#define WINS 0x3222333
#define KVWIN 4
#define RATE_H 650
#define RATE_E 650
#define SMUL 9
#define NPRE0 1
#define NPRE1 3
#define HWIN 4
#define EWIN 3
#define WTEST 450
#define DLY5 650
#define DLY6 600
#define DLY7 600
#define P12(a, b, c, d, e, f, g, h, i, j, k, l) ((unsigned long long)(a) | (b) << 5 | (c) << 10 | (d) << 15 | (e) << 20 | (f) << 25 | \
  (unsigned long long)(g) << 30 | (unsigned long long)(h) << 35 | (unsigned long long)(i) << 40 | (unsigned long long)(j) << 45 | \
  (unsigned long long)(k) << 50 | (unsigned long long)(l) << 55)
#define ORDER0 P12(0, 1, 2, 3, 4, 5, 16, 6, 7, 8, 9, 10)
#define ORDER1 P12(11, 12, 13, 14, 15, 17, 18, 19, 20, 23, 21, 22)
#define TAIL_K 17
#define RS 16
template <int N> struct IC { static constexpr int value = N; };
struct TMaps { CUtensorMap m[9]; };

struct __align__(128) Scratch {
  uint4 xo[128 * 64 * RS];
  uint2 ml[32 * 64];
  unsigned h[8 * 256];
  unsigned qa[32 * 256];
  unsigned xc[128 * 64];
  unsigned xao[8 * 512];
  unsigned xf[112 * 512];
  unsigned xm[2048];
  unsigned cnt[5 * 32];
};
__device__ Scratch g_scr;
#define g_xo scr->xo
#define g_ml scr->ml
#define g_h scr->h
#define g_qa scr->qa
#define g_xc scr->xc
#define g_xao scr->xao
#define g_xf scr->xf
#define g_xm scr->xm
#define g_epoch scr->cnt[0]

__device__ __forceinline__ uint32_t s2u(const void* p) { return (uint32_t)__cvta_generic_to_shared(p); }
__device__ __forceinline__ float bflo(uint32_t u) { return __uint_as_float(u << 16); }
__device__ __forceinline__ float bfhi(uint32_t u) { return __uint_as_float(u & 0xffff0000u); }
__device__ __forceinline__ float u2f(uint32_t u) { return __uint_as_float(u); }
__device__ __forceinline__ void fma8(float* acc, uint4 v, float s) {
  acc[0] += s * bflo(v.x); acc[1] += s * bfhi(v.x); acc[2] += s * bflo(v.y); acc[3] += s * bfhi(v.y);
  acc[4] += s * bflo(v.z); acc[5] += s * bfhi(v.z); acc[6] += s * bflo(v.w); acc[7] += s * bfhi(v.w);
}
__device__ __forceinline__ uint32_t pack2(float a, float b) {
  __nv_bfloat162 p = __floats2bfloat162_rn(a, b); return *(uint32_t*)&p;
}
__device__ __forceinline__ float bfr(float v) { return bfhi(pack2(v, v)); }
__device__ __forceinline__ float silu_bf(float c) { return bfr(__fdividef(c, 1.f + __expf(-c))); }
#define fbits(v) ((__float_as_uint(v) & ~1u) | par)
__device__ __forceinline__ uint32_t pack2t(float a, float b, unsigned par) {
  const uint32_t ua = ((__float_as_uint(a) + ((par ^ 1) << 16)) & 0xFFFE0000u) | (par << 16);
  return __byte_perm(ua, pack2(b, b), 0x7632);
}
__device__ __forceinline__ void nbar(int id, int n) { asm volatile("bar.sync %0, %1;" ::"r"(id), "r"(n) : "memory"); }
__device__ __forceinline__ void nbar_arrive(int id, int n) { asm volatile("bar.arrive %0, %1;" ::"r"(id), "r"(n) : "memory"); }
__device__ __forceinline__ uint4 ldc16(const void* p) {
  uint4 v; asm volatile("ld.relaxed.cta.global.v4.u32 {%0,%1,%2,%3}, [%4];" : "=r"(v.x), "=r"(v.y), "=r"(v.z), "=r"(v.w) : "l"(p) : "memory"); return v;
}
__device__ __forceinline__ unsigned ldc4(const void* p) {
  unsigned v; asm volatile("ld.relaxed.cta.global.u32 %0, [%1];" : "=r"(v) : "l"(p) : "memory"); return v;
}
__device__ __forceinline__ uint4 ldx16(const void* p) {
  uint4 v; asm volatile("ld.relaxed.gpu.global.v4.u32 {%0,%1,%2,%3}, [%4];" : "=r"(v.x), "=r"(v.y), "=r"(v.z), "=r"(v.w) : "l"(p) : "memory"); return v;
}
__device__ __forceinline__ unsigned ldx4(const void* p) {
  unsigned v; asm volatile("ld.relaxed.gpu.global.u32 %0, [%1];" : "=r"(v) : "l"(p) : "memory"); return v;
}
__device__ __forceinline__ unsigned long long ldx64(const void* p) {
  unsigned long long v; asm volatile("ld.relaxed.gpu.global.u64 %0, [%1];" : "=l"(v) : "l"(p) : "memory"); return v;
}
__device__ __forceinline__ void stx16(void* p, uint4 v) {
  asm volatile("st.relaxed.gpu.global.v4.u32 [%0], {%1,%2,%3,%4};" ::"l"(p), "r"(v.x), "r"(v.y), "r"(v.z), "r"(v.w) : "memory");
}
__device__ __forceinline__ void stx8(void* p, uint2 v) { asm volatile("st.relaxed.gpu.global.v2.u32 [%0], {%1,%2};" ::"l"(p), "r"(v.x), "r"(v.y) : "memory"); }
__device__ __forceinline__ void stx4(void* p, unsigned v) { asm volatile("st.relaxed.gpu.global.u32 [%0], %1;" ::"l"(p), "r"(v) : "memory"); }
__device__ __forceinline__ unsigned lop_x3(unsigned a, unsigned b, unsigned c) {
  unsigned d; asm("lop3.b32 %0, %1, %2, %3, 0x7E;" : "=r"(d) : "r"(a), "r"(b), "r"(c)); return d; }
#define X16(v) (lop_x3(v.x, v.y, par) | lop_x3(v.z, v.w, par))
#define X8(v) lop_x3(v.x, v.y, par)
#define RETRY(bad) if (!__any_sync(~0u, (bad) & 1) || ++it_ >= SPIN_MAX) break; __nanosleep(BACKOFF);
#define POLL _Pragma("unroll 1") for (int it_ = 0;;)
__device__ __forceinline__ void mbar_wait(uint32_t bar) {
  uint32_t ok; int it = 0;
  do {
    asm volatile("{.reg .pred p; mbarrier.try_wait.parity.shared::cta.b64 p, [%1], 0; selp.u32 %0,1,0,p;}"
                 : "=r"(ok) : "r"(bar) : "memory");
  } while (!ok && ++it < SPIN_MAX);
}
__device__ __forceinline__ float ex2(float v) { float r; asm("ex2.approx.ftz.f32 %0, %1;" : "=f"(r) : "f"(v)); return r; }
__device__ __forceinline__ float rcp(float v) { float r; asm("rcp.approx.ftz.f32 %0, %1;" : "=f"(r) : "f"(v)); return r; }
__device__ __forceinline__ void mma16(float* d, const uint32_t* a, uint32_t b0, uint32_t b1) {
  asm volatile("mma.sync.aligned.m16n8k16.row.col.f32.bf16.bf16.f32 {%0,%1,%2,%3}, {%4,%5,%6,%7}, {%8,%9}, {%0,%1,%2,%3};"
               : "+f"(d[0]), "+f"(d[1]), "+f"(d[2]), "+f"(d[3]) : "r"(a[0]), "r"(a[1]), "r"(a[2]), "r"(a[3]), "r"(b0), "r"(b1));
}
__device__ __forceinline__ float4 lds16(uint32_t a) {
  float4 v; asm volatile("ld.shared.v4.f32 {%0,%1,%2,%3}, [%4];" : "=f"(v.x), "=f"(v.y), "=f"(v.z), "=f"(v.w) : "r"(a) : "memory"); return v;
}
__device__ __forceinline__ void ldsm_t(uint32_t* r, uint32_t a) {
  asm volatile("ldmatrix.sync.aligned.m8n8.x4.trans.shared.b16 {%0,%1,%2,%3}, [%4];" : "=r"(r[0]), "=r"(r[1]), "=r"(r[2]), "=r"(r[3]) : "r"(a) : "memory");
}
__device__ __forceinline__ void ldsm(uint32_t* r, uint32_t a) {
  asm volatile("ldmatrix.sync.aligned.m8n8.x4.shared.b16 {%0,%1,%2,%3}, [%4];" : "=r"(r[0]), "=r"(r[1]), "=r"(r[2]), "=r"(r[3]) : "r"(a) : "memory");
}
template <int N>
__device__ __forceinline__ void tred(float* a, int lane, int m) {
  const bool hi = lane & m;
#pragma unroll
  for (int i = 0; i < N; i++) {
    float send = hi ? a[i] : a[i + N], keep = hi ? a[i + N] : a[i];
    a[i] = keep + __shfl_xor_sync(~0u, send, m);
  }
}
template <int N>
__device__ __forceinline__ void tmax(float* a, int lane, int m) {
  const bool hi = lane & m;
#pragma unroll
  for (int i = 0; i < N; i++) {
    float send = hi ? a[i] : a[i + N], keep = hi ? a[i + N] : a[i];
    a[i] = fmaxf(keep, __shfl_xor_sync(~0u, send, m));
  }
}
__device__ __forceinline__ void arrive2(uint32_t bar, uint32_t rbar, bool local, bool remote) {
  asm volatile("{.reg .pred p, q; setp.ne.s32 p, %2, 0; setp.ne.s32 q, %3, 0; @p mbarrier.arrive.shared::cta.b64 _, [%0];\n"
               "@q mbarrier.arrive.relaxed.cluster.shared::cluster.b64 _, [%1];}" ::"r"(bar), "r"(rbar), "r"((int)local), "r"((int)remote) : "memory");
}
__device__ __forceinline__ unsigned long long stream_policy() {
  unsigned long long p;
  asm volatile("createpolicy.fractional.L2::evict_first.b64 %0, 1.0;" : "=l"(p));
  return p;
}
__device__ __forceinline__ void tma3d(uint32_t dst, const CUtensorMap* tm, uint32_t bar, int c0, int c1, int c2) {
  asm volatile("cp.async.bulk.tensor.3d.shared::cluster.global.mbarrier::complete_tx::bytes.L2::cache_hint [%0], [%1, {%3, %4, %5}], [%2], %6;"
               ::"r"(dst), "l"(tm), "r"(bar), "r"(c0), "r"(c1), "r"(c2), "l"(stream_policy()) : "memory");
}
__device__ __forceinline__ void st_async2(uint32_t dst, uint32_t bar, float v0, float v1) {
  asm volatile("st.async.shared::cluster.mbarrier::complete_tx::bytes.v2.f32 [%0], {%1, %2}, [%3];" ::"r"(dst), "f"(v0), "f"(v1), "r"(bar) : "memory");
}
__device__ __forceinline__ void st_pair(int mode, uint32_t dst, uint32_t bar, float v0, float v1) {
  asm volatile("{.reg .pred p, q; setp.eq.s32 p, %4, 1; setp.eq.s32 q, %4, 2; @p st.shared.v2.f32 [%0], {%1, %2};\n"
               "@q st.async.shared::cluster.mbarrier::complete_tx::bytes.v2.f32 [%0], {%1, %2}, [%3];}"
               ::"r"(dst), "f"(v0), "f"(v1), "r"(bar), "r"(mode) : "memory");
}
__device__ __forceinline__ void spin_until(unsigned t) { while ((int)((unsigned)clock() - t) < 0) {} }
__device__ __forceinline__ unsigned wait_until(unsigned t) {
  unsigned now;
  for (;;) {
    asm volatile("mov.u32 %0, %%globaltimer_lo;" : "=r"(now));
    if ((int)(now - t) >= 0) break;
  }
  return now;
}
#define PIN(x) asm volatile("" : "+r"(x))
#define PINL(x) asm volatile("" : "+l"(x))
#define BAR_ARRIVE(i) asm volatile("mbarrier.arrive.shared::cta.b64 _, [%0];" ::"r"(bar0 + 8 * (i)) : "memory")
#define CNT_ADD(c) asm volatile("red.relaxed.gpu.global.add.u32 [%0], 1;" ::"l"(scr->cnt + (c)) : "memory")
#define BAR_INIT(i, cnt) asm volatile("mbarrier.init.shared::cta.b64 [%0], %1;" ::"r"(bar0 + 8 * (i)), "r"(cnt) : "memory")
#define BAR_ARM(i, bytes) asm volatile("mbarrier.arrive.expect_tx.shared::cta.b64 _, [%0], %1;" ::"r"(bar0 + 8 * (i)), "r"(bytes) : "memory")

__device__ __forceinline__ void tail(unsigned char* smem, Scratch* __restrict__ scr, const bf16* __restrict__ x, bf16* __restrict__ out,
                                     const unsigned par, const unsigned epoch, const int warp) {
  int tid, b;
  asm volatile("mov.u32 %0, %%tid.x;" : "=r"(tid));
  asm volatile("mov.u32 %0, %%ctaid.x;" : "=r"(b));
  const int lane = tid & 31, g = lane >> 2, tq = lane & 3;
  const uint32_t sb = __shfl_sync(~0u, s2u(smem), 0), bar0 = sb + OFF_BAR;
  float* s_sm = (float*)(smem + OFF_SM);
  const int prow = 4 * (lane >> 4) + ((lane & 7) >> 1) + 8 * (lane & 1);
  const float* s_co = (const float*)(smem + OFF_CO);
  const int opos = (b & 15) * 32 + (lane & 16) + 2 * (lane & 6) + ((lane >> 2) & 2) + (lane & 1);
  const float xv = b < 16 ? __bfloat162float(x[(b & 15) * 32 + lane]) : 0.f;
  const int rk = b & 1, ob = 32 * rk + ((b >> 1) & 31);
  uint32_t psb;
  asm volatile("mapa.shared::cluster.u32 %0, %1, %2;" : "=r"(psb) : "r"(sb), "r"(rk ^ 1));
  {
    uint32_t a[8][4];
    {
      const int rg = tid >> 4;
      const uint4* src = g_xo + ((size_t)b * 64 + rg) * RS;
      const uint32_t dst = sb + OFF_XO + rg * 256 + (((tid & 15) ^ (rg & 7)) << 4);
      unsigned long long todo = 0x0001000100010001ull;
#pragma unroll 1
      for (int it = 0; it < SPIN_MAX * 16; it++) {
        unsigned long long mk = *(volatile unsigned long long*)(smem + OFF_MASK);
        const unsigned long long nw = (mk >> rg) & todo;
        todo ^= nw;
#pragma unroll
        for (int i = 0; i < 4; i++)
          if (nw >> (16 * i) & 1)
            asm volatile("cp.async.cg.shared.global [%0], [%1], 16;" ::"r"(dst + i * 4096), "l"(src + i * 16 * RS + (tid & 15)) : "memory");
        if (!__any_sync(~0u, todo != 0)) break;
      }
      asm volatile("cp.async.mbarrier.arrive.noinc.shared::cta.b64 [%0];" ::"r"(bar0 + 8 * (XB + 2)) : "memory");
    }
    mbar_wait(bar0 + 8 * FB_UV); mbar_wait(bar0 + 8 * (FB_UV + 1));
    const uint32_t ab = sb + OFF_UV + (warp >> 2) * 8192 + (8 * (lane >> 4) + (lane & 7)) * 128 + (((2 * (warp & 3) + ((lane >> 3) & 1)) ^ (lane & 7)) << 4);
#pragma unroll
    for (int s = 0; s < 8; s++) ldsm_t(a[s], ab + (s >> 2) * 16384 + (s & 3) * 2048);
    const int chn = 2 * warp + (tq & 1);
    uint32_t a_b = sb + OFF_B + (tq >> 1) * 272 + (32 * (chn >> 2) + 8 * (g >> 1) + 2 * (chn & 3) + (g & 1)) * 2;
    uint32_t a_bq = sb + OFF_B + (lane & 1) * 272 + (lane >> 3) * 16;
    unsigned* p_c = g_xc + (b >> 2) * 256 + warp * 32 + (b & 3) * 8 + (g & 3) * 2 + (g >> 2);
    PIN(a_b); PIN(a_bq); PINL(p_c);
    mbar_wait(bar0 + 8 * (XB + 6));
    uint32_t wb[8];
#pragma unroll
    for (int s = 0; s < 8; s++) wb[s] = *(const uint32_t*)(smem + OFF_RA + (4 * s + tq) * 4);
    const float invL = *(const float*)(smem + OFF_RA + 128);
    float ov;
    POLL {
      mbar_wait(bar0 + 8 * (XB + 2));
      uint32_t ao[4][4];
#pragma unroll
      for (int s = 0; s < 4; s++)
        ldsm_t(ao[s], sb + OFF_XO + (16 * s + 8 * (lane >> 4) + (lane & 7)) * 256 + (((2 * warp + ((lane >> 3) & 1)) ^ (lane & 7)) << 4));
      float d[4][4] = {};
#pragma unroll
      for (int s = 0; s < 4; s++) mma16(d[s], ao[s], wb[2 * s], wb[2 * s + 1]);
      const unsigned p2 = par * 0x10001u;
      unsigned bad = 0;
#pragma unroll
      for (int s = 0; s < 4; s++) bad |= lop_x3(ao[s][0], ao[s][1], p2) | lop_x3(ao[s][2], ao[s][3], p2);
      bad = g == 0 ? bad | (bad >> 16) : 0u;
      ov = (tq & 1) ? (d[0][2] + d[1][2]) + (d[2][2] + d[3][2]) : (d[0][0] + d[1][0]) + (d[2][0] + d[3][0]);
      if (__builtin_expect(!__any_sync(~0u, bad & 1) || ++it_ >= SPIN_MAX, 1)) break;
#pragma unroll
      for (int i = 0; i < 4; i++)
        asm volatile("cp.async.cg.shared.global [%0], [%1], 16;"
                     ::"r"(sb + OFF_XO + ((lane >> 1) + 16 * i) * 256 + (((2 * warp + (lane & 1)) ^ ((lane >> 1) & 7)) << 4)),
                       "l"(g_xo + ((size_t)b * 64 + (lane >> 1) + 16 * i) * RS + 2 * warp + (lane & 1)) : "memory");
      asm volatile("cp.async.wait_all;" ::: "memory");
      __syncwarp();
    }
    {
      const float lo = ov - bfhi(__float_as_uint(ov));
      asm volatile("st.shared.u16 [%0], %1;" ::"r"(a_b), "h"((unsigned short)((tq & 2) ? pack2(lo, lo) : __float_as_uint(ov) >> 16)) : "memory");
    }
    nbar(1, 256);
    float d[4][4] = {};
#pragma unroll
    for (int y = 0; y < 4; y++) {
      uint32_t bq[4];
      ldsm(bq, a_bq + 64 * y);
      mma16(d[(2 * y) & 3], a[2 * y], bq[0], bq[1]); mma16(d[(2 * y + 1) & 3], a[2 * y + 1], bq[2], bq[3]);
    }
    const float r0 = ((d[0][0] + d[0][1]) + (d[1][0] + d[1][1])) + ((d[2][0] + d[2][1]) + (d[3][0] + d[3][1]));
    const float r1 = ((d[0][2] + d[0][3]) + (d[1][2] + d[1][3])) + ((d[2][2] + d[2][3]) + (d[3][2] + d[3][3]));
    if (tq == 0) stx4(p_c, pack2t(r0 * invL, r1 * invL, par));
  }
  unsigned tpub = clock();
  mbar_wait(bar0 + 8 * (XB + 4));
  const float gav = s_co[256 + (opos & 31)];
  const float gbv = s_co[288 + (lane & 4) + 2 * (lane & 1) + ((lane >> 1) & 1)];
  float4 cf[2];
#pragma unroll
  for (int s = 0; s < 2; s++) cf[s] = *(const float4*)(s_co + 32 * warp + 16 * s + 4 * tq);
  {
    uint32_t a[2][4][4];
    mbar_wait(bar0 + 8 * (FB_O + (warp >> 2)));
    const uint32_t ab = sb + OFF_O + (32 * warp + prow) * 128 + ((((lane >> 3) & 1) ^ (prow & 7)) << 4);
#pragma unroll
    for (int i = 0; i < 8; i++) ldsm_t(a[i >> 2][i & 3], (ab + (i >> 2) * 2048) ^ ((i & 3) << 5));
    uint4 v;
    const unsigned* pc = g_xc + (4 * (b >> 4) + 2 * rk + (warp >> 2)) * 256 + 64 * (warp & 3) + 2 * lane;
    uint32_t ro = ((tq >> 1) == rk ? sb : psb) + OFF_P + (8 * (tq & 1) + g) * 144 + (8 * rk + warp) * 8;
    uint32_t a_q = sb + OFF_P + (8 * (lane >> 4) + (lane & 7)) * 144;
    unsigned* p_ao = g_xao + (b >> 5) * 1024 + (opos >> 4) * 32 + (b & 16) + (opos & 15);
    PIN(ro); PIN(a_q); PINL(p_ao); PINL(pc);
    spin_until(tpub + DLY5);
    POLL {
      const unsigned long long u0 = ldx64(pc);
      v.x = (unsigned)u0; v.y = u0 >> 32;
      RETRY(X8(v))
    }
    v.z = lane & 16 ? v.x : 0u; v.w = lane & 16 ? v.y : 0u;
    if (lane & 16) v.x = v.y = 0u;
    float d[4][4] = {};
#pragma unroll
    for (int mt = 0; mt < 4; mt++) mma16(d[mt], a[0][mt], v.x, v.y);
#pragma unroll
    for (int mt = 0; mt < 4; mt++) mma16(d[mt], a[1][mt], v.z, v.w);
    float r[8];
#pragma unroll
    for (int i = 0; i < 8; i++) r[i] = d[i >> 1][2 * (i & 1)] + d[i >> 1][2 * (i & 1) + 1];
    tred<4>(r, lane, 2); tred<2>(r, lane, 1);
    st_pair((tq >> 1) == rk ? 1 : 2, ro, psb + OFF_BAR + 8 * (XB + 3), r[0], r[1]);
    __syncwarp();
    if (lane == 0) BAR_ARRIVE(XB + 3);
    if (warp == 0) {
      mbar_wait(bar0 + 8 * (XB + 3));
      float p[8];
#pragma unroll
      for (int i = 0; i < 8; i++) {
        const float4 q = lds16(a_q + i * 16);
        p[i] = (lane & 8) ? q.y + q.w : q.x + q.z;
      }
      const float t = ((p[0] + p[1]) + (p[2] + p[3])) + ((p[4] + p[5]) + (p[6] + p[7]));
      stx4(p_ao, fbits(gav * t + xv));
    }
  }
  tpub = clock();
  if (b < 112) {
    uint32_t af[2][4][4], ad[4][4];
    const uint32_t ab = sb + (32 * warp + 8 * (lane >> 4) + (lane & 7)) * 64 + ((((lane >> 3) & 1) ^ ((lane >> 1) & 3)) << 4);
    uint32_t ro = ((tq & 1) == rk ? sb : psb) + OFF_R4 + (8 * (tq >> 1) + g) * 176 + (10 * rk + warp) * 8;
    uint32_t a_q = sb + OFF_R4 + (8 * (lane >> 4) + (lane & 7)) * 176 + (lane & 8) * 10;
    uint32_t a_d = sb + OFF_D + warp * 2048 + (8 * (lane >> 4) + (lane & 7)) * 128 + ((((lane >> 3) & 1) ^ (lane & 7)) << 4);
    unsigned* p_f = g_xf + b * 512 + 64 * warp + 16 * tq + 2 * g;
    const unsigned* pa = g_xao + (g >> 1) * 1024 + 512 * rk + 64 * warp + 4 * (lane & 7);
    PIN(ro); PIN(a_q); PIN(a_d); PINL(p_f); PINL(pa);
    spin_until(tpub + DLY6);
    uint4 v[2];
    {
      bool have = false;
      POLL {
        v[0] = ldx16(pa); v[1] = ldx16(pa + 32);
        const unsigned t1 = (unsigned)clock() + WTEST;
        while (!have && (int)((unsigned)clock() - t1) < 0) {
          uint32_t ok;
          asm volatile("{.reg .pred p, q; mbarrier.test_wait.parity.shared::cta.b64 p, [%1], 0; mbarrier.test_wait.parity.shared::cta.b64 q, [%1+8], 0;\n"
                       "and.pred p, p, q; vote.sync.all.pred p, p, 0xffffffff; selp.u32 %0, 1, 0, p;}" : "=r"(ok) : "r"(bar0 + 8 * FB_G) : "memory");
          if (ok) {
#pragma unroll
            for (int i = 0; i < 8; i++) ldsm_t(af[i >> 2][i & 3], (ab + ((i & 2) ? OFF_U : OFF_G) + (i >> 2) * 1024) ^ ((i & 1) << 5));
            have = true;
          }
        }
        if (!__any_sync(~0u, (X16(v[0]) | X16(v[1])) & 1) || ++it_ >= SPIN_MAX) break;
      }
      float df[4][4] = {}, dg[2][4] = {};
      uint32_t zb[4];
      const uint32_t one = g == 0 ? 0x3F803F80u : 0u;
#pragma unroll
      for (int s = 0; s < 2; s++) {
        const uint32_t y0 = pack2(u2f(v[s].x), u2f(v[s].y)), y1 = pack2(u2f(v[s].z), u2f(v[s].w));
        const uint32_t ya[4] = {y0, one, y1, one};
        mma16(dg[s], ya, y0, y1);
        zb[2 * s] = pack2(u2f(v[s].x) * cf[s].x, u2f(v[s].y) * cf[s].y); zb[2 * s + 1] = pack2(u2f(v[s].z) * cf[s].z, u2f(v[s].w) * cf[s].w);
      }
      float st[2] = {(dg[0][2] + dg[0][3]) + (dg[1][2] + dg[1][3]), (dg[0][0] + dg[0][1]) + (dg[1][0] + dg[1][1])};
      if (!have) {
        mbar_wait(bar0 + 8 * FB_G); mbar_wait(bar0 + 8 * (FB_G + 1));
#pragma unroll
        for (int i = 0; i < 8; i++) ldsm_t(af[i >> 2][i & 3], (ab + ((i & 2) ? OFF_U : OFF_G) + (i >> 2) * 1024) ^ ((i & 1) << 5));
      }
#pragma unroll
      for (int i = 0; i < 8; i++) mma16(df[i & 3], af[i >> 2][i & 3], zb[2 * (i >> 2)], zb[2 * (i >> 2) + 1]);
#pragma unroll
      for (int o2 = 1; o2 < 4; o2 <<= 1) { st[0] += __shfl_xor_sync(~0u, st[0], o2); st[1] += __shfl_xor_sync(~0u, st[1], o2); }
#pragma unroll
      for (int o2 = 4; o2 < 32; o2 <<= 1) st[1] += __shfl_xor_sync(~0u, st[1], o2);
      float r[8];
#pragma unroll
      for (int i = 0; i < 8; i++) r[i] = df[i >> 1][2 * (i & 1)] + df[i >> 1][2 * (i & 1) + 1];
      tred<4>(r, lane, 2); tred<2>(r, lane, 1);
      const int md = (tq & 1) == rk ? 1 : 2;
      st_pair(md, ro, psb + OFF_BAR + 8 * (XB + 5), r[0], r[1]);
      st_pair(lane < 2 ? md : 0, ro + 16 * 176, psb + OFF_BAR + 8 * (XB + 5), st[0], st[1]);
      __syncwarp();
      if (lane == 0) BAR_ARRIVE(XB + 5);
      mbar_wait(bar0 + 8 * FB_D);
#pragma unroll
      for (int mt = 0; mt < 4; mt++)
        ldsm_t(ad[mt], a_d ^ (mt << 5));
    }
    mbar_wait(bar0 + 8 * (XB + 5));
    {
      float4 q[5], u[8];
#pragma unroll
      for (int i = 0; i < 5; i++) q[i] = lds16(a_q + i * 16);
#pragma unroll
      for (int i = 0; i < 8; i++) u[i] = *(const float4*)(smem + OFF_R4 + 16 * 176 + (i >> 2) * 80 + (i & 3) * 16);
      float p[6] = {((q[0].x + q[0].z) + (q[1].x + q[1].z)) + ((q[2].x + q[2].z) + (q[3].x + q[3].z)), q[4].x, q[4].z,
                    ((q[0].y + q[0].w) + (q[1].y + q[1].w)) + ((q[2].y + q[2].w) + (q[3].y + q[3].w)), q[4].y, q[4].w};
      tred<3>(p, lane, 8);
      const float P = p[0], A1 = p[1], A2 = p[2];
      const float mean = (((u[0].x + u[0].z) + (u[1].x + u[1].z)) + ((u[2].x + u[2].z) + (u[3].x + u[3].z)) +
                          ((u[4].x + u[4].z) + (u[5].x + u[5].z)) + ((u[6].x + u[6].z) + (u[7].x + u[7].z))) * (1.f / 512.f);
      const float sq = (((u[0].y + u[0].w) + (u[1].y + u[1].w)) + ((u[2].y + u[2].w) + (u[3].y + u[3].w)) +
                         ((u[4].y + u[4].w) + (u[5].y + u[5].w)) + ((u[6].y + u[6].w) + (u[7].y + u[7].w))) * (1.f / 512.f);
      float rstd;
      asm("rsqrt.approx.ftz.f32 %0, %1;" : "=f"(rstd) : "f"(fmaxf(sq - mean * mean, 0.f) + 1e-5f));
      const float gg = bfr(rstd * (P - mean * A1) + A2);
      const float uu = __shfl_xor_sync(~0u, gg, 16);
      const float hh = bfr(gg * rcp(1.f + ex2(gg * (-2.302208198f - 0.1029432397f * gg * gg)))) * uu;
      const uint32_t hw = pack2(hh, __shfl_down_sync(~0u, hh, 1));
      const uint32_t b0 = __shfl_sync(~0u, hw, 2 * tq), b1 = __shfl_sync(~0u, hw, 2 * tq + 8);
      float f0 = 0, f1 = 0;
#pragma unroll
      for (int mt = 0; mt < 4; mt++) {
        float dd[4] = {0, 0, 0, 0};
        mma16(dd, ad[mt], b0, b1);
        if (tq == mt) { f0 = dd[0]; f1 = dd[2]; }
      }
      stx8(p_f, make_uint2(fbits(f0), fbits(f1)));
    }
    tpub = clock();
    if (b < 64 && warp == (b >> 3)) {
      const uint4 y = (b & 4) ? v[1] : v[0];
      float a4[4] = {u2f(y.x), u2f(y.y), u2f(y.z), u2f(y.w)};
      tred<2>(a4, lane, 16); tred<1>(a4, lane, 8);
      a4[0] += __shfl_xor_sync(~0u, a4[0], 4);
      if (!(lane & 4)) s_sm[416 + 8 * (lane >> 4) + 2 * tq + ((lane >> 3) & 1)] = a4[0];
      if (warp == 7) nbar_arrive(2, 256);
    } else if (b < 64 && warp == 7) nbar_arrive(2, 256);
    if (b < 64 && warp < 7) {
      uint4 v;
      const unsigned* pf = g_xf + (tid >> 1) * 512 + 8 * ob + 4 * (tid & 1);
      const int col = 16 * (ob >> 1) + 4 * (ob & 1) + ((tid >> 1) & 3) + 8 * (tid & 1);
      bf16* po = out + col;
      PINL(po); PINL(pf);
      spin_until(tpub + DLY7);
      POLL { v = ldx16(pf); RETRY(X16(v)) }
      float f[4] = {u2f(v.x), u2f(v.y), u2f(v.z), u2f(v.w)};
      tred<2>(f, lane, 16); tred<1>(f, lane, 8);
      f[0] += __shfl_xor_sync(~0u, f[0], 4); f[0] += __shfl_xor_sync(~0u, f[0], 2);
      if (!(lane & 6)) s_sm[352 + warp * 8 + 4 * (lane & 1) + (lane >> 3)] = f[0];
      nbar(2, 256);
      if (tid < 8) {
        const float* q = s_sm + 352 + tid;
        const float t = ((q[0] + q[8]) + (q[16] + q[24])) + ((q[32] + q[40]) + q[48]);
        *po = __float2bfloat16(s_sm[416 + (col & 15)] + bfr(gbv * bfr(t)));
        if (b == 0 && tid == 0) stx4(&g_epoch, epoch + 1);
      }
    }
  }
}

__global__ void __cluster_dims__(2, 1, 1) __launch_bounds__(384, 1)
fused_kernel(const bf16* __restrict__ x, const bf16* __restrict__ cvec, const bf16* __restrict__ w_mod, bf16* __restrict__ out,
             Scratch* __restrict__ scr, const __grid_constant__ TMaps tms) {
  extern __shared__ __align__(1024) unsigned char smem[];
  const int tid = threadIdx.x, warp = __shfl_sync(~0u, tid >> 5, 0), lane = tid & 31;
  const int b = blockIdx.x, rk = b & 1, pr = b >> 1, hd = b >> 2;
  uint32_t sb = s2u(smem), bar0 = sb + OFF_BAR;

  unsigned gt_start;
  asm volatile("mov.u32 %0, %%globaltimer_lo;" : "=r"(gt_start));
  const int g = lane >> 2, tq = lane & 3;
  const int arow = 64 * (b >> 4) + ((tid & 255) >> 3);
  uint4 wm0, wm1;
  uint32_t c0w, c1w;
  if (warp < 8) {
    const bf16* wa = w_mod + (size_t)arow * 3072 + (lane & 4) * 128 + 32 * (b & 15) + 8 * tq;
    wm0 = ldx16(wa); wm1 = ldx16(wa + 32 * 3072);
    c0w = ldc4(cvec + (arow & ~1)); c1w = ldc4(cvec + (arow & ~1) + 32);
  }
  const unsigned t_off = gt_start + RATE_T0;
  if (warp == 11) {
    if (lane == 0) {
#pragma unroll
      for (int i = 0; i < FB_KV; i++) { BAR_INIT(i, 1); BAR_ARM(i, 16384); }
    }
    __syncwarp();
    asm volatile("fence.mbarrier_init.release.cluster;" ::: "memory");
    asm volatile("barrier.cluster.arrive.relaxed.aligned;" ::: "memory");
#pragma unroll 1
    for (int i = 0; i < FB_KV; i++) {
      if (i >= HWIN) mbar_wait(bar0 + 8 * (i - HWIN));
      wait_until(t_off + (i < 4 ? 2 * i + ((b >> 1) & 1) : 4 * i - 8 + (b & 3)) * (RATE_H / 4));
      if (lane == 0) {
        if (i < 4) tma3d(sb + OFF_WQ + i * 16384, &tms.m[0], bar0 + 8 * i, 0, i * 128, 2 * hd + rk);
        else tma3d(sb + OFF_WQ + i * 16384, &tms.m[1], bar0 + 8 * i, 0, (b & 3) * 128 + (i - 4) * 64, 2 * hd);
      }
      __syncwarp();
    }
  }
  if (warp == 10) {
    const uint4 xa = ldc16(x + 16 * lane), xb = ldc16(x + 16 * lane + 8);
    const unsigned ep = ldc4(&g_epoch);
    float xv[16] = {bflo(xa.x), bfhi(xa.x), bflo(xa.y), bfhi(xa.y), bflo(xa.z), bfhi(xa.z), bflo(xa.w), bfhi(xa.w),
                    bflo(xb.x), bfhi(xb.x), bflo(xb.y), bfhi(xb.y), bflo(xb.z), bfhi(xb.z), bflo(xb.w), bfhi(xb.w)};
    float s = 0;
#pragma unroll
    for (int i = 0; i < 16; i++) s += xv[i];
#pragma unroll
    for (int o = 16; o; o >>= 1) s += __shfl_xor_sync(~0u, s, o);
    const float mean = s * (1.f / 512.f);
    s = 0;
#pragma unroll
    for (int i = 0; i < 16; i++) { xv[i] -= mean; s += xv[i] * xv[i]; }
#pragma unroll
    for (int o = 16; o; o >>= 1) s += __shfl_xor_sync(~0u, s, o);
    const float rstd = rsqrtf(s * (1.f / 512.f) + 1e-5f);
    if ((lane >> 1) == (b & 15))
#pragma unroll
      for (int i = 0; i < 4; i++)
        *(float4*)(smem + OFF_SM + (256 + (lane & 1) * 16 + 4 * i) * 4) = make_float4(xv[4 * i] * rstd, xv[4 * i + 1] * rstd, xv[4 * i + 2] * rstd, xv[4 * i + 3] * rstd);
    if (lane == 0) *(volatile unsigned*)(smem + OFF_MASK + 8) = ep;
    nbar_arrive(1, 288);
  }
  if (warp >= 8) {
    asm volatile("setmaxnreg.dec.sync.aligned.u32 72;");
    if (tid == 288) {
#pragma unroll
      for (int q = FB_KV; q < FB_KV + 16; q++) { BAR_INIT(q, 1); BAR_ARM(q, 32768); }
    }
    if (tid == 320) {
#pragma unroll
      for (int q = 0; q <= 13 + NSLOT; q++) BAR_INIT(EB + q, q == 0 ? 4 : q < 5 ? 16 : q < 16 ? 12 : 6);
    }
    if (tid == 256) {
#pragma unroll
      for (int q = FB_MOD; q <= FB_D; q++) { BAR_INIT(q, 1); BAR_ARM(q, 16384); }
      BAR_INIT(QB, 9); BAR_ARM(QB, 1024);
#pragma unroll
      for (int q = 0; q < 7; q++) BAR_INIT(XB + q, q == 2 ? 256 : q == 5 || q == 3 ? 9 : 1);
      BAR_ARM(XB + 3, 1024);
      BAR_ARM(XB + 5, 1024 + 64 + 512);
      *(volatile unsigned long long*)(smem + OFF_MASK) = 0;
    }
    if (warp != 11) {
      __syncwarp();
      asm volatile("fence.mbarrier_init.release.cluster;" ::: "memory");
      __threadfence_block();
      asm volatile("barrier.cluster.arrive.relaxed.aligned;" ::: "memory");
    }
    if (warp == 11) {
      asm volatile("barrier.cluster.wait.acquire.aligned;" ::: "memory");
      const unsigned epoch = *(volatile unsigned*)(smem + OFF_MASK + 8), par = (epoch + 1) & 1;
      mbar_wait(bar0 + 8 * (FB_KV + 15));
      for (int it = 0; ldx4(scr->cnt + 96 + 32 * (b >> 6)) != (epoch + 1) * 64 && it < SPIN_MAX; it++) {}
      uint4 hh;
      POLL { hh = ldx16(g_ml + (b >> 2) * 64 + 2 * lane); RETRY(X16(hh)) }
      int mi = __float_as_int(fmaxf(u2f(hh.x), u2f(hh.z)));
      mi ^= (mi >> 31) & 0x7fffffff;
      mi = __reduce_max_sync(~0u, mi);
      mi ^= (mi >> 31) & 0x7fffffff;
      const float M = __int_as_float(mi);
      const uint32_t wp = pack2(ex2(u2f(hh.x) - M), ex2(u2f(hh.z) - M));
      float L = bflo(wp) * u2f(hh.y) + bfhi(wp) * u2f(hh.w);
#pragma unroll
      for (int o2 = 16; o2; o2 >>= 1) L += __shfl_xor_sync(~0u, L, o2);
      *(uint32_t*)(smem + OFF_RA + lane * 4) = wp;
      if (lane == 0) *(float*)(smem + OFF_RA + 128) = rcp(L);
      __syncwarp();
      if (lane == 0) BAR_ARRIVE(XB + 6);
    }
    if (warp == 10) {
      if (lane < 8) asm volatile("prefetch.tensormap [%0];" ::"l"(&tms.m[lane + 1]) : "memory");
      asm volatile("barrier.cluster.wait.acquire.aligned;" ::: "memory");
      const unsigned epoch = *(volatile unsigned*)(smem + OFF_MASK + 8);
#pragma unroll 1
      for (int e = 0; e < 2; e++) {
        for (int it = 0; ldx4(scr->cnt + (e ? 2 + rk : 1)) != (epoch + 1) * (e ? 64 : 128) && it < SPIN_MAX; it++) {}
        if (lane == 0) BAR_ARRIVE(XB + e);
      }
      mbar_wait(bar0 + 8 * (FB_KV + 14));
      unsigned long long m = 0;
#pragma unroll 1
      for (int it = 0; ~m && it < SPIN_MAX; it++) {
        m = ldx64(scr->cnt + 32 + 32 * (b >> 6)) ^ ((epoch & 1) ? ~0ull : 0ull);
        if (lane == 0) *(volatile unsigned long long*)(smem + OFF_MASK) = m;
      }
    }
    if (warp == 9) {
      asm volatile("barrier.cluster.wait.acquire.aligned;" ::: "memory");
      const unsigned epoch = *(volatile unsigned*)(smem + OFF_MASK + 8);
      const unsigned par = (epoch + 1) & 1, inv = par ^ 1;
      const uint4 inv4 = make_uint4(inv, inv, inv, inv);
      mbar_wait(bar0 + 8 * FB_KV);
#pragma unroll 2
      for (int k = 0; k < 8; k++) {
        const uint32_t cp = ldc4(cvec + 2 * (lane + 32 * k));
        *(uint32_t*)(smem + OFF_SILU + (lane + 32 * k) * 4) = pack2(silu_bf(bflo(cp)), silu_bf(bfhi(cp)));
      }
      __syncwarp();
      mbar_wait(bar0 + 8 * FB_MOD);
      const uint32_t ab = sb + OFF_MOD + (8 * (lane >> 4) + (lane & 7)) * 32 + ((((lane >> 3) ^ (lane >> 2)) & 1) << 4);
      float d[4][4] = {};
#pragma unroll 2
      for (int s4 = 0; s4 < 8; s4++)
#pragma unroll
        for (int s = 0; s < 4; s++) {
          uint32_t a[4];
          const uint32_t* ps = (const uint32_t*)(smem + OFF_SILU) + 32 * s4 + 8 * s + tq;
          ldsm_t(a, ab + (4 * s4 + s) * 512); mma16(d[s], a, ps[0], ps[4]);
        }
      const float t = (tq & 1) ? (d[0][2] + d[1][2]) + (d[2][2] + d[3][2]) : (d[0][0] + d[1][0]) + (d[2][0] + d[3][0]);
      if (tq < 2) stx4(g_xm + b * 16 + 2 * (g & 6) + 2 * tq + (g & 1), fbits(bfr(t)));
      __syncwarp();
      if (lane == 0) CNT_ADD(6);
      mbar_wait(bar0 + 8 * (FB_KV + 8));
      if (lane < 16) stx16(g_xc + (b >> 2) * 256 + (lane >> 1) * 32 + (b & 3) * 8 + (lane & 1) * 4, inv4);
      if (lane < 8) stx16(g_xao + (b >> 5) * 1024 + (b & 15) * 64 + (lane & 4) * 8 + (b & 16) + (lane & 3) * 4, inv4);
      if (b < 112)
#pragma unroll 1
        for (int k = 0; k < 4; k++) stx16(g_xf + b * 512 + (lane + 32 * k) * 4, inv4);
      nbar_arrive(2, 288);
      for (int it = 0; ldx4(scr->cnt + 6) != (epoch + 1) * 128 && it < SPIN_MAX; it++) __nanosleep(100);
      {
        uint4 sv[2], cb[2];
        unsigned ga, gb;
        POLL {
#pragma unroll
          for (int k = 0; k < 2; k++) { sv[k] = ldx16(g_xm + 512 + 256 * rk + 4 * (lane + 32 * k)); cb[k] = ldx16(g_xm + 1024 + 256 * rk + 4 * (lane + 32 * k)); }
          ga = ldx4(g_xm + (b & 15) * 32 + lane); gb = ldx4(g_xm + 1536 + 256 * rk + 8 * (pr & 31) + (lane & 7));
          RETRY(X16(sv[0]) | X16(sv[1]) | X16(cb[0]) | X16(cb[1]) | lop_x3(ga, gb, par))
        }
#pragma unroll
        for (int k = 0; k < 2; k++) {
          const float c0 = bfr(1.f + bfhi(cb[k].x)), c1 = bfr(1.f + bfhi(cb[k].y)), c2 = bfr(1.f + bfhi(cb[k].z)), c3 = bfr(1.f + bfhi(cb[k].w));
          *(float4*)(smem + OFF_CO + (lane + 32 * k) * 16) = make_float4(c0, c1, c2, c3);
          uint2* pb = (uint2*)(smem + OFF_BP) + lane + 32 * k;
          pb[0] = make_uint2(pack2(c0, c1), pack2(c2, c3));
          pb[64] = make_uint2(__byte_perm(sv[k].x, sv[k].y, 0x7632), __byte_perm(sv[k].z, sv[k].w, 0x7632));
        }
        *(float*)(smem + OFF_CO + 1024 + lane * 4) = bfhi(ga);
        *(float*)(smem + OFF_CO + 1152 + lane * 4) = bfhi(gb);
      }
      __syncwarp();
      if (lane == 0) BAR_ARRIVE(XB + 4);
    }
    if (warp == 8) {
      const unsigned stag = ((pr * SMUL) & 63) * RATE_NS >> 6;
      unsigned tnext = t_off + 4 * RATE_H;
      asm volatile("barrier.cluster.wait.acquire.aligned;" ::: "memory");
#pragma unroll 1
      for (int k = 0; k < 24; k++) {
        const int code = (k < 12 ? ORDER0 >> (5 * k) : ORDER1 >> (5 * (k - 12))) & 31;
        const bool kv = code < 16;
        const int n = code, w = code - 16;
        if (!kv && w >= 5 && b >= 112) break;
        if (kv) mbar_wait(bar0 + 8 * (FB_KV + n - (n < 6 ? EWIN : KVWIN)));
        if (k >= TAIL_K) mbar_wait(bar0 + 8 * (FB_KV + (int)((ORDER1 >> (5 * (k - 12 - ((WINS >> (4 * (k - TAIL_K))) & 15)))) & 31)));
        const int e = kv ? (n == 3 ? 2 : n == 5 ? 1 : n) : w == 0 ? 0 : w < 5 ? 16 + ((w - 1) >> 1) : w == 7 ? 19 : 18;
        if (e != 1 && k) mbar_wait(bar0 + 8 * (EB + e));
        wait_until(tnext + stag);
        tnext += k > TAIL_K ? RATE_TL : k < 4 ? RATE_E : RATE_NS;
        if (lane == 0) {
          if (kv)
            asm volatile("cp.async.bulk.tensor.3d.shared::cluster.global.mbarrier::complete_tx::bytes.multicast::cluster.L2::cache_hint [%0], [%1, {%3, %4, %5}], [%2], %6, %7;"
                         ::"r"(sb + (n % NSLOT) * SLOT + rk * 16384), "l"(&tms.m[2]), "r"(bar0 + 8 * (FB_KV + n)), "r"(0), "r"(((n >> 1) * 64 + pr) * 64),
                           "r"(4 * (n & 1) + 2 * rk), "h"((unsigned short)3), "l"(stream_policy()) : "memory");
          else {
            tma3d(sb + (w == 0 ? OFF_MOD : w < 5 ? OFF_UV + (w - 1) * 16384 : w == 5 ? OFF_G : w == 6 ? OFF_U : OFF_D),
                  &tms.m[w == 0 ? 3 : w < 3 ? 4 : w < 5 ? 5 : w + 1], bar0 + 8 * (FB_MOD + w),
                  w == 0 ? 1024 + b * 16 : w < 3 || w == 7 ? 0 : w < 5 ? (pr & 7) * 64 : pr * 32, w == 7 ? b * 16 : w == 1 || w == 2 ? (b & 3) * 128 + (w - 1) * 64 : 0,
                  w == 1 || w == 2 ? 2 * hd : w == 3 || w == 4 ? (b >> 4) * 4 + 2 * rk + w - 3 : w == 5 || w == 6 ? rk : 0);
          }
        }
        __syncwarp();
      }
    }
    if (b < 112) {
      const int mt = warp & 1, dd = (warp >> 1) & 1;
      mbar_wait(bar0 + 8 * (XB + 4));
      const uint32_t ab = sb + (mt ? OFF_U : OFF_G) + (8 * (lane >> 4) + (lane & 7)) * 64 + (((2 * dd + ((lane >> 3) & 1)) ^ ((lane >> 1) & 3)) << 4);
      uint32_t base;
      asm volatile("mapa.shared::cluster.u32 %0, %1, %2;" : "=r"(base) : "r"(sb), "r"(dd));
      uint2 bb[16];
#pragma unroll
      for (int s = 0; s < 16; s++) bb[s] = *(const uint2*)(smem + OFF_BP + (g & 1) * 512 + (4 * s + tq) * 8);
      mbar_wait(bar0 + 8 * (FB_G + mt));
      float e[4][4] = {};
#pragma unroll
      for (int s = 0; s < 16; s++) { uint32_t a[4]; ldsm_t(a, ab + s * 1024); mma16(e[s & 3], a, bb[s].x, bb[s].y); }
      float r[4];
#pragma unroll
      for (int i = 0; i < 4; i++) r[i] = (e[0][i] + e[1][i]) + (e[2][i] + e[3][i]);
      if (tq < 2) st_async2(base + OFF_R4 + (8 * mt + g) * 176 + (10 * rk + 8 + tq) * 8, base + OFF_BAR + 8 * (XB + 5), tq ? r[1] : r[0], tq ? r[3] : r[2]);
    }
    return;
  }

  float* s_sm = (float*)(smem + OFF_SM);
  unsigned par, epoch;
  uint32_t rsb;
  {
    float* s_r4 = (float*)(smem + OFF_R4);
    asm volatile("barrier.cluster.arrive.relaxed.aligned;" ::: "memory");
    asm volatile("mapa.shared::cluster.u32 %0, %1, %2;" : "=r"(rsb) : "r"(sb), "r"(rk ^ 1));
    const float c0 = (arow & 1) ? bfhi(c0w) : bflo(c0w), c1 = (arow & 1) ? bfhi(c1w) : bflo(c1w);
    float acc[8] = {0, 0, 0, 0, 0, 0, 0, 0};
    fma8(acc, wm0, silu_bf(c0)); fma8(acc, wm1, silu_bf(c1));
    tred<4>(acc, lane, 8); tred<2>(acc, lane, 16);
    *(float2*)(s_r4 + warp * 64 + 8 * (lane & 7) + ((lane >> 1) & 4) + ((lane >> 3) & 2)) = make_float2(acc[0], acc[1]);
    nbar(1, 288);
    epoch = *(volatile unsigned*)(smem + OFF_MASK + 8);
    par = (epoch + 1) & 1;
    if (warp == 0) {
      float t = 0.f, ca = b < 16 ? 1.f : 0.f;
#pragma unroll
      for (int w = 0; w < 8; w++) { t += s_r4[w * 64 + lane]; ca += s_r4[w * 64 + 32 + lane]; }
      t += ca * s_sm[256 + lane];
      const float nb = __shfl_down_sync(~0u, t, 1);
      const uint32_t w0 = lane < 8 ? pack2t(t, nb, par) : pack2(t, nb);
      const uint32_t w1 = __shfl_down_sync(~0u, w0, 8), w2 = __shfl_down_sync(~0u, w0, 16), w3 = __shfl_down_sync(~0u, w0, 24);
      if (lane < 8 && !(lane & 1)) stx16(g_h + (b >> 5) * 512 + (b & 15) * 32 + (b & 16) + 2 * lane, make_uint4(w0, w1, w2, w3));
      __syncwarp();
      if (lane == 0) CNT_ADD(1);
    }
  }
  asm volatile("barrier.cluster.wait.acquire.aligned;" ::: "memory");
  {
    uint32_t a[4][4][4];
    mbar_wait(bar0 + 8 * (warp >> 1));
    const uint32_t ab = sb + OFF_WQ + (64 * warp + 8 * (lane >> 4) + (lane & 7)) * 128;
#pragma unroll
    for (int s = 0; s < 4; s++)
#pragma unroll
      for (int mt = 0; mt < 4; mt++) ldsm_t(a[s][mt], ab + s * 2048 + (((2 * mt + ((lane >> 3) & 1)) ^ (lane & 7)) << 4));
    uint4 v0, v1;
    const unsigned* ph = g_h + (g >> 1) * 512 + 64 * warp + 4 * (lane & 7);
    uint32_t off = OFF_B + warp * 272 + (32 * rk + 8 * tq + (lane & 4)) * 4;
    PIN(off); PINL(ph);
    mbar_wait(bar0 + 8 * XB);
    POLL { v0 = ldx16(ph); v1 = ldx16(ph + 32); RETRY(lop_x3(v0.x, v1.x, par)) }
    float d[4][4] = {};
#pragma unroll
    for (int mt = 0; mt < 4; mt++) {
      mma16(d[mt], a[0][mt], v0.x, v0.y); mma16(d[mt], a[1][mt], v0.z, v0.w);
      mma16(d[mt], a[2][mt], v1.x, v1.y); mma16(d[mt], a[3][mt], v1.z, v1.w);
    }
    float r[8];
#pragma unroll
    for (int mt = 0; mt < 4; mt++) { r[2 * mt] = d[mt][0] + d[mt][1]; r[2 * mt + 1] = d[mt][2] + d[mt][3]; }
    tred<4>(r, lane, 2); tred<2>(r, lane, 1);
    const float rc = __shfl_xor_sync(~0u, (lane & 4) ? r[0] : r[1], 4);
    const uint32_t wd = (lane & 4) ? pack2(rc, r[1]) : pack2(r[0], rc);
    const uint32_t w1 = __shfl_down_sync(~0u, wd, 8), w2 = __shfl_down_sync(~0u, wd, 16), w3 = __shfl_down_sync(~0u, wd, 24);
    asm volatile("{.reg .pred p; setp.lt.s32 p, %7, 8; @p st.shared.v4.b32 [%0], {%2,%3,%4,%5};\n"
                 "@p st.async.shared::cluster.mbarrier::complete_tx::bytes.v4.b32 [%1], {%2,%3,%4,%5}, [%6];}"
                 ::"r"(sb + off), "r"(rsb + off), "r"(wd), "r"(w1), "r"(w2), "r"(w3), "r"(rsb + OFF_BAR + 8 * QB), "r"(lane) : "memory");
    __syncwarp();
    arrive2(bar0 + 8 * QB, 0, lane == 0, false);
    arrive2(bar0 + 8 * (EB + 2), rsb + OFF_BAR + 8 * (EB + 2), lane == 0, lane == 0);
  }
  {
    uint32_t a[8][4];
    uint32_t a_bq = sb + OFF_B + (lane & 7) * 272 + (lane >> 3) * 16;
    unsigned* p_qa = g_qa + b * 64 + 8 * warp + 4 * lane;
    PIN(a_bq); PINL(p_qa);
    mbar_wait(bar0 + 8 * (FB_UK + (warp >> 2)));
    const uint32_t ab = sb + OFF_WUK + (warp >> 2) * 16384 + (16 * (warp & 3) + (lane & 15)) * 128;
#pragma unroll
    for (int s = 0; s < 8; s++) ldsm(a[s], ab + (s >> 2) * 8192 + (((2 * (s & 3) + (lane >> 4)) ^ (lane & 7)) << 4));
    mbar_wait(bar0 + 8 * QB);
    float d[4][4] = {};
#pragma unroll
    for (int y = 0; y < 4; y++) {
      uint32_t bq[4];
      ldsm(bq, a_bq + 64 * y);
      mma16(d[(2 * y) & 3], a[2 * y], bq[0], bq[1]); mma16(d[(2 * y + 1) & 3], a[2 * y + 1], bq[2], bq[3]);
    }
    float r[2] = {((d[0][0] + d[0][1]) + (d[1][0] + d[1][1])) + ((d[2][0] + d[2][1]) + (d[3][0] + d[3][1])),
                  ((d[0][2] + d[0][3]) + (d[1][2] + d[1][3])) + ((d[2][2] + d[2][3]) + (d[3][2] + d[3][3]))};
    tred<1>(r, lane, 1);
    r[0] += __shfl_xor_sync(~0u, r[0], 2);
    const float nb = __shfl_xor_sync(~0u, r[0], 4);
    const uint32_t w0 = lane < 8 ? pack2t(r[0], nb, par) : pack2(r[0], nb);
    const uint32_t w1 = __shfl_down_sync(~0u, w0, 8), w2 = __shfl_down_sync(~0u, w0, 16), w3 = __shfl_down_sync(~0u, w0, 24);
    if (lane < 2) stx16(p_qa, make_uint4(w0, w1, w2, w3));
    arrive2(bar0 + 8 * (EB + 4), rsb + OFF_BAR + 8 * (EB + 4), lane == 0, lane == 0);
  }
  {
    if (warp) nbar_arrive(3, 256); else { nbar(3, 256); if (lane == 0) CNT_ADD(2 + (b >> 6)); }
    asm volatile("setmaxnreg.inc.sync.aligned.u32 216;");
    const unsigned* pq = g_qa + rk * 4096 + tid * 4;
    uint32_t a_q = sb + OFF_Q + ((tid & 63) >> 3) * 2048 + (tid >> 6) * 128 + (((tid & 7) ^ (tid >> 6)) << 4);
    PINL(pq); PIN(a_q);
    mbar_wait(bar0 + 8 * (XB + 1));
    uint4 v[4];
    POLL {
#pragma unroll
      for (int k = 0; k < 4; k++) v[k] = ldx16(pq + 1024 * k);
      RETRY(lop_x3(v[0].x, v[1].x, par) | lop_x3(v[2].x, v[3].x, par))
    }
#pragma unroll
    for (int k = 0; k < 4; k++)
      asm volatile("st.shared.v4.b32 [%0], {%1,%2,%3,%4};" ::"r"((a_q + k * 512) ^ ((k & 1) << 6)), "r"(v[k].x), "r"(v[k].y), "r"(v[k].z), "r"(v[k].w) : "memory");
    if (warp >= 4) nbar_arrive(1, 256); else nbar(1, 256);
  }
  sb = __shfl_sync(~0u, sb, 0); bar0 = sb + OFF_BAR;
  if (warp < 4) {
    uint32_t qf[32][4];
#pragma unroll
    for (int s = 0; s < 32; s++) ldsm(qf[s], sb + OFF_Q + (s >> 2) * 2048 + (lane & 15) * 128 + (((2 * (s & 3) + (lane >> 4)) ^ (lane & 7)) << 4));
    float l0 = 0.f, l1 = 0.f, m0 = -1e30f, m1 = -1e30f;
    const float sc = 0.08838834764831845f * 1.4426950408889634f;
    const uint32_t kofs = (16 * warp + 8 * (lane >> 4) + (lane & 7)) * 128 + ((((lane >> 3) & 1) ^ (lane & 7)) << 4);
    uint32_t st = sb;
#pragma unroll 1
    for (int t = 0; t < 8; t++) {
      float sa[4][4] = {};
#pragma unroll
      for (int hf = 0; hf < 2; hf++) {
        const int n = 2 * t + hf;
        mbar_wait(bar0 + 8 * (FB_KV + n));
        uint32_t kf[16][4];
#pragma unroll
        for (int y = 0; y < 16; y++) ldsm(kf[y], st + (y >> 2) * 8192 + (kofs ^ ((y & 3) << 5)));
#pragma unroll
        for (int y = 0; y < 16; y++) {
          mma16(sa[(2 * y) & 3], qf[16 * hf + y], kf[y][0], kf[y][1]); mma16(sa[((2 * y) & 3) + 1], qf[16 * hf + y], kf[y][2], kf[y][3]);
        }
        __syncwarp();
        arrive2(bar0 + 8 * (EB + NSLOT + n), rsb + OFF_BAR + 8 * (EB + NSLOT + n), lane == 0 && n < 14, lane == 0 && n < 16 - NSLOT);
        if (hf == 0) arrive2(bar0 + 8 * EB, 0, lane == 0 && t == 0, false);
        st = st + SLOT == sb + NSLOT * SLOT ? sb : st + SLOT;
      }
#pragma unroll
      for (int i = 0; i < 4; i++) { sa[0][i] = (sa[0][i] + sa[2][i]) * sc; sa[1][i] = (sa[1][i] + sa[3][i]) * sc; }
      float cm[2] = {fmaxf(fmaxf(sa[0][0], sa[0][1]), fmaxf(sa[1][0], sa[1][1])), fmaxf(fmaxf(sa[0][2], sa[0][3]), fmaxf(sa[1][2], sa[1][3]))};
      tmax<1>(cm, lane, 1);
      cm[0] = fmaxf(cm[0], __shfl_xor_sync(~0u, cm[0], 2));
      float* pm = s_sm + (t & 1) * 64;
      if (tq < 2) pm[(g + 8 * tq) * 4 + warp] = cm[0];
      if (t >= 2) nbar(6 + (t & 1), 256); else nbar(3, 128);
      const float4 a0 = *(const float4*)(pm + g * 4), b0 = *(const float4*)(pm + g * 4 + 32);
      const float n0 = fmaxf(fmaxf(fmaxf(a0.x, a0.y), fmaxf(a0.z, a0.w)), m0), n1 = fmaxf(fmaxf(fmaxf(b0.x, b0.y), fmaxf(b0.z, b0.w)), m1);
      uint32_t pk[4];
#pragma unroll
      for (int i = 0; i < 2; i++) { pk[2 * i] = pack2(ex2(sa[i][0] - n0), ex2(sa[i][1] - n0)); pk[2 * i + 1] = pack2(ex2(sa[i][2] - n1), ex2(sa[i][3] - n1)); }
      *(uint4*)(smem + OFF_P + (t & 1) * 2048 + tid * 16) = make_uint4(pk[0], pk[1], pk[2], pk[3]);
      const float al0 = ex2(m0 - n0), al1 = ex2(m1 - n1);
      if (tid < 32 && tq == 0) *(float2*)(s_sm + 192 + (t & 1) * 16 + 2 * g) = make_float2(al0, al1);
      nbar_arrive(4 + (t & 1), 256);
      m0 = n0; m1 = n1;
      l0 = l0 * al0 + (bflo(pk[0]) + bfhi(pk[0])) + (bflo(pk[2]) + bfhi(pk[2]));
      l1 = l1 * al1 + (bflo(pk[1]) + bfhi(pk[1])) + (bflo(pk[3]) + bfhi(pk[3]));
    }
    float lr[2] = {l0, l1};
    tred<1>(lr, lane, 1);
    lr[0] += __shfl_xor_sync(~0u, lr[0], 2);
    if (tq < 2) s_sm[128 + (g + 8 * tq) * 4 + warp] = lr[0];
    nbar(3, 128);
    if (warp == 0 && tq < 2) {
      const float4 a0 = *(const float4*)(s_sm + 128 + (g + 8 * tq) * 4);
      stx8(g_ml + (16 * rk + g + 8 * tq) * 64 + pr, make_uint2(fbits(tq ? m1 : m0), fbits((a0.x + a0.y) + (a0.z + a0.w))));
    }
    if (warp == 0) { __syncwarp(); if (lane == 0) CNT_ADD(96 + 32 * rk); }
    nbar(2, 288);
    if (tid == 0) asm volatile("red.relaxed.gpu.global.xor.b64 [%0], %1;" ::"l"(scr->cnt + 32 + 32 * rk), "l"(1ull << pr) : "memory");
  } else {
    float o[16][4] = {};
    const uint32_t vofs = (warp & 1) * 16384 + (lane & 15) * 128 + (((lane >> 4) ^ (lane & 7)) << 4);
    const int hf = (warp >> 1) & 1;
    uint32_t st = sb + hf * SLOT;
    auto pv = [&](const int t, auto np) {
      constexpr int npre = decltype(np)::value;
      uint32_t vf[4][8][4];
      const int n = 2 * t + hf;
      mbar_wait(bar0 + 8 * (FB_KV + n));
#pragma unroll
      for (int s = 0; s < npre; s++)
#pragma unroll
        for (int y = 0; y < 8; y++) ldsm_t(vf[s][y], st + (y >> 2) * 8192 + s * 2048 + (vofs ^ ((y & 3) << 5)));
      nbar(4 + (t & 1), 256);
      const float2 al = *(const float2*)(s_sm + 192 + (t & 1) * 16 + 2 * g);
      uint4 pf[4];
#pragma unroll
      for (int s = 0; s < 4; s++) pf[s] = *(const uint4*)(smem + OFF_P + (t & 1) * 2048 + s * 512 + lane * 16);
      if (t < 6) nbar_arrive(6 + (t & 1), 256);
#pragma unroll
      for (int s = npre; s < 4; s++)
#pragma unroll
        for (int y = 0; y < 8; y++) ldsm_t(vf[s][y], st + (y >> 2) * 8192 + s * 2048 + (vofs ^ ((y & 3) << 5)));
#pragma unroll
      for (int nt = 0; nt < 16; nt++) { o[nt][0] *= al.x; o[nt][1] *= al.x; o[nt][2] *= al.y; o[nt][3] *= al.y; }
#pragma unroll
      for (int s = 0; s < 4; s++) {
        const uint32_t pa[4] = {pf[s].x, pf[s].y, pf[s].z, pf[s].w};
#pragma unroll
        for (int y = 0; y < 8; y++) { mma16(o[2 * y], pa, vf[s][y][0], vf[s][y][1]); mma16(o[2 * y + 1], pa, vf[s][y][2], vf[s][y][3]); }
      }
      __syncwarp();
      arrive2(bar0 + 8 * (EB + NSLOT + n), rsb + OFF_BAR + 8 * (EB + NSLOT + n), lane == 0 && n < 14, lane == 0 && n < 16 - NSLOT);
      st = st + 2 * SLOT >= sb + NSLOT * SLOT ? st - (NSLOT - 2) * SLOT : st + 2 * SLOT;
    };
#pragma unroll 1
    for (int t = 0; t < 7; t++) pv(t, IC<NPRE0>());
    pv(7, IC<NPRE1>());
    uint4* po = g_xo + ((size_t)((16 * rk + (g & 6)) * 4 + warp - 4) * 64 + pr) * RS + (lane & 7);
    const bool odd = lane & 4;
#pragma unroll
    for (int e = 0; e < 2; e++)
#pragma unroll
      for (int j2 = 0; j2 < 2; j2++) {
        uint32_t c0[4], c1[4];
#pragma unroll
        for (int i = 0; i < 4; i++) {
          c0[i] = i ? pack2(o[8 * j2 + i][2 * e], o[8 * j2 + i][2 * e + 1]) : pack2t(o[8 * j2][2 * e], o[8 * j2][2 * e + 1], par);
          c1[i] = i ? pack2(o[8 * j2 + 4 + i][2 * e], o[8 * j2 + 4 + i][2 * e + 1]) : pack2t(o[8 * j2 + 4][2 * e], o[8 * j2 + 4][2 * e + 1], par);
          const uint32_t r = __shfl_xor_sync(~0u, odd ? c0[i] : c1[i], 4);
          if (odd) c0[i] = r; else c1[i] = r;
        }
        stx16(po + e * 8 * 4 * 64 * RS + 8 * j2, make_uint4(c0[0], c0[1], c0[2], c0[3]));
        stx16(po + (e * 8 + 1) * 4 * 64 * RS + 8 * j2, make_uint4(c1[0], c1[1], c1[2], c1[3]));
      }
    nbar_arrive(2, 288);
  }
  tail(smem, scr, x, out, par, epoch, warp);
}

static void launch(void* const* d_in, void* d_out) {
  static TMaps tms;
  static bool init = false;
  static void* scr = nullptr;
  if (!init) {
    void* fn = nullptr; cudaDriverEntryPointQueryResult qr;
    cudaGetDriverEntryPoint("cuTensorMapEncodeTiled", &fn, cudaEnableDefault, &qr);
    EncFn f = (EncFn)fn;
    const CUtensorMapSwizzle S32 = CU_TENSOR_MAP_SWIZZLE_32B, S64 = CU_TENSOR_MAP_SWIZZLE_64B, S128 = CU_TENSOR_MAP_SWIZZLE_128B;
    const CUtensorMapL2promotion P128 = CU_TENSOR_MAP_L2_PROMOTION_L2_128B, P256 = CU_TENSOR_MAP_L2_PROMOTION_L2_256B;
    enc3d(f, &tms.m[0], d_in[2], 64, 512, 64, 8192, 128, 64, 128, 1, S128, P128);
    enc3d(f, &tms.m[1], d_in[3], 64, 512, 64, 8192, 128, 64, 64, 2, S128, P256);
    enc3d(f, &tms.m[2], d_in[1], 64, SK, 8, 1024, 128, 64, 64, 2, S128, P256);
    enc3d(f, &tms.m[3], d_in[11], 3072, 256, 2, 6144, 256 * 6144, 16, 256, 2, S32, P128);
    enc3d(f, &tms.m[4], d_in[4], 64, 512, 64, 8192, 128, 64, 64, 2, S128, P256);
    enc3d(f, &tms.m[5], d_in[5], 512, 128, 32, 1024, 128 * 1024, 64, 128, 1, S128, P128);
    enc3d(f, &tms.m[6], d_in[7], 1792, 256, 2, 3584, 256 * 3584, 32, 256, 1, S64, P128);
    enc3d(f, &tms.m[7], d_in[8], 1792, 256, 2, 3584, 256 * 3584, 32, 256, 1, S64, P128);
    enc3d(f, &tms.m[8], d_in[9], 64, 1792, 8, 1024, 128, 64, 16, 8, S128, P256);
    cudaFuncSetAttribute(fused_kernel, cudaFuncAttributeMaxDynamicSharedMemorySize, SMEM_BYTES);
    cudaGetSymbolAddress(&scr, g_scr);
    init = true;
  }
  fused_kernel<<<NCTA, 384, SMEM_BYTES>>>((const bf16*)d_in[0], (const bf16*)d_in[10], (const bf16*)d_in[11], (bf16*)d_out, (Scratch*)scr, tms);
}

}

extern "C" void kernel_launch(void* const* d_in, const int* in_sizes, int n_in, void* d_out, int out_size) {
  static int big = -1;
  if (big < 0) big = v9::fits();
  if (big) v9::launch(d_in, d_out); else v8::launch(d_in, d_out);
}
```

```cpp
#include <cuda_runtime.h>
#include <cuda_bf16.h>
#include <cuda.h>
#include <stdint.h>
#include <stdio.h>
#include <stdlib.h>

typedef CUresult (*EncFn)(CUtensorMap*, CUtensorMapDataType, cuuint32_t, void*, const cuuint64_t*, const cuuint64_t*,
                          const cuuint32_t*, const cuuint32_t*, CUtensorMapInterleave, CUtensorMapSwizzle,
                          CUtensorMapL2promotion, CUtensorMapFloatOOBfill);

static void enc3d(EncFn fn, CUtensorMap* tm, void* p, uint64_t d0, uint64_t d1, uint64_t d2, uint64_t s1, uint64_t s2, uint32_t b0,
                  uint32_t b1, uint32_t b2, CUtensorMapSwizzle sw, CUtensorMapL2promotion pr) {
  cuuint64_t gd[3] = {d0, d1, d2}, gs[2] = {s1, s2};
  cuuint32_t bx[3] = {b0, b1, b2}, es[3] = {1, 1, 1};
  fn(tm, CU_TENSOR_MAP_DATA_TYPE_BFLOAT16, 3, p, gd, gs, bx, es, CU_TENSOR_MAP_INTERLEAVE_NONE, sw, pr, CU_TENSOR_MAP_FLOAT_OOB_FILL_NONE);
}

namespace v9 {
typedef __nv_bfloat16 bf16;
#define SK 32768
#define SPIN_MAX (1 << 20)
template <int N> struct IC { static constexpr int value = N; };

__device__ __forceinline__ uint32_t s2u(const void* p) { return (uint32_t)__cvta_generic_to_shared(p); }
__device__ __forceinline__ float bflo(uint32_t u) { return __uint_as_float(u << 16); }
__device__ __forceinline__ float bfhi(uint32_t u) { return __uint_as_float(u & 0xffff0000u); }
__device__ __forceinline__ float u2f(uint32_t u) { return __uint_as_float(u); }
__device__ __forceinline__ void fma8(float* acc, uint4 v, float s) {
  acc[0] += s * bflo(v.x); acc[1] += s * bfhi(v.x); acc[2] += s * bflo(v.y); acc[3] += s * bfhi(v.y);
  acc[4] += s * bflo(v.z); acc[5] += s * bfhi(v.z); acc[6] += s * bflo(v.w); acc[7] += s * bfhi(v.w);
}
__device__ __forceinline__ uint32_t pack2(float a, float b) {
  __nv_bfloat162 p = __floats2bfloat162_rn(a, b); return *(uint32_t*)&p;
}
__device__ __forceinline__ float bfr(float v) { return bfhi(pack2(v, v)); }
__device__ __forceinline__ float silu_bf(float c) { return bfr(__fdividef(c, 1.f + __expf(-c))); }
#define fbits(v) ((__float_as_uint(v) & ~1u) | par)
__device__ __forceinline__ uint32_t pack2t(float a, float b, unsigned par) {
  const uint32_t ua = ((__float_as_uint(a) + ((par ^ 1) << 16)) & 0xFFFE0000u) | (par << 16);
  return __byte_perm(ua, pack2(b, b), 0x7632);
}
__device__ __forceinline__ void nbar(int id, int n) { asm volatile("bar.sync %0, %1;" ::"r"(id), "r"(n) : "memory"); }
__device__ __forceinline__ void nbar_arrive(int id, int n) { asm volatile("bar.arrive %0, %1;" ::"r"(id), "r"(n) : "memory"); }
__device__ __forceinline__ uint4 ldc16(const void* p) {
  uint4 v; asm volatile("ld.relaxed.cta.global.v4.u32 {%0,%1,%2,%3}, [%4];" : "=r"(v.x), "=r"(v.y), "=r"(v.z), "=r"(v.w) : "l"(p) : "memory"); return v;
}
__device__ __forceinline__ unsigned ldc4(const void* p) {
  unsigned v; asm volatile("ld.relaxed.cta.global.u32 %0, [%1];" : "=r"(v) : "l"(p) : "memory"); return v;
}
__device__ __forceinline__ uint4 ldx16(const void* p) {
  uint4 v; asm volatile("ld.relaxed.gpu.global.v4.u32 {%0,%1,%2,%3}, [%4];" : "=r"(v.x), "=r"(v.y), "=r"(v.z), "=r"(v.w) : "l"(p) : "memory"); return v;
}
__device__ __forceinline__ unsigned ldx4(const void* p) {
  unsigned v; asm volatile("ld.relaxed.gpu.global.u32 %0, [%1];" : "=r"(v) : "l"(p) : "memory"); return v;
}
__device__ __forceinline__ unsigned long long ldx64(const void* p) {
  unsigned long long v; asm volatile("ld.relaxed.gpu.global.u64 %0, [%1];" : "=l"(v) : "l"(p) : "memory"); return v;
}
__device__ __forceinline__ void stx16(void* p, uint4 v) {
  asm volatile("st.relaxed.gpu.global.v4.u32 [%0], {%1,%2,%3,%4};" ::"l"(p), "r"(v.x), "r"(v.y), "r"(v.z), "r"(v.w) : "memory");
}
__device__ __forceinline__ void stx8(void* p, uint2 v) { asm volatile("st.relaxed.gpu.global.v2.u32 [%0], {%1,%2};" ::"l"(p), "r"(v.x), "r"(v.y) : "memory"); }
__device__ __forceinline__ void stx4(void* p, unsigned v) { asm volatile("st.relaxed.gpu.global.u32 [%0], %1;" ::"l"(p), "r"(v) : "memory"); }
__device__ __forceinline__ void pub4(void* p, unsigned v) { asm volatile("red.relaxed.gpu.global.xor.b32 [%0], %1;" ::"l"(p), "r"(v) : "memory"); }
__device__ __forceinline__ void pub8(void* p, unsigned lo, unsigned hi) {
  asm volatile("{.reg .b64 t; mov.b64 t, {%1, %2}; red.relaxed.gpu.global.xor.b64 [%0], t;}" ::"l"(p), "r"(lo), "r"(hi) : "memory");
}
__device__ __forceinline__ unsigned lop_x3(unsigned a, unsigned b, unsigned c) {
  unsigned d; asm("lop3.b32 %0, %1, %2, %3, 0x7E;" : "=r"(d) : "r"(a), "r"(b), "r"(c)); return d; }
__device__ __forceinline__ unsigned or3(unsigned a, unsigned b, unsigned c) {
  unsigned d; asm("lop3.b32 %0, %1, %2, %3, 0xFE;" : "=r"(d) : "r"(a), "r"(b), "r"(c)); return d; }
__device__ __forceinline__ unsigned and3(unsigned a, unsigned b, unsigned c) {
  unsigned d; asm("lop3.b32 %0, %1, %2, %3, 0x80;" : "=r"(d) : "r"(a), "r"(b), "r"(c)); return d; }
__device__ __forceinline__ unsigned dep16(const uint32_t* f) {
  unsigned d = 0;
#pragma unroll
  for (int i = 0; i < 8; i++) d = or3(d, f[8 * i], f[8 * i + 4]);
  return d;
}
__device__ __forceinline__ uint2 ldx8(const void* p) {
  uint2 v; asm volatile("{.reg .b64 t; ld.relaxed.gpu.global.b64 t, [%2]; mov.b64 {%0, %1}, t;}" : "=r"(v.x), "=r"(v.y) : "l"(p) : "memory"); return v;
}
__device__ __forceinline__ float lds4(uint32_t a) { float v; asm volatile("ld.shared.f32 %0, [%1];" : "=f"(v) : "r"(a) : "memory"); return v; }
__device__ __forceinline__ float shx(float v, int m) {
  float r; asm volatile("shfl.sync.bfly.b32 %0, %1, %2, 0x1f, 0xffffffff;" : "=f"(r) : "f"(v), "r"(m)); return r;
}
__device__ __forceinline__ uint32_t mbar_test(uint32_t bar, uint32_t ph) {
  uint32_t ok;
  asm volatile("{.reg .pred p; mbarrier.test_wait.parity.shared::cta.b64 p, [%1], %2; vote.sync.all.pred p, p, 0xffffffff; selp.u32 %0, 1, 0, p;}"
               : "=r"(ok) : "r"(bar), "r"(ph) : "memory");
  return ok;
}
#define X16(v) (lop_x3(v.x, v.y, par) | lop_x3(v.z, v.w, par))
#define RETRY(bad) if (!__any_sync(~0u, (bad) & 1) || ++it_ >= SPIN_MAX) break;
#define POLL _Pragma("unroll 1") for (int it_ = 0;;)
__device__ __forceinline__ void mbar_wait(uint32_t bar, uint32_t ph = 0) {
  asm volatile("{.reg .pred p; .reg .u32 n; mov.u32 n, 0;\n"
               "W%=: mbarrier.try_wait.parity.shared::cta.b64 p, [%0], %1; add.u32 n, n, 1; setp.lt.and.u32 p, n, 0x100000, !p; @p bra W%=;}"
               ::"r"(bar), "r"(ph) : "memory");
}
__device__ __forceinline__ float ex2(float v) { float r; asm("ex2.approx.ftz.f32 %0, %1;" : "=f"(r) : "f"(v)); return r; }
__device__ __forceinline__ float rcp(float v) { float r; asm("rcp.approx.ftz.f32 %0, %1;" : "=f"(r) : "f"(v)); return r; }
__device__ __forceinline__ void mma16(float* d, const uint32_t* a, uint32_t b0, uint32_t b1) {
  asm volatile("mma.sync.aligned.m16n8k16.row.col.f32.bf16.bf16.f32 {%0,%1,%2,%3}, {%4,%5,%6,%7}, {%8,%9}, {%0,%1,%2,%3};"
               : "+f"(d[0]), "+f"(d[1]), "+f"(d[2]), "+f"(d[3]) : "r"(a[0]), "r"(a[1]), "r"(a[2]), "r"(a[3]), "r"(b0), "r"(b1));
}
__device__ __forceinline__ void mma16c(float* d, const uint32_t* a, uint32_t b0, uint32_t b1, const float* c) {
  asm volatile("mma.sync.aligned.m16n8k16.row.col.f32.bf16.bf16.f32 {%0,%1,%2,%3}, {%4,%5,%6,%7}, {%8,%9}, {%10,%11,%12,%13};"
               : "=f"(d[0]), "=f"(d[1]), "=f"(d[2]), "=f"(d[3])
               : "r"(a[0]), "r"(a[1]), "r"(a[2]), "r"(a[3]), "r"(b0), "r"(b1), "f"(c[0]), "f"(c[1]), "f"(c[2]), "f"(c[3]));
}
__device__ __forceinline__ float4 lds16(uint32_t a) {
  float4 v; asm volatile("ld.shared.v4.f32 {%0,%1,%2,%3}, [%4];" : "=f"(v.x), "=f"(v.y), "=f"(v.z), "=f"(v.w) : "r"(a) : "memory"); return v;
}
__device__ __forceinline__ uint4 ldsv16(uint32_t a) {
  uint4 v; asm volatile("ld.relaxed.cluster.shared.v4.u32 {%0,%1,%2,%3}, [%4];" : "=r"(v.x), "=r"(v.y), "=r"(v.z), "=r"(v.w) : "r"(a) : "memory"); return v;
}
__device__ __forceinline__ void sts4(uint32_t a, float v) { asm volatile("st.shared.f32 [%0], %1;" ::"r"(a), "f"(v) : "memory"); }
__device__ __forceinline__ void sts16(uint32_t a, uint4 v) {
  asm volatile("st.shared.v4.b32 [%0], {%1,%2,%3,%4};" ::"r"(a), "r"(v.x), "r"(v.y), "r"(v.z), "r"(v.w) : "memory");
}
__device__ __forceinline__ void ldsm_t(uint32_t* r, uint32_t a) {
  asm volatile("ldmatrix.sync.aligned.m8n8.x4.trans.shared.b16 {%0,%1,%2,%3}, [%4];" : "=r"(r[0]), "=r"(r[1]), "=r"(r[2]), "=r"(r[3]) : "r"(a) : "memory");
}
__device__ __forceinline__ void ldsm_tp(uint32_t* r, uint32_t a, uint32_t on) {
  asm volatile("{.reg .pred p; setp.ne.u32 p, %5, 0; @p ldmatrix.sync.aligned.m8n8.x4.trans.shared.b16 {%0,%1,%2,%3}, [%4];}"
               : "=r"(r[0]), "=r"(r[1]), "=r"(r[2]), "=r"(r[3]) : "r"(a), "r"(on) : "memory");
}
__device__ __forceinline__ void ldsm(uint32_t* r, uint32_t a) {
  asm volatile("ldmatrix.sync.aligned.m8n8.x4.shared.b16 {%0,%1,%2,%3}, [%4];" : "=r"(r[0]), "=r"(r[1]), "=r"(r[2]), "=r"(r[3]) : "r"(a) : "memory");
}
__device__ __forceinline__ uint32_t mapa(uint32_t a, uint32_t r) {
  uint32_t v; asm volatile("mapa.shared::cluster.u32 %0, %1, %2;" : "=r"(v) : "r"(a), "r"(r)); return v;
}
__device__ __forceinline__ unsigned long long mapg(uint32_t a, uint32_t r) {
  unsigned long long v;
  asm volatile("{.reg .u32 t; .reg .u64 u; mapa.shared::cluster.u32 t, %1, %2; cvt.u64.u32 u, t; cvta.shared::cluster.u64 %0, u;}" : "=l"(v) : "r"(a), "r"(r));
  return v;
}
template <int N>
__device__ __forceinline__ void tred(float* a, int lane, int m) {
  const bool hi = lane & m;
#pragma unroll
  for (int i = 0; i < N; i++) {
    float send = hi ? a[i] : a[i + N], keep = hi ? a[i + N] : a[i];
    a[i] = keep + __shfl_xor_sync(~0u, send, m);
  }
}
template <int N>
__device__ __forceinline__ void tmax(float* a, int lane, int m) {
  const bool hi = lane & m;
#pragma unroll
  for (int i = 0; i < N; i++) {
    float send = hi ? a[i] : a[i + N], keep = hi ? a[i + N] : a[i];
    a[i] = fmaxf(keep, __shfl_xor_sync(~0u, send, m));
  }
}
__device__ __forceinline__ void arrive_n(uint32_t bar, bool on, int cnt) {
  asm volatile("{.reg .pred p; setp.ne.s32 p, %1, 0; @p mbarrier.arrive.shared::cta.b64 _, [%0], %2;}" ::"r"(bar), "r"((int)on), "r"(cnt) : "memory");
}
__device__ __forceinline__ unsigned long long stream_policy() {
  unsigned long long p;
  asm volatile("createpolicy.fractional.L2::evict_first.b64 %0, 1.0;" : "=l"(p));
  return p;
}
__device__ __forceinline__ void tma3d(uint32_t dst, const CUtensorMap* tm, uint32_t bar, int c0, int c1, int c2) {
  asm volatile("cp.async.bulk.tensor.3d.shared::cluster.global.mbarrier::complete_tx::bytes.L2::cache_hint [%0], [%1, {%3, %4, %5}], [%2], %6;"
               ::"r"(dst), "l"(tm), "r"(bar), "r"(c0), "r"(c1), "r"(c2), "l"(stream_policy()) : "memory");
}
__device__ __forceinline__ void spin_until(unsigned t) { while ((int)((unsigned)clock() - t) < 0) {} }
__device__ __forceinline__ void wait_until(unsigned t) {
  unsigned now;
  do { asm volatile("mov.u32 %0, %%globaltimer_lo;" : "=r"(now)); } while ((int)(now - t) < 0);
}
__device__ __forceinline__ void sleep_until(unsigned t) {
  unsigned now;
#pragma unroll 1
  do {
    __nanosleep(200);
    asm volatile("mov.u32 %0, %%globaltimer_lo;" : "=r"(now));
  } while ((int)(now - t) < 0);
}
#define PIN(x) asm volatile("" : "+r"(x))
#define PINL(x) asm volatile("" : "+l"(x))
#define BAR_ARRIVE(i) asm volatile("mbarrier.arrive.shared::cta.b64 _, [%0];" ::"r"(bar0 + 8 * (i)) : "memory")
#define CNT_ADD(c) asm volatile("red.relaxed.gpu.global.inc.u32 [%0], 0xffffffff;" ::"l"(scr->cnt + (c)) : "memory")
#define BAR_INIT(i, cnt) asm volatile("mbarrier.init.shared::cta.b64 [%0], %1;" ::"r"(bar0 + 8 * (i)), "r"(cnt) : "memory")
#define BAR_ARM(i, bytes) asm volatile("mbarrier.arrive.expect_tx.shared::cta.b64 _, [%0], %1;" ::"r"(bar0 + 8 * (i)), "r"(bytes) : "memory")
struct TMaps { CUtensorMap m[9]; };

#define NCTA9 120
#define TAU 20.f
#define NSL 100
#define NPE 2
#define WTEST 600
#define QN 4
#define NPO 3
#define VDLY 150
#define O_Q 131072
#define O_LZ 163840
#define O_CTX 196608
#define O_HZ 198656
#define O_HW 200704
#define O_X 201728
#define O_P 218112
#define O_B 222208
#define O_R 224512
#define O_SILU 228608
#define O_SM 229632
#define O_BAR 231424
#define O_EP (O_BAR + 256)
#define O_DBG (O_EP + 16)
#define SMEM9 (O_DBG + 144)
#define B_FULL 0
#define B_FM 8
#define B_EMPTY 10
#define B_EM 18
#define B_LZ 18
#define B_Q2 19
#define B_H 20
#define B_QF 21
#define B_TAB 22
#define B_W 23
#define B_ST 24
#define B_HZ 25
#define B_WZ 26
#define B_G2 28
#define B_G 27
enum { T_WQ, T_WUK, T_KV, T_MOD, T_UV, T_WO, T_GU, T_DN = 8 };
#define NBIG 40
struct Sched { unsigned zero, dth; uint2 r[3][8]; unsigned nr[3], nt[3], dt, t4, d7, d4, d6; };

struct __align__(128) Scratch {
  unsigned cnt[8 * 32];
  uint2 rec[32 * 4 * 8 * 64];
  uint2 hdr[32 * 16];
  unsigned h[8 * 256];
  uint4 qa[2048];
  unsigned xao[8 * 512];
  unsigned xf[32 * 56 * 16];
  unsigned xm[2048];
};
__device__ Scratch g_scr;
#define SMEM_BASE 1024u
#define DSC ((SMEM_BASE >> 4) | (1u << 16))
#define HI128 (64u | (1u << 30))
#define HI64 (32u | (2u << 30))
template <int TA, int TB, unsigned HIA, unsigned HIB>
__device__ __forceinline__ void wgmma32(float* d, uint32_t da, uint32_t db, int acc) {
  asm volatile("{.reg .pred p; .reg .b64 da, db; setp.ne.b32 p, %18, 0; mov.b64 da, {%16, %21}; mov.b64 db, {%17, %22};\n"
               "wgmma.mma_async.sync.aligned.m64n32k16.f32.bf16.bf16 "
               "{%0,%1,%2,%3,%4,%5,%6,%7,%8,%9,%10,%11,%12,%13,%14,%15}, da, db, p, 1, 1, %19, %20;}"
               : "+f"(d[0]), "+f"(d[1]), "+f"(d[2]), "+f"(d[3]), "+f"(d[4]), "+f"(d[5]), "+f"(d[6]), "+f"(d[7]),
                 "+f"(d[8]), "+f"(d[9]), "+f"(d[10]), "+f"(d[11]), "+f"(d[12]), "+f"(d[13]), "+f"(d[14]), "+f"(d[15])
               : "r"(da), "r"(db), "r"(acc), "n"(TA), "n"(TB), "n"(HIA), "n"(HIB));
}
__device__ __forceinline__ void wgmma32r(float* d, const uint32_t* a, uint32_t db) {
  asm volatile("{.reg .b64 db; mov.b64 db, {%20, %21};\n"
               "wgmma.mma_async.sync.aligned.m64n32k16.f32.bf16.bf16 "
               "{%0,%1,%2,%3,%4,%5,%6,%7,%8,%9,%10,%11,%12,%13,%14,%15}, {%16,%17,%18,%19}, db, 1, 1, 1, 1;}"
               : "+f"(d[0]), "+f"(d[1]), "+f"(d[2]), "+f"(d[3]), "+f"(d[4]), "+f"(d[5]), "+f"(d[6]), "+f"(d[7]),
                 "+f"(d[8]), "+f"(d[9]), "+f"(d[10]), "+f"(d[11]), "+f"(d[12]), "+f"(d[13]), "+f"(d[14]), "+f"(d[15])
               : "r"(a[0]), "r"(a[1]), "r"(a[2]), "r"(a[3]), "r"(db), "n"(HI64));
}
template <int N> __device__ __forceinline__ void wg_wait(float* a) {
  asm volatile("wgmma.wait_group.sync.aligned %16;"
               : "+f"(a[0]), "+f"(a[1]), "+f"(a[2]), "+f"(a[3]), "+f"(a[4]), "+f"(a[5]), "+f"(a[6]), "+f"(a[7]), "+f"(a[8]), "+f"(a[9]), "+f"(a[10]),
                 "+f"(a[11]), "+f"(a[12]), "+f"(a[13]), "+f"(a[14]), "+f"(a[15]) : "n"(N) : "memory");
}
__device__ __forceinline__ float sum8(uint32_t a) {
  const float4 p = lds16(a), q = lds16(a + 1024);
  return ((p.x + p.y) + (p.z + p.w)) + ((q.x + q.y) + (q.z + q.w));
}
__device__ __forceinline__ int posof(int c) { return (c & ~14) + 2 * (c & 6) + ((c >> 2) & 2); }

__global__ void __cluster_dims__(8, 1, 1) __launch_bounds__(384, 1)
fused_kernel(const bf16* __restrict__ x, const bf16* __restrict__ cvec, const bf16* __restrict__ w_mod, bf16* __restrict__ out,
             Scratch* __restrict__ scr, const __grid_constant__ Sched sch, const __grid_constant__ TMaps tms) {
  extern __shared__ __align__(1024) unsigned char smem[];
  const int tid = threadIdx.x, warp = __shfl_sync(~0u, tid >> 5, 0), lane = tid & 31;
  const int b = blockIdx.x, cl = b >> 3, rn = b & 7, rk = b & 1, hd = b >> 1, f = b - 64;
  const bool isA = b < 64;
  uint32_t sb = s2u(smem), bar0 = sb + O_BAR;
  unsigned gt_start;
  asm volatile("mov.u32 %0, %%globaltimer_lo;" : "=r"(gt_start));
  const int g = lane >> 2, tq = lane & 3;
  const int arow = 64 * rn + ((tid & 255) >> 4);
  uint4 wm[4];
  uint32_t cw, xw;
  if (warp < 8 && isA) {
    const bf16* wa = w_mod + (size_t)arow * 3072 + (lane & 8) * 64 + 64 * cl + 8 * (lane & 7);
#pragma unroll
    for (int i = 0; i < 4; i++) wm[i] = ldx16(wa + i * 16 * 3072);
    cw = ldc4(cvec + (arow & ~1) + 16 * tq);
    if (warp < 2) xw = ldc4(x + 64 * cl + (tid & 62));
  }
  if (warp == 11) {
    if (lane == 0) {
#pragma unroll
      for (int i = 0; i < B_EMPTY; i++) BAR_INIT(i, 1);
    }
    __syncwarp();
    asm volatile("fence.mbarrier_init.release.cluster;" ::: "memory");
    asm volatile("barrier.cluster.arrive.relaxed.aligned;" ::: "memory");
    if (isA) {
#pragma unroll 1
      for (int i = 0; i < 8; i++) {
        if (i >= 6) mbar_wait(bar0 + 8 * (i - 6));
        wait_until(gt_start + ((64 * i + b) * sch.dth >> 8));
        if (lane == 0) {
          BAR_ARM(i, 16384);
          tma3d(sb + i * 16384, &tms.m[i >> 2], bar0 + 8 * i, 0, i < 4 ? 128 * i : 256 * rk + 64 * (i - 4), i < 4 ? b : b & ~1);
        }
        __syncwarp();
      }
    }
  }
  if (warp == 10) {
    const unsigned ep = ldc4(&scr->cnt[0]);
    if (isA) {
      const uint4 xa = ldc16(x + 16 * lane), xb = ldc16(x + 16 * lane + 8);
      float xv[16] = {bflo(xa.x), bfhi(xa.x), bflo(xa.y), bfhi(xa.y), bflo(xa.z), bfhi(xa.z), bflo(xa.w), bfhi(xa.w),
                      bflo(xb.x), bfhi(xb.x), bflo(xb.y), bfhi(xb.y), bflo(xb.z), bfhi(xb.z), bflo(xb.w), bfhi(xb.w)};
      const float x0 = __shfl_sync(~0u, xv[0], 0);
      float s = 0, q = 0;
#pragma unroll
      for (int i = 0; i < 16; i++) { xv[i] -= x0; s += xv[i]; q += xv[i] * xv[i]; }
#pragma unroll
      for (int o = 16; o; o >>= 1) { s += __shfl_xor_sync(~0u, s, o); q += __shfl_xor_sync(~0u, q, o); }
      s *= 1.f / 512.f;
      float rstd;
      asm("rsqrt.approx.ftz.f32 %0, %1;" : "=f"(rstd) : "f"(fmaxf(q * (1.f / 512.f) - s * s, 0.f) + 1e-5f));
      *(float2*)(smem + O_SM + 1024) = make_float2(s + x0, rstd);
    }
    if (lane == 0) *(volatile unsigned*)(smem + O_EP) = ep;
    nbar_arrive(1, 288);
  }
  const int cls = isA ? (b >= NBIG) : 2, v0 = isA ? 2 : 0;
  if (warp >= 8) {
    asm volatile("setmaxnreg.dec.sync.aligned.u32 72;");
    if (warp == 8) {
      if (lane < 8) asm volatile("prefetch.tensormap [%0];" ::"l"(&tms.m[lane + 1]) : "memory");
      if ((sb & 0xFFFFFF) != SMEM_BASE) __trap();
    } else if (warp == 9) {
      if (lane == 0) {
#pragma unroll
        for (int i = B_EMPTY; i < B_EM; i++) BAR_INIT(i, 8);
        BAR_INIT(B_LZ, 8); BAR_INIT(B_Q2, 9); BAR_ARM(B_Q2, 1024);
        BAR_INIT(B_H, 1); BAR_INIT(B_QF, 1); BAR_ARM(B_QF, 32768);
        BAR_INIT(B_TAB, 1); BAR_INIT(B_W, 1); BAR_INIT(B_ST, 8); BAR_INIT(B_WZ, 1); BAR_INIT(B_G, 1); BAR_INIT(B_G2, 1);
      }

    }
    if (warp != 11) {
      __syncwarp();
      asm volatile("fence.mbarrier_init.release.cluster;" ::: "memory");
      __threadfence_block();
      asm volatile("barrier.cluster.arrive.relaxed.aligned;" ::: "memory");
    }
    asm volatile("barrier.cluster.wait.acquire.aligned;" ::: "memory");
    if (warp == 8) {
      const int nr = sch.nr[cls], vl = v0 + sch.nt[cls] - 1;
      unsigned long long hist = 0;
      int v = v0;
#pragma unroll 1
      for (int rd = 0; rd < nr; rd++) {
        const uint2 e = sch.r[cls][rd];
        const int type = e.y & 15, win = (e.y >> 4) & 15, pos = b + 64 - (int)((e.y >> 8) & 255), tile = e.y >> 16;
        const bool mod = type == T_MOD;
        const int ni = mod ? 1 : type == T_DN ? 2 : 4;
        unsigned t = gt_start + (e.x & 0xffff) + (pos * sch.dt >> 8);
        const int c0 = mod ? 1024 + 32 * b : type == T_WO ? 64 * rn : type == T_GU ? 32 * f : 0;
        int c1 = type == T_KV ? 64 * (tile + pos) : type == T_DN ? 32 * f : 0;
        int c2 = mod ? tile : type == T_WO ? 4 * cl : type == T_UV ? b : 0;
        const int i1 = type == T_DN ? 16 : type == T_UV ? 128 : 0;
#pragma unroll 1
        for (int j = 0; j < ni; j++) {
          const int slot = mod ? B_FM + tile : (v & 1) * 4 + j;
          if (mod ? tile : v >= 2) mbar_wait(bar0 + 8 * (B_EMPTY + (mod ? (vl & 1) * 4 : slot)), mod ? (vl >> 1) & 1 : ((v >> 1) - 1) & 1);
          const int hw = (int)(hist >> (6 * (win - 1))) & 63;
          if (hw) mbar_wait(bar0 + 8 * (hw & 15), (hw >> 4) & 1);
          wait_until(t);
          if (lane == 0) {
            BAR_ARM(slot, 16384);
            tma3d(sb + (mod ? (tile ? O_Q : O_X) : slot * 16384), &tms.m[type == T_GU ? type + (j & 1) : type], bar0 + 8 * slot, c0, c1, c2);
          }
          __syncwarp();
          hist = hist << 6 | (32 | (mod ? 0 : (v & 2) << 3) | slot);
          t += e.x >> 16; c1 += i1;
          c2 += type == T_KV ? 2 : type == T_WO ? 1 : type == T_GU ? j & 1 : 0;
        }
        v += !mod;
      }
      return;
    }
    const unsigned epoch = *(volatile unsigned*)(smem + O_EP), par = (epoch + 1) & 1;
    if (warp == 10) {
      if (isA) {
        for (int it = 0; ldx4(scr->cnt + 1) != (epoch + 1) * 128 && it < SPIN_MAX; it++) {}
        if (lane == 0) BAR_ARRIVE(B_H);
      } else mbar_wait(bar0);
      if (!(rn & (QN - 1))) {
        for (int it = 0; ldx4(scr->cnt + 32 + 32 * (rn >> 2)) != (epoch + 1) * 32 && it < SPIN_MAX; it++) {}
        if (lane == 0)
          asm volatile("cp.async.bulk.shared::cluster.global.mbarrier::complete_tx::bytes.multicast::cluster [%0], [%1], %4, [%2], %3;"
                       ::"r"(sb + O_Q + rn * 4096), "l"(scr->qa + rn * 256), "r"(bar0 + 8 * B_QF), "h"((unsigned short)0xff), "n"(4096 * QN) : "memory");
      }
      const unsigned dl = isA ? sch.d4 : sch.d6;
      unsigned tw = gt_start + sch.t4;
      if (!isA) {
        const int nt = sch.nt[2];
#pragma unroll 1
        for (int t = 0; t < nt; t++) mbar_wait(bar0 + 8 * B_EMPTY + (t & 1) * 32, (t >> 1) & 1);
        unsigned long long now;
        asm volatile("mov.u64 %0, %%globaltimer;" : "=l"(now));
        if (lane == 0) { asm volatile("red.relaxed.gpu.global.max.u64 [%0], %1;" ::"l"(scr->cnt + 130), "l"(now) : "memory"); CNT_ADD(128); }
        tw = (unsigned)now + 1700;
      }
      sleep_until(tw);
      uint4 an;
      for (int it = 0; an = ldx16(scr->cnt + 128), an.x != (epoch + 1) * 56 && it < SPIN_MAX; it++) {}
      wait_until(an.z + (dl >> 16));
      if (lane == 0) BAR_ARRIVE(B_G2);
      wait_until(an.z + (dl & 0xffff));
      if (lane == 0) BAR_ARRIVE(B_G);
    } else if (warp == 11) {
      {
        uint2* ph = scr->hdr + ((lane & 24) + 2 * tq + (g & 1)) * 16 + cl;
        const bool own = (lane >> 4) * 4 + tq == rn;
        if (own) { stx8(ph, make_uint2(par ^ 1, 0)); if (cl == 14) stx8(ph + 1, make_uint2(0, 0)); }
        uint32_t a_w = sb + O_HW + ((lane >> 4) * 4 + tq) * 128 + (g & 1) * 64 + ((lane >> 1) & 4);
        PIN(a_w); PINL(ph);
        const int vt = v0 + sch.nt[cls];
#pragma unroll 1
        for (int t = 0; t < vt; t++) mbar_wait(bar0 + 8 * B_EMPTY + (t & 1) * 32, (t >> 1) & 1);
        float hz[8], M;
        uint32_t wp[4];
#pragma unroll 1
        for (int e = 0; e < 2; e++) {
          POLL {
            unsigned ok = 1;
#pragma unroll
            for (int u = 0; u < 8; u++)
              asm volatile("ld.relaxed.cluster.shared.f32 %0, [%1];" : "=f"(hz[u]) : "r"(sb + O_HZ + e * 1024 + u * 128 + lane * 4) : "memory");
#pragma unroll
            for (int u = 0; u < 4; u++) ok = and3(ok, __float_as_uint(hz[u]), __float_as_uint(hz[u + 4]));
            RETRY(~ok)
          }
          if (e) break;
          M = fmaxf(fmaxf(fmaxf(hz[0], hz[1]), fmaxf(hz[2], hz[3])), fmaxf(fmaxf(hz[4], hz[5]), fmaxf(hz[6], hz[7])));
          M = u2f(fbits(M));
#pragma unroll
          for (int u = 0; u < 4; u++) {
            wp[u] = pack2(ex2(hz[u] - M), ex2(hz[u + 4] - M));
            sts4(a_w + ((rn - u) & 3) * 8, u2f(wp[u])); sts4(a_w + ((rn - u) & 3) * 8 + 32, u2f(wp[u]));
          }
          __syncwarp();
          if (lane == 0) BAR_ARRIVE(B_WZ);
        }
        float L = 0.f;
#pragma unroll
        for (int u = 0; u < 4; u++) L += bflo(wp[u]) * hz[u] + bfhi(wp[u]) * hz[u + 4];
        if (own) pub8(ph, __float_as_uint(M) | 1u, __float_as_uint(L));
      }
      if (isA) {
        mbar_wait(bar0 + 8 * B_G2);
        unsigned long long hh;
        POLL { hh = ldx64(scr->hdr + hd * 16 + (lane & 15)); RETRY((lane & 15) == 15 ? 0u : (unsigned)hh ^ par) }
        const float m = (lane & 15) == 15 ? -1e30f : u2f((unsigned)hh);
        int mi = __float_as_int(m);
        mi ^= (mi >> 31) & 0x7fffffff;
        mi = __reduce_max_sync(~0u, mi);
        mi ^= (mi >> 31) & 0x7fffffff;
        const float w = ex2(m - __int_as_float(mi));
        float L = w * u2f(hh >> 32);
#pragma unroll
        for (int o2 = 8; o2; o2 >>= 1) L += __shfl_xor_sync(~0u, L, o2);
        sts4(sb + O_SM + (384 + 2 * (lane & 6) + ((lane >> 2) & 2) + (lane & 1)) * 4, w * rcp(L));
        __syncwarp();
        if (lane == 0) BAR_ARRIVE(B_W);
      }
    } else {
#pragma unroll 4
      for (int i = 0; i < 72; i++) sts16(sb + O_LZ + i * 512 + lane * 16, make_uint4(0, 0, 0, 0));
      __syncwarp();
      if (lane < 8) asm volatile("mbarrier.arrive.release.cluster.shared::cluster.b64 _, [%0];" ::"r"(mapa(bar0 + 8 * B_LZ, lane)) : "memory");
      if (isA) {
        mbar_wait(bar0 + 8 * B_QF);
#pragma unroll 2
        for (int k = 0; k < 8; k++) {
          const uint32_t cp = ldc4(cvec + 2 * (lane + 32 * k));
          *(uint32_t*)(smem + O_SILU + (lane + 32 * k) * 4) = pack2(silu_bf(bflo(cp)), silu_bf(bfhi(cp)));
        }
        __syncwarp();
        uint32_t ab = sb + O_X + (8 * (lane >> 4) + (lane & 7)) * 64 + ((((lane >> 3) & 1) ^ ((lane >> 1) & 3)) << 4);
        float d[4][4] = {};
#pragma unroll 1
        for (int jm = 0; jm < 2; jm++) {
          mbar_wait(bar0 + 8 * (B_FM + jm));
#pragma unroll 2
          for (int s2 = 0; s2 < 8; s2++)
#pragma unroll
            for (int s = 0; s < 2; s++) {
              uint32_t a0[4], a1[4];
              const uint32_t* ps = (const uint32_t*)(smem + O_SILU) + 128 * jm + 16 * s2 + 8 * s + tq;
              ldsm_t(a0, ab + (2 * s2 + s) * 1024); ldsm_t(a1, (ab + (2 * s2 + s) * 1024) ^ 32);
              mma16(d[s], a0, ps[0], ps[4]); mma16(d[2 + s], a1, ps[0], ps[4]);
            }
          ab -= O_X - O_Q;
        }
        const float t0 = (tq & 1) ? d[0][2] + d[1][2] : d[0][0] + d[1][0], t1 = (tq & 1) ? d[2][2] + d[3][2] : d[2][0] + d[3][0];
        stx4(scr->xm + b * 32 + posof(8 * tq + g), fbits(bfr(bfr((tq & 2) ? t1 : t0) + ((b >> 4) == 2 ? 1.f : 0.f))));
        __syncwarp();
        if (lane == 0) CNT_ADD(96);
      } else sleep_until(gt_start + sch.t4);
      for (int it = 0; ldx4(scr->cnt + 96) != (epoch + 1) * 64 && it < SPIN_MAX; it++) __nanosleep(NSL);
      if (isA) {
        unsigned long long ga;
        POLL { ga = ldx64(scr->xm + 64 * rn + 2 * lane); RETRY(lop_x3((unsigned)ga, ga >> 32, par)) }
        *(float2*)(smem + O_SM + (320 + 2 * lane) * 4) = make_float2(bfhi((unsigned)ga), bfhi(ga >> 32));
      }
      __syncwarp();
      if (lane == 0) BAR_ARRIVE(B_TAB);
    }
    return;
  }

  float* s_sm = (float*)(smem + O_SM);
  unsigned par, epoch;
  asm volatile("barrier.cluster.arrive.relaxed.aligned;" ::: "memory");
  if (isA) {
    float* s_r = (float*)(smem + O_R);
    float acc[8] = {0, 0, 0, 0, 0, 0, 0, 0};
    const float sl = silu_bf((arow & 1) ? bfhi(cw) : bflo(cw));
#pragma unroll
    for (int i = 0; i < 4; i++) fma8(acc, wm[i], __shfl_sync(~0u, sl, i, 4));
    tred<4>(acc, lane, 16);
    *(float4*)(s_r + warp * 128 + 8 * (lane & 15) + ((lane >> 2) & 4)) = make_float4(acc[0], acc[1], acc[2], acc[3]);
    nbar(1, 288);
    epoch = *(volatile unsigned*)(smem + O_EP);
    par = (epoch + 1) & 1;
    if (warp < 2) {
      float t = 0.f, ca = rn == 0 ? 1.f : 0.f;
#pragma unroll
      for (int w = 0; w < 8; w++) { t += s_r[w * 128 + tid]; ca += s_r[w * 128 + 64 + tid]; }
      t += ca * ((((tid & 1) ? bfhi(xw) : bflo(xw)) - s_sm[256]) * s_sm[257]);
      const float nb = __shfl_down_sync(~0u, t, 1);
      const uint32_t w0 = lane < 8 ? pack2t(t, nb, par) : pack2(t, nb);
      const uint32_t w1 = __shfl_down_sync(~0u, w0, 8), w2 = __shfl_down_sync(~0u, w0, 16), w3 = __shfl_down_sync(~0u, w0, 24);
      if (lane < 8 && !(lane & 1)) stx16(scr->h + (rn >> 1) * 512 + (2 * cl + warp) * 32 + rk * 16 + 2 * lane, make_uint4(w0, w1, w2, w3));
      __syncwarp();
      if (lane == 0) CNT_ADD(1);
    }
    asm volatile("barrier.cluster.wait.acquire.aligned;" ::: "memory");
    const uint32_t rsb = mapa(sb, rn ^ 1);
    {
      uint32_t a[4][4][4];
      mbar_wait(bar0 + 8 * (warp >> 1));
      const uint32_t ab = sb + (64 * warp + 8 * (lane >> 4) + (lane & 7)) * 128;
#pragma unroll
      for (int s = 0; s < 4; s++)
#pragma unroll
        for (int mt = 0; mt < 4; mt++) ldsm_t(a[s][mt], ab + s * 2048 + (((2 * mt + ((lane >> 3) & 1)) ^ (lane & 7)) << 4));
      arrive_n(bar0 + 8 * (B_EMPTY + (warp >> 1)), lane == 0, 4 + (dep16(&a[0][0][0]) & sch.zero));
      uint4 v0, v1;
      const unsigned* ph = scr->h + (g >> 1) * 512 + 64 * warp + 4 * (lane & 7);
      uint32_t off = O_B + warp * 272 + (32 * rk + 8 * tq + (lane & 4)) * 4;
      PIN(off); PINL(ph);
      mbar_wait(bar0 + 8 * B_H);
      POLL { v0 = ldx16(ph); v1 = ldx16(ph + 32); RETRY(lop_x3(v0.x, v1.x, par)) }
      float d[4][4] = {};
#pragma unroll
      for (int mt = 0; mt < 4; mt++) {
        mma16(d[mt], a[0][mt], v0.x, v0.y); mma16(d[mt], a[1][mt], v0.z, v0.w);
        mma16(d[mt], a[2][mt], v1.x, v1.y); mma16(d[mt], a[3][mt], v1.z, v1.w);
      }
      float r[8];
#pragma unroll
      for (int mt = 0; mt < 4; mt++) { r[2 * mt] = d[mt][0] + d[mt][1]; r[2 * mt + 1] = d[mt][2] + d[mt][3]; }
      tred<4>(r, lane, 2); tred<2>(r, lane, 1);
      const float rc = __shfl_xor_sync(~0u, (lane & 4) ? r[0] : r[1], 4);
      const uint32_t wd = (lane & 4) ? pack2(rc, r[1]) : pack2(r[0], rc);
      const uint32_t w1 = __shfl_down_sync(~0u, wd, 8), w2 = __shfl_down_sync(~0u, wd, 16), w3 = __shfl_down_sync(~0u, wd, 24);
      asm volatile("{.reg .pred p; setp.lt.s32 p, %7, 8; @p st.shared.v4.b32 [%0], {%2,%3,%4,%5};\n"
                   "@p st.async.shared::cluster.mbarrier::complete_tx::bytes.v4.b32 [%1], {%2,%3,%4,%5}, [%6];}"
                   ::"r"(sb + off), "r"(rsb + off), "r"(wd), "r"(w1), "r"(w2), "r"(w3), "r"(rsb + O_BAR + 8 * B_Q2), "r"(lane) : "memory");
      __syncwarp();
      arrive_n(bar0 + 8 * B_Q2, lane == 0, 1);
    }
    {
      uint32_t a[2][8][4];
      uint32_t a_bq = sb + O_B + (lane & 7) * 272 + (lane >> 3) * 16;
      uint4* p_qa = scr->qa + (4 * rk + (warp >> 1)) * 256 + hd * 8 + ((4 * (warp & 1) + tq) ^ (hd & 7));
      PIN(a_bq); PINL(p_qa);
      mbar_wait(bar0 + 8 * (4 + (warp >> 1)));
      const uint32_t ab = sb + 65536 + (warp >> 1) * 16384 + (32 * (warp & 1) + (lane & 15)) * 128;
#pragma unroll
      for (int i = 0; i < 16; i++) ldsm(a[i >> 3][i & 7], ab + (i >> 3) * 2048 + ((i >> 2) & 1) * 8192 + (((2 * (i & 3) + (lane >> 4)) ^ (lane & 7)) << 4));
      arrive_n(bar0 + 8 * (B_EMPTY + 4 + (warp >> 1)), lane == 0, 4 + (dep16(&a[0][0][0]) & sch.zero));
      mbar_wait(bar0 + 8 * B_Q2);
      float d[4][4] = {};
#pragma unroll
      for (int y = 0; y < 4; y++) {
        uint32_t bq[4];
        ldsm(bq, a_bq + 64 * y);
#pragma unroll
        for (int mt = 0; mt < 2; mt++) { mma16(d[2 * mt], a[mt][2 * y], bq[0], bq[1]); mma16(d[2 * mt + 1], a[mt][2 * y + 1], bq[2], bq[3]); }
      }
      float r[4];
#pragma unroll
      for (int i = 0; i < 4; i++) r[i] = (d[i & 2][2 * (i & 1)] + d[i & 2][2 * (i & 1) + 1]) + (d[(i & 2) + 1][2 * (i & 1)] + d[(i & 2) + 1][2 * (i & 1) + 1]);
      tred<2>(r, lane, 2); tred<1>(r, lane, 1);
      const float nb = __shfl_xor_sync(~0u, r[0], 4);
      const uint32_t w0 = (lane >> 3) == (hd & 3) ? pack2t(r[0], nb, par) : pack2(r[0], nb);
      const uint32_t w1 = __shfl_down_sync(~0u, w0, 8), w2 = __shfl_down_sync(~0u, w0, 16), w3 = __shfl_down_sync(~0u, w0, 24);
      if (lane < 4) stx16(p_qa, make_uint4(w0, w1, w2, w3));
      if (warp) nbar_arrive(3, 256); else { nbar(3, 256); if (lane == 0) CNT_ADD(32 + 32 * rk); }
    }
  } else {
    nbar(1, 288);
    epoch = *(volatile unsigned*)(smem + O_EP);
    par = (epoch + 1) & 1;
    asm volatile("barrier.cluster.wait.acquire.aligned;" ::: "memory");
    mbar_wait(bar0);
  }
  asm volatile("setmaxnreg.inc.sync.aligned.u32 216;");
  uint2* p_rec = scr->rec + ((16 * (warp >> 2) + 2 * (warp & 3) + (g & 1) + 4 * (tq & 2)) * 32 + 4 * rn + (tq & 1)) * 64 + cl * 4 + (g >> 1);
  PINL(p_rec);
  {
    const unsigned inv = par ^ 1;
#pragma unroll
    for (int q = 0; q < 2; q++) { stx8(p_rec + q * 128, make_uint2(inv, 0)); if (cl == 14) stx8(p_rec + q * 128 + 4, make_uint2(0, 0)); }
    if (isA) { if (warp < 2) stx4(scr->xao + b * 64 + tid, inv); }
    else stx8(scr->xf + ((4 * warp + tq) * 56 + f) * 16 + 2 * g, make_uint2(inv, 0));
  }
  sb = __shfl_sync(~0u, sb, 0); bar0 = sb + O_BAR;
  const int nt = sch.nt[cls], wg = warp >> 2;
  uint32_t a_z[4];
#pragma unroll
  for (int u = 0; u < 4; u++) {
    const int s3 = (rn - u - (lane >> 1 & 1)) & 3;
    a_z[u] = sb + O_LZ + (s3 + 4 * (lane & 1)) * 4096 + wg * 512 + g * 64 + (((warp & 3) ^ (s3 & 1) ^ (2 * (lane & 1))) << 4);
    PIN(a_z[u]);
  }
  uint32_t z[4][4], a_w = sb + O_HW + warp * 128 + (g & 1) * 64 + (tq & 1) * 8;
  PIN(a_w);
  {
    const float sc = 0.08838834764831845f * 1.4426950408889634f;
    const uint32_t a_pm = sb + O_SM + lane * 16;
    float mrun = -1e30f;
    float o[4][16], sx[16], mref[8];
#pragma unroll
    for (int k = 0; k < 16; k++) { o[0][k] = o[1][k] = o[2][k] = o[3][k] = sx[k] = 0.f; mref[k >> 1] = -1e30f; }
    const int key = 16 * warp + (lane & 15);
    uint32_t a_p = sb + O_P + key * 64 + (((lane >> 4) ^ ((key >> 1) & 3)) << 4);
    uint32_t a_v = sb + wg * 32768 + (8 * (lane >> 4) + (lane & 7)) * 128 + (((2 * (warp & 3) + ((lane >> 3) & 1)) ^ (lane & 7)) << 4);
    const int rot = rn + warp;
    unsigned long long dst[4];
#pragma unroll
    for (int q = 0; q < 4; q++) {
      dst[q] = mapg(sb + O_LZ + rn * 4096 + (warp & 3) * 1024 + g * 64 + ((tq ^ (rn & 1) ^ ((rn >> 1) & 2)) << 4), 4 * wg + ((q + rot) & 3));
      PINL(dst[q]);
    }
    unsigned long long a_h = mapg(sb + O_HZ + wg * 1024 + rn * 128 + lane * 4, 2 * (warp & 3));
    unsigned long long a_h1 = mapg(sb + O_HZ + wg * 1024 + rn * 128 + lane * 4, 2 * (warp & 3) + 1);
    PIN(a_p); PIN(a_v); PINL(a_h); PINL(a_h1);
    uint32_t rel = lane < 4 && lane >= 2 * wg ? 2 - (tq >> 1) : 0;
    PIN(rel);
    uint32_t ones[4] = {0x3F803F80u, 0x3F803F80u, 0x3F803F80u, 0x3F803F80u};
    PIN(ones[0]); PIN(ones[1]); PIN(ones[2]); PIN(ones[3]);
    {
      asm volatile("{.reg .pred p; .reg .u32 n; mov.u32 n, 0;\n"
                   "W%=: mbarrier.try_wait.parity.acquire.cluster.shared::cta.b64 p, [%0], 0; add.u32 n, n, 1; setp.lt.and.u32 p, n, 0x100000, !p; @p bra W%=;}"
                   ::"r"(bar0 + 8 * B_LZ) : "memory");
      mbar_wait(bar0 + 8 * B_QF);
      unsigned bad = 0;
#pragma unroll
      for (int k = 0; k < 8; k++) bad |= __float_as_uint(lds4(sb + O_Q + k * 4096 + tid * 16 + (lane >> 3) * 4)) ^ par;
      if (__builtin_expect(__any_sync(~0u, bad & 1), 0)) {
#pragma unroll 1
        for (int k = 0; k < 8; k++) {
          uint4 v;
          POLL { v = ldx16(scr->qa + k * 256 + tid); RETRY(((lane & 16) ? ((lane & 8) ? v.w : v.z) : ((lane & 8) ? v.y : v.x)) ^ par) }
          sts16(sb + O_Q + k * 4096 + tid * 16, v);
        }
        asm volatile("fence.proxy.async.shared::cta;" ::: "memory");
      }
      if (warp >= 4) nbar_arrive(1, 256); else nbar(1, 256);
    }
#pragma unroll 1
    for (int t = 0; t < nt; t++) {
      const int v = v0 + t;
      const uint32_t fb = bar0 + (v & 1) * 32, ph = (v >> 1) & 1, av = a_v + (v & 1) * 65536;
      uint32_t vf[4][4][4], cnt;
      auto landed = [&]() {
        cnt = rel + (dep16(&vf[0][0][0]) & (nt >> 8));
        PIN(cnt);
      };
      if (wg == 0) {
        const uint32_t da = DSC + (v & 1) * 4096, db = DSC + O_Q / 16;
#pragma unroll
        for (int jj = 0; jj < 2; jj++) {
#pragma unroll 1
          for (int j = 2 * jj; j < 2 * jj + 2; j++) {
            mbar_wait(fb + 8 * j, ph);
            asm volatile("wgmma.fence.sync.aligned;" ::: "memory");
#pragma unroll
            for (int k = 0; k < 8; k++)
              wgmma32<0, 0, HI128, HI128>(sx, da + j * 1024 + (k >> 2) * 512 + (k & 3) * 2, db + j * 512 + (k >> 2) * 256 + (k & 3) * 2, jj || k ? 1 : j);
            asm volatile("wgmma.commit_group.sync.aligned;" ::: "memory");
          }
          if (jj == 0) {
#pragma unroll
            for (int i = 0; i < 16; i++) ldsm_t(vf[i >> 2][i & 3], av + (((i >> 2) + rot) & 3) * 8192 + (i & 3) * 2048);
            nbar(5, 256);
            landed();
          }
        }
      } else {
        nbar_arrive(5, 256);
#pragma unroll 1
        for (int j = 0; j < 2; j++) {
          mbar_wait(fb + 16 + 8 * j, ph);
          if (j) spin_until(clock() + VDLY);
#pragma unroll
          for (int q = 0; q < 4; q++)
            if (((q + rot) & 2) == 2 * j)
#pragma unroll
              for (int k = 0; k < 4; k++) ldsm_t(vf[q][k], av + ((q + rot) & 3) * 8192 + k * 2048);
        }
        cnt = 0;
      }
      wg_wait<0>(sx);
      asm volatile("{.reg .pred p; setp.ne.s32 p, %1, 0; @p mbarrier.arrive.shared::cta.b64 _, [%0], %1;}" ::"r"(fb + 8 * B_EMPTY + 8 * tq), "r"(cnt) : "memory");
#pragma unroll 1
      for (int pass = 0;; pass++) {
        int ex = !(t | pass);
        if (wg == 0 && (t | pass)) {
          float mx = -1e30f;
#pragma unroll
          for (int i = 0; i < 8; i++) mx = fmaxf(mx, fmaxf(sx[2 * (i & 6) + (i & 1)], sx[2 * (i & 6) + (i & 1) + 2]) * sc - mref[i]);
          ex = mx > TAU;
          uint32_t pk[8];
#pragma unroll
          for (int i = 0; i < 8; i++) pk[i] = pack2(ex2(sx[2 * i] * sc - mref[i & 6]), ex2(sx[2 * i + 1] * sc - mref[(i & 6) + 1]));
#pragma unroll
          for (int u = 0; u < 2; u++)
            asm volatile("stmatrix.sync.aligned.m8n8.x4.shared.b16 [%0], {%1,%2,%3,%4};"
                         ::"r"(a_p ^ (u << 5)), "r"(pk[4 * u]), "r"(pk[4 * u + 1]), "r"(pk[4 * u + 2]), "r"(pk[4 * u + 3]) : "memory");
          asm volatile("fence.proxy.async.shared::cta;" ::: "memory");
        }
        asm volatile("{.reg .pred p, q; setp.ne.s32 q, %0, 0; bar.red.or.pred p, 4, 256, q; selp.s32 %0, 1, 0, p;}" : "+r"(ex)::"memory");
        if (!ex || pass) break;
        if (wg == 0) {
          float cm[8];
#pragma unroll
          for (int i = 0; i < 8; i++) cm[i] = fmaxf(sx[2 * (i & 6) + (i & 1)], sx[2 * (i & 6) + (i & 1) + 2]);
          tmax<4>(cm, lane, 16); tmax<2>(cm, lane, 8); tmax<1>(cm, lane, 4);
          sts4(a_pm + warp * 4, cm[0] * sc);
        }
        nbar(4, 256);
        const float4 pm = lds16(a_pm);
        const float mn = u2f(__float_as_uint(fmaxf(fmaxf(fmaxf(pm.x, pm.y), fmaxf(pm.z, pm.w)), mrun)) | 1u), al = ex2(mrun - mn);
        mrun = mn;
#pragma unroll
        for (int i = 0; i < 8; i++) {
          const float a = __shfl_sync(~0u, al, 4 * i + tq), aw = wg ? a : 1.f;
          mref[i] = __shfl_sync(~0u, mn, 4 * i + tq);
#pragma unroll
          for (int e = 0; e < 2; e++) {
            const int k = 2 * (i & 6) + (i & 1) + 2 * e;
            o[0][k] *= a; o[1][k] *= a; o[2][k] *= a; o[3][k] *= a; sx[k] *= aw;
          }
        }
      }
      float hv = mrun;
      if (wg) {
        asm volatile("wgmma.fence.sync.aligned;" ::: "memory");
#pragma unroll
        for (int k = 0; k < 4; k++) wgmma32r(sx, ones, DSC + O_P / 16 + k * 64);
        asm volatile("wgmma.commit_group.sync.aligned;" ::: "memory");
        landed();
        asm volatile("{.reg .pred p; setp.ne.s32 p, %1, 0; @p mbarrier.arrive.shared::cta.b64 _, [%0], %1;}" ::"r"(fb + 8 * B_EMPTY + 8 * tq), "r"(cnt) : "memory");
        wg_wait<0>(sx);
        float lv[4];
#pragma unroll
        for (int j = 0; j < 4; j++) lv[j] = (lane & 4) ? sx[4 * j + 1] : sx[4 * j];
        hv = (lane & 16) ? ((lane & 8) ? lv[3] : lv[2]) : ((lane & 8) ? lv[1] : lv[0]);
      }
      asm volatile("{.reg .pred p; setp.eq.s32 p, %3, %4; @p st.relaxed.cluster.b32 [%0], %1; @p st.relaxed.cluster.b32 [%2], %1;}"
                   ::"l"(a_h), "r"(__float_as_uint(hv) | 1u), "l"(a_h1), "r"(t), "r"(nt - 1) : "memory");
#pragma unroll
      for (int q = 0; q < 4; q++) {
        asm volatile("wgmma.fence.sync.aligned;" ::: "memory");
#pragma unroll
        for (int k = 0; k < 4; k++) wgmma32r(o[q], vf[q][k], DSC + O_P / 16 + k * 64);
        asm volatile("wgmma.commit_group.sync.aligned;" ::: "memory");
        if (q == 3) {
#pragma unroll
          for (int u = 0; u < 4; u++) ldsm_t(z[u], a_z[u] + u * 1024);
        }
        wg_wait<0>(o[q]);
#pragma unroll
        for (int j = 0; j < 2; j++)
          asm volatile("{.reg .pred p; setp.eq.s32 p, %5, %6; @p st.relaxed.cluster.v4.b32 [%0], {%1,%2,%3,%4};}"
                       ::"l"(dst[q] + j * 512), "r"(pack2t(o[q][8 * j], o[q][8 * j + 1], 1)), "r"(pack2(o[q][8 * j + 2], o[q][8 * j + 3])),
                         "r"(pack2(o[q][8 * j + 4], o[q][8 * j + 5])), "r"(pack2(o[q][8 * j + 6], o[q][8 * j + 7])), "r"(t), "r"(nt - 1) : "memory");
      }
    }
  }
  {
    uint32_t wx[4][4];
    mbar_wait(bar0 + 8 * B_WZ);
#pragma unroll
    for (int u = 0; u < 4; u++) {
      uint2 wp;
      asm volatile("ld.shared.v2.u32 {%0, %1}, [%2];" : "=r"(wp.x), "=r"(wp.y) : "r"(a_w + u * 8) : "memory");
      const bool lo = (g >> 1) == (tq >> 1), hi = (g >> 1) == 2 + (tq >> 1);
      wx[u][0] = lo ? wp.x : 0u; wx[u][1] = lo ? wp.y : 0u; wx[u][2] = hi ? wp.x : 0u; wx[u][3] = hi ? wp.y : 0u;
    }
    auto bad = [&]() {
      const unsigned ok = and3(and3(and3(z[0][0], z[0][1], z[0][2]), and3(z[0][3], z[1][0], z[1][1]), and3(z[1][2], z[1][3], z[2][0])),
                               and3(and3(z[2][1], z[2][2], z[2][3]), and3(z[3][0], z[3][1], z[3][2]), z[3][3]), 0x10001u);
      return __any_sync(~0u, g == 0 && ok != 0x10001u);
    };
    POLL {
      if (it_)
#pragma unroll
        for (int u = 0; u < 4; u++) ldsm_t(z[u], a_z[u] + u * 1024);
      if (!bad() || ++it_ >= SPIN_MAX) break;
    }
    float d0[8][4] = {}, d[8][4], r[8];
#pragma unroll
    for (int i = 0; i < 8; i++) mma16(d0[i], wx[i >> 1], z[i >> 1][2 * (i & 1)], z[i >> 1][2 * (i & 1) + 1]);
    POLL {
#pragma unroll
      for (int u = 0; u < 4; u++) ldsm_t(z[u], a_z[u ^ 2] + u * 1024);
#pragma unroll
      for (int i = 0; i < 8; i++) mma16c(d[i], wx[(i >> 1) ^ 2], z[i >> 1][2 * (i & 1)], z[i >> 1][2 * (i & 1) + 1], d0[i]);
      if (!bad() || ++it_ >= SPIN_MAX) break;
    }
#pragma unroll
    for (int i = 0; i < 8; i++) r[i] = (tq & 2) ? ((g & 1) ? d[i][3] : d[i][2]) : ((g & 1) ? d[i][1] : d[i][0]);
#pragma unroll
    for (int q = 0; q < 2; q++) pub8(p_rec + q * 128, pack2t(r[4 * q], r[4 * q + 1], par) | 1u, pack2(r[4 * q + 2], r[4 * q + 3]));
  }
  const int vt = v0 + nt;
  const uint32_t bufa = sb + (vt & 1) * 65536, fulla = bar0 + (vt & 1) * 32, pha = (vt >> 1) & 1, phb = ((vt + 1) >> 1) & 1;
  const uint32_t bufo = sb + ((vt + 1) & 1) * 65536, fullb = bar0 + ((vt + 1) & 1) * 32;
  uint32_t a_rs = sb + O_R + (warp >> 2) * 1024 + (16 * tq + g) * 16 + ((warp + tq) & 3) * 4;
  if (isA) {
    const int row = 16 * (warp & 6) + 8 * (warp & 1) + (lane & 16) + ((lane & 7) >> 1) + 4 * (lane & 1);
    uint32_t ab = bufa + row * 128 + ((((lane >> 3) & 1) ^ (row & 7)) << 4);
    const uint2* pr = scr->rec + (hd * 32 + warp) * 64 + lane;
    unsigned long long a_c0 = mapg(sb + O_CTX + (64 * rn + 32 * (warp & 1) + posof(lane)) * 4, warp & 6);
    unsigned long long a_c1 = mapg(sb + O_CTX + (64 * rn + 32 * (warp & 1) + posof(lane)) * 4, warp | 1);
    uint32_t a_rl = sb + O_R + (32 * (warp & 1) + lane) * 16;
    uint32_t ao = bufo + (16 * warp + 8 * (lane >> 4) + (lane & 7)) * 128 + ((((lane >> 3) & 1) ^ (lane & 7)) << 4);
    uint32_t a_cx = sb + O_CTX + (16 * warp + 4 * tq) * 4, a_ga = sb + O_SM + (320 + posof(tid & 63)) * 4;
    unsigned* p_ao = scr->xao + b * 64 + (tid & 63);
    float xv = cl == 0 ? __bfloat162float(x[64 * rn + (tid & 63)]) : 0.f;
    unsigned p2 = lane >= 28 ? 0 : par;
    PIN(ab); PINL(pr); PINL(a_c0); PINL(a_c1); PIN(a_rl); PIN(a_rs); PIN(ao); PIN(a_cx); PIN(a_ga); PINL(p_ao); PIN(p2);
    asm volatile("" : "+f"(xv));
    uint32_t aw[4][4][4];
    auto wo = [&](const int j) {
      mbar_wait(fullb + 8 * j, phb);
#pragma unroll
      for (int mt = 0; mt < 4; mt++) ldsm_t(aw[j][mt], (ao + j * 16384) ^ (mt << 5));
    };
    {
      uint32_t a[4][4][4];
      uint2 z[4], y[4];
      float d[4][4] = {}, r[8];
      mbar_wait(fulla, pha);
      POLL {
#pragma unroll
        for (int q = 0; q < 4; q++) z[q] = ldx8(pr + q * 512);
        RETRY(lop_x3(z[0].x, z[1].x, par) | lop_x3(z[2].x, z[3].x, par))
      }
#pragma unroll
      for (int q = 0; q < 4; q++) {
        if (q == 3) {
          mbar_wait(bar0 + 8 * B_G);
#pragma unroll
          for (int u = 0; u < 4; u++) y[u] = ldx8(pr + u * 512 + 32);
        }
        mbar_wait(fulla + 8 * q, pha);
#pragma unroll
        for (int mt = 0; mt < 4; mt++) ldsm_t(a[q][mt], (ab + q * 16384) ^ (mt << 5));
#pragma unroll
        for (int mt = 0; mt < 4; mt++) mma16(d[mt], a[q][mt], z[q].x, z[q].y);
      }
      mbar_wait(bar0 + 8 * B_W);
      const float4 W = lds16(sb + O_SM + (384 + 4 * tq) * 4);
#pragma unroll
      for (int i = 0; i < 8; i++) { r[i] = W.x * d[i >> 1][2 * (i & 1)] + W.y * d[i >> 1][2 * (i & 1) + 1]; asm volatile("" : "+f"(r[i])); }
#pragma unroll
      for (int j = 0; j < NPE; j++) wo(j);
      POLL {
        if (it_)
#pragma unroll
          for (int u = 0; u < 4; u++) y[u] = ldx8(pr + u * 512 + 32);
#pragma unroll
        for (int mt = 0; mt < 4; mt++) d[mt][0] = d[mt][1] = d[mt][2] = d[mt][3] = 0.f;
#pragma unroll
        for (int q = 0; q < 4; q++)
#pragma unroll
          for (int mt = 0; mt < 4; mt++) mma16(d[mt], a[q][mt], y[q].x, y[q].y);
        RETRY(or3(lop_x3(y[0].x, y[1].x, p2), lop_x3(y[2].x, y[3].x, p2), 0))
      }
#pragma unroll
      for (int i = 0; i < 8; i++) r[i] = W.w * d[i >> 1][2 * (i & 1) + 1] + (W.z * d[i >> 1][2 * (i & 1)] + r[i]);
      tred<4>(r, lane, 2); tred<2>(r, lane, 1);
      sts4(a_rs, r[0]); sts4(a_rs + 128, r[1]);
      nbar(1, 256);
      const uint32_t cv = __float_as_uint(sum8(a_rl)) | 1u;
      asm volatile("st.relaxed.cluster.b32 [%0], %2; st.relaxed.cluster.b32 [%1], %2;" ::"l"(a_c0), "l"(a_c1), "r"(cv) : "memory");
    }
    {
#pragma unroll
      for (int j = NPE; j < NPO; j++) wo(j);
      uint4 c[4];
      POLL {
#pragma unroll
        for (int j = 0; j < 4; j++) c[j] = ldsv16(a_cx + j * 512);
        RETRY(~and3(and3(and3(c[0].x, c[0].y, c[0].z), and3(c[1].x, c[1].y, c[1].z), and3(c[0].w, c[1].w, c[2].x)),
                    and3(and3(c[2].y, c[2].z, c[2].w), and3(c[3].x, c[3].y, c[3].z), c[3].w), ~0u))
      }
      float d[4][4] = {};
#pragma unroll
      for (int j = 0; j < 4; j++) {
        if (j + 1 >= NPO && j < 3) wo(j + 1);
        const uint32_t b0 = pack2(u2f(c[j].x), u2f(c[j].y)), b1 = pack2(u2f(c[j].z), u2f(c[j].w));
#pragma unroll
        for (int mt = 0; mt < 4; mt++) mma16(d[mt], aw[j][mt], b0, b1);
      }
      const float r0 = (tq & 2) ? ((tq & 1) ? d[3][0] : d[2][0]) : ((tq & 1) ? d[1][0] : d[0][0]);
      const float r1 = (tq & 2) ? ((tq & 1) ? d[3][2] : d[2][2]) : ((tq & 1) ? d[1][2] : d[0][2]);
      sts4(a_rs + 2048, r0); sts4(a_rs + 2048 + 128, r1);
      if (warp >= 2) nbar_arrive(2, 256);
      else {
        mbar_wait(bar0 + 8 * B_TAB);
        const float gav = lds4(a_ga);
        nbar(2, 256);
        pub4(p_ao, __float_as_uint(gav * sum8(a_rl + 2048) + xv) | 1u);
      }
    }
  } else {
    uint32_t af[4][4][4], ad[2][4][4];
    uint32_t ab = bufa + (32 * warp + 8 * (lane >> 4) + (lane & 7)) * 64 + ((((lane >> 3) & 1) ^ ((lane >> 1) & 3)) << 4);
    uint32_t a_d = bufo + warp * 2048 + (8 * (lane >> 4) + (lane & 7)) * 128 + ((((lane >> 3) & 1) ^ (lane & 7)) << 4);
    uint32_t a_rl = sb + O_R + lane * 16, a_st = sb + O_SM + (352 + 8 * (lane >> 4) + warp) * 4;
    unsigned* p_f = scr->xf + ((4 * warp + tq) * 56 + f) * 16 + 2 * g;
    const unsigned* pa = scr->xao + (lane & 16) * 16 + 32 * warp + 2 * (lane & 15);
    const unsigned* pf = scr->xf + f * 896 + 4 * tid;
    const int col = ((tid >> 1) & 7) + 8 * (tid & 1);
    bf16* po = out + 16 * f + col;
    uint32_t a_q = sb + O_SM + (warp * 16 + 4 * tq + (lane >> 3)) * 4;
    unsigned d7 = sch.d7;
    PIN(ab); PIN(a_d); PIN(a_rl); PINL(p_f); PINL(pa); PIN(a_rs); PIN(a_st); PINL(pf); PINL(po); PIN(a_q); PIN(d7);
    mbar_wait(bar0 + 8 * B_TAB);
    uint2 cf;
    uint2 bb[4];
    unsigned gbw;
    POLL {
      unsigned bad = 0;
      cf = ldx8(scr->xm + 1024 + (lane & 16) * 16 + 32 * warp + posof(2 * (lane & 15)));
#pragma unroll
      for (int s = 0; s < 4; s++) {
        const uint4 w = ldx16(scr->xm + 1024 - (g & 1) * 512 + 256 * (s >> 1) + 32 * warp + 16 * (s & 1) + 4 * tq);
        bb[s] = make_uint2(__byte_perm(w.x, w.y, 0x7632), __byte_perm(w.z, w.w, 0x7632));
        bad = or3(bad, lop_x3(w.x, w.y, par), lop_x3(w.z, w.w, par));
      }
      gbw = ldx4(scr->xm + 1536 + 16 * (f & 31) + posof(col));
      RETRY(or3(bad, lop_x3(cf.x, cf.y, par), gbw ^ par))
    }
    const float gbv = bfhi(gbw);
    float e[4][4] = {};
    uint2 v[8];
    auto item = [&](const int it) {
      mbar_wait(fulla + 8 * it, pha);
#pragma unroll
      for (int i = 0; i < 4; i++) ldsm_t(af[it][i], (ab + it * 16384 + (i >> 1) * 1024) ^ ((i & 1) << 5));
    };
    auto item_mma = [&](const int it) {
#pragma unroll
      for (int i = 0; i < 4; i++) mma16(e[2 * (it & 1) + (i & 1)], af[it][i], bb[(it & 2) + (i >> 1)].x, bb[(it & 2) + (i >> 1)].y);
    };
    item(0); item_mma(0); item(1); item_mma(1);
    mbar_wait(bar0 + 8 * B_G);
#pragma unroll
    for (int i = 0; i < 8; i++) v[i] = ldx8(pa + i * 512);
    const unsigned t3 = clock() + WTEST;
    item(2); item_mma(2);
    uint32_t have3;
    do have3 = mbar_test(fulla + 24, pha); while (!have3 && (int)((unsigned)clock() - t3) < 0);
    if (have3) { item(3); item_mma(3); }
    float y0, y1, df[4][4], st[2];
    uint32_t have0, bz[4][2] = {};
    auto mm = [&](const int it, const int i) { mma16(df[2 * (it & 1) + (i & 1)], af[it][i], bz[(it & 2) + (i >> 1)][0], bz[(it & 2) + (i >> 1)][1]); };
    POLL {
      if (it_)
#pragma unroll
        for (int i = 0; i < 8; i++) v[i] = ldx8(pa + i * 512);
      y0 = ((u2f(v[0].x) + u2f(v[1].x)) + (u2f(v[2].x) + u2f(v[3].x))) + ((u2f(v[4].x) + u2f(v[5].x)) + (u2f(v[6].x) + u2f(v[7].x)));
      y1 = ((u2f(v[0].y) + u2f(v[1].y)) + (u2f(v[2].y) + u2f(v[3].y))) + ((u2f(v[4].y) + u2f(v[5].y)) + (u2f(v[6].y) + u2f(v[7].y)));
      const uint32_t zb = pack2(y0 * u2f(cf.x), y1 * u2f(cf.y));
#pragma unroll
      for (int i = 0; i < 8; i++) bz[i >> 1][i & 1] = g == i ? zb : 0u;
      st[0] = y0 + y1; st[1] = y0 * y0 + y1 * y1;
      tred<1>(st, lane, 16);
#pragma unroll
      for (int i = 0; i < 4; i++) df[i][0] = df[i][1] = df[i][2] = df[i][3] = 0.f;
      mm(0, 0); mm(0, 1); mm(1, 0); mm(1, 1);
      st[0] += shx(st[0], 8);
      mm(0, 2); mm(0, 3); mm(1, 2); mm(1, 3);
      RETRY(or3(or3(lop_x3(v[0].x, v[0].y, par), lop_x3(v[1].x, v[1].y, par), lop_x3(v[2].x, v[2].y, par)),
                or3(lop_x3(v[3].x, v[3].y, par), lop_x3(v[4].x, v[4].y, par), lop_x3(v[5].x, v[5].y, par)),
                or3(lop_x3(v[6].x, v[6].y, par), lop_x3(v[7].x, v[7].y, par), 0)))
    }
    {
      st[0] += shx(st[0], 4);
      mm(2, 0); mm(2, 1);
      st[0] += shx(st[0], 2);
      mm(2, 2); mm(2, 3);
      st[0] += shx(st[0], 1);
      sts4(a_st, st[0]);
      __syncwarp();
      arrive_n(bar0 + 8 * B_ST, lane == 0, 1);
      if (!have3) { item(3); item_mma(3); }
      have0 = mbar_test(fullb, phb);
      mm(3, 0); mm(3, 1); mm(3, 2); mm(3, 3);
#pragma unroll
      for (int mt = 0; mt < 4; mt++) ldsm_tp(ad[0][mt], a_d ^ (mt << 5), have0);
    }
    mbar_wait(bar0 + 8 * B_ST);
    float mean, rstd;
    {
      float4 u[4];
#pragma unroll
      for (int i = 0; i < 4; i++) u[i] = lds16(sb + O_SM + (352 + 4 * i) * 4);
      mean = (((u[0].x + u[0].y) + (u[0].z + u[0].w)) + ((u[1].x + u[1].y) + (u[1].z + u[1].w))) * (1.f / 512.f);
      const float sq = (((u[2].x + u[2].y) + (u[2].z + u[2].w)) + ((u[3].x + u[3].y) + (u[3].z + u[3].w))) * (1.f / 512.f);
      asm("rsqrt.approx.ftz.f32 %0, %1;" : "=f"(rstd) : "f"(fmaxf(sq - mean * mean, 0.f) + 1e-5f));
    }
    float r[8];
#pragma unroll
    for (int i = 0; i < 8; i++) r[i] = df[i >> 1][2 * (i & 1)] + df[i >> 1][2 * (i & 1) + 1];
    tred<4>(r, lane, 2); tred<2>(r, lane, 1);
    float A[4];
#pragma unroll
    for (int i = 0; i < 4; i++) A[i] = (tq & 2) ? ((tq & 1) ? e[3][i] : e[2][i]) : ((tq & 1) ? e[1][i] : e[0][i]);
    sts4(a_rs, rstd * r[0] + (A[1] - rstd * mean * A[0])); sts4(a_rs + 128, rstd * r[1] + (A[3] - rstd * mean * A[2]));
    const uint32_t have1 = mbar_test(fullb + 8, phb);
    nbar(1, 256);
    {
      const float4 g0 = lds16(a_rl), g1 = lds16(a_rl + 1024), u0 = lds16(a_rl + 512), u1 = lds16(a_rl + 1536);
#pragma unroll
      for (int mt = 0; mt < 4; mt++) ldsm_tp(ad[1][mt], (a_d + 16384) ^ (mt << 5), have1);
      const float gg = bfr(((g0.x + g0.y) + (g0.z + g0.w)) + ((g1.x + g1.y) + (g1.z + g1.w)));
      const float uu = bfr(((u0.x + u0.y) + (u0.z + u0.w)) + ((u1.x + u1.y) + (u1.z + u1.w)));
      const float hh = bfr(gg * rcp(1.f + ex2(gg * (-2.302208198f - 0.1029432397f * gg * gg)))) * uu;
      const uint32_t hw = pack2(hh, __shfl_down_sync(~0u, hh, 1));
      uint32_t hb[4];
#pragma unroll
      for (int i = 0; i < 4; i++) hb[i] = __shfl_sync(~0u, hw, 8 * i + 2 * tq);
      float dd[4][4] = {};
#pragma unroll
      for (int j = 0; j < 2; j++)
        if (!(j ? have1 : have0)) {
          mbar_wait(fullb + 8 * j, phb);
#pragma unroll
          for (int mt = 0; mt < 4; mt++) ldsm_t(ad[j][mt], (a_d + j * 16384) ^ (mt << 5));
        }
#pragma unroll
      for (int j = 0; j < 2; j++)
#pragma unroll
        for (int mt = 0; mt < 4; mt++) mma16(dd[mt], ad[j][mt], hb[2 * j], hb[2 * j + 1]);
      const float f0 = (tq & 2) ? ((tq & 1) ? dd[3][0] : dd[2][0]) : ((tq & 1) ? dd[1][0] : dd[0][0]);
      const float f1 = (tq & 2) ? ((tq & 1) ? dd[3][2] : dd[2][2]) : ((tq & 1) ? dd[1][2] : dd[0][2]);
      pub8(p_f, __float_as_uint(f0) | 1u, __float_as_uint(f1));
    }
    const unsigned tpub = clock();
    if (f < 32) {
      if (warp == ((f & 15) >> 1) && (g >> 1) == ((f >> 3) & 2) + (f & 1)) {
        sts4(sb + O_SM + (112 + 4 * tq + (g & 1)) * 4, y0); sts4(sb + O_SM + (114 + 4 * tq + (g & 1)) * 4, y1);
      }
      __syncwarp();
      if (warp == 7) nbar_arrive(2, 256);
      else {
        uint4 u;
        float q4[4];
        spin_until(tpub + d7);
        POLL {
          u = ldx16(pf);
          q4[0] = u2f(u.x); q4[1] = u2f(u.y); q4[2] = u2f(u.z); q4[3] = u2f(u.w);
          tred<2>(q4, lane, 16); tred<1>(q4, lane, 8);
          q4[0] += __shfl_xor_sync(~0u, q4[0], 4);
          RETRY(lop_x3(u.x, u.z, par))
        }
        sts4(a_q, q4[0]);
        nbar(2, 256);
        if (tid < 16) {
          float q[8];
#pragma unroll
          for (int i = 0; i < 8; i++) q[i] = lds4(sb + O_SM + (tid + 16 * i) * 4);
          const float t = ((q[0] + q[1]) + (q[2] + q[3])) + ((q[4] + q[5]) + q[6]);
          *po = __float2bfloat16(q[7] + bfr(gbv * bfr(t)));
          if (f == 0 && tid == 0) stx4(&scr->cnt[0], epoch + 1);
        }
      }
    }
  }
}

static void make_sched(Sched& s) {
  const char* order = "FFAAbcFmmvog....d";
  const double dt = 5010 * 1e-3, dth = 4850 * 1e-3, dtt = 5150 * 1e-3;
  const int nbig = NBIG;
  s.zero = 0; s.dth = (unsigned)(dth * 256 + 0.5);
  double t = 512 * dth + 80;
  int tile = 0, jm = 0;
  for (int i = 0; i < 3; i++) s.nr[i] = s.nt[i] = 0;
  auto add = [&](int c, int type, double step, int win, int b0, int tl) {
    s.r[c][s.nr[c]++] = make_uint2((unsigned)(t + 0.5) | (unsigned)(step + 0.5) << 16, type | win << 4 | (b0 + 64) << 8 | tl << 16);
    if (type == T_KV) s.nt[c]++;
  };
  const int w1 = 6, w2 = 4, wt = 6;
  for (const char* p = order; *p; p++) {
    const char c = *p;
    if (c == 'v' || c == 'o' || c == 'm') {
      const int ty = c == 'v' ? T_UV : c == 'o' ? T_WO : T_MOD;
      const double d = c == 'm' ? dt : dtt;
      add(0, ty, 64 * d, wt, 0, c == 'm' ? jm : 0); add(1, ty, 64 * d, wt, 0, c == 'm' ? jm : 0);
      t += (c == 'm' ? 64 : 256) * d; jm += c == 'm';
    } else if (c == 'g' || c == 'd') {
      add(2, c == 'g' ? T_GU : T_DN, 56 * dtt, wt, 64, 0);
      t += (c == 'g' ? 224 : 112) * dtt;
    } else if (c == '.') t += 100;
    else if (c == '-') t -= 100;
    else {
      const int na = c == 'F' ? 0 : c == 'C' || c == 'c' || c == 'a' ? nbig : 64, nf = c == 'A' || c == 'a' ? 0 : 56, n = na + nf;
      const int w = na && nf ? w2 : w1;
      const bool ff = c == 'b' || c == 'c';
      if (na) add(0, T_KV, n * dt, w, ff ? -56 : 0, tile);
      if (na == 64) add(1, T_KV, n * dt, w, ff ? -56 : 0, tile);
      if (nf) add(2, T_KV, n * dt, w, ff ? 64 : 64 - na, tile);
      tile += n; t += 4 * n * dt;
      s.t4 = (unsigned)t + 600;
    }
  }
  s.dt = (unsigned)(dt * 256 + 0.5); s.d7 = 300; s.d4 = 1550 | 1200 << 16; s.d6 = 3430;
}

static void launch(void* const* d_in, void* d_out) {
  static TMaps tms;
  static Sched sch;
  static bool init = false;
  static void* scr = nullptr;
  if (!init) {
    void* fn = nullptr; cudaDriverEntryPointQueryResult qr;
    cudaGetDriverEntryPoint("cuTensorMapEncodeTiled", &fn, cudaEnableDefault, &qr);
    EncFn f = (EncFn)fn;
    const CUtensorMapSwizzle S64 = CU_TENSOR_MAP_SWIZZLE_64B, S128 = CU_TENSOR_MAP_SWIZZLE_128B;
    const CUtensorMapL2promotion P256 = CU_TENSOR_MAP_L2_PROMOTION_L2_256B;
    enc3d(f, &tms.m[0], d_in[2], 64, 512, 64, 8192, 128, 64, 128, 1, S128, CU_TENSOR_MAP_L2_PROMOTION_L2_128B);
    enc3d(f, &tms.m[1], d_in[3], 64, 512, 64, 8192, 128, 64, 64, 2, S128, P256);
    enc3d(f, &tms.m[2], d_in[1], 64, SK, 8, 1024, 128, 64, 64, 2, S128, P256);
    enc3d(f, &tms.m[3], d_in[11], 3072, 256, 2, 6144, 256 * 6144, 32, 256, 1, S64, CU_TENSOR_MAP_L2_PROMOTION_L2_128B);
    enc3d(f, &tms.m[4], d_in[4], 64, 512, 64, 8192, 128, 64, 128, 1, S128, CU_TENSOR_MAP_L2_PROMOTION_L2_128B);
    enc3d(f, &tms.m[5], d_in[5], 512, 128, 32, 1024, 128 * 1024, 64, 128, 1, S128, CU_TENSOR_MAP_L2_PROMOTION_L2_128B);
    enc3d(f, &tms.m[6], d_in[7], 1792, 256, 2, 3584, 256 * 3584, 32, 256, 1, S64, CU_TENSOR_MAP_L2_PROMOTION_L2_128B);
    enc3d(f, &tms.m[7], d_in[8], 1792, 256, 2, 3584, 256 * 3584, 32, 256, 1, S64, CU_TENSOR_MAP_L2_PROMOTION_L2_128B);
    enc3d(f, &tms.m[8], d_in[9], 64, 1792, 8, 1024, 128, 64, 16, 8, S128, P256);
    cudaFuncSetAttribute(fused_kernel, cudaFuncAttributeMaxDynamicSharedMemorySize, SMEM9);
    cudaGetSymbolAddress(&scr, g_scr);
    make_sched(sch);
    init = true;
  }
  fused_kernel<<<NCTA9, 384, SMEM9>>>((const bf16*)d_in[0], (const bf16*)d_in[10], (const bf16*)d_in[11], (bf16*)d_out, (Scratch*)scr, sch, tms);
}

static bool fits() {
  cudaFuncSetAttribute(fused_kernel, cudaFuncAttributeMaxDynamicSharedMemorySize, SMEM9);
  cudaLaunchConfig_t cfg = {};
  cfg.gridDim = dim3(NCTA9); cfg.blockDim = dim3(384); cfg.dynamicSmemBytes = SMEM9;
  cudaLaunchAttribute at[1];
  at[0].id = cudaLaunchAttributeClusterDimension; at[0].val.clusterDim.x = 8; at[0].val.clusterDim.y = 1; at[0].val.clusterDim.z = 1;
  cfg.attrs = at; cfg.numAttrs = 1;
  int n = 0;
  if (cudaOccupancyMaxActiveClusters(&n, fused_kernel, &cfg) != cudaSuccess) { (void)cudaGetLastError(); return false; }
  return n >= NCTA9 / 8;
}
}
#undef BAR_ARM
#undef BAR_ARRIVE
#undef BAR_INIT
#undef B_EM
#undef B_EMPTY
#undef B_FM
#undef B_FULL
#undef B_G
#undef B_G2
#undef B_H
#undef B_HZ
#undef B_LZ
#undef B_Q2
#undef B_QF
#undef B_ST
#undef B_TAB
#undef B_W
#undef B_WZ
#undef CNT_ADD
#undef DSC
#undef HI128
#undef HI64
#undef NBIG
#undef NCTA9
#undef NPE
#undef NPO
#undef NSL
#undef O_B
#undef O_BAR
#undef O_CTX
#undef O_DBG
#undef O_EP
#undef O_HW
#undef O_HZ
#undef O_LZ
#undef O_P
#undef O_Q
#undef O_R
#undef O_SILU
#undef O_SM
#undef O_X
#undef PIN
#undef PINL
#undef POLL
#undef QN
#undef RETRY
#undef SK
#undef SMEM9
#undef SMEM_BASE
#undef SPIN_MAX
#undef TAU
#undef VDLY
#undef WTEST
#undef X16
#undef fbits

namespace v8 {
typedef __nv_bfloat16 bf16;
#define NCTA 128
#define SK 32768
#define SLOT 32768
#define NSLOT 6
#define OFF_WQ (2 * SLOT)
#define OFF_WUK (4 * SLOT)
#define OFF_Q 196608
#define OFF_P (OFF_Q + 16384)
#define OFF_B (OFF_P + 4096)
#define OFF_R4 (OFF_B + 2304)
#define OFF_SILU (OFF_R4 + 4096)
#define OFF_RA (OFF_SILU + 1024)
#define OFF_SM (OFF_RA + 1024)
#define OFF_BP (OFF_SM + 1792)
#define OFF_CO (OFF_BP + 1024)
#define OFF_BAR (OFF_CO + 1280)
#define OFF_MASK (OFF_BAR + 512)
#define OFF_DBG (OFF_MASK + 16)
#define SMEM_BYTES (OFF_DBG + 128)
#define OFF_MOD OFF_Q
#define OFF_UV (4 * SLOT)
#define OFF_O (5 * SLOT)
#define OFF_G 0
#define OFF_U 16384
#define OFF_D SLOT
#define OFF_XO (OFF_D + 16384)
#define FB_UK 4
#define FB_KV 6
#define FB_MOD 22
#define FB_UV 23
#define FB_O 25
#define FB_G 27
#define FB_D 29
#define EB 30
#define QB 50
#define XB 51
#define SPIN_MAX (1 << 20)
#define BACKOFF 40
#define RATE_NS 652
#define RATE_T0 200
#define RATE_TL 300
#define WINS 0x3222333
#define KVWIN 4
#define RATE_H 650
#define RATE_E 650
#define SMUL 9
#define NPRE0 1
#define NPRE1 3
#define HWIN 4
#define EWIN 3
#define WTEST 450
#define DLY5 650
#define DLY6 600
#define DLY7 600
#define P12(a, b, c, d, e, f, g, h, i, j, k, l) ((unsigned long long)(a) | (b) << 5 | (c) << 10 | (d) << 15 | (e) << 20 | (f) << 25 | \
  (unsigned long long)(g) << 30 | (unsigned long long)(h) << 35 | (unsigned long long)(i) << 40 | (unsigned long long)(j) << 45 | \
  (unsigned long long)(k) << 50 | (unsigned long long)(l) << 55)
#define ORDER0 P12(0, 1, 2, 3, 4, 5, 16, 6, 7, 8, 9, 10)
#define ORDER1 P12(11, 12, 13, 14, 15, 17, 18, 19, 20, 23, 21, 22)
#define TAIL_K 17
#define RS 16
template <int N> struct IC { static constexpr int value = N; };
struct TMaps { CUtensorMap m[9]; };

struct __align__(128) Scratch {
  uint4 xo[128 * 64 * RS];
  uint2 ml[32 * 64];
  unsigned h[8 * 256];
  unsigned qa[32 * 256];
  unsigned xc[128 * 64];
  unsigned xao[8 * 512];
  unsigned xf[112 * 512];
  unsigned xm[2048];
  unsigned cnt[5 * 32];
};
__device__ Scratch g_scr;
#define g_xo scr->xo
#define g_ml scr->ml
#define g_h scr->h
#define g_qa scr->qa
#define g_xc scr->xc
#define g_xao scr->xao
#define g_xf scr->xf
#define g_xm scr->xm
#define g_epoch scr->cnt[0]

__device__ __forceinline__ uint32_t s2u(const void* p) { return (uint32_t)__cvta_generic_to_shared(p); }
__device__ __forceinline__ float bflo(uint32_t u) { return __uint_as_float(u << 16); }
__device__ __forceinline__ float bfhi(uint32_t u) { return __uint_as_float(u & 0xffff0000u); }
__device__ __forceinline__ float u2f(uint32_t u) { return __uint_as_float(u); }
__device__ __forceinline__ void fma8(float* acc, uint4 v, float s) {
  acc[0] += s * bflo(v.x); acc[1] += s * bfhi(v.x); acc[2] += s * bflo(v.y); acc[3] += s * bfhi(v.y);
  acc[4] += s * bflo(v.z); acc[5] += s * bfhi(v.z); acc[6] += s * bflo(v.w); acc[7] += s * bfhi(v.w);
}
__device__ __forceinline__ uint32_t pack2(float a, float b) {
  __nv_bfloat162 p = __floats2bfloat162_rn(a, b); return *(uint32_t*)&p;
}
__device__ __forceinline__ float bfr(float v) { return bfhi(pack2(v, v)); }
__device__ __forceinline__ float silu_bf(float c) { return bfr(__fdividef(c, 1.f + __expf(-c))); }
#define fbits(v) ((__float_as_uint(v) & ~1u) | par)
__device__ __forceinline__ uint32_t pack2t(float a, float b, unsigned par) {
  const uint32_t ua = ((__float_as_uint(a) + ((par ^ 1) << 16)) & 0xFFFE0000u) | (par << 16);
  return __byte_perm(ua, pack2(b, b), 0x7632);
}
__device__ __forceinline__ void nbar(int id, int n) { asm volatile("bar.sync %0, %1;" ::"r"(id), "r"(n) : "memory"); }
__device__ __forceinline__ void nbar_arrive(int id, int n) { asm volatile("bar.arrive %0, %1;" ::"r"(id), "r"(n) : "memory"); }
__device__ __forceinline__ uint4 ldc16(const void* p) {
  uint4 v; asm volatile("ld.relaxed.cta.global.v4.u32 {%0,%1,%2,%3}, [%4];" : "=r"(v.x), "=r"(v.y), "=r"(v.z), "=r"(v.w) : "l"(p) : "memory"); return v;
}
__device__ __forceinline__ unsigned ldc4(const void* p) {
  unsigned v; asm volatile("ld.relaxed.cta.global.u32 %0, [%1];" : "=r"(v) : "l"(p) : "memory"); return v;
}
__device__ __forceinline__ uint4 ldx16(const void* p) {
  uint4 v; asm volatile("ld.relaxed.gpu.global.v4.u32 {%0,%1,%2,%3}, [%4];" : "=r"(v.x), "=r"(v.y), "=r"(v.z), "=r"(v.w) : "l"(p) : "memory"); return v;
}
__device__ __forceinline__ unsigned ldx4(const void* p) {
  unsigned v; asm volatile("ld.relaxed.gpu.global.u32 %0, [%1];" : "=r"(v) : "l"(p) : "memory"); return v;
}
__device__ __forceinline__ unsigned long long ldx64(const void* p) {
  unsigned long long v; asm volatile("ld.relaxed.gpu.global.u64 %0, [%1];" : "=l"(v) : "l"(p) : "memory"); return v;
}
__device__ __forceinline__ void stx16(void* p, uint4 v) {
  asm volatile("st.relaxed.gpu.global.v4.u32 [%0], {%1,%2,%3,%4};" ::"l"(p), "r"(v.x), "r"(v.y), "r"(v.z), "r"(v.w) : "memory");
}
__device__ __forceinline__ void stx8(void* p, uint2 v) { asm volatile("st.relaxed.gpu.global.v2.u32 [%0], {%1,%2};" ::"l"(p), "r"(v.x), "r"(v.y) : "memory"); }
__device__ __forceinline__ void stx4(void* p, unsigned v) { asm volatile("st.relaxed.gpu.global.u32 [%0], %1;" ::"l"(p), "r"(v) : "memory"); }
__device__ __forceinline__ unsigned lop_x3(unsigned a, unsigned b, unsigned c) {
  unsigned d; asm("lop3.b32 %0, %1, %2, %3, 0x7E;" : "=r"(d) : "r"(a), "r"(b), "r"(c)); return d; }
#define X16(v) (lop_x3(v.x, v.y, par) | lop_x3(v.z, v.w, par))
#define X8(v) lop_x3(v.x, v.y, par)
#define RETRY(bad) if (!__any_sync(~0u, (bad) & 1) || ++it_ >= SPIN_MAX) break; __nanosleep(BACKOFF);
#define POLL _Pragma("unroll 1") for (int it_ = 0;;)
__device__ __forceinline__ void mbar_wait(uint32_t bar) {
  uint32_t ok; int it = 0;
  do {
    asm volatile("{.reg .pred p; mbarrier.try_wait.parity.shared::cta.b64 p, [%1], 0; selp.u32 %0,1,0,p;}"
                 : "=r"(ok) : "r"(bar) : "memory");
  } while (!ok && ++it < SPIN_MAX);
}
__device__ __forceinline__ float ex2(float v) { float r; asm("ex2.approx.ftz.f32 %0, %1;" : "=f"(r) : "f"(v)); return r; }
__device__ __forceinline__ float rcp(float v) { float r; asm("rcp.approx.ftz.f32 %0, %1;" : "=f"(r) : "f"(v)); return r; }
__device__ __forceinline__ void mma16(float* d, const uint32_t* a, uint32_t b0, uint32_t b1) {
  asm volatile("mma.sync.aligned.m16n8k16.row.col.f32.bf16.bf16.f32 {%0,%1,%2,%3}, {%4,%5,%6,%7}, {%8,%9}, {%0,%1,%2,%3};"
               : "+f"(d[0]), "+f"(d[1]), "+f"(d[2]), "+f"(d[3]) : "r"(a[0]), "r"(a[1]), "r"(a[2]), "r"(a[3]), "r"(b0), "r"(b1));
}
__device__ __forceinline__ float4 lds16(uint32_t a) {
  float4 v; asm volatile("ld.shared.v4.f32 {%0,%1,%2,%3}, [%4];" : "=f"(v.x), "=f"(v.y), "=f"(v.z), "=f"(v.w) : "r"(a) : "memory"); return v;
}
__device__ __forceinline__ void ldsm_t(uint32_t* r, uint32_t a) {
  asm volatile("ldmatrix.sync.aligned.m8n8.x4.trans.shared.b16 {%0,%1,%2,%3}, [%4];" : "=r"(r[0]), "=r"(r[1]), "=r"(r[2]), "=r"(r[3]) : "r"(a) : "memory");
}
__device__ __forceinline__ void ldsm(uint32_t* r, uint32_t a) {
  asm volatile("ldmatrix.sync.aligned.m8n8.x4.shared.b16 {%0,%1,%2,%3}, [%4];" : "=r"(r[0]), "=r"(r[1]), "=r"(r[2]), "=r"(r[3]) : "r"(a) : "memory");
}
template <int N>
__device__ __forceinline__ void tred(float* a, int lane, int m) {
  const bool hi = lane & m;
#pragma unroll
  for (int i = 0; i < N; i++) {
    float send = hi ? a[i] : a[i + N], keep = hi ? a[i + N] : a[i];
    a[i] = keep + __shfl_xor_sync(~0u, send, m);
  }
}
template <int N>
__device__ __forceinline__ void tmax(float* a, int lane, int m) {
  const bool hi = lane & m;
#pragma unroll
  for (int i = 0; i < N; i++) {
    float send = hi ? a[i] : a[i + N], keep = hi ? a[i + N] : a[i];
    a[i] = fmaxf(keep, __shfl_xor_sync(~0u, send, m));
  }
}
__device__ __forceinline__ void arrive2(uint32_t bar, uint32_t rbar, bool local, bool remote) {
  asm volatile("{.reg .pred p, q; setp.ne.s32 p, %2, 0; setp.ne.s32 q, %3, 0; @p mbarrier.arrive.shared::cta.b64 _, [%0];\n"
               "@q mbarrier.arrive.relaxed.cluster.shared::cluster.b64 _, [%1];}" ::"r"(bar), "r"(rbar), "r"((int)local), "r"((int)remote) : "memory");
}
__device__ __forceinline__ unsigned long long stream_policy() {
  unsigned long long p;
  asm volatile("createpolicy.fractional.L2::evict_first.b64 %0, 1.0;" : "=l"(p));
  return p;
}
__device__ __forceinline__ void tma3d(uint32_t dst, const CUtensorMap* tm, uint32_t bar, int c0, int c1, int c2) {
  asm volatile("cp.async.bulk.tensor.3d.shared::cluster.global.mbarrier::complete_tx::bytes.L2::cache_hint [%0], [%1, {%3, %4, %5}], [%2], %6;"
               ::"r"(dst), "l"(tm), "r"(bar), "r"(c0), "r"(c1), "r"(c2), "l"(stream_policy()) : "memory");
}
__device__ __forceinline__ void st_async2(uint32_t dst, uint32_t bar, float v0, float v1) {
  asm volatile("st.async.shared::cluster.mbarrier::complete_tx::bytes.v2.f32 [%0], {%1, %2}, [%3];" ::"r"(dst), "f"(v0), "f"(v1), "r"(bar) : "memory");
}
__device__ __forceinline__ void st_pair(int mode, uint32_t dst, uint32_t bar, float v0, float v1) {
  asm volatile("{.reg .pred p, q; setp.eq.s32 p, %4, 1; setp.eq.s32 q, %4, 2; @p st.shared.v2.f32 [%0], {%1, %2};\n"
               "@q st.async.shared::cluster.mbarrier::complete_tx::bytes.v2.f32 [%0], {%1, %2}, [%3];}"
               ::"r"(dst), "f"(v0), "f"(v1), "r"(bar), "r"(mode) : "memory");
}
__device__ __forceinline__ void spin_until(unsigned t) { while ((int)((unsigned)clock() - t) < 0) {} }
__device__ __forceinline__ unsigned wait_until(unsigned t) {
  unsigned now;
  for (;;) {
    asm volatile("mov.u32 %0, %%globaltimer_lo;" : "=r"(now));
    if ((int)(now - t) >= 0) break;
  }
  return now;
}
#define PIN(x) asm volatile("" : "+r"(x))
#define PINL(x) asm volatile("" : "+l"(x))
#define BAR_ARRIVE(i) asm volatile("mbarrier.arrive.shared::cta.b64 _, [%0];" ::"r"(bar0 + 8 * (i)) : "memory")
#define CNT_ADD(c) asm volatile("red.relaxed.gpu.global.add.u32 [%0], 1;" ::"l"(scr->cnt + (c)) : "memory")
#define BAR_INIT(i, cnt) asm volatile("mbarrier.init.shared::cta.b64 [%0], %1;" ::"r"(bar0 + 8 * (i)), "r"(cnt) : "memory")
#define BAR_ARM(i, bytes) asm volatile("mbarrier.arrive.expect_tx.shared::cta.b64 _, [%0], %1;" ::"r"(bar0 + 8 * (i)), "r"(bytes) : "memory")

__device__ __forceinline__ void tail(unsigned char* smem, Scratch* __restrict__ scr, const bf16* __restrict__ x, bf16* __restrict__ out,
                                     const unsigned par, const unsigned epoch, const int warp) {
  int tid, b;
  asm volatile("mov.u32 %0, %%tid.x;" : "=r"(tid));
  asm volatile("mov.u32 %0, %%ctaid.x;" : "=r"(b));
  const int lane = tid & 31, g = lane >> 2, tq = lane & 3;
  const uint32_t sb = __shfl_sync(~0u, s2u(smem), 0), bar0 = sb + OFF_BAR;
  float* s_sm = (float*)(smem + OFF_SM);
  const int prow = 4 * (lane >> 4) + ((lane & 7) >> 1) + 8 * (lane & 1);
  const float* s_co = (const float*)(smem + OFF_CO);
  const int opos = (b & 15) * 32 + (lane & 16) + 2 * (lane & 6) + ((lane >> 2) & 2) + (lane & 1);
  const float xv = b < 16 ? __bfloat162float(x[(b & 15) * 32 + lane]) : 0.f;
  const int rk = b & 1, ob = 32 * rk + ((b >> 1) & 31);
  uint32_t psb;
  asm volatile("mapa.shared::cluster.u32 %0, %1, %2;" : "=r"(psb) : "r"(sb), "r"(rk ^ 1));
  {
    uint32_t a[8][4];
    {
      const int rg = tid >> 4;
      const uint4* src = g_xo + ((size_t)b * 64 + rg) * RS;
      const uint32_t dst = sb + OFF_XO + rg * 256 + (((tid & 15) ^ (rg & 7)) << 4);
      unsigned long long todo = 0x0001000100010001ull;
#pragma unroll 1
      for (int it = 0; it < SPIN_MAX * 16; it++) {
        unsigned long long mk = *(volatile unsigned long long*)(smem + OFF_MASK);
        const unsigned long long nw = (mk >> rg) & todo;
        todo ^= nw;
#pragma unroll
        for (int i = 0; i < 4; i++)
          if (nw >> (16 * i) & 1)
            asm volatile("cp.async.cg.shared.global [%0], [%1], 16;" ::"r"(dst + i * 4096), "l"(src + i * 16 * RS + (tid & 15)) : "memory");
        if (!__any_sync(~0u, todo != 0)) break;
      }
      asm volatile("cp.async.mbarrier.arrive.noinc.shared::cta.b64 [%0];" ::"r"(bar0 + 8 * (XB + 2)) : "memory");
    }
    mbar_wait(bar0 + 8 * FB_UV); mbar_wait(bar0 + 8 * (FB_UV + 1));
    const uint32_t ab = sb + OFF_UV + (warp >> 2) * 8192 + (8 * (lane >> 4) + (lane & 7)) * 128 + (((2 * (warp & 3) + ((lane >> 3) & 1)) ^ (lane & 7)) << 4);
#pragma unroll
    for (int s = 0; s < 8; s++) ldsm_t(a[s], ab + (s >> 2) * 16384 + (s & 3) * 2048);
    const int chn = 2 * warp + (tq & 1);
    uint32_t a_b = sb + OFF_B + (tq >> 1) * 272 + (32 * (chn >> 2) + 8 * (g >> 1) + 2 * (chn & 3) + (g & 1)) * 2;
    uint32_t a_bq = sb + OFF_B + (lane & 1) * 272 + (lane >> 3) * 16;
    unsigned* p_c = g_xc + (b >> 2) * 256 + warp * 32 + (b & 3) * 8 + (g & 3) * 2 + (g >> 2);
    PIN(a_b); PIN(a_bq); PINL(p_c);
    mbar_wait(bar0 + 8 * (XB + 6));
    uint32_t wb[8];
#pragma unroll
    for (int s = 0; s < 8; s++) wb[s] = *(const uint32_t*)(smem + OFF_RA + (4 * s + tq) * 4);
    const float invL = *(const float*)(smem + OFF_RA + 128);
    float ov;
    POLL {
      mbar_wait(bar0 + 8 * (XB + 2));
      uint32_t ao[4][4];
#pragma unroll
      for (int s = 0; s < 4; s++)
        ldsm_t(ao[s], sb + OFF_XO + (16 * s + 8 * (lane >> 4) + (lane & 7)) * 256 + (((2 * warp + ((lane >> 3) & 1)) ^ (lane & 7)) << 4));
      float d[4][4] = {};
#pragma unroll
      for (int s = 0; s < 4; s++) mma16(d[s], ao[s], wb[2 * s], wb[2 * s + 1]);
      const unsigned p2 = par * 0x10001u;
      unsigned bad = 0;
#pragma unroll
      for (int s = 0; s < 4; s++) bad |= lop_x3(ao[s][0], ao[s][1], p2) | lop_x3(ao[s][2], ao[s][3], p2);
      bad = g == 0 ? bad | (bad >> 16) : 0u;
      ov = (tq & 1) ? (d[0][2] + d[1][2]) + (d[2][2] + d[3][2]) : (d[0][0] + d[1][0]) + (d[2][0] + d[3][0]);
      if (__builtin_expect(!__any_sync(~0u, bad & 1) || ++it_ >= SPIN_MAX, 1)) break;
#pragma unroll
      for (int i = 0; i < 4; i++)
        asm volatile("cp.async.cg.shared.global [%0], [%1], 16;"
                     ::"r"(sb + OFF_XO + ((lane >> 1) + 16 * i) * 256 + (((2 * warp + (lane & 1)) ^ ((lane >> 1) & 7)) << 4)),
                       "l"(g_xo + ((size_t)b * 64 + (lane >> 1) + 16 * i) * RS + 2 * warp + (lane & 1)) : "memory");
      asm volatile("cp.async.wait_all;" ::: "memory");
      __syncwarp();
    }
    {
      const float lo = ov - bfhi(__float_as_uint(ov));
      asm volatile("st.shared.u16 [%0], %1;" ::"r"(a_b), "h"((unsigned short)((tq & 2) ? pack2(lo, lo) : __float_as_uint(ov) >> 16)) : "memory");
    }
    nbar(1, 256);
    float d[4][4] = {};
#pragma unroll
    for (int y = 0; y < 4; y++) {
      uint32_t bq[4];
      ldsm(bq, a_bq + 64 * y);
      mma16(d[(2 * y) & 3], a[2 * y], bq[0], bq[1]); mma16(d[(2 * y + 1) & 3], a[2 * y + 1], bq[2], bq[3]);
    }
    const float r0 = ((d[0][0] + d[0][1]) + (d[1][0] + d[1][1])) + ((d[2][0] + d[2][1]) + (d[3][0] + d[3][1]));
    const float r1 = ((d[0][2] + d[0][3]) + (d[1][2] + d[1][3])) + ((d[2][2] + d[2][3]) + (d[3][2] + d[3][3]));
    if (tq == 0) stx4(p_c, pack2t(r0 * invL, r1 * invL, par));
  }
  unsigned tpub = clock();
  mbar_wait(bar0 + 8 * (XB + 4));
  const float gav = s_co[256 + (opos & 31)];
  const float gbv = s_co[288 + (lane & 4) + 2 * (lane & 1) + ((lane >> 1) & 1)];
  float4 cf[2];
#pragma unroll
  for (int s = 0; s < 2; s++) cf[s] = *(const float4*)(s_co + 32 * warp + 16 * s + 4 * tq);
  {
    uint32_t a[2][4][4];
    mbar_wait(bar0 + 8 * (FB_O + (warp >> 2)));
    const uint32_t ab = sb + OFF_O + (32 * warp + prow) * 128 + ((((lane >> 3) & 1) ^ (prow & 7)) << 4);
#pragma unroll
    for (int i = 0; i < 8; i++) ldsm_t(a[i >> 2][i & 3], (ab + (i >> 2) * 2048) ^ ((i & 3) << 5));
    uint4 v;
    const unsigned* pc = g_xc + (4 * (b >> 4) + 2 * rk + (warp >> 2)) * 256 + 64 * (warp & 3) + 2 * lane;
    uint32_t ro = ((tq >> 1) == rk ? sb : psb) + OFF_P + (8 * (tq & 1) + g) * 144 + (8 * rk + warp) * 8;
    uint32_t a_q = sb + OFF_P + (8 * (lane >> 4) + (lane & 7)) * 144;
    unsigned* p_ao = g_xao + (b >> 5) * 1024 + (opos >> 4) * 32 + (b & 16) + (opos & 15);
    PIN(ro); PIN(a_q); PINL(p_ao); PINL(pc);
    spin_until(tpub + DLY5);
    POLL {
      const unsigned long long u0 = ldx64(pc);
      v.x = (unsigned)u0; v.y = u0 >> 32;
      RETRY(X8(v))
    }
    v.z = lane & 16 ? v.x : 0u; v.w = lane & 16 ? v.y : 0u;
    if (lane & 16) v.x = v.y = 0u;
    float d[4][4] = {};
#pragma unroll
    for (int mt = 0; mt < 4; mt++) mma16(d[mt], a[0][mt], v.x, v.y);
#pragma unroll
    for (int mt = 0; mt < 4; mt++) mma16(d[mt], a[1][mt], v.z, v.w);
    float r[8];
#pragma unroll
    for (int i = 0; i < 8; i++) r[i] = d[i >> 1][2 * (i & 1)] + d[i >> 1][2 * (i & 1) + 1];
    tred<4>(r, lane, 2); tred<2>(r, lane, 1);
    st_pair((tq >> 1) == rk ? 1 : 2, ro, psb + OFF_BAR + 8 * (XB + 3), r[0], r[1]);
    __syncwarp();
    if (lane == 0) BAR_ARRIVE(XB + 3);
    if (warp == 0) {
      mbar_wait(bar0 + 8 * (XB + 3));
      float p[8];
#pragma unroll
      for (int i = 0; i < 8; i++) {
        const float4 q = lds16(a_q + i * 16);
        p[i] = (lane & 8) ? q.y + q.w : q.x + q.z;
      }
      const float t = ((p[0] + p[1]) + (p[2] + p[3])) + ((p[4] + p[5]) + (p[6] + p[7]));
      stx4(p_ao, fbits(gav * t + xv));
    }
  }
  tpub = clock();
  if (b < 112) {
    uint32_t af[2][4][4], ad[4][4];
    const uint32_t ab = sb + (32 * warp + 8 * (lane >> 4) + (lane & 7)) * 64 + ((((lane >> 3) & 1) ^ ((lane >> 1) & 3)) << 4);
    uint32_t ro = ((tq & 1) == rk ? sb : psb) + OFF_R4 + (8 * (tq >> 1) + g) * 176 + (10 * rk + warp) * 8;
    uint32_t a_q = sb + OFF_R4 + (8 * (lane >> 4) + (lane & 7)) * 176 + (lane & 8) * 10;
    uint32_t a_d = sb + OFF_D + warp * 2048 + (8 * (lane >> 4) + (lane & 7)) * 128 + ((((lane >> 3) & 1) ^ (lane & 7)) << 4);
    unsigned* p_f = g_xf + b * 512 + 64 * warp + 16 * tq + 2 * g;
    const unsigned* pa = g_xao + (g >> 1) * 1024 + 512 * rk + 64 * warp + 4 * (lane & 7);
    PIN(ro); PIN(a_q); PIN(a_d); PINL(p_f); PINL(pa);
    spin_until(tpub + DLY6);
    uint4 v[2];
    {
      bool have = false;
      POLL {
        v[0] = ldx16(pa); v[1] = ldx16(pa + 32);
        const unsigned t1 = (unsigned)clock() + WTEST;
        while (!have && (int)((unsigned)clock() - t1) < 0) {
          uint32_t ok;
          asm volatile("{.reg .pred p, q; mbarrier.test_wait.parity.shared::cta.b64 p, [%1], 0; mbarrier.test_wait.parity.shared::cta.b64 q, [%1+8], 0;\n"
                       "and.pred p, p, q; vote.sync.all.pred p, p, 0xffffffff; selp.u32 %0, 1, 0, p;}" : "=r"(ok) : "r"(bar0 + 8 * FB_G) : "memory");
          if (ok) {
#pragma unroll
            for (int i = 0; i < 8; i++) ldsm_t(af[i >> 2][i & 3], (ab + ((i & 2) ? OFF_U : OFF_G) + (i >> 2) * 1024) ^ ((i & 1) << 5));
            have = true;
          }
        }
        if (!__any_sync(~0u, (X16(v[0]) | X16(v[1])) & 1) || ++it_ >= SPIN_MAX) break;
      }
      float df[4][4] = {}, dg[2][4] = {};
      uint32_t zb[4];
      const uint32_t one = g == 0 ? 0x3F803F80u : 0u;
#pragma unroll
      for (int s = 0; s < 2; s++) {
        const uint32_t y0 = pack2(u2f(v[s].x), u2f(v[s].y)), y1 = pack2(u2f(v[s].z), u2f(v[s].w));
        const uint32_t ya[4] = {y0, one, y1, one};
        mma16(dg[s], ya, y0, y1);
        zb[2 * s] = pack2(u2f(v[s].x) * cf[s].x, u2f(v[s].y) * cf[s].y); zb[2 * s + 1] = pack2(u2f(v[s].z) * cf[s].z, u2f(v[s].w) * cf[s].w);
      }
      float st[2] = {(dg[0][2] + dg[0][3]) + (dg[1][2] + dg[1][3]), (dg[0][0] + dg[0][1]) + (dg[1][0] + dg[1][1])};
      if (!have) {
        mbar_wait(bar0 + 8 * FB_G); mbar_wait(bar0 + 8 * (FB_G + 1));
#pragma unroll
        for (int i = 0; i < 8; i++) ldsm_t(af[i >> 2][i & 3], (ab + ((i & 2) ? OFF_U : OFF_G) + (i >> 2) * 1024) ^ ((i & 1) << 5));
      }
#pragma unroll
      for (int i = 0; i < 8; i++) mma16(df[i & 3], af[i >> 2][i & 3], zb[2 * (i >> 2)], zb[2 * (i >> 2) + 1]);
#pragma unroll
      for (int o2 = 1; o2 < 4; o2 <<= 1) { st[0] += __shfl_xor_sync(~0u, st[0], o2); st[1] += __shfl_xor_sync(~0u, st[1], o2); }
#pragma unroll
      for (int o2 = 4; o2 < 32; o2 <<= 1) st[1] += __shfl_xor_sync(~0u, st[1], o2);
      float r[8];
#pragma unroll
      for (int i = 0; i < 8; i++) r[i] = df[i >> 1][2 * (i & 1)] + df[i >> 1][2 * (i & 1) + 1];
      tred<4>(r, lane, 2); tred<2>(r, lane, 1);
      const int md = (tq & 1) == rk ? 1 : 2;
      st_pair(md, ro, psb + OFF_BAR + 8 * (XB + 5), r[0], r[1]);
      st_pair(lane < 2 ? md : 0, ro + 16 * 176, psb + OFF_BAR + 8 * (XB + 5), st[0], st[1]);
      __syncwarp();
      if (lane == 0) BAR_ARRIVE(XB + 5);
      mbar_wait(bar0 + 8 * FB_D);
#pragma unroll
      for (int mt = 0; mt < 4; mt++)
        ldsm_t(ad[mt], a_d ^ (mt << 5));
    }
    mbar_wait(bar0 + 8 * (XB + 5));
    {
      float4 q[5], u[8];
#pragma unroll
      for (int i = 0; i < 5; i++) q[i] = lds16(a_q + i * 16);
#pragma unroll
      for (int i = 0; i < 8; i++) u[i] = *(const float4*)(smem + OFF_R4 + 16 * 176 + (i >> 2) * 80 + (i & 3) * 16);
      float p[6] = {((q[0].x + q[0].z) + (q[1].x + q[1].z)) + ((q[2].x + q[2].z) + (q[3].x + q[3].z)), q[4].x, q[4].z,
                    ((q[0].y + q[0].w) + (q[1].y + q[1].w)) + ((q[2].y + q[2].w) + (q[3].y + q[3].w)), q[4].y, q[4].w};
      tred<3>(p, lane, 8);
      const float P = p[0], A1 = p[1], A2 = p[2];
      const float mean = (((u[0].x + u[0].z) + (u[1].x + u[1].z)) + ((u[2].x + u[2].z) + (u[3].x + u[3].z)) +
                          ((u[4].x + u[4].z) + (u[5].x + u[5].z)) + ((u[6].x + u[6].z) + (u[7].x + u[7].z))) * (1.f / 512.f);
      const float sq = (((u[0].y + u[0].w) + (u[1].y + u[1].w)) + ((u[2].y + u[2].w) + (u[3].y + u[3].w)) +
                         ((u[4].y + u[4].w) + (u[5].y + u[5].w)) + ((u[6].y + u[6].w) + (u[7].y + u[7].w))) * (1.f / 512.f);
      float rstd;
      asm("rsqrt.approx.ftz.f32 %0, %1;" : "=f"(rstd) : "f"(fmaxf(sq - mean * mean, 0.f) + 1e-5f));
      const float gg = bfr(rstd * (P - mean * A1) + A2);
      const float uu = __shfl_xor_sync(~0u, gg, 16);
      const float hh = bfr(gg * rcp(1.f + ex2(gg * (-2.302208198f - 0.1029432397f * gg * gg)))) * uu;
      const uint32_t hw = pack2(hh, __shfl_down_sync(~0u, hh, 1));
      const uint32_t b0 = __shfl_sync(~0u, hw, 2 * tq), b1 = __shfl_sync(~0u, hw, 2 * tq + 8);
      float f0 = 0, f1 = 0;
#pragma unroll
      for (int mt = 0; mt < 4; mt++) {
        float dd[4] = {0, 0, 0, 0};
        mma16(dd, ad[mt], b0, b1);
        if (tq == mt) { f0 = dd[0]; f1 = dd[2]; }
      }
      stx8(p_f, make_uint2(fbits(f0), fbits(f1)));
    }
    tpub = clock();
    if (b < 64 && warp == (b >> 3)) {
      const uint4 y = (b & 4) ? v[1] : v[0];
      float a4[4] = {u2f(y.x), u2f(y.y), u2f(y.z), u2f(y.w)};
      tred<2>(a4, lane, 16); tred<1>(a4, lane, 8);
      a4[0] += __shfl_xor_sync(~0u, a4[0], 4);
      if (!(lane & 4)) s_sm[416 + 8 * (lane >> 4) + 2 * tq + ((lane >> 3) & 1)] = a4[0];
      if (warp == 7) nbar_arrive(2, 256);
    } else if (b < 64 && warp == 7) nbar_arrive(2, 256);
    if (b < 64 && warp < 7) {
      uint4 v;
      const unsigned* pf = g_xf + (tid >> 1) * 512 + 8 * ob + 4 * (tid & 1);
      const int col = 16 * (ob >> 1) + 4 * (ob & 1) + ((tid >> 1) & 3) + 8 * (tid & 1);
      bf16* po = out + col;
      PINL(po); PINL(pf);
      spin_until(tpub + DLY7);
      POLL { v = ldx16(pf); RETRY(X16(v)) }
      float f[4] = {u2f(v.x), u2f(v.y), u2f(v.z), u2f(v.w)};
      tred<2>(f, lane, 16); tred<1>(f, lane, 8);
      f[0] += __shfl_xor_sync(~0u, f[0], 4); f[0] += __shfl_xor_sync(~0u, f[0], 2);
      if (!(lane & 6)) s_sm[352 + warp * 8 + 4 * (lane & 1) + (lane >> 3)] = f[0];
      nbar(2, 256);
      if (tid < 8) {
        const float* q = s_sm + 352 + tid;
        const float t = ((q[0] + q[8]) + (q[16] + q[24])) + ((q[32] + q[40]) + q[48]);
        *po = __float2bfloat16(s_sm[416 + (col & 15)] + bfr(gbv * bfr(t)));
        if (b == 0 && tid == 0) stx4(&g_epoch, epoch + 1);
      }
    }
  }
}

__global__ void __cluster_dims__(2, 1, 1) __launch_bounds__(384, 1)
fused_kernel(const bf16* __restrict__ x, const bf16* __restrict__ cvec, const bf16* __restrict__ w_mod, bf16* __restrict__ out,
             Scratch* __restrict__ scr, const __grid_constant__ TMaps tms) {
  extern __shared__ __align__(1024) unsigned char smem[];
  const int tid = threadIdx.x, warp = __shfl_sync(~0u, tid >> 5, 0), lane = tid & 31;
  const int b = blockIdx.x, rk = b & 1, pr = b >> 1, hd = b >> 2;
  uint32_t sb = s2u(smem), bar0 = sb + OFF_BAR;

  unsigned gt_start;
  asm volatile("mov.u32 %0, %%globaltimer_lo;" : "=r"(gt_start));
  const int g = lane >> 2, tq = lane & 3;
  const int arow = 64 * (b >> 4) + ((tid & 255) >> 3);
  uint4 wm0, wm1;
  uint32_t c0w, c1w;
  if (warp < 8) {
    const bf16* wa = w_mod + (size_t)arow * 3072 + (lane & 4) * 128 + 32 * (b & 15) + 8 * tq;
    wm0 = ldx16(wa); wm1 = ldx16(wa + 32 * 3072);
    c0w = ldc4(cvec + (arow & ~1)); c1w = ldc4(cvec + (arow & ~1) + 32);
  }
  const unsigned t_off = gt_start + RATE_T0;
  if (warp == 11) {
    if (lane == 0) {
#pragma unroll
      for (int i = 0; i < FB_KV; i++) { BAR_INIT(i, 1); BAR_ARM(i, 16384); }
    }
    __syncwarp();
    asm volatile("fence.mbarrier_init.release.cluster;" ::: "memory");
    asm volatile("barrier.cluster.arrive.relaxed.aligned;" ::: "memory");
#pragma unroll 1
    for (int i = 0; i < FB_KV; i++) {
      if (i >= HWIN) mbar_wait(bar0 + 8 * (i - HWIN));
      wait_until(t_off + (i < 4 ? 2 * i + ((b >> 1) & 1) : 4 * i - 8 + (b & 3)) * (RATE_H / 4));
      if (lane == 0) {
        if (i < 4) tma3d(sb + OFF_WQ + i * 16384, &tms.m[0], bar0 + 8 * i, 0, i * 128, 2 * hd + rk);
        else tma3d(sb + OFF_WQ + i * 16384, &tms.m[1], bar0 + 8 * i, 0, (b & 3) * 128 + (i - 4) * 64, 2 * hd);
      }
      __syncwarp();
    }
  }
  if (warp == 10) {
    const uint4 xa = ldc16(x + 16 * lane), xb = ldc16(x + 16 * lane + 8);
    const unsigned ep = ldc4(&g_epoch);
    float xv[16] = {bflo(xa.x), bfhi(xa.x), bflo(xa.y), bfhi(xa.y), bflo(xa.z), bfhi(xa.z), bflo(xa.w), bfhi(xa.w),
                    bflo(xb.x), bfhi(xb.x), bflo(xb.y), bfhi(xb.y), bflo(xb.z), bfhi(xb.z), bflo(xb.w), bfhi(xb.w)};
    float s = 0;
#pragma unroll
    for (int i = 0; i < 16; i++) s += xv[i];
#pragma unroll
    for (int o = 16; o; o >>= 1) s += __shfl_xor_sync(~0u, s, o);
    const float mean = s * (1.f / 512.f);
    s = 0;
#pragma unroll
    for (int i = 0; i < 16; i++) { xv[i] -= mean; s += xv[i] * xv[i]; }
#pragma unroll
    for (int o = 16; o; o >>= 1) s += __shfl_xor_sync(~0u, s, o);
    const float rstd = rsqrtf(s * (1.f / 512.f) + 1e-5f);
    if ((lane >> 1) == (b & 15))
#pragma unroll
      for (int i = 0; i < 4; i++)
        *(float4*)(smem + OFF_SM + (256 + (lane & 1) * 16 + 4 * i) * 4) = make_float4(xv[4 * i] * rstd, xv[4 * i + 1] * rstd, xv[4 * i + 2] * rstd, xv[4 * i + 3] * rstd);
    if (lane == 0) *(volatile unsigned*)(smem + OFF_MASK + 8) = ep;
    nbar_arrive(1, 288);
  }
  if (warp >= 8) {
    asm volatile("setmaxnreg.dec.sync.aligned.u32 72;");
    if (tid == 288) {
#pragma unroll
      for (int q = FB_KV; q < FB_KV + 16; q++) { BAR_INIT(q, 1); BAR_ARM(q, 32768); }
    }
    if (tid == 320) {
#pragma unroll
      for (int q = 0; q <= 13 + NSLOT; q++) BAR_INIT(EB + q, q == 0 ? 4 : q < 5 ? 16 : q < 16 ? 12 : 6);
    }
    if (tid == 256) {
#pragma unroll
      for (int q = FB_MOD; q <= FB_D; q++) { BAR_INIT(q, 1); BAR_ARM(q, 16384); }
      BAR_INIT(QB, 9); BAR_ARM(QB, 1024);
#pragma unroll
      for (int q = 0; q < 7; q++) BAR_INIT(XB + q, q == 2 ? 256 : q == 5 || q == 3 ? 9 : 1);
      BAR_ARM(XB + 3, 1024);
      BAR_ARM(XB + 5, 1024 + 64 + 512);
      *(volatile unsigned long long*)(smem + OFF_MASK) = 0;
    }
    if (warp != 11) {
      __syncwarp();
      asm volatile("fence.mbarrier_init.release.cluster;" ::: "memory");
      __threadfence_block();
      asm volatile("barrier.cluster.arrive.relaxed.aligned;" ::: "memory");
    }
    if (warp == 11) {
      asm volatile("barrier.cluster.wait.acquire.aligned;" ::: "memory");
      const unsigned epoch = *(volatile unsigned*)(smem + OFF_MASK + 8), par = (epoch + 1) & 1;
      mbar_wait(bar0 + 8 * (FB_KV + 15));
      for (int it = 0; ldx4(scr->cnt + 96 + 32 * (b >> 6)) != (epoch + 1) * 64 && it < SPIN_MAX; it++) {}
      uint4 hh;
      POLL { hh = ldx16(g_ml + (b >> 2) * 64 + 2 * lane); RETRY(X16(hh)) }
      int mi = __float_as_int(fmaxf(u2f(hh.x), u2f(hh.z)));
      mi ^= (mi >> 31) & 0x7fffffff;
      mi = __reduce_max_sync(~0u, mi);
      mi ^= (mi >> 31) & 0x7fffffff;
      const float M = __int_as_float(mi);
      const uint32_t wp = pack2(ex2(u2f(hh.x) - M), ex2(u2f(hh.z) - M));
      float L = bflo(wp) * u2f(hh.y) + bfhi(wp) * u2f(hh.w);
#pragma unroll
      for (int o2 = 16; o2; o2 >>= 1) L += __shfl_xor_sync(~0u, L, o2);
      *(uint32_t*)(smem + OFF_RA + lane * 4) = wp;
      if (lane == 0) *(float*)(smem + OFF_RA + 128) = rcp(L);
      __syncwarp();
      if (lane == 0) BAR_ARRIVE(XB + 6);
    }
    if (warp == 10) {
      if (lane < 8) asm volatile("prefetch.tensormap [%0];" ::"l"(&tms.m[lane + 1]) : "memory");
      asm volatile("barrier.cluster.wait.acquire.aligned;" ::: "memory");
      const unsigned epoch = *(volatile unsigned*)(smem + OFF_MASK + 8);
#pragma unroll 1
      for (int e = 0; e < 2; e++) {
        for (int it = 0; ldx4(scr->cnt + (e ? 2 + rk : 1)) != (epoch + 1) * (e ? 64 : 128) && it < SPIN_MAX; it++) {}
        if (lane == 0) BAR_ARRIVE(XB + e);
      }
      mbar_wait(bar0 + 8 * (FB_KV + 14));
      unsigned long long m = 0;
#pragma unroll 1
      for (int it = 0; ~m && it < SPIN_MAX; it++) {
        m = ldx64(scr->cnt + 32 + 32 * (b >> 6)) ^ ((epoch & 1) ? ~0ull : 0ull);
        if (lane == 0) *(volatile unsigned long long*)(smem + OFF_MASK) = m;
      }
    }
    if (warp == 9) {
      asm volatile("barrier.cluster.wait.acquire.aligned;" ::: "memory");
      const unsigned epoch = *(volatile unsigned*)(smem + OFF_MASK + 8);
      const unsigned par = (epoch + 1) & 1, inv = par ^ 1;
      const uint4 inv4 = make_uint4(inv, inv, inv, inv);
      mbar_wait(bar0 + 8 * FB_KV);
#pragma unroll 2
      for (int k = 0; k < 8; k++) {
        const uint32_t cp = ldc4(cvec + 2 * (lane + 32 * k));
        *(uint32_t*)(smem + OFF_SILU + (lane + 32 * k) * 4) = pack2(silu_bf(bflo(cp)), silu_bf(bfhi(cp)));
      }
      __syncwarp();
      mbar_wait(bar0 + 8 * FB_MOD);
      const uint32_t ab = sb + OFF_MOD + (8 * (lane >> 4) + (lane & 7)) * 32 + ((((lane >> 3) ^ (lane >> 2)) & 1) << 4);
      float d[4][4] = {};
#pragma unroll 2
      for (int s4 = 0; s4 < 8; s4++)
#pragma unroll
        for (int s = 0; s < 4; s++) {
          uint32_t a[4];
          const uint32_t* ps = (const uint32_t*)(smem + OFF_SILU) + 32 * s4 + 8 * s + tq;
          ldsm_t(a, ab + (4 * s4 + s) * 512); mma16(d[s], a, ps[0], ps[4]);
        }
      const float t = (tq & 1) ? (d[0][2] + d[1][2]) + (d[2][2] + d[3][2]) : (d[0][0] + d[1][0]) + (d[2][0] + d[3][0]);
      if (tq < 2) stx4(g_xm + b * 16 + 2 * (g & 6) + 2 * tq + (g & 1), fbits(bfr(t)));
      __syncwarp();
      if (lane == 0) CNT_ADD(6);
      mbar_wait(bar0 + 8 * (FB_KV + 8));
      if (lane < 16) stx16(g_xc + (b >> 2) * 256 + (lane >> 1) * 32 + (b & 3) * 8 + (lane & 1) * 4, inv4);
      if (lane < 8) stx16(g_xao + (b >> 5) * 1024 + (b & 15) * 64 + (lane & 4) * 8 + (b & 16) + (lane & 3) * 4, inv4);
      if (b < 112)
#pragma unroll 1
        for (int k = 0; k < 4; k++) stx16(g_xf + b * 512 + (lane + 32 * k) * 4, inv4);
      nbar_arrive(2, 288);
      for (int it = 0; ldx4(scr->cnt + 6) != (epoch + 1) * 128 && it < SPIN_MAX; it++) __nanosleep(100);
      {
        uint4 sv[2], cb[2];
        unsigned ga, gb;
        POLL {
#pragma unroll
          for (int k = 0; k < 2; k++) { sv[k] = ldx16(g_xm + 512 + 256 * rk + 4 * (lane + 32 * k)); cb[k] = ldx16(g_xm + 1024 + 256 * rk + 4 * (lane + 32 * k)); }
          ga = ldx4(g_xm + (b & 15) * 32 + lane); gb = ldx4(g_xm + 1536 + 256 * rk + 8 * (pr & 31) + (lane & 7));
          RETRY(X16(sv[0]) | X16(sv[1]) | X16(cb[0]) | X16(cb[1]) | lop_x3(ga, gb, par))
        }
#pragma unroll
        for (int k = 0; k < 2; k++) {
          const float c0 = bfr(1.f + bfhi(cb[k].x)), c1 = bfr(1.f + bfhi(cb[k].y)), c2 = bfr(1.f + bfhi(cb[k].z)), c3 = bfr(1.f + bfhi(cb[k].w));
          *(float4*)(smem + OFF_CO + (lane + 32 * k) * 16) = make_float4(c0, c1, c2, c3);
          uint2* pb = (uint2*)(smem + OFF_BP) + lane + 32 * k;
          pb[0] = make_uint2(pack2(c0, c1), pack2(c2, c3));
          pb[64] = make_uint2(__byte_perm(sv[k].x, sv[k].y, 0x7632), __byte_perm(sv[k].z, sv[k].w, 0x7632));
        }
        *(float*)(smem + OFF_CO + 1024 + lane * 4) = bfhi(ga);
        *(float*)(smem + OFF_CO + 1152 + lane * 4) = bfhi(gb);
      }
      __syncwarp();
      if (lane == 0) BAR_ARRIVE(XB + 4);
    }
    if (warp == 8) {
      const unsigned stag = ((pr * SMUL) & 63) * RATE_NS >> 6;
      unsigned tnext = t_off + 4 * RATE_H;
      asm volatile("barrier.cluster.wait.acquire.aligned;" ::: "memory");
#pragma unroll 1
      for (int k = 0; k < 24; k++) {
        const int code = (k < 12 ? ORDER0 >> (5 * k) : ORDER1 >> (5 * (k - 12))) & 31;
        const bool kv = code < 16;
        const int n = code, w = code - 16;
        if (!kv && w >= 5 && b >= 112) break;
        if (kv) mbar_wait(bar0 + 8 * (FB_KV + n - (n < 6 ? EWIN : KVWIN)));
        if (k >= TAIL_K) mbar_wait(bar0 + 8 * (FB_KV + (int)((ORDER1 >> (5 * (k - 12 - ((WINS >> (4 * (k - TAIL_K))) & 15)))) & 31)));
        const int e = kv ? (n == 3 ? 2 : n == 5 ? 1 : n) : w == 0 ? 0 : w < 5 ? 16 + ((w - 1) >> 1) : w == 7 ? 19 : 18;
        if (e != 1 && k) mbar_wait(bar0 + 8 * (EB + e));
        wait_until(tnext + stag);
        tnext += k > TAIL_K ? RATE_TL : k < 4 ? RATE_E : RATE_NS;
        if (lane == 0) {
          if (kv)
            asm volatile("cp.async.bulk.tensor.3d.shared::cluster.global.mbarrier::complete_tx::bytes.multicast::cluster.L2::cache_hint [%0], [%1, {%3, %4, %5}], [%2], %6, %7;"
                         ::"r"(sb + (n % NSLOT) * SLOT + rk * 16384), "l"(&tms.m[2]), "r"(bar0 + 8 * (FB_KV + n)), "r"(0), "r"(((n >> 1) * 64 + pr) * 64),
                           "r"(4 * (n & 1) + 2 * rk), "h"((unsigned short)3), "l"(stream_policy()) : "memory");
          else {
            tma3d(sb + (w == 0 ? OFF_MOD : w < 5 ? OFF_UV + (w - 1) * 16384 : w == 5 ? OFF_G : w == 6 ? OFF_U : OFF_D),
                  &tms.m[w == 0 ? 3 : w < 3 ? 4 : w < 5 ? 5 : w + 1], bar0 + 8 * (FB_MOD + w),
                  w == 0 ? 1024 + b * 16 : w < 3 || w == 7 ? 0 : w < 5 ? (pr & 7) * 64 : pr * 32, w == 7 ? b * 16 : w == 1 || w == 2 ? (b & 3) * 128 + (w - 1) * 64 : 0,
                  w == 1 || w == 2 ? 2 * hd : w == 3 || w == 4 ? (b >> 4) * 4 + 2 * rk + w - 3 : w == 5 || w == 6 ? rk : 0);
          }
        }
        __syncwarp();
      }
    }
    if (b < 112) {
      const int mt = warp & 1, dd = (warp >> 1) & 1;
      mbar_wait(bar0 + 8 * (XB + 4));
      const uint32_t ab = sb + (mt ? OFF_U : OFF_G) + (8 * (lane >> 4) + (lane & 7)) * 64 + (((2 * dd + ((lane >> 3) & 1)) ^ ((lane >> 1) & 3)) << 4);
      uint32_t base;
      asm volatile("mapa.shared::cluster.u32 %0, %1, %2;" : "=r"(base) : "r"(sb), "r"(dd));
      uint2 bb[16];
#pragma unroll
      for (int s = 0; s < 16; s++) bb[s] = *(const uint2*)(smem + OFF_BP + (g & 1) * 512 + (4 * s + tq) * 8);
      mbar_wait(bar0 + 8 * (FB_G + mt));
      float e[4][4] = {};
#pragma unroll
      for (int s = 0; s < 16; s++) { uint32_t a[4]; ldsm_t(a, ab + s * 1024); mma16(e[s & 3], a, bb[s].x, bb[s].y); }
      float r[4];
#pragma unroll
      for (int i = 0; i < 4; i++) r[i] = (e[0][i] + e[1][i]) + (e[2][i] + e[3][i]);
      if (tq < 2) st_async2(base + OFF_R4 + (8 * mt + g) * 176 + (10 * rk + 8 + tq) * 8, base + OFF_BAR + 8 * (XB + 5), tq ? r[1] : r[0], tq ? r[3] : r[2]);
    }
    return;
  }

  float* s_sm = (float*)(smem + OFF_SM);
  unsigned par, epoch;
  uint32_t rsb;
  {
    float* s_r4 = (float*)(smem + OFF_R4);
    asm volatile("barrier.cluster.arrive.relaxed.aligned;" ::: "memory");
    asm volatile("mapa.shared::cluster.u32 %0, %1, %2;" : "=r"(rsb) : "r"(sb), "r"(rk ^ 1));
    const float c0 = (arow & 1) ? bfhi(c0w) : bflo(c0w), c1 = (arow & 1) ? bfhi(c1w) : bflo(c1w);
    float acc[8] = {0, 0, 0, 0, 0, 0, 0, 0};
    fma8(acc, wm0, silu_bf(c0)); fma8(acc, wm1, silu_bf(c1));
    tred<4>(acc, lane, 8); tred<2>(acc, lane, 16);
    *(float2*)(s_r4 + warp * 64 + 8 * (lane & 7) + ((lane >> 1) & 4) + ((lane >> 3) & 2)) = make_float2(acc[0], acc[1]);
    nbar(1, 288);
    epoch = *(volatile unsigned*)(smem + OFF_MASK + 8);
    par = (epoch + 1) & 1;
    if (warp == 0) {
      float t = 0.f, ca = b < 16 ? 1.f : 0.f;
#pragma unroll
      for (int w = 0; w < 8; w++) { t += s_r4[w * 64 + lane]; ca += s_r4[w * 64 + 32 + lane]; }
      t += ca * s_sm[256 + lane];
      const float nb = __shfl_down_sync(~0u, t, 1);
      const uint32_t w0 = lane < 8 ? pack2t(t, nb, par) : pack2(t, nb);
      const uint32_t w1 = __shfl_down_sync(~0u, w0, 8), w2 = __shfl_down_sync(~0u, w0, 16), w3 = __shfl_down_sync(~0u, w0, 24);
      if (lane < 8 && !(lane & 1)) stx16(g_h + (b >> 5) * 512 + (b & 15) * 32 + (b & 16) + 2 * lane, make_uint4(w0, w1, w2, w3));
      __syncwarp();
      if (lane == 0) CNT_ADD(1);
    }
  }
  asm volatile("barrier.cluster.wait.acquire.aligned;" ::: "memory");
  {
    uint32_t a[4][4][4];
    mbar_wait(bar0 + 8 * (warp >> 1));
    const uint32_t ab = sb + OFF_WQ + (64 * warp + 8 * (lane >> 4) + (lane & 7)) * 128;
#pragma unroll
    for (int s = 0; s < 4; s++)
#pragma unroll
      for (int mt = 0; mt < 4; mt++) ldsm_t(a[s][mt], ab + s * 2048 + (((2 * mt + ((lane >> 3) & 1)) ^ (lane & 7)) << 4));
    uint4 v0, v1;
    const unsigned* ph = g_h + (g >> 1) * 512 + 64 * warp + 4 * (lane & 7);
    uint32_t off = OFF_B + warp * 272 + (32 * rk + 8 * tq + (lane & 4)) * 4;
    PIN(off); PINL(ph);
    mbar_wait(bar0 + 8 * XB);
    POLL { v0 = ldx16(ph); v1 = ldx16(ph + 32); RETRY(lop_x3(v0.x, v1.x, par)) }
    float d[4][4] = {};
#pragma unroll
    for (int mt = 0; mt < 4; mt++) {
      mma16(d[mt], a[0][mt], v0.x, v0.y); mma16(d[mt], a[1][mt], v0.z, v0.w);
      mma16(d[mt], a[2][mt], v1.x, v1.y); mma16(d[mt], a[3][mt], v1.z, v1.w);
    }
    float r[8];
#pragma unroll
    for (int mt = 0; mt < 4; mt++) { r[2 * mt] = d[mt][0] + d[mt][1]; r[2 * mt + 1] = d[mt][2] + d[mt][3]; }
    tred<4>(r, lane, 2); tred<2>(r, lane, 1);
    const float rc = __shfl_xor_sync(~0u, (lane & 4) ? r[0] : r[1], 4);
    const uint32_t wd = (lane & 4) ? pack2(rc, r[1]) : pack2(r[0], rc);
    const uint32_t w1 = __shfl_down_sync(~0u, wd, 8), w2 = __shfl_down_sync(~0u, wd, 16), w3 = __shfl_down_sync(~0u, wd, 24);
    asm volatile("{.reg .pred p; setp.lt.s32 p, %7, 8; @p st.shared.v4.b32 [%0], {%2,%3,%4,%5};\n"
                 "@p st.async.shared::cluster.mbarrier::complete_tx::bytes.v4.b32 [%1], {%2,%3,%4,%5}, [%6];}"
                 ::"r"(sb + off), "r"(rsb + off), "r"(wd), "r"(w1), "r"(w2), "r"(w3), "r"(rsb + OFF_BAR + 8 * QB), "r"(lane) : "memory");
    __syncwarp();
    arrive2(bar0 + 8 * QB, 0, lane == 0, false);
    arrive2(bar0 + 8 * (EB + 2), rsb + OFF_BAR + 8 * (EB + 2), lane == 0, lane == 0);
  }
  {
    uint32_t a[8][4];
    uint32_t a_bq = sb + OFF_B + (lane & 7) * 272 + (lane >> 3) * 16;
    unsigned* p_qa = g_qa + b * 64 + 8 * warp + 4 * lane;
    PIN(a_bq); PINL(p_qa);
    mbar_wait(bar0 + 8 * (FB_UK + (warp >> 2)));
    const uint32_t ab = sb + OFF_WUK + (warp >> 2) * 16384 + (16 * (warp & 3) + (lane & 15)) * 128;
#pragma unroll
    for (int s = 0; s < 8; s++) ldsm(a[s], ab + (s >> 2) * 8192 + (((2 * (s & 3) + (lane >> 4)) ^ (lane & 7)) << 4));
    mbar_wait(bar0 + 8 * QB);
    float d[4][4] = {};
#pragma unroll
    for (int y = 0; y < 4; y++) {
      uint32_t bq[4];
      ldsm(bq, a_bq + 64 * y);
      mma16(d[(2 * y) & 3], a[2 * y], bq[0], bq[1]); mma16(d[(2 * y + 1) & 3], a[2 * y + 1], bq[2], bq[3]);
    }
    float r[2] = {((d[0][0] + d[0][1]) + (d[1][0] + d[1][1])) + ((d[2][0] + d[2][1]) + (d[3][0] + d[3][1])),
                  ((d[0][2] + d[0][3]) + (d[1][2] + d[1][3])) + ((d[2][2] + d[2][3]) + (d[3][2] + d[3][3]))};
    tred<1>(r, lane, 1);
    r[0] += __shfl_xor_sync(~0u, r[0], 2);
    const float nb = __shfl_xor_sync(~0u, r[0], 4);
    const uint32_t w0 = lane < 8 ? pack2t(r[0], nb, par) : pack2(r[0], nb);
    const uint32_t w1 = __shfl_down_sync(~0u, w0, 8), w2 = __shfl_down_sync(~0u, w0, 16), w3 = __shfl_down_sync(~0u, w0, 24);
    if (lane < 2) stx16(p_qa, make_uint4(w0, w1, w2, w3));
    arrive2(bar0 + 8 * (EB + 4), rsb + OFF_BAR + 8 * (EB + 4), lane == 0, lane == 0);
  }
  {
    if (warp) nbar_arrive(3, 256); else { nbar(3, 256); if (lane == 0) CNT_ADD(2 + (b >> 6)); }
    asm volatile("setmaxnreg.inc.sync.aligned.u32 216;");
    const unsigned* pq = g_qa + rk * 4096 + tid * 4;
    uint32_t a_q = sb + OFF_Q + ((tid & 63) >> 3) * 2048 + (tid >> 6) * 128 + (((tid & 7) ^ (tid >> 6)) << 4);
    PINL(pq); PIN(a_q);
    mbar_wait(bar0 + 8 * (XB + 1));
    uint4 v[4];
    POLL {
#pragma unroll
      for (int k = 0; k < 4; k++) v[k] = ldx16(pq + 1024 * k);
      RETRY(lop_x3(v[0].x, v[1].x, par) | lop_x3(v[2].x, v[3].x, par))
    }
#pragma unroll
    for (int k = 0; k < 4; k++)
      asm volatile("st.shared.v4.b32 [%0], {%1,%2,%3,%4};" ::"r"((a_q + k * 512) ^ ((k & 1) << 6)), "r"(v[k].x), "r"(v[k].y), "r"(v[k].z), "r"(v[k].w) : "memory");
    if (warp >= 4) nbar_arrive(1, 256); else nbar(1, 256);
  }
  sb = __shfl_sync(~0u, sb, 0); bar0 = sb + OFF_BAR;
  if (warp < 4) {
    uint32_t qf[32][4];
#pragma unroll
    for (int s = 0; s < 32; s++) ldsm(qf[s], sb + OFF_Q + (s >> 2) * 2048 + (lane & 15) * 128 + (((2 * (s & 3) + (lane >> 4)) ^ (lane & 7)) << 4));
    float l0 = 0.f, l1 = 0.f, m0 = -1e30f, m1 = -1e30f;
    const float sc = 0.08838834764831845f * 1.4426950408889634f;
    const uint32_t kofs = (16 * warp + 8 * (lane >> 4) + (lane & 7)) * 128 + ((((lane >> 3) & 1) ^ (lane & 7)) << 4);
    uint32_t st = sb;
#pragma unroll 1
    for (int t = 0; t < 8; t++) {
      float sa[4][4] = {};
#pragma unroll
      for (int hf = 0; hf < 2; hf++) {
        const int n = 2 * t + hf;
        mbar_wait(bar0 + 8 * (FB_KV + n));
        uint32_t kf[16][4];
#pragma unroll
        for (int y = 0; y < 16; y++) ldsm(kf[y], st + (y >> 2) * 8192 + (kofs ^ ((y & 3) << 5)));
#pragma unroll
        for (int y = 0; y < 16; y++) {
          mma16(sa[(2 * y) & 3], qf[16 * hf + y], kf[y][0], kf[y][1]); mma16(sa[((2 * y) & 3) + 1], qf[16 * hf + y], kf[y][2], kf[y][3]);
        }
        __syncwarp();
        arrive2(bar0 + 8 * (EB + NSLOT + n), rsb + OFF_BAR + 8 * (EB + NSLOT + n), lane == 0 && n < 14, lane == 0 && n < 16 - NSLOT);
        if (hf == 0) arrive2(bar0 + 8 * EB, 0, lane == 0 && t == 0, false);
        st = st + SLOT == sb + NSLOT * SLOT ? sb : st + SLOT;
      }
#pragma unroll
      for (int i = 0; i < 4; i++) { sa[0][i] = (sa[0][i] + sa[2][i]) * sc; sa[1][i] = (sa[1][i] + sa[3][i]) * sc; }
      float cm[2] = {fmaxf(fmaxf(sa[0][0], sa[0][1]), fmaxf(sa[1][0], sa[1][1])), fmaxf(fmaxf(sa[0][2], sa[0][3]), fmaxf(sa[1][2], sa[1][3]))};
      tmax<1>(cm, lane, 1);
      cm[0] = fmaxf(cm[0], __shfl_xor_sync(~0u, cm[0], 2));
      float* pm = s_sm + (t & 1) * 64;
      if (tq < 2) pm[(g + 8 * tq) * 4 + warp] = cm[0];
      if (t >= 2) nbar(6 + (t & 1), 256); else nbar(3, 128);
      const float4 a0 = *(const float4*)(pm + g * 4), b0 = *(const float4*)(pm + g * 4 + 32);
      const float n0 = fmaxf(fmaxf(fmaxf(a0.x, a0.y), fmaxf(a0.z, a0.w)), m0), n1 = fmaxf(fmaxf(fmaxf(b0.x, b0.y), fmaxf(b0.z, b0.w)), m1);
      uint32_t pk[4];
#pragma unroll
      for (int i = 0; i < 2; i++) { pk[2 * i] = pack2(ex2(sa[i][0] - n0), ex2(sa[i][1] - n0)); pk[2 * i + 1] = pack2(ex2(sa[i][2] - n1), ex2(sa[i][3] - n1)); }
      *(uint4*)(smem + OFF_P + (t & 1) * 2048 + tid * 16) = make_uint4(pk[0], pk[1], pk[2], pk[3]);
      const float al0 = ex2(m0 - n0), al1 = ex2(m1 - n1);
      if (tid < 32 && tq == 0) *(float2*)(s_sm + 192 + (t & 1) * 16 + 2 * g) = make_float2(al0, al1);
      nbar_arrive(4 + (t & 1), 256);
      m0 = n0; m1 = n1;
      l0 = l0 * al0 + (bflo(pk[0]) + bfhi(pk[0])) + (bflo(pk[2]) + bfhi(pk[2]));
      l1 = l1 * al1 + (bflo(pk[1]) + bfhi(pk[1])) + (bflo(pk[3]) + bfhi(pk[3]));
    }
    float lr[2] = {l0, l1};
    tred<1>(lr, lane, 1);
    lr[0] += __shfl_xor_sync(~0u, lr[0], 2);
    if (tq < 2) s_sm[128 + (g + 8 * tq) * 4 + warp] = lr[0];
    nbar(3, 128);
    if (warp == 0 && tq < 2) {
      const float4 a0 = *(const float4*)(s_sm + 128 + (g + 8 * tq) * 4);
      stx8(g_ml + (16 * rk + g + 8 * tq) * 64 + pr, make_uint2(fbits(tq ? m1 : m0), fbits((a0.x + a0.y) + (a0.z + a0.w))));
    }
    if (warp == 0) { __syncwarp(); if (lane == 0) CNT_ADD(96 + 32 * rk); }
    nbar(2, 288);
    if (tid == 0) asm volatile("red.relaxed.gpu.global.xor.b64 [%0], %1;" ::"l"(scr->cnt + 32 + 32 * rk), "l"(1ull << pr) : "memory");
  } else {
    float o[16][4] = {};
    const uint32_t vofs = (warp & 1) * 16384 + (lane & 15) * 128 + (((lane >> 4) ^ (lane & 7)) << 4);
    const int hf = (warp >> 1) & 1;
    uint32_t st = sb + hf * SLOT;
    auto pv = [&](const int t, auto np) {
      constexpr int npre = decltype(np)::value;
      uint32_t vf[4][8][4];
      const int n = 2 * t + hf;
      mbar_wait(bar0 + 8 * (FB_KV + n));
#pragma unroll
      for (int s = 0; s < npre; s++)
#pragma unroll
        for (int y = 0; y < 8; y++) ldsm_t(vf[s][y], st + (y >> 2) * 8192 + s * 2048 + (vofs ^ ((y & 3) << 5)));
      nbar(4 + (t & 1), 256);
      const float2 al = *(const float2*)(s_sm + 192 + (t & 1) * 16 + 2 * g);
      uint4 pf[4];
#pragma unroll
      for (int s = 0; s < 4; s++) pf[s] = *(const uint4*)(smem + OFF_P + (t & 1) * 2048 + s * 512 + lane * 16);
      if (t < 6) nbar_arrive(6 + (t & 1), 256);
#pragma unroll
      for (int s = npre; s < 4; s++)
#pragma unroll
        for (int y = 0; y < 8; y++) ldsm_t(vf[s][y], st + (y >> 2) * 8192 + s * 2048 + (vofs ^ ((y & 3) << 5)));
#pragma unroll
      for (int nt = 0; nt < 16; nt++) { o[nt][0] *= al.x; o[nt][1] *= al.x; o[nt][2] *= al.y; o[nt][3] *= al.y; }
#pragma unroll
      for (int s = 0; s < 4; s++) {
        const uint32_t pa[4] = {pf[s].x, pf[s].y, pf[s].z, pf[s].w};
#pragma unroll
        for (int y = 0; y < 8; y++) { mma16(o[2 * y], pa, vf[s][y][0], vf[s][y][1]); mma16(o[2 * y + 1], pa, vf[s][y][2], vf[s][y][3]); }
      }
      __syncwarp();
      arrive2(bar0 + 8 * (EB + NSLOT + n), rsb + OFF_BAR + 8 * (EB + NSLOT + n), lane == 0 && n < 14, lane == 0 && n < 16 - NSLOT);
      st = st + 2 * SLOT >= sb + NSLOT * SLOT ? st - (NSLOT - 2) * SLOT : st + 2 * SLOT;
    };
#pragma unroll 1
    for (int t = 0; t < 7; t++) pv(t, IC<NPRE0>());
    pv(7, IC<NPRE1>());
    uint4* po = g_xo + ((size_t)((16 * rk + (g & 6)) * 4 + warp - 4) * 64 + pr) * RS + (lane & 7);
    const bool odd = lane & 4;
#pragma unroll
    for (int e = 0; e < 2; e++)
#pragma unroll
      for (int j2 = 0; j2 < 2; j2++) {
        uint32_t c0[4], c1[4];
#pragma unroll
        for (int i = 0; i < 4; i++) {
          c0[i] = i ? pack2(o[8 * j2 + i][2 * e], o[8 * j2 + i][2 * e + 1]) : pack2t(o[8 * j2][2 * e], o[8 * j2][2 * e + 1], par);
          c1[i] = i ? pack2(o[8 * j2 + 4 + i][2 * e], o[8 * j2 + 4 + i][2 * e + 1]) : pack2t(o[8 * j2 + 4][2 * e], o[8 * j2 + 4][2 * e + 1], par);
          const uint32_t r = __shfl_xor_sync(~0u, odd ? c0[i] : c1[i], 4);
          if (odd) c0[i] = r; else c1[i] = r;
        }
        stx16(po + e * 8 * 4 * 64 * RS + 8 * j2, make_uint4(c0[0], c0[1], c0[2], c0[3]));
        stx16(po + (e * 8 + 1) * 4 * 64 * RS + 8 * j2, make_uint4(c1[0], c1[1], c1[2], c1[3]));
      }
    nbar_arrive(2, 288);
  }
  tail(smem, scr, x, out, par, epoch, warp);
}

static void launch(void* const* d_in, void* d_out) {
  static TMaps tms;
  static bool init = false;
  static void* scr = nullptr;
  if (!init) {
    void* fn = nullptr; cudaDriverEntryPointQueryResult qr;
    cudaGetDriverEntryPoint("cuTensorMapEncodeTiled", &fn, cudaEnableDefault, &qr);
    EncFn f = (EncFn)fn;
    const CUtensorMapSwizzle S32 = CU_TENSOR_MAP_SWIZZLE_32B, S64 = CU_TENSOR_MAP_SWIZZLE_64B, S128 = CU_TENSOR_MAP_SWIZZLE_128B;
    const CUtensorMapL2promotion P128 = CU_TENSOR_MAP_L2_PROMOTION_L2_128B, P256 = CU_TENSOR_MAP_L2_PROMOTION_L2_256B;
    enc3d(f, &tms.m[0], d_in[2], 64, 512, 64, 8192, 128, 64, 128, 1, S128, P128);
    enc3d(f, &tms.m[1], d_in[3], 64, 512, 64, 8192, 128, 64, 64, 2, S128, P256);
    enc3d(f, &tms.m[2], d_in[1], 64, SK, 8, 1024, 128, 64, 64, 2, S128, P256);
    enc3d(f, &tms.m[3], d_in[11], 3072, 256, 2, 6144, 256 * 6144, 16, 256, 2, S32, P128);
    enc3d(f, &tms.m[4], d_in[4], 64, 512, 64, 8192, 128, 64, 64, 2, S128, P256);
    enc3d(f, &tms.m[5], d_in[5], 512, 128, 32, 1024, 128 * 1024, 64, 128, 1, S128, P128);
    enc3d(f, &tms.m[6], d_in[7], 1792, 256, 2, 3584, 256 * 3584, 32, 256, 1, S64, P128);
    enc3d(f, &tms.m[7], d_in[8], 1792, 256, 2, 3584, 256 * 3584, 32, 256, 1, S64, P128);
    enc3d(f, &tms.m[8], d_in[9], 64, 1792, 8, 1024, 128, 64, 16, 8, S128, P256);
    cudaFuncSetAttribute(fused_kernel, cudaFuncAttributeMaxDynamicSharedMemorySize, SMEM_BYTES);
    cudaGetSymbolAddress(&scr, g_scr);
    init = true;
  }
  fused_kernel<<<NCTA, 384, SMEM_BYTES>>>((const bf16*)d_in[0], (const bf16*)d_in[10], (const bf16*)d_in[11], (bf16*)d_out, (Scratch*)scr, tms);
}

}

extern "C" void kernel_launch(void* const* d_in, const int* in_sizes, int n_in, void* d_out, int out_size) {
  static int big = -1;
  if (big < 0) big = v9::fits();
  if (big) v9::launch(d_in, d_out); else v8::launch(d_in, d_out);
}
```

```cpp
#include <cuda_runtime.h>
#include <cuda_bf16.h>
#include <cuda.h>
#include <stdint.h>
#include <stdio.h>
#include <stdlib.h>

typedef CUresult (*EncFn)(CUtensorMap*, CUtensorMapDataType, cuuint32_t, void*, const cuuint64_t*, const cuuint64_t*,
                          const cuuint32_t*, const cuuint32_t*, CUtensorMapInterleave, CUtensorMapSwizzle,
                          CUtensorMapL2promotion, CUtensorMapFloatOOBfill);

static void enc3d(EncFn fn, CUtensorMap* tm, void* p, uint64_t d0, uint64_t d1, uint64_t d2, uint64_t s1, uint64_t s2, uint32_t b0,
                  uint32_t b1, uint32_t b2, CUtensorMapSwizzle sw, CUtensorMapL2promotion pr) {
  cuuint64_t gd[3] = {d0, d1, d2}, gs[2] = {s1, s2};
  cuuint32_t bx[3] = {b0, b1, b2}, es[3] = {1, 1, 1};
  fn(tm, CU_TENSOR_MAP_DATA_TYPE_BFLOAT16, 3, p, gd, gs, bx, es, CU_TENSOR_MAP_INTERLEAVE_NONE, sw, pr, CU_TENSOR_MAP_FLOAT_OOB_FILL_NONE);
}

namespace v9 {
typedef __nv_bfloat16 bf16;
#define SK 32768
#define SPIN_MAX (1 << 20)
template <int N> struct IC { static constexpr int value = N; };

__device__ __forceinline__ uint32_t s2u(const void* p) { return (uint32_t)__cvta_generic_to_shared(p); }
__device__ __forceinline__ float bflo(uint32_t u) { return __uint_as_float(u << 16); }
__device__ __forceinline__ float bfhi(uint32_t u) { return __uint_as_float(u & 0xffff0000u); }
__device__ __forceinline__ float u2f(uint32_t u) { return __uint_as_float(u); }
__device__ __forceinline__ void fma8(float* acc, uint4 v, float s) {
  acc[0] += s * bflo(v.x); acc[1] += s * bfhi(v.x); acc[2] += s * bflo(v.y); acc[3] += s * bfhi(v.y);
  acc[4] += s * bflo(v.z); acc[5] += s * bfhi(v.z); acc[6] += s * bflo(v.w); acc[7] += s * bfhi(v.w);
}
__device__ __forceinline__ uint32_t pack2(float a, float b) {
  __nv_bfloat162 p = __floats2bfloat162_rn(a, b); return *(uint32_t*)&p;
}
__device__ __forceinline__ float bfr(float v) { return bfhi(pack2(v, v)); }
__device__ __forceinline__ float silu_bf(float c) { return bfr(__fdividef(c, 1.f + __expf(-c))); }
#define fbits(v) ((__float_as_uint(v) & ~1u) | par)
__device__ __forceinline__ uint32_t pack2t(float a, float b, unsigned par) {
  const uint32_t ua = ((__float_as_uint(a) + ((par ^ 1) << 16)) & 0xFFFE0000u) | (par << 16);
  return __byte_perm(ua, pack2(b, b), 0x7632);
}
__device__ __forceinline__ void nbar(int id, int n) { asm volatile("bar.sync %0, %1;" ::"r"(id), "r"(n) : "memory"); }
__device__ __forceinline__ void nbar_arrive(int id, int n) { asm volatile("bar.arrive %0, %1;" ::"r"(id), "r"(n) : "memory"); }
__device__ __forceinline__ uint4 ldc16(const void* p) {
  uint4 v; asm volatile("ld.relaxed.cta.global.v4.u32 {%0,%1,%2,%3}, [%4];" : "=r"(v.x), "=r"(v.y), "=r"(v.z), "=r"(v.w) : "l"(p) : "memory"); return v;
}
__device__ __forceinline__ unsigned ldc4(const void* p) {
  unsigned v; asm volatile("ld.relaxed.cta.global.u32 %0, [%1];" : "=r"(v) : "l"(p) : "memory"); return v;
}
__device__ __forceinline__ uint4 ldx16(const void* p) {
  uint4 v; asm volatile("ld.relaxed.gpu.global.v4.u32 {%0,%1,%2,%3}, [%4];" : "=r"(v.x), "=r"(v.y), "=r"(v.z), "=r"(v.w) : "l"(p) : "memory"); return v;
}
__device__ __forceinline__ unsigned ldx4(const void* p) {
  unsigned v; asm volatile("ld.relaxed.gpu.global.u32 %0, [%1];" : "=r"(v) : "l"(p) : "memory"); return v;
}
__device__ __forceinline__ unsigned long long ldx64(const void* p) {
  unsigned long long v; asm volatile("ld.relaxed.gpu.global.u64 %0, [%1];" : "=l"(v) : "l"(p) : "memory"); return v;
}
__device__ __forceinline__ void stx16(void* p, uint4 v) {
  asm volatile("st.relaxed.gpu.global.v4.u32 [%0], {%1,%2,%3,%4};" ::"l"(p), "r"(v.x), "r"(v.y), "r"(v.z), "r"(v.w) : "memory");
}
__device__ __forceinline__ void stx8(void* p, uint2 v) { asm volatile("st.relaxed.gpu.global.v2.u32 [%0], {%1,%2};" ::"l"(p), "r"(v.x), "r"(v.y) : "memory"); }
__device__ __forceinline__ void stx4(void* p, unsigned v) { asm volatile("st.relaxed.gpu.global.u32 [%0], %1;" ::"l"(p), "r"(v) : "memory"); }
__device__ __forceinline__ void pub4(void* p, unsigned v) { asm volatile("red.relaxed.gpu.global.xor.b32 [%0], %1;" ::"l"(p), "r"(v) : "memory"); }
__device__ __forceinline__ void pub8(void* p, unsigned lo, unsigned hi) {
  asm volatile("{.reg .b64 t; mov.b64 t, {%1, %2}; red.relaxed.gpu.global.xor.b64 [%0], t;}" ::"l"(p), "r"(lo), "r"(hi) : "memory");
}
__device__ __forceinline__ unsigned lop_x3(unsigned a, unsigned b, unsigned c) {
  unsigned d; asm("lop3.b32 %0, %1, %2, %3, 0x7E;" : "=r"(d) : "r"(a), "r"(b), "r"(c)); return d; }
__device__ __forceinline__ unsigned or3(unsigned a, unsigned b, unsigned c) {
  unsigned d; asm("lop3.b32 %0, %1, %2, %3, 0xFE;" : "=r"(d) : "r"(a), "r"(b), "r"(c)); return d; }
__device__ __forceinline__ unsigned and3(unsigned a, unsigned b, unsigned c) {
  unsigned d; asm("lop3.b32 %0, %1, %2, %3, 0x80;" : "=r"(d) : "r"(a), "r"(b), "r"(c)); return d; }
__device__ __forceinline__ unsigned dep16(const uint32_t* f) {
  unsigned d = 0;
#pragma unroll
  for (int i = 0; i < 8; i++) d = or3(d, f[8 * i], f[8 * i + 4]);
  return d;
}
__device__ __forceinline__ uint2 ldx8(const void* p) {
  uint2 v; asm volatile("{.reg .b64 t; ld.relaxed.gpu.global.b64 t, [%2]; mov.b64 {%0, %1}, t;}" : "=r"(v.x), "=r"(v.y) : "l"(p) : "memory"); return v;
}
__device__ __forceinline__ float lds4(uint32_t a) { float v; asm volatile("ld.shared.f32 %0, [%1];" : "=f"(v) : "r"(a) : "memory"); return v; }
__device__ __forceinline__ float shx(float v, int m) {
  float r; asm volatile("shfl.sync.bfly.b32 %0, %1, %2, 0x1f, 0xffffffff;" : "=f"(r) : "f"(v), "r"(m)); return r;
}
__device__ __forceinline__ uint32_t mbar_test(uint32_t bar, uint32_t ph) {
  uint32_t ok;
  asm volatile("{.reg .pred p; mbarrier.test_wait.parity.shared::cta.b64 p, [%1], %2; vote.sync.all.pred p, p, 0xffffffff; selp.u32 %0, 1, 0, p;}"
               : "=r"(ok) : "r"(bar), "r"(ph) : "memory");
  return ok;
}
#define X16(v) (lop_x3(v.x, v.y, par) | lop_x3(v.z, v.w, par))
#define RETRY(bad) if (!__any_sync(~0u, (bad) & 1) || ++it_ >= SPIN_MAX) break;
#define POLL _Pragma("unroll 1") for (int it_ = 0;;)
__device__ __forceinline__ void mbar_wait(uint32_t bar, uint32_t ph = 0) {
  asm volatile("{.reg .pred p; .reg .u32 n; mov.u32 n, 0;\n"
               "W%=: mbarrier.try_wait.parity.shared::cta.b64 p, [%0], %1; add.u32 n, n, 1; setp.lt.and.u32 p, n, 0x100000, !p; @p bra W%=;}"
               ::"r"(bar), "r"(ph) : "memory");
}
__device__ __forceinline__ float ex2(float v) { float r; asm("ex2.approx.ftz.f32 %0, %1;" : "=f"(r) : "f"(v)); return r; }
__device__ __forceinline__ float rcp(float v) { float r; asm("rcp.approx.ftz.f32 %0, %1;" : "=f"(r) : "f"(v)); return r; }
__device__ __forceinline__ void mma16(float* d, const uint32_t* a, uint32_t b0, uint32_t b1) {
  asm volatile("mma.sync.aligned.m16n8k16.row.col.f32.bf16.bf16.f32 {%0,%1,%2,%3}, {%4,%5,%6,%7}, {%8,%9}, {%0,%1,%2,%3};"
               : "+f"(d[0]), "+f"(d[1]), "+f"(d[2]), "+f"(d[3]) : "r"(a[0]), "r"(a[1]), "r"(a[2]), "r"(a[3]), "r"(b0), "r"(b1));
}
__device__ __forceinline__ void mma16c(float* d, const uint32_t* a, uint32_t b0, uint32_t b1, const float* c) {
  asm volatile("mma.sync.aligned.m16n8k16.row.col.f32.bf16.bf16.f32 {%0,%1,%2,%3}, {%4,%5,%6,%7}, {%8,%9}, {%10,%11,%12,%13};"
               : "=f"(d[0]), "=f"(d[1]), "=f"(d[2]), "=f"(d[3])
               : "r"(a[0]), "r"(a[1]), "r"(a[2]), "r"(a[3]), "r"(b0), "r"(b1), "f"(c[0]), "f"(c[1]), "f"(c[2]), "f"(c[3]));
}
__device__ __forceinline__ float4 lds16(uint32_t a) {
  float4 v; asm volatile("ld.shared.v4.f32 {%0,%1,%2,%3}, [%4];" : "=f"(v.x), "=f"(v.y), "=f"(v.z), "=f"(v.w) : "r"(a) : "memory"); return v;
}
__device__ __forceinline__ uint4 ldsv16(uint32_t a) {
  uint4 v; asm volatile("ld.relaxed.cluster.shared.v4.u32 {%0,%1,%2,%3}, [%4];" : "=r"(v.x), "=r"(v.y), "=r"(v.z), "=r"(v.w) : "r"(a) : "memory"); return v;
}
__device__ __forceinline__ void sts4(uint32_t a, float v) { asm volatile("st.shared.f32 [%0], %1;" ::"r"(a), "f"(v) : "memory"); }
__device__ __forceinline__ void sts16(uint32_t a, uint4 v) {
  asm volatile("st.shared.v4.b32 [%0], {%1,%2,%3,%4};" ::"r"(a), "r"(v.x), "r"(v.y), "r"(v.z), "r"(v.w) : "memory");
}
__device__ __forceinline__ void ldsm_t(uint32_t* r, uint32_t a) {
  asm volatile("ldmatrix.sync.aligned.m8n8.x4.trans.shared.b16 {%0,%1,%2,%3}, [%4];" : "=r"(r[0]), "=r"(r[1]), "=r"(r[2]), "=r"(r[3]) : "r"(a) : "memory");
}
__device__ __forceinline__ void ldsm(uint32_t* r, uint32_t a) {
  asm volatile("ldmatrix.sync.aligned.m8n8.x4.shared.b16 {%0,%1,%2,%3}, [%4];" : "=r"(r[0]), "=r"(r[1]), "=r"(r[2]), "=r"(r[3]) : "r"(a) : "memory");
}
__device__ __forceinline__ uint32_t mapa(uint32_t a, uint32_t r) {
  uint32_t v; asm volatile("mapa.shared::cluster.u32 %0, %1, %2;" : "=r"(v) : "r"(a), "r"(r)); return v;
}
__device__ __forceinline__ unsigned long long mapg(uint32_t a, uint32_t r) {
  unsigned long long v;
  asm volatile("{.reg .u32 t; .reg .u64 u; mapa.shared::cluster.u32 t, %1, %2; cvt.u64.u32 u, t; cvta.shared::cluster.u64 %0, u;}" : "=l"(v) : "r"(a), "r"(r));
  return v;
}
template <int N>
__device__ __forceinline__ void tred(float* a, int lane, int m) {
  const bool hi = lane & m;
#pragma unroll
  for (int i = 0; i < N; i++) {
    float send = hi ? a[i] : a[i + N], keep = hi ? a[i + N] : a[i];
    a[i] = keep + __shfl_xor_sync(~0u, send, m);
  }
}
template <int N>
__device__ __forceinline__ void tmax(float* a, int lane, int m) {
  const bool hi = lane & m;
#pragma unroll
  for (int i = 0; i < N; i++) {
    float send = hi ? a[i] : a[i + N], keep = hi ? a[i + N] : a[i];
    a[i] = fmaxf(keep, __shfl_xor_sync(~0u, send, m));
  }
}
__device__ __forceinline__ void arrive_n(uint32_t bar, bool on, int cnt) {
  asm volatile("{.reg .pred p; setp.ne.s32 p, %1, 0; @p mbarrier.arrive.shared::cta.b64 _, [%0], %2;}" ::"r"(bar), "r"((int)on), "r"(cnt) : "memory");
}
__device__ __forceinline__ unsigned long long stream_policy() {
  unsigned long long p;
  asm volatile("createpolicy.fractional.L2::evict_first.b64 %0, 1.0;" : "=l"(p));
  return p;
}
__device__ __forceinline__ void tma3d(uint32_t dst, const CUtensorMap* tm, uint32_t bar, int c0, int c1, int c2) {
  asm volatile("cp.async.bulk.tensor.3d.shared::cluster.global.mbarrier::complete_tx::bytes.L2::cache_hint [%0], [%1, {%3, %4, %5}], [%2], %6;"
               ::"r"(dst), "l"(tm), "r"(bar), "r"(c0), "r"(c1), "r"(c2), "l"(stream_policy()) : "memory");
}
__device__ __forceinline__ void spin_until(unsigned t) { while ((int)((unsigned)clock() - t) < 0) {} }
__device__ __forceinline__ void wait_until(unsigned t) {
  unsigned now;
  do { asm volatile("mov.u32 %0, %%globaltimer_lo;" : "=r"(now)); } while ((int)(now - t) < 0);
}
__device__ __forceinline__ void sleep_until(unsigned t) {
  unsigned now;
#pragma unroll 1
  do {
    __nanosleep(200);
    asm volatile("mov.u32 %0, %%globaltimer_lo;" : "=r"(now));
  } while ((int)(now - t) < 0);
}
#define PIN(x) asm volatile("" : "+r"(x))
#define PINL(x) asm volatile("" : "+l"(x))
#define BAR_ARRIVE(i) asm volatile("mbarrier.arrive.shared::cta.b64 _, [%0];" ::"r"(bar0 + 8 * (i)) : "memory")
#define CNT_ADD(c) asm volatile("red.relaxed.gpu.global.inc.u32 [%0], 0xffffffff;" ::"l"(scr->cnt + (c)) : "memory")
#define BAR_INIT(i, cnt) asm volatile("mbarrier.init.shared::cta.b64 [%0], %1;" ::"r"(bar0 + 8 * (i)), "r"(cnt) : "memory")
#define BAR_ARM(i, bytes) asm volatile("mbarrier.arrive.expect_tx.shared::cta.b64 _, [%0], %1;" ::"r"(bar0 + 8 * (i)), "r"(bytes) : "memory")
struct TMaps { CUtensorMap m[9]; };

#define NCTA9 120
#define TAU 20.f
#define NSL 100
#define NPE 2
#define WTEST 600
#define QN 4
#define NPO 3
#define VDLY 150
#define O_Q 131072
#define O_LZ 163840
#define O_CTX 196608
#define O_HZ 198656
#define O_HW 200704
#define O_X 201728
#define O_P 218112
#define O_B 222208
#define O_R 224512
#define O_SILU 228608
#define O_SM 229632
#define O_BAR 231424
#define O_EP (O_BAR + 256)
#define O_DBG (O_EP + 16)
#define SMEM9 (O_DBG + 144)
#define B_FULL 0
#define B_FM 8
#define B_EMPTY 10
#define B_EM 18
#define B_LZ 18
#define B_Q2 19
#define B_H 20
#define B_QF 21
#define B_TAB 22
#define B_W 23
#define B_ST 24
#define B_HZ 25
#define B_WZ 26
#define B_G2 28
#define B_G 27
enum { T_WQ, T_WUK, T_KV, T_MOD, T_UV, T_WO, T_GU, T_DN = 8 };
#define NBIG 40
struct Sched { unsigned zero, dth; uint2 r[3][8]; unsigned nr[3], nt[3], dt, t4, d4, d6; };

struct __align__(128) Scratch {
  unsigned cnt[8 * 32];
  uint2 rec[32 * 4 * 8 * 64];
  uint2 hdr[32 * 16];
  unsigned h[8 * 256];
  uint4 qa[2048];
  unsigned xao[8 * 512];
  unsigned xm[2048];
};
__device__ Scratch g_scr;
#define SMEM_BASE 1024u
#define DSC ((SMEM_BASE >> 4) | (1u << 16))
#define HI128 (64u | (1u << 30))
#define HI64 (32u | (2u << 30))
template <int TA, int TB, unsigned HIA, unsigned HIB>
__device__ __forceinline__ void wgmma32(float* d, uint32_t da, uint32_t db, int acc) {
  asm volatile("{.reg .pred p; .reg .b64 da, db; setp.ne.b32 p, %18, 0; mov.b64 da, {%16, %21}; mov.b64 db, {%17, %22};\n"
               "wgmma.mma_async.sync.aligned.m64n32k16.f32.bf16.bf16 "
               "{%0,%1,%2,%3,%4,%5,%6,%7,%8,%9,%10,%11,%12,%13,%14,%15}, da, db, p, 1, 1, %19, %20;}"
               : "+f"(d[0]), "+f"(d[1]), "+f"(d[2]), "+f"(d[3]), "+f"(d[4]), "+f"(d[5]), "+f"(d[6]), "+f"(d[7]),
                 "+f"(d[8]), "+f"(d[9]), "+f"(d[10]), "+f"(d[11]), "+f"(d[12]), "+f"(d[13]), "+f"(d[14]), "+f"(d[15])
               : "r"(da), "r"(db), "r"(acc), "n"(TA), "n"(TB), "n"(HIA), "n"(HIB));
}
__device__ __forceinline__ void wgmma32r(float* d, const uint32_t* a, uint32_t db) {
  asm volatile("{.reg .b64 db; mov.b64 db, {%20, %21};\n"
               "wgmma.mma_async.sync.aligned.m64n32k16.f32.bf16.bf16 "
               "{%0,%1,%2,%3,%4,%5,%6,%7,%8,%9,%10,%11,%12,%13,%14,%15}, {%16,%17,%18,%19}, db, 1, 1, 1, 1;}"
               : "+f"(d[0]), "+f"(d[1]), "+f"(d[2]), "+f"(d[3]), "+f"(d[4]), "+f"(d[5]), "+f"(d[6]), "+f"(d[7]),
                 "+f"(d[8]), "+f"(d[9]), "+f"(d[10]), "+f"(d[11]), "+f"(d[12]), "+f"(d[13]), "+f"(d[14]), "+f"(d[15])
               : "r"(a[0]), "r"(a[1]), "r"(a[2]), "r"(a[3]), "r"(db), "n"(HI64));
}
template <int N> __device__ __forceinline__ void wg_wait(float* a) {
  asm volatile("wgmma.wait_group.sync.aligned %16;"
               : "+f"(a[0]), "+f"(a[1]), "+f"(a[2]), "+f"(a[3]), "+f"(a[4]), "+f"(a[5]), "+f"(a[6]), "+f"(a[7]), "+f"(a[8]), "+f"(a[9]), "+f"(a[10]),
                 "+f"(a[11]), "+f"(a[12]), "+f"(a[13]), "+f"(a[14]), "+f"(a[15]) : "n"(N) : "memory");
}
__device__ __forceinline__ float sum8(uint32_t a) {
  const float4 p = lds16(a), q = lds16(a + 1024);
  return ((p.x + p.y) + (p.z + p.w)) + ((q.x + q.y) + (q.z + q.w));
}
__device__ __forceinline__ int posof(int c) { return (c & ~14) + 2 * (c & 6) + ((c >> 2) & 2); }

__global__ void __cluster_dims__(8, 1, 1) __launch_bounds__(384, 1)
fused_kernel(const bf16* __restrict__ x, const bf16* __restrict__ cvec, const bf16* __restrict__ w_mod, bf16* __restrict__ out,
             Scratch* __restrict__ scr, const __grid_constant__ Sched sch, const __grid_constant__ TMaps tms) {
  extern __shared__ __align__(1024) unsigned char smem[];
  const int tid = threadIdx.x, warp = __shfl_sync(~0u, tid >> 5, 0), lane = tid & 31;
  const int b = blockIdx.x, cl = b >> 3, rn = b & 7, rk = b & 1, hd = b >> 1, f = b - 64;
  const bool isA = b < 64;
  uint32_t sb = s2u(smem), bar0 = sb + O_BAR;
  unsigned gt_start;
  asm volatile("mov.u32 %0, %%globaltimer_lo;" : "=r"(gt_start));
  const int g = lane >> 2, tq = lane & 3;
  const int arow = 64 * rn + ((tid & 255) >> 4);
  uint4 wm[4];
  uint32_t cw, xw;
  if (warp < 8 && isA) {
    const bf16* wa = w_mod + (size_t)arow * 3072 + (lane & 8) * 64 + 64 * cl + 8 * (lane & 7);
#pragma unroll
    for (int i = 0; i < 4; i++) wm[i] = ldx16(wa + i * 16 * 3072);
    cw = ldc4(cvec + (arow & ~1) + 16 * tq);
    if (warp < 2) xw = ldc4(x + 64 * cl + (tid & 62));
  }
  if (warp == 11) {
    if (lane == 0) {
#pragma unroll
      for (int i = 0; i < B_EMPTY; i++) BAR_INIT(i, 1);
    }
    __syncwarp();
    asm volatile("fence.mbarrier_init.release.cluster;" ::: "memory");
    asm volatile("barrier.cluster.arrive.relaxed.aligned;" ::: "memory");
    if (isA) {
#pragma unroll 1
      for (int i = 0; i < 8; i++) {
        if (i >= 6) mbar_wait(bar0 + 8 * (i - 6));
        wait_until(gt_start + ((64 * i + b) * sch.dth >> 8));
        if (lane == 0) {
          BAR_ARM(i, 16384);
          tma3d(sb + i * 16384, &tms.m[i >> 2], bar0 + 8 * i, 0, i < 4 ? 128 * i : 256 * rk + 64 * (i - 4), i < 4 ? b : b & ~1);
        }
        __syncwarp();
      }
    }
  }
  if (warp == 10) {
    const unsigned ep = ldc4(&scr->cnt[0]);
    if (isA) {
      const uint4 xa = ldc16(x + 16 * lane), xb = ldc16(x + 16 * lane + 8);
      float xv[16] = {bflo(xa.x), bfhi(xa.x), bflo(xa.y), bfhi(xa.y), bflo(xa.z), bfhi(xa.z), bflo(xa.w), bfhi(xa.w),
                      bflo(xb.x), bfhi(xb.x), bflo(xb.y), bfhi(xb.y), bflo(xb.z), bfhi(xb.z), bflo(xb.w), bfhi(xb.w)};
      const float x0 = __shfl_sync(~0u, xv[0], 0);
      float s = 0, q = 0;
#pragma unroll
      for (int i = 0; i < 16; i++) { xv[i] -= x0; s += xv[i]; q += xv[i] * xv[i]; }
#pragma unroll
      for (int o = 16; o; o >>= 1) { s += __shfl_xor_sync(~0u, s, o); q += __shfl_xor_sync(~0u, q, o); }
      s *= 1.f / 512.f;
      float rstd;
      asm("rsqrt.approx.ftz.f32 %0, %1;" : "=f"(rstd) : "f"(fmaxf(q * (1.f / 512.f) - s * s, 0.f) + 1e-5f));
      *(float2*)(smem + O_SM + 1024) = make_float2(s + x0, rstd);
    }
    if (lane == 0) *(volatile unsigned*)(smem + O_EP) = ep;
    nbar_arrive(1, 288);
  }
  const int cls = isA ? (b >= NBIG) : 2, v0 = isA ? 2 : 0;
  if (warp >= 8) {
    asm volatile("setmaxnreg.dec.sync.aligned.u32 72;");
    if (warp == 8) {
      if (lane < 8) asm volatile("prefetch.tensormap [%0];" ::"l"(&tms.m[lane + 1]) : "memory");
      if ((sb & 0xFFFFFF) != SMEM_BASE) __trap();
    } else if (warp == 9) {
      if (lane == 0) {
#pragma unroll
        for (int i = B_EMPTY; i < B_EM; i++) BAR_INIT(i, 8);
        BAR_INIT(B_LZ, 8); BAR_INIT(B_Q2, 9); BAR_ARM(B_Q2, 1024);
        BAR_INIT(B_H, 1); BAR_INIT(B_QF, 1); BAR_ARM(B_QF, 32768);
        BAR_INIT(B_TAB, 1); BAR_INIT(B_W, 1); BAR_INIT(B_ST, 8); BAR_INIT(B_WZ, 1); BAR_INIT(B_G, 1); BAR_INIT(B_G2, 1);
      }

    }
    if (warp != 11) {
      __syncwarp();
      asm volatile("fence.mbarrier_init.release.cluster;" ::: "memory");
      __threadfence_block();
      asm volatile("barrier.cluster.arrive.relaxed.aligned;" ::: "memory");
    }
    asm volatile("barrier.cluster.wait.acquire.aligned;" ::: "memory");
    if (warp == 8) {
      const int nr = sch.nr[cls], vl = v0 + sch.nt[cls] - 1;
      unsigned long long hist = 0;
      int v = v0;
#pragma unroll 1
      for (int rd = 0; rd < nr; rd++) {
        const uint2 e = sch.r[cls][rd];
        const int type = e.y & 15, win = (e.y >> 4) & 15, pos = b + 64 - (int)((e.y >> 8) & 255), tile = e.y >> 16;
        const bool mod = type == T_MOD;
        const int ni = mod ? 1 : type == T_DN ? 2 : 4;
        unsigned t = gt_start + (e.x & 0xffff) + (pos * sch.dt >> 8);
        const int c0 = mod ? 1024 + 32 * b : type == T_WO || type == T_DN ? 64 * rn : type == T_GU ? 32 * f : 0;
        int c1 = type == T_KV ? 64 * (tile + pos) : 0;
        int c2 = mod ? tile : type == T_WO ? 4 * cl : type == T_DN ? 2 * cl - 16 : type == T_UV ? b : 0;
        const int i1 = type == T_UV ? 128 : 0;
#pragma unroll 1
        for (int j = 0; j < ni; j++) {
          const int slot = mod ? B_FM + tile : (v & 1) * 4 + j;
          if (mod ? tile : v >= 2) mbar_wait(bar0 + 8 * (B_EMPTY + (mod ? (vl & 1) * 4 : slot)), mod ? (vl >> 1) & 1 : ((v >> 1) - 1) & 1);
          const int hw = (int)(hist >> (6 * (win - 1))) & 63;
          if (hw) mbar_wait(bar0 + 8 * (hw & 15), (hw >> 4) & 1);
          wait_until(t);
          if (lane == 0) {
            BAR_ARM(slot, 16384);
            tma3d(sb + (mod ? (tile ? O_Q : O_X) : slot * 16384), &tms.m[type == T_GU ? type + (j & 1) : type], bar0 + 8 * slot, c0, c1, c2);
          }
          __syncwarp();
          hist = hist << 6 | (32 | (mod ? 0 : (v & 2) << 3) | slot);
          t += e.x >> 16; c1 += i1;
          c2 += type == T_KV ? 2 : type == T_WO || type == T_DN ? 1 : type == T_GU ? j & 1 : 0;
        }
        v += !mod;
      }
      return;
    }
    const unsigned epoch = *(volatile unsigned*)(smem + O_EP), par = (epoch + 1) & 1;
    if (warp == 10) {
      if (isA) {
        for (int it = 0; ldx4(scr->cnt + 1) != (epoch + 1) * 128 && it < SPIN_MAX; it++) {}
        if (lane == 0) BAR_ARRIVE(B_H);
      } else mbar_wait(bar0);
      if (!(rn & (QN - 1))) {
        for (int it = 0; ldx4(scr->cnt + 32 + 32 * (rn >> 2)) != (epoch + 1) * 32 && it < SPIN_MAX; it++) {}
        if (lane == 0)
          asm volatile("cp.async.bulk.shared::cluster.global.mbarrier::complete_tx::bytes.multicast::cluster [%0], [%1], %4, [%2], %3;"
                       ::"r"(sb + O_Q + rn * 4096), "l"(scr->qa + rn * 256), "r"(bar0 + 8 * B_QF), "h"((unsigned short)0xff), "n"(4096 * QN) : "memory");
      }
      const unsigned dl = isA ? sch.d4 : sch.d6;
      unsigned tw = gt_start + sch.t4;
      if (!isA) {
        const int nt = sch.nt[2];
#pragma unroll 1
        for (int t = 0; t < nt; t++) mbar_wait(bar0 + 8 * B_EMPTY + (t & 1) * 32, (t >> 1) & 1);
        unsigned long long now;
        asm volatile("mov.u64 %0, %%globaltimer;" : "=l"(now));
        if (lane == 0) { asm volatile("red.relaxed.gpu.global.max.u64 [%0], %1;" ::"l"(scr->cnt + 130), "l"(now) : "memory"); CNT_ADD(128); }
        tw = (unsigned)now + 1700;
      }
      sleep_until(tw);
      uint4 an;
      for (int it = 0; an = ldx16(scr->cnt + 128), an.x != (epoch + 1) * 56 && it < SPIN_MAX; it++) {}
      wait_until(an.z + (dl >> 16));
      if (lane == 0) BAR_ARRIVE(B_G2);
      wait_until(an.z + (dl & 0xffff));
      if (lane == 0) BAR_ARRIVE(B_G);
    } else if (warp == 11) {
      {
        uint2* ph = scr->hdr + ((lane & 24) + 2 * tq + (g & 1)) * 16 + cl;
        const bool own = (lane >> 4) * 4 + tq == rn;
        if (own) { stx8(ph, make_uint2(par ^ 1, 0)); if (cl == 14) stx8(ph + 1, make_uint2(0, 0)); }
        uint32_t a_w = sb + O_HW + ((lane >> 4) * 4 + tq) * 128 + (g & 1) * 64 + ((lane >> 1) & 4);
        PIN(a_w); PINL(ph);
        const int vt = v0 + sch.nt[cls];
#pragma unroll 1
        for (int t = 0; t < vt; t++) mbar_wait(bar0 + 8 * B_EMPTY + (t & 1) * 32, (t >> 1) & 1);
        float hz[8], M;
        uint32_t wp[4];
#pragma unroll 1
        for (int e = 0; e < 2; e++) {
          POLL {
            unsigned ok = 1;
#pragma unroll
            for (int u = 0; u < 8; u++)
              asm volatile("ld.relaxed.cluster.shared.f32 %0, [%1];" : "=f"(hz[u]) : "r"(sb + O_HZ + e * 1024 + u * 128 + lane * 4) : "memory");
#pragma unroll
            for (int u = 0; u < 4; u++) ok = and3(ok, __float_as_uint(hz[u]), __float_as_uint(hz[u + 4]));
            RETRY(~ok)
          }
          if (e) break;
          M = fmaxf(fmaxf(fmaxf(hz[0], hz[1]), fmaxf(hz[2], hz[3])), fmaxf(fmaxf(hz[4], hz[5]), fmaxf(hz[6], hz[7])));
          M = u2f(fbits(M));
#pragma unroll
          for (int u = 0; u < 4; u++) {
            wp[u] = pack2(ex2(hz[u] - M), ex2(hz[u + 4] - M));
            sts4(a_w + ((rn - u) & 3) * 8, u2f(wp[u])); sts4(a_w + ((rn - u) & 3) * 8 + 32, u2f(wp[u]));
          }
          __syncwarp();
          if (lane == 0) BAR_ARRIVE(B_WZ);
        }
        float L = 0.f;
#pragma unroll
        for (int u = 0; u < 4; u++) L += bflo(wp[u]) * hz[u] + bfhi(wp[u]) * hz[u + 4];
        if (own) pub8(ph, __float_as_uint(M) | 1u, __float_as_uint(L));
      }
      if (isA) {
        mbar_wait(bar0 + 8 * B_G2);
        unsigned long long hh;
        POLL { hh = ldx64(scr->hdr + hd * 16 + (lane & 15)); RETRY((lane & 15) == 15 ? 0u : (unsigned)hh ^ par) }
        const float m = (lane & 15) == 15 ? -1e30f : u2f((unsigned)hh);
        int mi = __float_as_int(m);
        mi ^= (mi >> 31) & 0x7fffffff;
        mi = __reduce_max_sync(~0u, mi);
        mi ^= (mi >> 31) & 0x7fffffff;
        const float w = ex2(m - __int_as_float(mi));
        float L = w * u2f(hh >> 32);
#pragma unroll
        for (int o2 = 8; o2; o2 >>= 1) L += __shfl_xor_sync(~0u, L, o2);
        sts4(sb + O_SM + (384 + 2 * (lane & 6) + ((lane >> 2) & 2) + (lane & 1)) * 4, w * rcp(L));
        __syncwarp();
        if (lane == 0) BAR_ARRIVE(B_W);
      }
    } else {
#pragma unroll 4
      for (int i = 0; i < 72; i++) sts16(sb + O_LZ + i * 512 + lane * 16, make_uint4(0, 0, 0, 0));
      __syncwarp();
      if (lane < 8) asm volatile("mbarrier.arrive.release.cluster.shared::cluster.b64 _, [%0];" ::"r"(mapa(bar0 + 8 * B_LZ, lane)) : "memory");
      if (isA) {
        mbar_wait(bar0 + 8 * B_QF);
#pragma unroll 2
        for (int k = 0; k < 8; k++) {
          const uint32_t cp = ldc4(cvec + 2 * (lane + 32 * k));
          *(uint32_t*)(smem + O_SILU + (lane + 32 * k) * 4) = pack2(silu_bf(bflo(cp)), silu_bf(bfhi(cp)));
        }
        __syncwarp();
        uint32_t ab = sb + O_X + (8 * (lane >> 4) + (lane & 7)) * 64 + ((((lane >> 3) & 1) ^ ((lane >> 1) & 3)) << 4);
        float d[4][4] = {};
#pragma unroll 1
        for (int jm = 0; jm < 2; jm++) {
          mbar_wait(bar0 + 8 * (B_FM + jm));
#pragma unroll 2
          for (int s2 = 0; s2 < 8; s2++)
#pragma unroll
            for (int s = 0; s < 2; s++) {
              uint32_t a0[4], a1[4];
              const uint32_t* ps = (const uint32_t*)(smem + O_SILU) + 128 * jm + 16 * s2 + 8 * s + tq;
              ldsm_t(a0, ab + (2 * s2 + s) * 1024); ldsm_t(a1, (ab + (2 * s2 + s) * 1024) ^ 32);
              mma16(d[s], a0, ps[0], ps[4]); mma16(d[2 + s], a1, ps[0], ps[4]);
            }
          ab -= O_X - O_Q;
        }
        const float t0 = (tq & 1) ? d[0][2] + d[1][2] : d[0][0] + d[1][0], t1 = (tq & 1) ? d[2][2] + d[3][2] : d[2][0] + d[3][0];
        stx4(scr->xm + b * 32 + posof(8 * tq + g), fbits(bfr(bfr((tq & 2) ? t1 : t0) + ((b >> 4) == 2 ? 1.f : 0.f))));
        __syncwarp();
        if (lane == 0) CNT_ADD(96);
      } else sleep_until(gt_start + sch.t4);
      for (int it = 0; ldx4(scr->cnt + 96) != (epoch + 1) * 64 && it < SPIN_MAX; it++) __nanosleep(NSL);
      if (isA) {
        unsigned long long ga;
        POLL { ga = ldx64(scr->xm + 64 * rn + 2 * lane); RETRY(lop_x3((unsigned)ga, ga >> 32, par)) }
        *(float2*)(smem + O_SM + (320 + 2 * lane) * 4) = make_float2(bfhi((unsigned)ga), bfhi(ga >> 32));
      }
      __syncwarp();
      if (lane == 0) BAR_ARRIVE(B_TAB);
    }
    return;
  }

  float* s_sm = (float*)(smem + O_SM);
  unsigned par, epoch;
  asm volatile("barrier.cluster.arrive.relaxed.aligned;" ::: "memory");
  if (isA) {
    float* s_r = (float*)(smem + O_R);
    float acc[8] = {0, 0, 0, 0, 0, 0, 0, 0};
    const float sl = silu_bf((arow & 1) ? bfhi(cw) : bflo(cw));
#pragma unroll
    for (int i = 0; i < 4; i++) fma8(acc, wm[i], __shfl_sync(~0u, sl, i, 4));
    tred<4>(acc, lane, 16);
    *(float4*)(s_r + warp * 128 + 8 * (lane & 15) + ((lane >> 2) & 4)) = make_float4(acc[0], acc[1], acc[2], acc[3]);
    nbar(1, 288);
    epoch = *(volatile unsigned*)(smem + O_EP);
    par = (epoch + 1) & 1;
    if (warp < 2) {
      float t = 0.f, ca = rn == 0 ? 1.f : 0.f;
#pragma unroll
      for (int w = 0; w < 8; w++) { t += s_r[w * 128 + tid]; ca += s_r[w * 128 + 64 + tid]; }
      t += ca * ((((tid & 1) ? bfhi(xw) : bflo(xw)) - s_sm[256]) * s_sm[257]);
      const float nb = __shfl_down_sync(~0u, t, 1);
      const uint32_t w0 = lane < 8 ? pack2t(t, nb, par) : pack2(t, nb);
      const uint32_t w1 = __shfl_down_sync(~0u, w0, 8), w2 = __shfl_down_sync(~0u, w0, 16), w3 = __shfl_down_sync(~0u, w0, 24);
      if (lane < 8 && !(lane & 1)) stx16(scr->h + (rn >> 1) * 512 + (2 * cl + warp) * 32 + rk * 16 + 2 * lane, make_uint4(w0, w1, w2, w3));
      __syncwarp();
      if (lane == 0) CNT_ADD(1);
    }
    asm volatile("barrier.cluster.wait.acquire.aligned;" ::: "memory");
    const uint32_t rsb = mapa(sb, rn ^ 1);
    {
      uint32_t a[4][4][4];
      mbar_wait(bar0 + 8 * (warp >> 1));
      const uint32_t ab = sb + (64 * warp + 8 * (lane >> 4) + (lane & 7)) * 128;
#pragma unroll
      for (int s = 0; s < 4; s++)
#pragma unroll
        for (int mt = 0; mt < 4; mt++) ldsm_t(a[s][mt], ab + s * 2048 + (((2 * mt + ((lane >> 3) & 1)) ^ (lane & 7)) << 4));
      arrive_n(bar0 + 8 * (B_EMPTY + (warp >> 1)), lane == 0, 4 + (dep16(&a[0][0][0]) & sch.zero));
      uint4 v0, v1;
      const unsigned* ph = scr->h + (g >> 1) * 512 + 64 * warp + 4 * (lane & 7);
      uint32_t off = O_B + warp * 272 + (32 * rk + 8 * tq + (lane & 4)) * 4;
      PIN(off); PINL(ph);
      mbar_wait(bar0 + 8 * B_H);
      POLL { v0 = ldx16(ph); v1 = ldx16(ph + 32); RETRY(lop_x3(v0.x, v1.x, par)) }
      float d[4][4] = {};
#pragma unroll
      for (int mt = 0; mt < 4; mt++) {
        mma16(d[mt], a[0][mt], v0.x, v0.y); mma16(d[mt], a[1][mt], v0.z, v0.w);
        mma16(d[mt], a[2][mt], v1.x, v1.y); mma16(d[mt], a[3][mt], v1.z, v1.w);
      }
      float r[8];
#pragma unroll
      for (int mt = 0; mt < 4; mt++) { r[2 * mt] = d[mt][0] + d[mt][1]; r[2 * mt + 1] = d[mt][2] + d[mt][3]; }
      tred<4>(r, lane, 2); tred<2>(r, lane, 1);
      const float rc = __shfl_xor_sync(~0u, (lane & 4) ? r[0] : r[1], 4);
      const uint32_t wd = (lane & 4) ? pack2(rc, r[1]) : pack2(r[0], rc);
      const uint32_t w1 = __shfl_down_sync(~0u, wd, 8), w2 = __shfl_down_sync(~0u, wd, 16), w3 = __shfl_down_sync(~0u, wd, 24);
      asm volatile("{.reg .pred p; setp.lt.s32 p, %7, 8; @p st.shared.v4.b32 [%0], {%2,%3,%4,%5};\n"
                   "@p st.async.shared::cluster.mbarrier::complete_tx::bytes.v4.b32 [%1], {%2,%3,%4,%5}, [%6];}"
                   ::"r"(sb + off), "r"(rsb + off), "r"(wd), "r"(w1), "r"(w2), "r"(w3), "r"(rsb + O_BAR + 8 * B_Q2), "r"(lane) : "memory");
      __syncwarp();
      arrive_n(bar0 + 8 * B_Q2, lane == 0, 1);
    }
    {
      uint32_t a[2][8][4];
      uint32_t a_bq = sb + O_B + (lane & 7) * 272 + (lane >> 3) * 16;
      uint4* p_qa = scr->qa + (4 * rk + (warp >> 1)) * 256 + hd * 8 + ((4 * (warp & 1) + tq) ^ (hd & 7));
      PIN(a_bq); PINL(p_qa);
      mbar_wait(bar0 + 8 * (4 + (warp >> 1)));
      const uint32_t ab = sb + 65536 + (warp >> 1) * 16384 + (32 * (warp & 1) + (lane & 15)) * 128;
#pragma unroll
      for (int i = 0; i < 16; i++) ldsm(a[i >> 3][i & 7], ab + (i >> 3) * 2048 + ((i >> 2) & 1) * 8192 + (((2 * (i & 3) + (lane >> 4)) ^ (lane & 7)) << 4));
      arrive_n(bar0 + 8 * (B_EMPTY + 4 + (warp >> 1)), lane == 0, 4 + (dep16(&a[0][0][0]) & sch.zero));
      mbar_wait(bar0 + 8 * B_Q2);
      float d[4][4] = {};
#pragma unroll
      for (int y = 0; y < 4; y++) {
        uint32_t bq[4];
        ldsm(bq, a_bq + 64 * y);
#pragma unroll
        for (int mt = 0; mt < 2; mt++) { mma16(d[2 * mt], a[mt][2 * y], bq[0], bq[1]); mma16(d[2 * mt + 1], a[mt][2 * y + 1], bq[2], bq[3]); }
      }
      float r[4];
#pragma unroll
      for (int i = 0; i < 4; i++) r[i] = (d[i & 2][2 * (i & 1)] + d[i & 2][2 * (i & 1) + 1]) + (d[(i & 2) + 1][2 * (i & 1)] + d[(i & 2) + 1][2 * (i & 1) + 1]);
      tred<2>(r, lane, 2); tred<1>(r, lane, 1);
      const float nb = __shfl_xor_sync(~0u, r[0], 4);
      const uint32_t w0 = (lane >> 3) == (hd & 3) ? pack2t(r[0], nb, par) : pack2(r[0], nb);
      const uint32_t w1 = __shfl_down_sync(~0u, w0, 8), w2 = __shfl_down_sync(~0u, w0, 16), w3 = __shfl_down_sync(~0u, w0, 24);
      if (lane < 4) stx16(p_qa, make_uint4(w0, w1, w2, w3));
      if (warp) nbar_arrive(3, 256); else { nbar(3, 256); if (lane == 0) CNT_ADD(32 + 32 * rk); }
    }
  } else {
    nbar(1, 288);
    epoch = *(volatile unsigned*)(smem + O_EP);
    par = (epoch + 1) & 1;
    asm volatile("barrier.cluster.wait.acquire.aligned;" ::: "memory");
    mbar_wait(bar0);
  }
  asm volatile("setmaxnreg.inc.sync.aligned.u32 216;");
  uint2* p_rec = scr->rec + ((16 * (warp >> 2) + 2 * (warp & 3) + (g & 1) + 4 * (tq & 2)) * 32 + 4 * rn + (tq & 1)) * 64 + cl * 4 + (g >> 1);
  PINL(p_rec);
  {
    const unsigned inv = par ^ 1;
#pragma unroll
    for (int q = 0; q < 2; q++) { stx8(p_rec + q * 128, make_uint2(inv, 0)); if (cl == 14) stx8(p_rec + q * 128 + 4, make_uint2(0, 0)); }
    if (isA) { if (warp < 2) stx4(scr->xao + b * 64 + tid, inv); }
    else if (f == 0) { stx4(out + 2 * tid, 0); __threadfence(); }
  }
  sb = __shfl_sync(~0u, sb, 0); bar0 = sb + O_BAR;
  const int nt = sch.nt[cls], wg = warp >> 2;
  uint32_t a_z[4];
#pragma unroll
  for (int u = 0; u < 4; u++) {
    const int s3 = (rn - u - (lane >> 1 & 1)) & 3;
    a_z[u] = sb + O_LZ + (s3 + 4 * (lane & 1)) * 4096 + wg * 512 + g * 64 + (((warp & 3) ^ (s3 & 1) ^ (2 * (lane & 1))) << 4);
    PIN(a_z[u]);
  }
  uint32_t z[4][4], a_w = sb + O_HW + warp * 128 + (g & 1) * 64 + (tq & 1) * 8;
  PIN(a_w);
  {
    const float sc = 0.08838834764831845f * 1.4426950408889634f;
    const uint32_t a_pm = sb + O_SM + lane * 16;
    float mrun = -1e30f;
    float o[4][16], sx[16], mref[8];
#pragma unroll
    for (int k = 0; k < 16; k++) { o[0][k] = o[1][k] = o[2][k] = o[3][k] = sx[k] = 0.f; mref[k >> 1] = -1e30f; }
    const int key = 16 * warp + (lane & 15);
    uint32_t a_p = sb + O_P + key * 64 + (((lane >> 4) ^ ((key >> 1) & 3)) << 4);
    uint32_t a_v = sb + wg * 32768 + (8 * (lane >> 4) + (lane & 7)) * 128 + (((2 * (warp & 3) + ((lane >> 3) & 1)) ^ (lane & 7)) << 4);
    const int rot = rn + warp;
    unsigned long long dst[4];
#pragma unroll
    for (int q = 0; q < 4; q++) {
      dst[q] = mapg(sb + O_LZ + rn * 4096 + (warp & 3) * 1024 + g * 64 + ((tq ^ (rn & 1) ^ ((rn >> 1) & 2)) << 4), 4 * wg + ((q + rot) & 3));
      PINL(dst[q]);
    }
    unsigned long long a_h = mapg(sb + O_HZ + wg * 1024 + rn * 128 + lane * 4, 2 * (warp & 3));
    unsigned long long a_h1 = mapg(sb + O_HZ + wg * 1024 + rn * 128 + lane * 4, 2 * (warp & 3) + 1);
    PIN(a_p); PIN(a_v); PINL(a_h); PINL(a_h1);
    uint32_t rel = lane < 4 && lane >= 2 * wg ? 2 - (tq >> 1) : 0;
    PIN(rel);
    uint32_t ones[4] = {0x3F803F80u, 0x3F803F80u, 0x3F803F80u, 0x3F803F80u};
    PIN(ones[0]); PIN(ones[1]); PIN(ones[2]); PIN(ones[3]);
    {
      asm volatile("{.reg .pred p; .reg .u32 n; mov.u32 n, 0;\n"
                   "W%=: mbarrier.try_wait.parity.acquire.cluster.shared::cta.b64 p, [%0], 0; add.u32 n, n, 1; setp.lt.and.u32 p, n, 0x100000, !p; @p bra W%=;}"
                   ::"r"(bar0 + 8 * B_LZ) : "memory");
      mbar_wait(bar0 + 8 * B_QF);
      unsigned bad = 0;
#pragma unroll
      for (int k = 0; k < 8; k++) bad |= __float_as_uint(lds4(sb + O_Q + k * 4096 + tid * 16 + (lane >> 3) * 4)) ^ par;
      if (__builtin_expect(__any_sync(~0u, bad & 1), 0)) {
#pragma unroll 1
        for (int k = 0; k < 8; k++) {
          uint4 v;
          POLL { v = ldx16(scr->qa + k * 256 + tid); RETRY(((lane & 16) ? ((lane & 8) ? v.w : v.z) : ((lane & 8) ? v.y : v.x)) ^ par) }
          sts16(sb + O_Q + k * 4096 + tid * 16, v);
        }
        asm volatile("fence.proxy.async.shared::cta;" ::: "memory");
      }
      if (warp >= 4) nbar_arrive(1, 256); else nbar(1, 256);
    }
#pragma unroll 1
    for (int t = 0; t < nt; t++) {
      const int v = v0 + t;
      const uint32_t fb = bar0 + (v & 1) * 32, ph = (v >> 1) & 1, av = a_v + (v & 1) * 65536;
      uint32_t vf[4][4][4], cnt;
      auto landed = [&]() {
        cnt = rel + (dep16(&vf[0][0][0]) & (nt >> 8));
        PIN(cnt);
      };
      if (wg == 0) {
        const uint32_t da = DSC + (v & 1) * 4096, db = DSC + O_Q / 16;
#pragma unroll
        for (int jj = 0; jj < 2; jj++) {
#pragma unroll 1
          for (int j = 2 * jj; j < 2 * jj + 2; j++) {
            mbar_wait(fb + 8 * j, ph);
            asm volatile("wgmma.fence.sync.aligned;" ::: "memory");
#pragma unroll
            for (int k = 0; k < 8; k++)
              wgmma32<0, 0, HI128, HI128>(sx, da + j * 1024 + (k >> 2) * 512 + (k & 3) * 2, db + j * 512 + (k >> 2) * 256 + (k & 3) * 2, jj || k ? 1 : j);
            asm volatile("wgmma.commit_group.sync.aligned;" ::: "memory");
          }
          if (jj == 0) {
#pragma unroll
            for (int i = 0; i < 16; i++) ldsm_t(vf[i >> 2][i & 3], av + (((i >> 2) + rot) & 3) * 8192 + (i & 3) * 2048);
            nbar(5, 256);
            landed();
          }
        }
      } else {
        nbar_arrive(5, 256);
#pragma unroll 1
        for (int j = 0; j < 2; j++) {
          mbar_wait(fb + 16 + 8 * j, ph);
          if (j) spin_until(clock() + VDLY);
#pragma unroll
          for (int q = 0; q < 4; q++)
            if (((q + rot) & 2) == 2 * j)
#pragma unroll
              for (int k = 0; k < 4; k++) ldsm_t(vf[q][k], av + ((q + rot) & 3) * 8192 + k * 2048);
        }
        cnt = 0;
      }
      wg_wait<0>(sx);
      asm volatile("{.reg .pred p; setp.ne.s32 p, %1, 0; @p mbarrier.arrive.shared::cta.b64 _, [%0], %1;}" ::"r"(fb + 8 * B_EMPTY + 8 * tq), "r"(cnt) : "memory");
#pragma unroll 1
      for (int pass = 0;; pass++) {
        int ex = !(t | pass);
        if (wg == 0 && (t | pass)) {
          float mx = -1e30f;
#pragma unroll
          for (int i = 0; i < 8; i++) mx = fmaxf(mx, fmaxf(sx[2 * (i & 6) + (i & 1)], sx[2 * (i & 6) + (i & 1) + 2]) * sc - mref[i]);
          ex = mx > TAU;
          uint32_t pk[8];
#pragma unroll
          for (int i = 0; i < 8; i++) pk[i] = pack2(ex2(sx[2 * i] * sc - mref[i & 6]), ex2(sx[2 * i + 1] * sc - mref[(i & 6) + 1]));
#pragma unroll
          for (int u = 0; u < 2; u++)
            asm volatile("stmatrix.sync.aligned.m8n8.x4.shared.b16 [%0], {%1,%2,%3,%4};"
                         ::"r"(a_p ^ (u << 5)), "r"(pk[4 * u]), "r"(pk[4 * u + 1]), "r"(pk[4 * u + 2]), "r"(pk[4 * u + 3]) : "memory");
          asm volatile("fence.proxy.async.shared::cta;" ::: "memory");
        }
        asm volatile("{.reg .pred p, q; setp.ne.s32 q, %0, 0; bar.red.or.pred p, 4, 256, q; selp.s32 %0, 1, 0, p;}" : "+r"(ex)::"memory");
        if (!ex || pass) break;
        if (wg == 0) {
          float cm[8];
#pragma unroll
          for (int i = 0; i < 8; i++) cm[i] = fmaxf(sx[2 * (i & 6) + (i & 1)], sx[2 * (i & 6) + (i & 1) + 2]);
          tmax<4>(cm, lane, 16); tmax<2>(cm, lane, 8); tmax<1>(cm, lane, 4);
          sts4(a_pm + warp * 4, cm[0] * sc);
        }
        nbar(4, 256);
        const float4 pm = lds16(a_pm);
        const float mn = u2f(__float_as_uint(fmaxf(fmaxf(fmaxf(pm.x, pm.y), fmaxf(pm.z, pm.w)), mrun)) | 1u), al = ex2(mrun - mn);
        mrun = mn;
#pragma unroll
        for (int i = 0; i < 8; i++) {
          const float a = __shfl_sync(~0u, al, 4 * i + tq), aw = wg ? a : 1.f;
          mref[i] = __shfl_sync(~0u, mn, 4 * i + tq);
#pragma unroll
          for (int e = 0; e < 2; e++) {
            const int k = 2 * (i & 6) + (i & 1) + 2 * e;
            o[0][k] *= a; o[1][k] *= a; o[2][k] *= a; o[3][k] *= a; sx[k] *= aw;
          }
        }
      }
      float hv = mrun;
      if (wg) {
        asm volatile("wgmma.fence.sync.aligned;" ::: "memory");
#pragma unroll
        for (int k = 0; k < 4; k++) wgmma32r(sx, ones, DSC + O_P / 16 + k * 64);
        asm volatile("wgmma.commit_group.sync.aligned;" ::: "memory");
        landed();
        asm volatile("{.reg .pred p; setp.ne.s32 p, %1, 0; @p mbarrier.arrive.shared::cta.b64 _, [%0], %1;}" ::"r"(fb + 8 * B_EMPTY + 8 * tq), "r"(cnt) : "memory");
        wg_wait<0>(sx);
        float lv[4];
#pragma unroll
        for (int j = 0; j < 4; j++) lv[j] = (lane & 4) ? sx[4 * j + 1] : sx[4 * j];
        hv = (lane & 16) ? ((lane & 8) ? lv[3] : lv[2]) : ((lane & 8) ? lv[1] : lv[0]);
      }
      asm volatile("{.reg .pred p; setp.eq.s32 p, %3, %4; @p st.relaxed.cluster.b32 [%0], %1; @p st.relaxed.cluster.b32 [%2], %1;}"
                   ::"l"(a_h), "r"(__float_as_uint(hv) | 1u), "l"(a_h1), "r"(t), "r"(nt - 1) : "memory");
#pragma unroll
      for (int q = 0; q < 4; q++) {
        asm volatile("wgmma.fence.sync.aligned;" ::: "memory");
#pragma unroll
        for (int k = 0; k < 4; k++) wgmma32r(o[q], vf[q][k], DSC + O_P / 16 + k * 64);
        asm volatile("wgmma.commit_group.sync.aligned;" ::: "memory");
        if (q == 3) {
#pragma unroll
          for (int u = 0; u < 4; u++) ldsm_t(z[u], a_z[u] + u * 1024);
        }
        wg_wait<0>(o[q]);
#pragma unroll
        for (int j = 0; j < 2; j++)
          asm volatile("{.reg .pred p; setp.eq.s32 p, %5, %6; @p st.relaxed.cluster.v4.b32 [%0], {%1,%2,%3,%4};}"
                       ::"l"(dst[q] + j * 512), "r"(pack2t(o[q][8 * j], o[q][8 * j + 1], 1)), "r"(pack2(o[q][8 * j + 2], o[q][8 * j + 3])),
                         "r"(pack2(o[q][8 * j + 4], o[q][8 * j + 5])), "r"(pack2(o[q][8 * j + 6], o[q][8 * j + 7])), "r"(t), "r"(nt - 1) : "memory");
      }
    }
  }
  {
    uint32_t wx[4][4];
    mbar_wait(bar0 + 8 * B_WZ);
#pragma unroll
    for (int u = 0; u < 4; u++) {
      uint2 wp;
      asm volatile("ld.shared.v2.u32 {%0, %1}, [%2];" : "=r"(wp.x), "=r"(wp.y) : "r"(a_w + u * 8) : "memory");
      const bool lo = (g >> 1) == (tq >> 1), hi = (g >> 1) == 2 + (tq >> 1);
      wx[u][0] = lo ? wp.x : 0u; wx[u][1] = lo ? wp.y : 0u; wx[u][2] = hi ? wp.x : 0u; wx[u][3] = hi ? wp.y : 0u;
    }
    auto bad = [&]() {
      const unsigned ok = and3(and3(and3(z[0][0], z[0][1], z[0][2]), and3(z[0][3], z[1][0], z[1][1]), and3(z[1][2], z[1][3], z[2][0])),
                               and3(and3(z[2][1], z[2][2], z[2][3]), and3(z[3][0], z[3][1], z[3][2]), z[3][3]), 0x10001u);
      return __any_sync(~0u, g == 0 && ok != 0x10001u);
    };
    POLL {
      if (it_)
#pragma unroll
        for (int u = 0; u < 4; u++) ldsm_t(z[u], a_z[u] + u * 1024);
      if (!bad() || ++it_ >= SPIN_MAX) break;
    }
    float d0[8][4] = {}, d[8][4], r[8];
#pragma unroll
    for (int i = 0; i < 8; i++) mma16(d0[i], wx[i >> 1], z[i >> 1][2 * (i & 1)], z[i >> 1][2 * (i & 1) + 1]);
    POLL {
#pragma unroll
      for (int u = 0; u < 4; u++) ldsm_t(z[u], a_z[u ^ 2] + u * 1024);
#pragma unroll
      for (int i = 0; i < 8; i++) mma16c(d[i], wx[(i >> 1) ^ 2], z[i >> 1][2 * (i & 1)], z[i >> 1][2 * (i & 1) + 1], d0[i]);
      if (!bad() || ++it_ >= SPIN_MAX) break;
    }
#pragma unroll
    for (int i = 0; i < 8; i++) r[i] = (tq & 2) ? ((g & 1) ? d[i][3] : d[i][2]) : ((g & 1) ? d[i][1] : d[i][0]);
#pragma unroll
    for (int q = 0; q < 2; q++) pub8(p_rec + q * 128, pack2t(r[4 * q], r[4 * q + 1], par) | 1u, pack2(r[4 * q + 2], r[4 * q + 3]));
  }
  const int vt = v0 + nt;
  const uint32_t bufa = sb + (vt & 1) * 65536, fulla = bar0 + (vt & 1) * 32, pha = (vt >> 1) & 1, phb = ((vt + 1) >> 1) & 1;
  const uint32_t bufo = sb + ((vt + 1) & 1) * 65536, fullb = bar0 + ((vt + 1) & 1) * 32;
  uint32_t a_rs = sb + O_R + (warp >> 2) * 1024 + (16 * tq + g) * 16 + ((warp + tq) & 3) * 4;
  if (isA) {
    const int row = 16 * (warp & 6) + 8 * (warp & 1) + (lane & 16) + ((lane & 7) >> 1) + 4 * (lane & 1);
    uint32_t ab = bufa + row * 128 + ((((lane >> 3) & 1) ^ (row & 7)) << 4);
    const uint2* pr = scr->rec + (hd * 32 + warp) * 64 + lane;
    unsigned long long a_c0 = mapg(sb + O_CTX + (64 * rn + 32 * (warp & 1) + posof(lane)) * 4, warp & 6);
    unsigned long long a_c1 = mapg(sb + O_CTX + (64 * rn + 32 * (warp & 1) + posof(lane)) * 4, warp | 1);
    uint32_t a_rl = sb + O_R + (32 * (warp & 1) + lane) * 16;
    uint32_t ao = bufo + (16 * warp + 8 * (lane >> 4) + (lane & 7)) * 128 + ((((lane >> 3) & 1) ^ (lane & 7)) << 4);
    uint32_t a_cx = sb + O_CTX + (16 * warp + 4 * tq) * 4, a_ga = sb + O_SM + (320 + posof(tid & 63)) * 4;
    unsigned* p_ao = scr->xao + b * 64 + (tid & 63);
    float xv = cl == 0 ? __bfloat162float(x[64 * rn + (tid & 63)]) : 0.f;
    unsigned p2 = lane >= 28 ? 0 : par;
    PIN(ab); PINL(pr); PINL(a_c0); PINL(a_c1); PIN(a_rl); PIN(a_rs); PIN(ao); PIN(a_cx); PIN(a_ga); PINL(p_ao); PIN(p2);
    asm volatile("" : "+f"(xv));
    uint32_t aw[4][4][4];
    auto wo = [&](const int j) {
      mbar_wait(fullb + 8 * j, phb);
#pragma unroll
      for (int mt = 0; mt < 4; mt++) ldsm_t(aw[j][mt], (ao + j * 16384) ^ (mt << 5));
    };
    {
      uint32_t a[4][4][4];
      uint2 z[4], y[4];
      float d[4][4] = {}, r[8];
      mbar_wait(fulla, pha);
      POLL {
#pragma unroll
        for (int q = 0; q < 4; q++) z[q] = ldx8(pr + q * 512);
        RETRY(lop_x3(z[0].x, z[1].x, par) | lop_x3(z[2].x, z[3].x, par))
      }
#pragma unroll
      for (int q = 0; q < 4; q++) {
        if (q == 3) {
          mbar_wait(bar0 + 8 * B_G);
#pragma unroll
          for (int u = 0; u < 4; u++) y[u] = ldx8(pr + u * 512 + 32);
        }
        mbar_wait(fulla + 8 * q, pha);
#pragma unroll
        for (int mt = 0; mt < 4; mt++) ldsm_t(a[q][mt], (ab + q * 16384) ^ (mt << 5));
#pragma unroll
        for (int mt = 0; mt < 4; mt++) mma16(d[mt], a[q][mt], z[q].x, z[q].y);
      }
      mbar_wait(bar0 + 8 * B_W);
      const float4 W = lds16(sb + O_SM + (384 + 4 * tq) * 4);
#pragma unroll
      for (int i = 0; i < 8; i++) { r[i] = W.x * d[i >> 1][2 * (i & 1)] + W.y * d[i >> 1][2 * (i & 1) + 1]; asm volatile("" : "+f"(r[i])); }
#pragma unroll
      for (int j = 0; j < NPE; j++) wo(j);
      POLL {
        if (it_)
#pragma unroll
          for (int u = 0; u < 4; u++) y[u] = ldx8(pr + u * 512 + 32);
#pragma unroll
        for (int mt = 0; mt < 4; mt++) d[mt][0] = d[mt][1] = d[mt][2] = d[mt][3] = 0.f;
#pragma unroll
        for (int q = 0; q < 4; q++)
#pragma unroll
          for (int mt = 0; mt < 4; mt++) mma16(d[mt], a[q][mt], y[q].x, y[q].y);
        RETRY(or3(lop_x3(y[0].x, y[1].x, p2), lop_x3(y[2].x, y[3].x, p2), 0))
      }
#pragma unroll
      for (int i = 0; i < 8; i++) r[i] = W.w * d[i >> 1][2 * (i & 1) + 1] + (W.z * d[i >> 1][2 * (i & 1)] + r[i]);
      tred<4>(r, lane, 2); tred<2>(r, lane, 1);
      sts4(a_rs, r[0]); sts4(a_rs + 128, r[1]);
      nbar(1, 256);
      const uint32_t cv = __float_as_uint(sum8(a_rl)) | 1u;
      asm volatile("st.relaxed.cluster.b32 [%0], %2; st.relaxed.cluster.b32 [%1], %2;" ::"l"(a_c0), "l"(a_c1), "r"(cv) : "memory");
    }
    {
#pragma unroll
      for (int j = NPE; j < NPO; j++) wo(j);
      uint4 c[4];
      POLL {
#pragma unroll
        for (int j = 0; j < 4; j++) c[j] = ldsv16(a_cx + j * 512);
        RETRY(~and3(and3(and3(c[0].x, c[0].y, c[0].z), and3(c[1].x, c[1].y, c[1].z), and3(c[0].w, c[1].w, c[2].x)),
                    and3(and3(c[2].y, c[2].z, c[2].w), and3(c[3].x, c[3].y, c[3].z), c[3].w), ~0u))
      }
      float d[4][4] = {};
#pragma unroll
      for (int j = 0; j < 4; j++) {
        if (j + 1 >= NPO && j < 3) wo(j + 1);
        const uint32_t b0 = pack2(u2f(c[j].x), u2f(c[j].y)), b1 = pack2(u2f(c[j].z), u2f(c[j].w));
#pragma unroll
        for (int mt = 0; mt < 4; mt++) mma16(d[mt], aw[j][mt], b0, b1);
      }
      const float r0 = (tq & 2) ? ((tq & 1) ? d[3][0] : d[2][0]) : ((tq & 1) ? d[1][0] : d[0][0]);
      const float r1 = (tq & 2) ? ((tq & 1) ? d[3][2] : d[2][2]) : ((tq & 1) ? d[1][2] : d[0][2]);
      sts4(a_rs + 2048, r0); sts4(a_rs + 2048 + 128, r1);
      if (warp >= 2) nbar_arrive(2, 256);
      else {
        mbar_wait(bar0 + 8 * B_TAB);
        const float gav = lds4(a_ga);
        nbar(2, 256);
        pub4(p_ao, __float_as_uint(gav * sum8(a_rl + 2048) + xv) | 1u);
      }
    }
  } else {
    uint32_t af[4][4][4], ad[2][4][4];
    uint32_t ab = bufa + (32 * warp + 8 * (lane >> 4) + (lane & 7)) * 64 + ((((lane >> 3) & 1) ^ ((lane >> 1) & 3)) << 4);
    uint32_t a_d = bufo + (32 * warp + 8 * (lane >> 4) + (lane & 7)) * 128 + ((((lane >> 3) & 1) ^ (lane & 7)) << 4);
    uint32_t a_rl = sb + O_R + lane * 16, a_st = sb + O_SM + (352 + 8 * (lane >> 4) + warp) * 4;
    const unsigned* pa = scr->xao + (lane & 16) * 16 + 32 * warp + 2 * (lane & 15);
    unsigned long long a_h = mapg(sb + O_CTX + rn * 64 + (lane & 6) * 8 + (lane >> 3) * 4, warp);
    uint32_t a_hl = sb + O_CTX + warp * 64 + tq * 16, a_x = sb + O_X + (64 * rn + (tid & 63)) * 4, a_y = sb + O_X + ((lane & 16) * 16 + 32 * warp + 2 * (lane & 15)) * 4;
    bf16* po = out + 64 * rn + (tid & 63);
    PIN(ab); PIN(a_d); PIN(a_rl); PINL(pa); PIN(a_rs); PIN(a_st); PINL(po); PINL(a_h); PIN(a_hl); PIN(a_x); PIN(a_y);
    mbar_wait(bar0 + 8 * B_TAB);
    uint2 cf;
    uint2 bb[4];
    unsigned gbw;
    POLL {
      unsigned bad = 0;
      cf = ldx8(scr->xm + 1024 + (lane & 16) * 16 + 32 * warp + posof(2 * (lane & 15)));
#pragma unroll
      for (int s = 0; s < 4; s++) {
        const uint4 w = ldx16(scr->xm + 1024 - (g & 1) * 512 + 256 * (s >> 1) + 32 * warp + 16 * (s & 1) + 4 * tq);
        bb[s] = make_uint2(__byte_perm(w.x, w.y, 0x7632), __byte_perm(w.z, w.w, 0x7632));
        bad = or3(bad, lop_x3(w.x, w.y, par), lop_x3(w.z, w.w, par));
      }
      gbw = ldx4(scr->xm + 1536 + 64 * rn + posof(tid & 63));
      RETRY(or3(bad, lop_x3(cf.x, cf.y, par), gbw ^ par))
    }
    const float gbv = bfhi(gbw);
    float e[4][4] = {};
    uint2 v[8];
    auto item = [&](const int it) {
      mbar_wait(fulla + 8 * it, pha);
#pragma unroll
      for (int i = 0; i < 4; i++) ldsm_t(af[it][i], (ab + it * 16384 + (i >> 1) * 1024) ^ ((i & 1) << 5));
    };
    auto item_mma = [&](const int it) {
#pragma unroll
      for (int i = 0; i < 4; i++) mma16(e[2 * (it & 1) + (i & 1)], af[it][i], bb[(it & 2) + (i >> 1)].x, bb[(it & 2) + (i >> 1)].y);
    };
    item(0); item_mma(0); item(1); item_mma(1);
    mbar_wait(bar0 + 8 * B_G);
#pragma unroll
    for (int i = 0; i < 8; i++) v[i] = ldx8(pa + i * 512);
    const unsigned t3 = clock() + WTEST;
    item(2); item_mma(2);
    uint32_t have3;
    do have3 = mbar_test(fulla + 24, pha); while (!have3 && (int)((unsigned)clock() - t3) < 0);
    if (have3) { item(3); item_mma(3); }
    float y0, y1, df[4][4], st[2];
    uint32_t bz[4][2] = {};
    auto mm = [&](const int it, const int i) { mma16(df[2 * (it & 1) + (i & 1)], af[it][i], bz[(it & 2) + (i >> 1)][0], bz[(it & 2) + (i >> 1)][1]); };
    POLL {
      if (it_)
#pragma unroll
        for (int i = 0; i < 8; i++) v[i] = ldx8(pa + i * 512);
      y0 = ((u2f(v[0].x) + u2f(v[1].x)) + (u2f(v[2].x) + u2f(v[3].x))) + ((u2f(v[4].x) + u2f(v[5].x)) + (u2f(v[6].x) + u2f(v[7].x)));
      y1 = ((u2f(v[0].y) + u2f(v[1].y)) + (u2f(v[2].y) + u2f(v[3].y))) + ((u2f(v[4].y) + u2f(v[5].y)) + (u2f(v[6].y) + u2f(v[7].y)));
      const uint32_t zb = pack2(y0 * u2f(cf.x), y1 * u2f(cf.y));
#pragma unroll
      for (int i = 0; i < 8; i++) bz[i >> 1][i & 1] = g == i ? zb : 0u;
      st[0] = y0 + y1; st[1] = y0 * y0 + y1 * y1;
      tred<1>(st, lane, 16);
#pragma unroll
      for (int i = 0; i < 4; i++) df[i][0] = df[i][1] = df[i][2] = df[i][3] = 0.f;
      mm(0, 0); mm(0, 1); mm(1, 0); mm(1, 1);
      st[0] += shx(st[0], 8);
      mm(0, 2); mm(0, 3); mm(1, 2); mm(1, 3);
      RETRY(or3(or3(lop_x3(v[0].x, v[0].y, par), lop_x3(v[1].x, v[1].y, par), lop_x3(v[2].x, v[2].y, par)),
                or3(lop_x3(v[3].x, v[3].y, par), lop_x3(v[4].x, v[4].y, par), lop_x3(v[5].x, v[5].y, par)),
                or3(lop_x3(v[6].x, v[6].y, par), lop_x3(v[7].x, v[7].y, par), 0)))
    }
    {
      st[0] += shx(st[0], 4);
      mm(2, 0); mm(2, 1);
      st[0] += shx(st[0], 2);
      mm(2, 2); mm(2, 3);
      st[0] += shx(st[0], 1);
      sts4(a_st, st[0]);
      asm volatile("st.shared.v2.f32 [%0], {%1, %2};" ::"r"(a_y), "f"(y0), "f"(y1) : "memory");
      __syncwarp();
      arrive_n(bar0 + 8 * B_ST, lane == 0, 1);
      if (!have3) { item(3); item_mma(3); }
      mm(3, 0); mm(3, 1); mm(3, 2); mm(3, 3);
    }
    mbar_wait(bar0 + 8 * B_ST);
    float mean, rstd;
    {
      float4 u[4];
#pragma unroll
      for (int i = 0; i < 4; i++) u[i] = lds16(sb + O_SM + (352 + 4 * i) * 4);
      mean = (((u[0].x + u[0].y) + (u[0].z + u[0].w)) + ((u[1].x + u[1].y) + (u[1].z + u[1].w))) * (1.f / 512.f);
      const float sq = (((u[2].x + u[2].y) + (u[2].z + u[2].w)) + ((u[3].x + u[3].y) + (u[3].z + u[3].w))) * (1.f / 512.f);
      asm("rsqrt.approx.ftz.f32 %0, %1;" : "=f"(rstd) : "f"(fmaxf(sq - mean * mean, 0.f) + 1e-5f));
    }
    float r[8];
#pragma unroll
    for (int i = 0; i < 8; i++) r[i] = df[i >> 1][2 * (i & 1)] + df[i >> 1][2 * (i & 1) + 1];
    tred<4>(r, lane, 2); tred<2>(r, lane, 1);
    float A[4];
#pragma unroll
    for (int i = 0; i < 4; i++) A[i] = (tq & 2) ? ((tq & 1) ? e[3][i] : e[2][i]) : ((tq & 1) ? e[1][i] : e[0][i]);
    sts4(a_rs, rstd * r[0] + (A[1] - rstd * mean * A[0])); sts4(a_rs + 128, rstd * r[1] + (A[3] - rstd * mean * A[2]));
    nbar(1, 256);
    {
      const float4 g0 = lds16(a_rl), g1 = lds16(a_rl + 1024), u0 = lds16(a_rl + 512), u1 = lds16(a_rl + 1536);
      const float gg = bfr(((g0.x + g0.y) + (g0.z + g0.w)) + ((g1.x + g1.y) + (g1.z + g1.w)));
      const float uu = bfr(((u0.x + u0.y) + (u0.z + u0.w)) + ((u1.x + u1.y) + (u1.z + u1.w)));
      const float hh = bfr(gg * rcp(1.f + ex2(gg * (-2.302208198f - 0.1029432397f * gg * gg)))) * uu;
      const uint32_t hw = pack2t(hh, __shfl_down_sync(~0u, hh, 1), 1);
      asm volatile("{.reg .pred p; setp.eq.s32 p, %2, 0; @p st.relaxed.cluster.b32 [%0], %1;}" ::"l"(a_h), "r"(hw), "r"(lane & 1) : "memory");
    }
    mbar_wait(fullb + 8 * wg, phb);
#pragma unroll
    for (int i = 0; i < 8; i++) ldsm_t(ad[i >> 2][i & 3], (a_d + (i >> 2) * 2048) ^ ((i & 3) << 5));
    const float x7 = lds4(a_x) * (1.f / 7.f);
    float dd[4][4];
    POLL {
      const uint4 hb = ldsv16(a_hl);
#pragma unroll
      for (int mt = 0; mt < 4; mt++) { dd[mt][0] = dd[mt][1] = dd[mt][2] = dd[mt][3] = 0.f; mma16(dd[mt], ad[0][mt], hb.x, hb.y); }
#pragma unroll
      for (int mt = 0; mt < 4; mt++) mma16(dd[mt], ad[1][mt], hb.z, hb.w);
      RETRY(~and3(hb.x, hb.y, hb.z & hb.w))
    }
    sts4(a_rs + 2048, (tq & 2) ? ((tq & 1) ? dd[3][0] : dd[2][0]) : ((tq & 1) ? dd[1][0] : dd[0][0]));
    sts4(a_rs + 2048 + 128, (tq & 2) ? ((tq & 1) ? dd[3][2] : dd[2][2]) : ((tq & 1) ? dd[1][2] : dd[0][2]));
    if (warp >= 2) nbar_arrive(2, 256);
    else {
      nbar(2, 256);
      const float t = gbv * sum8(a_rl + 2048 + warp * 512) + x7;
      asm volatile("{.reg .pred p; setp.eq.s32 p, %2, 0; @p red.relaxed.gpu.global.add.noftz.bf16x2 [%0], %1;}"
                   ::"l"(po), "r"(pack2(t, __shfl_down_sync(~0u, t, 1))), "r"(lane & 1) : "memory");
      if (f == 0 && tid == 0) stx4(&scr->cnt[0], epoch + 1);
    }
  }
}

static void make_sched(Sched& s) {
  const char* order = "FFAAbcFmmvog...d";
  const double dt = 5010 * 1e-3, dth = 4850 * 1e-3, dtt = 5200 * 1e-3;
  const int nbig = NBIG;
  s.zero = 0; s.dth = (unsigned)(dth * 256 + 0.5);
  double t = 512 * dth + 80;
  int tile = 0, jm = 0;
  for (int i = 0; i < 3; i++) s.nr[i] = s.nt[i] = 0;
  auto add = [&](int c, int type, double step, int win, int b0, int tl) {
    s.r[c][s.nr[c]++] = make_uint2((unsigned)(t + 0.5) | (unsigned)(step + 0.5) << 16, type | win << 4 | (b0 + 64) << 8 | tl << 16);
    if (type == T_KV) s.nt[c]++;
  };
  const int w1 = 6, w2 = 4, wt = 6;
  for (const char* p = order; *p; p++) {
    const char c = *p;
    if (c == 'v' || c == 'o' || c == 'm') {
      const int ty = c == 'v' ? T_UV : c == 'o' ? T_WO : T_MOD;
      const double d = c == 'm' ? dt : dtt;
      add(0, ty, 64 * d, wt, 0, c == 'm' ? jm : 0); add(1, ty, 64 * d, wt, 0, c == 'm' ? jm : 0);
      t += (c == 'm' ? 64 : 256) * d; jm += c == 'm';
    } else if (c == 'g' || c == 'd') {
      const int cs = c == 'g' ? 40 : 0;
      t += 3 * cs;
      add(2, c == 'g' ? T_GU : T_DN, 56 * dtt - cs, wt, 64, 0);
      t -= 3 * cs;
      t += (c == 'g' ? 224 : 112) * dtt;
    } else if (c == '.') t += 100;
    else if (c == '-') t -= 100;
    else {
      const int na = c == 'F' ? 0 : c == 'C' || c == 'c' || c == 'a' ? nbig : 64, nf = c == 'A' || c == 'a' ? 0 : 56, n = na + nf;
      const int w = na && nf ? w2 : w1;
      const bool ff = c == 'b' || c == 'c';
      if (na) add(0, T_KV, n * dt, w, ff ? -56 : 0, tile);
      if (na == 64) add(1, T_KV, n * dt, w, ff ? -56 : 0, tile);
      if (nf) add(2, T_KV, n * dt, w, ff ? 64 : 64 - na, tile);
      tile += n; t += 4 * n * dt;
      s.t4 = (unsigned)t + 600;
    }
  }
  s.dt = (unsigned)(dt * 256 + 0.5); s.d4 = 1550 | 1200 << 16; s.d6 = 3400;
}

static void launch(void* const* d_in, void* d_out) {
  static TMaps tms;
  static Sched sch;
  static bool init = false;
  static void* scr = nullptr;
  if (!init) {
    void* fn = nullptr; cudaDriverEntryPointQueryResult qr;
    cudaGetDriverEntryPoint("cuTensorMapEncodeTiled", &fn, cudaEnableDefault, &qr);
    EncFn f = (EncFn)fn;
    const CUtensorMapSwizzle S64 = CU_TENSOR_MAP_SWIZZLE_64B, S128 = CU_TENSOR_MAP_SWIZZLE_128B;
    const CUtensorMapL2promotion P256 = CU_TENSOR_MAP_L2_PROMOTION_L2_256B;
    enc3d(f, &tms.m[0], d_in[2], 64, 512, 64, 8192, 128, 64, 128, 1, S128, CU_TENSOR_MAP_L2_PROMOTION_L2_128B);
    enc3d(f, &tms.m[1], d_in[3], 64, 512, 64, 8192, 128, 64, 64, 2, S128, P256);
    enc3d(f, &tms.m[2], d_in[1], 64, SK, 8, 1024, 128, 64, 64, 2, S128, P256);
    enc3d(f, &tms.m[3], d_in[11], 3072, 256, 2, 6144, 256 * 6144, 32, 256, 1, S64, CU_TENSOR_MAP_L2_PROMOTION_L2_128B);
    enc3d(f, &tms.m[4], d_in[4], 64, 512, 64, 8192, 128, 64, 128, 1, S128, CU_TENSOR_MAP_L2_PROMOTION_L2_128B);
    enc3d(f, &tms.m[5], d_in[5], 512, 128, 32, 1024, 128 * 1024, 64, 128, 1, S128, CU_TENSOR_MAP_L2_PROMOTION_L2_128B);
    enc3d(f, &tms.m[6], d_in[7], 1792, 256, 2, 3584, 256 * 3584, 32, 256, 1, S64, CU_TENSOR_MAP_L2_PROMOTION_L2_128B);
    enc3d(f, &tms.m[7], d_in[8], 1792, 256, 2, 3584, 256 * 3584, 32, 256, 1, S64, CU_TENSOR_MAP_L2_PROMOTION_L2_128B);
    enc3d(f, &tms.m[8], d_in[9], 512, 128, 14, 1024, 128 * 1024, 64, 128, 1, S128, CU_TENSOR_MAP_L2_PROMOTION_L2_128B);
    cudaFuncSetAttribute(fused_kernel, cudaFuncAttributeMaxDynamicSharedMemorySize, SMEM9);
    cudaGetSymbolAddress(&scr, g_scr);
    make_sched(sch);
    init = true;
  }
  fused_kernel<<<NCTA9, 384, SMEM9>>>((const bf16*)d_in[0], (const bf16*)d_in[10], (const bf16*)d_in[11], (bf16*)d_out, (Scratch*)scr, sch, tms);
}

static bool fits() {
  cudaFuncSetAttribute(fused_kernel, cudaFuncAttributeMaxDynamicSharedMemorySize, SMEM9);
  cudaLaunchConfig_t cfg = {};
  cfg.gridDim = dim3(NCTA9); cfg.blockDim = dim3(384); cfg.dynamicSmemBytes = SMEM9;
  cudaLaunchAttribute at[1];
  at[0].id = cudaLaunchAttributeClusterDimension; at[0].val.clusterDim.x = 8; at[0].val.clusterDim.y = 1; at[0].val.clusterDim.z = 1;
  cfg.attrs = at; cfg.numAttrs = 1;
  int n = 0;
  if (cudaOccupancyMaxActiveClusters(&n, fused_kernel, &cfg) != cudaSuccess) { (void)cudaGetLastError(); return false; }
  return n >= NCTA9 / 8;
}
}
#undef BAR_ARM
#undef BAR_ARRIVE
#undef BAR_INIT
#undef B_EM
#undef B_EMPTY
#undef B_FM
#undef B_FULL
#undef B_G
#undef B_G2
#undef B_H
#undef B_HZ
#undef B_LZ
#undef B_Q2
#undef B_QF
#undef B_ST
#undef B_TAB
#undef B_W
#undef B_WZ
#undef CNT_ADD
#undef DSC
#undef HI128
#undef HI64
#undef NBIG
#undef NCTA9
#undef NPE
#undef NPO
#undef NSL
#undef O_B
#undef O_BAR
#undef O_CTX
#undef O_DBG
#undef O_EP
#undef O_HW
#undef O_HZ
#undef O_LZ
#undef O_P
#undef O_Q
#undef O_R
#undef O_SILU
#undef O_SM
#undef O_X
#undef PIN
#undef PINL
#undef POLL
#undef QN
#undef RETRY
#undef SK
#undef SMEM9
#undef SMEM_BASE
#undef SPIN_MAX
#undef TAU
#undef VDLY
#undef WTEST
#undef X16
#undef fbits

namespace v8 {
typedef __nv_bfloat16 bf16;
#define NCTA 128
#define SK 32768
#define SLOT 32768
#define NSLOT 6
#define OFF_WQ (2 * SLOT)
#define OFF_WUK (4 * SLOT)
#define OFF_Q 196608
#define OFF_P (OFF_Q + 16384)
#define OFF_B (OFF_P + 4096)
#define OFF_R4 (OFF_B + 2304)
#define OFF_SILU (OFF_R4 + 4096)
#define OFF_RA (OFF_SILU + 1024)
#define OFF_SM (OFF_RA + 1024)
#define OFF_BP (OFF_SM + 1792)
#define OFF_CO (OFF_BP + 1024)
#define OFF_BAR (OFF_CO + 1280)
#define OFF_MASK (OFF_BAR + 512)
#define OFF_DBG (OFF_MASK + 16)
#define SMEM_BYTES (OFF_DBG + 128)
#define OFF_MOD OFF_Q
#define OFF_UV (4 * SLOT)
#define OFF_O (5 * SLOT)
#define OFF_G 0
#define OFF_U 16384
#define OFF_D SLOT
#define OFF_XO (OFF_D + 16384)
#define FB_UK 4
#define FB_KV 6
#define FB_MOD 22
#define FB_UV 23
#define FB_O 25
#define FB_G 27
#define FB_D 29
#define EB 30
#define QB 50
#define XB 51
#define SPIN_MAX (1 << 20)
#define BACKOFF 40
#define RATE_NS 652
#define RATE_T0 200
#define RATE_TL 300
#define WINS 0x3222333
#define KVWIN 4
#define RATE_H 650
#define RATE_E 650
#define SMUL 9
#define NPRE0 1
#define NPRE1 3
#define HWIN 4
#define EWIN 3
#define WTEST 450
#define DLY5 650
#define DLY6 600
#define DLY7 600
#define P12(a, b, c, d, e, f, g, h, i, j, k, l) ((unsigned long long)(a) | (b) << 5 | (c) << 10 | (d) << 15 | (e) << 20 | (f) << 25 | \
  (unsigned long long)(g) << 30 | (unsigned long long)(h) << 35 | (unsigned long long)(i) << 40 | (unsigned long long)(j) << 45 | \
  (unsigned long long)(k) << 50 | (unsigned long long)(l) << 55)
#define ORDER0 P12(0, 1, 2, 3, 4, 5, 16, 6, 7, 8, 9, 10)
#define ORDER1 P12(11, 12, 13, 14, 15, 17, 18, 19, 20, 23, 21, 22)
#define TAIL_K 17
#define RS 16
template <int N> struct IC { static constexpr int value = N; };
struct TMaps { CUtensorMap m[9]; };

struct __align__(128) Scratch {
  uint4 xo[128 * 64 * RS];
  uint2 ml[32 * 64];
  unsigned h[8 * 256];
  unsigned qa[32 * 256];
  unsigned xc[128 * 64];
  unsigned xao[8 * 512];
  unsigned xf[112 * 512];
  unsigned xm[2048];
  unsigned cnt[5 * 32];
};
__device__ Scratch g_scr;
#define g_xo scr->xo
#define g_ml scr->ml
#define g_h scr->h
#define g_qa scr->qa
#define g_xc scr->xc
#define g_xao scr->xao
#define g_xf scr->xf
#define g_xm scr->xm
#define g_epoch scr->cnt[0]

__device__ __forceinline__ uint32_t s2u(const void* p) { return (uint32_t)__cvta_generic_to_shared(p); }
__device__ __forceinline__ float bflo(uint32_t u) { return __uint_as_float(u << 16); }
__device__ __forceinline__ float bfhi(uint32_t u) { return __uint_as_float(u & 0xffff0000u); }
__device__ __forceinline__ float u2f(uint32_t u) { return __uint_as_float(u); }
__device__ __forceinline__ void fma8(float* acc, uint4 v, float s) {
  acc[0] += s * bflo(v.x); acc[1] += s * bfhi(v.x); acc[2] += s * bflo(v.y); acc[3] += s * bfhi(v.y);
  acc[4] += s * bflo(v.z); acc[5] += s * bfhi(v.z); acc[6] += s * bflo(v.w); acc[7] += s * bfhi(v.w);
}
__device__ __forceinline__ uint32_t pack2(float a, float b) {
  __nv_bfloat162 p = __floats2bfloat162_rn(a, b); return *(uint32_t*)&p;
}
__device__ __forceinline__ float bfr(float v) { return bfhi(pack2(v, v)); }
__device__ __forceinline__ float silu_bf(float c) { return bfr(__fdividef(c, 1.f + __expf(-c))); }
#define fbits(v) ((__float_as_uint(v) & ~1u) | par)
__device__ __forceinline__ uint32_t pack2t(float a, float b, unsigned par) {
  const uint32_t ua = ((__float_as_uint(a) + ((par ^ 1) << 16)) & 0xFFFE0000u) | (par << 16);
  return __byte_perm(ua, pack2(b, b), 0x7632);
}
__device__ __forceinline__ void nbar(int id, int n) { asm volatile("bar.sync %0, %1;" ::"r"(id), "r"(n) : "memory"); }
__device__ __forceinline__ void nbar_arrive(int id, int n) { asm volatile("bar.arrive %0, %1;" ::"r"(id), "r"(n) : "memory"); }
__device__ __forceinline__ uint4 ldc16(const void* p) {
  uint4 v; asm volatile("ld.relaxed.cta.global.v4.u32 {%0,%1,%2,%3}, [%4];" : "=r"(v.x), "=r"(v.y), "=r"(v.z), "=r"(v.w) : "l"(p) : "memory"); return v;
}
__device__ __forceinline__ unsigned ldc4(const void* p) {
  unsigned v; asm volatile("ld.relaxed.cta.global.u32 %0, [%1];" : "=r"(v) : "l"(p) : "memory"); return v;
}
__device__ __forceinline__ uint4 ldx16(const void* p) {
  uint4 v; asm volatile("ld.relaxed.gpu.global.v4.u32 {%0,%1,%2,%3}, [%4];" : "=r"(v.x), "=r"(v.y), "=r"(v.z), "=r"(v.w) : "l"(p) : "memory"); return v;
}
__device__ __forceinline__ unsigned ldx4(const void* p) {
  unsigned v; asm volatile("ld.relaxed.gpu.global.u32 %0, [%1];" : "=r"(v) : "l"(p) : "memory"); return v;
}
__device__ __forceinline__ unsigned long long ldx64(const void* p) {
  unsigned long long v; asm volatile("ld.relaxed.gpu.global.u64 %0, [%1];" : "=l"(v) : "l"(p) : "memory"); return v;
}
__device__ __forceinline__ void stx16(void* p, uint4 v) {
  asm volatile("st.relaxed.gpu.global.v4.u32 [%0], {%1,%2,%3,%4};" ::"l"(p), "r"(v.x), "r"(v.y), "r"(v.z), "r"(v.w) : "memory");
}
__device__ __forceinline__ void stx8(void* p, uint2 v) { asm volatile("st.relaxed.gpu.global.v2.u32 [%0], {%1,%2};" ::"l"(p), "r"(v.x), "r"(v.y) : "memory"); }
__device__ __forceinline__ void stx4(void* p, unsigned v) { asm volatile("st.relaxed.gpu.global.u32 [%0], %1;" ::"l"(p), "r"(v) : "memory"); }
__device__ __forceinline__ unsigned lop_x3(unsigned a, unsigned b, unsigned c) {
  unsigned d; asm("lop3.b32 %0, %1, %2, %3, 0x7E;" : "=r"(d) : "r"(a), "r"(b), "r"(c)); return d; }
#define X16(v) (lop_x3(v.x, v.y, par) | lop_x3(v.z, v.w, par))
#define X8(v) lop_x3(v.x, v.y, par)
#define RETRY(bad) if (!__any_sync(~0u, (bad) & 1) || ++it_ >= SPIN_MAX) break; __nanosleep(BACKOFF);
#define POLL _Pragma("unroll 1") for (int it_ = 0;;)
__device__ __forceinline__ void mbar_wait(uint32_t bar) {
  uint32_t ok; int it = 0;
  do {
    asm volatile("{.reg .pred p; mbarrier.try_wait.parity.shared::cta.b64 p, [%1], 0; selp.u32 %0,1,0,p;}"
                 : "=r"(ok) : "r"(bar) : "memory");
  } while (!ok && ++it < SPIN_MAX);
}
__device__ __forceinline__ float ex2(float v) { float r; asm("ex2.approx.ftz.f32 %0, %1;" : "=f"(r) : "f"(v)); return r; }
__device__ __forceinline__ float rcp(float v) { float r; asm("rcp.approx.ftz.f32 %0, %1;" : "=f"(r) : "f"(v)); return r; }
__device__ __forceinline__ void mma16(float* d, const uint32_t* a, uint32_t b0, uint32_t b1) {
  asm volatile("mma.sync.aligned.m16n8k16.row.col.f32.bf16.bf16.f32 {%0,%1,%2,%3}, {%4,%5,%6,%7}, {%8,%9}, {%0,%1,%2,%3};"
               : "+f"(d[0]), "+f"(d[1]), "+f"(d[2]), "+f"(d[3]) : "r"(a[0]), "r"(a[1]), "r"(a[2]), "r"(a[3]), "r"(b0), "r"(b1));
}
__device__ __forceinline__ float4 lds16(uint32_t a) {
  float4 v; asm volatile("ld.shared.v4.f32 {%0,%1,%2,%3}, [%4];" : "=f"(v.x), "=f"(v.y), "=f"(v.z), "=f"(v.w) : "r"(a) : "memory"); return v;
}
__device__ __forceinline__ void ldsm_t(uint32_t* r, uint32_t a) {
  asm volatile("ldmatrix.sync.aligned.m8n8.x4.trans.shared.b16 {%0,%1,%2,%3}, [%4];" : "=r"(r[0]), "=r"(r[1]), "=r"(r[2]), "=r"(r[3]) : "r"(a) : "memory");
}
__device__ __forceinline__ void ldsm(uint32_t* r, uint32_t a) {
  asm volatile("ldmatrix.sync.aligned.m8n8.x4.shared.b16 {%0,%1,%2,%3}, [%4];" : "=r"(r[0]), "=r"(r[1]), "=r"(r[2]), "=r"(r[3]) : "r"(a) : "memory");
}
template <int N>
__device__ __forceinline__ void tred(float* a, int lane, int m) {
  const bool hi = lane & m;
#pragma unroll
  for (int i = 0; i < N; i++) {
    float send = hi ? a[i] : a[i + N], keep = hi ? a[i + N] : a[i];
    a[i] = keep + __shfl_xor_sync(~0u, send, m);
  }
}
template <int N>
__device__ __forceinline__ void tmax(float* a, int lane, int m) {
  const bool hi = lane & m;
#pragma unroll
  for (int i = 0; i < N; i++) {
    float send = hi ? a[i] : a[i + N], keep = hi ? a[i + N] : a[i];
    a[i] = fmaxf(keep, __shfl_xor_sync(~0u, send, m));
  }
}
__device__ __forceinline__ void arrive2(uint32_t bar, uint32_t rbar, bool local, bool remote) {
  asm volatile("{.reg .pred p, q; setp.ne.s32 p, %2, 0; setp.ne.s32 q, %3, 0; @p mbarrier.arrive.shared::cta.b64 _, [%0];\n"
               "@q mbarrier.arrive.relaxed.cluster.shared::cluster.b64 _, [%1];}" ::"r"(bar), "r"(rbar), "r"((int)local), "r"((int)remote) : "memory");
}
__device__ __forceinline__ unsigned long long stream_policy() {
  unsigned long long p;
  asm volatile("createpolicy.fractional.L2::evict_first.b64 %0, 1.0;" : "=l"(p));
  return p;
}
__device__ __forceinline__ void tma3d(uint32_t dst, const CUtensorMap* tm, uint32_t bar, int c0, int c1, int c2) {
  asm volatile("cp.async.bulk.tensor.3d.shared::cluster.global.mbarrier::complete_tx::bytes.L2::cache_hint [%0], [%1, {%3, %4, %5}], [%2], %6;"
               ::"r"(dst), "l"(tm), "r"(bar), "r"(c0), "r"(c1), "r"(c2), "l"(stream_policy()) : "memory");
}
__device__ __forceinline__ void st_async2(uint32_t dst, uint32_t bar, float v0, float v1) {
  asm volatile("st.async.shared::cluster.mbarrier::complete_tx::bytes.v2.f32 [%0], {%1, %2}, [%3];" ::"r"(dst), "f"(v0), "f"(v1), "r"(bar) : "memory");
}
__device__ __forceinline__ void st_pair(int mode, uint32_t dst, uint32_t bar, float v0, float v1) {
  asm volatile("{.reg .pred p, q; setp.eq.s32 p, %4, 1; setp.eq.s32 q, %4, 2; @p st.shared.v2.f32 [%0], {%1, %2};\n"
               "@q st.async.shared::cluster.mbarrier::complete_tx::bytes.v2.f32 [%0], {%1, %2}, [%3];}"
               ::"r"(dst), "f"(v0), "f"(v1), "r"(bar), "r"(mode) : "memory");
}
__device__ __forceinline__ void spin_until(unsigned t) { while ((int)((unsigned)clock() - t) < 0) {} }
__device__ __forceinline__ unsigned wait_until(unsigned t) {
  unsigned now;
  for (;;) {
    asm volatile("mov.u32 %0, %%globaltimer_lo;" : "=r"(now));
    if ((int)(now - t) >= 0) break;
  }
  return now;
}
#define PIN(x) asm volatile("" : "+r"(x))
#define PINL(x) asm volatile("" : "+l"(x))
#define BAR_ARRIVE(i) asm volatile("mbarrier.arrive.shared::cta.b64 _, [%0];" ::"r"(bar0 + 8 * (i)) : "memory")
#define CNT_ADD(c) asm volatile("red.relaxed.gpu.global.add.u32 [%0], 1;" ::"l"(scr->cnt + (c)) : "memory")
#define BAR_INIT(i, cnt) asm volatile("mbarrier.init.shared::cta.b64 [%0], %1;" ::"r"(bar0 + 8 * (i)), "r"(cnt) : "memory")
#define BAR_ARM(i, bytes) asm volatile("mbarrier.arrive.expect_tx.shared::cta.b64 _, [%0], %1;" ::"r"(bar0 + 8 * (i)), "r"(bytes) : "memory")

__device__ __forceinline__ void tail(unsigned char* smem, Scratch* __restrict__ scr, const bf16* __restrict__ x, bf16* __restrict__ out,
                                     const unsigned par, const unsigned epoch, const int warp) {
  int tid, b;
  asm volatile("mov.u32 %0, %%tid.x;" : "=r"(tid));
  asm volatile("mov.u32 %0, %%ctaid.x;" : "=r"(b));
  const int lane = tid & 31, g = lane >> 2, tq = lane & 3;
  const uint32_t sb = __shfl_sync(~0u, s2u(smem), 0), bar0 = sb + OFF_BAR;
  float* s_sm = (float*)(smem + OFF_SM);
  const int prow = 4 * (lane >> 4) + ((lane & 7) >> 1) + 8 * (lane & 1);
  const float* s_co = (const float*)(smem + OFF_CO);
  const int opos = (b & 15) * 32 + (lane & 16) + 2 * (lane & 6) + ((lane >> 2) & 2) + (lane & 1);
  const float xv = b < 16 ? __bfloat162float(x[(b & 15) * 32 + lane]) : 0.f;
  const int rk = b & 1, ob = 32 * rk + ((b >> 1) & 31);
  uint32_t psb;
  asm volatile("mapa.shared::cluster.u32 %0, %1, %2;" : "=r"(psb) : "r"(sb), "r"(rk ^ 1));
  {
    uint32_t a[8][4];
    {
      const int rg = tid >> 4;
      const uint4* src = g_xo + ((size_t)b * 64 + rg) * RS;
      const uint32_t dst = sb + OFF_XO + rg * 256 + (((tid & 15) ^ (rg & 7)) << 4);
      unsigned long long todo = 0x0001000100010001ull;
#pragma unroll 1
      for (int it = 0; it < SPIN_MAX * 16; it++) {
        unsigned long long mk = *(volatile unsigned long long*)(smem + OFF_MASK);
        const unsigned long long nw = (mk >> rg) & todo;
        todo ^= nw;
#pragma unroll
        for (int i = 0; i < 4; i++)
          if (nw >> (16 * i) & 1)
            asm volatile("cp.async.cg.shared.global [%0], [%1], 16;" ::"r"(dst + i * 4096), "l"(src + i * 16 * RS + (tid & 15)) : "memory");
        if (!__any_sync(~0u, todo != 0)) break;
      }
      asm volatile("cp.async.mbarrier.arrive.noinc.shared::cta.b64 [%0];" ::"r"(bar0 + 8 * (XB + 2)) : "memory");
    }
    mbar_wait(bar0 + 8 * FB_UV); mbar_wait(bar0 + 8 * (FB_UV + 1));
    const uint32_t ab = sb + OFF_UV + (warp >> 2) * 8192 + (8 * (lane >> 4) + (lane & 7)) * 128 + (((2 * (warp & 3) + ((lane >> 3) & 1)) ^ (lane & 7)) << 4);
#pragma unroll
    for (int s = 0; s < 8; s++) ldsm_t(a[s], ab + (s >> 2) * 16384 + (s & 3) * 2048);
    const int chn = 2 * warp + (tq & 1);
    uint32_t a_b = sb + OFF_B + (tq >> 1) * 272 + (32 * (chn >> 2) + 8 * (g >> 1) + 2 * (chn & 3) + (g & 1)) * 2;
    uint32_t a_bq = sb + OFF_B + (lane & 1) * 272 + (lane >> 3) * 16;
    unsigned* p_c = g_xc + (b >> 2) * 256 + warp * 32 + (b & 3) * 8 + (g & 3) * 2 + (g >> 2);
    PIN(a_b); PIN(a_bq); PINL(p_c);
    mbar_wait(bar0 + 8 * (XB + 6));
    uint32_t wb[8];
#pragma unroll
    for (int s = 0; s < 8; s++) wb[s] = *(const uint32_t*)(smem + OFF_RA + (4 * s + tq) * 4);
    const float invL = *(const float*)(smem + OFF_RA + 128);
    float ov;
    POLL {
      mbar_wait(bar0 + 8 * (XB + 2));
      uint32_t ao[4][4];
#pragma unroll
      for (int s = 0; s < 4; s++)
        ldsm_t(ao[s], sb + OFF_XO + (16 * s + 8 * (lane >> 4) + (lane & 7)) * 256 + (((2 * warp + ((lane >> 3) & 1)) ^ (lane & 7)) << 4));
      float d[4][4] = {};
#pragma unroll
      for (int s = 0; s < 4; s++) mma16(d[s], ao[s], wb[2 * s], wb[2 * s + 1]);
      const unsigned p2 = par * 0x10001u;
      unsigned bad = 0;
#pragma unroll
      for (int s = 0; s < 4; s++) bad |= lop_x3(ao[s][0], ao[s][1], p2) | lop_x3(ao[s][2], ao[s][3], p2);
      bad = g == 0 ? bad | (bad >> 16) : 0u;
      ov = (tq & 1) ? (d[0][2] + d[1][2]) + (d[2][2] + d[3][2]) : (d[0][0] + d[1][0]) + (d[2][0] + d[3][0]);
      if (__builtin_expect(!__any_sync(~0u, bad & 1) || ++it_ >= SPIN_MAX, 1)) break;
#pragma unroll
      for (int i = 0; i < 4; i++)
        asm volatile("cp.async.cg.shared.global [%0], [%1], 16;"
                     ::"r"(sb + OFF_XO + ((lane >> 1) + 16 * i) * 256 + (((2 * warp + (lane & 1)) ^ ((lane >> 1) & 7)) << 4)),
                       "l"(g_xo + ((size_t)b * 64 + (lane >> 1) + 16 * i) * RS + 2 * warp + (lane & 1)) : "memory");
      asm volatile("cp.async.wait_all;" ::: "memory");
      __syncwarp();
    }
    {
      const float lo = ov - bfhi(__float_as_uint(ov));
      asm volatile("st.shared.u16 [%0], %1;" ::"r"(a_b), "h"((unsigned short)((tq & 2) ? pack2(lo, lo) : __float_as_uint(ov) >> 16)) : "memory");
    }
    nbar(1, 256);
    float d[4][4] = {};
#pragma unroll
    for (int y = 0; y < 4; y++) {
      uint32_t bq[4];
      ldsm(bq, a_bq + 64 * y);
      mma16(d[(2 * y) & 3], a[2 * y], bq[0], bq[1]); mma16(d[(2 * y + 1) & 3], a[2 * y + 1], bq[2], bq[3]);
    }
    const float r0 = ((d[0][0] + d[0][1]) + (d[1][0] + d[1][1])) + ((d[2][0] + d[2][1]) + (d[3][0] + d[3][1]));
    const float r1 = ((d[0][2] + d[0][3]) + (d[1][2] + d[1][3])) + ((d[2][2] + d[2][3]) + (d[3][2] + d[3][3]));
    if (tq == 0) stx4(p_c, pack2t(r0 * invL, r1 * invL, par));
  }
  unsigned tpub = clock();
  mbar_wait(bar0 + 8 * (XB + 4));
  const float gav = s_co[256 + (opos & 31)];
  const float gbv = s_co[288 + (lane & 4) + 2 * (lane & 1) + ((lane >> 1) & 1)];
  float4 cf[2];
#pragma unroll
  for (int s = 0; s < 2; s++) cf[s] = *(const float4*)(s_co + 32 * warp + 16 * s + 4 * tq);
  {
    uint32_t a[2][4][4];
    mbar_wait(bar0 + 8 * (FB_O + (warp >> 2)));
    const uint32_t ab = sb + OFF_O + (32 * warp + prow) * 128 + ((((lane >> 3) & 1) ^ (prow & 7)) << 4);
#pragma unroll
    for (int i = 0; i < 8; i++) ldsm_t(a[i >> 2][i & 3], (ab + (i >> 2) * 2048) ^ ((i & 3) << 5));
    uint4 v;
    const unsigned* pc = g_xc + (4 * (b >> 4) + 2 * rk + (warp >> 2)) * 256 + 64 * (warp & 3) + 2 * lane;
    uint32_t ro = ((tq >> 1) == rk ? sb : psb) + OFF_P + (8 * (tq & 1) + g) * 144 + (8 * rk + warp) * 8;
    uint32_t a_q = sb + OFF_P + (8 * (lane >> 4) + (lane & 7)) * 144;
    unsigned* p_ao = g_xao + (b >> 5) * 1024 + (opos >> 4) * 32 + (b & 16) + (opos & 15);
    PIN(ro); PIN(a_q); PINL(p_ao); PINL(pc);
    spin_until(tpub + DLY5);
    POLL {
      const unsigned long long u0 = ldx64(pc);
      v.x = (unsigned)u0; v.y = u0 >> 32;
      RETRY(X8(v))
    }
    v.z = lane & 16 ? v.x : 0u; v.w = lane & 16 ? v.y : 0u;
    if (lane & 16) v.x = v.y = 0u;
    float d[4][4] = {};
#pragma unroll
    for (int mt = 0; mt < 4; mt++) mma16(d[mt], a[0][mt], v.x, v.y);
#pragma unroll
    for (int mt = 0; mt < 4; mt++) mma16(d[mt], a[1][mt], v.z, v.w);
    float r[8];
#pragma unroll
    for (int i = 0; i < 8; i++) r[i] = d[i >> 1][2 * (i & 1)] + d[i >> 1][2 * (i & 1) + 1];
    tred<4>(r, lane, 2); tred<2>(r, lane, 1);
    st_pair((tq >> 1) == rk ? 1 : 2, ro, psb + OFF_BAR + 8 * (XB + 3), r[0], r[1]);
    __syncwarp();
    if (lane == 0) BAR_ARRIVE(XB + 3);
    if (warp == 0) {
      mbar_wait(bar0 + 8 * (XB + 3));
      float p[8];
#pragma unroll
      for (int i = 0; i < 8; i++) {
        const float4 q = lds16(a_q + i * 16);
        p[i] = (lane & 8) ? q.y + q.w : q.x + q.z;
      }
      const float t = ((p[0] + p[1]) + (p[2] + p[3])) + ((p[4] + p[5]) + (p[6] + p[7]));
      stx4(p_ao, fbits(gav * t + xv));
    }
  }
  tpub = clock();
  if (b < 112) {
    uint32_t af[2][4][4], ad[4][4];
    const uint32_t ab = sb + (32 * warp + 8 * (lane >> 4) + (lane & 7)) * 64 + ((((lane >> 3) & 1) ^ ((lane >> 1) & 3)) << 4);
    uint32_t ro = ((tq & 1) == rk ? sb : psb) + OFF_R4 + (8 * (tq >> 1) + g) * 176 + (10 * rk + warp) * 8;
    uint32_t a_q = sb + OFF_R4 + (8 * (lane >> 4) + (lane & 7)) * 176 + (lane & 8) * 10;
    uint32_t a_d = sb + OFF_D + warp * 2048 + (8 * (lane >> 4) + (lane & 7)) * 128 + ((((lane >> 3) & 1) ^ (lane & 7)) << 4);
    unsigned* p_f = g_xf + b * 512 + 64 * warp + 16 * tq + 2 * g;
    const unsigned* pa = g_xao + (g >> 1) * 1024 + 512 * rk + 64 * warp + 4 * (lane & 7);
    PIN(ro); PIN(a_q); PIN(a_d); PINL(p_f); PINL(pa);
    spin_until(tpub + DLY6);
    uint4 v[2];
    {
      bool have = false;
      POLL {
        v[0] = ldx16(pa); v[1] = ldx16(pa + 32);
        const unsigned t1 = (unsigned)clock() + WTEST;
        while (!have && (int)((unsigned)clock() - t1) < 0) {
          uint32_t ok;
          asm volatile("{.reg .pred p, q; mbarrier.test_wait.parity.shared::cta.b64 p, [%1], 0; mbarrier.test_wait.parity.shared::cta.b64 q, [%1+8], 0;\n"
                       "and.pred p, p, q; vote.sync.all.pred p, p, 0xffffffff; selp.u32 %0, 1, 0, p;}" : "=r"(ok) : "r"(bar0 + 8 * FB_G) : "memory");
          if (ok) {
#pragma unroll
            for (int i = 0; i < 8; i++) ldsm_t(af[i >> 2][i & 3], (ab + ((i & 2) ? OFF_U : OFF_G) + (i >> 2) * 1024) ^ ((i & 1) << 5));
            have = true;
          }
        }
        if (!__any_sync(~0u, (X16(v[0]) | X16(v[1])) & 1) || ++it_ >= SPIN_MAX) break;
      }
      float df[4][4] = {}, dg[2][4] = {};
      uint32_t zb[4];
      const uint32_t one = g == 0 ? 0x3F803F80u : 0u;
#pragma unroll
      for (int s = 0; s < 2; s++) {
        const uint32_t y0 = pack2(u2f(v[s].x), u2f(v[s].y)), y1 = pack2(u2f(v[s].z), u2f(v[s].w));
        const uint32_t ya[4] = {y0, one, y1, one};
        mma16(dg[s], ya, y0, y1);
        zb[2 * s] = pack2(u2f(v[s].x) * cf[s].x, u2f(v[s].y) * cf[s].y); zb[2 * s + 1] = pack2(u2f(v[s].z) * cf[s].z, u2f(v[s].w) * cf[s].w);
      }
      float st[2] = {(dg[0][2] + dg[0][3]) + (dg[1][2] + dg[1][3]), (dg[0][0] + dg[0][1]) + (dg[1][0] + dg[1][1])};
      if (!have) {
        mbar_wait(bar0 + 8 * FB_G); mbar_wait(bar0 + 8 * (FB_G + 1));
#pragma unroll
        for (int i = 0; i < 8; i++) ldsm_t(af[i >> 2][i & 3], (ab + ((i & 2) ? OFF_U : OFF_G) + (i >> 2) * 1024) ^ ((i & 1) << 5));
      }
#pragma unroll
      for (int i = 0; i < 8; i++) mma16(df[i & 3], af[i >> 2][i & 3], zb[2 * (i >> 2)], zb[2 * (i >> 2) + 1]);
#pragma unroll
      for (int o2 = 1; o2 < 4; o2 <<= 1) { st[0] += __shfl_xor_sync(~0u, st[0], o2); st[1] += __shfl_xor_sync(~0u, st[1], o2); }
#pragma unroll
      for (int o2 = 4; o2 < 32; o2 <<= 1) st[1] += __shfl_xor_sync(~0u, st[1], o2);
      float r[8];
#pragma unroll
      for (int i = 0; i < 8; i++) r[i] = df[i >> 1][2 * (i & 1)] + df[i >> 1][2 * (i & 1) + 1];
      tred<4>(r, lane, 2); tred<2>(r, lane, 1);
      const int md = (tq & 1) == rk ? 1 : 2;
      st_pair(md, ro, psb + OFF_BAR + 8 * (XB + 5), r[0], r[1]);
      st_pair(lane < 2 ? md : 0, ro + 16 * 176, psb + OFF_BAR + 8 * (XB + 5), st[0], st[1]);
      __syncwarp();
      if (lane == 0) BAR_ARRIVE(XB + 5);
      mbar_wait(bar0 + 8 * FB_D);
#pragma unroll
      for (int mt = 0; mt < 4; mt++)
        ldsm_t(ad[mt], a_d ^ (mt << 5));
    }
    mbar_wait(bar0 + 8 * (XB + 5));
    {
      float4 q[5], u[8];
#pragma unroll
      for (int i = 0; i < 5; i++) q[i] = lds16(a_q + i * 16);
#pragma unroll
      for (int i = 0; i < 8; i++) u[i] = *(const float4*)(smem + OFF_R4 + 16 * 176 + (i >> 2) * 80 + (i & 3) * 16);
      float p[6] = {((q[0].x + q[0].z) + (q[1].x + q[1].z)) + ((q[2].x + q[2].z) + (q[3].x + q[3].z)), q[4].x, q[4].z,
                    ((q[0].y + q[0].w) + (q[1].y + q[1].w)) + ((q[2].y + q[2].w) + (q[3].y + q[3].w)), q[4].y, q[4].w};
      tred<3>(p, lane, 8);
      const float P = p[0], A1 = p[1], A2 = p[2];
      const float mean = (((u[0].x + u[0].z) + (u[1].x + u[1].z)) + ((u[2].x + u[2].z) + (u[3].x + u[3].z)) +
                          ((u[4].x + u[4].z) + (u[5].x + u[5].z)) + ((u[6].x + u[6].z) + (u[7].x + u[7].z))) * (1.f / 512.f);
      const float sq = (((u[0].y + u[0].w) + (u[1].y + u[1].w)) + ((u[2].y + u[2].w) + (u[3].y + u[3].w)) +
                         ((u[4].y + u[4].w) + (u[5].y + u[5].w)) + ((u[6].y + u[6].w) + (u[7].y + u[7].w))) * (1.f / 512.f);
      float rstd;
      asm("rsqrt.approx.ftz.f32 %0, %1;" : "=f"(rstd) : "f"(fmaxf(sq - mean * mean, 0.f) + 1e-5f));
      const float gg = bfr(rstd * (P - mean * A1) + A2);
      const float uu = __shfl_xor_sync(~0u, gg, 16);
      const float hh = bfr(gg * rcp(1.f + ex2(gg * (-2.302208198f - 0.1029432397f * gg * gg)))) * uu;
      const uint32_t hw = pack2(hh, __shfl_down_sync(~0u, hh, 1));
      const uint32_t b0 = __shfl_sync(~0u, hw, 2 * tq), b1 = __shfl_sync(~0u, hw, 2 * tq + 8);
      float f0 = 0, f1 = 0;
#pragma unroll
      for (int mt = 0; mt < 4; mt++) {
        float dd[4] = {0, 0, 0, 0};
        mma16(dd, ad[mt], b0, b1);
        if (tq == mt) { f0 = dd[0]; f1 = dd[2]; }
      }
      stx8(p_f, make_uint2(fbits(f0), fbits(f1)));
    }
    tpub = clock();
    if (b < 64 && warp == (b >> 3)) {
      const uint4 y = (b & 4) ? v[1] : v[0];
      float a4[4] = {u2f(y.x), u2f(y.y), u2f(y.z), u2f(y.w)};
      tred<2>(a4, lane, 16); tred<1>(a4, lane, 8);
      a4[0] += __shfl_xor_sync(~0u, a4[0], 4);
      if (!(lane & 4)) s_sm[416 + 8 * (lane >> 4) + 2 * tq + ((lane >> 3) & 1)] = a4[0];
      if (warp == 7) nbar_arrive(2, 256);
    } else if (b < 64 && warp == 7) nbar_arrive(2, 256);
    if (b < 64 && warp < 7) {
      uint4 v;
      const unsigned* pf = g_xf + (tid >> 1) * 512 + 8 * ob + 4 * (tid & 1);
      const int col = 16 * (ob >> 1) + 4 * (ob & 1) + ((tid >> 1) & 3) + 8 * (tid & 1);
      bf16* po = out + col;
      PINL(po); PINL(pf);
      spin_until(tpub + DLY7);
      POLL { v = ldx16(pf); RETRY(X16(v)) }
      float f[4] = {u2f(v.x), u2f(v.y), u2f(v.z), u2f(v.w)};
      tred<2>(f, lane, 16); tred<1>(f, lane, 8);
      f[0] += __shfl_xor_sync(~0u, f[0], 4); f[0] += __shfl_xor_sync(~0u, f[0], 2);
      if (!(lane & 6)) s_sm[352 + warp * 8 + 4 * (lane & 1) + (lane >> 3)] = f[0];
      nbar(2, 256);
      if (tid < 8) {
        const float* q = s_sm + 352 + tid;
        const float t = ((q[0] + q[8]) + (q[16] + q[24])) + ((q[32] + q[40]) + q[48]);
        *po = __float2bfloat16(s_sm[416 + (col & 15)] + bfr(gbv * bfr(t)));
        if (b == 0 && tid == 0) stx4(&g_epoch, epoch + 1);
      }
    }
  }
}

__global__ void __cluster_dims__(2, 1, 1) __launch_bounds__(384, 1)
fused_kernel(const bf16* __restrict__ x, const bf16* __restrict__ cvec, const bf16* __restrict__ w_mod, bf16* __restrict__ out,
             Scratch* __restrict__ scr, const __grid_constant__ TMaps tms) {
  extern __shared__ __align__(1024) unsigned char smem[];
  const int tid = threadIdx.x, warp = __shfl_sync(~0u, tid >> 5, 0), lane = tid & 31;
  const int b = blockIdx.x, rk = b & 1, pr = b >> 1, hd = b >> 2;
  uint32_t sb = s2u(smem), bar0 = sb + OFF_BAR;

  unsigned gt_start;
  asm volatile("mov.u32 %0, %%globaltimer_lo;" : "=r"(gt_start));
  const int g = lane >> 2, tq = lane & 3;
  const int arow = 64 * (b >> 4) + ((tid & 255) >> 3);
  uint4 wm0, wm1;
  uint32_t c0w, c1w;
  if (warp < 8) {
    const bf16* wa = w_mod + (size_t)arow * 3072 + (lane & 4) * 128 + 32 * (b & 15) + 8 * tq;
    wm0 = ldx16(wa); wm1 = ldx16(wa + 32 * 3072);
    c0w = ldc4(cvec + (arow & ~1)); c1w = ldc4(cvec + (arow & ~1) + 32);
  }
  const unsigned t_off = gt_start + RATE_T0;
  if (warp == 11) {
    if (lane == 0) {
#pragma unroll
      for (int i = 0; i < FB_KV; i++) { BAR_INIT(i, 1); BAR_ARM(i, 16384); }
    }
    __syncwarp();
    asm volatile("fence.mbarrier_init.release.cluster;" ::: "memory");
    asm volatile("barrier.cluster.arrive.relaxed.aligned;" ::: "memory");
#pragma unroll 1
    for (int i = 0; i < FB_KV; i++) {
      if (i >= HWIN) mbar_wait(bar0 + 8 * (i - HWIN));
      wait_until(t_off + (i < 4 ? 2 * i + ((b >> 1) & 1) : 4 * i - 8 + (b & 3)) * (RATE_H / 4));
      if (lane == 0) {
        if (i < 4) tma3d(sb + OFF_WQ + i * 16384, &tms.m[0], bar0 + 8 * i, 0, i * 128, 2 * hd + rk);
        else tma3d(sb + OFF_WQ + i * 16384, &tms.m[1], bar0 + 8 * i, 0, (b & 3) * 128 + (i - 4) * 64, 2 * hd);
      }
      __syncwarp();
    }
  }
  if (warp == 10) {
    const uint4 xa = ldc16(x + 16 * lane), xb = ldc16(x + 16 * lane + 8);
    const unsigned ep = ldc4(&g_epoch);
    float xv[16] = {bflo(xa.x), bfhi(xa.x), bflo(xa.y), bfhi(xa.y), bflo(xa.z), bfhi(xa.z), bflo(xa.w), bfhi(xa.w),
                    bflo(xb.x), bfhi(xb.x), bflo(xb.y), bfhi(xb.y), bflo(xb.z), bfhi(xb.z), bflo(xb.w), bfhi(xb.w)};
    float s = 0;
#pragma unroll
    for (int i = 0; i < 16; i++) s += xv[i];
#pragma unroll
    for (int o = 16; o; o >>= 1) s += __shfl_xor_sync(~0u, s, o);
    const float mean = s * (1.f / 512.f);
    s = 0;
#pragma unroll
    for (int i = 0; i < 16; i++) { xv[i] -= mean; s += xv[i] * xv[i]; }
#pragma unroll
    for (int o = 16; o; o >>= 1) s += __shfl_xor_sync(~0u, s, o);
    const float rstd = rsqrtf(s * (1.f / 512.f) + 1e-5f);
    if ((lane >> 1) == (b & 15))
#pragma unroll
      for (int i = 0; i < 4; i++)
        *(float4*)(smem + OFF_SM + (256 + (lane & 1) * 16 + 4 * i) * 4) = make_float4(xv[4 * i] * rstd, xv[4 * i + 1] * rstd, xv[4 * i + 2] * rstd, xv[4 * i + 3] * rstd);
    if (lane == 0) *(volatile unsigned*)(smem + OFF_MASK + 8) = ep;
    nbar_arrive(1, 288);
  }
  if (warp >= 8) {
    asm volatile("setmaxnreg.dec.sync.aligned.u32 72;");
    if (tid == 288) {
#pragma unroll
      for (int q = FB_KV; q < FB_KV + 16; q++) { BAR_INIT(q, 1); BAR_ARM(q, 32768); }
    }
    if (tid == 320) {
#pragma unroll
      for (int q = 0; q <= 13 + NSLOT; q++) BAR_INIT(EB + q, q == 0 ? 4 : q < 5 ? 16 : q < 16 ? 12 : 6);
    }
    if (tid == 256) {
#pragma unroll
      for (int q = FB_MOD; q <= FB_D; q++) { BAR_INIT(q, 1); BAR_ARM(q, 16384); }
      BAR_INIT(QB, 9); BAR_ARM(QB, 1024);
#pragma unroll
      for (int q = 0; q < 7; q++) BAR_INIT(XB + q, q == 2 ? 256 : q == 5 || q == 3 ? 9 : 1);
      BAR_ARM(XB + 3, 1024);
      BAR_ARM(XB + 5, 1024 + 64 + 512);
      *(volatile unsigned long long*)(smem + OFF_MASK) = 0;
    }
    if (warp != 11) {
      __syncwarp();
      asm volatile("fence.mbarrier_init.release.cluster;" ::: "memory");
      __threadfence_block();
      asm volatile("barrier.cluster.arrive.relaxed.aligned;" ::: "memory");
    }
    if (warp == 11) {
      asm volatile("barrier.cluster.wait.acquire.aligned;" ::: "memory");
      const unsigned epoch = *(volatile unsigned*)(smem + OFF_MASK + 8), par = (epoch + 1) & 1;
      mbar_wait(bar0 + 8 * (FB_KV + 15));
      for (int it = 0; ldx4(scr->cnt + 96 + 32 * (b >> 6)) != (epoch + 1) * 64 && it < SPIN_MAX; it++) {}
      uint4 hh;
      POLL { hh = ldx16(g_ml + (b >> 2) * 64 + 2 * lane); RETRY(X16(hh)) }
      int mi = __float_as_int(fmaxf(u2f(hh.x), u2f(hh.z)));
      mi ^= (mi >> 31) & 0x7fffffff;
      mi = __reduce_max_sync(~0u, mi);
      mi ^= (mi >> 31) & 0x7fffffff;
      const float M = __int_as_float(mi);
      const uint32_t wp = pack2(ex2(u2f(hh.x) - M), ex2(u2f(hh.z) - M));
      float L = bflo(wp) * u2f(hh.y) + bfhi(wp) * u2f(hh.w);
#pragma unroll
      for (int o2 = 16; o2; o2 >>= 1) L += __shfl_xor_sync(~0u, L, o2);
      *(uint32_t*)(smem + OFF_RA + lane * 4) = wp;
      if (lane == 0) *(float*)(smem + OFF_RA + 128) = rcp(L);
      __syncwarp();
      if (lane == 0) BAR_ARRIVE(XB + 6);
    }
    if (warp == 10) {
      if (lane < 8) asm volatile("prefetch.tensormap [%0];" ::"l"(&tms.m[lane + 1]) : "memory");
      asm volatile("barrier.cluster.wait.acquire.aligned;" ::: "memory");
      const unsigned epoch = *(volatile unsigned*)(smem + OFF_MASK + 8);
#pragma unroll 1
      for (int e = 0; e < 2; e++) {
        for (int it = 0; ldx4(scr->cnt + (e ? 2 + rk : 1)) != (epoch + 1) * (e ? 64 : 128) && it < SPIN_MAX; it++) {}
        if (lane == 0) BAR_ARRIVE(XB + e);
      }
      mbar_wait(bar0 + 8 * (FB_KV + 14));
      unsigned long long m = 0;
#pragma unroll 1
      for (int it = 0; ~m && it < SPIN_MAX; it++) {
        m = ldx64(scr->cnt + 32 + 32 * (b >> 6)) ^ ((epoch & 1) ? ~0ull : 0ull);
        if (lane == 0) *(volatile unsigned long long*)(smem + OFF_MASK) = m;
      }
    }
    if (warp == 9) {
      asm volatile("barrier.cluster.wait.acquire.aligned;" ::: "memory");
      const unsigned epoch = *(volatile unsigned*)(smem + OFF_MASK + 8);
      const unsigned par = (epoch + 1) & 1, inv = par ^ 1;
      const uint4 inv4 = make_uint4(inv, inv, inv, inv);
      mbar_wait(bar0 + 8 * FB_KV);
#pragma unroll 2
      for (int k = 0; k < 8; k++) {
        const uint32_t cp = ldc4(cvec + 2 * (lane + 32 * k));
        *(uint32_t*)(smem + OFF_SILU + (lane + 32 * k) * 4) = pack2(silu_bf(bflo(cp)), silu_bf(bfhi(cp)));
      }
      __syncwarp();
      mbar_wait(bar0 + 8 * FB_MOD);
      const uint32_t ab = sb + OFF_MOD + (8 * (lane >> 4) + (lane & 7)) * 32 + ((((lane >> 3) ^ (lane >> 2)) & 1) << 4);
      float d[4][4] = {};
#pragma unroll 2
      for (int s4 = 0; s4 < 8; s4++)
#pragma unroll
        for (int s = 0; s < 4; s++) {
          uint32_t a[4];
          const uint32_t* ps = (const uint32_t*)(smem + OFF_SILU) + 32 * s4 + 8 * s + tq;
          ldsm_t(a, ab + (4 * s4 + s) * 512); mma16(d[s], a, ps[0], ps[4]);
        }
      const float t = (tq & 1) ? (d[0][2] + d[1][2]) + (d[2][2] + d[3][2]) : (d[0][0] + d[1][0]) + (d[2][0] + d[3][0]);
      if (tq < 2) stx4(g_xm + b * 16 + 2 * (g & 6) + 2 * tq + (g & 1), fbits(bfr(t)));
      __syncwarp();
      if (lane == 0) CNT_ADD(6);
      mbar_wait(bar0 + 8 * (FB_KV + 8));
      if (lane < 16) stx16(g_xc + (b >> 2) * 256 + (lane >> 1) * 32 + (b & 3) * 8 + (lane & 1) * 4, inv4);
      if (lane < 8) stx16(g_xao + (b >> 5) * 1024 + (b & 15) * 64 + (lane & 4) * 8 + (b & 16) + (lane & 3) * 4, inv4);
      if (b < 112)
#pragma unroll 1
        for (int k = 0; k < 4; k++) stx16(g_xf + b * 512 + (lane + 32 * k) * 4, inv4);
      nbar_arrive(2, 288);
      for (int it = 0; ldx4(scr->cnt + 6) != (epoch + 1) * 128 && it < SPIN_MAX; it++) __nanosleep(100);
      {
        uint4 sv[2], cb[2];
        unsigned ga, gb;
        POLL {
#pragma unroll
          for (int k = 0; k < 2; k++) { sv[k] = ldx16(g_xm + 512 + 256 * rk + 4 * (lane + 32 * k)); cb[k] = ldx16(g_xm + 1024 + 256 * rk + 4 * (lane + 32 * k)); }
          ga = ldx4(g_xm + (b & 15) * 32 + lane); gb = ldx4(g_xm + 1536 + 256 * rk + 8 * (pr & 31) + (lane & 7));
          RETRY(X16(sv[0]) | X16(sv[1]) | X16(cb[0]) | X16(cb[1]) | lop_x3(ga, gb, par))
        }
#pragma unroll
        for (int k = 0; k < 2; k++) {
          const float c0 = bfr(1.f + bfhi(cb[k].x)), c1 = bfr(1.f + bfhi(cb[k].y)), c2 = bfr(1.f + bfhi(cb[k].z)), c3 = bfr(1.f + bfhi(cb[k].w));
          *(float4*)(smem + OFF_CO + (lane + 32 * k) * 16) = make_float4(c0, c1, c2, c3);
          uint2* pb = (uint2*)(smem + OFF_BP) + lane + 32 * k;
          pb[0] = make_uint2(pack2(c0, c1), pack2(c2, c3));
          pb[64] = make_uint2(__byte_perm(sv[k].x, sv[k].y, 0x7632), __byte_perm(sv[k].z, sv[k].w, 0x7632));
        }
        *(float*)(smem + OFF_CO + 1024 + lane * 4) = bfhi(ga);
        *(float*)(smem + OFF_CO + 1152 + lane * 4) = bfhi(gb);
      }
      __syncwarp();
      if (lane == 0) BAR_ARRIVE(XB + 4);
    }
    if (warp == 8) {
      const unsigned stag = ((pr * SMUL) & 63) * RATE_NS >> 6;
      unsigned tnext = t_off + 4 * RATE_H;
      asm volatile("barrier.cluster.wait.acquire.aligned;" ::: "memory");
#pragma unroll 1
      for (int k = 0; k < 24; k++) {
        const int code = (k < 12 ? ORDER0 >> (5 * k) : ORDER1 >> (5 * (k - 12))) & 31;
        const bool kv = code < 16;
        const int n = code, w = code - 16;
        if (!kv && w >= 5 && b >= 112) break;
        if (kv) mbar_wait(bar0 + 8 * (FB_KV + n - (n < 6 ? EWIN : KVWIN)));
        if (k >= TAIL_K) mbar_wait(bar0 + 8 * (FB_KV + (int)((ORDER1 >> (5 * (k - 12 - ((WINS >> (4 * (k - TAIL_K))) & 15)))) & 31)));
        const int e = kv ? (n == 3 ? 2 : n == 5 ? 1 : n) : w == 0 ? 0 : w < 5 ? 16 + ((w - 1) >> 1) : w == 7 ? 19 : 18;
        if (e != 1 && k) mbar_wait(bar0 + 8 * (EB + e));
        wait_until(tnext + stag);
        tnext += k > TAIL_K ? RATE_TL : k < 4 ? RATE_E : RATE_NS;
        if (lane == 0) {
          if (kv)
            asm volatile("cp.async.bulk.tensor.3d.shared::cluster.global.mbarrier::complete_tx::bytes.multicast::cluster.L2::cache_hint [%0], [%1, {%3, %4, %5}], [%2], %6, %7;"
                         ::"r"(sb + (n % NSLOT) * SLOT + rk * 16384), "l"(&tms.m[2]), "r"(bar0 + 8 * (FB_KV + n)), "r"(0), "r"(((n >> 1) * 64 + pr) * 64),
                           "r"(4 * (n & 1) + 2 * rk), "h"((unsigned short)3), "l"(stream_policy()) : "memory");
          else {
            tma3d(sb + (w == 0 ? OFF_MOD : w < 5 ? OFF_UV + (w - 1) * 16384 : w == 5 ? OFF_G : w == 6 ? OFF_U : OFF_D),
                  &tms.m[w == 0 ? 3 : w < 3 ? 4 : w < 5 ? 5 : w + 1], bar0 + 8 * (FB_MOD + w),
                  w == 0 ? 1024 + b * 16 : w < 3 || w == 7 ? 0 : w < 5 ? (pr & 7) * 64 : pr * 32, w == 7 ? b * 16 : w == 1 || w == 2 ? (b & 3) * 128 + (w - 1) * 64 : 0,
                  w == 1 || w == 2 ? 2 * hd : w == 3 || w == 4 ? (b >> 4) * 4 + 2 * rk + w - 3 : w == 5 || w == 6 ? rk : 0);
          }
        }
        __syncwarp();
      }
    }
    if (b < 112) {
      const int mt = warp & 1, dd = (warp >> 1) & 1;
      mbar_wait(bar0 + 8 * (XB + 4));
      const uint32_t ab = sb + (mt ? OFF_U : OFF_G) + (8 * (lane >> 4) + (lane & 7)) * 64 + (((2 * dd + ((lane >> 3) & 1)) ^ ((lane >> 1) & 3)) << 4);
      uint32_t base;
      asm volatile("mapa.shared::cluster.u32 %0, %1, %2;" : "=r"(base) : "r"(sb), "r"(dd));
      uint2 bb[16];
#pragma unroll
      for (int s = 0; s < 16; s++) bb[s] = *(const uint2*)(smem + OFF_BP + (g & 1) * 512 + (4 * s + tq) * 8);
      mbar_wait(bar0 + 8 * (FB_G + mt));
      float e[4][4] = {};
#pragma unroll
      for (int s = 0; s < 16; s++) { uint32_t a[4]; ldsm_t(a, ab + s * 1024); mma16(e[s & 3], a, bb[s].x, bb[s].y); }
      float r[4];
#pragma unroll
      for (int i = 0; i < 4; i++) r[i] = (e[0][i] + e[1][i]) + (e[2][i] + e[3][i]);
      if (tq < 2) st_async2(base + OFF_R4 + (8 * mt + g) * 176 + (10 * rk + 8 + tq) * 8, base + OFF_BAR + 8 * (XB + 5), tq ? r[1] : r[0], tq ? r[3] : r[2]);
    }
    return;
  }

  float* s_sm = (float*)(smem + OFF_SM);
  unsigned par, epoch;
  uint32_t rsb;
  {
    float* s_r4 = (float*)(smem + OFF_R4);
    asm volatile("barrier.cluster.arrive.relaxed.aligned;" ::: "memory");
    asm volatile("mapa.shared::cluster.u32 %0, %1, %2;" : "=r"(rsb) : "r"(sb), "r"(rk ^ 1));
    const float c0 = (arow & 1) ? bfhi(c0w) : bflo(c0w), c1 = (arow & 1) ? bfhi(c1w) : bflo(c1w);
    float acc[8] = {0, 0, 0, 0, 0, 0, 0, 0};
    fma8(acc, wm0, silu_bf(c0)); fma8(acc, wm1, silu_bf(c1));
    tred<4>(acc, lane, 8); tred<2>(acc, lane, 16);
    *(float2*)(s_r4 + warp * 64 + 8 * (lane & 7) + ((lane >> 1) & 4) + ((lane >> 3) & 2)) = make_float2(acc[0], acc[1]);
    nbar(1, 288);
    epoch = *(volatile unsigned*)(smem + OFF_MASK + 8);
    par = (epoch + 1) & 1;
    if (warp == 0) {
      float t = 0.f, ca = b < 16 ? 1.f : 0.f;
#pragma unroll
      for (int w = 0; w < 8; w++) { t += s_r4[w * 64 + lane]; ca += s_r4[w * 64 + 32 + lane]; }
      t += ca * s_sm[256 + lane];
      const float nb = __shfl_down_sync(~0u, t, 1);
      const uint32_t w0 = lane < 8 ? pack2t(t, nb, par) : pack2(t, nb);
      const uint32_t w1 = __shfl_down_sync(~0u, w0, 8), w2 = __shfl_down_sync(~0u, w0, 16), w3 = __shfl_down_sync(~0u, w0, 24);
      if (lane < 8 && !(lane & 1)) stx16(g_h + (b >> 5) * 512 + (b & 15) * 32 + (b & 16) + 2 * lane, make_uint4(w0, w1, w2, w3));
      __syncwarp();
      if (lane == 0) CNT_ADD(1);
    }
  }
  asm volatile("barrier.cluster.wait.acquire.aligned;" ::: "memory");
  {
    uint32_t a[4][4][4];
    mbar_wait(bar0 + 8 * (warp >> 1));
    const uint32_t ab = sb + OFF_WQ + (64 * warp + 8 * (lane >> 4) + (lane & 7)) * 128;
#pragma unroll
    for (int s = 0; s < 4; s++)
#pragma unroll
      for (int mt = 0; mt < 4; mt++) ldsm_t(a[s][mt], ab + s * 2048 + (((2 * mt + ((lane >> 3) & 1)) ^ (lane & 7)) << 4));
    uint4 v0, v1;
    const unsigned* ph = g_h + (g >> 1) * 512 + 64 * warp + 4 * (lane & 7);
    uint32_t off = OFF_B + warp * 272 + (32 * rk + 8 * tq + (lane & 4)) * 4;
    PIN(off); PINL(ph);
    mbar_wait(bar0 + 8 * XB);
    POLL { v0 = ldx16(ph); v1 = ldx16(ph + 32); RETRY(lop_x3(v0.x, v1.x, par)) }
    float d[4][4] = {};
#pragma unroll
    for (int mt = 0; mt < 4; mt++) {
      mma16(d[mt], a[0][mt], v0.x, v0.y); mma16(d[mt], a[1][mt], v0.z, v0.w);
      mma16(d[mt], a[2][mt], v1.x, v1.y); mma16(d[mt], a[3][mt], v1.z, v1.w);
    }
    float r[8];
#pragma unroll
    for (int mt = 0; mt < 4; mt++) { r[2 * mt] = d[mt][0] + d[mt][1]; r[2 * mt + 1] = d[mt][2] + d[mt][3]; }
    tred<4>(r, lane, 2); tred<2>(r, lane, 1);
    const float rc = __shfl_xor_sync(~0u, (lane & 4) ? r[0] : r[1], 4);
    const uint32_t wd = (lane & 4) ? pack2(rc, r[1]) : pack2(r[0], rc);
    const uint32_t w1 = __shfl_down_sync(~0u, wd, 8), w2 = __shfl_down_sync(~0u, wd, 16), w3 = __shfl_down_sync(~0u, wd, 24);
    asm volatile("{.reg .pred p; setp.lt.s32 p, %7, 8; @p st.shared.v4.b32 [%0], {%2,%3,%4,%5};\n"
                 "@p st.async.shared::cluster.mbarrier::complete_tx::bytes.v4.b32 [%1], {%2,%3,%4,%5}, [%6];}"
                 ::"r"(sb + off), "r"(rsb + off), "r"(wd), "r"(w1), "r"(w2), "r"(w3), "r"(rsb + OFF_BAR + 8 * QB), "r"(lane) : "memory");
    __syncwarp();
    arrive2(bar0 + 8 * QB, 0, lane == 0, false);
    arrive2(bar0 + 8 * (EB + 2), rsb + OFF_BAR + 8 * (EB + 2), lane == 0, lane == 0);
  }
  {
    uint32_t a[8][4];
    uint32_t a_bq = sb + OFF_B + (lane & 7) * 272 + (lane >> 3) * 16;
    unsigned* p_qa = g_qa + b * 64 + 8 * warp + 4 * lane;
    PIN(a_bq); PINL(p_qa);
    mbar_wait(bar0 + 8 * (FB_UK + (warp >> 2)));
    const uint32_t ab = sb + OFF_WUK + (warp >> 2) * 16384 + (16 * (warp & 3) + (lane & 15)) * 128;
#pragma unroll
    for (int s = 0; s < 8; s++) ldsm(a[s], ab + (s >> 2) * 8192 + (((2 * (s & 3) + (lane >> 4)) ^ (lane & 7)) << 4));
    mbar_wait(bar0 + 8 * QB);
    float d[4][4] = {};
#pragma unroll
    for (int y = 0; y < 4; y++) {
      uint32_t bq[4];
      ldsm(bq, a_bq + 64 * y);
      mma16(d[(2 * y) & 3], a[2 * y], bq[0], bq[1]); mma16(d[(2 * y + 1) & 3], a[2 * y + 1], bq[2], bq[3]);
    }
    float r[2] = {((d[0][0] + d[0][1]) + (d[1][0] + d[1][1])) + ((d[2][0] + d[2][1]) + (d[3][0] + d[3][1])),
                  ((d[0][2] + d[0][3]) + (d[1][2] + d[1][3])) + ((d[2][2] + d[2][3]) + (d[3][2] + d[3][3]))};
    tred<1>(r, lane, 1);
    r[0] += __shfl_xor_sync(~0u, r[0], 2);
    const float nb = __shfl_xor_sync(~0u, r[0], 4);
    const uint32_t w0 = lane < 8 ? pack2t(r[0], nb, par) : pack2(r[0], nb);
    const uint32_t w1 = __shfl_down_sync(~0u, w0, 8), w2 = __shfl_down_sync(~0u, w0, 16), w3 = __shfl_down_sync(~0u, w0, 24);
    if (lane < 2) stx16(p_qa, make_uint4(w0, w1, w2, w3));
    arrive2(bar0 + 8 * (EB + 4), rsb + OFF_BAR + 8 * (EB + 4), lane == 0, lane == 0);
  }
  {
    if (warp) nbar_arrive(3, 256); else { nbar(3, 256); if (lane == 0) CNT_ADD(2 + (b >> 6)); }
    asm volatile("setmaxnreg.inc.sync.aligned.u32 216;");
    const unsigned* pq = g_qa + rk * 4096 + tid * 4;
    uint32_t a_q = sb + OFF_Q + ((tid & 63) >> 3) * 2048 + (tid >> 6) * 128 + (((tid & 7) ^ (tid >> 6)) << 4);
    PINL(pq); PIN(a_q);
    mbar_wait(bar0 + 8 * (XB + 1));
    uint4 v[4];
    POLL {
#pragma unroll
      for (int k = 0; k < 4; k++) v[k] = ldx16(pq + 1024 * k);
      RETRY(lop_x3(v[0].x, v[1].x, par) | lop_x3(v[2].x, v[3].x, par))
    }
#pragma unroll
    for (int k = 0; k < 4; k++)
      asm volatile("st.shared.v4.b32 [%0], {%1,%2,%3,%4};" ::"r"((a_q + k * 512) ^ ((k & 1) << 6)), "r"(v[k].x), "r"(v[k].y), "r"(v[k].z), "r"(v[k].w) : "memory");
    if (warp >= 4) nbar_arrive(1, 256); else nbar(1, 256);
  }
  sb = __shfl_sync(~0u, sb, 0); bar0 = sb + OFF_BAR;
  if (warp < 4) {
    uint32_t qf[32][4];
#pragma unroll
    for (int s = 0; s < 32; s++) ldsm(qf[s], sb + OFF_Q + (s >> 2) * 2048 + (lane & 15) * 128 + (((2 * (s & 3) + (lane >> 4)) ^ (lane & 7)) << 4));
    float l0 = 0.f, l1 = 0.f, m0 = -1e30f, m1 = -1e30f;
    const float sc = 0.08838834764831845f * 1.4426950408889634f;
    const uint32_t kofs = (16 * warp + 8 * (lane >> 4) + (lane & 7)) * 128 + ((((lane >> 3) & 1) ^ (lane & 7)) << 4);
    uint32_t st = sb;
#pragma unroll 1
    for (int t = 0; t < 8; t++) {
      float sa[4][4] = {};
#pragma unroll
      for (int hf = 0; hf < 2; hf++) {
        const int n = 2 * t + hf;
        mbar_wait(bar0 + 8 * (FB_KV + n));
        uint32_t kf[16][4];
#pragma unroll
        for (int y = 0; y < 16; y++) ldsm(kf[y], st + (y >> 2) * 8192 + (kofs ^ ((y & 3) << 5)));
#pragma unroll
        for (int y = 0; y < 16; y++) {
          mma16(sa[(2 * y) & 3], qf[16 * hf + y], kf[y][0], kf[y][1]); mma16(sa[((2 * y) & 3) + 1], qf[16 * hf + y], kf[y][2], kf[y][3]);
        }
        __syncwarp();
        arrive2(bar0 + 8 * (EB + NSLOT + n), rsb + OFF_BAR + 8 * (EB + NSLOT + n), lane == 0 && n < 14, lane == 0 && n < 16 - NSLOT);
        if (hf == 0) arrive2(bar0 + 8 * EB, 0, lane == 0 && t == 0, false);
        st = st + SLOT == sb + NSLOT * SLOT ? sb : st + SLOT;
      }
#pragma unroll
      for (int i = 0; i < 4; i++) { sa[0][i] = (sa[0][i] + sa[2][i]) * sc; sa[1][i] = (sa[1][i] + sa[3][i]) * sc; }
      float cm[2] = {fmaxf(fmaxf(sa[0][0], sa[0][1]), fmaxf(sa[1][0], sa[1][1])), fmaxf(fmaxf(sa[0][2], sa[0][3]), fmaxf(sa[1][2], sa[1][3]))};
      tmax<1>(cm, lane, 1);
      cm[0] = fmaxf(cm[0], __shfl_xor_sync(~0u, cm[0], 2));
      float* pm = s_sm + (t & 1) * 64;
      if (tq < 2) pm[(g + 8 * tq) * 4 + warp] = cm[0];
      if (t >= 2) nbar(6 + (t & 1), 256); else nbar(3, 128);
      const float4 a0 = *(const float4*)(pm + g * 4), b0 = *(const float4*)(pm + g * 4 + 32);
      const float n0 = fmaxf(fmaxf(fmaxf(a0.x, a0.y), fmaxf(a0.z, a0.w)), m0), n1 = fmaxf(fmaxf(fmaxf(b0.x, b0.y), fmaxf(b0.z, b0.w)), m1);
      uint32_t pk[4];
#pragma unroll
      for (int i = 0; i < 2; i++) { pk[2 * i] = pack2(ex2(sa[i][0] - n0), ex2(sa[i][1] - n0)); pk[2 * i + 1] = pack2(ex2(sa[i][2] - n1), ex2(sa[i][3] - n1)); }
      *(uint4*)(smem + OFF_P + (t & 1) * 2048 + tid * 16) = make_uint4(pk[0], pk[1], pk[2], pk[3]);
      const float al0 = ex2(m0 - n0), al1 = ex2(m1 - n1);
      if (tid < 32 && tq == 0) *(float2*)(s_sm + 192 + (t & 1) * 16 + 2 * g) = make_float2(al0, al1);
      nbar_arrive(4 + (t & 1), 256);
      m0 = n0; m1 = n1;
      l0 = l0 * al0 + (bflo(pk[0]) + bfhi(pk[0])) + (bflo(pk[2]) + bfhi(pk[2]));
      l1 = l1 * al1 + (bflo(pk[1]) + bfhi(pk[1])) + (bflo(pk[3]) + bfhi(pk[3]));
    }
    float lr[2] = {l0, l1};
    tred<1>(lr, lane, 1);
    lr[0] += __shfl_xor_sync(~0u, lr[0], 2);
    if (tq < 2) s_sm[128 + (g + 8 * tq) * 4 + warp] = lr[0];
    nbar(3, 128);
    if (warp == 0 && tq < 2) {
      const float4 a0 = *(const float4*)(s_sm + 128 + (g + 8 * tq) * 4);
      stx8(g_ml + (16 * rk + g + 8 * tq) * 64 + pr, make_uint2(fbits(tq ? m1 : m0), fbits((a0.x + a0.y) + (a0.z + a0.w))));
    }
    if (warp == 0) { __syncwarp(); if (lane == 0) CNT_ADD(96 + 32 * rk); }
    nbar(2, 288);
    if (tid == 0) asm volatile("red.relaxed.gpu.global.xor.b64 [%0], %1;" ::"l"(scr->cnt + 32 + 32 * rk), "l"(1ull << pr) : "memory");
  } else {
    float o[16][4] = {};
    const uint32_t vofs = (warp & 1) * 16384 + (lane & 15) * 128 + (((lane >> 4) ^ (lane & 7)) << 4);
    const int hf = (warp >> 1) & 1;
    uint32_t st = sb + hf * SLOT;
    auto pv = [&](const int t, auto np) {
      constexpr int npre = decltype(np)::value;
      uint32_t vf[4][8][4];
      const int n = 2 * t + hf;
      mbar_wait(bar0 + 8 * (FB_KV + n));
#pragma unroll
      for (int s = 0; s < npre; s++)
#pragma unroll
        for (int y = 0; y < 8; y++) ldsm_t(vf[s][y], st + (y >> 2) * 8192 + s * 2048 + (vofs ^ ((y & 3) << 5)));
      nbar(4 + (t & 1), 256);
      const float2 al = *(const float2*)(s_sm + 192 + (t & 1) * 16 + 2 * g);
      uint4 pf[4];
#pragma unroll
      for (int s = 0; s < 4; s++) pf[s] = *(const uint4*)(smem + OFF_P + (t & 1) * 2048 + s * 512 + lane * 16);
      if (t < 6) nbar_arrive(6 + (t & 1), 256);
#pragma unroll
      for (int s = npre; s < 4; s++)
#pragma unroll
        for (int y = 0; y < 8; y++) ldsm_t(vf[s][y], st + (y >> 2) * 8192 + s * 2048 + (vofs ^ ((y & 3) << 5)));
#pragma unroll
      for (int nt = 0; nt < 16; nt++) { o[nt][0] *= al.x; o[nt][1] *= al.x; o[nt][2] *= al.y; o[nt][3] *= al.y; }
#pragma unroll
      for (int s = 0; s < 4; s++) {
        const uint32_t pa[4] = {pf[s].x, pf[s].y, pf[s].z, pf[s].w};
#pragma unroll
        for (int y = 0; y < 8; y++) { mma16(o[2 * y], pa, vf[s][y][0], vf[s][y][1]); mma16(o[2 * y + 1], pa, vf[s][y][2], vf[s][y][3]); }
      }
      __syncwarp();
      arrive2(bar0 + 8 * (EB + NSLOT + n), rsb + OFF_BAR + 8 * (EB + NSLOT + n), lane == 0 && n < 14, lane == 0 && n < 16 - NSLOT);
      st = st + 2 * SLOT >= sb + NSLOT * SLOT ? st - (NSLOT - 2) * SLOT : st + 2 * SLOT;
    };
#pragma unroll 1
    for (int t = 0; t < 7; t++) pv(t, IC<NPRE0>());
    pv(7, IC<NPRE1>());
    uint4* po = g_xo + ((size_t)((16 * rk + (g & 6)) * 4 + warp - 4) * 64 + pr) * RS + (lane & 7);
    const bool odd = lane & 4;
#pragma unroll
    for (int e = 0; e < 2; e++)
#pragma unroll
      for (int j2 = 0; j2 < 2; j2++) {
        uint32_t c0[4], c1[4];
#pragma unroll
        for (int i = 0; i < 4; i++) {
          c0[i] = i ? pack2(o[8 * j2 + i][2 * e], o[8 * j2 + i][2 * e + 1]) : pack2t(o[8 * j2][2 * e], o[8 * j2][2 * e + 1], par);
          c1[i] = i ? pack2(o[8 * j2 + 4 + i][2 * e], o[8 * j2 + 4 + i][2 * e + 1]) : pack2t(o[8 * j2 + 4][2 * e], o[8 * j2 + 4][2 * e + 1], par);
          const uint32_t r = __shfl_xor_sync(~0u, odd ? c0[i] : c1[i], 4);
          if (odd) c0[i] = r; else c1[i] = r;
        }
        stx16(po + e * 8 * 4 * 64 * RS + 8 * j2, make_uint4(c0[0], c0[1], c0[2], c0[3]));
        stx16(po + (e * 8 + 1) * 4 * 64 * RS + 8 * j2, make_uint4(c1[0], c1[1], c1[2], c1[3]));
      }
    nbar_arrive(2, 288);
  }
  tail(smem, scr, x, out, par, epoch, warp);
}

static void launch(void* const* d_in, void* d_out) {
  static TMaps tms;
  static bool init = false;
  static void* scr = nullptr;
  if (!init) {
    void* fn = nullptr; cudaDriverEntryPointQueryResult qr;
    cudaGetDriverEntryPoint("cuTensorMapEncodeTiled", &fn, cudaEnableDefault, &qr);
    EncFn f = (EncFn)fn;
    const CUtensorMapSwizzle S32 = CU_TENSOR_MAP_SWIZZLE_32B, S64 = CU_TENSOR_MAP_SWIZZLE_64B, S128 = CU_TENSOR_MAP_SWIZZLE_128B;
    const CUtensorMapL2promotion P128 = CU_TENSOR_MAP_L2_PROMOTION_L2_128B, P256 = CU_TENSOR_MAP_L2_PROMOTION_L2_256B;
    enc3d(f, &tms.m[0], d_in[2], 64, 512, 64, 8192, 128, 64, 128, 1, S128, P128);
    enc3d(f, &tms.m[1], d_in[3], 64, 512, 64, 8192, 128, 64, 64, 2, S128, P256);
    enc3d(f, &tms.m[2], d_in[1], 64, SK, 8, 1024, 128, 64, 64, 2, S128, P256);
    enc3d(f, &tms.m[3], d_in[11], 3072, 256, 2, 6144, 256 * 6144, 16, 256, 2, S32, P128);
    enc3d(f, &tms.m[4], d_in[4], 64, 512, 64, 8192, 128, 64, 64, 2, S128, P256);
    enc3d(f, &tms.m[5], d_in[5], 512, 128, 32, 1024, 128 * 1024, 64, 128, 1, S128, P128);
    enc3d(f, &tms.m[6], d_in[7], 1792, 256, 2, 3584, 256 * 3584, 32, 256, 1, S64, P128);
    enc3d(f, &tms.m[7], d_in[8], 1792, 256, 2, 3584, 256 * 3584, 32, 256, 1, S64, P128);
    enc3d(f, &tms.m[8], d_in[9], 64, 1792, 8, 1024, 128, 64, 16, 8, S128, P256);
    cudaFuncSetAttribute(fused_kernel, cudaFuncAttributeMaxDynamicSharedMemorySize, SMEM_BYTES);
    cudaGetSymbolAddress(&scr, g_scr);
    init = true;
  }
  fused_kernel<<<NCTA, 384, SMEM_BYTES>>>((const bf16*)d_in[0], (const bf16*)d_in[10], (const bf16*)d_in[11], (bf16*)d_out, (Scratch*)scr, tms);
}

}

extern "C" void kernel_launch(void* const* d_in, const int* in_sizes, int n_in, void* d_out, int out_size) {
  static int big = -1;
  if (big < 0) big = v9::fits();
  if (big) v9::launch(d_in, d_out); else v8::launch(d_in, d_out);
}
```

```cpp
#include <cuda_runtime.h>
#include <cuda_bf16.h>
#include <cuda.h>
#include <stdint.h>
#include <stdio.h>
#include <stdlib.h>

typedef CUresult (*EncFn)(CUtensorMap*, CUtensorMapDataType, cuuint32_t, void*, const cuuint64_t*, const cuuint64_t*,
                          const cuuint32_t*, const cuuint32_t*, CUtensorMapInterleave, CUtensorMapSwizzle,
                          CUtensorMapL2promotion, CUtensorMapFloatOOBfill);

static void enc3d(EncFn fn, CUtensorMap* tm, void* p, uint64_t d0, uint64_t d1, uint64_t d2, uint64_t s1, uint64_t s2, uint32_t b0,
                  uint32_t b1, uint32_t b2, CUtensorMapSwizzle sw, CUtensorMapL2promotion pr) {
  cuuint64_t gd[3] = {d0, d1, d2}, gs[2] = {s1, s2};
  cuuint32_t bx[3] = {b0, b1, b2}, es[3] = {1, 1, 1};
  fn(tm, CU_TENSOR_MAP_DATA_TYPE_BFLOAT16, 3, p, gd, gs, bx, es, CU_TENSOR_MAP_INTERLEAVE_NONE, sw, pr, CU_TENSOR_MAP_FLOAT_OOB_FILL_NONE);
}

namespace v9 {
typedef __nv_bfloat16 bf16;
#define SK 32768
#define SPIN_MAX (1 << 20)
template <int N> struct IC { static constexpr int value = N; };

__device__ __forceinline__ uint32_t s2u(const void* p) { return (uint32_t)__cvta_generic_to_shared(p); }
__device__ __forceinline__ float bflo(uint32_t u) { return __uint_as_float(u << 16); }
__device__ __forceinline__ float bfhi(uint32_t u) { return __uint_as_float(u & 0xffff0000u); }
__device__ __forceinline__ float u2f(uint32_t u) { return __uint_as_float(u); }
__device__ __forceinline__ void fma8(float* acc, uint4 v, float s) {
  acc[0] += s * bflo(v.x); acc[1] += s * bfhi(v.x); acc[2] += s * bflo(v.y); acc[3] += s * bfhi(v.y);
  acc[4] += s * bflo(v.z); acc[5] += s * bfhi(v.z); acc[6] += s * bflo(v.w); acc[7] += s * bfhi(v.w);
}
__device__ __forceinline__ uint32_t pack2(float a, float b) {
  __nv_bfloat162 p = __floats2bfloat162_rn(a, b); return *(uint32_t*)&p;
}
__device__ __forceinline__ float bfr(float v) { return bfhi(pack2(v, v)); }
__device__ __forceinline__ float silu_bf(float c) { return bfr(__fdividef(c, 1.f + __expf(-c))); }
#define fbits(v) ((__float_as_uint(v) & ~1u) | par)
__device__ __forceinline__ uint32_t pack2t(float a, float b, unsigned par) {
  const uint32_t ua = ((__float_as_uint(a) + ((par ^ 1) << 16)) & 0xFFFE0000u) | (par << 16);
  return __byte_perm(ua, pack2(b, b), 0x7632);
}
__device__ __forceinline__ void nbar(int id, int n) { asm volatile("bar.sync %0, %1;" ::"r"(id), "r"(n) : "memory"); }
__device__ __forceinline__ void nbar_arrive(int id, int n) { asm volatile("bar.arrive %0, %1;" ::"r"(id), "r"(n) : "memory"); }
__device__ __forceinline__ uint4 ldc16(const void* p) {
  uint4 v; asm volatile("ld.relaxed.cta.global.v4.u32 {%0,%1,%2,%3}, [%4];" : "=r"(v.x), "=r"(v.y), "=r"(v.z), "=r"(v.w) : "l"(p) : "memory"); return v;
}
__device__ __forceinline__ unsigned ldc4(const void* p) {
  unsigned v; asm volatile("ld.relaxed.cta.global.u32 %0, [%1];" : "=r"(v) : "l"(p) : "memory"); return v;
}
__device__ __forceinline__ uint4 ldx16(const void* p) {
  uint4 v; asm volatile("ld.relaxed.gpu.global.v4.u32 {%0,%1,%2,%3}, [%4];" : "=r"(v.x), "=r"(v.y), "=r"(v.z), "=r"(v.w) : "l"(p) : "memory"); return v;
}
__device__ __forceinline__ unsigned ldx4(const void* p) {
  unsigned v; asm volatile("ld.relaxed.gpu.global.u32 %0, [%1];" : "=r"(v) : "l"(p) : "memory"); return v;
}
__device__ __forceinline__ unsigned long long ldx64(const void* p) {
  unsigned long long v; asm volatile("ld.relaxed.gpu.global.u64 %0, [%1];" : "=l"(v) : "l"(p) : "memory"); return v;
}
__device__ __forceinline__ void stx16(void* p, uint4 v) {
  asm volatile("st.relaxed.gpu.global.v4.u32 [%0], {%1,%2,%3,%4};" ::"l"(p), "r"(v.x), "r"(v.y), "r"(v.z), "r"(v.w) : "memory");
}
__device__ __forceinline__ void stx8(void* p, uint2 v) { asm volatile("st.relaxed.gpu.global.v2.u32 [%0], {%1,%2};" ::"l"(p), "r"(v.x), "r"(v.y) : "memory"); }
__device__ __forceinline__ void stx4(void* p, unsigned v) { asm volatile("st.relaxed.gpu.global.u32 [%0], %1;" ::"l"(p), "r"(v) : "memory"); }
__device__ __forceinline__ void pub4(void* p, unsigned v) { asm volatile("red.relaxed.gpu.global.xor.b32 [%0], %1;" ::"l"(p), "r"(v) : "memory"); }
__device__ __forceinline__ void pub8(void* p, unsigned lo, unsigned hi) {
  asm volatile("{.reg .b64 t; mov.b64 t, {%1, %2}; red.relaxed.gpu.global.xor.b64 [%0], t;}" ::"l"(p), "r"(lo), "r"(hi) : "memory");
}
__device__ __forceinline__ unsigned lop_x3(unsigned a, unsigned b, unsigned c) {
  unsigned d; asm("lop3.b32 %0, %1, %2, %3, 0x7E;" : "=r"(d) : "r"(a), "r"(b), "r"(c)); return d; }
__device__ __forceinline__ unsigned or3(unsigned a, unsigned b, unsigned c) {
  unsigned d; asm("lop3.b32 %0, %1, %2, %3, 0xFE;" : "=r"(d) : "r"(a), "r"(b), "r"(c)); return d; }
__device__ __forceinline__ unsigned and3(unsigned a, unsigned b, unsigned c) {
  unsigned d; asm("lop3.b32 %0, %1, %2, %3, 0x80;" : "=r"(d) : "r"(a), "r"(b), "r"(c)); return d; }
__device__ __forceinline__ unsigned dep16(const uint32_t* f) {
  unsigned d = 0;
#pragma unroll
  for (int i = 0; i < 8; i++) d = or3(d, f[8 * i], f[8 * i + 4]);
  return d;
}
__device__ __forceinline__ uint2 ldx8(const void* p) {
  uint2 v; asm volatile("{.reg .b64 t; ld.relaxed.gpu.global.b64 t, [%2]; mov.b64 {%0, %1}, t;}" : "=r"(v.x), "=r"(v.y) : "l"(p) : "memory"); return v;
}
__device__ __forceinline__ float lds4(uint32_t a) { float v; asm volatile("ld.shared.f32 %0, [%1];" : "=f"(v) : "r"(a) : "memory"); return v; }
__device__ __forceinline__ float shx(float v, int m) {
  float r; asm volatile("shfl.sync.bfly.b32 %0, %1, %2, 0x1f, 0xffffffff;" : "=f"(r) : "f"(v), "r"(m)); return r;
}
__device__ __forceinline__ uint32_t mbar_test(uint32_t bar, uint32_t ph) {
  uint32_t ok;
  asm volatile("{.reg .pred p; mbarrier.test_wait.parity.shared::cta.b64 p, [%1], %2; vote.sync.all.pred p, p, 0xffffffff; selp.u32 %0, 1, 0, p;}"
               : "=r"(ok) : "r"(bar), "r"(ph) : "memory");
  return ok;
}
#define X16(v) (lop_x3(v.x, v.y, par) | lop_x3(v.z, v.w, par))
#define RETRY(bad) if (!__any_sync(~0u, (bad) & 1) || ++it_ >= SPIN_MAX) break;
#define POLL _Pragma("unroll 1") for (int it_ = 0;;)
__device__ __forceinline__ void mbar_wait(uint32_t bar, uint32_t ph = 0) {
  asm volatile("{.reg .pred p; .reg .u32 n; mov.u32 n, 0;\n"
               "W%=: mbarrier.try_wait.parity.shared::cta.b64 p, [%0], %1; add.u32 n, n, 1; setp.lt.and.u32 p, n, 0x100000, !p; @p bra W%=;}"
               ::"r"(bar), "r"(ph) : "memory");
}
__device__ __forceinline__ float ex2(float v) { float r; asm("ex2.approx.ftz.f32 %0, %1;" : "=f"(r) : "f"(v)); return r; }
__device__ __forceinline__ float rcp(float v) { float r; asm("rcp.approx.ftz.f32 %0, %1;" : "=f"(r) : "f"(v)); return r; }
__device__ __forceinline__ void mma16(float* d, const uint32_t* a, uint32_t b0, uint32_t b1) {
  asm volatile("mma.sync.aligned.m16n8k16.row.col.f32.bf16.bf16.f32 {%0,%1,%2,%3}, {%4,%5,%6,%7}, {%8,%9}, {%0,%1,%2,%3};"
               : "+f"(d[0]), "+f"(d[1]), "+f"(d[2]), "+f"(d[3]) : "r"(a[0]), "r"(a[1]), "r"(a[2]), "r"(a[3]), "r"(b0), "r"(b1));
}
__device__ __forceinline__ void mma16c(float* d, const uint32_t* a, uint32_t b0, uint32_t b1, const float* c) {
  asm volatile("mma.sync.aligned.m16n8k16.row.col.f32.bf16.bf16.f32 {%0,%1,%2,%3}, {%4,%5,%6,%7}, {%8,%9}, {%10,%11,%12,%13};"
               : "=f"(d[0]), "=f"(d[1]), "=f"(d[2]), "=f"(d[3])
               : "r"(a[0]), "r"(a[1]), "r"(a[2]), "r"(a[3]), "r"(b0), "r"(b1), "f"(c[0]), "f"(c[1]), "f"(c[2]), "f"(c[3]));
}
__device__ __forceinline__ float4 lds16(uint32_t a) {
  float4 v; asm volatile("ld.shared.v4.f32 {%0,%1,%2,%3}, [%4];" : "=f"(v.x), "=f"(v.y), "=f"(v.z), "=f"(v.w) : "r"(a) : "memory"); return v;
}
__device__ __forceinline__ uint4 ldsv16(uint32_t a) {
  uint4 v; asm volatile("ld.relaxed.cluster.shared.v4.u32 {%0,%1,%2,%3}, [%4];" : "=r"(v.x), "=r"(v.y), "=r"(v.z), "=r"(v.w) : "r"(a) : "memory"); return v;
}
__device__ __forceinline__ void sts4(uint32_t a, float v) { asm volatile("st.shared.f32 [%0], %1;" ::"r"(a), "f"(v) : "memory"); }
__device__ __forceinline__ void sts16(uint32_t a, uint4 v) {
  asm volatile("st.shared.v4.b32 [%0], {%1,%2,%3,%4};" ::"r"(a), "r"(v.x), "r"(v.y), "r"(v.z), "r"(v.w) : "memory");
}
__device__ __forceinline__ void ldsm_t(uint32_t* r, uint32_t a) {
  asm volatile("ldmatrix.sync.aligned.m8n8.x4.trans.shared.b16 {%0,%1,%2,%3}, [%4];" : "=r"(r[0]), "=r"(r[1]), "=r"(r[2]), "=r"(r[3]) : "r"(a) : "memory");
}
__device__ __forceinline__ void ldsm(uint32_t* r, uint32_t a) {
  asm volatile("ldmatrix.sync.aligned.m8n8.x4.shared.b16 {%0,%1,%2,%3}, [%4];" : "=r"(r[0]), "=r"(r[1]), "=r"(r[2]), "=r"(r[3]) : "r"(a) : "memory");
}
__device__ __forceinline__ uint32_t mapa(uint32_t a, uint32_t r) {
  uint32_t v; asm volatile("mapa.shared::cluster.u32 %0, %1, %2;" : "=r"(v) : "r"(a), "r"(r)); return v;
}
__device__ __forceinline__ unsigned long long mapg(uint32_t a, uint32_t r) {
  unsigned long long v;
  asm volatile("{.reg .u32 t; .reg .u64 u; mapa.shared::cluster.u32 t, %1, %2; cvt.u64.u32 u, t; cvta.shared::cluster.u64 %0, u;}" : "=l"(v) : "r"(a), "r"(r));
  return v;
}
template <int N>
__device__ __forceinline__ void tred(float* a, int lane, int m) {
  const bool hi = lane & m;
#pragma unroll
  for (int i = 0; i < N; i++) {
    float send = hi ? a[i] : a[i + N], keep = hi ? a[i + N] : a[i];
    a[i] = keep + __shfl_xor_sync(~0u, send, m);
  }
}
template <int N>
__device__ __forceinline__ void tmax(float* a, int lane, int m) {
  const bool hi = lane & m;
#pragma unroll
  for (int i = 0; i < N; i++) {
    float send = hi ? a[i] : a[i + N], keep = hi ? a[i + N] : a[i];
    a[i] = fmaxf(keep, __shfl_xor_sync(~0u, send, m));
  }
}
__device__ __forceinline__ void arrive_n(uint32_t bar, bool on, int cnt) {
  asm volatile("{.reg .pred p; setp.ne.s32 p, %1, 0; @p mbarrier.arrive.shared::cta.b64 _, [%0], %2;}" ::"r"(bar), "r"((int)on), "r"(cnt) : "memory");
}
__device__ __forceinline__ unsigned long long stream_policy() {
  unsigned long long p;
  asm volatile("createpolicy.fractional.L2::evict_first.b64 %0, 1.0;" : "=l"(p));
  return p;
}
__device__ __forceinline__ void tma3d(uint32_t dst, const CUtensorMap* tm, uint32_t bar, int c0, int c1, int c2) {
  asm volatile("cp.async.bulk.tensor.3d.shared::cluster.global.mbarrier::complete_tx::bytes.L2::cache_hint [%0], [%1, {%3, %4, %5}], [%2], %6;"
               ::"r"(dst), "l"(tm), "r"(bar), "r"(c0), "r"(c1), "r"(c2), "l"(stream_policy()) : "memory");
}
__device__ __forceinline__ void spin_until(unsigned t) { while ((int)((unsigned)clock() - t) < 0) {} }
__device__ __forceinline__ void wait_until(unsigned t) {
  unsigned now;
  do { asm volatile("mov.u32 %0, %%globaltimer_lo;" : "=r"(now)); } while ((int)(now - t) < 0);
}
__device__ __forceinline__ void sleep_until(unsigned t) {
  unsigned now;
#pragma unroll 1
  do {
    __nanosleep(200);
    asm volatile("mov.u32 %0, %%globaltimer_lo;" : "=r"(now));
  } while ((int)(now - t) < 0);
}
#define PIN(x) asm volatile("" : "+r"(x))
#define PINL(x) asm volatile("" : "+l"(x))
#define BAR_ARRIVE(i) asm volatile("mbarrier.arrive.shared::cta.b64 _, [%0];" ::"r"(bar0 + 8 * (i)) : "memory")
#define CNT_ADD(c) asm volatile("red.relaxed.gpu.global.inc.u32 [%0], 0xffffffff;" ::"l"(scr->cnt + (c)) : "memory")
#define BAR_INIT(i, cnt) asm volatile("mbarrier.init.shared::cta.b64 [%0], %1;" ::"r"(bar0 + 8 * (i)), "r"(cnt) : "memory")
#define BAR_ARM(i, bytes) asm volatile("mbarrier.arrive.expect_tx.shared::cta.b64 _, [%0], %1;" ::"r"(bar0 + 8 * (i)), "r"(bytes) : "memory")
struct TMaps { CUtensorMap m[9]; };

#define NCTA9 120
#define TAU 20
#define NSL 100
#define NPE 2
#define WTEST 600
#define QN 4
#define FDLY 60
#define NPO 3
#define VDLY 150
#define O_Q 131072
#define O_LZ 163840
#define O_CTX 196608
#define O_HZ 198656
#define O_HW 200704
#define O_X 201728
#define O_P 218112
#define O_B 222208
#define O_R 224512
#define O_SILU 228608
#define O_SM 229632
#define O_BAR 231424
#define O_EP (O_BAR + 256)
#define O_DBG (O_EP + 16)
#define SMEM9 (O_DBG + 144)
#define B_FULL 0
#define B_FM 8
#define B_EMPTY 10
#define B_EM 18
#define B_LZ 18
#define B_Q2 19
#define B_H 20
#define B_QF 21
#define B_TAB 22
#define B_W 23
#define B_ST 24
#define B_HZ 25
#define B_WZ 26
#define B_G2 28
#define B_G 27
enum { T_WQ, T_WUK, T_KV, T_MOD, T_UV, T_WO, T_GU, T_DN = 8 };
#define NBIG 40
struct Sched { unsigned zero, dth; uint2 r[3][8]; unsigned nr[3], nt[3], dt, t4, d4, d6; };

struct __align__(128) Scratch {
  unsigned cnt[8 * 32];
  uint2 rec[32 * 4 * 8 * 64];
  uint2 hdr[32 * 16];
  unsigned h[8 * 256];
  uint4 qa[2048];
  unsigned xao[8 * 512];
  unsigned xab[8 * 256];
  unsigned xm[2048];
};
__device__ Scratch g_scr;
#define SMEM_BASE 1024u
#define DSC ((SMEM_BASE >> 4) | (1u << 16))
#define HI128 (64u | (1u << 30))
#define HI64 (32u | (2u << 30))
template <int TA, int TB, unsigned HIA, unsigned HIB>
__device__ __forceinline__ void wgmma32(float* d, uint32_t da, uint32_t db, int acc) {
  asm volatile("{.reg .pred p; .reg .b64 da, db; setp.ne.b32 p, %18, 0; mov.b64 da, {%16, %21}; mov.b64 db, {%17, %22};\n"
               "wgmma.mma_async.sync.aligned.m64n32k16.f32.bf16.bf16 "
               "{%0,%1,%2,%3,%4,%5,%6,%7,%8,%9,%10,%11,%12,%13,%14,%15}, da, db, p, 1, 1, %19, %20;}"
               : "+f"(d[0]), "+f"(d[1]), "+f"(d[2]), "+f"(d[3]), "+f"(d[4]), "+f"(d[5]), "+f"(d[6]), "+f"(d[7]),
                 "+f"(d[8]), "+f"(d[9]), "+f"(d[10]), "+f"(d[11]), "+f"(d[12]), "+f"(d[13]), "+f"(d[14]), "+f"(d[15])
               : "r"(da), "r"(db), "r"(acc), "n"(TA), "n"(TB), "n"(HIA), "n"(HIB));
}
__device__ __forceinline__ void wgmma32r(float* d, const uint32_t* a, uint32_t db) {
  asm volatile("{.reg .b64 db; mov.b64 db, {%20, %21};\n"
               "wgmma.mma_async.sync.aligned.m64n32k16.f32.bf16.bf16 "
               "{%0,%1,%2,%3,%4,%5,%6,%7,%8,%9,%10,%11,%12,%13,%14,%15}, {%16,%17,%18,%19}, db, 1, 1, 1, 1;}"
               : "+f"(d[0]), "+f"(d[1]), "+f"(d[2]), "+f"(d[3]), "+f"(d[4]), "+f"(d[5]), "+f"(d[6]), "+f"(d[7]),
                 "+f"(d[8]), "+f"(d[9]), "+f"(d[10]), "+f"(d[11]), "+f"(d[12]), "+f"(d[13]), "+f"(d[14]), "+f"(d[15])
               : "r"(a[0]), "r"(a[1]), "r"(a[2]), "r"(a[3]), "r"(db), "n"(HI64));
}
template <int N> __device__ __forceinline__ void wg_wait(float* a) {
  asm volatile("wgmma.wait_group.sync.aligned %16;"
               : "+f"(a[0]), "+f"(a[1]), "+f"(a[2]), "+f"(a[3]), "+f"(a[4]), "+f"(a[5]), "+f"(a[6]), "+f"(a[7]), "+f"(a[8]), "+f"(a[9]), "+f"(a[10]),
                 "+f"(a[11]), "+f"(a[12]), "+f"(a[13]), "+f"(a[14]), "+f"(a[15]) : "n"(N) : "memory");
}
__device__ __forceinline__ float sum8(uint32_t a) {
  const float4 p = lds16(a), q = lds16(a + 1024);
  return ((p.x + p.y) + (p.z + p.w)) + ((q.x + q.y) + (q.z + q.w));
}
__device__ __forceinline__ int posof(int c) { return (c & ~14) + 2 * (c & 6) + ((c >> 2) & 2); }

__global__ void __cluster_dims__(8, 1, 1) __launch_bounds__(384, 1)
fused_kernel(const bf16* __restrict__ x, const bf16* __restrict__ cvec, const bf16* __restrict__ w_mod, bf16* __restrict__ out,
             Scratch* __restrict__ scr, const __grid_constant__ Sched sch, const __grid_constant__ TMaps tms) {
  extern __shared__ __align__(1024) unsigned char smem[];
  const int tid = threadIdx.x, warp = __shfl_sync(~0u, tid >> 5, 0), lane = tid & 31;
  const int b = blockIdx.x, cl = b >> 3, rn = b & 7, rk = b & 1, hd = b >> 1, f = b - 64;
  const bool isA = b < 64;
  uint32_t sb = s2u(smem), bar0 = sb + O_BAR;
  unsigned gt_start;
  asm volatile("mov.u32 %0, %%globaltimer_lo;" : "=r"(gt_start));
  const int g = lane >> 2, tq = lane & 3;
  const int arow = 64 * rn + ((tid & 255) >> 4);
  uint4 wm[4];
  uint32_t cw, xw;
  if (warp < 8 && isA) {
    const bf16* wa = w_mod + (size_t)arow * 3072 + (lane & 8) * 64 + 64 * cl + 8 * (lane & 7);
#pragma unroll
    for (int i = 0; i < 4; i++) wm[i] = ldx16(wa + i * 16 * 3072);
    cw = ldc4(cvec + (arow & ~1) + 16 * tq);
    if (warp < 2) xw = ldc4(x + 64 * cl + (tid & 62));
  }
  if (warp == 11) {
    if (lane == 0) {
#pragma unroll
      for (int i = 0; i < B_EMPTY; i++) BAR_INIT(i, 1);
    }
    __syncwarp();
    asm volatile("fence.mbarrier_init.release.cluster;" ::: "memory");
    asm volatile("barrier.cluster.arrive.relaxed.aligned;" ::: "memory");
    if (isA) {
#pragma unroll 1
      for (int i = 0; i < 8; i++) {
        if (i >= 6) mbar_wait(bar0 + 8 * (i - 6));
        wait_until(gt_start + ((64 * i + b) * sch.dth >> 8));
        if (lane == 0) {
          BAR_ARM(i, 16384);
          tma3d(sb + i * 16384, &tms.m[i >> 2], bar0 + 8 * i, 0, i < 4 ? 128 * i : 256 * rk + 64 * (i - 4), i < 4 ? b : b & ~1);
        }
        __syncwarp();
      }
    }
  }
  if (warp == 10) {
    const unsigned ep = ldc4(&scr->cnt[0]);
    if (isA) {
      const uint4 xa = ldc16(x + 16 * lane), xb = ldc16(x + 16 * lane + 8);
      float xv[16] = {bflo(xa.x), bfhi(xa.x), bflo(xa.y), bfhi(xa.y), bflo(xa.z), bfhi(xa.z), bflo(xa.w), bfhi(xa.w),
                      bflo(xb.x), bfhi(xb.x), bflo(xb.y), bfhi(xb.y), bflo(xb.z), bfhi(xb.z), bflo(xb.w), bfhi(xb.w)};
      const float x0 = __shfl_sync(~0u, xv[0], 0);
      float s = 0, q = 0;
#pragma unroll
      for (int i = 0; i < 16; i++) { xv[i] -= x0; s += xv[i]; q += xv[i] * xv[i]; }
#pragma unroll
      for (int o = 16; o; o >>= 1) { s += __shfl_xor_sync(~0u, s, o); q += __shfl_xor_sync(~0u, q, o); }
      s *= 1.f / 512.f;
      float rstd;
      asm("rsqrt.approx.ftz.f32 %0, %1;" : "=f"(rstd) : "f"(fmaxf(q * (1.f / 512.f) - s * s, 0.f) + 1e-5f));
      *(float2*)(smem + O_SM + 1024) = make_float2(s + x0, rstd);
    }
    if (lane == 0) *(volatile unsigned*)(smem + O_EP) = ep;
    nbar_arrive(1, 288);
  }
  const int cls = isA ? (b >= NBIG) : 2, v0 = isA ? 2 : 0;
  if (warp >= 8) {
    asm volatile("setmaxnreg.dec.sync.aligned.u32 56;");
    if (warp == 8) {
      if (lane < 8) asm volatile("prefetch.tensormap [%0];" ::"l"(&tms.m[lane + 1]) : "memory");
      if ((sb & 0xFFFFFF) != SMEM_BASE) __trap();
    } else if (warp == 9) {
      if (lane == 0) {
#pragma unroll
        for (int i = B_EMPTY; i < B_EM; i++) BAR_INIT(i, 8);
        BAR_INIT(B_LZ, 8); BAR_INIT(B_Q2, 9); BAR_ARM(B_Q2, 1024);
        BAR_INIT(B_H, 1); BAR_INIT(B_QF, 1); BAR_ARM(B_QF, 32768);
        BAR_INIT(B_TAB, 1); BAR_INIT(B_W, 1); BAR_INIT(B_ST, 8); BAR_INIT(B_WZ, 1); BAR_INIT(B_G, 1); BAR_INIT(B_G2, 1);
      }

    }
    if (warp != 11) {
      __syncwarp();
      asm volatile("fence.mbarrier_init.release.cluster;" ::: "memory");
      __threadfence_block();
      asm volatile("barrier.cluster.arrive.relaxed.aligned;" ::: "memory");
    }
    asm volatile("barrier.cluster.wait.acquire.aligned;" ::: "memory");
    if (warp == 8) {
      const int nr = sch.nr[cls], vl = v0 + sch.nt[cls] - 1;
      unsigned long long hist = 0;
      int v = v0;
#pragma unroll 1
      for (int rd = 0; rd < nr; rd++) {
        const uint2 e = sch.r[cls][rd];
        const int type = e.y & 15, win = (e.y >> 4) & 15, pos = b + 64 - (int)((e.y >> 8) & 255), tile = e.y >> 16;
        const bool mod = type == T_MOD;
        const int ni = mod ? 1 : type == T_DN ? 2 : 4;
        unsigned t = gt_start + (e.x & 0xffff) + (pos * sch.dt >> 8);
        const int c0 = mod ? 1024 + 32 * b : type == T_WO || type == T_DN ? 64 * rn : type == T_GU ? 32 * f : 0;
        int c1 = type == T_KV ? 64 * (tile + pos) : 0;
        int c2 = mod ? tile : type == T_WO ? 4 * cl : type == T_DN ? 2 * cl - 16 : type == T_UV ? b : 0;
        const int i1 = type == T_UV ? 128 : 0;
#pragma unroll 1
        for (int j = 0; j < ni; j++) {
          const int slot = mod ? B_FM + tile : (v & 1) * 4 + j;
          if (mod ? tile : v >= 2) mbar_wait(bar0 + 8 * (B_EMPTY + (mod ? (vl & 1) * 4 : slot)), mod ? (vl >> 1) & 1 : ((v >> 1) - 1) & 1);
          const int hw = (int)(hist >> (6 * (win - 1))) & 63;
          if (hw) mbar_wait(bar0 + 8 * (hw & 15), (hw >> 4) & 1);
          wait_until(t);
          if (lane == 0) {
            BAR_ARM(slot, 16384);
            tma3d(sb + (mod ? (tile ? O_Q : O_X) : slot * 16384), &tms.m[type == T_GU ? type + (j & 1) : type], bar0 + 8 * slot, c0, c1, c2);
          }
          __syncwarp();
          hist = hist << 6 | (32 | (mod ? 0 : (v & 2) << 3) | slot);
          t += e.x >> 16; c1 += i1;
          c2 += type == T_KV ? 2 : type == T_WO || type == T_DN ? 1 : type == T_GU ? j & 1 : 0;
        }
        v += !mod;
      }
      return;
    }
    const unsigned epoch = *(volatile unsigned*)(smem + O_EP), par = (epoch + 1) & 1;
    if (warp == 10) {
      if (isA) {
        for (int it = 0; ldx4(scr->cnt + 1) != (epoch + 1) * 128 && it < SPIN_MAX; it++) {}
        if (lane == 0) BAR_ARRIVE(B_H);
      } else mbar_wait(bar0);
      if (!(rn & (QN - 1))) {
        for (int it = 0; ldx4(scr->cnt + 32 + 32 * (rn >> 2)) != (epoch + 1) * 32 && it < SPIN_MAX; it++) {}
        if (lane == 0)
          asm volatile("cp.async.bulk.shared::cluster.global.mbarrier::complete_tx::bytes.multicast::cluster [%0], [%1], %4, [%2], %3;"
                       ::"r"(sb + O_Q + rn * 4096), "l"(scr->qa + rn * 256), "r"(bar0 + 8 * B_QF), "h"((unsigned short)0xff), "n"(4096 * QN) : "memory");
      }
      const unsigned dl = isA ? sch.d4 : sch.d6;
      unsigned tw = gt_start + sch.t4;
      if (!isA) {
        const int nt = sch.nt[2];
#pragma unroll 1
        for (int t = 0; t < nt; t++) mbar_wait(bar0 + 8 * B_EMPTY + (t & 1) * 32, (t >> 1) & 1);
        unsigned long long now;
        asm volatile("mov.u64 %0, %%globaltimer;" : "=l"(now));
        if (lane == 0) { asm volatile("red.relaxed.gpu.global.max.u64 [%0], %1;" ::"l"(scr->cnt + 130), "l"(now) : "memory"); CNT_ADD(128); }
        tw = (unsigned)now + 1700;
      }
      sleep_until(tw);
      uint4 an;
      for (int it = 0; an = ldx16(scr->cnt + 128), an.x != (epoch + 1) * 56 && it < SPIN_MAX; it++) {}
      wait_until(an.z + (dl >> 16));
      if (lane == 0) BAR_ARRIVE(B_G2);
      wait_until(an.z + (dl & 0xffff));
      if (lane == 0) BAR_ARRIVE(B_G);
    } else if (warp == 11) {
      {
        uint2* ph = scr->hdr + ((lane & 24) + 2 * tq + (g & 1)) * 16 + cl;
        const bool own = (lane >> 4) * 4 + tq == rn;
        if (own) { stx8(ph, make_uint2(par ^ 1, 0)); if (cl == 14) stx8(ph + 1, make_uint2(0, 0)); }
        uint32_t a_w = sb + O_HW + ((lane >> 4) * 4 + tq) * 128 + (g & 1) * 64 + ((lane >> 1) & 4);
        PIN(a_w); PINL(ph);
        const int vt = v0 + sch.nt[cls];
#pragma unroll 1
        for (int t = 0; t < vt; t++) mbar_wait(bar0 + 8 * B_EMPTY + (t & 1) * 32, (t >> 1) & 1);
        float hz[8], M;
        uint32_t wp[4];
#pragma unroll 1
        for (int e = 0; e < 2; e++) {
          POLL {
            unsigned ok = 1;
#pragma unroll
            for (int u = 0; u < 8; u++)
              asm volatile("ld.relaxed.cluster.shared.f32 %0, [%1];" : "=f"(hz[u]) : "r"(sb + O_HZ + e * 1024 + u * 128 + lane * 4) : "memory");
#pragma unroll
            for (int u = 0; u < 4; u++) ok = and3(ok, __float_as_uint(hz[u]), __float_as_uint(hz[u + 4]));
            RETRY(~ok)
          }
          if (e) break;
          M = fmaxf(fmaxf(fmaxf(hz[0], hz[1]), fmaxf(hz[2], hz[3])), fmaxf(fmaxf(hz[4], hz[5]), fmaxf(hz[6], hz[7])));
          M = u2f(fbits(M));
#pragma unroll
          for (int u = 0; u < 4; u++) {
            wp[u] = pack2(ex2(hz[u] - M), ex2(hz[u + 4] - M));
            sts4(a_w + ((rn - u) & 3) * 8, u2f(wp[u])); sts4(a_w + ((rn - u) & 3) * 8 + 32, u2f(wp[u]));
          }
          __syncwarp();
          if (lane == 0) BAR_ARRIVE(B_WZ);
        }
        float L = 0.f;
#pragma unroll
        for (int u = 0; u < 4; u++) L += bflo(wp[u]) * hz[u] + bfhi(wp[u]) * hz[u + 4];
        if (own) pub8(ph, __float_as_uint(M) | 1u, __float_as_uint(L));
      }
      if (isA) {
        mbar_wait(bar0 + 8 * B_G2);
        unsigned long long hh;
        POLL { hh = ldx64(scr->hdr + hd * 16 + (lane & 15)); RETRY((lane & 15) == 15 ? 0u : (unsigned)hh ^ par) }
        const float m = (lane & 15) == 15 ? -1e30f : u2f((unsigned)hh);
        int mi = __float_as_int(m);
        mi ^= (mi >> 31) & 0x7fffffff;
        mi = __reduce_max_sync(~0u, mi);
        mi ^= (mi >> 31) & 0x7fffffff;
        const float w = ex2(m - __int_as_float(mi));
        float L = w * u2f(hh >> 32);
#pragma unroll
        for (int o2 = 8; o2; o2 >>= 1) L += __shfl_xor_sync(~0u, L, o2);
        sts4(sb + O_SM + (384 + 2 * (lane & 6) + ((lane >> 2) & 2) + (lane & 1)) * 4, w * rcp(L));
        __syncwarp();
        if (lane == 0) BAR_ARRIVE(B_W);
      }
    } else {
#pragma unroll 4
      for (int i = 0; i < 72; i++) sts16(sb + O_LZ + i * 512 + lane * 16, make_uint4(0, 0, 0, 0));
      __syncwarp();
      if (lane < 8) asm volatile("mbarrier.arrive.release.cluster.shared::cluster.b64 _, [%0];" ::"r"(mapa(bar0 + 8 * B_LZ, lane)) : "memory");
      if (isA) {
        mbar_wait(bar0 + 8 * B_QF);
#pragma unroll 2
        for (int k = 0; k < 8; k++) {
          const uint32_t cp = ldc4(cvec + 2 * (lane + 32 * k));
          *(uint32_t*)(smem + O_SILU + (lane + 32 * k) * 4) = pack2(silu_bf(bflo(cp)), silu_bf(bfhi(cp)));
        }
        __syncwarp();
        uint32_t ab = sb + O_X + (8 * (lane >> 4) + (lane & 7)) * 64 + ((((lane >> 3) & 1) ^ ((lane >> 1) & 3)) << 4);
        float d[4][4] = {};
#pragma unroll 1
        for (int jm = 0; jm < 2; jm++) {
          mbar_wait(bar0 + 8 * (B_FM + jm));
#pragma unroll 2
          for (int s2 = 0; s2 < 8; s2++)
#pragma unroll
            for (int s = 0; s < 2; s++) {
              uint32_t a0[4], a1[4];
              const uint32_t* ps = (const uint32_t*)(smem + O_SILU) + 128 * jm + 16 * s2 + 8 * s + tq;
              ldsm_t(a0, ab + (2 * s2 + s) * 1024); ldsm_t(a1, (ab + (2 * s2 + s) * 1024) ^ 32);
              mma16(d[s], a0, ps[0], ps[4]); mma16(d[2 + s], a1, ps[0], ps[4]);
            }
          ab -= O_X - O_Q;
        }
        const float t0 = (tq & 1) ? d[0][2] + d[1][2] : d[0][0] + d[1][0], t1 = (tq & 1) ? d[2][2] + d[3][2] : d[2][0] + d[3][0];
        stx4(scr->xm + b * 32 + posof(8 * tq + g), fbits(bfr(bfr((tq & 2) ? t1 : t0) + ((b >> 4) == 2 ? 1.f : 0.f))));
        __syncwarp();
        if (lane == 0) CNT_ADD(96);
      } else sleep_until(gt_start + sch.t4);
      for (int it = 0; ldx4(scr->cnt + 96) != (epoch + 1) * 64 && it < SPIN_MAX; it++) __nanosleep(NSL);
      if (isA) {
        unsigned long long ga;
        POLL { ga = ldx64(scr->xm + 64 * rn + 2 * lane); RETRY(lop_x3((unsigned)ga, ga >> 32, par)) }
        *(float2*)(smem + O_SM + (320 + 2 * lane) * 4) = make_float2(bfhi((unsigned)ga), bfhi(ga >> 32));
      }
      __syncwarp();
      if (lane == 0) BAR_ARRIVE(B_TAB);
    }
    return;
  }

  float* s_sm = (float*)(smem + O_SM);
  unsigned par, epoch;
  asm volatile("barrier.cluster.arrive.relaxed.aligned;" ::: "memory");
  if (isA) {
    float* s_r = (float*)(smem + O_R);
    float acc[8] = {0, 0, 0, 0, 0, 0, 0, 0};
    const float sl = silu_bf((arow & 1) ? bfhi(cw) : bflo(cw));
#pragma unroll
    for (int i = 0; i < 4; i++) fma8(acc, wm[i], __shfl_sync(~0u, sl, i, 4));
    tred<4>(acc, lane, 16);
    *(float4*)(s_r + warp * 128 + 8 * (lane & 15) + ((lane >> 2) & 4)) = make_float4(acc[0], acc[1], acc[2], acc[3]);
    nbar(1, 288);
    epoch = *(volatile unsigned*)(smem + O_EP);
    par = (epoch + 1) & 1;
    if (warp < 2) {
      float t = 0.f, ca = rn == 0 ? 1.f : 0.f;
#pragma unroll
      for (int w = 0; w < 8; w++) { t += s_r[w * 128 + tid]; ca += s_r[w * 128 + 64 + tid]; }
      t += ca * ((((tid & 1) ? bfhi(xw) : bflo(xw)) - s_sm[256]) * s_sm[257]);
      const float nb = __shfl_down_sync(~0u, t, 1);
      const uint32_t w0 = lane < 8 ? pack2t(t, nb, par) : pack2(t, nb);
      const uint32_t w1 = __shfl_down_sync(~0u, w0, 8), w2 = __shfl_down_sync(~0u, w0, 16), w3 = __shfl_down_sync(~0u, w0, 24);
      if (lane < 8 && !(lane & 1)) stx16(scr->h + (rn >> 1) * 512 + (2 * cl + warp) * 32 + rk * 16 + 2 * lane, make_uint4(w0, w1, w2, w3));
      __syncwarp();
      if (lane == 0) CNT_ADD(1);
    }
    asm volatile("barrier.cluster.wait.acquire.aligned;" ::: "memory");
    const uint32_t rsb = mapa(sb, rn ^ 1);
    {
      uint32_t a[4][4][4];
      mbar_wait(bar0 + 8 * (warp >> 1));
      const uint32_t ab = sb + (64 * warp + 8 * (lane >> 4) + (lane & 7)) * 128;
#pragma unroll
      for (int s = 0; s < 4; s++)
#pragma unroll
        for (int mt = 0; mt < 4; mt++) ldsm_t(a[s][mt], ab + s * 2048 + (((2 * mt + ((lane >> 3) & 1)) ^ (lane & 7)) << 4));
      arrive_n(bar0 + 8 * (B_EMPTY + (warp >> 1)), lane == 0, 4 + (dep16(&a[0][0][0]) & sch.zero));
      uint4 v0, v1;
      const unsigned* ph = scr->h + (g >> 1) * 512 + 64 * warp + 4 * (lane & 7);
      uint32_t off = O_B + warp * 272 + (32 * rk + 8 * tq + (lane & 4)) * 4;
      PIN(off); PINL(ph);
      mbar_wait(bar0 + 8 * B_H);
      POLL { v0 = ldx16(ph); v1 = ldx16(ph + 32); RETRY(lop_x3(v0.x, v1.x, par)) }
      float d[4][4] = {};
#pragma unroll
      for (int mt = 0; mt < 4; mt++) {
        mma16(d[mt], a[0][mt], v0.x, v0.y); mma16(d[mt], a[1][mt], v0.z, v0.w);
        mma16(d[mt], a[2][mt], v1.x, v1.y); mma16(d[mt], a[3][mt], v1.z, v1.w);
      }
      float r[8];
#pragma unroll
      for (int mt = 0; mt < 4; mt++) { r[2 * mt] = d[mt][0] + d[mt][1]; r[2 * mt + 1] = d[mt][2] + d[mt][3]; }
      tred<4>(r, lane, 2); tred<2>(r, lane, 1);
      const float rc = __shfl_xor_sync(~0u, (lane & 4) ? r[0] : r[1], 4);
      const uint32_t wd = (lane & 4) ? pack2(rc, r[1]) : pack2(r[0], rc);
      const uint32_t w1 = __shfl_down_sync(~0u, wd, 8), w2 = __shfl_down_sync(~0u, wd, 16), w3 = __shfl_down_sync(~0u, wd, 24);
      asm volatile("{.reg .pred p; setp.lt.s32 p, %7, 8; @p st.shared.v4.b32 [%0], {%2,%3,%4,%5};\n"
                   "@p st.async.shared::cluster.mbarrier::complete_tx::bytes.v4.b32 [%1], {%2,%3,%4,%5}, [%6];}"
                   ::"r"(sb + off), "r"(rsb + off), "r"(wd), "r"(w1), "r"(w2), "r"(w3), "r"(rsb + O_BAR + 8 * B_Q2), "r"(lane) : "memory");
      __syncwarp();
      arrive_n(bar0 + 8 * B_Q2, lane == 0, 1);
    }
    {
      uint32_t a[2][8][4];
      uint32_t a_bq = sb + O_B + (lane & 7) * 272 + (lane >> 3) * 16;
      uint4* p_qa = scr->qa + (4 * rk + (warp >> 1)) * 256 + hd * 8 + ((4 * (warp & 1) + tq) ^ (hd & 7));
      PIN(a_bq); PINL(p_qa);
      mbar_wait(bar0 + 8 * (4 + (warp >> 1)));
      const uint32_t ab = sb + 65536 + (warp >> 1) * 16384 + (32 * (warp & 1) + (lane & 15)) * 128;
#pragma unroll
      for (int i = 0; i < 16; i++) ldsm(a[i >> 3][i & 7], ab + (i >> 3) * 2048 + ((i >> 2) & 1) * 8192 + (((2 * (i & 3) + (lane >> 4)) ^ (lane & 7)) << 4));
      arrive_n(bar0 + 8 * (B_EMPTY + 4 + (warp >> 1)), lane == 0, 4 + (dep16(&a[0][0][0]) & sch.zero));
      mbar_wait(bar0 + 8 * B_Q2);
      float d[4][4] = {};
#pragma unroll
      for (int y = 0; y < 4; y++) {
        uint32_t bq[4];
        ldsm(bq, a_bq + 64 * y);
#pragma unroll
        for (int mt = 0; mt < 2; mt++) { mma16(d[2 * mt], a[mt][2 * y], bq[0], bq[1]); mma16(d[2 * mt + 1], a[mt][2 * y + 1], bq[2], bq[3]); }
      }
      float r[4];
#pragma unroll
      for (int i = 0; i < 4; i++) r[i] = (d[i & 2][2 * (i & 1)] + d[i & 2][2 * (i & 1) + 1]) + (d[(i & 2) + 1][2 * (i & 1)] + d[(i & 2) + 1][2 * (i & 1) + 1]);
      tred<2>(r, lane, 2); tred<1>(r, lane, 1);
      const float nb = __shfl_xor_sync(~0u, r[0], 4);
      const uint32_t w0 = (lane >> 3) == (hd & 3) ? pack2t(r[0], nb, par) : pack2(r[0], nb);
      const uint32_t w1 = __shfl_down_sync(~0u, w0, 8), w2 = __shfl_down_sync(~0u, w0, 16), w3 = __shfl_down_sync(~0u, w0, 24);
      if (lane < 4) stx16(p_qa, make_uint4(w0, w1, w2, w3));
      if (warp) nbar_arrive(3, 256); else { nbar(3, 256); if (lane == 0) CNT_ADD(32 + 32 * rk); }
    }
  } else {
    nbar(1, 288);
    epoch = *(volatile unsigned*)(smem + O_EP);
    par = (epoch + 1) & 1;
    asm volatile("barrier.cluster.wait.acquire.aligned;" ::: "memory");
    mbar_wait(bar0);
  }
  asm volatile("setmaxnreg.inc.sync.aligned.u32 224;");
  uint2* p_rec = scr->rec + ((16 * (warp >> 2) + 2 * (warp & 3) + (g & 1) + 4 * (tq & 2)) * 32 + 4 * rn + (tq & 1)) * 64 + cl * 4 + (g >> 1);
  PINL(p_rec);
  {
    const unsigned inv = par ^ 1;
#pragma unroll
    for (int q = 0; q < 2; q++) { stx8(p_rec + q * 128, make_uint2(inv, 0)); if (cl == 14) stx8(p_rec + q * 128 + 4, make_uint2(0, 0)); }
    if (isA) { if (warp < 2) { stx4(scr->xao + b * 64 + tid, inv); stx4(scr->xab + cl * 256 + (2 * (rn & 3) + warp) * 32 + (rn >> 2) * 16 + (lane >> 1), inv); } }
    else if (f == 0) { stx4(out + 2 * tid, 0); __threadfence(); }
  }
  sb = __shfl_sync(~0u, sb, 0); bar0 = sb + O_BAR;
  const int nt = sch.nt[cls], wg = warp >> 2;
  uint32_t a_z[4];
#pragma unroll
  for (int u = 0; u < 4; u++) {
    const int s3 = (rn - u - (lane >> 1 & 1)) & 3;
    a_z[u] = sb + O_LZ + (s3 + 4 * (lane & 1)) * 4096 + wg * 512 + g * 64 + (((warp & 3) ^ (s3 & 1) ^ (2 * (lane & 1))) << 4);
    PIN(a_z[u]);
  }
  uint32_t z[4][4], a_w = sb + O_HW + warp * 128 + (g & 1) * 64 + (tq & 1) * 8;
  PIN(a_w);
  {
    const float sc = 0.08838834764831845f * 1.4426950408889634f;
    float mrun = -1e30f;
    float o[4][16], sx[16], mref[8];
#pragma unroll
    for (int k = 0; k < 16; k++) { o[0][k] = o[1][k] = o[2][k] = o[3][k] = sx[k] = 0.f; mref[k >> 1] = -1e30f; }
    const int key = 16 * warp + (lane & 15);
    uint32_t a_p = sb + O_P + key * 64 + (((lane >> 4) ^ ((key >> 1) & 3)) << 4);
    uint32_t a_v = sb + wg * 32768 + (8 * (lane >> 4) + (lane & 7)) * 128 + (((2 * (warp & 3) + ((lane >> 3) & 1)) ^ (lane & 7)) << 4);
    const int rot = rn + warp;
    unsigned long long dst[4];
#pragma unroll
    for (int q = 0; q < 4; q++) {
      dst[q] = mapg(sb + O_LZ + rn * 4096 + (warp & 3) * 1024 + g * 64 + ((tq ^ (rn & 1) ^ ((rn >> 1) & 2)) << 4), 4 * wg + ((q + rot) & 3));
      PINL(dst[q]);
    }
    unsigned long long a_h = mapg(sb + O_HZ + wg * 1024 + rn * 128 + lane * 4, 2 * (warp & 3));
    unsigned long long a_h1 = mapg(sb + O_HZ + wg * 1024 + rn * 128 + lane * 4, 2 * (warp & 3) + 1);
    PIN(a_p); PIN(a_v); PINL(a_h); PINL(a_h1);
    uint32_t rel = lane < 4 && lane >= 2 * wg ? 2 - (tq >> 1) : 0;
    PIN(rel);
    uint32_t ones[4] = {0x3F803F80u, 0x3F803F80u, 0x3F803F80u, 0x3F803F80u};
    PIN(ones[0]); PIN(ones[1]); PIN(ones[2]); PIN(ones[3]);
    {
      asm volatile("{.reg .pred p; .reg .u32 n; mov.u32 n, 0;\n"
                   "W%=: mbarrier.try_wait.parity.acquire.cluster.shared::cta.b64 p, [%0], 0; add.u32 n, n, 1; setp.lt.and.u32 p, n, 0x100000, !p; @p bra W%=;}"
                   ::"r"(bar0 + 8 * B_LZ) : "memory");
      mbar_wait(bar0 + 8 * B_QF);
      unsigned bad = 0;
#pragma unroll
      for (int k = 0; k < 8; k++) bad |= __float_as_uint(lds4(sb + O_Q + k * 4096 + tid * 16 + (lane >> 3) * 4)) ^ par;
      if (__builtin_expect(__any_sync(~0u, bad & 1), 0)) {
#pragma unroll 1
        for (int k = 0; k < 8; k++) {
          uint4 v;
          POLL { v = ldx16(scr->qa + k * 256 + tid); RETRY(((lane & 16) ? ((lane & 8) ? v.w : v.z) : ((lane & 8) ? v.y : v.x)) ^ par) }
          sts16(sb + O_Q + k * 4096 + tid * 16, v);
        }
        asm volatile("fence.proxy.async.shared::cta;" ::: "memory");
      }
      if (warp >= 4) nbar_arrive(1, 256); else nbar(1, 256);
    }
#pragma unroll 1
    for (int t = 0; t < nt; t++) {
      const int v = v0 + t;
      const uint32_t fb = bar0 + (v & 1) * 32, ph = (v >> 1) & 1, av = a_v + (v & 1) * 65536;
      uint32_t vf[4][4][4], cnt;
      auto landed = [&]() {
        cnt = rel + (dep16(&vf[0][0][0]) & (nt >> 8));
        PIN(cnt);
      };
      if (wg == 0) {
        const uint32_t da = DSC + (v & 1) * 4096, db = DSC + O_Q / 16;
#pragma unroll
        for (int jj = 0; jj < 2; jj++) {
#pragma unroll 1
          for (int j = 2 * jj; j < 2 * jj + 2; j++) {
            mbar_wait(fb + 8 * j, ph);
            asm volatile("wgmma.fence.sync.aligned;" ::: "memory");
#pragma unroll
            for (int k = 0; k < 8; k++)
              wgmma32<0, 0, HI128, HI128>(sx, da + j * 1024 + (k >> 2) * 512 + (k & 3) * 2, db + j * 512 + (k >> 2) * 256 + (k & 3) * 2, jj || k ? 1 : j);
            asm volatile("wgmma.commit_group.sync.aligned;" ::: "memory");
          }
          if (jj == 0) {
#pragma unroll
            for (int i = 0; i < 16; i++) ldsm_t(vf[i >> 2][i & 3], av + (((i >> 2) + rot) & 3) * 8192 + (i & 3) * 2048);
            nbar(5, 256);
            landed();
          }
        }
      } else {
        nbar_arrive(5, 256);
#pragma unroll 1
        for (int j = 0; j < 2; j++) {
          mbar_wait(fb + 16 + 8 * j, ph);
          if (j) spin_until(clock() + VDLY);
#pragma unroll
          for (int q = 0; q < 4; q++)
            if (((q + rot) & 2) == 2 * j)
#pragma unroll
              for (int k = 0; k < 4; k++) ldsm_t(vf[q][k], av + ((q + rot) & 3) * 8192 + k * 2048);
        }
        cnt = 0;
      }
      wg_wait<0>(sx);
      asm volatile("{.reg .pred p; setp.ne.s32 p, %1, 0; @p mbarrier.arrive.shared::cta.b64 _, [%0], %1;}" ::"r"(fb + 8 * B_EMPTY + 8 * tq), "r"(cnt) : "memory");
#pragma unroll 1
      for (int pass = 0;; pass++) {
        int ex = !(t | pass);
        if (wg == 0 && (t | pass)) {
          uint32_t pk[8];
#pragma unroll
          for (int i = 0; i < 8; i++) pk[i] = pack2(ex2(sx[2 * i] * sc - mref[i & 6]), ex2(sx[2 * i + 1] * sc - mref[(i & 6) + 1]));
          asm volatile("stmatrix.sync.aligned.m8n8.x4.shared.b16 [%0], {%2,%3,%4,%5};\n"
                       "stmatrix.sync.aligned.m8n8.x4.shared.b16 [%1], {%6,%7,%8,%9};"
                       ::"r"(a_p), "r"(a_p ^ 32), "r"(pk[0]), "r"(pk[1]), "r"(pk[2]), "r"(pk[3]), "r"(pk[4]), "r"(pk[5]), "r"(pk[6]), "r"(pk[7]) : "memory");
          const uint32_t mx = __vmaxu2(__vmaxu2(__vmaxu2(pk[0], pk[1]), __vmaxu2(pk[2], pk[3])), __vmaxu2(__vmaxu2(pk[4], pk[5]), __vmaxu2(pk[6], pk[7])));
          ex = max(mx, mx << 16) > (127u + TAU) << 23;
          asm volatile("fence.proxy.async.shared::cta;" ::: "memory");
        }
        asm volatile("{.reg .pred p, q; setp.ne.s32 q, %0, 0; bar.red.or.pred p, 4, 256, q; selp.s32 %0, 1, 0, p;}" : "+r"(ex)::"memory");
        if (!ex || pass) break;
        int ln;
        asm volatile("mov.u32 %0, %%laneid;" : "=r"(ln));
        const uint32_t a_pm = sb + O_SM + ln * 16;
        if (wg == 0) {
          float cm[8];
#pragma unroll
          for (int i = 0; i < 8; i++) cm[i] = fmaxf(sx[2 * (i & 6) + (i & 1)], sx[2 * (i & 6) + (i & 1) + 2]);
          tmax<4>(cm, lane, 16); tmax<2>(cm, lane, 8); tmax<1>(cm, lane, 4);
          sts4(a_pm + warp * 4, cm[0] * sc);
        }
        nbar(4, 256);
        const float4 pm = lds16(a_pm);
        const float mn = u2f(__float_as_uint(fmaxf(fmaxf(fmaxf(pm.x, pm.y), fmaxf(pm.z, pm.w)), mrun)) | 1u), al = ex2(mrun - mn);
        mrun = mn;
#pragma unroll
        for (int i = 0; i < 8; i++) {
          const float a = __shfl_sync(~0u, al, 4 * i + (ln & 3)), aw = wg ? a : 1.f;
          mref[i] = __shfl_sync(~0u, mn, 4 * i + (ln & 3));
#pragma unroll
          for (int e = 0; e < 2; e++) {
            const int k = 2 * (i & 6) + (i & 1) + 2 * e;
            o[0][k] *= a; o[1][k] *= a; o[2][k] *= a; o[3][k] *= a; sx[k] *= aw;
          }
        }
      }
      float hv = mrun;
      if (wg) {
        asm volatile("wgmma.fence.sync.aligned;" ::: "memory");
#pragma unroll
        for (int k = 0; k < 4; k++) wgmma32r(sx, ones, DSC + O_P / 16 + k * 64);
        asm volatile("wgmma.commit_group.sync.aligned;" ::: "memory");
        landed();
        asm volatile("{.reg .pred p; setp.ne.s32 p, %1, 0; @p mbarrier.arrive.shared::cta.b64 _, [%0], %1;}" ::"r"(fb + 8 * B_EMPTY + 8 * tq), "r"(cnt) : "memory");
        wg_wait<0>(sx);
        float lv[4];
#pragma unroll
        for (int j = 0; j < 4; j++) lv[j] = (lane & 4) ? sx[4 * j + 1] : sx[4 * j];
        hv = (lane & 16) ? ((lane & 8) ? lv[3] : lv[2]) : ((lane & 8) ? lv[1] : lv[0]);
      }
      asm volatile("{.reg .pred p; setp.eq.s32 p, %3, %4; @p st.relaxed.cluster.b32 [%0], %1; @p st.relaxed.cluster.b32 [%2], %1;}"
                   ::"l"(a_h), "r"(__float_as_uint(hv) | 1u), "l"(a_h1), "r"(t), "r"(nt - 1) : "memory");
#pragma unroll
      for (int q = 0; q < 4; q++) {
        asm volatile("wgmma.fence.sync.aligned;" ::: "memory");
#pragma unroll
        for (int k = 0; k < 4; k++) wgmma32r(o[q], vf[q][k], DSC + O_P / 16 + k * 64);
        asm volatile("wgmma.commit_group.sync.aligned;" ::: "memory");
        if (q == 3) {
#pragma unroll
          for (int u = 0; u < 4; u++) ldsm_t(z[u], a_z[u] + u * 1024);
        }
        wg_wait<0>(o[q]);
#pragma unroll
        for (int j = 0; j < 2; j++)
          asm volatile("{.reg .pred p; setp.eq.s32 p, %5, %6; @p st.relaxed.cluster.v4.b32 [%0], {%1,%2,%3,%4};}"
                       ::"l"(dst[q] + j * 512), "r"(pack2t(o[q][8 * j], o[q][8 * j + 1], 1)), "r"(pack2(o[q][8 * j + 2], o[q][8 * j + 3])),
                         "r"(pack2(o[q][8 * j + 4], o[q][8 * j + 5])), "r"(pack2(o[q][8 * j + 6], o[q][8 * j + 7])), "r"(t), "r"(nt - 1) : "memory");
      }
    }
  }
  {
    uint32_t wx[4][4];
    mbar_wait(bar0 + 8 * B_WZ);
#pragma unroll
    for (int u = 0; u < 4; u++) {
      uint2 wp;
      asm volatile("ld.shared.v2.u32 {%0, %1}, [%2];" : "=r"(wp.x), "=r"(wp.y) : "r"(a_w + u * 8) : "memory");
      const bool lo = (g >> 1) == (tq >> 1), hi = (g >> 1) == 2 + (tq >> 1);
      wx[u][0] = lo ? wp.x : 0u; wx[u][1] = lo ? wp.y : 0u; wx[u][2] = hi ? wp.x : 0u; wx[u][3] = hi ? wp.y : 0u;
    }
    auto bad = [&]() {
      const unsigned ok = and3(and3(and3(z[0][0], z[0][1], z[0][2]), and3(z[0][3], z[1][0], z[1][1]), and3(z[1][2], z[1][3], z[2][0])),
                               and3(and3(z[2][1], z[2][2], z[2][3]), and3(z[3][0], z[3][1], z[3][2]), z[3][3]), 0x10001u);
      return __any_sync(~0u, g == 0 && ok != 0x10001u);
    };
    POLL {
      if (it_)
#pragma unroll
        for (int u = 0; u < 4; u++) ldsm_t(z[u], a_z[u] + u * 1024);
      if (!bad() || ++it_ >= SPIN_MAX) break;
    }
    float d0[8][4] = {}, d[8][4], r[8];
#pragma unroll
    for (int i = 0; i < 8; i++) mma16(d0[i], wx[i >> 1], z[i >> 1][2 * (i & 1)], z[i >> 1][2 * (i & 1) + 1]);
    POLL {
#pragma unroll
      for (int u = 0; u < 4; u++) ldsm_t(z[u], a_z[u ^ 2] + u * 1024);
#pragma unroll
      for (int i = 0; i < 8; i++) mma16c(d[i], wx[(i >> 1) ^ 2], z[i >> 1][2 * (i & 1)], z[i >> 1][2 * (i & 1) + 1], d0[i]);
      if (!bad() || ++it_ >= SPIN_MAX) break;
    }
#pragma unroll
    for (int i = 0; i < 8; i++) r[i] = (tq & 2) ? ((g & 1) ? d[i][3] : d[i][2]) : ((g & 1) ? d[i][1] : d[i][0]);
#pragma unroll
    for (int q = 0; q < 2; q++) pub8(p_rec + q * 128, pack2t(r[4 * q], r[4 * q + 1], par) | 1u, pack2(r[4 * q + 2], r[4 * q + 3]));
  }
  const int vt = v0 + nt;
  const uint32_t bufa = sb + (vt & 1) * 65536, fulla = bar0 + (vt & 1) * 32, pha = (vt >> 1) & 1, phb = ((vt + 1) >> 1) & 1;
  const uint32_t bufo = sb + ((vt + 1) & 1) * 65536, fullb = bar0 + ((vt + 1) & 1) * 32;
  uint32_t a_rs = sb + O_R + (warp >> 2) * 1024 + (16 * tq + g) * 16 + ((warp + tq) & 3) * 4;
  if (isA) {
    const int row = 16 * (warp & 6) + 8 * (warp & 1) + (lane & 16) + ((lane & 7) >> 1) + 4 * (lane & 1);
    uint32_t ab = bufa + row * 128 + ((((lane >> 3) & 1) ^ (row & 7)) << 4);
    const uint2* pr = scr->rec + (hd * 32 + warp) * 64 + lane;
    unsigned long long a_c0 = mapg(sb + O_CTX + (64 * rn + 32 * (warp & 1) + posof(lane)) * 4, warp & 6);
    unsigned long long a_c1 = mapg(sb + O_CTX + (64 * rn + 32 * (warp & 1) + posof(lane)) * 4, warp | 1);
    uint32_t a_rl = sb + O_R + (32 * (warp & 1) + lane) * 16;
    uint32_t ao = bufo + (16 * warp + 8 * (lane >> 4) + (lane & 7)) * 128 + ((((lane >> 3) & 1) ^ (lane & 7)) << 4);
    uint32_t a_cx = sb + O_CTX + (16 * warp + 4 * tq) * 4, a_ga = sb + O_SM + (320 + posof(tid & 63)) * 4;
    unsigned* p_ao = scr->xao + b * 64 + (tid & 63);
    unsigned* p_ab = scr->xab + cl * 256 + (2 * (rn & 3) + (warp & 1)) * 32 + (rn >> 2) * 16 + (lane >> 1);
    float xv = cl == 0 ? __bfloat162float(x[64 * rn + (tid & 63)]) : 0.f;
    unsigned p2 = lane >= 28 ? 0 : par;
    PIN(ab); PINL(pr); PINL(a_c0); PINL(a_c1); PIN(a_rl); PIN(a_rs); PIN(ao); PIN(a_cx); PIN(a_ga); PINL(p_ao); PINL(p_ab); PIN(p2);
    asm volatile("" : "+f"(xv));
    uint32_t aw[4][4][4];
    auto wo = [&](const int j) {
      mbar_wait(fullb + 8 * j, phb);
#pragma unroll
      for (int mt = 0; mt < 4; mt++) ldsm_t(aw[j][mt], (ao + j * 16384) ^ (mt << 5));
    };
    {
      uint32_t a[4][4][4];
      uint2 z[4], y[4] = {};
      float d[4][4] = {}, r[8];
      mbar_wait(fulla, pha);
      POLL {
#pragma unroll
        for (int q = 0; q < 4; q++) z[q] = ldx8(pr + q * 512);
        RETRY(lop_x3(z[0].x, z[1].x, par) | lop_x3(z[2].x, z[3].x, par))
      }
#pragma unroll
      for (int q = 0; q < 4; q++) {
        if (q == 3) {
          mbar_wait(bar0 + 8 * B_G);
          if (lane < 28)
#pragma unroll
            for (int u = 0; u < 4; u++) y[u] = ldx8(pr + u * 512 + 32);
          __syncwarp();
        }
        mbar_wait(fulla + 8 * q, pha);
#pragma unroll
        for (int mt = 0; mt < 4; mt++) ldsm_t(a[q][mt], (ab + q * 16384) ^ (mt << 5));
#pragma unroll
        for (int mt = 0; mt < 4; mt++) mma16(d[mt], a[q][mt], z[q].x, z[q].y);
      }
      mbar_wait(bar0 + 8 * B_W);
      const float4 W = lds16(sb + O_SM + (384 + 4 * tq) * 4);
#pragma unroll
      for (int i = 0; i < 8; i++) { r[i] = W.x * d[i >> 1][2 * (i & 1)] + W.y * d[i >> 1][2 * (i & 1) + 1]; asm volatile("" : "+f"(r[i])); }
#pragma unroll
      for (int j = 0; j < NPE; j++) wo(j);
      POLL {
        if (it_)
#pragma unroll
          for (int u = 0; u < 4; u++) y[u] = ldx8(pr + u * 512 + 32);
#pragma unroll
        for (int mt = 0; mt < 4; mt++) d[mt][0] = d[mt][1] = d[mt][2] = d[mt][3] = 0.f;
#pragma unroll
        for (int q = 0; q < 4; q++)
#pragma unroll
          for (int mt = 0; mt < 4; mt++) mma16(d[mt], a[q][mt], y[q].x, y[q].y);
        RETRY(or3(lop_x3(y[0].x, y[1].x, p2), lop_x3(y[2].x, y[3].x, p2), 0))
      }
#pragma unroll
      for (int i = 0; i < 8; i++) r[i] = W.w * d[i >> 1][2 * (i & 1) + 1] + (W.z * d[i >> 1][2 * (i & 1)] + r[i]);
      tred<4>(r, lane, 2); tred<2>(r, lane, 1);
      sts4(a_rs, r[0]); sts4(a_rs + 128, r[1]);
      nbar(1, 256);
      const uint32_t cv = __float_as_uint(sum8(a_rl)) | 1u;
      asm volatile("st.relaxed.cluster.b32 [%0], %2; st.relaxed.cluster.b32 [%1], %2;" ::"l"(a_c0), "l"(a_c1), "r"(cv) : "memory");
    }
    {
#pragma unroll
      for (int j = NPE; j < NPO; j++) wo(j);
      uint4 c[4];
      POLL {
#pragma unroll
        for (int j = 0; j < 4; j++) c[j] = ldsv16(a_cx + j * 512);
        RETRY(~and3(and3(and3(c[0].x, c[0].y, c[0].z), and3(c[1].x, c[1].y, c[1].z), and3(c[0].w, c[1].w, c[2].x)),
                    and3(and3(c[2].y, c[2].z, c[2].w), and3(c[3].x, c[3].y, c[3].z), c[3].w), ~0u))
      }
      float d[4][4] = {};
#pragma unroll
      for (int j = 0; j < 4; j++) {
        if (j + 1 >= NPO && j < 3) wo(j + 1);
        const uint32_t b0 = pack2(u2f(c[j].x), u2f(c[j].y)), b1 = pack2(u2f(c[j].z), u2f(c[j].w));
#pragma unroll
        for (int mt = 0; mt < 4; mt++) mma16(d[mt], aw[j][mt], b0, b1);
      }
      const float r0 = (tq & 2) ? ((tq & 1) ? d[3][0] : d[2][0]) : ((tq & 1) ? d[1][0] : d[0][0]);
      const float r1 = (tq & 2) ? ((tq & 1) ? d[3][2] : d[2][2]) : ((tq & 1) ? d[1][2] : d[0][2]);
      sts4(a_rs + 2048, r0); sts4(a_rs + 2048 + 128, r1);
      if (warp >= 2) nbar_arrive(2, 256);
      else {
        mbar_wait(bar0 + 8 * B_TAB);
        const float gav = lds4(a_ga);
        nbar(2, 256);
        const float t = gav * sum8(a_rl + 2048) + xv;
        asm volatile("{.reg .pred p; setp.eq.s32 p, %2, 0; @p red.relaxed.gpu.global.xor.b32 [%0], %1;}"
                     ::"l"(p_ab), "r"(pack2t(t, __shfl_down_sync(~0u, t, 1), par) | 1u), "r"(lane & 1) : "memory");
        pub4(p_ao, __float_as_uint(t) | 1u);
      }
    }
  } else {
    uint32_t af[4][4][4];
    uint32_t ab = bufa + (32 * warp + 8 * (lane >> 4) + (lane & 7)) * 64 + ((((lane >> 3) & 1) ^ ((lane >> 1) & 3)) << 4);
    uint32_t a_d = bufo + (8 * (lane >> 4) + (lane & 7)) * 128 + (((2 * (warp & 3) + ((lane >> 3) & 1)) ^ (lane & 7)) << 4);
    uint32_t a_rl = sb + O_R + lane * 16, a_st = sb + O_SM + (352 + 8 * (lane >> 4) + warp) * 4;
    const unsigned* pa = scr->xab + tid;
    unsigned long long a_h = mapg(sb + O_CTX + rn * 64 + (lane & 6) * 8 + (lane >> 3) * 4, 2 * (warp & 3) + (lane & 1));
    const int col = 64 * rn + 16 * (warp & 3) + 8 * (tq & 1) + g;
    uint32_t a_hl = sb + O_CTX + tq * 16;
    const unsigned* px = scr->xao + (tq & 2) * 1024 + col;
    bf16* po = out + col;
    PIN(ab); PIN(a_d); PIN(a_rl); PINL(pa); PIN(a_rs); PIN(a_st); PINL(po); PINL(a_h); PIN(a_hl); PINL(px);
    mbar_wait(bar0 + 8 * B_TAB);
    uint2 cf;
    uint2 bb[4];
    unsigned gbw;
    POLL {
      unsigned bad = 0;
      cf = ldx8(scr->xm + 1024 + (lane & 16) * 16 + 32 * warp + posof(2 * (lane & 15)));
#pragma unroll
      for (int s = 0; s < 4; s++) {
        const uint4 w = ldx16(scr->xm + 1024 - (g & 1) * 512 + 256 * (s >> 1) + 32 * warp + 16 * (s & 1) + 4 * tq);
        bb[s] = make_uint2(__byte_perm(w.x, w.y, 0x7632), __byte_perm(w.z, w.w, 0x7632));
        bad = or3(bad, lop_x3(w.x, w.y, par), lop_x3(w.z, w.w, par));
      }
      gbw = ldx4(scr->xm + 1536 + posof(col));
      RETRY(or3(bad, lop_x3(cf.x, cf.y, par), gbw ^ par))
    }
    const float gbv = bfhi(gbw);
    float e[4][4] = {};
    unsigned v[8];
    auto item = [&](const int it) {
      mbar_wait(fulla + 8 * it, pha);
#pragma unroll
      for (int i = 0; i < 4; i++) ldsm_t(af[it][i], (ab + it * 16384 + (i >> 1) * 1024) ^ ((i & 1) << 5));
    };
    auto item_mma = [&](const int it) {
#pragma unroll
      for (int i = 0; i < 4; i++) mma16(e[2 * (it & 1) + (i & 1)], af[it][i], bb[(it & 2) + (i >> 1)].x, bb[(it & 2) + (i >> 1)].y);
    };
    item(0); item_mma(0); item(1); item_mma(1);
    mbar_wait(bar0 + 8 * B_G);
#pragma unroll
    for (int i = 0; i < 8; i++) v[i] = ldx4(pa + i * 256);
    const unsigned t3 = clock() + WTEST;
    item(2); item_mma(2);
    uint32_t have3;
    do have3 = mbar_test(fulla + 24, pha); while (!have3 && (int)((unsigned)clock() - t3) < 0);
    if (have3) { item(3); item_mma(3); }
    float y0, y1, df[4][4], st[2];
    uint32_t bz[4][2] = {};
    auto mm = [&](const int it, const int i) { mma16(df[2 * (it & 1) + (i & 1)], af[it][i], bz[(it & 2) + (i >> 1)][0], bz[(it & 2) + (i >> 1)][1]); };
    POLL {
      if (it_)
#pragma unroll
        for (int i = 0; i < 8; i++) v[i] = ldx4(pa + i * 256);
      y0 = ((bflo(v[0]) + bflo(v[1])) + (bflo(v[2]) + bflo(v[3]))) + ((bflo(v[4]) + bflo(v[5])) + (bflo(v[6]) + bflo(v[7])));
      y1 = ((bfhi(v[0]) + bfhi(v[1])) + (bfhi(v[2]) + bfhi(v[3]))) + ((bfhi(v[4]) + bfhi(v[5])) + (bfhi(v[6]) + bfhi(v[7])));
      const uint32_t zb = pack2(y0 * u2f(cf.x), y1 * u2f(cf.y));
#pragma unroll
      for (int s = 0; s < 4; s++) {
        const uint32_t w = __shfl_sync(~0u, zb, 8 * s + (lane & 7));
        bz[s][0] = (lane & 4) ? 0u : w; bz[s][1] = (lane & 4) ? w : 0u;
      }
      st[0] = y0 + y1; st[1] = y0 * y0 + y1 * y1;
      tred<1>(st, lane, 16);
#pragma unroll
      for (int i = 0; i < 4; i++) df[i][0] = df[i][1] = df[i][2] = df[i][3] = 0.f;
      mm(0, 0); mm(0, 1); mm(1, 0); mm(1, 1);
      st[0] += shx(st[0], 8);
      mm(0, 2); mm(0, 3); mm(1, 2); mm(1, 3);
      RETRY(or3(or3(lop_x3(v[0], v[1], par), lop_x3(v[2], v[3], par), lop_x3(v[4], v[5], par)), lop_x3(v[6], v[7], par), 0))
    }
    unsigned xq[4];
    if (wg == 0)
#pragma unroll
      for (int i = 0; i < 4; i++) xq[i] = ldx4(px + i * 512);
    {
      st[0] += shx(st[0], 4);
      mm(2, 0); mm(2, 1);
      st[0] += shx(st[0], 2);
      mm(2, 2); mm(2, 3);
      st[0] += shx(st[0], 1);
      sts4(a_st, st[0]);
      __syncwarp();
      arrive_n(bar0 + 8 * B_ST, lane == 0, 1);
      if (!have3) { item(3); item_mma(3); }
      mm(3, 0); mm(3, 1); mm(3, 2); mm(3, 3);
    }
    mbar_wait(bar0 + 8 * B_ST);
    float mean, rstd;
    {
      float4 u[4];
#pragma unroll
      for (int i = 0; i < 4; i++) u[i] = lds16(sb + O_SM + (352 + 4 * i) * 4);
      mean = (((u[0].x + u[0].y) + (u[0].z + u[0].w)) + ((u[1].x + u[1].y) + (u[1].z + u[1].w))) * (1.f / 512.f);
      const float sq = (((u[2].x + u[2].y) + (u[2].z + u[2].w)) + ((u[3].x + u[3].y) + (u[3].z + u[3].w))) * (1.f / 512.f);
      asm("rsqrt.approx.ftz.f32 %0, %1;" : "=f"(rstd) : "f"(fmaxf(sq - mean * mean, 0.f) + 1e-5f));
    }
    float A[4], r[4];
#pragma unroll
    for (int i = 0; i < 4; i++) {
      A[i] = (tq & 2) ? ((tq & 1) ? e[3][i] : e[2][i]) : ((tq & 1) ? e[1][i] : e[0][i]);
      r[i] = (tq & 2) ? ((tq & 1) ? df[3][i] : df[2][i]) : ((tq & 1) ? df[1][i] : df[0][i]);
    }
    sts4(a_rs, rstd * (r[0] + r[1]) + (A[1] - rstd * mean * A[0])); sts4(a_rs + 128, rstd * (r[2] + r[3]) + (A[3] - rstd * mean * A[2]));
    nbar(1, 256);
    if (wg) {
      const float4 g0 = lds16(a_rl), g1 = lds16(a_rl + 1024), u0 = lds16(a_rl + 512), u1 = lds16(a_rl + 1536);
      const float gg = bfr(((g0.x + g0.y) + (g0.z + g0.w)) + ((g1.x + g1.y) + (g1.z + g1.w)));
      const float uu = bfr(((u0.x + u0.y) + (u0.z + u0.w)) + ((u1.x + u1.y) + (u1.z + u1.w)));
      const float hh = bfr(gg * rcp(1.f + ex2(gg * (-2.302208198f - 0.1029432397f * gg * gg)))) * uu, hn = __shfl_xor_sync(~0u, hh, 1);
      asm volatile("st.relaxed.cluster.b32 [%0], %1;" ::"l"(a_h), "r"(pack2t((lane & 1) ? hn : hh, (lane & 1) ? hh : hn, 1)) : "memory");
    } else {
      uint32_t ad[16][4];
      spin_until(clock() + FDLY);
#pragma unroll
      for (int j = 0; j < 2; j++) {
        mbar_wait(fullb + 8 * j, phb);
#pragma unroll
        for (int i = 0; i < 8; i++) ldsm_t(ad[8 * j + i], a_d + (8 * j + i) * 2048);
      }
      POLL {
        if (it_)
#pragma unroll
          for (int i = 0; i < 4; i++) xq[i] = ldx4(px + i * 512);
        RETRY(lop_x3(xq[0], xq[1], par) | lop_x3(xq[2], xq[3], par))
      }
      float x7 = (u2f(xq[0]) + u2f(xq[1])) + (u2f(xq[2]) + u2f(xq[3]));
      x7 = (x7 + __shfl_xor_sync(~0u, x7, 2)) * (1.f / 7.f);
      uint4 hb[8];
      POLL {
        unsigned ok[8];
#pragma unroll
        for (int i = 0; i < 8; i++) { hb[i] = ldsv16(a_hl + i * 64); ok[i] = and3(hb[i].x, hb[i].y, hb[i].z); }
        RETRY(~and3(and3(and3(ok[0], ok[1], ok[2]), and3(ok[3], ok[4], ok[5]), and3(ok[6], ok[7], hb[0].w)),
                    and3(and3(hb[1].w, hb[2].w, hb[3].w), and3(hb[4].w, hb[5].w, hb[6].w), hb[7].w), 1))
      }
      float dd[4][4] = {};
#pragma unroll
      for (int i = 0; i < 8; i++) { mma16(dd[(2 * i) & 3], ad[2 * i], hb[i].x, hb[i].y); mma16(dd[(2 * i + 1) & 3], ad[2 * i + 1], hb[i].z, hb[i].w); }
      const float t = gbv * ((tq & 1) ? (dd[0][2] + dd[1][2]) + (dd[2][2] + dd[3][2]) : (dd[0][0] + dd[1][0]) + (dd[2][0] + dd[3][0])) + x7;
      asm volatile("{.reg .pred p; setp.eq.s32 p, %2, 0; @p red.relaxed.gpu.global.add.noftz.bf16x2 [%0], %1;}"
                   ::"l"(po), "r"(pack2(t, __shfl_down_sync(~0u, t, 4))), "r"(lane & 6) : "memory");
      if (f == 0 && tid == 0) stx4(&scr->cnt[0], epoch + 1);
    }
  }
}

static void make_sched(Sched& s) {
  const char* order = "FFAAbcFmmvog...d";
  const double dt = 5010 * 1e-3, dth = 4850 * 1e-3, dtt = 5200 * 1e-3;
  const int nbig = NBIG;
  s.zero = 0; s.dth = (unsigned)(dth * 256 + 0.5);
  double t = 512 * dth + 80;
  int tile = 0, jm = 0;
  for (int i = 0; i < 3; i++) s.nr[i] = s.nt[i] = 0;
  auto add = [&](int c, int type, double step, int win, int b0, int tl) {
    s.r[c][s.nr[c]++] = make_uint2((unsigned)(t + 0.5) | (unsigned)(step + 0.5) << 16, type | win << 4 | (b0 + 64) << 8 | tl << 16);
    if (type == T_KV) s.nt[c]++;
  };
  const int w1 = 6, w2 = 4, wt = 6;
  for (const char* p = order; *p; p++) {
    const char c = *p;
    if (c == 'v' || c == 'o' || c == 'm') {
      const int ty = c == 'v' ? T_UV : c == 'o' ? T_WO : T_MOD;
      const double d = c == 'm' ? dt : dtt;
      add(0, ty, 64 * d, wt, 0, c == 'm' ? jm : 0); add(1, ty, 64 * d, wt, 0, c == 'm' ? jm : 0);
      t += (c == 'm' ? 64 : 256) * d; jm += c == 'm';
    } else if (c == 'g' || c == 'd') {
      const int cs = c == 'g' ? 40 : 0;
      t += 3 * cs;
      add(2, c == 'g' ? T_GU : T_DN, 56 * dtt - cs, wt, 64, 0);
      t -= 3 * cs;
      t += (c == 'g' ? 224 : 112) * dtt;
    } else if (c == '.') t += 100;
    else if (c == '-') t -= 100;
    else {
      const int na = c == 'F' ? 0 : c == 'C' || c == 'c' || c == 'a' ? nbig : 64, nf = c == 'A' || c == 'a' ? 0 : 56, n = na + nf;
      const int w = na && nf ? w2 : w1;
      const bool ff = c == 'b' || c == 'c';
      const int cf = c == 'c' ? 40 : 0, ca = cf * 7 / 5;
      t += 3 * ca;
      if (na) add(0, T_KV, n * dt - ca, w, ff ? -56 : 0, tile);
      t -= 3 * ca;
      if (na == 64) add(1, T_KV, n * dt, w, ff ? -56 : 0, tile);
      if (nf) add(2, T_KV, n * dt - cf, w, ff ? 64 : 64 - na, tile);
      tile += n; t += 4 * n * dt;
      s.t4 = (unsigned)t + 600;
    }
  }
  s.dt = (unsigned)(dt * 256 + 0.5); s.d4 = 1550 | 1200 << 16; s.d6 = 3330;
}

static void launch(void* const* d_in, void* d_out) {
  static TMaps tms;
  static Sched sch;
  static bool init = false;
  static void* scr = nullptr;
  if (!init) {
    void* fn = nullptr; cudaDriverEntryPointQueryResult qr;
    cudaGetDriverEntryPoint("cuTensorMapEncodeTiled", &fn, cudaEnableDefault, &qr);
    EncFn f = (EncFn)fn;
    const CUtensorMapSwizzle S64 = CU_TENSOR_MAP_SWIZZLE_64B, S128 = CU_TENSOR_MAP_SWIZZLE_128B;
    const CUtensorMapL2promotion P256 = CU_TENSOR_MAP_L2_PROMOTION_L2_256B;
    enc3d(f, &tms.m[0], d_in[2], 64, 512, 64, 8192, 128, 64, 128, 1, S128, CU_TENSOR_MAP_L2_PROMOTION_L2_128B);
    enc3d(f, &tms.m[1], d_in[3], 64, 512, 64, 8192, 128, 64, 64, 2, S128, P256);
    enc3d(f, &tms.m[2], d_in[1], 64, SK, 8, 1024, 128, 64, 64, 2, S128, P256);
    enc3d(f, &tms.m[3], d_in[11], 3072, 256, 2, 6144, 256 * 6144, 32, 256, 1, S64, CU_TENSOR_MAP_L2_PROMOTION_L2_128B);
    enc3d(f, &tms.m[4], d_in[4], 64, 512, 64, 8192, 128, 64, 128, 1, S128, CU_TENSOR_MAP_L2_PROMOTION_L2_128B);
    enc3d(f, &tms.m[5], d_in[5], 512, 128, 32, 1024, 128 * 1024, 64, 128, 1, S128, CU_TENSOR_MAP_L2_PROMOTION_L2_128B);
    enc3d(f, &tms.m[6], d_in[7], 1792, 256, 2, 3584, 256 * 3584, 32, 256, 1, S64, CU_TENSOR_MAP_L2_PROMOTION_L2_128B);
    enc3d(f, &tms.m[7], d_in[8], 1792, 256, 2, 3584, 256 * 3584, 32, 256, 1, S64, CU_TENSOR_MAP_L2_PROMOTION_L2_128B);
    enc3d(f, &tms.m[8], d_in[9], 512, 128, 14, 1024, 128 * 1024, 64, 128, 1, S128, CU_TENSOR_MAP_L2_PROMOTION_L2_128B);
    cudaFuncSetAttribute(fused_kernel, cudaFuncAttributeMaxDynamicSharedMemorySize, SMEM9);
    cudaGetSymbolAddress(&scr, g_scr);
    make_sched(sch);
    init = true;
  }
  fused_kernel<<<NCTA9, 384, SMEM9>>>((const bf16*)d_in[0], (const bf16*)d_in[10], (const bf16*)d_in[11], (bf16*)d_out, (Scratch*)scr, sch, tms);
}

static bool fits() {
  cudaFuncSetAttribute(fused_kernel, cudaFuncAttributeMaxDynamicSharedMemorySize, SMEM9);
  cudaLaunchConfig_t cfg = {};
  cfg.gridDim = dim3(NCTA9); cfg.blockDim = dim3(384); cfg.dynamicSmemBytes = SMEM9;
  cudaLaunchAttribute at[1];
  at[0].id = cudaLaunchAttributeClusterDimension; at[0].val.clusterDim.x = 8; at[0].val.clusterDim.y = 1; at[0].val.clusterDim.z = 1;
  cfg.attrs = at; cfg.numAttrs = 1;
  int n = 0;
  if (cudaOccupancyMaxActiveClusters(&n, fused_kernel, &cfg) != cudaSuccess) { (void)cudaGetLastError(); return false; }
  return n >= NCTA9 / 8;
}
}
#undef BAR_ARM
#undef BAR_ARRIVE
#undef BAR_INIT
#undef B_EM
#undef B_EMPTY
#undef B_FM
#undef B_FULL
#undef B_G
#undef B_G2
#undef B_H
#undef B_HZ
#undef B_LZ
#undef B_Q2
#undef B_QF
#undef B_ST
#undef B_TAB
#undef B_W
#undef B_WZ
#undef CNT_ADD
#undef DSC
#undef FDLY
#undef HI128
#undef HI64
#undef NBIG
#undef NCTA9
#undef NPE
#undef NPO
#undef NSL
#undef O_B
#undef O_BAR
#undef O_CTX
#undef O_DBG
#undef O_EP
#undef O_HW
#undef O_HZ
#undef O_LZ
#undef O_P
#undef O_Q
#undef O_R
#undef O_SILU
#undef O_SM
#undef O_X
#undef PIN
#undef PINL
#undef POLL
#undef QN
#undef RETRY
#undef SK
#undef SMEM9
#undef SMEM_BASE
#undef SPIN_MAX
#undef TAU
#undef VDLY
#undef WTEST
#undef X16
#undef fbits

namespace v8 {
typedef __nv_bfloat16 bf16;
#define NCTA 128
#define SK 32768
#define SLOT 32768
#define NSLOT 6
#define OFF_WQ (2 * SLOT)
#define OFF_WUK (4 * SLOT)
#define OFF_Q 196608
#define OFF_P (OFF_Q + 16384)
#define OFF_B (OFF_P + 4096)
#define OFF_R4 (OFF_B + 2304)
#define OFF_SILU (OFF_R4 + 4096)
#define OFF_RA (OFF_SILU + 1024)
#define OFF_SM (OFF_RA + 1024)
#define OFF_BP (OFF_SM + 1792)
#define OFF_CO (OFF_BP + 1024)
#define OFF_BAR (OFF_CO + 1280)
#define OFF_MASK (OFF_BAR + 512)
#define OFF_DBG (OFF_MASK + 16)
#define SMEM_BYTES (OFF_DBG + 128)
#define OFF_MOD OFF_Q
#define OFF_UV (4 * SLOT)
#define OFF_O (5 * SLOT)
#define OFF_G 0
#define OFF_U 16384
#define OFF_D SLOT
#define OFF_XO (OFF_D + 16384)
#define FB_UK 4
#define FB_KV 6
#define FB_MOD 22
#define FB_UV 23
#define FB_O 25
#define FB_G 27
#define FB_D 29
#define EB 30
#define QB 50
#define XB 51
#define SPIN_MAX (1 << 20)
#define BACKOFF 40
#define RATE_NS 652
#define RATE_T0 200
#define RATE_TL 300
#define WINS 0x3222333
#define KVWIN 4
#define RATE_H 650
#define RATE_E 650
#define SMUL 9
#define NPRE0 1
#define NPRE1 3
#define HWIN 4
#define EWIN 3
#define WTEST 450
#define DLY5 650
#define DLY6 600
#define DLY7 600
#define P12(a, b, c, d, e, f, g, h, i, j, k, l) ((unsigned long long)(a) | (b) << 5 | (c) << 10 | (d) << 15 | (e) << 20 | (f) << 25 | \
  (unsigned long long)(g) << 30 | (unsigned long long)(h) << 35 | (unsigned long long)(i) << 40 | (unsigned long long)(j) << 45 | \
  (unsigned long long)(k) << 50 | (unsigned long long)(l) << 55)
#define ORDER0 P12(0, 1, 2, 3, 4, 5, 16, 6, 7, 8, 9, 10)
#define ORDER1 P12(11, 12, 13, 14, 15, 17, 18, 19, 20, 23, 21, 22)
#define TAIL_K 17
#define RS 16
template <int N> struct IC { static constexpr int value = N; };
struct TMaps { CUtensorMap m[9]; };

struct __align__(128) Scratch {
  uint4 xo[128 * 64 * RS];
  uint2 ml[32 * 64];
  unsigned h[8 * 256];
  unsigned qa[32 * 256];
  unsigned xc[128 * 64];
  unsigned xao[8 * 512];
  unsigned xf[112 * 512];
  unsigned xm[2048];
  unsigned cnt[5 * 32];
};
__device__ Scratch g_scr;
#define g_xo scr->xo
#define g_ml scr->ml
#define g_h scr->h
#define g_qa scr->qa
#define g_xc scr->xc
#define g_xao scr->xao
#define g_xf scr->xf
#define g_xm scr->xm
#define g_epoch scr->cnt[0]

__device__ __forceinline__ uint32_t s2u(const void* p) { return (uint32_t)__cvta_generic_to_shared(p); }
__device__ __forceinline__ float bflo(uint32_t u) { return __uint_as_float(u << 16); }
__device__ __forceinline__ float bfhi(uint32_t u) { return __uint_as_float(u & 0xffff0000u); }
__device__ __forceinline__ float u2f(uint32_t u) { return __uint_as_float(u); }
__device__ __forceinline__ void fma8(float* acc, uint4 v, float s) {
  acc[0] += s * bflo(v.x); acc[1] += s * bfhi(v.x); acc[2] += s * bflo(v.y); acc[3] += s * bfhi(v.y);
  acc[4] += s * bflo(v.z); acc[5] += s * bfhi(v.z); acc[6] += s * bflo(v.w); acc[7] += s * bfhi(v.w);
}
__device__ __forceinline__ uint32_t pack2(float a, float b) {
  __nv_bfloat162 p = __floats2bfloat162_rn(a, b); return *(uint32_t*)&p;
}
__device__ __forceinline__ float bfr(float v) { return bfhi(pack2(v, v)); }
__device__ __forceinline__ float silu_bf(float c) { return bfr(__fdividef(c, 1.f + __expf(-c))); }
#define fbits(v) ((__float_as_uint(v) & ~1u) | par)
__device__ __forceinline__ uint32_t pack2t(float a, float b, unsigned par) {
  const uint32_t ua = ((__float_as_uint(a) + ((par ^ 1) << 16)) & 0xFFFE0000u) | (par << 16);
  return __byte_perm(ua, pack2(b, b), 0x7632);
}
__device__ __forceinline__ void nbar(int id, int n) { asm volatile("bar.sync %0, %1;" ::"r"(id), "r"(n) : "memory"); }
__device__ __forceinline__ void nbar_arrive(int id, int n) { asm volatile("bar.arrive %0, %1;" ::"r"(id), "r"(n) : "memory"); }
__device__ __forceinline__ uint4 ldc16(const void* p) {
  uint4 v; asm volatile("ld.relaxed.cta.global.v4.u32 {%0,%1,%2,%3}, [%4];" : "=r"(v.x), "=r"(v.y), "=r"(v.z), "=r"(v.w) : "l"(p) : "memory"); return v;
}
__device__ __forceinline__ unsigned ldc4(const void* p) {
  unsigned v; asm volatile("ld.relaxed.cta.global.u32 %0, [%1];" : "=r"(v) : "l"(p) : "memory"); return v;
}
__device__ __forceinline__ uint4 ldx16(const void* p) {
  uint4 v; asm volatile("ld.relaxed.gpu.global.v4.u32 {%0,%1,%2,%3}, [%4];" : "=r"(v.x), "=r"(v.y), "=r"(v.z), "=r"(v.w) : "l"(p) : "memory"); return v;
}
__device__ __forceinline__ unsigned ldx4(const void* p) {
  unsigned v; asm volatile("ld.relaxed.gpu.global.u32 %0, [%1];" : "=r"(v) : "l"(p) : "memory"); return v;
}
__device__ __forceinline__ unsigned long long ldx64(const void* p) {
  unsigned long long v; asm volatile("ld.relaxed.gpu.global.u64 %0, [%1];" : "=l"(v) : "l"(p) : "memory"); return v;
}
__device__ __forceinline__ void stx16(void* p, uint4 v) {
  asm volatile("st.relaxed.gpu.global.v4.u32 [%0], {%1,%2,%3,%4};" ::"l"(p), "r"(v.x), "r"(v.y), "r"(v.z), "r"(v.w) : "memory");
}
__device__ __forceinline__ void stx8(void* p, uint2 v) { asm volatile("st.relaxed.gpu.global.v2.u32 [%0], {%1,%2};" ::"l"(p), "r"(v.x), "r"(v.y) : "memory"); }
__device__ __forceinline__ void stx4(void* p, unsigned v) { asm volatile("st.relaxed.gpu.global.u32 [%0], %1;" ::"l"(p), "r"(v) : "memory"); }
__device__ __forceinline__ unsigned lop_x3(unsigned a, unsigned b, unsigned c) {
  unsigned d; asm("lop3.b32 %0, %1, %2, %3, 0x7E;" : "=r"(d) : "r"(a), "r"(b), "r"(c)); return d; }
#define X16(v) (lop_x3(v.x, v.y, par) | lop_x3(v.z, v.w, par))
#define X8(v) lop_x3(v.x, v.y, par)
#define RETRY(bad) if (!__any_sync(~0u, (bad) & 1) || ++it_ >= SPIN_MAX) break; __nanosleep(BACKOFF);
#define POLL _Pragma("unroll 1") for (int it_ = 0;;)
__device__ __forceinline__ void mbar_wait(uint32_t bar) {
  uint32_t ok; int it = 0;
  do {
    asm volatile("{.reg .pred p; mbarrier.try_wait.parity.shared::cta.b64 p, [%1], 0; selp.u32 %0,1,0,p;}"
                 : "=r"(ok) : "r"(bar) : "memory");
  } while (!ok && ++it < SPIN_MAX);
}
__device__ __forceinline__ float ex2(float v) { float r; asm("ex2.approx.ftz.f32 %0, %1;" : "=f"(r) : "f"(v)); return r; }
__device__ __forceinline__ float rcp(float v) { float r; asm("rcp.approx.ftz.f32 %0, %1;" : "=f"(r) : "f"(v)); return r; }
__device__ __forceinline__ void mma16(float* d, const uint32_t* a, uint32_t b0, uint32_t b1) {
  asm volatile("mma.sync.aligned.m16n8k16.row.col.f32.bf16.bf16.f32 {%0,%1,%2,%3}, {%4,%5,%6,%7}, {%8,%9}, {%0,%1,%2,%3};"
               : "+f"(d[0]), "+f"(d[1]), "+f"(d[2]), "+f"(d[3]) : "r"(a[0]), "r"(a[1]), "r"(a[2]), "r"(a[3]), "r"(b0), "r"(b1));
}
__device__ __forceinline__ float4 lds16(uint32_t a) {
  float4 v; asm volatile("ld.shared.v4.f32 {%0,%1,%2,%3}, [%4];" : "=f"(v.x), "=f"(v.y), "=f"(v.z), "=f"(v.w) : "r"(a) : "memory"); return v;
}
__device__ __forceinline__ void ldsm_t(uint32_t* r, uint32_t a) {
  asm volatile("ldmatrix.sync.aligned.m8n8.x4.trans.shared.b16 {%0,%1,%2,%3}, [%4];" : "=r"(r[0]), "=r"(r[1]), "=r"(r[2]), "=r"(r[3]) : "r"(a) : "memory");
}
__device__ __forceinline__ void ldsm(uint32_t* r, uint32_t a) {
  asm volatile("ldmatrix.sync.aligned.m8n8.x4.shared.b16 {%0,%1,%2,%3}, [%4];" : "=r"(r[0]), "=r"(r[1]), "=r"(r[2]), "=r"(r[3]) : "r"(a) : "memory");
}
template <int N>
__device__ __forceinline__ void tred(float* a, int lane, int m) {
  const bool hi = lane & m;
#pragma unroll
  for (int i = 0; i < N; i++) {
    float send = hi ? a[i] : a[i + N], keep = hi ? a[i + N] : a[i];
    a[i] = keep + __shfl_xor_sync(~0u, send, m);
  }
}
template <int N>
__device__ __forceinline__ void tmax(float* a, int lane, int m) {
  const bool hi = lane & m;
#pragma unroll
  for (int i = 0; i < N; i++) {
    float send = hi ? a[i] : a[i + N], keep = hi ? a[i + N] : a[i];
    a[i] = fmaxf(keep, __shfl_xor_sync(~0u, send, m));
  }
}
__device__ __forceinline__ void arrive2(uint32_t bar, uint32_t rbar, bool local, bool remote) {
  asm volatile("{.reg .pred p, q; setp.ne.s32 p, %2, 0; setp.ne.s32 q, %3, 0; @p mbarrier.arrive.shared::cta.b64 _, [%0];\n"
               "@q mbarrier.arrive.relaxed.cluster.shared::cluster.b64 _, [%1];}" ::"r"(bar), "r"(rbar), "r"((int)local), "r"((int)remote) : "memory");
}
__device__ __forceinline__ unsigned long long stream_policy() {
  unsigned long long p;
  asm volatile("createpolicy.fractional.L2::evict_first.b64 %0, 1.0;" : "=l"(p));
  return p;
}
__device__ __forceinline__ void tma3d(uint32_t dst, const CUtensorMap* tm, uint32_t bar, int c0, int c1, int c2) {
  asm volatile("cp.async.bulk.tensor.3d.shared::cluster.global.mbarrier::complete_tx::bytes.L2::cache_hint [%0], [%1, {%3, %4, %5}], [%2], %6;"
               ::"r"(dst), "l"(tm), "r"(bar), "r"(c0), "r"(c1), "r"(c2), "l"(stream_policy()) : "memory");
}
__device__ __forceinline__ void st_async2(uint32_t dst, uint32_t bar, float v0, float v1) {
  asm volatile("st.async.shared::cluster.mbarrier::complete_tx::bytes.v2.f32 [%0], {%1, %2}, [%3];" ::"r"(dst), "f"(v0), "f"(v1), "r"(bar) : "memory");
}
__device__ __forceinline__ void st_pair(int mode, uint32_t dst, uint32_t bar, float v0, float v1) {
  asm volatile("{.reg .pred p, q; setp.eq.s32 p, %4, 1; setp.eq.s32 q, %4, 2; @p st.shared.v2.f32 [%0], {%1, %2};\n"
               "@q st.async.shared::cluster.mbarrier::complete_tx::bytes.v2.f32 [%0], {%1, %2}, [%3];}"
               ::"r"(dst), "f"(v0), "f"(v1), "r"(bar), "r"(mode) : "memory");
}
__device__ __forceinline__ void spin_until(unsigned t) { while ((int)((unsigned)clock() - t) < 0) {} }
__device__ __forceinline__ unsigned wait_until(unsigned t) {
  unsigned now;
  for (;;) {
    asm volatile("mov.u32 %0, %%globaltimer_lo;" : "=r"(now));
    if ((int)(now - t) >= 0) break;
  }
  return now;
}
#define PIN(x) asm volatile("" : "+r"(x))
#define PINL(x) asm volatile("" : "+l"(x))
#define BAR_ARRIVE(i) asm volatile("mbarrier.arrive.shared::cta.b64 _, [%0];" ::"r"(bar0 + 8 * (i)) : "memory")
#define CNT_ADD(c) asm volatile("red.relaxed.gpu.global.add.u32 [%0], 1;" ::"l"(scr->cnt + (c)) : "memory")
#define BAR_INIT(i, cnt) asm volatile("mbarrier.init.shared::cta.b64 [%0], %1;" ::"r"(bar0 + 8 * (i)), "r"(cnt) : "memory")
#define BAR_ARM(i, bytes) asm volatile("mbarrier.arrive.expect_tx.shared::cta.b64 _, [%0], %1;" ::"r"(bar0 + 8 * (i)), "r"(bytes) : "memory")

__device__ __forceinline__ void tail(unsigned char* smem, Scratch* __restrict__ scr, const bf16* __restrict__ x, bf16* __restrict__ out,
                                     const unsigned par, const unsigned epoch, const int warp) {
  int tid, b;
  asm volatile("mov.u32 %0, %%tid.x;" : "=r"(tid));
  asm volatile("mov.u32 %0, %%ctaid.x;" : "=r"(b));
  const int lane = tid & 31, g = lane >> 2, tq = lane & 3;
  const uint32_t sb = __shfl_sync(~0u, s2u(smem), 0), bar0 = sb + OFF_BAR;
  float* s_sm = (float*)(smem + OFF_SM);
  const int prow = 4 * (lane >> 4) + ((lane & 7) >> 1) + 8 * (lane & 1);
  const float* s_co = (const float*)(smem + OFF_CO);
  const int opos = (b & 15) * 32 + (lane & 16) + 2 * (lane & 6) + ((lane >> 2) & 2) + (lane & 1);
  const float xv = b < 16 ? __bfloat162float(x[(b & 15) * 32 + lane]) : 0.f;
  const int rk = b & 1, ob = 32 * rk + ((b >> 1) & 31);
  uint32_t psb;
  asm volatile("mapa.shared::cluster.u32 %0, %1, %2;" : "=r"(psb) : "r"(sb), "r"(rk ^ 1));
  {
    uint32_t a[8][4];
    {
      const int rg = tid >> 4;
      const uint4* src = g_xo + ((size_t)b * 64 + rg) * RS;
      const uint32_t dst = sb + OFF_XO + rg * 256 + (((tid & 15) ^ (rg & 7)) << 4);
      unsigned long long todo = 0x0001000100010001ull;
#pragma unroll 1
      for (int it = 0; it < SPIN_MAX * 16; it++) {
        unsigned long long mk = *(volatile unsigned long long*)(smem + OFF_MASK);
        const unsigned long long nw = (mk >> rg) & todo;
        todo ^= nw;
#pragma unroll
        for (int i = 0; i < 4; i++)
          if (nw >> (16 * i) & 1)
            asm volatile("cp.async.cg.shared.global [%0], [%1], 16;" ::"r"(dst + i * 4096), "l"(src + i * 16 * RS + (tid & 15)) : "memory");
        if (!__any_sync(~0u, todo != 0)) break;
      }
      asm volatile("cp.async.mbarrier.arrive.noinc.shared::cta.b64 [%0];" ::"r"(bar0 + 8 * (XB + 2)) : "memory");
    }
    mbar_wait(bar0 + 8 * FB_UV); mbar_wait(bar0 + 8 * (FB_UV + 1));
    const uint32_t ab = sb + OFF_UV + (warp >> 2) * 8192 + (8 * (lane >> 4) + (lane & 7)) * 128 + (((2 * (warp & 3) + ((lane >> 3) & 1)) ^ (lane & 7)) << 4);
#pragma unroll
    for (int s = 0; s < 8; s++) ldsm_t(a[s], ab + (s >> 2) * 16384 + (s & 3) * 2048);
    const int chn = 2 * warp + (tq & 1);
    uint32_t a_b = sb + OFF_B + (tq >> 1) * 272 + (32 * (chn >> 2) + 8 * (g >> 1) + 2 * (chn & 3) + (g & 1)) * 2;
    uint32_t a_bq = sb + OFF_B + (lane & 1) * 272 + (lane >> 3) * 16;
    unsigned* p_c = g_xc + (b >> 2) * 256 + warp * 32 + (b & 3) * 8 + (g & 3) * 2 + (g >> 2);
    PIN(a_b); PIN(a_bq); PINL(p_c);
    mbar_wait(bar0 + 8 * (XB + 6));
    uint32_t wb[8];
#pragma unroll
    for (int s = 0; s < 8; s++) wb[s] = *(const uint32_t*)(smem + OFF_RA + (4 * s + tq) * 4);
    const float invL = *(const float*)(smem + OFF_RA + 128);
    float ov;
    POLL {
      mbar_wait(bar0 + 8 * (XB + 2));
      uint32_t ao[4][4];
#pragma unroll
      for (int s = 0; s < 4; s++)
        ldsm_t(ao[s], sb + OFF_XO + (16 * s + 8 * (lane >> 4) + (lane & 7)) * 256 + (((2 * warp + ((lane >> 3) & 1)) ^ (lane & 7)) << 4));
      float d[4][4] = {};
#pragma unroll
      for (int s = 0; s < 4; s++) mma16(d[s], ao[s], wb[2 * s], wb[2 * s + 1]);
      const unsigned p2 = par * 0x10001u;
      unsigned bad = 0;
#pragma unroll
      for (int s = 0; s < 4; s++) bad |= lop_x3(ao[s][0], ao[s][1], p2) | lop_x3(ao[s][2], ao[s][3], p2);
      bad = g == 0 ? bad | (bad >> 16) : 0u;
      ov = (tq & 1) ? (d[0][2] + d[1][2]) + (d[2][2] + d[3][2]) : (d[0][0] + d[1][0]) + (d[2][0] + d[3][0]);
      if (__builtin_expect(!__any_sync(~0u, bad & 1) || ++it_ >= SPIN_MAX, 1)) break;
#pragma unroll
      for (int i = 0; i < 4; i++)
        asm volatile("cp.async.cg.shared.global [%0], [%1], 16;"
                     ::"r"(sb + OFF_XO + ((lane >> 1) + 16 * i) * 256 + (((2 * warp + (lane & 1)) ^ ((lane >> 1) & 7)) << 4)),
                       "l"(g_xo + ((size_t)b * 64 + (lane >> 1) + 16 * i) * RS + 2 * warp + (lane & 1)) : "memory");
      asm volatile("cp.async.wait_all;" ::: "memory");
      __syncwarp();
    }
    {
      const float lo = ov - bfhi(__float_as_uint(ov));
      asm volatile("st.shared.u16 [%0], %1;" ::"r"(a_b), "h"((unsigned short)((tq & 2) ? pack2(lo, lo) : __float_as_uint(ov) >> 16)) : "memory");
    }
    nbar(1, 256);
    float d[4][4] = {};
#pragma unroll
    for (int y = 0; y < 4; y++) {
      uint32_t bq[4];
      ldsm(bq, a_bq + 64 * y);
      mma16(d[(2 * y) & 3], a[2 * y], bq[0], bq[1]); mma16(d[(2 * y + 1) & 3], a[2 * y + 1], bq[2], bq[3]);
    }
    const float r0 = ((d[0][0] + d[0][1]) + (d[1][0] + d[1][1])) + ((d[2][0] + d[2][1]) + (d[3][0] + d[3][1]));
    const float r1 = ((d[0][2] + d[0][3]) + (d[1][2] + d[1][3])) + ((d[2][2] + d[2][3]) + (d[3][2] + d[3][3]));
    if (tq == 0) stx4(p_c, pack2t(r0 * invL, r1 * invL, par));
  }
  unsigned tpub = clock();
  mbar_wait(bar0 + 8 * (XB + 4));
  const float gav = s_co[256 + (opos & 31)];
  const float gbv = s_co[288 + (lane & 4) + 2 * (lane & 1) + ((lane >> 1) & 1)];
  float4 cf[2];
#pragma unroll
  for (int s = 0; s < 2; s++) cf[s] = *(const float4*)(s_co + 32 * warp + 16 * s + 4 * tq);
  {
    uint32_t a[2][4][4];
    mbar_wait(bar0 + 8 * (FB_O + (warp >> 2)));
    const uint32_t ab = sb + OFF_O + (32 * warp + prow) * 128 + ((((lane >> 3) & 1) ^ (prow & 7)) << 4);
#pragma unroll
    for (int i = 0; i < 8; i++) ldsm_t(a[i >> 2][i & 3], (ab + (i >> 2) * 2048) ^ ((i & 3) << 5));
    uint4 v;
    const unsigned* pc = g_xc + (4 * (b >> 4) + 2 * rk + (warp >> 2)) * 256 + 64 * (warp & 3) + 2 * lane;
    uint32_t ro = ((tq >> 1) == rk ? sb : psb) + OFF_P + (8 * (tq & 1) + g) * 144 + (8 * rk + warp) * 8;
    uint32_t a_q = sb + OFF_P + (8 * (lane >> 4) + (lane & 7)) * 144;
    unsigned* p_ao = g_xao + (b >> 5) * 1024 + (opos >> 4) * 32 + (b & 16) + (opos & 15);
    PIN(ro); PIN(a_q); PINL(p_ao); PINL(pc);
    spin_until(tpub + DLY5);
    POLL {
      const unsigned long long u0 = ldx64(pc);
      v.x = (unsigned)u0; v.y = u0 >> 32;
      RETRY(X8(v))
    }
    v.z = lane & 16 ? v.x : 0u; v.w = lane & 16 ? v.y : 0u;
    if (lane & 16) v.x = v.y = 0u;
    float d[4][4] = {};
#pragma unroll
    for (int mt = 0; mt < 4; mt++) mma16(d[mt], a[0][mt], v.x, v.y);
#pragma unroll
    for (int mt = 0; mt < 4; mt++) mma16(d[mt], a[1][mt], v.z, v.w);
    float r[8];
#pragma unroll
    for (int i = 0; i < 8; i++) r[i] = d[i >> 1][2 * (i & 1)] + d[i >> 1][2 * (i & 1) + 1];
    tred<4>(r, lane, 2); tred<2>(r, lane, 1);
    st_pair((tq >> 1) == rk ? 1 : 2, ro, psb + OFF_BAR + 8 * (XB + 3), r[0], r[1]);
    __syncwarp();
    if (lane == 0) BAR_ARRIVE(XB + 3);
    if (warp == 0) {
      mbar_wait(bar0 + 8 * (XB + 3));
      float p[8];
#pragma unroll
      for (int i = 0; i < 8; i++) {
        const float4 q = lds16(a_q + i * 16);
        p[i] = (lane & 8) ? q.y + q.w : q.x + q.z;
      }
      const float t = ((p[0] + p[1]) + (p[2] + p[3])) + ((p[4] + p[5]) + (p[6] + p[7]));
      stx4(p_ao, fbits(gav * t + xv));
    }
  }
  tpub = clock();
  if (b < 112) {
    uint32_t af[2][4][4], ad[4][4];
    const uint32_t ab = sb + (32 * warp + 8 * (lane >> 4) + (lane & 7)) * 64 + ((((lane >> 3) & 1) ^ ((lane >> 1) & 3)) << 4);
    uint32_t ro = ((tq & 1) == rk ? sb : psb) + OFF_R4 + (8 * (tq >> 1) + g) * 176 + (10 * rk + warp) * 8;
    uint32_t a_q = sb + OFF_R4 + (8 * (lane >> 4) + (lane & 7)) * 176 + (lane & 8) * 10;
    uint32_t a_d = sb + OFF_D + warp * 2048 + (8 * (lane >> 4) + (lane & 7)) * 128 + ((((lane >> 3) & 1) ^ (lane & 7)) << 4);
    unsigned* p_f = g_xf + b * 512 + 64 * warp + 16 * tq + 2 * g;
    const unsigned* pa = g_xao + (g >> 1) * 1024 + 512 * rk + 64 * warp + 4 * (lane & 7);
    PIN(ro); PIN(a_q); PIN(a_d); PINL(p_f); PINL(pa);
    spin_until(tpub + DLY6);
    uint4 v[2];
    {
      bool have = false;
      POLL {
        v[0] = ldx16(pa); v[1] = ldx16(pa + 32);
        const unsigned t1 = (unsigned)clock() + WTEST;
        while (!have && (int)((unsigned)clock() - t1) < 0) {
          uint32_t ok;
          asm volatile("{.reg .pred p, q; mbarrier.test_wait.parity.shared::cta.b64 p, [%1], 0; mbarrier.test_wait.parity.shared::cta.b64 q, [%1+8], 0;\n"
                       "and.pred p, p, q; vote.sync.all.pred p, p, 0xffffffff; selp.u32 %0, 1, 0, p;}" : "=r"(ok) : "r"(bar0 + 8 * FB_G) : "memory");
          if (ok) {
#pragma unroll
            for (int i = 0; i < 8; i++) ldsm_t(af[i >> 2][i & 3], (ab + ((i & 2) ? OFF_U : OFF_G) + (i >> 2) * 1024) ^ ((i & 1) << 5));
            have = true;
          }
        }
        if (!__any_sync(~0u, (X16(v[0]) | X16(v[1])) & 1) || ++it_ >= SPIN_MAX) break;
      }
      float df[4][4] = {}, dg[2][4] = {};
      uint32_t zb[4];
      const uint32_t one = g == 0 ? 0x3F803F80u : 0u;
#pragma unroll
      for (int s = 0; s < 2; s++) {
        const uint32_t y0 = pack2(u2f(v[s].x), u2f(v[s].y)), y1 = pack2(u2f(v[s].z), u2f(v[s].w));
        const uint32_t ya[4] = {y0, one, y1, one};
        mma16(dg[s], ya, y0, y1);
        zb[2 * s] = pack2(u2f(v[s].x) * cf[s].x, u2f(v[s].y) * cf[s].y); zb[2 * s + 1] = pack2(u2f(v[s].z) * cf[s].z, u2f(v[s].w) * cf[s].w);
      }
      float st[2] = {(dg[0][2] + dg[0][3]) + (dg[1][2] + dg[1][3]), (dg[0][0] + dg[0][1]) + (dg[1][0] + dg[1][1])};
      if (!have) {
        mbar_wait(bar0 + 8 * FB_G); mbar_wait(bar0 + 8 * (FB_G + 1));
#pragma unroll
        for (int i = 0; i < 8; i++) ldsm_t(af[i >> 2][i & 3], (ab + ((i & 2) ? OFF_U : OFF_G) + (i >> 2) * 1024) ^ ((i & 1) << 5));
      }
#pragma unroll
      for (int i = 0; i < 8; i++) mma16(df[i & 3], af[i >> 2][i & 3], zb[2 * (i >> 2)], zb[2 * (i >> 2) + 1]);
#pragma unroll
      for (int o2 = 1; o2 < 4; o2 <<= 1) { st[0] += __shfl_xor_sync(~0u, st[0], o2); st[1] += __shfl_xor_sync(~0u, st[1], o2); }
#pragma unroll
      for (int o2 = 4; o2 < 32; o2 <<= 1) st[1] += __shfl_xor_sync(~0u, st[1], o2);
      float r[8];
#pragma unroll
      for (int i = 0; i < 8; i++) r[i] = df[i >> 1][2 * (i & 1)] + df[i >> 1][2 * (i & 1) + 1];
      tred<4>(r, lane, 2); tred<2>(r, lane, 1);
      const int md = (tq & 1) == rk ? 1 : 2;
      st_pair(md, ro, psb + OFF_BAR + 8 * (XB + 5), r[0], r[1]);
      st_pair(lane < 2 ? md : 0, ro + 16 * 176, psb + OFF_BAR + 8 * (XB + 5), st[0], st[1]);
      __syncwarp();
      if (lane == 0) BAR_ARRIVE(XB + 5);
      mbar_wait(bar0 + 8 * FB_D);
#pragma unroll
      for (int mt = 0; mt < 4; mt++)
        ldsm_t(ad[mt], a_d ^ (mt << 5));
    }
    mbar_wait(bar0 + 8 * (XB + 5));
    {
      float4 q[5], u[8];
#pragma unroll
      for (int i = 0; i < 5; i++) q[i] = lds16(a_q + i * 16);
#pragma unroll
      for (int i = 0; i < 8; i++) u[i] = *(const float4*)(smem + OFF_R4 + 16 * 176 + (i >> 2) * 80 + (i & 3) * 16);
      float p[6] = {((q[0].x + q[0].z) + (q[1].x + q[1].z)) + ((q[2].x + q[2].z) + (q[3].x + q[3].z)), q[4].x, q[4].z,
                    ((q[0].y + q[0].w) + (q[1].y + q[1].w)) + ((q[2].y + q[2].w) + (q[3].y + q[3].w)), q[4].y, q[4].w};
      tred<3>(p, lane, 8);
      const float P = p[0], A1 = p[1], A2 = p[2];
      const float mean = (((u[0].x + u[0].z) + (u[1].x + u[1].z)) + ((u[2].x + u[2].z) + (u[3].x + u[3].z)) +
                          ((u[4].x + u[4].z) + (u[5].x + u[5].z)) + ((u[6].x + u[6].z) + (u[7].x + u[7].z))) * (1.f / 512.f);
      const float sq = (((u[0].y + u[0].w) + (u[1].y + u[1].w)) + ((u[2].y + u[2].w) + (u[3].y + u[3].w)) +
                         ((u[4].y + u[4].w) + (u[5].y + u[5].w)) + ((u[6].y + u[6].w) + (u[7].y + u[7].w))) * (1.f / 512.f);
      float rstd;
      asm("rsqrt.approx.ftz.f32 %0, %1;" : "=f"(rstd) : "f"(fmaxf(sq - mean * mean, 0.f) + 1e-5f));
      const float gg = bfr(rstd * (P - mean * A1) + A2);
      const float uu = __shfl_xor_sync(~0u, gg, 16);
      const float hh = bfr(gg * rcp(1.f + ex2(gg * (-2.302208198f - 0.1029432397f * gg * gg)))) * uu;
      const uint32_t hw = pack2(hh, __shfl_down_sync(~0u, hh, 1));
      const uint32_t b0 = __shfl_sync(~0u, hw, 2 * tq), b1 = __shfl_sync(~0u, hw, 2 * tq + 8);
      float f0 = 0, f1 = 0;
#pragma unroll
      for (int mt = 0; mt < 4; mt++) {
        float dd[4] = {0, 0, 0, 0};
        mma16(dd, ad[mt], b0, b1);
        if (tq == mt) { f0 = dd[0]; f1 = dd[2]; }
      }
      stx8(p_f, make_uint2(fbits(f0), fbits(f1)));
    }
    tpub = clock();
    if (b < 64 && warp == (b >> 3)) {
      const uint4 y = (b & 4) ? v[1] : v[0];
      float a4[4] = {u2f(y.x), u2f(y.y), u2f(y.z), u2f(y.w)};
      tred<2>(a4, lane, 16); tred<1>(a4, lane, 8);
      a4[0] += __shfl_xor_sync(~0u, a4[0], 4);
      if (!(lane & 4)) s_sm[416 + 8 * (lane >> 4) + 2 * tq + ((lane >> 3) & 1)] = a4[0];
      if (warp == 7) nbar_arrive(2, 256);
    } else if (b < 64 && warp == 7) nbar_arrive(2, 256);
    if (b < 64 && warp < 7) {
      uint4 v;
      const unsigned* pf = g_xf + (tid >> 1) * 512 + 8 * ob + 4 * (tid & 1);
      const int col = 16 * (ob >> 1) + 4 * (ob & 1) + ((tid >> 1) & 3) + 8 * (tid & 1);
      bf16* po = out + col;
      PINL(po); PINL(pf);
      spin_until(tpub + DLY7);
      POLL { v = ldx16(pf); RETRY(X16(v)) }
      float f[4] = {u2f(v.x), u2f(v.y), u2f(v.z), u2f(v.w)};
      tred<2>(f, lane, 16); tred<1>(f, lane, 8);
      f[0] += __shfl_xor_sync(~0u, f[0], 4); f[0] += __shfl_xor_sync(~0u, f[0], 2);
      if (!(lane & 6)) s_sm[352 + warp * 8 + 4 * (lane & 1) + (lane >> 3)] = f[0];
      nbar(2, 256);
      if (tid < 8) {
        const float* q = s_sm + 352 + tid;
        const float t = ((q[0] + q[8]) + (q[16] + q[24])) + ((q[32] + q[40]) + q[48]);
        *po = __float2bfloat16(s_sm[416 + (col & 15)] + bfr(gbv * bfr(t)));
        if (b == 0 && tid == 0) stx4(&g_epoch, epoch + 1);
      }
    }
  }
}

__global__ void __cluster_dims__(2, 1, 1) __launch_bounds__(384, 1)
fused_kernel(const bf16* __restrict__ x, const bf16* __restrict__ cvec, const bf16* __restrict__ w_mod, bf16* __restrict__ out,
             Scratch* __restrict__ scr, const __grid_constant__ TMaps tms) {
  extern __shared__ __align__(1024) unsigned char smem[];
  const int tid = threadIdx.x, warp = __shfl_sync(~0u, tid >> 5, 0), lane = tid & 31;
  const int b = blockIdx.x, rk = b & 1, pr = b >> 1, hd = b >> 2;
  uint32_t sb = s2u(smem), bar0 = sb + OFF_BAR;

  unsigned gt_start;
  asm volatile("mov.u32 %0, %%globaltimer_lo;" : "=r"(gt_start));
  const int g = lane >> 2, tq = lane & 3;
  const int arow = 64 * (b >> 4) + ((tid & 255) >> 3);
  uint4 wm0, wm1;
  uint32_t c0w, c1w;
  if (warp < 8) {
    const bf16* wa = w_mod + (size_t)arow * 3072 + (lane & 4) * 128 + 32 * (b & 15) + 8 * tq;
    wm0 = ldx16(wa); wm1 = ldx16(wa + 32 * 3072);
    c0w = ldc4(cvec + (arow & ~1)); c1w = ldc4(cvec + (arow & ~1) + 32);
  }
  const unsigned t_off = gt_start + RATE_T0;
  if (warp == 11) {
    if (lane == 0) {
#pragma unroll
      for (int i = 0; i < FB_KV; i++) { BAR_INIT(i, 1); BAR_ARM(i, 16384); }
    }
    __syncwarp();
    asm volatile("fence.mbarrier_init.release.cluster;" ::: "memory");
    asm volatile("barrier.cluster.arrive.relaxed.aligned;" ::: "memory");
#pragma unroll 1
    for (int i = 0; i < FB_KV; i++) {
      if (i >= HWIN) mbar_wait(bar0 + 8 * (i - HWIN));
      wait_until(t_off + (i < 4 ? 2 * i + ((b >> 1) & 1) : 4 * i - 8 + (b & 3)) * (RATE_H / 4));
      if (lane == 0) {
        if (i < 4) tma3d(sb + OFF_WQ + i * 16384, &tms.m[0], bar0 + 8 * i, 0, i * 128, 2 * hd + rk);
        else tma3d(sb + OFF_WQ + i * 16384, &tms.m[1], bar0 + 8 * i, 0, (b & 3) * 128 + (i - 4) * 64, 2 * hd);
      }
      __syncwarp();
    }
  }
  if (warp == 10) {
    const uint4 xa = ldc16(x + 16 * lane), xb = ldc16(x + 16 * lane + 8);
    const unsigned ep = ldc4(&g_epoch);
    float xv[16] = {bflo(xa.x), bfhi(xa.x), bflo(xa.y), bfhi(xa.y), bflo(xa.z), bfhi(xa.z), bflo(xa.w), bfhi(xa.w),
                    bflo(xb.x), bfhi(xb.x), bflo(xb.y), bfhi(xb.y), bflo(xb.z), bfhi(xb.z), bflo(xb.w), bfhi(xb.w)};
    float s = 0;
#pragma unroll
    for (int i = 0; i < 16; i++) s += xv[i];
#pragma unroll
    for (int o = 16; o; o >>= 1) s += __shfl_xor_sync(~0u, s, o);
    const float mean = s * (1.f / 512.f);
    s = 0;
#pragma unroll
    for (int i = 0; i < 16; i++) { xv[i] -= mean; s += xv[i] * xv[i]; }
#pragma unroll
    for (int o = 16; o; o >>= 1) s += __shfl_xor_sync(~0u, s, o);
    const float rstd = rsqrtf(s * (1.f / 512.f) + 1e-5f);
    if ((lane >> 1) == (b & 15))
#pragma unroll
      for (int i = 0; i < 4; i++)
        *(float4*)(smem + OFF_SM + (256 + (lane & 1) * 16 + 4 * i) * 4) = make_float4(xv[4 * i] * rstd, xv[4 * i + 1] * rstd, xv[4 * i + 2] * rstd, xv[4 * i + 3] * rstd);
    if (lane == 0) *(volatile unsigned*)(smem + OFF_MASK + 8) = ep;
    nbar_arrive(1, 288);
  }
  if (warp >= 8) {
    asm volatile("setmaxnreg.dec.sync.aligned.u32 72;");
    if (tid == 288) {
#pragma unroll
      for (int q = FB_KV; q < FB_KV + 16; q++) { BAR_INIT(q, 1); BAR_ARM(q, 32768); }
    }
    if (tid == 320) {
#pragma unroll
      for (int q = 0; q <= 13 + NSLOT; q++) BAR_INIT(EB + q, q == 0 ? 4 : q < 5 ? 16 : q < 16 ? 12 : 6);
    }
    if (tid == 256) {
#pragma unroll
      for (int q = FB_MOD; q <= FB_D; q++) { BAR_INIT(q, 1); BAR_ARM(q, 16384); }
      BAR_INIT(QB, 9); BAR_ARM(QB, 1024);
#pragma unroll
      for (int q = 0; q < 7; q++) BAR_INIT(XB + q, q == 2 ? 256 : q == 5 || q == 3 ? 9 : 1);
      BAR_ARM(XB + 3, 1024);
      BAR_ARM(XB + 5, 1024 + 64 + 512);
      *(volatile unsigned long long*)(smem + OFF_MASK) = 0;
    }
    if (warp != 11) {
      __syncwarp();
      asm volatile("fence.mbarrier_init.release.cluster;" ::: "memory");
      __threadfence_block();
      asm volatile("barrier.cluster.arrive.relaxed.aligned;" ::: "memory");
    }
    if (warp == 11) {
      asm volatile("barrier.cluster.wait.acquire.aligned;" ::: "memory");
      const unsigned epoch = *(volatile unsigned*)(smem + OFF_MASK + 8), par = (epoch + 1) & 1;
      mbar_wait(bar0 + 8 * (FB_KV + 15));
      for (int it = 0; ldx4(scr->cnt + 96 + 32 * (b >> 6)) != (epoch + 1) * 64 && it < SPIN_MAX; it++) {}
      uint4 hh;
      POLL { hh = ldx16(g_ml + (b >> 2) * 64 + 2 * lane); RETRY(X16(hh)) }
      int mi = __float_as_int(fmaxf(u2f(hh.x), u2f(hh.z)));
      mi ^= (mi >> 31) & 0x7fffffff;
      mi = __reduce_max_sync(~0u, mi);
      mi ^= (mi >> 31) & 0x7fffffff;
      const float M = __int_as_float(mi);
      const uint32_t wp = pack2(ex2(u2f(hh.x) - M), ex2(u2f(hh.z) - M));
      float L = bflo(wp) * u2f(hh.y) + bfhi(wp) * u2f(hh.w);
#pragma unroll
      for (int o2 = 16; o2; o2 >>= 1) L += __shfl_xor_sync(~0u, L, o2);
      *(uint32_t*)(smem + OFF_RA + lane * 4) = wp;
      if (lane == 0) *(float*)(smem + OFF_RA + 128) = rcp(L);
      __syncwarp();
      if (lane == 0) BAR_ARRIVE(XB + 6);
    }
    if (warp == 10) {
      if (lane < 8) asm volatile("prefetch.tensormap [%0];" ::"l"(&tms.m[lane + 1]) : "memory");
      asm volatile("barrier.cluster.wait.acquire.aligned;" ::: "memory");
      const unsigned epoch = *(volatile unsigned*)(smem + OFF_MASK + 8);
#pragma unroll 1
      for (int e = 0; e < 2; e++) {
        for (int it = 0; ldx4(scr->cnt + (e ? 2 + rk : 1)) != (epoch + 1) * (e ? 64 : 128) && it < SPIN_MAX; it++) {}
        if (lane == 0) BAR_ARRIVE(XB + e);
      }
      mbar_wait(bar0 + 8 * (FB_KV + 14));
      unsigned long long m = 0;
#pragma unroll 1
      for (int it = 0; ~m && it < SPIN_MAX; it++) {
        m = ldx64(scr->cnt + 32 + 32 * (b >> 6)) ^ ((epoch & 1) ? ~0ull : 0ull);
        if (lane == 0) *(volatile unsigned long long*)(smem + OFF_MASK) = m;
      }
    }
    if (warp == 9) {
      asm volatile("barrier.cluster.wait.acquire.aligned;" ::: "memory");
      const unsigned epoch = *(volatile unsigned*)(smem + OFF_MASK + 8);
      const unsigned par = (epoch + 1) & 1, inv = par ^ 1;
      const uint4 inv4 = make_uint4(inv, inv, inv, inv);
      mbar_wait(bar0 + 8 * FB_KV);
#pragma unroll 2
      for (int k = 0; k < 8; k++) {
        const uint32_t cp = ldc4(cvec + 2 * (lane + 32 * k));
        *(uint32_t*)(smem + OFF_SILU + (lane + 32 * k) * 4) = pack2(silu_bf(bflo(cp)), silu_bf(bfhi(cp)));
      }
      __syncwarp();
      mbar_wait(bar0 + 8 * FB_MOD);
      const uint32_t ab = sb + OFF_MOD + (8 * (lane >> 4) + (lane & 7)) * 32 + ((((lane >> 3) ^ (lane >> 2)) & 1) << 4);
      float d[4][4] = {};
#pragma unroll 2
      for (int s4 = 0; s4 < 8; s4++)
#pragma unroll
        for (int s = 0; s < 4; s++) {
          uint32_t a[4];
          const uint32_t* ps = (const uint32_t*)(smem + OFF_SILU) + 32 * s4 + 8 * s + tq;
          ldsm_t(a, ab + (4 * s4 + s) * 512); mma16(d[s], a, ps[0], ps[4]);
        }
      const float t = (tq & 1) ? (d[0][2] + d[1][2]) + (d[2][2] + d[3][2]) : (d[0][0] + d[1][0]) + (d[2][0] + d[3][0]);
      if (tq < 2) stx4(g_xm + b * 16 + 2 * (g & 6) + 2 * tq + (g & 1), fbits(bfr(t)));
      __syncwarp();
      if (lane == 0) CNT_ADD(6);
      mbar_wait(bar0 + 8 * (FB_KV + 8));
      if (lane < 16) stx16(g_xc + (b >> 2) * 256 + (lane >> 1) * 32 + (b & 3) * 8 + (lane & 1) * 4, inv4);
      if (lane < 8) stx16(g_xao + (b >> 5) * 1024 + (b & 15) * 64 + (lane & 4) * 8 + (b & 16) + (lane & 3) * 4, inv4);
      if (b < 112)
#pragma unroll 1
        for (int k = 0; k < 4; k++) stx16(g_xf + b * 512 + (lane + 32 * k) * 4, inv4);
      nbar_arrive(2, 288);
      for (int it = 0; ldx4(scr->cnt + 6) != (epoch + 1) * 128 && it < SPIN_MAX; it++) __nanosleep(100);
      {
        uint4 sv[2], cb[2];
        unsigned ga, gb;
        POLL {
#pragma unroll
          for (int k = 0; k < 2; k++) { sv[k] = ldx16(g_xm + 512 + 256 * rk + 4 * (lane + 32 * k)); cb[k] = ldx16(g_xm + 1024 + 256 * rk + 4 * (lane + 32 * k)); }
          ga = ldx4(g_xm + (b & 15) * 32 + lane); gb = ldx4(g_xm + 1536 + 256 * rk + 8 * (pr & 31) + (lane & 7));
          RETRY(X16(sv[0]) | X16(sv[1]) | X16(cb[0]) | X16(cb[1]) | lop_x3(ga, gb, par))
        }
#pragma unroll
        for (int k = 0; k < 2; k++) {
          const float c0 = bfr(1.f + bfhi(cb[k].x)), c1 = bfr(1.f + bfhi(cb[k].y)), c2 = bfr(1.f + bfhi(cb[k].z)), c3 = bfr(1.f + bfhi(cb[k].w));
          *(float4*)(smem + OFF_CO + (lane + 32 * k) * 16) = make_float4(c0, c1, c2, c3);
          uint2* pb = (uint2*)(smem + OFF_BP) + lane + 32 * k;
          pb[0] = make_uint2(pack2(c0, c1), pack2(c2, c3));
          pb[64] = make_uint2(__byte_perm(sv[k].x, sv[k].y, 0x7632), __byte_perm(sv[k].z, sv[k].w, 0x7632));
        }
        *(float*)(smem + OFF_CO + 1024 + lane * 4) = bfhi(ga);
        *(float*)(smem + OFF_CO + 1152 + lane * 4) = bfhi(gb);
      }
      __syncwarp();
      if (lane == 0) BAR_ARRIVE(XB + 4);
    }
    if (warp == 8) {
      const unsigned stag = ((pr * SMUL) & 63) * RATE_NS >> 6;
      unsigned tnext = t_off + 4 * RATE_H;
      asm volatile("barrier.cluster.wait.acquire.aligned;" ::: "memory");
#pragma unroll 1
      for (int k = 0; k < 24; k++) {
        const int code = (k < 12 ? ORDER0 >> (5 * k) : ORDER1 >> (5 * (k - 12))) & 31;
        const bool kv = code < 16;
        const int n = code, w = code - 16;
        if (!kv && w >= 5 && b >= 112) break;
        if (kv) mbar_wait(bar0 + 8 * (FB_KV + n - (n < 6 ? EWIN : KVWIN)));
        if (k >= TAIL_K) mbar_wait(bar0 + 8 * (FB_KV + (int)((ORDER1 >> (5 * (k - 12 - ((WINS >> (4 * (k - TAIL_K))) & 15)))) & 31)));
        const int e = kv ? (n == 3 ? 2 : n == 5 ? 1 : n) : w == 0 ? 0 : w < 5 ? 16 + ((w - 1) >> 1) : w == 7 ? 19 : 18;
        if (e != 1 && k) mbar_wait(bar0 + 8 * (EB + e));
        wait_until(tnext + stag);
        tnext += k > TAIL_K ? RATE_TL : k < 4 ? RATE_E : RATE_NS;
        if (lane == 0) {
          if (kv)
            asm volatile("cp.async.bulk.tensor.3d.shared::cluster.global.mbarrier::complete_tx::bytes.multicast::cluster.L2::cache_hint [%0], [%1, {%3, %4, %5}], [%2], %6, %7;"
                         ::"r"(sb + (n % NSLOT) * SLOT + rk * 16384), "l"(&tms.m[2]), "r"(bar0 + 8 * (FB_KV + n)), "r"(0), "r"(((n >> 1) * 64 + pr) * 64),
                           "r"(4 * (n & 1) + 2 * rk), "h"((unsigned short)3), "l"(stream_policy()) : "memory");
          else {
            tma3d(sb + (w == 0 ? OFF_MOD : w < 5 ? OFF_UV + (w - 1) * 16384 : w == 5 ? OFF_G : w == 6 ? OFF_U : OFF_D),
                  &tms.m[w == 0 ? 3 : w < 3 ? 4 : w < 5 ? 5 : w + 1], bar0 + 8 * (FB_MOD + w),
                  w == 0 ? 1024 + b * 16 : w < 3 || w == 7 ? 0 : w < 5 ? (pr & 7) * 64 : pr * 32, w == 7 ? b * 16 : w == 1 || w == 2 ? (b & 3) * 128 + (w - 1) * 64 : 0,
                  w == 1 || w == 2 ? 2 * hd : w == 3 || w == 4 ? (b >> 4) * 4 + 2 * rk + w - 3 : w == 5 || w == 6 ? rk : 0);
          }
        }
        __syncwarp();
      }
    }
    if (b < 112) {
      const int mt = warp & 1, dd = (warp >> 1) & 1;
      mbar_wait(bar0 + 8 * (XB + 4));
      const uint32_t ab = sb + (mt ? OFF_U : OFF_G) + (8 * (lane >> 4) + (lane & 7)) * 64 + (((2 * dd + ((lane >> 3) & 1)) ^ ((lane >> 1) & 3)) << 4);
      uint32_t base;
      asm volatile("mapa.shared::cluster.u32 %0, %1, %2;" : "=r"(base) : "r"(sb), "r"(dd));
      uint2 bb[16];
#pragma unroll
      for (int s = 0; s < 16; s++) bb[s] = *(const uint2*)(smem + OFF_BP + (g & 1) * 512 + (4 * s + tq) * 8);
      mbar_wait(bar0 + 8 * (FB_G + mt));
      float e[4][4] = {};
#pragma unroll
      for (int s = 0; s < 16; s++) { uint32_t a[4]; ldsm_t(a, ab + s * 1024); mma16(e[s & 3], a, bb[s].x, bb[s].y); }
      float r[4];
#pragma unroll
      for (int i = 0; i < 4; i++) r[i] = (e[0][i] + e[1][i]) + (e[2][i] + e[3][i]);
      if (tq < 2) st_async2(base + OFF_R4 + (8 * mt + g) * 176 + (10 * rk + 8 + tq) * 8, base + OFF_BAR + 8 * (XB + 5), tq ? r[1] : r[0], tq ? r[3] : r[2]);
    }
    return;
  }

  float* s_sm = (float*)(smem + OFF_SM);
  unsigned par, epoch;
  uint32_t rsb;
  {
    float* s_r4 = (float*)(smem + OFF_R4);
    asm volatile("barrier.cluster.arrive.relaxed.aligned;" ::: "memory");
    asm volatile("mapa.shared::cluster.u32 %0, %1, %2;" : "=r"(rsb) : "r"(sb), "r"(rk ^ 1));
    const float c0 = (arow & 1) ? bfhi(c0w) : bflo(c0w), c1 = (arow & 1) ? bfhi(c1w) : bflo(c1w);
    float acc[8] = {0, 0, 0, 0, 0, 0, 0, 0};
    fma8(acc, wm0, silu_bf(c0)); fma8(acc, wm1, silu_bf(c1));
    tred<4>(acc, lane, 8); tred<2>(acc, lane, 16);
    *(float2*)(s_r4 + warp * 64 + 8 * (lane & 7) + ((lane >> 1) & 4) + ((lane >> 3) & 2)) = make_float2(acc[0], acc[1]);
    nbar(1, 288);
    epoch = *(volatile unsigned*)(smem + OFF_MASK + 8);
    par = (epoch + 1) & 1;
    if (warp == 0) {
      float t = 0.f, ca = b < 16 ? 1.f : 0.f;
#pragma unroll
      for (int w = 0; w < 8; w++) { t += s_r4[w * 64 + lane]; ca += s_r4[w * 64 + 32 + lane]; }
      t += ca * s_sm[256 + lane];
      const float nb = __shfl_down_sync(~0u, t, 1);
      const uint32_t w0 = lane < 8 ? pack2t(t, nb, par) : pack2(t, nb);
      const uint32_t w1 = __shfl_down_sync(~0u, w0, 8), w2 = __shfl_down_sync(~0u, w0, 16), w3 = __shfl_down_sync(~0u, w0, 24);
      if (lane < 8 && !(lane & 1)) stx16(g_h + (b >> 5) * 512 + (b & 15) * 32 + (b & 16) + 2 * lane, make_uint4(w0, w1, w2, w3));
      __syncwarp();
      if (lane == 0) CNT_ADD(1);
    }
  }
  asm volatile("barrier.cluster.wait.acquire.aligned;" ::: "memory");
  {
    uint32_t a[4][4][4];
    mbar_wait(bar0 + 8 * (warp >> 1));
    const uint32_t ab = sb + OFF_WQ + (64 * warp + 8 * (lane >> 4) + (lane & 7)) * 128;
#pragma unroll
    for (int s = 0; s < 4; s++)
#pragma unroll
      for (int mt = 0; mt < 4; mt++) ldsm_t(a[s][mt], ab + s * 2048 + (((2 * mt + ((lane >> 3) & 1)) ^ (lane & 7)) << 4));
    uint4 v0, v1;
    const unsigned* ph = g_h + (g >> 1) * 512 + 64 * warp + 4 * (lane & 7);
    uint32_t off = OFF_B + warp * 272 + (32 * rk + 8 * tq + (lane & 4)) * 4;
    PIN(off); PINL(ph);
    mbar_wait(bar0 + 8 * XB);
    POLL { v0 = ldx16(ph); v1 = ldx16(ph + 32); RETRY(lop_x3(v0.x, v1.x, par)) }
    float d[4][4] = {};
#pragma unroll
    for (int mt = 0; mt < 4; mt++) {
      mma16(d[mt], a[0][mt], v0.x, v0.y); mma16(d[mt], a[1][mt], v0.z, v0.w);
      mma16(d[mt], a[2][mt], v1.x, v1.y); mma16(d[mt], a[3][mt], v1.z, v1.w);
    }
    float r[8];
#pragma unroll
    for (int mt = 0; mt < 4; mt++) { r[2 * mt] = d[mt][0] + d[mt][1]; r[2 * mt + 1] = d[mt][2] + d[mt][3]; }
    tred<4>(r, lane, 2); tred<2>(r, lane, 1);
    const float rc = __shfl_xor_sync(~0u, (lane & 4) ? r[0] : r[1], 4);
    const uint32_t wd = (lane & 4) ? pack2(rc, r[1]) : pack2(r[0], rc);
    const uint32_t w1 = __shfl_down_sync(~0u, wd, 8), w2 = __shfl_down_sync(~0u, wd, 16), w3 = __shfl_down_sync(~0u, wd, 24);
    asm volatile("{.reg .pred p; setp.lt.s32 p, %7, 8; @p st.shared.v4.b32 [%0], {%2,%3,%4,%5};\n"
                 "@p st.async.shared::cluster.mbarrier::complete_tx::bytes.v4.b32 [%1], {%2,%3,%4,%5}, [%6];}"
                 ::"r"(sb + off), "r"(rsb + off), "r"(wd), "r"(w1), "r"(w2), "r"(w3), "r"(rsb + OFF_BAR + 8 * QB), "r"(lane) : "memory");
    __syncwarp();
    arrive2(bar0 + 8 * QB, 0, lane == 0, false);
    arrive2(bar0 + 8 * (EB + 2), rsb + OFF_BAR + 8 * (EB + 2), lane == 0, lane == 0);
  }
  {
    uint32_t a[8][4];
    uint32_t a_bq = sb + OFF_B + (lane & 7) * 272 + (lane >> 3) * 16;
    unsigned* p_qa = g_qa + b * 64 + 8 * warp + 4 * lane;
    PIN(a_bq); PINL(p_qa);
    mbar_wait(bar0 + 8 * (FB_UK + (warp >> 2)));
    const uint32_t ab = sb + OFF_WUK + (warp >> 2) * 16384 + (16 * (warp & 3) + (lane & 15)) * 128;
#pragma unroll
    for (int s = 0; s < 8; s++) ldsm(a[s], ab + (s >> 2) * 8192 + (((2 * (s & 3) + (lane >> 4)) ^ (lane & 7)) << 4));
    mbar_wait(bar0 + 8 * QB);
    float d[4][4] = {};
#pragma unroll
    for (int y = 0; y < 4; y++) {
      uint32_t bq[4];
      ldsm(bq, a_bq + 64 * y);
      mma16(d[(2 * y) & 3], a[2 * y], bq[0], bq[1]); mma16(d[(2 * y + 1) & 3], a[2 * y + 1], bq[2], bq[3]);
    }
    float r[2] = {((d[0][0] + d[0][1]) + (d[1][0] + d[1][1])) + ((d[2][0] + d[2][1]) + (d[3][0] + d[3][1])),
                  ((d[0][2] + d[0][3]) + (d[1][2] + d[1][3])) + ((d[2][2] + d[2][3]) + (d[3][2] + d[3][3]))};
    tred<1>(r, lane, 1);
    r[0] += __shfl_xor_sync(~0u, r[0], 2);
    const float nb = __shfl_xor_sync(~0u, r[0], 4);
    const uint32_t w0 = lane < 8 ? pack2t(r[0], nb, par) : pack2(r[0], nb);
    const uint32_t w1 = __shfl_down_sync(~0u, w0, 8), w2 = __shfl_down_sync(~0u, w0, 16), w3 = __shfl_down_sync(~0u, w0, 24);
    if (lane < 2) stx16(p_qa, make_uint4(w0, w1, w2, w3));
    arrive2(bar0 + 8 * (EB + 4), rsb + OFF_BAR + 8 * (EB + 4), lane == 0, lane == 0);
  }
  {
    if (warp) nbar_arrive(3, 256); else { nbar(3, 256); if (lane == 0) CNT_ADD(2 + (b >> 6)); }
    asm volatile("setmaxnreg.inc.sync.aligned.u32 216;");
    const unsigned* pq = g_qa + rk * 4096 + tid * 4;
    uint32_t a_q = sb + OFF_Q + ((tid & 63) >> 3) * 2048 + (tid >> 6) * 128 + (((tid & 7) ^ (tid >> 6)) << 4);
    PINL(pq); PIN(a_q);
    mbar_wait(bar0 + 8 * (XB + 1));
    uint4 v[4];
    POLL {
#pragma unroll
      for (int k = 0; k < 4; k++) v[k] = ldx16(pq + 1024 * k);
      RETRY(lop_x3(v[0].x, v[1].x, par) | lop_x3(v[2].x, v[3].x, par))
    }
#pragma unroll
    for (int k = 0; k < 4; k++)
      asm volatile("st.shared.v4.b32 [%0], {%1,%2,%3,%4};" ::"r"((a_q + k * 512) ^ ((k & 1) << 6)), "r"(v[k].x), "r"(v[k].y), "r"(v[k].z), "r"(v[k].w) : "memory");
    if (warp >= 4) nbar_arrive(1, 256); else nbar(1, 256);
  }
  sb = __shfl_sync(~0u, sb, 0); bar0 = sb + OFF_BAR;
  if (warp < 4) {
    uint32_t qf[32][4];
#pragma unroll
    for (int s = 0; s < 32; s++) ldsm(qf[s], sb + OFF_Q + (s >> 2) * 2048 + (lane & 15) * 128 + (((2 * (s & 3) + (lane >> 4)) ^ (lane & 7)) << 4));
    float l0 = 0.f, l1 = 0.f, m0 = -1e30f, m1 = -1e30f;
    const float sc = 0.08838834764831845f * 1.4426950408889634f;
    const uint32_t kofs = (16 * warp + 8 * (lane >> 4) + (lane & 7)) * 128 + ((((lane >> 3) & 1) ^ (lane & 7)) << 4);
    uint32_t st = sb;
#pragma unroll 1
    for (int t = 0; t < 8; t++) {
      float sa[4][4] = {};
#pragma unroll
      for (int hf = 0; hf < 2; hf++) {
        const int n = 2 * t + hf;
        mbar_wait(bar0 + 8 * (FB_KV + n));
        uint32_t kf[16][4];
#pragma unroll
        for (int y = 0; y < 16; y++) ldsm(kf[y], st + (y >> 2) * 8192 + (kofs ^ ((y & 3) << 5)));
#pragma unroll
        for (int y = 0; y < 16; y++) {
          mma16(sa[(2 * y) & 3], qf[16 * hf + y], kf[y][0], kf[y][1]); mma16(sa[((2 * y) & 3) + 1], qf[16 * hf + y], kf[y][2], kf[y][3]);
        }
        __syncwarp();
        arrive2(bar0 + 8 * (EB + NSLOT + n), rsb + OFF_BAR + 8 * (EB + NSLOT + n), lane == 0 && n < 14, lane == 0 && n < 16 - NSLOT);
        if (hf == 0) arrive2(bar0 + 8 * EB, 0, lane == 0 && t == 0, false);
        st = st + SLOT == sb + NSLOT * SLOT ? sb : st + SLOT;
      }
#pragma unroll
      for (int i = 0; i < 4; i++) { sa[0][i] = (sa[0][i] + sa[2][i]) * sc; sa[1][i] = (sa[1][i] + sa[3][i]) * sc; }
      float cm[2] = {fmaxf(fmaxf(sa[0][0], sa[0][1]), fmaxf(sa[1][0], sa[1][1])), fmaxf(fmaxf(sa[0][2], sa[0][3]), fmaxf(sa[1][2], sa[1][3]))};
      tmax<1>(cm, lane, 1);
      cm[0] = fmaxf(cm[0], __shfl_xor_sync(~0u, cm[0], 2));
      float* pm = s_sm + (t & 1) * 64;
      if (tq < 2) pm[(g + 8 * tq) * 4 + warp] = cm[0];
      if (t >= 2) nbar(6 + (t & 1), 256); else nbar(3, 128);
      const float4 a0 = *(const float4*)(pm + g * 4), b0 = *(const float4*)(pm + g * 4 + 32);
      const float n0 = fmaxf(fmaxf(fmaxf(a0.x, a0.y), fmaxf(a0.z, a0.w)), m0), n1 = fmaxf(fmaxf(fmaxf(b0.x, b0.y), fmaxf(b0.z, b0.w)), m1);
      uint32_t pk[4];
#pragma unroll
      for (int i = 0; i < 2; i++) { pk[2 * i] = pack2(ex2(sa[i][0] - n0), ex2(sa[i][1] - n0)); pk[2 * i + 1] = pack2(ex2(sa[i][2] - n1), ex2(sa[i][3] - n1)); }
      *(uint4*)(smem + OFF_P + (t & 1) * 2048 + tid * 16) = make_uint4(pk[0], pk[1], pk[2], pk[3]);
      const float al0 = ex2(m0 - n0), al1 = ex2(m1 - n1);
      if (tid < 32 && tq == 0) *(float2*)(s_sm + 192 + (t & 1) * 16 + 2 * g) = make_float2(al0, al1);
      nbar_arrive(4 + (t & 1), 256);
      m0 = n0; m1 = n1;
      l0 = l0 * al0 + (bflo(pk[0]) + bfhi(pk[0])) + (bflo(pk[2]) + bfhi(pk[2]));
      l1 = l1 * al1 + (bflo(pk[1]) + bfhi(pk[1])) + (bflo(pk[3]) + bfhi(pk[3]));
    }
    float lr[2] = {l0, l1};
    tred<1>(lr, lane, 1);
    lr[0] += __shfl_xor_sync(~0u, lr[0], 2);
    if (tq < 2) s_sm[128 + (g + 8 * tq) * 4 + warp] = lr[0];
    nbar(3, 128);
    if (warp == 0 && tq < 2) {
      const float4 a0 = *(const float4*)(s_sm + 128 + (g + 8 * tq) * 4);
      stx8(g_ml + (16 * rk + g + 8 * tq) * 64 + pr, make_uint2(fbits(tq ? m1 : m0), fbits((a0.x + a0.y) + (a0.z + a0.w))));
    }
    if (warp == 0) { __syncwarp(); if (lane == 0) CNT_ADD(96 + 32 * rk); }
    nbar(2, 288);
    if (tid == 0) asm volatile("red.relaxed.gpu.global.xor.b64 [%0], %1;" ::"l"(scr->cnt + 32 + 32 * rk), "l"(1ull << pr) : "memory");
  } else {
    float o[16][4] = {};
    const uint32_t vofs = (warp & 1) * 16384 + (lane & 15) * 128 + (((lane >> 4) ^ (lane & 7)) << 4);
    const int hf = (warp >> 1) & 1;
    uint32_t st = sb + hf * SLOT;
    auto pv = [&](const int t, auto np) {
      constexpr int npre = decltype(np)::value;
      uint32_t vf[4][8][4];
      const int n = 2 * t + hf;
      mbar_wait(bar0 + 8 * (FB_KV + n));
#pragma unroll
      for (int s = 0; s < npre; s++)
#pragma unroll
        for (int y = 0; y < 8; y++) ldsm_t(vf[s][y], st + (y >> 2) * 8192 + s * 2048 + (vofs ^ ((y & 3) << 5)));
      nbar(4 + (t & 1), 256);
      const float2 al = *(const float2*)(s_sm + 192 + (t & 1) * 16 + 2 * g);
      uint4 pf[4];
#pragma unroll
      for (int s = 0; s < 4; s++) pf[s] = *(const uint4*)(smem + OFF_P + (t & 1) * 2048 + s * 512 + lane * 16);
      if (t < 6) nbar_arrive(6 + (t & 1), 256);
#pragma unroll
      for (int s = npre; s < 4; s++)
#pragma unroll
        for (int y = 0; y < 8; y++) ldsm_t(vf[s][y], st + (y >> 2) * 8192 + s * 2048 + (vofs ^ ((y & 3) << 5)));
#pragma unroll
      for (int nt = 0; nt < 16; nt++) { o[nt][0] *= al.x; o[nt][1] *= al.x; o[nt][2] *= al.y; o[nt][3] *= al.y; }
#pragma unroll
      for (int s = 0; s < 4; s++) {
        const uint32_t pa[4] = {pf[s].x, pf[s].y, pf[s].z, pf[s].w};
#pragma unroll
        for (int y = 0; y < 8; y++) { mma16(o[2 * y], pa, vf[s][y][0], vf[s][y][1]); mma16(o[2 * y + 1], pa, vf[s][y][2], vf[s][y][3]); }
      }
      __syncwarp();
      arrive2(bar0 + 8 * (EB + NSLOT + n), rsb + OFF_BAR + 8 * (EB + NSLOT + n), lane == 0 && n < 14, lane == 0 && n < 16 - NSLOT);
      st = st + 2 * SLOT >= sb + NSLOT * SLOT ? st - (NSLOT - 2) * SLOT : st + 2 * SLOT;
    };
#pragma unroll 1
    for (int t = 0; t < 7; t++) pv(t, IC<NPRE0>());
    pv(7, IC<NPRE1>());
    uint4* po = g_xo + ((size_t)((16 * rk + (g & 6)) * 4 + warp - 4) * 64 + pr) * RS + (lane & 7);
    const bool odd = lane & 4;
#pragma unroll
    for (int e = 0; e < 2; e++)
#pragma unroll
      for (int j2 = 0; j2 < 2; j2++) {
        uint32_t c0[4], c1[4];
#pragma unroll
        for (int i = 0; i < 4; i++) {
          c0[i] = i ? pack2(o[8 * j2 + i][2 * e], o[8 * j2 + i][2 * e + 1]) : pack2t(o[8 * j2][2 * e], o[8 * j2][2 * e + 1], par);
          c1[i] = i ? pack2(o[8 * j2 + 4 + i][2 * e], o[8 * j2 + 4 + i][2 * e + 1]) : pack2t(o[8 * j2 + 4][2 * e], o[8 * j2 + 4][2 * e + 1], par);
          const uint32_t r = __shfl_xor_sync(~0u, odd ? c0[i] : c1[i], 4);
          if (odd) c0[i] = r; else c1[i] = r;
        }
        stx16(po + e * 8 * 4 * 64 * RS + 8 * j2, make_uint4(c0[0], c0[1], c0[2], c0[3]));
        stx16(po + (e * 8 + 1) * 4 * 64 * RS + 8 * j2, make_uint4(c1[0], c1[1], c1[2], c1[3]));
      }
    nbar_arrive(2, 288);
  }
  tail(smem, scr, x, out, par, epoch, warp);
}

static void launch(void* const* d_in, void* d_out) {
  static TMaps tms;
  static bool init = false;
  static void* scr = nullptr;
  if (!init) {
    void* fn = nullptr; cudaDriverEntryPointQueryResult qr;
    cudaGetDriverEntryPoint("cuTensorMapEncodeTiled", &fn, cudaEnableDefault, &qr);
    EncFn f = (EncFn)fn;
    const CUtensorMapSwizzle S32 = CU_TENSOR_MAP_SWIZZLE_32B, S64 = CU_TENSOR_MAP_SWIZZLE_64B, S128 = CU_TENSOR_MAP_SWIZZLE_128B;
    const CUtensorMapL2promotion P128 = CU_TENSOR_MAP_L2_PROMOTION_L2_128B, P256 = CU_TENSOR_MAP_L2_PROMOTION_L2_256B;
    enc3d(f, &tms.m[0], d_in[2], 64, 512, 64, 8192, 128, 64, 128, 1, S128, P128);
    enc3d(f, &tms.m[1], d_in[3], 64, 512, 64, 8192, 128, 64, 64, 2, S128, P256);
    enc3d(f, &tms.m[2], d_in[1], 64, SK, 8, 1024, 128, 64, 64, 2, S128, P256);
    enc3d(f, &tms.m[3], d_in[11], 3072, 256, 2, 6144, 256 * 6144, 16, 256, 2, S32, P128);
    enc3d(f, &tms.m[4], d_in[4], 64, 512, 64, 8192, 128, 64, 64, 2, S128, P256);
    enc3d(f, &tms.m[5], d_in[5], 512, 128, 32, 1024, 128 * 1024, 64, 128, 1, S128, P128);
    enc3d(f, &tms.m[6], d_in[7], 1792, 256, 2, 3584, 256 * 3584, 32, 256, 1, S64, P128);
    enc3d(f, &tms.m[7], d_in[8], 1792, 256, 2, 3584, 256 * 3584, 32, 256, 1, S64, P128);
    enc3d(f, &tms.m[8], d_in[9], 64, 1792, 8, 1024, 128, 64, 16, 8, S128, P256);
    cudaFuncSetAttribute(fused_kernel, cudaFuncAttributeMaxDynamicSharedMemorySize, SMEM_BYTES);
    cudaGetSymbolAddress(&scr, g_scr);
    init = true;
  }
  fused_kernel<<<NCTA, 384, SMEM_BYTES>>>((const bf16*)d_in[0], (const bf16*)d_in[10], (const bf16*)d_in[11], (bf16*)d_out, (Scratch*)scr, tms);
}

}

extern "C" void kernel_launch(void* const* d_in, const int* in_sizes, int n_in, void* d_out, int out_size) {
  static int big = -1;
  if (big < 0) big = v9::fits();
  if (big) v9::launch(d_in, d_out); else v8::launch(d_in, d_out);
}
```

```cpp
#include <cuda_runtime.h>
#include <cuda_bf16.h>
#include <cuda.h>
#include <stdint.h>
#include <stdio.h>
#include <stdlib.h>

typedef CUresult (*EncFn)(CUtensorMap*, CUtensorMapDataType, cuuint32_t, void*, const cuuint64_t*, const cuuint64_t*,
                          const cuuint32_t*, const cuuint32_t*, CUtensorMapInterleave, CUtensorMapSwizzle,
                          CUtensorMapL2promotion, CUtensorMapFloatOOBfill);

static void enc3d(EncFn fn, CUtensorMap* tm, void* p, uint64_t d0, uint64_t d1, uint64_t d2, uint64_t s1, uint64_t s2, uint32_t b0,
                  uint32_t b1, uint32_t b2, CUtensorMapSwizzle sw, CUtensorMapL2promotion pr) {
  cuuint64_t gd[3] = {d0, d1, d2}, gs[2] = {s1, s2};
  cuuint32_t bx[3] = {b0, b1, b2}, es[3] = {1, 1, 1};
  fn(tm, CU_TENSOR_MAP_DATA_TYPE_BFLOAT16, 3, p, gd, gs, bx, es, CU_TENSOR_MAP_INTERLEAVE_NONE, sw, pr, CU_TENSOR_MAP_FLOAT_OOB_FILL_NONE);
}

namespace v9 {
typedef __nv_bfloat16 bf16;
#define SK 32768
#define SPIN_MAX (1 << 20)
template <int N> struct IC { static constexpr int value = N; };

__device__ __forceinline__ uint32_t s2u(const void* p) { return (uint32_t)__cvta_generic_to_shared(p); }
__device__ __forceinline__ float bflo(uint32_t u) { return __uint_as_float(u << 16); }
__device__ __forceinline__ float bfhi(uint32_t u) { return __uint_as_float(u & 0xffff0000u); }
__device__ __forceinline__ float u2f(uint32_t u) { return __uint_as_float(u); }
__device__ __forceinline__ void fma8(float* acc, uint4 v, float s) {
  acc[0] += s * bflo(v.x); acc[1] += s * bfhi(v.x); acc[2] += s * bflo(v.y); acc[3] += s * bfhi(v.y);
  acc[4] += s * bflo(v.z); acc[5] += s * bfhi(v.z); acc[6] += s * bflo(v.w); acc[7] += s * bfhi(v.w);
}
__device__ __forceinline__ uint32_t pack2(float a, float b) {
  __nv_bfloat162 p = __floats2bfloat162_rn(a, b); return *(uint32_t*)&p;
}
__device__ __forceinline__ float bfr(float v) { return bfhi(pack2(v, v)); }
__device__ __forceinline__ float silu_bf(float c) { return bfr(__fdividef(c, 1.f + __expf(-c))); }
#define fbits(v) ((__float_as_uint(v) & ~1u) | par)
__device__ __forceinline__ uint32_t pack2t(float a, float b, unsigned par) {
  const uint32_t ua = ((__float_as_uint(a) + ((par ^ 1) << 16)) & 0xFFFE0000u) | (par << 16);
  return __byte_perm(ua, pack2(b, b), 0x7632);
}
__device__ __forceinline__ void nbar(int id, int n) { asm volatile("bar.sync %0, %1;" ::"r"(id), "r"(n) : "memory"); }
__device__ __forceinline__ void nbar_arrive(int id, int n) { asm volatile("bar.arrive %0, %1;" ::"r"(id), "r"(n) : "memory"); }
__device__ __forceinline__ uint4 ldc16(const void* p) {
  uint4 v; asm volatile("ld.relaxed.cta.global.v4.u32 {%0,%1,%2,%3}, [%4];" : "=r"(v.x), "=r"(v.y), "=r"(v.z), "=r"(v.w) : "l"(p) : "memory"); return v;
}
__device__ __forceinline__ unsigned ldc4(const void* p) {
  unsigned v; asm volatile("ld.relaxed.cta.global.u32 %0, [%1];" : "=r"(v) : "l"(p) : "memory"); return v;
}
__device__ __forceinline__ uint4 ldx16(const void* p) {
  uint4 v; asm volatile("ld.relaxed.gpu.global.v4.u32 {%0,%1,%2,%3}, [%4];" : "=r"(v.x), "=r"(v.y), "=r"(v.z), "=r"(v.w) : "l"(p) : "memory"); return v;
}
__device__ __forceinline__ unsigned ldx4(const void* p) {
  unsigned v; asm volatile("ld.relaxed.gpu.global.u32 %0, [%1];" : "=r"(v) : "l"(p) : "memory"); return v;
}
__device__ __forceinline__ unsigned long long ldx64(const void* p) {
  unsigned long long v; asm volatile("ld.relaxed.gpu.global.u64 %0, [%1];" : "=l"(v) : "l"(p) : "memory"); return v;
}
__device__ __forceinline__ void stx16(void* p, uint4 v) {
  asm volatile("st.relaxed.gpu.global.v4.u32 [%0], {%1,%2,%3,%4};" ::"l"(p), "r"(v.x), "r"(v.y), "r"(v.z), "r"(v.w) : "memory");
}
__device__ __forceinline__ void stx8(void* p, uint2 v) { asm volatile("st.relaxed.gpu.global.v2.u32 [%0], {%1,%2};" ::"l"(p), "r"(v.x), "r"(v.y) : "memory"); }
__device__ __forceinline__ void stx4(void* p, unsigned v) { asm volatile("st.relaxed.gpu.global.u32 [%0], %1;" ::"l"(p), "r"(v) : "memory"); }
__device__ __forceinline__ void pub4(void* p, unsigned v) { asm volatile("red.relaxed.gpu.global.xor.b32 [%0], %1;" ::"l"(p), "r"(v) : "memory"); }
__device__ __forceinline__ void pub8(void* p, unsigned lo, unsigned hi) {
  asm volatile("{.reg .b64 t; mov.b64 t, {%1, %2}; red.relaxed.gpu.global.xor.b64 [%0], t;}" ::"l"(p), "r"(lo), "r"(hi) : "memory");
}
__device__ __forceinline__ unsigned lop_x3(unsigned a, unsigned b, unsigned c) {
  unsigned d; asm("lop3.b32 %0, %1, %2, %3, 0x7E;" : "=r"(d) : "r"(a), "r"(b), "r"(c)); return d; }
__device__ __forceinline__ unsigned or3(unsigned a, unsigned b, unsigned c) {
  unsigned d; asm("lop3.b32 %0, %1, %2, %3, 0xFE;" : "=r"(d) : "r"(a), "r"(b), "r"(c)); return d; }
__device__ __forceinline__ unsigned and3(unsigned a, unsigned b, unsigned c) {
  unsigned d; asm("lop3.b32 %0, %1, %2, %3, 0x80;" : "=r"(d) : "r"(a), "r"(b), "r"(c)); return d; }
__device__ __forceinline__ unsigned dep16(const uint32_t* f) {
  unsigned d = 0;
#pragma unroll
  for (int i = 0; i < 8; i++) d = or3(d, f[8 * i], f[8 * i + 4]);
  return d;
}
__device__ __forceinline__ uint2 ldx8(const void* p) {
  uint2 v; asm volatile("{.reg .b64 t; ld.relaxed.gpu.global.b64 t, [%2]; mov.b64 {%0, %1}, t;}" : "=r"(v.x), "=r"(v.y) : "l"(p) : "memory"); return v;
}
__device__ __forceinline__ float lds4(uint32_t a) { float v; asm volatile("ld.shared.f32 %0, [%1];" : "=f"(v) : "r"(a) : "memory"); return v; }
__device__ __forceinline__ float shx(float v, int m) {
  float r; asm volatile("shfl.sync.bfly.b32 %0, %1, %2, 0x1f, 0xffffffff;" : "=f"(r) : "f"(v), "r"(m)); return r;
}
__device__ __forceinline__ uint32_t mbar_test(uint32_t bar, uint32_t ph) {
  uint32_t ok;
  asm volatile("{.reg .pred p; mbarrier.test_wait.parity.shared::cta.b64 p, [%1], %2; vote.sync.all.pred p, p, 0xffffffff; selp.u32 %0, 1, 0, p;}"
               : "=r"(ok) : "r"(bar), "r"(ph) : "memory");
  return ok;
}
#define X16(v) (lop_x3(v.x, v.y, par) | lop_x3(v.z, v.w, par))
#define RETRY(bad) if (!__any_sync(~0u, (bad) & 1) || ++it_ >= SPIN_MAX) break;
#define POLL _Pragma("unroll 1") for (int it_ = 0;;)
__device__ __forceinline__ void mbar_wait(uint32_t bar, uint32_t ph = 0) {
  asm volatile("{.reg .pred p; .reg .u32 n; mov.u32 n, 0;\n"
               "W%=: mbarrier.try_wait.parity.shared::cta.b64 p, [%0], %1; add.u32 n, n, 1; setp.lt.and.u32 p, n, 0x100000, !p; @p bra W%=;}"
               ::"r"(bar), "r"(ph) : "memory");
}
__device__ __forceinline__ float ex2(float v) { float r; asm("ex2.approx.ftz.f32 %0, %1;" : "=f"(r) : "f"(v)); return r; }
__device__ __forceinline__ float rcp(float v) { float r; asm("rcp.approx.ftz.f32 %0, %1;" : "=f"(r) : "f"(v)); return r; }
__device__ __forceinline__ void mma16(float* d, const uint32_t* a, uint32_t b0, uint32_t b1) {
  asm volatile("mma.sync.aligned.m16n8k16.row.col.f32.bf16.bf16.f32 {%0,%1,%2,%3}, {%4,%5,%6,%7}, {%8,%9}, {%0,%1,%2,%3};"
               : "+f"(d[0]), "+f"(d[1]), "+f"(d[2]), "+f"(d[3]) : "r"(a[0]), "r"(a[1]), "r"(a[2]), "r"(a[3]), "r"(b0), "r"(b1));
}
__device__ __forceinline__ void mma16c(float* d, const uint32_t* a, uint32_t b0, uint32_t b1, const float* c) {
  asm volatile("mma.sync.aligned.m16n8k16.row.col.f32.bf16.bf16.f32 {%0,%1,%2,%3}, {%4,%5,%6,%7}, {%8,%9}, {%10,%11,%12,%13};"
               : "=f"(d[0]), "=f"(d[1]), "=f"(d[2]), "=f"(d[3])
               : "r"(a[0]), "r"(a[1]), "r"(a[2]), "r"(a[3]), "r"(b0), "r"(b1), "f"(c[0]), "f"(c[1]), "f"(c[2]), "f"(c[3]));
}
__device__ __forceinline__ float4 lds16(uint32_t a) {
  float4 v; asm volatile("ld.shared.v4.f32 {%0,%1,%2,%3}, [%4];" : "=f"(v.x), "=f"(v.y), "=f"(v.z), "=f"(v.w) : "r"(a) : "memory"); return v;
}
__device__ __forceinline__ uint4 ldsv16(uint32_t a) {
  uint4 v; asm volatile("ld.relaxed.cluster.shared.v4.u32 {%0,%1,%2,%3}, [%4];" : "=r"(v.x), "=r"(v.y), "=r"(v.z), "=r"(v.w) : "r"(a) : "memory"); return v;
}
__device__ __forceinline__ void sts4(uint32_t a, float v) { asm volatile("st.shared.f32 [%0], %1;" ::"r"(a), "f"(v) : "memory"); }
__device__ __forceinline__ void sts16(uint32_t a, uint4 v) {
  asm volatile("st.shared.v4.b32 [%0], {%1,%2,%3,%4};" ::"r"(a), "r"(v.x), "r"(v.y), "r"(v.z), "r"(v.w) : "memory");
}
__device__ __forceinline__ void ldsm_t(uint32_t* r, uint32_t a) {
  asm volatile("ldmatrix.sync.aligned.m8n8.x4.trans.shared.b16 {%0,%1,%2,%3}, [%4];" : "=r"(r[0]), "=r"(r[1]), "=r"(r[2]), "=r"(r[3]) : "r"(a) : "memory");
}
__device__ __forceinline__ void ldsm(uint32_t* r, uint32_t a) {
  asm volatile("ldmatrix.sync.aligned.m8n8.x4.shared.b16 {%0,%1,%2,%3}, [%4];" : "=r"(r[0]), "=r"(r[1]), "=r"(r[2]), "=r"(r[3]) : "r"(a) : "memory");
}
__device__ __forceinline__ uint32_t mapa(uint32_t a, uint32_t r) {
  uint32_t v; asm volatile("mapa.shared::cluster.u32 %0, %1, %2;" : "=r"(v) : "r"(a), "r"(r)); return v;
}
__device__ __forceinline__ unsigned long long mapg(uint32_t a, uint32_t r) {
  unsigned long long v;
  asm volatile("{.reg .u32 t; .reg .u64 u; mapa.shared::cluster.u32 t, %1, %2; cvt.u64.u32 u, t; cvta.shared::cluster.u64 %0, u;}" : "=l"(v) : "r"(a), "r"(r));
  return v;
}
template <int N>
__device__ __forceinline__ void tred(float* a, int lane, int m) {
  const bool hi = lane & m;
#pragma unroll
  for (int i = 0; i < N; i++) {
    float send = hi ? a[i] : a[i + N], keep = hi ? a[i + N] : a[i];
    a[i] = keep + __shfl_xor_sync(~0u, send, m);
  }
}
template <int N>
__device__ __forceinline__ void tmax(float* a, int lane, int m) {
  const bool hi = lane & m;
#pragma unroll
  for (int i = 0; i < N; i++) {
    float send = hi ? a[i] : a[i + N], keep = hi ? a[i + N] : a[i];
    a[i] = fmaxf(keep, __shfl_xor_sync(~0u, send, m));
  }
}
__device__ __forceinline__ void arrive_n(uint32_t bar, bool on, int cnt) {
  asm volatile("{.reg .pred p; setp.ne.s32 p, %1, 0; @p mbarrier.arrive.shared::cta.b64 _, [%0], %2;}" ::"r"(bar), "r"((int)on), "r"(cnt) : "memory");
}
__device__ __forceinline__ unsigned long long stream_policy() {
  unsigned long long p;
  asm volatile("createpolicy.fractional.L2::evict_first.b64 %0, 1.0;" : "=l"(p));
  return p;
}
__device__ __forceinline__ void tma3d(uint32_t dst, const CUtensorMap* tm, uint32_t bar, int c0, int c1, int c2) {
  asm volatile("cp.async.bulk.tensor.3d.shared::cluster.global.mbarrier::complete_tx::bytes.L2::cache_hint [%0], [%1, {%3, %4, %5}], [%2], %6;"
               ::"r"(dst), "l"(tm), "r"(bar), "r"(c0), "r"(c1), "r"(c2), "l"(stream_policy()) : "memory");
}
__device__ __forceinline__ void spin_until(unsigned t) { while ((int)((unsigned)clock() - t) < 0) {} }
__device__ __forceinline__ void wait_until(unsigned t) {
  unsigned now;
  do { asm volatile("mov.u32 %0, %%globaltimer_lo;" : "=r"(now)); } while ((int)(now - t) < 0);
}
__device__ __forceinline__ void sleep_until(unsigned t) {
  unsigned now;
#pragma unroll 1
  do {
    __nanosleep(200);
    asm volatile("mov.u32 %0, %%globaltimer_lo;" : "=r"(now));
  } while ((int)(now - t) < 0);
}
#define PIN(x) asm volatile("" : "+r"(x))
#define PINL(x) asm volatile("" : "+l"(x))
#define BAR_ARRIVE(i) asm volatile("mbarrier.arrive.shared::cta.b64 _, [%0];" ::"r"(bar0 + 8 * (i)) : "memory")
#define LANE0(op, p, c, v) asm volatile("{.reg .pred q; setp.eq.s32 q, %2, 0; @q " op " [%0], %1;}" ::"l"((p) + lane), c(v), "r"(lane) : "memory")
#define CNT_ADD(c) LANE0("red.relaxed.gpu.global.add.u32", scr->cnt + (c), "r", 1)
#define BAR_INIT(i, cnt) asm volatile("mbarrier.init.shared::cta.b64 [%0], %1;" ::"r"(bar0 + 8 * (i)), "r"(cnt) : "memory")
#define BAR_ARM(i, bytes) asm volatile("mbarrier.arrive.expect_tx.shared::cta.b64 _, [%0], %1;" ::"r"(bar0 + 8 * (i)), "r"(bytes) : "memory")
struct TMaps { CUtensorMap m[9]; };

#define NCTA9 120
#define TAU 20
#define NSL 100
#define NPE 2
#define QN 4
#define FDLY 60
#define VJ 1
#define NPO 3
#define VDLY 150
#define O_Q 131072
#define O_LZ 163840
#define O_CTX 196608
#define O_HZ 198656
#define O_HW 200704
#define O_X 201728
#define O_P 218112
#define O_B 222208
#define O_R 224512
#define O_SILU 228608
#define O_SM 229632
#define O_BAR 231424
#define O_EP (O_BAR + 256)
#define O_DBG (O_EP + 16)
#define SMEM9 (O_DBG + 144)
#define B_FULL 0
#define B_FM 8
#define B_EMPTY 10
#define B_EM 18
#define B_LZ 18
#define B_Q2 19
#define B_H 20
#define B_QF 21
#define B_TAB 22
#define B_W 23
#define B_ST 24
#define B_HZ 25
#define B_WZ 26
#define B_G2 28
#define B_G 27
enum { T_WQ, T_WUK, T_KV, T_MOD, T_UV, T_WO, T_GU, T_DN = 8 };
#define NBIG 40
struct Sched { unsigned zero, dth; uint2 r[3][8]; unsigned nr[3], nt[3], dt, t4, d4, d6, wt, pad; };

struct __align__(128) Scratch {
  unsigned cnt[8 * 32];
  uint2 rec[32 * 4 * 8 * 64];
  uint2 hdr[32 * 16];
  unsigned h[8 * 256];
  uint4 qa[2048];
  unsigned xao[8 * 512];
  unsigned xab[8 * 256];
  unsigned xm[2048];
};
__device__ Scratch g_scr;
#define SMEM_BASE 1024u
#define DSC ((SMEM_BASE >> 4) | (1u << 16))
#define HI128 (64u | (1u << 30))
#define HI64 (32u | (2u << 30))
template <int TA, int TB, unsigned HIA, unsigned HIB>
__device__ __forceinline__ void wgmma32(float* d, uint32_t da, uint32_t db, int acc) {
  asm volatile("{.reg .pred p; .reg .b64 da, db; setp.ne.b32 p, %18, 0; mov.b64 da, {%16, %21}; mov.b64 db, {%17, %22};\n"
               "wgmma.mma_async.sync.aligned.m64n32k16.f32.bf16.bf16 "
               "{%0,%1,%2,%3,%4,%5,%6,%7,%8,%9,%10,%11,%12,%13,%14,%15}, da, db, p, 1, 1, %19, %20;}"
               : "+f"(d[0]), "+f"(d[1]), "+f"(d[2]), "+f"(d[3]), "+f"(d[4]), "+f"(d[5]), "+f"(d[6]), "+f"(d[7]),
                 "+f"(d[8]), "+f"(d[9]), "+f"(d[10]), "+f"(d[11]), "+f"(d[12]), "+f"(d[13]), "+f"(d[14]), "+f"(d[15])
               : "r"(da), "r"(db), "r"(acc), "n"(TA), "n"(TB), "n"(HIA), "n"(HIB));
}
__device__ __forceinline__ void wgmma32r(float* d, const uint32_t* a, uint32_t db) {
  asm volatile("{.reg .b64 db; mov.b64 db, {%20, %21};\n"
               "wgmma.mma_async.sync.aligned.m64n32k16.f32.bf16.bf16 "
               "{%0,%1,%2,%3,%4,%5,%6,%7,%8,%9,%10,%11,%12,%13,%14,%15}, {%16,%17,%18,%19}, db, 1, 1, 1, 1;}"
               : "+f"(d[0]), "+f"(d[1]), "+f"(d[2]), "+f"(d[3]), "+f"(d[4]), "+f"(d[5]), "+f"(d[6]), "+f"(d[7]),
                 "+f"(d[8]), "+f"(d[9]), "+f"(d[10]), "+f"(d[11]), "+f"(d[12]), "+f"(d[13]), "+f"(d[14]), "+f"(d[15])
               : "r"(a[0]), "r"(a[1]), "r"(a[2]), "r"(a[3]), "r"(db), "n"(HI64));
}
template <int N> __device__ __forceinline__ void wg_wait(float* a) {
  asm volatile("wgmma.wait_group.sync.aligned %16;"
               : "+f"(a[0]), "+f"(a[1]), "+f"(a[2]), "+f"(a[3]), "+f"(a[4]), "+f"(a[5]), "+f"(a[6]), "+f"(a[7]), "+f"(a[8]), "+f"(a[9]), "+f"(a[10]),
                 "+f"(a[11]), "+f"(a[12]), "+f"(a[13]), "+f"(a[14]), "+f"(a[15]) : "n"(N) : "memory");
}
__device__ __forceinline__ float sum8(uint32_t a) {
  const float4 p = lds16(a), q = lds16(a + 1024);
  return ((p.x + p.y) + (p.z + p.w)) + ((q.x + q.y) + (q.z + q.w));
}
__device__ __forceinline__ int posof(int c) { return (c & ~14) + 2 * (c & 6) + ((c >> 2) & 2); }

__global__ void __cluster_dims__(8, 1, 1) __launch_bounds__(384, 1)
fused_kernel(const bf16* __restrict__ x, const bf16* __restrict__ cvec, const bf16* __restrict__ w_mod, bf16* __restrict__ out,
             Scratch* __restrict__ scr, const __grid_constant__ Sched sch, const __grid_constant__ TMaps tms) {
  extern __shared__ __align__(1024) unsigned char smem[];
  const int tid = threadIdx.x, warp = __shfl_sync(~0u, tid >> 5, 0), lane = tid & 31;
  const int b = blockIdx.x, cl = b >> 3, rn = b & 7, rk = b & 1, hd = b >> 1, f = b - 64;
  const bool isA = b < 64;
  uint32_t sb = s2u(smem), bar0 = sb + O_BAR;
  unsigned gt_start;
  asm volatile("mov.u32 %0, %%globaltimer_lo;" : "=r"(gt_start));
  const int g = lane >> 2, tq = lane & 3;
  const int arow = 64 * rn + ((tid & 255) >> 4);
  uint4 wm[4];
  uint32_t cw, xw;
  if (warp < 8 && isA) {
    const bf16* wa = w_mod + (size_t)arow * 3072 + (lane & 8) * 64 + 64 * cl + 8 * (lane & 7);
#pragma unroll
    for (int i = 0; i < 4; i++) wm[i] = ldx16(wa + i * 16 * 3072);
    cw = ldc4(cvec + (arow & ~1) + 16 * tq);
    if (warp < 2) xw = ldc4(x + 64 * cl + (tid & 62));
  }
  if (warp == 11) {
    if (lane == 0) {
#pragma unroll
      for (int i = 0; i < B_EMPTY; i++) BAR_INIT(i, 1);
    }
    __syncwarp();
    asm volatile("fence.mbarrier_init.release.cluster;" ::: "memory");
    asm volatile("barrier.cluster.arrive.relaxed.aligned;" ::: "memory");
    if (isA) {
#pragma unroll 1
      for (int i = 0; i < 8; i++) {
        if (i >= 6) mbar_wait(bar0 + 8 * (i - 6));
        wait_until(gt_start + ((64 * i + b) * sch.dth >> 8));
        if (lane == 0) {
          BAR_ARM(i, 16384);
          tma3d(sb + i * 16384, &tms.m[i >> 2], bar0 + 8 * i, 0, i < 4 ? 128 * i : 256 * rk + 64 * (i - 4), i < 4 ? b : b & ~1);
        }
        __syncwarp();
      }
    }
  }
  if (warp == 10) {
    const unsigned ep = ldc4(&scr->cnt[0]);
    if (isA) {
      const uint4 xa = ldc16(x + 16 * lane), xb = ldc16(x + 16 * lane + 8);
      float xv[16] = {bflo(xa.x), bfhi(xa.x), bflo(xa.y), bfhi(xa.y), bflo(xa.z), bfhi(xa.z), bflo(xa.w), bfhi(xa.w),
                      bflo(xb.x), bfhi(xb.x), bflo(xb.y), bfhi(xb.y), bflo(xb.z), bfhi(xb.z), bflo(xb.w), bfhi(xb.w)};
      const float x0 = __shfl_sync(~0u, xv[0], 0);
      float s = 0, q = 0;
#pragma unroll
      for (int i = 0; i < 16; i++) { xv[i] -= x0; s += xv[i]; q += xv[i] * xv[i]; }
#pragma unroll
      for (int o = 16; o; o >>= 1) { s += __shfl_xor_sync(~0u, s, o); q += __shfl_xor_sync(~0u, q, o); }
      s *= 1.f / 512.f;
      float rstd;
      asm("rsqrt.approx.ftz.f32 %0, %1;" : "=f"(rstd) : "f"(fmaxf(q * (1.f / 512.f) - s * s, 0.f) + 1e-5f));
      *(float2*)(smem + O_SM + 1024) = make_float2(s + x0, rstd);
    }
    if (lane == 0) *(volatile unsigned*)(smem + O_EP) = ep;
    nbar_arrive(1, 288);
  }
  const int cls = isA ? (b >= NBIG) : 2, v0 = isA ? 2 : 0;
  if (warp >= 8) {
    asm volatile("setmaxnreg.dec.sync.aligned.u32 56;");
    if (warp == 8) {
      if (lane < 8) asm volatile("prefetch.tensormap [%0];" ::"l"(&tms.m[lane + 1]) : "memory");
      if ((sb & 0xFFFFFF) != SMEM_BASE) __trap();
    } else if (warp == 9) {
      if (lane == 0) {
#pragma unroll
        for (int i = B_EMPTY; i < B_EM; i++) BAR_INIT(i, 8);
        BAR_INIT(B_LZ, 8); BAR_INIT(B_Q2, 9); BAR_ARM(B_Q2, 1024);
        BAR_INIT(B_H, 1); BAR_INIT(B_QF, 1); BAR_ARM(B_QF, 32768);
        BAR_INIT(B_TAB, 1); BAR_INIT(B_W, 1); BAR_INIT(B_ST, 8); BAR_INIT(B_WZ, 1); BAR_INIT(B_G, 1); BAR_INIT(B_G2, 1);
      }

    }
    if (warp != 11) {
      __syncwarp();
      asm volatile("fence.mbarrier_init.release.cluster;" ::: "memory");
      __threadfence_block();
      asm volatile("barrier.cluster.arrive.relaxed.aligned;" ::: "memory");
    }
    asm volatile("barrier.cluster.wait.acquire.aligned;" ::: "memory");
    if (warp == 8) {
      const int nr = sch.nr[cls], vl = v0 + sch.nt[cls] - 1;
      unsigned long long hist = 0;
      int v = v0;
#pragma unroll 1
      for (int rd = 0; rd < nr; rd++) {
        const uint2 e = sch.r[cls][rd];
        const int type = e.y & 15, win = (e.y >> 4) & 15, pos = b + 64 - (int)((e.y >> 8) & 255), tile = e.y >> 16;
        const bool mod = type == T_MOD;
        const int ni = mod ? 1 : type == T_DN ? 2 : 4;
        unsigned t = gt_start + (e.x & 0xffff) + (pos * sch.dt >> 8);
        const int c0 = mod ? 1024 + 32 * b : type == T_WO || type == T_DN ? 64 * rn : type == T_GU ? 32 * f : 0;
        int c1 = type == T_KV ? 64 * (tile + pos) : 0;
        int c2 = mod ? tile : type == T_WO ? 4 * cl : type == T_DN ? 2 * cl - 16 : type == T_UV ? b : 0;
        const int i1 = type == T_UV ? 128 : 0;
#pragma unroll 1
        for (int j = 0; j < ni; j++) {
          const int slot = mod ? B_FM + tile : (v & 1) * 4 + j;
          if (mod ? tile : v >= 2) mbar_wait(bar0 + 8 * (B_EMPTY + (mod ? (vl & 1) * 4 : slot)), mod ? (vl >> 1) & 1 : ((v >> 1) - 1) & 1);
          const int hw = (int)(hist >> (6 * (win - 1))) & 63;
          if (hw) mbar_wait(bar0 + 8 * (hw & 15), (hw >> 4) & 1);
          wait_until(t);
          if (lane == 0) {
            BAR_ARM(slot, 16384);
            tma3d(sb + (mod ? (tile ? O_Q : O_X) : slot * 16384), &tms.m[type == T_GU ? type + (j & 1) : type], bar0 + 8 * slot, c0, c1, c2);
          }
          __syncwarp();
          hist = hist << 6 | (32 | (mod ? 0 : (v & 2) << 3) | slot);
          t += e.x >> 16; c1 += i1;
          c2 += type == T_KV ? 2 : type == T_WO || type == T_DN ? 1 : type == T_GU ? j & 1 : 0;
        }
        v += !mod;
      }
      return;
    }
    const unsigned epoch = *(volatile unsigned*)(smem + O_EP), par = (epoch + 1) & 1;
    if (warp == 10) {
      if (isA) {
        for (int it = 0; ldx4(scr->cnt + 1) != (epoch + 1) * 128 && it < SPIN_MAX; it++) {}
        if (lane == 0) BAR_ARRIVE(B_H);
      } else mbar_wait(bar0);
      if (!(rn & (QN - 1))) {
        for (int it = 0; ldx4(scr->cnt + 32 + 32 * (rn >> 2)) != (epoch + 1) * 32 && it < SPIN_MAX; it++) {}
        if (lane == 0)
          asm volatile("cp.async.bulk.shared::cluster.global.mbarrier::complete_tx::bytes.multicast::cluster [%0], [%1], %4, [%2], %3;"
                       ::"r"(sb + O_Q + rn * 4096), "l"(scr->qa + rn * 256), "r"(bar0 + 8 * B_QF), "h"((unsigned short)0xff), "n"(4096 * QN) : "memory");
      }
      const unsigned dl = isA ? sch.d4 : sch.d6;
      unsigned tw = gt_start + sch.t4;
      if (!isA) {
        const int nt = sch.nt[2];
#pragma unroll 1
        for (int t = 0; t < nt; t++) mbar_wait(bar0 + 8 * B_EMPTY + (t & 1) * 32, (t >> 1) & 1);
        unsigned long long now;
        asm volatile("mov.u64 %0, %%globaltimer;" : "=l"(now));
        LANE0("red.relaxed.gpu.global.max.u64", scr->cnt + 130, "l", now);
        CNT_ADD(128);
        tw = (unsigned)now + 1700;
      }
      sleep_until(tw);
      uint4 an;
      for (int it = 0; an = ldx16(scr->cnt + 128), an.x != (epoch + 1) * 56 && it < SPIN_MAX; it++) {}
      wait_until(an.z + (dl >> 16));
      if (lane == 0) BAR_ARRIVE(B_G2);
      wait_until(an.z + (dl & 0xffff));
      if (lane == 0) BAR_ARRIVE(B_G);
    } else if (warp == 11) {
      {
        uint2* ph = scr->hdr + ((lane & 24) + 2 * tq + (g & 1)) * 16 + cl;
        const bool own = (lane >> 4) * 4 + tq == rn;
        if (own) { stx8(ph, make_uint2(par ^ 1, 0)); if (cl == 14) stx8(ph + 1, make_uint2(0, 0)); }
        uint32_t a_w = sb + O_HW + ((lane >> 4) * 4 + tq) * 128 + (g & 1) * 64 + ((lane >> 1) & 4);
        PIN(a_w); PINL(ph);
        const int vt = v0 + sch.nt[cls];
#pragma unroll 1
        for (int t = 0; t < vt; t++) mbar_wait(bar0 + 8 * B_EMPTY + (t & 1) * 32, (t >> 1) & 1);
        float hz[8], M;
        uint32_t wp[4];
#pragma unroll 1
        for (int e = 0; e < 2; e++) {
          POLL {
            unsigned ok = 1;
#pragma unroll
            for (int u = 0; u < 8; u++)
              asm volatile("ld.relaxed.cluster.shared.f32 %0, [%1];" : "=f"(hz[u]) : "r"(sb + O_HZ + e * 1024 + u * 128 + lane * 4) : "memory");
#pragma unroll
            for (int u = 0; u < 4; u++) ok = and3(ok, __float_as_uint(hz[u]), __float_as_uint(hz[u + 4]));
            RETRY(~ok)
          }
          if (e) break;
          M = fmaxf(fmaxf(fmaxf(hz[0], hz[1]), fmaxf(hz[2], hz[3])), fmaxf(fmaxf(hz[4], hz[5]), fmaxf(hz[6], hz[7])));
          M = u2f(fbits(M));
#pragma unroll
          for (int u = 0; u < 4; u++) {
            wp[u] = pack2(ex2(hz[u] - M), ex2(hz[u + 4] - M));
            sts4(a_w + ((rn - u) & 3) * 8, u2f(wp[u])); sts4(a_w + ((rn - u) & 3) * 8 + 32, u2f(wp[u]));
          }
          __syncwarp();
          if (lane == 0) BAR_ARRIVE(B_WZ);
        }
        float L = 0.f;
#pragma unroll
        for (int u = 0; u < 4; u++) L += bflo(wp[u]) * hz[u] + bfhi(wp[u]) * hz[u + 4];
        if (own) pub8(ph, __float_as_uint(M) | 1u, __float_as_uint(L));
      }
      if (isA) {
        mbar_wait(bar0 + 8 * B_G2);
        unsigned long long hh;
        POLL { hh = ldx64(scr->hdr + hd * 16 + (lane & 15)); RETRY((lane & 15) == 15 ? 0u : (unsigned)hh ^ par) }
        const float m = (lane & 15) == 15 ? -1e30f : u2f((unsigned)hh);
        int mi = __float_as_int(m);
        mi ^= (mi >> 31) & 0x7fffffff;
        mi = __reduce_max_sync(~0u, mi);
        mi ^= (mi >> 31) & 0x7fffffff;
        const float w = ex2(m - __int_as_float(mi));
        float L = w * u2f(hh >> 32);
#pragma unroll
        for (int o2 = 8; o2; o2 >>= 1) L += __shfl_xor_sync(~0u, L, o2);
        sts4(sb + O_SM + (384 + 2 * (lane & 6) + ((lane >> 2) & 2) + (lane & 1)) * 4, w * rcp(L));
        __syncwarp();
        if (lane == 0) BAR_ARRIVE(B_W);
      }
    } else {
#pragma unroll 4
      for (int i = 0; i < 72; i++) sts16(sb + O_LZ + i * 512 + lane * 16, make_uint4(0, 0, 0, 0));
      __syncwarp();
      if (lane < 8) asm volatile("mbarrier.arrive.release.cluster.shared::cluster.b64 _, [%0];" ::"r"(mapa(bar0 + 8 * B_LZ, lane)) : "memory");
      if (isA) {
        mbar_wait(bar0 + 8 * B_QF);
#pragma unroll 2
        for (int k = 0; k < 8; k++) {
          const uint32_t cp = ldc4(cvec + 2 * (lane + 32 * k));
          *(uint32_t*)(smem + O_SILU + (lane + 32 * k) * 4) = pack2(silu_bf(bflo(cp)), silu_bf(bfhi(cp)));
        }
        __syncwarp();
        uint32_t ab = sb + O_X + (8 * (lane >> 4) + (lane & 7)) * 64 + ((((lane >> 3) & 1) ^ ((lane >> 1) & 3)) << 4);
        float d[4][4] = {};
#pragma unroll 1
        for (int jm = 0; jm < 2; jm++) {
          mbar_wait(bar0 + 8 * (B_FM + jm));
#pragma unroll 2
          for (int s2 = 0; s2 < 8; s2++)
#pragma unroll
            for (int s = 0; s < 2; s++) {
              uint32_t a0[4], a1[4];
              const uint32_t* ps = (const uint32_t*)(smem + O_SILU) + 128 * jm + 16 * s2 + 8 * s + tq;
              ldsm_t(a0, ab + (2 * s2 + s) * 1024); ldsm_t(a1, (ab + (2 * s2 + s) * 1024) ^ 32);
              mma16(d[s], a0, ps[0], ps[4]); mma16(d[2 + s], a1, ps[0], ps[4]);
            }
          ab -= O_X - O_Q;
        }
        const float t0 = (tq & 1) ? d[0][2] + d[1][2] : d[0][0] + d[1][0], t1 = (tq & 1) ? d[2][2] + d[3][2] : d[2][0] + d[3][0];
        stx4(scr->xm + b * 32 + posof(8 * tq + g), fbits(bfr(bfr((tq & 2) ? t1 : t0) + ((b >> 4) == 2 ? 1.f : 0.f))));
        __syncwarp();
        CNT_ADD(96);
      } else sleep_until(gt_start + sch.t4);
      for (int it = 0; ldx4(scr->cnt + 96) != (epoch + 1) * 64 && it < SPIN_MAX; it++) __nanosleep(NSL);
      if (isA) {
        unsigned long long ga;
        POLL { ga = ldx64(scr->xm + 64 * rn + 2 * lane); RETRY(lop_x3((unsigned)ga, ga >> 32, par)) }
        *(float2*)(smem + O_SM + (320 + 2 * lane) * 4) = make_float2(bfhi((unsigned)ga), bfhi(ga >> 32));
      }
      __syncwarp();
      if (lane == 0) BAR_ARRIVE(B_TAB);
    }
    return;
  }

  float* s_sm = (float*)(smem + O_SM);
  unsigned par, epoch;
  asm volatile("barrier.cluster.arrive.relaxed.aligned;" ::: "memory");
  if (isA) {
    float* s_r = (float*)(smem + O_R);
    float acc[8] = {0, 0, 0, 0, 0, 0, 0, 0};
    const float sl = silu_bf((arow & 1) ? bfhi(cw) : bflo(cw));
#pragma unroll
    for (int i = 0; i < 4; i++) fma8(acc, wm[i], __shfl_sync(~0u, sl, i, 4));
    tred<4>(acc, lane, 16);
    *(float4*)(s_r + warp * 128 + 8 * (lane & 15) + ((lane >> 2) & 4)) = make_float4(acc[0], acc[1], acc[2], acc[3]);
    nbar(1, 288);
    epoch = *(volatile unsigned*)(smem + O_EP);
    par = (epoch + 1) & 1;
    if (warp < 2) {
      float t = 0.f, ca = rn == 0 ? 1.f : 0.f;
#pragma unroll
      for (int w = 0; w < 8; w++) { t += s_r[w * 128 + tid]; ca += s_r[w * 128 + 64 + tid]; }
      t += ca * ((((tid & 1) ? bfhi(xw) : bflo(xw)) - s_sm[256]) * s_sm[257]);
      const float nb = __shfl_down_sync(~0u, t, 1);
      const uint32_t w0 = lane < 8 ? pack2t(t, nb, par) : pack2(t, nb);
      const uint32_t w1 = __shfl_down_sync(~0u, w0, 8), w2 = __shfl_down_sync(~0u, w0, 16), w3 = __shfl_down_sync(~0u, w0, 24);
      if (lane < 8 && !(lane & 1)) stx16(scr->h + (rn >> 1) * 512 + (2 * cl + warp) * 32 + rk * 16 + 2 * lane, make_uint4(w0, w1, w2, w3));
      __syncwarp();
      CNT_ADD(1);
    }
    asm volatile("barrier.cluster.wait.acquire.aligned;" ::: "memory");
    const uint32_t rsb = mapa(sb, rn ^ 1);
    {
      uint32_t a[4][4][4];
      mbar_wait(bar0 + 8 * (warp >> 1));
      const uint32_t ab = sb + (64 * warp + 8 * (lane >> 4) + (lane & 7)) * 128;
#pragma unroll
      for (int s = 0; s < 4; s++)
#pragma unroll
        for (int mt = 0; mt < 4; mt++) ldsm_t(a[s][mt], ab + s * 2048 + (((2 * mt + ((lane >> 3) & 1)) ^ (lane & 7)) << 4));
      arrive_n(bar0 + 8 * (B_EMPTY + (warp >> 1)), lane == 0, 4 + (dep16(&a[0][0][0]) & sch.zero));
      uint4 v0, v1;
      const unsigned* ph = scr->h + (g >> 1) * 512 + 64 * warp + 4 * (lane & 7);
      uint32_t off = O_B + warp * 272 + (32 * rk + 8 * tq + (lane & 4)) * 4;
      PIN(off); PINL(ph);
      mbar_wait(bar0 + 8 * B_H);
      POLL { v0 = ldx16(ph); v1 = ldx16(ph + 32); RETRY(lop_x3(v0.x, v1.x, par)) }
      float d[4][4] = {};
#pragma unroll
      for (int mt = 0; mt < 4; mt++) {
        mma16(d[mt], a[0][mt], v0.x, v0.y); mma16(d[mt], a[1][mt], v0.z, v0.w);
        mma16(d[mt], a[2][mt], v1.x, v1.y); mma16(d[mt], a[3][mt], v1.z, v1.w);
      }
      float r[8];
#pragma unroll
      for (int mt = 0; mt < 4; mt++) { r[2 * mt] = d[mt][0] + d[mt][1]; r[2 * mt + 1] = d[mt][2] + d[mt][3]; }
      tred<4>(r, lane, 2); tred<2>(r, lane, 1);
      const float rc = __shfl_xor_sync(~0u, (lane & 4) ? r[0] : r[1], 4);
      const uint32_t wd = (lane & 4) ? pack2(rc, r[1]) : pack2(r[0], rc);
      const uint32_t w1 = __shfl_down_sync(~0u, wd, 8), w2 = __shfl_down_sync(~0u, wd, 16), w3 = __shfl_down_sync(~0u, wd, 24);
      asm volatile("{.reg .pred p; setp.lt.s32 p, %7, 8; @p st.shared.v4.b32 [%0], {%2,%3,%4,%5};\n"
                   "@p st.async.shared::cluster.mbarrier::complete_tx::bytes.v4.b32 [%1], {%2,%3,%4,%5}, [%6];}"
                   ::"r"(sb + off), "r"(rsb + off), "r"(wd), "r"(w1), "r"(w2), "r"(w3), "r"(rsb + O_BAR + 8 * B_Q2), "r"(lane) : "memory");
      __syncwarp();
      arrive_n(bar0 + 8 * B_Q2, lane == 0, 1);
    }
    {
      uint32_t a[2][8][4];
      uint32_t a_bq = sb + O_B + (lane & 7) * 272 + (lane >> 3) * 16;
      uint4* p_qa = scr->qa + (4 * rk + (warp >> 1)) * 256 + hd * 8 + ((4 * (warp & 1) + tq) ^ (hd & 7));
      PIN(a_bq); PINL(p_qa);
      mbar_wait(bar0 + 8 * (4 + (warp >> 1)));
      const uint32_t ab = sb + 65536 + (warp >> 1) * 16384 + (32 * (warp & 1) + (lane & 15)) * 128;
#pragma unroll
      for (int i = 0; i < 16; i++) ldsm(a[i >> 3][i & 7], ab + (i >> 3) * 2048 + ((i >> 2) & 1) * 8192 + (((2 * (i & 3) + (lane >> 4)) ^ (lane & 7)) << 4));
      arrive_n(bar0 + 8 * (B_EMPTY + 4 + (warp >> 1)), lane == 0, 4 + (dep16(&a[0][0][0]) & sch.zero));
      mbar_wait(bar0 + 8 * B_Q2);
      float d[4][4] = {};
#pragma unroll
      for (int y = 0; y < 4; y++) {
        uint32_t bq[4];
        ldsm(bq, a_bq + 64 * y);
#pragma unroll
        for (int mt = 0; mt < 2; mt++) { mma16(d[2 * mt], a[mt][2 * y], bq[0], bq[1]); mma16(d[2 * mt + 1], a[mt][2 * y + 1], bq[2], bq[3]); }
      }
      float r[4];
#pragma unroll
      for (int i = 0; i < 4; i++) r[i] = (d[i & 2][2 * (i & 1)] + d[i & 2][2 * (i & 1) + 1]) + (d[(i & 2) + 1][2 * (i & 1)] + d[(i & 2) + 1][2 * (i & 1) + 1]);
      tred<2>(r, lane, 2); tred<1>(r, lane, 1);
      const float nb = __shfl_xor_sync(~0u, r[0], 4);
      const uint32_t w0 = (lane >> 3) == (hd & 3) ? pack2t(r[0], nb, par) : pack2(r[0], nb);
      const uint32_t w1 = __shfl_down_sync(~0u, w0, 8), w2 = __shfl_down_sync(~0u, w0, 16), w3 = __shfl_down_sync(~0u, w0, 24);
      if (lane < 4) stx16(p_qa, make_uint4(w0, w1, w2, w3));
      if (warp) nbar_arrive(3, 256); else { nbar(3, 256); CNT_ADD(32 + 32 * rk); }
    }
  } else {
    nbar(1, 288);
    epoch = *(volatile unsigned*)(smem + O_EP);
    par = (epoch + 1) & 1;
    asm volatile("barrier.cluster.wait.acquire.aligned;" ::: "memory");
    mbar_wait(bar0);
  }
  asm volatile("setmaxnreg.inc.sync.aligned.u32 224;");
  uint2* p_rec = scr->rec + ((16 * (warp >> 2) + 2 * (warp & 3) + (g & 1) + 4 * (tq & 2)) * 32 + 4 * rn + (tq & 1)) * 64 + cl * 4 + (g >> 1);
  PINL(p_rec);
  {
    const unsigned inv = par ^ 1;
#pragma unroll
    for (int q = 0; q < 2; q++) { stx8(p_rec + q * 128, make_uint2(inv, 0)); if (cl == 14) stx8(p_rec + q * 128 + 4, make_uint2(0, 0)); }
    if (isA) { if (warp < 2) { stx4(scr->xao + b * 64 + tid, inv); stx4(scr->xab + cl * 256 + (2 * (rn & 3) + warp) * 32 + (rn >> 2) * 16 + (lane >> 1), inv); } }
    else if (f == 0) { stx4(out + 2 * tid, 0); __threadfence(); }
  }
  sb = __shfl_sync(~0u, sb, 0); bar0 = sb + O_BAR;
  const int nt = sch.nt[cls], wg = warp >> 2;
  uint32_t a_z[4];
#pragma unroll
  for (int u = 0; u < 4; u++) {
    const int s3 = (rn - u - (lane >> 1 & 1)) & 3;
    a_z[u] = sb + O_LZ + (s3 + 4 * (lane & 1)) * 4096 + wg * 512 + g * 64 + (((warp & 3) ^ (s3 & 1) ^ (2 * (lane & 1))) << 4);
    PIN(a_z[u]);
  }
  uint32_t z[4][4], a_w = sb + O_HW + warp * 128 + (g & 1) * 64 + (tq & 1) * 8;
  PIN(a_w);
  {
    const float sc = 0.08838834764831845f * 1.4426950408889634f;
    float mrun = -1e30f;
    float o[4][16], sx[16], mref[8];
#pragma unroll
    for (int k = 0; k < 16; k++) { o[0][k] = o[1][k] = o[2][k] = o[3][k] = sx[k] = 0.f; mref[k >> 1] = -1e30f; }
    const int key = 16 * warp + (lane & 15);
    uint32_t a_p = sb + O_P + key * 64 + (((lane >> 4) ^ ((key >> 1) & 3)) << 4);
    uint32_t a_v = sb + wg * 32768 + (8 * (lane >> 4) + (lane & 7)) * 128 + (((2 * (warp & 3) + ((lane >> 3) & 1)) ^ (lane & 7)) << 4);
    const int rot = rn + warp;
    unsigned long long dst[4];
#pragma unroll
    for (int q = 0; q < 4; q++) {
      dst[q] = mapg(sb + O_LZ + rn * 4096 + (warp & 3) * 1024 + g * 64 + ((tq ^ (rn & 1) ^ ((rn >> 1) & 2)) << 4), 4 * wg + ((q + rot) & 3));
      PINL(dst[q]);
    }
    unsigned long long a_h = mapg(sb + O_HZ + wg * 1024 + rn * 128 + lane * 4, 2 * (warp & 3));
    unsigned long long a_h1 = mapg(sb + O_HZ + wg * 1024 + rn * 128 + lane * 4, 2 * (warp & 3) + 1);
    PIN(a_p); PIN(a_v); PINL(a_h); PINL(a_h1);
    uint32_t rel = lane < 4 && lane >= 2 * wg ? 2 - (tq >> 1) : 0;
    PIN(rel);
    uint32_t ones[4] = {0x3F803F80u, 0x3F803F80u, 0x3F803F80u, 0x3F803F80u};
    PIN(ones[0]); PIN(ones[1]); PIN(ones[2]); PIN(ones[3]);
    {
      asm volatile("{.reg .pred p; .reg .u32 n; mov.u32 n, 0;\n"
                   "W%=: mbarrier.try_wait.parity.acquire.cluster.shared::cta.b64 p, [%0], 0; add.u32 n, n, 1; setp.lt.and.u32 p, n, 0x100000, !p; @p bra W%=;}"
                   ::"r"(bar0 + 8 * B_LZ) : "memory");
      mbar_wait(bar0 + 8 * B_QF);
      unsigned bad = 0;
#pragma unroll
      for (int k = 0; k < 8; k++) bad |= __float_as_uint(lds4(sb + O_Q + k * 4096 + tid * 16 + (lane >> 3) * 4)) ^ par;
      if (__builtin_expect(__any_sync(~0u, bad & 1), 0)) {
#pragma unroll 1
        for (int k = 0; k < 8; k++) {
          uint4 v;
          POLL { v = ldx16(scr->qa + k * 256 + tid); RETRY(((lane & 16) ? ((lane & 8) ? v.w : v.z) : ((lane & 8) ? v.y : v.x)) ^ par) }
          sts16(sb + O_Q + k * 4096 + tid * 16, v);
        }
        asm volatile("fence.proxy.async.shared::cta;" ::: "memory");
      }
      if (warp >= 4) nbar_arrive(1, 256); else nbar(1, 256);
    }
#pragma unroll 1
    for (int t = 0; t < nt; t++) {
      const int v = v0 + t;
      const uint32_t fb = bar0 + (v & 1) * 32, ph = (v >> 1) & 1, av = a_v + (v & 1) * 65536;
      uint32_t vf[4][4][4], cnt;
      auto landed = [&]() {
        cnt = rel + (dep16(&vf[0][0][0]) & (nt >> 8));
        PIN(cnt);
      };
      if (wg == 0) {
        const uint32_t da = DSC + (v & 1) * 4096, db = DSC + O_Q / 16;
#pragma unroll 1
        for (int j = 0; j < 4; j++) {
          mbar_wait(fb + 8 * j, ph);
          asm volatile("wgmma.fence.sync.aligned;" ::: "memory");
#pragma unroll
          for (int k = 0; k < 8; k++)
            wgmma32<0, 0, HI128, HI128>(sx, da + j * 1024 + (k >> 2) * 512 + (k & 3) * 2, db + j * 512 + (k >> 2) * 256 + (k & 3) * 2, k ? 1 : j);
          asm volatile("wgmma.commit_group.sync.aligned;" ::: "memory");
          if (j == VJ) {
#pragma unroll
            for (int i = 0; i < 16; i++) ldsm_t(vf[i >> 2][i & 3], av + (((i >> 2) + rot) & 3) * 8192 + (i & 3) * 2048);
            nbar(5, 256);
            landed();
          }
        }
      } else {
        nbar_arrive(5, 256);
#pragma unroll 1
        for (int j = 0; j < 2; j++) {
          mbar_wait(fb + 16 + 8 * j, ph);
          if (j) spin_until(clock() + VDLY);
#pragma unroll
          for (int q = 0; q < 4; q++)
            if (((q + rot) & 2) == 2 * j)
#pragma unroll
              for (int k = 0; k < 4; k++) ldsm_t(vf[q][k], av + ((q + rot) & 3) * 8192 + k * 2048);
        }
        cnt = 0;
      }
      wg_wait<0>(sx);
      asm volatile("{.reg .pred p; setp.ne.s32 p, %1, 0; @p mbarrier.arrive.shared::cta.b64 _, [%0], %1;}" ::"r"(fb + 8 * B_EMPTY + 8 * tq), "r"(cnt) : "memory");
#pragma unroll 1
      for (int pass = 0;; pass++) {
        int ex = !(t | pass);
        if (wg == 0 && (t | pass)) {
          uint32_t pk[8];
#pragma unroll
          for (int i = 0; i < 8; i++) pk[i] = pack2(ex2(sx[2 * i] * sc - mref[i & 6]), ex2(sx[2 * i + 1] * sc - mref[(i & 6) + 1]));
          asm volatile("stmatrix.sync.aligned.m8n8.x4.shared.b16 [%0], {%2,%3,%4,%5};\n"
                       "stmatrix.sync.aligned.m8n8.x4.shared.b16 [%1], {%6,%7,%8,%9};"
                       ::"r"(a_p), "r"(a_p ^ 32), "r"(pk[0]), "r"(pk[1]), "r"(pk[2]), "r"(pk[3]), "r"(pk[4]), "r"(pk[5]), "r"(pk[6]), "r"(pk[7]) : "memory");
          const uint32_t mx = __vmaxu2(__vmaxu2(__vmaxu2(pk[0], pk[1]), __vmaxu2(pk[2], pk[3])), __vmaxu2(__vmaxu2(pk[4], pk[5]), __vmaxu2(pk[6], pk[7])));
          ex = max(mx, mx << 16) > (127u + TAU) << 23;
          asm volatile("fence.proxy.async.shared::cta;" ::: "memory");
        }
        asm volatile("{.reg .pred p, q; setp.ne.s32 q, %0, 0; bar.red.or.pred p, 4, 256, q; selp.s32 %0, 1, 0, p;}" : "+r"(ex)::"memory");
        if (!ex || pass) break;
        int ln;
        asm volatile("mov.u32 %0, %%laneid;" : "=r"(ln));
        const uint32_t a_pm = sb + O_SM + ln * 16;
        if (wg == 0) {
          float cm[8];
#pragma unroll
          for (int i = 0; i < 8; i++) cm[i] = fmaxf(sx[2 * (i & 6) + (i & 1)], sx[2 * (i & 6) + (i & 1) + 2]);
          tmax<4>(cm, lane, 16); tmax<2>(cm, lane, 8); tmax<1>(cm, lane, 4);
          sts4(a_pm + warp * 4, cm[0] * sc);
        }
        nbar(4, 256);
        const float4 pm = lds16(a_pm);
        const float mn = u2f(__float_as_uint(fmaxf(fmaxf(fmaxf(pm.x, pm.y), fmaxf(pm.z, pm.w)), mrun)) | 1u), al = ex2(mrun - mn);
        mrun = mn;
#pragma unroll
        for (int i = 0; i < 8; i++) {
          const float a = __shfl_sync(~0u, al, 4 * i + (ln & 3)), aw = wg ? a : 1.f;
          mref[i] = __shfl_sync(~0u, mn, 4 * i + (ln & 3));
#pragma unroll
          for (int e = 0; e < 2; e++) {
            const int k = 2 * (i & 6) + (i & 1) + 2 * e;
            o[0][k] *= a; o[1][k] *= a; o[2][k] *= a; o[3][k] *= a; sx[k] *= aw;
          }
        }
      }
      float hv = mrun;
      if (wg) {
        asm volatile("wgmma.fence.sync.aligned;" ::: "memory");
#pragma unroll
        for (int k = 0; k < 4; k++) wgmma32r(sx, ones, DSC + O_P / 16 + k * 64);
        asm volatile("wgmma.commit_group.sync.aligned;" ::: "memory");
        landed();
        asm volatile("{.reg .pred p; setp.ne.s32 p, %1, 0; @p mbarrier.arrive.shared::cta.b64 _, [%0], %1;}" ::"r"(fb + 8 * B_EMPTY + 8 * tq), "r"(cnt) : "memory");
        wg_wait<0>(sx);
        float lv[4];
#pragma unroll
        for (int j = 0; j < 4; j++) lv[j] = (lane & 4) ? sx[4 * j + 1] : sx[4 * j];
        hv = (lane & 16) ? ((lane & 8) ? lv[3] : lv[2]) : ((lane & 8) ? lv[1] : lv[0]);
      }
      asm volatile("{.reg .pred p; setp.eq.s32 p, %3, %4; @p st.relaxed.cluster.b32 [%0], %1; @p st.relaxed.cluster.b32 [%2], %1;}"
                   ::"l"(a_h), "r"(__float_as_uint(hv) | 1u), "l"(a_h1), "r"(t), "r"(nt - 1) : "memory");
#pragma unroll
      for (int q = 0; q < 4; q++) {
        asm volatile("wgmma.fence.sync.aligned;" ::: "memory");
#pragma unroll
        for (int k = 0; k < 4; k++) wgmma32r(o[q], vf[q][k], DSC + O_P / 16 + k * 64);
        asm volatile("wgmma.commit_group.sync.aligned;" ::: "memory");
        if (q == 3) {
#pragma unroll
          for (int u = 0; u < 4; u++) ldsm_t(z[u], a_z[u] + u * 1024);
        }
        wg_wait<0>(o[q]);
#pragma unroll
        for (int j = 0; j < 2; j++)
          asm volatile("{.reg .pred p; setp.eq.s32 p, %5, %6; @p st.relaxed.cluster.v4.b32 [%0], {%1,%2,%3,%4};}"
                       ::"l"(dst[q] + j * 512), "r"(pack2t(o[q][8 * j], o[q][8 * j + 1], 1)), "r"(pack2(o[q][8 * j + 2], o[q][8 * j + 3])),
                         "r"(pack2(o[q][8 * j + 4], o[q][8 * j + 5])), "r"(pack2(o[q][8 * j + 6], o[q][8 * j + 7])), "r"(t), "r"(nt - 1) : "memory");
      }
    }
  }
  {
    uint32_t wx[4][4];
    mbar_wait(bar0 + 8 * B_WZ);
#pragma unroll
    for (int u = 0; u < 4; u++) {
      uint2 wp;
      asm volatile("ld.shared.v2.u32 {%0, %1}, [%2];" : "=r"(wp.x), "=r"(wp.y) : "r"(a_w + u * 8) : "memory");
      const bool lo = (g >> 1) == (tq >> 1), hi = (g >> 1) == 2 + (tq >> 1);
      wx[u][0] = lo ? wp.x : 0u; wx[u][1] = lo ? wp.y : 0u; wx[u][2] = hi ? wp.x : 0u; wx[u][3] = hi ? wp.y : 0u;
    }
    auto bad = [&]() {
      const unsigned ok = and3(and3(and3(z[0][0], z[0][1], z[0][2]), and3(z[0][3], z[1][0], z[1][1]), and3(z[1][2], z[1][3], z[2][0])),
                               and3(and3(z[2][1], z[2][2], z[2][3]), and3(z[3][0], z[3][1], z[3][2]), z[3][3]), 0x10001u);
      return __any_sync(~0u, g == 0 && ok != 0x10001u);
    };
    POLL {
      if (it_)
#pragma unroll
        for (int u = 0; u < 4; u++) ldsm_t(z[u], a_z[u] + u * 1024);
      if (!bad() || ++it_ >= SPIN_MAX) break;
    }
    float d0[8][4] = {}, d[8][4], r[8];
#pragma unroll
    for (int i = 0; i < 8; i++) mma16(d0[i], wx[i >> 1], z[i >> 1][2 * (i & 1)], z[i >> 1][2 * (i & 1) + 1]);
    POLL {
#pragma unroll
      for (int u = 0; u < 4; u++) ldsm_t(z[u], a_z[u ^ 2] + u * 1024);
#pragma unroll
      for (int i = 0; i < 8; i++) mma16c(d[i], wx[(i >> 1) ^ 2], z[i >> 1][2 * (i & 1)], z[i >> 1][2 * (i & 1) + 1], d0[i]);
      if (!bad() || ++it_ >= SPIN_MAX) break;
    }
#pragma unroll
    for (int i = 0; i < 8; i++) r[i] = (tq & 2) ? ((g & 1) ? d[i][3] : d[i][2]) : ((g & 1) ? d[i][1] : d[i][0]);
#pragma unroll
    for (int q = 0; q < 2; q++) pub8(p_rec + q * 128, pack2t(r[4 * q], r[4 * q + 1], par) | 1u, pack2(r[4 * q + 2], r[4 * q + 3]));
  }
  const int vt = v0 + nt;
  const uint32_t bufa = sb + (vt & 1) * 65536, fulla = bar0 + (vt & 1) * 32, pha = (vt >> 1) & 1, phb = ((vt + 1) >> 1) & 1;
  const uint32_t bufo = sb + ((vt + 1) & 1) * 65536, fullb = bar0 + ((vt + 1) & 1) * 32;
  uint32_t a_rs = sb + O_R + (warp >> 2) * 1024 + (16 * tq + g) * 16 + ((warp + tq) & 3) * 4;
  if (isA) {
    const int row = 16 * (warp & 6) + 8 * (warp & 1) + (lane & 16) + ((lane & 7) >> 1) + 4 * (lane & 1);
    uint32_t ab = bufa + row * 128 + ((((lane >> 3) & 1) ^ (row & 7)) << 4);
    const uint2* pr = scr->rec + (hd * 32 + warp) * 64 + lane;
    unsigned long long a_c0 = mapg(sb + O_CTX + (64 * rn + 32 * (warp & 1) + posof(lane)) * 4, warp & 6);
    unsigned long long a_c1 = mapg(sb + O_CTX + (64 * rn + 32 * (warp & 1) + posof(lane)) * 4, warp | 1);
    uint32_t a_rl = sb + O_R + (32 * (warp & 1) + lane) * 16;
    uint32_t ao = bufo + (16 * warp + 8 * (lane >> 4) + (lane & 7)) * 128 + ((((lane >> 3) & 1) ^ (lane & 7)) << 4);
    uint32_t a_cx = sb + O_CTX + (16 * warp + 4 * tq) * 4, a_ga = sb + O_SM + (320 + posof(tid & 63)) * 4;
    unsigned* p_ao = scr->xao + b * 64 + (tid & 63);
    unsigned* p_ab = scr->xab + cl * 256 + (2 * (rn & 3) + (warp & 1)) * 32 + (rn >> 2) * 16 + (lane >> 1);
    float xv = cl == 0 ? __bfloat162float(x[64 * rn + (tid & 63)]) : 0.f;
    unsigned p2 = lane >= 28 ? 0 : par;
    PIN(ab); PINL(pr); PINL(a_c0); PINL(a_c1); PIN(a_rl); PIN(a_rs); PIN(ao); PIN(a_cx); PIN(a_ga); PINL(p_ao); PINL(p_ab); PIN(p2);
    asm volatile("" : "+f"(xv));
    uint32_t aw[4][4][4];
    auto wo = [&](const int j) {
      mbar_wait(fullb + 8 * j, phb);
#pragma unroll
      for (int mt = 0; mt < 4; mt++) ldsm_t(aw[j][mt], (ao + j * 16384) ^ (mt << 5));
    };
    {
      uint32_t a[4][4][4];
      uint2 z[4], y[4] = {};
      float d[4][4] = {}, r[8];
      mbar_wait(fulla, pha);
      POLL {
#pragma unroll
        for (int q = 0; q < 4; q++) z[q] = ldx8(pr + q * 512);
        RETRY(lop_x3(z[0].x, z[1].x, par) | lop_x3(z[2].x, z[3].x, par))
      }
#pragma unroll
      for (int q = 0; q < 4; q++) {
        if (q == 3) {
          mbar_wait(bar0 + 8 * B_G);
          if (lane < 28)
#pragma unroll
            for (int u = 0; u < 4; u++) y[u] = ldx8(pr + u * 512 + 32);
          __syncwarp();
        }
        mbar_wait(fulla + 8 * q, pha);
#pragma unroll
        for (int mt = 0; mt < 4; mt++) ldsm_t(a[q][mt], (ab + q * 16384) ^ (mt << 5));
#pragma unroll
        for (int mt = 0; mt < 4; mt++) mma16(d[mt], a[q][mt], z[q].x, z[q].y);
      }
      mbar_wait(bar0 + 8 * B_W);
      const float4 W = lds16(sb + O_SM + (384 + 4 * tq) * 4);
#pragma unroll
      for (int i = 0; i < 8; i++) { r[i] = W.x * d[i >> 1][2 * (i & 1)] + W.y * d[i >> 1][2 * (i & 1) + 1]; asm volatile("" : "+f"(r[i])); }
#pragma unroll
      for (int j = 0; j < NPE; j++) wo(j);
      POLL {
        if (it_)
#pragma unroll
          for (int u = 0; u < 4; u++) y[u] = ldx8(pr + u * 512 + 32);
#pragma unroll
        for (int mt = 0; mt < 4; mt++) d[mt][0] = d[mt][1] = d[mt][2] = d[mt][3] = 0.f;
#pragma unroll
        for (int q = 0; q < 4; q++)
#pragma unroll
          for (int mt = 0; mt < 4; mt++) mma16(d[mt], a[q][mt], y[q].x, y[q].y);
        RETRY(or3(lop_x3(y[0].x, y[1].x, p2), lop_x3(y[2].x, y[3].x, p2), 0))
      }
#pragma unroll
      for (int i = 0; i < 8; i++) r[i] = W.w * d[i >> 1][2 * (i & 1) + 1] + (W.z * d[i >> 1][2 * (i & 1)] + r[i]);
      tred<4>(r, lane, 2); tred<2>(r, lane, 1);
      sts4(a_rs, r[0]); sts4(a_rs + 128, r[1]);
      nbar(1, 256);
      const uint32_t cv = __float_as_uint(sum8(a_rl)) | 1u;
      asm volatile("st.relaxed.cluster.b32 [%0], %2; st.relaxed.cluster.b32 [%1], %2;" ::"l"(a_c0), "l"(a_c1), "r"(cv) : "memory");
    }
    {
#pragma unroll
      for (int j = NPE; j < NPO; j++) wo(j);
      uint4 c[4];
      POLL {
#pragma unroll
        for (int j = 0; j < 4; j++) c[j] = ldsv16(a_cx + j * 512);
        RETRY(~and3(and3(and3(c[0].x, c[0].y, c[0].z), and3(c[1].x, c[1].y, c[1].z), and3(c[0].w, c[1].w, c[2].x)),
                    and3(and3(c[2].y, c[2].z, c[2].w), and3(c[3].x, c[3].y, c[3].z), c[3].w), ~0u))
      }
      float d[4][4] = {};
#pragma unroll
      for (int j = 0; j < 4; j++) {
        if (j + 1 >= NPO && j < 3) wo(j + 1);
        const uint32_t b0 = pack2(u2f(c[j].x), u2f(c[j].y)), b1 = pack2(u2f(c[j].z), u2f(c[j].w));
#pragma unroll
        for (int mt = 0; mt < 4; mt++) mma16(d[mt], aw[j][mt], b0, b1);
      }
      const float r0 = (tq & 2) ? ((tq & 1) ? d[3][0] : d[2][0]) : ((tq & 1) ? d[1][0] : d[0][0]);
      const float r1 = (tq & 2) ? ((tq & 1) ? d[3][2] : d[2][2]) : ((tq & 1) ? d[1][2] : d[0][2]);
      sts4(a_rs + 2048, r0); sts4(a_rs + 2048 + 128, r1);
      if (warp >= 2) nbar_arrive(2, 256);
      else {
        mbar_wait(bar0 + 8 * B_TAB);
        const float gav = lds4(a_ga);
        nbar(2, 256);
        const float t = gav * sum8(a_rl + 2048) + xv;
        asm volatile("{.reg .pred p; setp.eq.s32 p, %2, 0; @p red.relaxed.gpu.global.xor.b32 [%0], %1;}"
                     ::"l"(p_ab), "r"(pack2t(t, __shfl_down_sync(~0u, t, 1), par) | 1u), "r"(lane & 1) : "memory");
        pub4(p_ao, __float_as_uint(t) | 1u);
      }
    }
  } else {
    uint32_t af[4][4][4];
    uint32_t ab = bufa + (32 * warp + 8 * (lane >> 4) + (lane & 7)) * 64 + ((((lane >> 3) & 1) ^ ((lane >> 1) & 3)) << 4);
    uint32_t a_d = bufo + (8 * (lane >> 4) + (lane & 7)) * 128 + (((2 * (warp & 3) + ((lane >> 3) & 1)) ^ (lane & 7)) << 4);
    uint32_t a_rl = sb + O_R + lane * 16, a_st = sb + O_SM + (352 + 8 * (lane >> 4) + warp) * 4;
    const unsigned* pa = scr->xab + tid;
    unsigned long long a_h = mapg(sb + O_CTX + rn * 64 + (lane & 6) * 8 + (lane >> 3) * 4, 2 * (warp & 3) + (lane & 1));
    const int col = 64 * rn + 16 * (warp & 3) + 8 * (tq & 1) + g;
    uint32_t a_hl = sb + O_CTX + tq * 16;
    const unsigned* px = scr->xao + (tq & 2) * 1024 + col;
    bf16* po = out + col;
    PIN(ab); PIN(a_d); PIN(a_rl); PINL(pa); PIN(a_rs); PIN(a_st); PINL(po); PINL(a_h); PIN(a_hl); PINL(px);
    mbar_wait(bar0 + 8 * B_TAB);
    uint2 cf;
    uint2 bb[4];
    unsigned gbw;
    POLL {
      unsigned bad = 0;
      cf = ldx8(scr->xm + 1024 + (lane & 16) * 16 + 32 * warp + posof(2 * (lane & 15)));
#pragma unroll
      for (int s = 0; s < 4; s++) {
        const uint4 w = ldx16(scr->xm + 1024 - (g & 1) * 512 + 256 * (s >> 1) + 32 * warp + 16 * (s & 1) + 4 * tq);
        bb[s] = make_uint2(__byte_perm(w.x, w.y, 0x7632), __byte_perm(w.z, w.w, 0x7632));
        bad = or3(bad, lop_x3(w.x, w.y, par), lop_x3(w.z, w.w, par));
      }
      gbw = ldx4(scr->xm + 1536 + posof(col));
      RETRY(or3(bad, lop_x3(cf.x, cf.y, par), gbw ^ par))
    }
    const float gbv = bfhi(gbw);
    float e[4][4] = {};
    unsigned v[8];
    auto item = [&](const int it) {
      mbar_wait(fulla + 8 * it, pha);
#pragma unroll
      for (int i = 0; i < 4; i++) ldsm_t(af[it][i], (ab + it * 16384 + (i >> 1) * 1024) ^ ((i & 1) << 5));
    };
    auto item_mma = [&](const int it) {
#pragma unroll
      for (int i = 0; i < 4; i++) mma16(e[2 * (it & 1) + (i & 1)], af[it][i], bb[(it & 2) + (i >> 1)].x, bb[(it & 2) + (i >> 1)].y);
    };
    unsigned t3 = sch.wt;
    PIN(t3);
    item(0); item_mma(0); item(1); item_mma(1);
    mbar_wait(bar0 + 8 * B_G);
#pragma unroll
    for (int i = 0; i < 8; i++) v[i] = ldx4(pa + i * 256);
    t3 += clock();
    uint32_t have2, have3 = 0;
    do have2 = mbar_test(fulla + 16, pha); while (!have2 && (int)((unsigned)clock() - t3) < 0);
    if (have2) {
      item(2); item_mma(2);
      do have3 = mbar_test(fulla + 24, pha); while (!have3 && (int)((unsigned)clock() - t3) < 0);
      if (have3) { item(3); item_mma(3); }
    }
    float y0, y1, df[4][4], st[2];
    uint32_t bz[4][2] = {};
    auto mm = [&](const int it, const int i) { mma16(df[2 * (it & 1) + (i & 1)], af[it][i], bz[(it & 2) + (i >> 1)][0], bz[(it & 2) + (i >> 1)][1]); };
    POLL {
      if (it_)
#pragma unroll
        for (int i = 0; i < 8; i++) v[i] = ldx4(pa + i * 256);
      y0 = ((bflo(v[0]) + bflo(v[1])) + (bflo(v[2]) + bflo(v[3]))) + ((bflo(v[4]) + bflo(v[5])) + (bflo(v[6]) + bflo(v[7])));
      y1 = ((bfhi(v[0]) + bfhi(v[1])) + (bfhi(v[2]) + bfhi(v[3]))) + ((bfhi(v[4]) + bfhi(v[5])) + (bfhi(v[6]) + bfhi(v[7])));
      const uint32_t zb = pack2(y0 * u2f(cf.x), y1 * u2f(cf.y));
#pragma unroll
      for (int s = 0; s < 4; s++) {
        const uint32_t w = __shfl_sync(~0u, zb, 8 * s + (lane & 7));
        bz[s][0] = (lane & 4) ? 0u : w; bz[s][1] = (lane & 4) ? w : 0u;
      }
      st[0] = y0 + y1; st[1] = y0 * y0 + y1 * y1;
      tred<1>(st, lane, 16);
#pragma unroll
      for (int i = 0; i < 4; i++) df[i][0] = df[i][1] = df[i][2] = df[i][3] = 0.f;
      mm(0, 0); mm(0, 1); mm(1, 0); mm(1, 1);
      st[0] += shx(st[0], 8);
      mm(0, 2); mm(0, 3); mm(1, 2); mm(1, 3);
      RETRY(or3(or3(lop_x3(v[0], v[1], par), lop_x3(v[2], v[3], par), lop_x3(v[4], v[5], par)), lop_x3(v[6], v[7], par), 0))
    }
    unsigned xq[4];
    if (wg == 0)
#pragma unroll
      for (int i = 0; i < 4; i++) xq[i] = ldx4(px + i * 512);
    if (have2) { mm(2, 0); mm(2, 1); mm(2, 2); mm(2, 3); }
    st[0] += shx(st[0], 4);
    st[0] += shx(st[0], 2);
    st[0] += shx(st[0], 1);
    sts4(a_st, st[0]);
    __syncwarp();
    arrive_n(bar0 + 8 * B_ST, lane == 0, 1);
    if (!have2) { item(2); item_mma(2); mm(2, 0); mm(2, 1); mm(2, 2); mm(2, 3); }
    if (!have3) { item(3); item_mma(3); }
    mm(3, 0); mm(3, 1); mm(3, 2); mm(3, 3);
    mbar_wait(bar0 + 8 * B_ST);
    float mean, rstd;
    {
      float4 u[4];
#pragma unroll
      for (int i = 0; i < 4; i++) u[i] = lds16(sb + O_SM + (352 + 4 * i) * 4);
      mean = (((u[0].x + u[0].y) + (u[0].z + u[0].w)) + ((u[1].x + u[1].y) + (u[1].z + u[1].w))) * (1.f / 512.f);
      const float sq = (((u[2].x + u[2].y) + (u[2].z + u[2].w)) + ((u[3].x + u[3].y) + (u[3].z + u[3].w))) * (1.f / 512.f);
      asm("rsqrt.approx.ftz.f32 %0, %1;" : "=f"(rstd) : "f"(fmaxf(sq - mean * mean, 0.f) + 1e-5f));
    }
    float A[4], r[4];
#pragma unroll
    for (int i = 0; i < 4; i++) {
      A[i] = (tq & 2) ? ((tq & 1) ? e[3][i] : e[2][i]) : ((tq & 1) ? e[1][i] : e[0][i]);
      r[i] = (tq & 2) ? ((tq & 1) ? df[3][i] : df[2][i]) : ((tq & 1) ? df[1][i] : df[0][i]);
    }
    sts4(a_rs, rstd * (r[0] + r[1]) + (A[1] - rstd * mean * A[0])); sts4(a_rs + 128, rstd * (r[2] + r[3]) + (A[3] - rstd * mean * A[2]));
    nbar(1, 256);
    if (wg) {
      const float4 g0 = lds16(a_rl), g1 = lds16(a_rl + 1024), u0 = lds16(a_rl + 512), u1 = lds16(a_rl + 1536);
      const float gg = bfr(((g0.x + g0.y) + (g0.z + g0.w)) + ((g1.x + g1.y) + (g1.z + g1.w)));
      const float uu = bfr(((u0.x + u0.y) + (u0.z + u0.w)) + ((u1.x + u1.y) + (u1.z + u1.w)));
      const float hh = bfr(gg * rcp(1.f + ex2(gg * (-2.302208198f - 0.1029432397f * gg * gg)))) * uu, hn = __shfl_xor_sync(~0u, hh, 1);
      asm volatile("st.relaxed.cluster.b32 [%0], %1;" ::"l"(a_h), "r"(pack2t((lane & 1) ? hn : hh, (lane & 1) ? hh : hn, 1)) : "memory");
    } else {
      uint32_t ad[16][4];
      spin_until(clock() + FDLY);
#pragma unroll
      for (int j = 0; j < 2; j++) {
        mbar_wait(fullb + 8 * j, phb);
#pragma unroll
        for (int i = 0; i < 8; i++) ldsm_t(ad[8 * j + i], a_d + (8 * j + i) * 2048);
      }
      POLL {
        if (it_)
#pragma unroll
          for (int i = 0; i < 4; i++) xq[i] = ldx4(px + i * 512);
        RETRY(lop_x3(xq[0], xq[1], par) | lop_x3(xq[2], xq[3], par))
      }
      float x7 = (u2f(xq[0]) + u2f(xq[1])) + (u2f(xq[2]) + u2f(xq[3]));
      x7 = (x7 + __shfl_xor_sync(~0u, x7, 2)) * (1.f / 7.f);
      uint4 hb[8];
      POLL {
        unsigned ok[8];
#pragma unroll
        for (int i = 0; i < 8; i++) { hb[i] = ldsv16(a_hl + i * 64); ok[i] = and3(hb[i].x, hb[i].y, hb[i].z); }
        RETRY(~and3(and3(and3(ok[0], ok[1], ok[2]), and3(ok[3], ok[4], ok[5]), and3(ok[6], ok[7], hb[0].w)),
                    and3(and3(hb[1].w, hb[2].w, hb[3].w), and3(hb[4].w, hb[5].w, hb[6].w), hb[7].w), 1))
      }
      float dd[4][4] = {};
#pragma unroll
      for (int i = 0; i < 8; i++) { mma16(dd[(2 * i) & 3], ad[2 * i], hb[i].x, hb[i].y); mma16(dd[(2 * i + 1) & 3], ad[2 * i + 1], hb[i].z, hb[i].w); }
      const float t = gbv * ((tq & 1) ? (dd[0][2] + dd[1][2]) + (dd[2][2] + dd[3][2]) : (dd[0][0] + dd[1][0]) + (dd[2][0] + dd[3][0])) + x7;
      asm volatile("{.reg .pred p; setp.eq.s32 p, %2, 0; @p red.relaxed.gpu.global.add.noftz.bf16x2 [%0], %1;}"
                   ::"l"(po), "r"(pack2(t, __shfl_down_sync(~0u, t, 4))), "r"(lane & 6) : "memory");
      if (f == 0 && tid == 0) stx4(&scr->cnt[0], epoch + 1);
    }
  }
}

static void make_sched(Sched& s) {
  const char* order = "FFAAbcFmmvog...d";
  const double dt = 5010 * 1e-3, dth = 4850 * 1e-3, dtt = 5200 * 1e-3;
  const int nbig = NBIG;
  s.zero = 0; s.dth = (unsigned)(dth * 256 + 0.5);
  double t = 512 * dth + 80;
  int tile = 0, jm = 0;
  for (int i = 0; i < 3; i++) s.nr[i] = s.nt[i] = 0;
  auto add = [&](int c, int type, double step, int win, int b0, int tl) {
    s.r[c][s.nr[c]++] = make_uint2((unsigned)(t + 0.5) | (unsigned)(step + 0.5) << 16, type | win << 4 | (b0 + 64) << 8 | tl << 16);
    if (type == T_KV) s.nt[c]++;
  };
  const int w1 = 6, w2 = 4, wt = 6;
  for (const char* p = order; *p; p++) {
    const char c = *p;
    if (c == 'v' || c == 'o' || c == 'm') {
      const int ty = c == 'v' ? T_UV : c == 'o' ? T_WO : T_MOD;
      const double d = c == 'm' ? dt : dtt;
      add(0, ty, 64 * d, wt, 0, c == 'm' ? jm : 0); add(1, ty, 64 * d, wt, 0, c == 'm' ? jm : 0);
      t += (c == 'm' ? 64 : 256) * d; jm += c == 'm';
    } else if (c == 'g' || c == 'd') {
      const int cs = c == 'g' ? 40 : 0;
      t += 3 * cs;
      add(2, c == 'g' ? T_GU : T_DN, 56 * dtt - cs, wt, 64, 0);
      t -= 3 * cs;
      t += (c == 'g' ? 224 : 112) * dtt;
    } else if (c == '.') t += 100;
    else if (c == '-') t -= 100;
    else {
      const int na = c == 'F' ? 0 : c == 'C' || c == 'c' || c == 'a' ? nbig : 64, nf = c == 'A' || c == 'a' ? 0 : 56, n = na + nf;
      const int w = na && nf ? w2 : w1;
      const bool ff = c == 'b' || c == 'c';
      const int cf = c == 'c' ? 40 : 0, ca = cf * 7 / 5;
      t += 3 * ca;
      if (na) add(0, T_KV, n * dt - ca, w, ff ? -56 : 0, tile);
      t -= 3 * ca;
      if (na == 64) add(1, T_KV, n * dt, w, ff ? -56 : 0, tile);
      if (nf) add(2, T_KV, n * dt - cf, w, ff ? 64 : 64 - na, tile);
      tile += n; t += 4 * n * dt;
      s.t4 = (unsigned)t + 600;
    }
  }
  s.dt = (unsigned)(dt * 256 + 0.5); s.d4 = 1550 | 1200 << 16; s.d6 = 3310; s.wt = 250;
}

static void launch(void* const* d_in, void* d_out) {
  static TMaps tms;
  static Sched sch;
  static bool init = false;
  static void* scr = nullptr;
  if (!init) {
    void* fn = nullptr; cudaDriverEntryPointQueryResult qr;
    cudaGetDriverEntryPoint("cuTensorMapEncodeTiled", &fn, cudaEnableDefault, &qr);
    EncFn f = (EncFn)fn;
    const CUtensorMapSwizzle S64 = CU_TENSOR_MAP_SWIZZLE_64B, S128 = CU_TENSOR_MAP_SWIZZLE_128B;
    const CUtensorMapL2promotion P256 = CU_TENSOR_MAP_L2_PROMOTION_L2_256B;
    enc3d(f, &tms.m[0], d_in[2], 64, 512, 64, 8192, 128, 64, 128, 1, S128, CU_TENSOR_MAP_L2_PROMOTION_L2_128B);
    enc3d(f, &tms.m[1], d_in[3], 64, 512, 64, 8192, 128, 64, 64, 2, S128, P256);
    enc3d(f, &tms.m[2], d_in[1], 64, SK, 8, 1024, 128, 64, 64, 2, S128, P256);
    enc3d(f, &tms.m[3], d_in[11], 3072, 256, 2, 6144, 256 * 6144, 32, 256, 1, S64, CU_TENSOR_MAP_L2_PROMOTION_L2_128B);
    enc3d(f, &tms.m[4], d_in[4], 64, 512, 64, 8192, 128, 64, 128, 1, S128, CU_TENSOR_MAP_L2_PROMOTION_L2_128B);
    enc3d(f, &tms.m[5], d_in[5], 512, 128, 32, 1024, 128 * 1024, 64, 128, 1, S128, CU_TENSOR_MAP_L2_PROMOTION_L2_128B);
    enc3d(f, &tms.m[6], d_in[7], 1792, 256, 2, 3584, 256 * 3584, 32, 256, 1, S64, CU_TENSOR_MAP_L2_PROMOTION_L2_128B);
    enc3d(f, &tms.m[7], d_in[8], 1792, 256, 2, 3584, 256 * 3584, 32, 256, 1, S64, CU_TENSOR_MAP_L2_PROMOTION_L2_128B);
    enc3d(f, &tms.m[8], d_in[9], 512, 128, 14, 1024, 128 * 1024, 64, 128, 1, S128, CU_TENSOR_MAP_L2_PROMOTION_L2_128B);
    cudaFuncSetAttribute(fused_kernel, cudaFuncAttributeMaxDynamicSharedMemorySize, SMEM9);
    cudaGetSymbolAddress(&scr, g_scr);
    make_sched(sch);
    init = true;
  }
  fused_kernel<<<NCTA9, 384, SMEM9>>>((const bf16*)d_in[0], (const bf16*)d_in[10], (const bf16*)d_in[11], (bf16*)d_out, (Scratch*)scr, sch, tms);
}

static bool fits() {
  cudaFuncSetAttribute(fused_kernel, cudaFuncAttributeMaxDynamicSharedMemorySize, SMEM9);
  cudaLaunchConfig_t cfg = {};
  cfg.gridDim = dim3(NCTA9); cfg.blockDim = dim3(384); cfg.dynamicSmemBytes = SMEM9;
  cudaLaunchAttribute at[1];
  at[0].id = cudaLaunchAttributeClusterDimension; at[0].val.clusterDim.x = 8; at[0].val.clusterDim.y = 1; at[0].val.clusterDim.z = 1;
  cfg.attrs = at; cfg.numAttrs = 1;
  int n = 0;
  if (cudaOccupancyMaxActiveClusters(&n, fused_kernel, &cfg) != cudaSuccess) { (void)cudaGetLastError(); return false; }
  return n >= NCTA9 / 8;
}
}
#undef BAR_ARM
#undef BAR_ARRIVE
#undef BAR_INIT
#undef B_EM
#undef B_EMPTY
#undef B_FM
#undef B_FULL
#undef B_G
#undef B_G2
#undef B_H
#undef B_HZ
#undef B_LZ
#undef B_Q2
#undef B_QF
#undef B_ST
#undef B_TAB
#undef B_W
#undef B_WZ
#undef CNT_ADD
#undef DSC
#undef FDLY
#undef HI128
#undef HI64
#undef LANE0
#undef NBIG
#undef NCTA9
#undef NPE
#undef NPO
#undef NSL
#undef O_B
#undef O_BAR
#undef O_CTX
#undef O_DBG
#undef O_EP
#undef O_HW
#undef O_HZ
#undef O_LZ
#undef O_P
#undef O_Q
#undef O_R
#undef O_SILU
#undef O_SM
#undef O_X
#undef PIN
#undef PINL
#undef POLL
#undef QN
#undef RETRY
#undef SK
#undef SMEM9
#undef SMEM_BASE
#undef SPIN_MAX
#undef TAU
#undef VDLY
#undef VJ
#undef X16
#undef fbits

namespace v8 {
typedef __nv_bfloat16 bf16;
#define NCTA 128
#define SK 32768
#define SLOT 32768
#define NSLOT 6
#define OFF_WQ (2 * SLOT)
#define OFF_WUK (4 * SLOT)
#define OFF_Q 196608
#define OFF_P (OFF_Q + 16384)
#define OFF_B (OFF_P + 4096)
#define OFF_R4 (OFF_B + 2304)
#define OFF_SILU (OFF_R4 + 4096)
#define OFF_RA (OFF_SILU + 1024)
#define OFF_SM (OFF_RA + 1024)
#define OFF_BP (OFF_SM + 1792)
#define OFF_CO (OFF_BP + 1024)
#define OFF_BAR (OFF_CO + 1280)
#define OFF_MASK (OFF_BAR + 512)
#define OFF_DBG (OFF_MASK + 16)
#define SMEM_BYTES (OFF_DBG + 128)
#define OFF_MOD OFF_Q
#define OFF_UV (4 * SLOT)
#define OFF_O (5 * SLOT)
#define OFF_G 0
#define OFF_U 16384
#define OFF_D SLOT
#define OFF_XO (OFF_D + 16384)
#define FB_UK 4
#define FB_KV 6
#define FB_MOD 22
#define FB_UV 23
#define FB_O 25
#define FB_G 27
#define FB_D 29
#define EB 30
#define QB 50
#define XB 51
#define SPIN_MAX (1 << 20)
#define BACKOFF 40
#define RATE_NS 652
#define RATE_T0 200
#define RATE_TL 300
#define WINS 0x3222333
#define KVWIN 4
#define RATE_H 650
#define RATE_E 650
#define SMUL 9
#define NPRE0 1
#define NPRE1 3
#define HWIN 4
#define EWIN 3
#define WTEST 450
#define DLY5 650
#define DLY6 600
#define DLY7 600
#define P12(a, b, c, d, e, f, g, h, i, j, k, l) ((unsigned long long)(a) | (b) << 5 | (c) << 10 | (d) << 15 | (e) << 20 | (f) << 25 | \
  (unsigned long long)(g) << 30 | (unsigned long long)(h) << 35 | (unsigned long long)(i) << 40 | (unsigned long long)(j) << 45 | \
  (unsigned long long)(k) << 50 | (unsigned long long)(l) << 55)
#define ORDER0 P12(0, 1, 2, 3, 4, 5, 16, 6, 7, 8, 9, 10)
#define ORDER1 P12(11, 12, 13, 14, 15, 17, 18, 19, 20, 23, 21, 22)
#define TAIL_K 17
#define RS 16
template <int N> struct IC { static constexpr int value = N; };
struct TMaps { CUtensorMap m[9]; };

struct __align__(128) Scratch {
  uint4 xo[128 * 64 * RS];
  uint2 ml[32 * 64];
  unsigned h[8 * 256];
  unsigned qa[32 * 256];
  unsigned xc[128 * 64];
  unsigned xao[8 * 512];
  unsigned xf[112 * 512];
  unsigned xm[2048];
  unsigned cnt[5 * 32];
};
__device__ Scratch g_scr;
#define g_xo scr->xo
#define g_ml scr->ml
#define g_h scr->h
#define g_qa scr->qa
#define g_xc scr->xc
#define g_xao scr->xao
#define g_xf scr->xf
#define g_xm scr->xm
#define g_epoch scr->cnt[0]

__device__ __forceinline__ uint32_t s2u(const void* p) { return (uint32_t)__cvta_generic_to_shared(p); }
__device__ __forceinline__ float bflo(uint32_t u) { return __uint_as_float(u << 16); }
__device__ __forceinline__ float bfhi(uint32_t u) { return __uint_as_float(u & 0xffff0000u); }
__device__ __forceinline__ float u2f(uint32_t u) { return __uint_as_float(u); }
__device__ __forceinline__ void fma8(float* acc, uint4 v, float s) {
  acc[0] += s * bflo(v.x); acc[1] += s * bfhi(v.x); acc[2] += s * bflo(v.y); acc[3] += s * bfhi(v.y);
  acc[4] += s * bflo(v.z); acc[5] += s * bfhi(v.z); acc[6] += s * bflo(v.w); acc[7] += s * bfhi(v.w);
}
__device__ __forceinline__ uint32_t pack2(float a, float b) {
  __nv_bfloat162 p = __floats2bfloat162_rn(a, b); return *(uint32_t*)&p;
}
__device__ __forceinline__ float bfr(float v) { return bfhi(pack2(v, v)); }
__device__ __forceinline__ float silu_bf(float c) { return bfr(__fdividef(c, 1.f + __expf(-c))); }
#define fbits(v) ((__float_as_uint(v) & ~1u) | par)
__device__ __forceinline__ uint32_t pack2t(float a, float b, unsigned par) {
  const uint32_t ua = ((__float_as_uint(a) + ((par ^ 1) << 16)) & 0xFFFE0000u) | (par << 16);
  return __byte_perm(ua, pack2(b, b), 0x7632);
}
__device__ __forceinline__ void nbar(int id, int n) { asm volatile("bar.sync %0, %1;" ::"r"(id), "r"(n) : "memory"); }
__device__ __forceinline__ void nbar_arrive(int id, int n) { asm volatile("bar.arrive %0, %1;" ::"r"(id), "r"(n) : "memory"); }
__device__ __forceinline__ uint4 ldc16(const void* p) {
  uint4 v; asm volatile("ld.relaxed.cta.global.v4.u32 {%0,%1,%2,%3}, [%4];" : "=r"(v.x), "=r"(v.y), "=r"(v.z), "=r"(v.w) : "l"(p) : "memory"); return v;
}
__device__ __forceinline__ unsigned ldc4(const void* p) {
  unsigned v; asm volatile("ld.relaxed.cta.global.u32 %0, [%1];" : "=r"(v) : "l"(p) : "memory"); return v;
}
__device__ __forceinline__ uint4 ldx16(const void* p) {
  uint4 v; asm volatile("ld.relaxed.gpu.global.v4.u32 {%0,%1,%2,%3}, [%4];" : "=r"(v.x), "=r"(v.y), "=r"(v.z), "=r"(v.w) : "l"(p) : "memory"); return v;
}
__device__ __forceinline__ unsigned ldx4(const void* p) {
  unsigned v; asm volatile("ld.relaxed.gpu.global.u32 %0, [%1];" : "=r"(v) : "l"(p) : "memory"); return v;
}
__device__ __forceinline__ unsigned long long ldx64(const void* p) {
  unsigned long long v; asm volatile("ld.relaxed.gpu.global.u64 %0, [%1];" : "=l"(v) : "l"(p) : "memory"); return v;
}
__device__ __forceinline__ void stx16(void* p, uint4 v) {
  asm volatile("st.relaxed.gpu.global.v4.u32 [%0], {%1,%2,%3,%4};" ::"l"(p), "r"(v.x), "r"(v.y), "r"(v.z), "r"(v.w) : "memory");
}
__device__ __forceinline__ void stx8(void* p, uint2 v) { asm volatile("st.relaxed.gpu.global.v2.u32 [%0], {%1,%2};" ::"l"(p), "r"(v.x), "r"(v.y) : "memory"); }
__device__ __forceinline__ void stx4(void* p, unsigned v) { asm volatile("st.relaxed.gpu.global.u32 [%0], %1;" ::"l"(p), "r"(v) : "memory"); }
__device__ __forceinline__ unsigned lop_x3(unsigned a, unsigned b, unsigned c) {
  unsigned d; asm("lop3.b32 %0, %1, %2, %3, 0x7E;" : "=r"(d) : "r"(a), "r"(b), "r"(c)); return d; }
#define X16(v) (lop_x3(v.x, v.y, par) | lop_x3(v.z, v.w, par))
#define X8(v) lop_x3(v.x, v.y, par)
#define RETRY(bad) if (!__any_sync(~0u, (bad) & 1) || ++it_ >= SPIN_MAX) break; __nanosleep(BACKOFF);
#define POLL _Pragma("unroll 1") for (int it_ = 0;;)
__device__ __forceinline__ void mbar_wait(uint32_t bar) {
  uint32_t ok; int it = 0;
  do {
    asm volatile("{.reg .pred p; mbarrier.try_wait.parity.shared::cta.b64 p, [%1], 0; selp.u32 %0,1,0,p;}"
                 : "=r"(ok) : "r"(bar) : "memory");
  } while (!ok && ++it < SPIN_MAX);
}
__device__ __forceinline__ float ex2(float v) { float r; asm("ex2.approx.ftz.f32 %0, %1;" : "=f"(r) : "f"(v)); return r; }
__device__ __forceinline__ float rcp(float v) { float r; asm("rcp.approx.ftz.f32 %0, %1;" : "=f"(r) : "f"(v)); return r; }
__device__ __forceinline__ void mma16(float* d, const uint32_t* a, uint32_t b0, uint32_t b1) {
  asm volatile("mma.sync.aligned.m16n8k16.row.col.f32.bf16.bf16.f32 {%0,%1,%2,%3}, {%4,%5,%6,%7}, {%8,%9}, {%0,%1,%2,%3};"
               : "+f"(d[0]), "+f"(d[1]), "+f"(d[2]), "+f"(d[3]) : "r"(a[0]), "r"(a[1]), "r"(a[2]), "r"(a[3]), "r"(b0), "r"(b1));
}
__device__ __forceinline__ float4 lds16(uint32_t a) {
  float4 v; asm volatile("ld.shared.v4.f32 {%0,%1,%2,%3}, [%4];" : "=f"(v.x), "=f"(v.y), "=f"(v.z), "=f"(v.w) : "r"(a) : "memory"); return v;
}
__device__ __forceinline__ void ldsm_t(uint32_t* r, uint32_t a) {
  asm volatile("ldmatrix.sync.aligned.m8n8.x4.trans.shared.b16 {%0,%1,%2,%3}, [%4];" : "=r"(r[0]), "=r"(r[1]), "=r"(r[2]), "=r"(r[3]) : "r"(a) : "memory");
}
__device__ __forceinline__ void ldsm(uint32_t* r, uint32_t a) {
  asm volatile("ldmatrix.sync.aligned.m8n8.x4.shared.b16 {%0,%1,%2,%3}, [%4];" : "=r"(r[0]), "=r"(r[1]), "=r"(r[2]), "=r"(r[3]) : "r"(a) : "memory");
}
template <int N>
__device__ __forceinline__ void tred(float* a, int lane, int m) {
  const bool hi = lane & m;
#pragma unroll
  for (int i = 0; i < N; i++) {
    float send = hi ? a[i] : a[i + N], keep = hi ? a[i + N] : a[i];
    a[i] = keep + __shfl_xor_sync(~0u, send, m);
  }
}
template <int N>
__device__ __forceinline__ void tmax(float* a, int lane, int m) {
  const bool hi = lane & m;
#pragma unroll
  for (int i = 0; i < N; i++) {
    float send = hi ? a[i] : a[i + N], keep = hi ? a[i + N] : a[i];
    a[i] = fmaxf(keep, __shfl_xor_sync(~0u, send, m));
  }
}
__device__ __forceinline__ void arrive2(uint32_t bar, uint32_t rbar, bool local, bool remote) {
  asm volatile("{.reg .pred p, q; setp.ne.s32 p, %2, 0; setp.ne.s32 q, %3, 0; @p mbarrier.arrive.shared::cta.b64 _, [%0];\n"
               "@q mbarrier.arrive.relaxed.cluster.shared::cluster.b64 _, [%1];}" ::"r"(bar), "r"(rbar), "r"((int)local), "r"((int)remote) : "memory");
}
__device__ __forceinline__ unsigned long long stream_policy() {
  unsigned long long p;
  asm volatile("createpolicy.fractional.L2::evict_first.b64 %0, 1.0;" : "=l"(p));
  return p;
}
__device__ __forceinline__ void tma3d(uint32_t dst, const CUtensorMap* tm, uint32_t bar, int c0, int c1, int c2) {
  asm volatile("cp.async.bulk.tensor.3d.shared::cluster.global.mbarrier::complete_tx::bytes.L2::cache_hint [%0], [%1, {%3, %4, %5}], [%2], %6;"
               ::"r"(dst), "l"(tm), "r"(bar), "r"(c0), "r"(c1), "r"(c2), "l"(stream_policy()) : "memory");
}
__device__ __forceinline__ void st_async2(uint32_t dst, uint32_t bar, float v0, float v1) {
  asm volatile("st.async.shared::cluster.mbarrier::complete_tx::bytes.v2.f32 [%0], {%1, %2}, [%3];" ::"r"(dst), "f"(v0), "f"(v1), "r"(bar) : "memory");
}
__device__ __forceinline__ void st_pair(int mode, uint32_t dst, uint32_t bar, float v0, float v1) {
  asm volatile("{.reg .pred p, q; setp.eq.s32 p, %4, 1; setp.eq.s32 q, %4, 2; @p st.shared.v2.f32 [%0], {%1, %2};\n"
               "@q st.async.shared::cluster.mbarrier::complete_tx::bytes.v2.f32 [%0], {%1, %2}, [%3];}"
               ::"r"(dst), "f"(v0), "f"(v1), "r"(bar), "r"(mode) : "memory");
}
__device__ __forceinline__ void spin_until(unsigned t) { while ((int)((unsigned)clock() - t) < 0) {} }
__device__ __forceinline__ unsigned wait_until(unsigned t) {
  unsigned now;
  for (;;) {
    asm volatile("mov.u32 %0, %%globaltimer_lo;" : "=r"(now));
    if ((int)(now - t) >= 0) break;
  }
  return now;
}
#define PIN(x) asm volatile("" : "+r"(x))
#define PINL(x) asm volatile("" : "+l"(x))
#define BAR_ARRIVE(i) asm volatile("mbarrier.arrive.shared::cta.b64 _, [%0];" ::"r"(bar0 + 8 * (i)) : "memory")
#define CNT_ADD(c) asm volatile("red.relaxed.gpu.global.add.u32 [%0], 1;" ::"l"(scr->cnt + (c)) : "memory")
#define BAR_INIT(i, cnt) asm volatile("mbarrier.init.shared::cta.b64 [%0], %1;" ::"r"(bar0 + 8 * (i)), "r"(cnt) : "memory")
#define BAR_ARM(i, bytes) asm volatile("mbarrier.arrive.expect_tx.shared::cta.b64 _, [%0], %1;" ::"r"(bar0 + 8 * (i)), "r"(bytes) : "memory")

__device__ __forceinline__ void tail(unsigned char* smem, Scratch* __restrict__ scr, const bf16* __restrict__ x, bf16* __restrict__ out,
                                     const unsigned par, const unsigned epoch, const int warp) {
  int tid, b;
  asm volatile("mov.u32 %0, %%tid.x;" : "=r"(tid));
  asm volatile("mov.u32 %0, %%ctaid.x;" : "=r"(b));
  const int lane = tid & 31, g = lane >> 2, tq = lane & 3;
  const uint32_t sb = __shfl_sync(~0u, s2u(smem), 0), bar0 = sb + OFF_BAR;
  float* s_sm = (float*)(smem + OFF_SM);
  const int prow = 4 * (lane >> 4) + ((lane & 7) >> 1) + 8 * (lane & 1);
  const float* s_co = (const float*)(smem + OFF_CO);
  const int opos = (b & 15) * 32 + (lane & 16) + 2 * (lane & 6) + ((lane >> 2) & 2) + (lane & 1);
  const float xv = b < 16 ? __bfloat162float(x[(b & 15) * 32 + lane]) : 0.f;
  const int rk = b & 1, ob = 32 * rk + ((b >> 1) & 31);
  uint32_t psb;
  asm volatile("mapa.shared::cluster.u32 %0, %1, %2;" : "=r"(psb) : "r"(sb), "r"(rk ^ 1));
  {
    uint32_t a[8][4];
    {
      const int rg = tid >> 4;
      const uint4* src = g_xo + ((size_t)b * 64 + rg) * RS;
      const uint32_t dst = sb + OFF_XO + rg * 256 + (((tid & 15) ^ (rg & 7)) << 4);
      unsigned long long todo = 0x0001000100010001ull;
#pragma unroll 1
      for (int it = 0; it < SPIN_MAX * 16; it++) {
        unsigned long long mk = *(volatile unsigned long long*)(smem + OFF_MASK);
        const unsigned long long nw = (mk >> rg) & todo;
        todo ^= nw;
#pragma unroll
        for (int i = 0; i < 4; i++)
          if (nw >> (16 * i) & 1)
            asm volatile("cp.async.cg.shared.global [%0], [%1], 16;" ::"r"(dst + i * 4096), "l"(src + i * 16 * RS + (tid & 15)) : "memory");
        if (!__any_sync(~0u, todo != 0)) break;
      }
      asm volatile("cp.async.mbarrier.arrive.noinc.shared::cta.b64 [%0];" ::"r"(bar0 + 8 * (XB + 2)) : "memory");
    }
    mbar_wait(bar0 + 8 * FB_UV); mbar_wait(bar0 + 8 * (FB_UV + 1));
    const uint32_t ab = sb + OFF_UV + (warp >> 2) * 8192 + (8 * (lane >> 4) + (lane & 7)) * 128 + (((2 * (warp & 3) + ((lane >> 3) & 1)) ^ (lane & 7)) << 4);
#pragma unroll
    for (int s = 0; s < 8; s++) ldsm_t(a[s], ab + (s >> 2) * 16384 + (s & 3) * 2048);
    const int chn = 2 * warp + (tq & 1);
    uint32_t a_b = sb + OFF_B + (tq >> 1) * 272 + (32 * (chn >> 2) + 8 * (g >> 1) + 2 * (chn & 3) + (g & 1)) * 2;
    uint32_t a_bq = sb + OFF_B + (lane & 1) * 272 + (lane >> 3) * 16;
    unsigned* p_c = g_xc + (b >> 2) * 256 + warp * 32 + (b & 3) * 8 + (g & 3) * 2 + (g >> 2);
    PIN(a_b); PIN(a_bq); PINL(p_c);
    mbar_wait(bar0 + 8 * (XB + 6));
    uint32_t wb[8];
#pragma unroll
    for (int s = 0; s < 8; s++) wb[s] = *(const uint32_t*)(smem + OFF_RA + (4 * s + tq) * 4);
    const float invL = *(const float*)(smem + OFF_RA + 128);
    float ov;
    POLL {
      mbar_wait(bar0 + 8 * (XB + 2));
      uint32_t ao[4][4];
#pragma unroll
      for (int s = 0; s < 4; s++)
        ldsm_t(ao[s], sb + OFF_XO + (16 * s + 8 * (lane >> 4) + (lane & 7)) * 256 + (((2 * warp + ((lane >> 3) & 1)) ^ (lane & 7)) << 4));
      float d[4][4] = {};
#pragma unroll
      for (int s = 0; s < 4; s++) mma16(d[s], ao[s], wb[2 * s], wb[2 * s + 1]);
      const unsigned p2 = par * 0x10001u;
      unsigned bad = 0;
#pragma unroll
      for (int s = 0; s < 4; s++) bad |= lop_x3(ao[s][0], ao[s][1], p2) | lop_x3(ao[s][2], ao[s][3], p2);
      bad = g == 0 ? bad | (bad >> 16) : 0u;
      ov = (tq & 1) ? (d[0][2] + d[1][2]) + (d[2][2] + d[3][2]) : (d[0][0] + d[1][0]) + (d[2][0] + d[3][0]);
      if (__builtin_expect(!__any_sync(~0u, bad & 1) || ++it_ >= SPIN_MAX, 1)) break;
#pragma unroll
      for (int i = 0; i < 4; i++)
        asm volatile("cp.async.cg.shared.global [%0], [%1], 16;"
                     ::"r"(sb + OFF_XO + ((lane >> 1) + 16 * i) * 256 + (((2 * warp + (lane & 1)) ^ ((lane >> 1) & 7)) << 4)),
                       "l"(g_xo + ((size_t)b * 64 + (lane >> 1) + 16 * i) * RS + 2 * warp + (lane & 1)) : "memory");
      asm volatile("cp.async.wait_all;" ::: "memory");
      __syncwarp();
    }
    {
      const float lo = ov - bfhi(__float_as_uint(ov));
      asm volatile("st.shared.u16 [%0], %1;" ::"r"(a_b), "h"((unsigned short)((tq & 2) ? pack2(lo, lo) : __float_as_uint(ov) >> 16)) : "memory");
    }
    nbar(1, 256);
    float d[4][4] = {};
#pragma unroll
    for (int y = 0; y < 4; y++) {
      uint32_t bq[4];
      ldsm(bq, a_bq + 64 * y);
      mma16(d[(2 * y) & 3], a[2 * y], bq[0], bq[1]); mma16(d[(2 * y + 1) & 3], a[2 * y + 1], bq[2], bq[3]);
    }
    const float r0 = ((d[0][0] + d[0][1]) + (d[1][0] + d[1][1])) + ((d[2][0] + d[2][1]) + (d[3][0] + d[3][1]));
    const float r1 = ((d[0][2] + d[0][3]) + (d[1][2] + d[1][3])) + ((d[2][2] + d[2][3]) + (d[3][2] + d[3][3]));
    if (tq == 0) stx4(p_c, pack2t(r0 * invL, r1 * invL, par));
  }
  unsigned tpub = clock();
  mbar_wait(bar0 + 8 * (XB + 4));
  const float gav = s_co[256 + (opos & 31)];
  const float gbv = s_co[288 + (lane & 4) + 2 * (lane & 1) + ((lane >> 1) & 1)];
  float4 cf[2];
#pragma unroll
  for (int s = 0; s < 2; s++) cf[s] = *(const float4*)(s_co + 32 * warp + 16 * s + 4 * tq);
  {
    uint32_t a[2][4][4];
    mbar_wait(bar0 + 8 * (FB_O + (warp >> 2)));
    const uint32_t ab = sb + OFF_O + (32 * warp + prow) * 128 + ((((lane >> 3) & 1) ^ (prow & 7)) << 4);
#pragma unroll
    for (int i = 0; i < 8; i++) ldsm_t(a[i >> 2][i & 3], (ab + (i >> 2) * 2048) ^ ((i & 3) << 5));
    uint4 v;
    const unsigned* pc = g_xc + (4 * (b >> 4) + 2 * rk + (warp >> 2)) * 256 + 64 * (warp & 3) + 2 * lane;
    uint32_t ro = ((tq >> 1) == rk ? sb : psb) + OFF_P + (8 * (tq & 1) + g) * 144 + (8 * rk + warp) * 8;
    uint32_t a_q = sb + OFF_P + (8 * (lane >> 4) + (lane & 7)) * 144;
    unsigned* p_ao = g_xao + (b >> 5) * 1024 + (opos >> 4) * 32 + (b & 16) + (opos & 15);
    PIN(ro); PIN(a_q); PINL(p_ao); PINL(pc);
    spin_until(tpub + DLY5);
    POLL {
      const unsigned long long u0 = ldx64(pc);
      v.x = (unsigned)u0; v.y = u0 >> 32;
      RETRY(X8(v))
    }
    v.z = lane & 16 ? v.x : 0u; v.w = lane & 16 ? v.y : 0u;
    if (lane & 16) v.x = v.y = 0u;
    float d[4][4] = {};
#pragma unroll
    for (int mt = 0; mt < 4; mt++) mma16(d[mt], a[0][mt], v.x, v.y);
#pragma unroll
    for (int mt = 0; mt < 4; mt++) mma16(d[mt], a[1][mt], v.z, v.w);
    float r[8];
#pragma unroll
    for (int i = 0; i < 8; i++) r[i] = d[i >> 1][2 * (i & 1)] + d[i >> 1][2 * (i & 1) + 1];
    tred<4>(r, lane, 2); tred<2>(r, lane, 1);
    st_pair((tq >> 1) == rk ? 1 : 2, ro, psb + OFF_BAR + 8 * (XB + 3), r[0], r[1]);
    __syncwarp();
    if (lane == 0) BAR_ARRIVE(XB + 3);
    if (warp == 0) {
      mbar_wait(bar0 + 8 * (XB + 3));
      float p[8];
#pragma unroll
      for (int i = 0; i < 8; i++) {
        const float4 q = lds16(a_q + i * 16);
        p[i] = (lane & 8) ? q.y + q.w : q.x + q.z;
      }
      const float t = ((p[0] + p[1]) + (p[2] + p[3])) + ((p[4] + p[5]) + (p[6] + p[7]));
      stx4(p_ao, fbits(gav * t + xv));
    }
  }
  tpub = clock();
  if (b < 112) {
    uint32_t af[2][4][4], ad[4][4];
    const uint32_t ab = sb + (32 * warp + 8 * (lane >> 4) + (lane & 7)) * 64 + ((((lane >> 3) & 1) ^ ((lane >> 1) & 3)) << 4);
    uint32_t ro = ((tq & 1) == rk ? sb : psb) + OFF_R4 + (8 * (tq >> 1) + g) * 176 + (10 * rk + warp) * 8;
    uint32_t a_q = sb + OFF_R4 + (8 * (lane >> 4) + (lane & 7)) * 176 + (lane & 8) * 10;
    uint32_t a_d = sb + OFF_D + warp * 2048 + (8 * (lane >> 4) + (lane & 7)) * 128 + ((((lane >> 3) & 1) ^ (lane & 7)) << 4);
    unsigned* p_f = g_xf + b * 512 + 64 * warp + 16 * tq + 2 * g;
    const unsigned* pa = g_xao + (g >> 1) * 1024 + 512 * rk + 64 * warp + 4 * (lane & 7);
    PIN(ro); PIN(a_q); PIN(a_d); PINL(p_f); PINL(pa);
    spin_until(tpub + DLY6);
    uint4 v[2];
    {
      bool have = false;
      POLL {
        v[0] = ldx16(pa); v[1] = ldx16(pa + 32);
        const unsigned t1 = (unsigned)clock() + WTEST;
        while (!have && (int)((unsigned)clock() - t1) < 0) {
          uint32_t ok;
          asm volatile("{.reg .pred p, q; mbarrier.test_wait.parity.shared::cta.b64 p, [%1], 0; mbarrier.test_wait.parity.shared::cta.b64 q, [%1+8], 0;\n"
                       "and.pred p, p, q; vote.sync.all.pred p, p, 0xffffffff; selp.u32 %0, 1, 0, p;}" : "=r"(ok) : "r"(bar0 + 8 * FB_G) : "memory");
          if (ok) {
#pragma unroll
            for (int i = 0; i < 8; i++) ldsm_t(af[i >> 2][i & 3], (ab + ((i & 2) ? OFF_U : OFF_G) + (i >> 2) * 1024) ^ ((i & 1) << 5));
            have = true;
          }
        }
        if (!__any_sync(~0u, (X16(v[0]) | X16(v[1])) & 1) || ++it_ >= SPIN_MAX) break;
      }
      float df[4][4] = {}, dg[2][4] = {};
      uint32_t zb[4];
      const uint32_t one = g == 0 ? 0x3F803F80u : 0u;
#pragma unroll
      for (int s = 0; s < 2; s++) {
        const uint32_t y0 = pack2(u2f(v[s].x), u2f(v[s].y)), y1 = pack2(u2f(v[s].z), u2f(v[s].w));
        const uint32_t ya[4] = {y0, one, y1, one};
        mma16(dg[s], ya, y0, y1);
        zb[2 * s] = pack2(u2f(v[s].x) * cf[s].x, u2f(v[s].y) * cf[s].y); zb[2 * s + 1] = pack2(u2f(v[s].z) * cf[s].z, u2f(v[s].w) * cf[s].w);
      }
      float st[2] = {(dg[0][2] + dg[0][3]) + (dg[1][2] + dg[1][3]), (dg[0][0] + dg[0][1]) + (dg[1][0] + dg[1][1])};
      if (!have) {
        mbar_wait(bar0 + 8 * FB_G); mbar_wait(bar0 + 8 * (FB_G + 1));
#pragma unroll
        for (int i = 0; i < 8; i++) ldsm_t(af[i >> 2][i & 3], (ab + ((i & 2) ? OFF_U : OFF_G) + (i >> 2) * 1024) ^ ((i & 1) << 5));
      }
#pragma unroll
      for (int i = 0; i < 8; i++) mma16(df[i & 3], af[i >> 2][i & 3], zb[2 * (i >> 2)], zb[2 * (i >> 2) + 1]);
#pragma unroll
      for (int o2 = 1; o2 < 4; o2 <<= 1) { st[0] += __shfl_xor_sync(~0u, st[0], o2); st[1] += __shfl_xor_sync(~0u, st[1], o2); }
#pragma unroll
      for (int o2 = 4; o2 < 32; o2 <<= 1) st[1] += __shfl_xor_sync(~0u, st[1], o2);
      float r[8];
#pragma unroll
      for (int i = 0; i < 8; i++) r[i] = df[i >> 1][2 * (i & 1)] + df[i >> 1][2 * (i & 1) + 1];
      tred<4>(r, lane, 2); tred<2>(r, lane, 1);
      const int md = (tq & 1) == rk ? 1 : 2;
      st_pair(md, ro, psb + OFF_BAR + 8 * (XB + 5), r[0], r[1]);
      st_pair(lane < 2 ? md : 0, ro + 16 * 176, psb + OFF_BAR + 8 * (XB + 5), st[0], st[1]);
      __syncwarp();
      if (lane == 0) BAR_ARRIVE(XB + 5);
      mbar_wait(bar0 + 8 * FB_D);
#pragma unroll
      for (int mt = 0; mt < 4; mt++)
        ldsm_t(ad[mt], a_d ^ (mt << 5));
    }
    mbar_wait(bar0 + 8 * (XB + 5));
    {
      float4 q[5], u[8];
#pragma unroll
      for (int i = 0; i < 5; i++) q[i] = lds16(a_q + i * 16);
#pragma unroll
      for (int i = 0; i < 8; i++) u[i] = *(const float4*)(smem + OFF_R4 + 16 * 176 + (i >> 2) * 80 + (i & 3) * 16);
      float p[6] = {((q[0].x + q[0].z) + (q[1].x + q[1].z)) + ((q[2].x + q[2].z) + (q[3].x + q[3].z)), q[4].x, q[4].z,
                    ((q[0].y + q[0].w) + (q[1].y + q[1].w)) + ((q[2].y + q[2].w) + (q[3].y + q[3].w)), q[4].y, q[4].w};
      tred<3>(p, lane, 8);
      const float P = p[0], A1 = p[1], A2 = p[2];
      const float mean = (((u[0].x + u[0].z) + (u[1].x + u[1].z)) + ((u[2].x + u[2].z) + (u[3].x + u[3].z)) +
                          ((u[4].x + u[4].z) + (u[5].x + u[5].z)) + ((u[6].x + u[6].z) + (u[7].x + u[7].z))) * (1.f / 512.f);
      const float sq = (((u[0].y + u[0].w) + (u[1].y + u[1].w)) + ((u[2].y + u[2].w) + (u[3].y + u[3].w)) +
                         ((u[4].y + u[4].w) + (u[5].y + u[5].w)) + ((u[6].y + u[6].w) + (u[7].y + u[7].w))) * (1.f / 512.f);
      float rstd;
      asm("rsqrt.approx.ftz.f32 %0, %1;" : "=f"(rstd) : "f"(fmaxf(sq - mean * mean, 0.f) + 1e-5f));
      const float gg = bfr(rstd * (P - mean * A1) + A2);
      const float uu = __shfl_xor_sync(~0u, gg, 16);
      const float hh = bfr(gg * rcp(1.f + ex2(gg * (-2.302208198f - 0.1029432397f * gg * gg)))) * uu;
      const uint32_t hw = pack2(hh, __shfl_down_sync(~0u, hh, 1));
      const uint32_t b0 = __shfl_sync(~0u, hw, 2 * tq), b1 = __shfl_sync(~0u, hw, 2 * tq + 8);
      float f0 = 0, f1 = 0;
#pragma unroll
      for (int mt = 0; mt < 4; mt++) {
        float dd[4] = {0, 0, 0, 0};
        mma16(dd, ad[mt], b0, b1);
        if (tq == mt) { f0 = dd[0]; f1 = dd[2]; }
      }
      stx8(p_f, make_uint2(fbits(f0), fbits(f1)));
    }
    tpub = clock();
    if (b < 64 && warp == (b >> 3)) {
      const uint4 y = (b & 4) ? v[1] : v[0];
      float a4[4] = {u2f(y.x), u2f(y.y), u2f(y.z), u2f(y.w)};
      tred<2>(a4, lane, 16); tred<1>(a4, lane, 8);
      a4[0] += __shfl_xor_sync(~0u, a4[0], 4);
      if (!(lane & 4)) s_sm[416 + 8 * (lane >> 4) + 2 * tq + ((lane >> 3) & 1)] = a4[0];
      if (warp == 7) nbar_arrive(2, 256);
    } else if (b < 64 && warp == 7) nbar_arrive(2, 256);
    if (b < 64 && warp < 7) {
      uint4 v;
      const unsigned* pf = g_xf + (tid >> 1) * 512 + 8 * ob + 4 * (tid & 1);
      const int col = 16 * (ob >> 1) + 4 * (ob & 1) + ((tid >> 1) & 3) + 8 * (tid & 1);
      bf16* po = out + col;
      PINL(po); PINL(pf);
      spin_until(tpub + DLY7);
      POLL { v = ldx16(pf); RETRY(X16(v)) }
      float f[4] = {u2f(v.x), u2f(v.y), u2f(v.z), u2f(v.w)};
      tred<2>(f, lane, 16); tred<1>(f, lane, 8);
      f[0] += __shfl_xor_sync(~0u, f[0], 4); f[0] += __shfl_xor_sync(~0u, f[0], 2);
      if (!(lane & 6)) s_sm[352 + warp * 8 + 4 * (lane & 1) + (lane >> 3)] = f[0];
      nbar(2, 256);
      if (tid < 8) {
        const float* q = s_sm + 352 + tid;
        const float t = ((q[0] + q[8]) + (q[16] + q[24])) + ((q[32] + q[40]) + q[48]);
        *po = __float2bfloat16(s_sm[416 + (col & 15)] + bfr(gbv * bfr(t)));
        if (b == 0 && tid == 0) stx4(&g_epoch, epoch + 1);
      }
    }
  }
}

__global__ void __cluster_dims__(2, 1, 1) __launch_bounds__(384, 1)
fused_kernel(const bf16* __restrict__ x, const bf16* __restrict__ cvec, const bf16* __restrict__ w_mod, bf16* __restrict__ out,
             Scratch* __restrict__ scr, const __grid_constant__ TMaps tms) {
  extern __shared__ __align__(1024) unsigned char smem[];
  const int tid = threadIdx.x, warp = __shfl_sync(~0u, tid >> 5, 0), lane = tid & 31;
  const int b = blockIdx.x, rk = b & 1, pr = b >> 1, hd = b >> 2;
  uint32_t sb = s2u(smem), bar0 = sb + OFF_BAR;

  unsigned gt_start;
  asm volatile("mov.u32 %0, %%globaltimer_lo;" : "=r"(gt_start));
  const int g = lane >> 2, tq = lane & 3;
  const int arow = 64 * (b >> 4) + ((tid & 255) >> 3);
  uint4 wm0, wm1;
  uint32_t c0w, c1w;
  if (warp < 8) {
    const bf16* wa = w_mod + (size_t)arow * 3072 + (lane & 4) * 128 + 32 * (b & 15) + 8 * tq;
    wm0 = ldx16(wa); wm1 = ldx16(wa + 32 * 3072);
    c0w = ldc4(cvec + (arow & ~1)); c1w = ldc4(cvec + (arow & ~1) + 32);
  }
  const unsigned t_off = gt_start + RATE_T0;
  if (warp == 11) {
    if (lane == 0) {
#pragma unroll
      for (int i = 0; i < FB_KV; i++) { BAR_INIT(i, 1); BAR_ARM(i, 16384); }
    }
    __syncwarp();
    asm volatile("fence.mbarrier_init.release.cluster;" ::: "memory");
    asm volatile("barrier.cluster.arrive.relaxed.aligned;" ::: "memory");
#pragma unroll 1
    for (int i = 0; i < FB_KV; i++) {
      if (i >= HWIN) mbar_wait(bar0 + 8 * (i - HWIN));
      wait_until(t_off + (i < 4 ? 2 * i + ((b >> 1) & 1) : 4 * i - 8 + (b & 3)) * (RATE_H / 4));
      if (lane == 0) {
        if (i < 4) tma3d(sb + OFF_WQ + i * 16384, &tms.m[0], bar0 + 8 * i, 0, i * 128, 2 * hd + rk);
        else tma3d(sb + OFF_WQ + i * 16384, &tms.m[1], bar0 + 8 * i, 0, (b & 3) * 128 + (i - 4) * 64, 2 * hd);
      }
      __syncwarp();
    }
  }
  if (warp == 10) {
    const uint4 xa = ldc16(x + 16 * lane), xb = ldc16(x + 16 * lane + 8);
    const unsigned ep = ldc4(&g_epoch);
    float xv[16] = {bflo(xa.x), bfhi(xa.x), bflo(xa.y), bfhi(xa.y), bflo(xa.z), bfhi(xa.z), bflo(xa.w), bfhi(xa.w),
                    bflo(xb.x), bfhi(xb.x), bflo(xb.y), bfhi(xb.y), bflo(xb.z), bfhi(xb.z), bflo(xb.w), bfhi(xb.w)};
    float s = 0;
#pragma unroll
    for (int i = 0; i < 16; i++) s += xv[i];
#pragma unroll
    for (int o = 16; o; o >>= 1) s += __shfl_xor_sync(~0u, s, o);
    const float mean = s * (1.f / 512.f);
    s = 0;
#pragma unroll
    for (int i = 0; i < 16; i++) { xv[i] -= mean; s += xv[i] * xv[i]; }
#pragma unroll
    for (int o = 16; o; o >>= 1) s += __shfl_xor_sync(~0u, s, o);
    const float rstd = rsqrtf(s * (1.f / 512.f) + 1e-5f);
    if ((lane >> 1) == (b & 15))
#pragma unroll
      for (int i = 0; i < 4; i++)
        *(float4*)(smem + OFF_SM + (256 + (lane & 1) * 16 + 4 * i) * 4) = make_float4(xv[4 * i] * rstd, xv[4 * i + 1] * rstd, xv[4 * i + 2] * rstd, xv[4 * i + 3] * rstd);
    if (lane == 0) *(volatile unsigned*)(smem + OFF_MASK + 8) = ep;
    nbar_arrive(1, 288);
  }
  if (warp >= 8) {
    asm volatile("setmaxnreg.dec.sync.aligned.u32 72;");
    if (tid == 288) {
#pragma unroll
      for (int q = FB_KV; q < FB_KV + 16; q++) { BAR_INIT(q, 1); BAR_ARM(q, 32768); }
    }
    if (tid == 320) {
#pragma unroll
      for (int q = 0; q <= 13 + NSLOT; q++) BAR_INIT(EB + q, q == 0 ? 4 : q < 5 ? 16 : q < 16 ? 12 : 6);
    }
    if (tid == 256) {
#pragma unroll
      for (int q = FB_MOD; q <= FB_D; q++) { BAR_INIT(q, 1); BAR_ARM(q, 16384); }
      BAR_INIT(QB, 9); BAR_ARM(QB, 1024);
#pragma unroll
      for (int q = 0; q < 7; q++) BAR_INIT(XB + q, q == 2 ? 256 : q == 5 || q == 3 ? 9 : 1);
      BAR_ARM(XB + 3, 1024);
      BAR_ARM(XB + 5, 1024 + 64 + 512);
      *(volatile unsigned long long*)(smem + OFF_MASK) = 0;
    }
    if (warp != 11) {
      __syncwarp();
      asm volatile("fence.mbarrier_init.release.cluster;" ::: "memory");
      __threadfence_block();
      asm volatile("barrier.cluster.arrive.relaxed.aligned;" ::: "memory");
    }
    if (warp == 11) {
      asm volatile("barrier.cluster.wait.acquire.aligned;" ::: "memory");
      const unsigned epoch = *(volatile unsigned*)(smem + OFF_MASK + 8), par = (epoch + 1) & 1;
      mbar_wait(bar0 + 8 * (FB_KV + 15));
      for (int it = 0; ldx4(scr->cnt + 96 + 32 * (b >> 6)) != (epoch + 1) * 64 && it < SPIN_MAX; it++) {}
      uint4 hh;
      POLL { hh = ldx16(g_ml + (b >> 2) * 64 + 2 * lane); RETRY(X16(hh)) }
      int mi = __float_as_int(fmaxf(u2f(hh.x), u2f(hh.z)));
      mi ^= (mi >> 31) & 0x7fffffff;
      mi = __reduce_max_sync(~0u, mi);
      mi ^= (mi >> 31) & 0x7fffffff;
      const float M = __int_as_float(mi);
      const uint32_t wp = pack2(ex2(u2f(hh.x) - M), ex2(u2f(hh.z) - M));
      float L = bflo(wp) * u2f(hh.y) + bfhi(wp) * u2f(hh.w);
#pragma unroll
      for (int o2 = 16; o2; o2 >>= 1) L += __shfl_xor_sync(~0u, L, o2);
      *(uint32_t*)(smem + OFF_RA + lane * 4) = wp;
      if (lane == 0) *(float*)(smem + OFF_RA + 128) = rcp(L);
      __syncwarp();
      if (lane == 0) BAR_ARRIVE(XB + 6);
    }
    if (warp == 10) {
      if (lane < 8) asm volatile("prefetch.tensormap [%0];" ::"l"(&tms.m[lane + 1]) : "memory");
      asm volatile("barrier.cluster.wait.acquire.aligned;" ::: "memory");
      const unsigned epoch = *(volatile unsigned*)(smem + OFF_MASK + 8);
#pragma unroll 1
      for (int e = 0; e < 2; e++) {
        for (int it = 0; ldx4(scr->cnt + (e ? 2 + rk : 1)) != (epoch + 1) * (e ? 64 : 128) && it < SPIN_MAX; it++) {}
        if (lane == 0) BAR_ARRIVE(XB + e);
      }
      mbar_wait(bar0 + 8 * (FB_KV + 14));
      unsigned long long m = 0;
#pragma unroll 1
      for (int it = 0; ~m && it < SPIN_MAX; it++) {
        m = ldx64(scr->cnt + 32 + 32 * (b >> 6)) ^ ((epoch & 1) ? ~0ull : 0ull);
        if (lane == 0) *(volatile unsigned long long*)(smem + OFF_MASK) = m;
      }
    }
    if (warp == 9) {
      asm volatile("barrier.cluster.wait.acquire.aligned;" ::: "memory");
      const unsigned epoch = *(volatile unsigned*)(smem + OFF_MASK + 8);
      const unsigned par = (epoch + 1) & 1, inv = par ^ 1;
      const uint4 inv4 = make_uint4(inv, inv, inv, inv);
      mbar_wait(bar0 + 8 * FB_KV);
#pragma unroll 2
      for (int k = 0; k < 8; k++) {
        const uint32_t cp = ldc4(cvec + 2 * (lane + 32 * k));
        *(uint32_t*)(smem + OFF_SILU + (lane + 32 * k) * 4) = pack2(silu_bf(bflo(cp)), silu_bf(bfhi(cp)));
      }
      __syncwarp();
      mbar_wait(bar0 + 8 * FB_MOD);
      const uint32_t ab = sb + OFF_MOD + (8 * (lane >> 4) + (lane & 7)) * 32 + ((((lane >> 3) ^ (lane >> 2)) & 1) << 4);
      float d[4][4] = {};
#pragma unroll 2
      for (int s4 = 0; s4 < 8; s4++)
#pragma unroll
        for (int s = 0; s < 4; s++) {
          uint32_t a[4];
          const uint32_t* ps = (const uint32_t*)(smem + OFF_SILU) + 32 * s4 + 8 * s + tq;
          ldsm_t(a, ab + (4 * s4 + s) * 512); mma16(d[s], a, ps[0], ps[4]);
        }
      const float t = (tq & 1) ? (d[0][2] + d[1][2]) + (d[2][2] + d[3][2]) : (d[0][0] + d[1][0]) + (d[2][0] + d[3][0]);
      if (tq < 2) stx4(g_xm + b * 16 + 2 * (g & 6) + 2 * tq + (g & 1), fbits(bfr(t)));
      __syncwarp();
      if (lane == 0) CNT_ADD(6);
      mbar_wait(bar0 + 8 * (FB_KV + 8));
      if (lane < 16) stx16(g_xc + (b >> 2) * 256 + (lane >> 1) * 32 + (b & 3) * 8 + (lane & 1) * 4, inv4);
      if (lane < 8) stx16(g_xao + (b >> 5) * 1024 + (b & 15) * 64 + (lane & 4) * 8 + (b & 16) + (lane & 3) * 4, inv4);
      if (b < 112)
#pragma unroll 1
        for (int k = 0; k < 4; k++) stx16(g_xf + b * 512 + (lane + 32 * k) * 4, inv4);
      nbar_arrive(2, 288);
      for (int it = 0; ldx4(scr->cnt + 6) != (epoch + 1) * 128 && it < SPIN_MAX; it++) __nanosleep(100);
      {
        uint4 sv[2], cb[2];
        unsigned ga, gb;
        POLL {
#pragma unroll
          for (int k = 0; k < 2; k++) { sv[k] = ldx16(g_xm + 512 + 256 * rk + 4 * (lane + 32 * k)); cb[k] = ldx16(g_xm + 1024 + 256 * rk + 4 * (lane + 32 * k)); }
          ga = ldx4(g_xm + (b & 15) * 32 + lane); gb = ldx4(g_xm + 1536 + 256 * rk + 8 * (pr & 31) + (lane & 7));
          RETRY(X16(sv[0]) | X16(sv[1]) | X16(cb[0]) | X16(cb[1]) | lop_x3(ga, gb, par))
        }
#pragma unroll
        for (int k = 0; k < 2; k++) {
          const float c0 = bfr(1.f + bfhi(cb[k].x)), c1 = bfr(1.f + bfhi(cb[k].y)), c2 = bfr(1.f + bfhi(cb[k].z)), c3 = bfr(1.f + bfhi(cb[k].w));
          *(float4*)(smem + OFF_CO + (lane + 32 * k) * 16) = make_float4(c0, c1, c2, c3);
          uint2* pb = (uint2*)(smem + OFF_BP) + lane + 32 * k;
          pb[0] = make_uint2(pack2(c0, c1), pack2(c2, c3));
          pb[64] = make_uint2(__byte_perm(sv[k].x, sv[k].y, 0x7632), __byte_perm(sv[k].z, sv[k].w, 0x7632));
        }
        *(float*)(smem + OFF_CO + 1024 + lane * 4) = bfhi(ga);
        *(float*)(smem + OFF_CO + 1152 + lane * 4) = bfhi(gb);
      }
      __syncwarp();
      if (lane == 0) BAR_ARRIVE(XB + 4);
    }
    if (warp == 8) {
      const unsigned stag = ((pr * SMUL) & 63) * RATE_NS >> 6;
      unsigned tnext = t_off + 4 * RATE_H;
      asm volatile("barrier.cluster.wait.acquire.aligned;" ::: "memory");
#pragma unroll 1
      for (int k = 0; k < 24; k++) {
        const int code = (k < 12 ? ORDER0 >> (5 * k) : ORDER1 >> (5 * (k - 12))) & 31;
        const bool kv = code < 16;
        const int n = code, w = code - 16;
        if (!kv && w >= 5 && b >= 112) break;
        if (kv) mbar_wait(bar0 + 8 * (FB_KV + n - (n < 6 ? EWIN : KVWIN)));
        if (k >= TAIL_K) mbar_wait(bar0 + 8 * (FB_KV + (int)((ORDER1 >> (5 * (k - 12 - ((WINS >> (4 * (k - TAIL_K))) & 15)))) & 31)));
        const int e = kv ? (n == 3 ? 2 : n == 5 ? 1 : n) : w == 0 ? 0 : w < 5 ? 16 + ((w - 1) >> 1) : w == 7 ? 19 : 18;
        if (e != 1 && k) mbar_wait(bar0 + 8 * (EB + e));
        wait_until(tnext + stag);
        tnext += k > TAIL_K ? RATE_TL : k < 4 ? RATE_E : RATE_NS;
        if (lane == 0) {
          if (kv)
            asm volatile("cp.async.bulk.tensor.3d.shared::cluster.global.mbarrier::complete_tx::bytes.multicast::cluster.L2::cache_hint [%0], [%1, {%3, %4, %5}], [%2], %6, %7;"
                         ::"r"(sb + (n % NSLOT) * SLOT + rk * 16384), "l"(&tms.m[2]), "r"(bar0 + 8 * (FB_KV + n)), "r"(0), "r"(((n >> 1) * 64 + pr) * 64),
                           "r"(4 * (n & 1) + 2 * rk), "h"((unsigned short)3), "l"(stream_policy()) : "memory");
          else {
            tma3d(sb + (w == 0 ? OFF_MOD : w < 5 ? OFF_UV + (w - 1) * 16384 : w == 5 ? OFF_G : w == 6 ? OFF_U : OFF_D),
                  &tms.m[w == 0 ? 3 : w < 3 ? 4 : w < 5 ? 5 : w + 1], bar0 + 8 * (FB_MOD + w),
                  w == 0 ? 1024 + b * 16 : w < 3 || w == 7 ? 0 : w < 5 ? (pr & 7) * 64 : pr * 32, w == 7 ? b * 16 : w == 1 || w == 2 ? (b & 3) * 128 + (w - 1) * 64 : 0,
                  w == 1 || w == 2 ? 2 * hd : w == 3 || w == 4 ? (b >> 4) * 4 + 2 * rk + w - 3 : w == 5 || w == 6 ? rk : 0);
          }
        }
        __syncwarp();
      }
    }
    if (b < 112) {
      const int mt = warp & 1, dd = (warp >> 1) & 1;
      mbar_wait(bar0 + 8 * (XB + 4));
      const uint32_t ab = sb + (mt ? OFF_U : OFF_G) + (8 * (lane >> 4) + (lane & 7)) * 64 + (((2 * dd + ((lane >> 3) & 1)) ^ ((lane >> 1) & 3)) << 4);
      uint32_t base;
      asm volatile("mapa.shared::cluster.u32 %0, %1, %2;" : "=r"(base) : "r"(sb), "r"(dd));
      uint2 bb[16];
#pragma unroll
      for (int s = 0; s < 16; s++) bb[s] = *(const uint2*)(smem + OFF_BP + (g & 1) * 512 + (4 * s + tq) * 8);
      mbar_wait(bar0 + 8 * (FB_G + mt));
      float e[4][4] = {};
#pragma unroll
      for (int s = 0; s < 16; s++) { uint32_t a[4]; ldsm_t(a, ab + s * 1024); mma16(e[s & 3], a, bb[s].x, bb[s].y); }
      float r[4];
#pragma unroll
      for (int i = 0; i < 4; i++) r[i] = (e[0][i] + e[1][i]) + (e[2][i] + e[3][i]);
      if (tq < 2) st_async2(base + OFF_R4 + (8 * mt + g) * 176 + (10 * rk + 8 + tq) * 8, base + OFF_BAR + 8 * (XB + 5), tq ? r[1] : r[0], tq ? r[3] : r[2]);
    }
    return;
  }

  float* s_sm = (float*)(smem + OFF_SM);
  unsigned par, epoch;
  uint32_t rsb;
  {
    float* s_r4 = (float*)(smem + OFF_R4);
    asm volatile("barrier.cluster.arrive.relaxed.aligned;" ::: "memory");
    asm volatile("mapa.shared::cluster.u32 %0, %1, %2;" : "=r"(rsb) : "r"(sb), "r"(rk ^ 1));
    const float c0 = (arow & 1) ? bfhi(c0w) : bflo(c0w), c1 = (arow & 1) ? bfhi(c1w) : bflo(c1w);
    float acc[8] = {0, 0, 0, 0, 0, 0, 0, 0};
    fma8(acc, wm0, silu_bf(c0)); fma8(acc, wm1, silu_bf(c1));
    tred<4>(acc, lane, 8); tred<2>(acc, lane, 16);
    *(float2*)(s_r4 + warp * 64 + 8 * (lane & 7) + ((lane >> 1) & 4) + ((lane >> 3) & 2)) = make_float2(acc[0], acc[1]);
    nbar(1, 288);
    epoch = *(volatile unsigned*)(smem + OFF_MASK + 8);
    par = (epoch + 1) & 1;
    if (warp == 0) {
      float t = 0.f, ca = b < 16 ? 1.f : 0.f;
#pragma unroll
      for (int w = 0; w < 8; w++) { t += s_r4[w * 64 + lane]; ca += s_r4[w * 64 + 32 + lane]; }
      t += ca * s_sm[256 + lane];
      const float nb = __shfl_down_sync(~0u, t, 1);
      const uint32_t w0 = lane < 8 ? pack2t(t, nb, par) : pack2(t, nb);
      const uint32_t w1 = __shfl_down_sync(~0u, w0, 8), w2 = __shfl_down_sync(~0u, w0, 16), w3 = __shfl_down_sync(~0u, w0, 24);
      if (lane < 8 && !(lane & 1)) stx16(g_h + (b >> 5) * 512 + (b & 15) * 32 + (b & 16) + 2 * lane, make_uint4(w0, w1, w2, w3));
      __syncwarp();
      if (lane == 0) CNT_ADD(1);
    }
  }
  asm volatile("barrier.cluster.wait.acquire.aligned;" ::: "memory");
  {
    uint32_t a[4][4][4];
    mbar_wait(bar0 + 8 * (warp >> 1));
    const uint32_t ab = sb + OFF_WQ + (64 * warp + 8 * (lane >> 4) + (lane & 7)) * 128;
#pragma unroll
    for (int s = 0; s < 4; s++)
#pragma unroll
      for (int mt = 0; mt < 4; mt++) ldsm_t(a[s][mt], ab + s * 2048 + (((2 * mt + ((lane >> 3) & 1)) ^ (lane & 7)) << 4));
    uint4 v0, v1;
    const unsigned* ph = g_h + (g >> 1) * 512 + 64 * warp + 4 * (lane & 7);
    uint32_t off = OFF_B + warp * 272 + (32 * rk + 8 * tq + (lane & 4)) * 4;
    PIN(off); PINL(ph);
    mbar_wait(bar0 + 8 * XB);
    POLL { v0 = ldx16(ph); v1 = ldx16(ph + 32); RETRY(lop_x3(v0.x, v1.x, par)) }
    float d[4][4] = {};
#pragma unroll
    for (int mt = 0; mt < 4; mt++) {
      mma16(d[mt], a[0][mt], v0.x, v0.y); mma16(d[mt], a[1][mt], v0.z, v0.w);
      mma16(d[mt], a[2][mt], v1.x, v1.y); mma16(d[mt], a[3][mt], v1.z, v1.w);
    }
    float r[8];
#pragma unroll
    for (int mt = 0; mt < 4; mt++) { r[2 * mt] = d[mt][0] + d[mt][1]; r[2 * mt + 1] = d[mt][2] + d[mt][3]; }
    tred<4>(r, lane, 2); tred<2>(r, lane, 1);
    const float rc = __shfl_xor_sync(~0u, (lane & 4) ? r[0] : r[1], 4);
    const uint32_t wd = (lane & 4) ? pack2(rc, r[1]) : pack2(r[0], rc);
    const uint32_t w1 = __shfl_down_sync(~0u, wd, 8), w2 = __shfl_down_sync(~0u, wd, 16), w3 = __shfl_down_sync(~0u, wd, 24);
    asm volatile("{.reg .pred p; setp.lt.s32 p, %7, 8; @p st.shared.v4.b32 [%0], {%2,%3,%4,%5};\n"
                 "@p st.async.shared::cluster.mbarrier::complete_tx::bytes.v4.b32 [%1], {%2,%3,%4,%5}, [%6];}"
                 ::"r"(sb + off), "r"(rsb + off), "r"(wd), "r"(w1), "r"(w2), "r"(w3), "r"(rsb + OFF_BAR + 8 * QB), "r"(lane) : "memory");
    __syncwarp();
    arrive2(bar0 + 8 * QB, 0, lane == 0, false);
    arrive2(bar0 + 8 * (EB + 2), rsb + OFF_BAR + 8 * (EB + 2), lane == 0, lane == 0);
  }
  {
    uint32_t a[8][4];
    uint32_t a_bq = sb + OFF_B + (lane & 7) * 272 + (lane >> 3) * 16;
    unsigned* p_qa = g_qa + b * 64 + 8 * warp + 4 * lane;
    PIN(a_bq); PINL(p_qa);
    mbar_wait(bar0 + 8 * (FB_UK + (warp >> 2)));
    const uint32_t ab = sb + OFF_WUK + (warp >> 2) * 16384 + (16 * (warp & 3) + (lane & 15)) * 128;
#pragma unroll
    for (int s = 0; s < 8; s++) ldsm(a[s], ab + (s >> 2) * 8192 + (((2 * (s & 3) + (lane >> 4)) ^ (lane & 7)) << 4));
    mbar_wait(bar0 + 8 * QB);
    float d[4][4] = {};
#pragma unroll
    for (int y = 0; y < 4; y++) {
      uint32_t bq[4];
      ldsm(bq, a_bq + 64 * y);
      mma16(d[(2 * y) & 3], a[2 * y], bq[0], bq[1]); mma16(d[(2 * y + 1) & 3], a[2 * y + 1], bq[2], bq[3]);
    }
    float r[2] = {((d[0][0] + d[0][1]) + (d[1][0] + d[1][1])) + ((d[2][0] + d[2][1]) + (d[3][0] + d[3][1])),
                  ((d[0][2] + d[0][3]) + (d[1][2] + d[1][3])) + ((d[2][2] + d[2][3]) + (d[3][2] + d[3][3]))};
    tred<1>(r, lane, 1);
    r[0] += __shfl_xor_sync(~0u, r[0], 2);
    const float nb = __shfl_xor_sync(~0u, r[0], 4);
    const uint32_t w0 = lane < 8 ? pack2t(r[0], nb, par) : pack2(r[0], nb);
    const uint32_t w1 = __shfl_down_sync(~0u, w0, 8), w2 = __shfl_down_sync(~0u, w0, 16), w3 = __shfl_down_sync(~0u, w0, 24);
    if (lane < 2) stx16(p_qa, make_uint4(w0, w1, w2, w3));
    arrive2(bar0 + 8 * (EB + 4), rsb + OFF_BAR + 8 * (EB + 4), lane == 0, lane == 0);
  }
  {
    if (warp) nbar_arrive(3, 256); else { nbar(3, 256); if (lane == 0) CNT_ADD(2 + (b >> 6)); }
    asm volatile("setmaxnreg.inc.sync.aligned.u32 216;");
    const unsigned* pq = g_qa + rk * 4096 + tid * 4;
    uint32_t a_q = sb + OFF_Q + ((tid & 63) >> 3) * 2048 + (tid >> 6) * 128 + (((tid & 7) ^ (tid >> 6)) << 4);
    PINL(pq); PIN(a_q);
    mbar_wait(bar0 + 8 * (XB + 1));
    uint4 v[4];
    POLL {
#pragma unroll
      for (int k = 0; k < 4; k++) v[k] = ldx16(pq + 1024 * k);
      RETRY(lop_x3(v[0].x, v[1].x, par) | lop_x3(v[2].x, v[3].x, par))
    }
#pragma unroll
    for (int k = 0; k < 4; k++)
      asm volatile("st.shared.v4.b32 [%0], {%1,%2,%3,%4};" ::"r"((a_q + k * 512) ^ ((k & 1) << 6)), "r"(v[k].x), "r"(v[k].y), "r"(v[k].z), "r"(v[k].w) : "memory");
    if (warp >= 4) nbar_arrive(1, 256); else nbar(1, 256);
  }
  sb = __shfl_sync(~0u, sb, 0); bar0 = sb + OFF_BAR;
  if (warp < 4) {
    uint32_t qf[32][4];
#pragma unroll
    for (int s = 0; s < 32; s++) ldsm(qf[s], sb + OFF_Q + (s >> 2) * 2048 + (lane & 15) * 128 + (((2 * (s & 3) + (lane >> 4)) ^ (lane & 7)) << 4));
    float l0 = 0.f, l1 = 0.f, m0 = -1e30f, m1 = -1e30f;
    const float sc = 0.08838834764831845f * 1.4426950408889634f;
    const uint32_t kofs = (16 * warp + 8 * (lane >> 4) + (lane & 7)) * 128 + ((((lane >> 3) & 1) ^ (lane & 7)) << 4);
    uint32_t st = sb;
#pragma unroll 1
    for (int t = 0; t < 8; t++) {
      float sa[4][4] = {};
#pragma unroll
      for (int hf = 0; hf < 2; hf++) {
        const int n = 2 * t + hf;
        mbar_wait(bar0 + 8 * (FB_KV + n));
        uint32_t kf[16][4];
#pragma unroll
        for (int y = 0; y < 16; y++) ldsm(kf[y], st + (y >> 2) * 8192 + (kofs ^ ((y & 3) << 5)));
#pragma unroll
        for (int y = 0; y < 16; y++) {
          mma16(sa[(2 * y) & 3], qf[16 * hf + y], kf[y][0], kf[y][1]); mma16(sa[((2 * y) & 3) + 1], qf[16 * hf + y], kf[y][2], kf[y][3]);
        }
        __syncwarp();
        arrive2(bar0 + 8 * (EB + NSLOT + n), rsb + OFF_BAR + 8 * (EB + NSLOT + n), lane == 0 && n < 14, lane == 0 && n < 16 - NSLOT);
        if (hf == 0) arrive2(bar0 + 8 * EB, 0, lane == 0 && t == 0, false);
        st = st + SLOT == sb + NSLOT * SLOT ? sb : st + SLOT;
      }
#pragma unroll
      for (int i = 0; i < 4; i++) { sa[0][i] = (sa[0][i] + sa[2][i]) * sc; sa[1][i] = (sa[1][i] + sa[3][i]) * sc; }
      float cm[2] = {fmaxf(fmaxf(sa[0][0], sa[0][1]), fmaxf(sa[1][0], sa[1][1])), fmaxf(fmaxf(sa[0][2], sa[0][3]), fmaxf(sa[1][2], sa[1][3]))};
      tmax<1>(cm, lane, 1);
      cm[0] = fmaxf(cm[0], __shfl_xor_sync(~0u, cm[0], 2));
      float* pm = s_sm + (t & 1) * 64;
      if (tq < 2) pm[(g + 8 * tq) * 4 + warp] = cm[0];
      if (t >= 2) nbar(6 + (t & 1), 256); else nbar(3, 128);
      const float4 a0 = *(const float4*)(pm + g * 4), b0 = *(const float4*)(pm + g * 4 + 32);
      const float n0 = fmaxf(fmaxf(fmaxf(a0.x, a0.y), fmaxf(a0.z, a0.w)), m0), n1 = fmaxf(fmaxf(fmaxf(b0.x, b0.y), fmaxf(b0.z, b0.w)), m1);
      uint32_t pk[4];
#pragma unroll
      for (int i = 0; i < 2; i++) { pk[2 * i] = pack2(ex2(sa[i][0] - n0), ex2(sa[i][1] - n0)); pk[2 * i + 1] = pack2(ex2(sa[i][2] - n1), ex2(sa[i][3] - n1)); }
      *(uint4*)(smem + OFF_P + (t & 1) * 2048 + tid * 16) = make_uint4(pk[0], pk[1], pk[2], pk[3]);
      const float al0 = ex2(m0 - n0), al1 = ex2(m1 - n1);
      if (tid < 32 && tq == 0) *(float2*)(s_sm + 192 + (t & 1) * 16 + 2 * g) = make_float2(al0, al1);
      nbar_arrive(4 + (t & 1), 256);
      m0 = n0; m1 = n1;
      l0 = l0 * al0 + (bflo(pk[0]) + bfhi(pk[0])) + (bflo(pk[2]) + bfhi(pk[2]));
      l1 = l1 * al1 + (bflo(pk[1]) + bfhi(pk[1])) + (bflo(pk[3]) + bfhi(pk[3]));
    }
    float lr[2] = {l0, l1};
    tred<1>(lr, lane, 1);
    lr[0] += __shfl_xor_sync(~0u, lr[0], 2);
    if (tq < 2) s_sm[128 + (g + 8 * tq) * 4 + warp] = lr[0];
    nbar(3, 128);
    if (warp == 0 && tq < 2) {
      const float4 a0 = *(const float4*)(s_sm + 128 + (g + 8 * tq) * 4);
      stx8(g_ml + (16 * rk + g + 8 * tq) * 64 + pr, make_uint2(fbits(tq ? m1 : m0), fbits((a0.x + a0.y) + (a0.z + a0.w))));
    }
    if (warp == 0) { __syncwarp(); if (lane == 0) CNT_ADD(96 + 32 * rk); }
    nbar(2, 288);
    if (tid == 0) asm volatile("red.relaxed.gpu.global.xor.b64 [%0], %1;" ::"l"(scr->cnt + 32 + 32 * rk), "l"(1ull << pr) : "memory");
  } else {
    float o[16][4] = {};
    const uint32_t vofs = (warp & 1) * 16384 + (lane & 15) * 128 + (((lane >> 4) ^ (lane & 7)) << 4);
    const int hf = (warp >> 1) & 1;
    uint32_t st = sb + hf * SLOT;
    auto pv = [&](const int t, auto np) {
      constexpr int npre = decltype(np)::value;
      uint32_t vf[4][8][4];
      const int n = 2 * t + hf;
      mbar_wait(bar0 + 8 * (FB_KV + n));
#pragma unroll
      for (int s = 0; s < npre; s++)
#pragma unroll
        for (int y = 0; y < 8; y++) ldsm_t(vf[s][y], st + (y >> 2) * 8192 + s * 2048 + (vofs ^ ((y & 3) << 5)));
      nbar(4 + (t & 1), 256);
      const float2 al = *(const float2*)(s_sm + 192 + (t & 1) * 16 + 2 * g);
      uint4 pf[4];
#pragma unroll
      for (int s = 0; s < 4; s++) pf[s] = *(const uint4*)(smem + OFF_P + (t & 1) * 2048 + s * 512 + lane * 16);
      if (t < 6) nbar_arrive(6 + (t & 1), 256);
#pragma unroll
      for (int s = npre; s < 4; s++)
#pragma unroll
        for (int y = 0; y < 8; y++) ldsm_t(vf[s][y], st + (y >> 2) * 8192 + s * 2048 + (vofs ^ ((y & 3) << 5)));
#pragma unroll
      for (int nt = 0; nt < 16; nt++) { o[nt][0] *= al.x; o[nt][1] *= al.x; o[nt][2] *= al.y; o[nt][3] *= al.y; }
#pragma unroll
      for (int s = 0; s < 4; s++) {
        const uint32_t pa[4] = {pf[s].x, pf[s].y, pf[s].z, pf[s].w};
#pragma unroll
        for (int y = 0; y < 8; y++) { mma16(o[2 * y], pa, vf[s][y][0], vf[s][y][1]); mma16(o[2 * y + 1], pa, vf[s][y][2], vf[s][y][3]); }
      }
      __syncwarp();
      arrive2(bar0 + 8 * (EB + NSLOT + n), rsb + OFF_BAR + 8 * (EB + NSLOT + n), lane == 0 && n < 14, lane == 0 && n < 16 - NSLOT);
      st = st + 2 * SLOT >= sb + NSLOT * SLOT ? st - (NSLOT - 2) * SLOT : st + 2 * SLOT;
    };
#pragma unroll 1
    for (int t = 0; t < 7; t++) pv(t, IC<NPRE0>());
    pv(7, IC<NPRE1>());
    uint4* po = g_xo + ((size_t)((16 * rk + (g & 6)) * 4 + warp - 4) * 64 + pr) * RS + (lane & 7);
    const bool odd = lane & 4;
#pragma unroll
    for (int e = 0; e < 2; e++)
#pragma unroll
      for (int j2 = 0; j2 < 2; j2++) {
        uint32_t c0[4], c1[4];
#pragma unroll
        for (int i = 0; i < 4; i++) {
          c0[i] = i ? pack2(o[8 * j2 + i][2 * e], o[8 * j2 + i][2 * e + 1]) : pack2t(o[8 * j2][2 * e], o[8 * j2][2 * e + 1], par);
          c1[i] = i ? pack2(o[8 * j2 + 4 + i][2 * e], o[8 * j2 + 4 + i][2 * e + 1]) : pack2t(o[8 * j2 + 4][2 * e], o[8 * j2 + 4][2 * e + 1], par);
          const uint32_t r = __shfl_xor_sync(~0u, odd ? c0[i] : c1[i], 4);
          if (odd) c0[i] = r; else c1[i] = r;
        }
        stx16(po + e * 8 * 4 * 64 * RS + 8 * j2, make_uint4(c0[0], c0[1], c0[2], c0[3]));
        stx16(po + (e * 8 + 1) * 4 * 64 * RS + 8 * j2, make_uint4(c1[0], c1[1], c1[2], c1[3]));
      }
    nbar_arrive(2, 288);
  }
  tail(smem, scr, x, out, par, epoch, warp);
}

static void launch(void* const* d_in, void* d_out) {
  static TMaps tms;
  static bool init = false;
  static void* scr = nullptr;
  if (!init) {
    void* fn = nullptr; cudaDriverEntryPointQueryResult qr;
    cudaGetDriverEntryPoint("cuTensorMapEncodeTiled", &fn, cudaEnableDefault, &qr);
    EncFn f = (EncFn)fn;
    const CUtensorMapSwizzle S32 = CU_TENSOR_MAP_SWIZZLE_32B, S64 = CU_TENSOR_MAP_SWIZZLE_64B, S128 = CU_TENSOR_MAP_SWIZZLE_128B;
    const CUtensorMapL2promotion P128 = CU_TENSOR_MAP_L2_PROMOTION_L2_128B, P256 = CU_TENSOR_MAP_L2_PROMOTION_L2_256B;
    enc3d(f, &tms.m[0], d_in[2], 64, 512, 64, 8192, 128, 64, 128, 1, S128, P128);
    enc3d(f, &tms.m[1], d_in[3], 64, 512, 64, 8192, 128, 64, 64, 2, S128, P256);
    enc3d(f, &tms.m[2], d_in[1], 64, SK, 8, 1024, 128, 64, 64, 2, S128, P256);
    enc3d(f, &tms.m[3], d_in[11], 3072, 256, 2, 6144, 256 * 6144, 16, 256, 2, S32, P128);
    enc3d(f, &tms.m[4], d_in[4], 64, 512, 64, 8192, 128, 64, 64, 2, S128, P256);
    enc3d(f, &tms.m[5], d_in[5], 512, 128, 32, 1024, 128 * 1024, 64, 128, 1, S128, P128);
    enc3d(f, &tms.m[6], d_in[7], 1792, 256, 2, 3584, 256 * 3584, 32, 256, 1, S64, P128);
    enc3d(f, &tms.m[7], d_in[8], 1792, 256, 2, 3584, 256 * 3584, 32, 256, 1, S64, P128);
    enc3d(f, &tms.m[8], d_in[9], 64, 1792, 8, 1024, 128, 64, 16, 8, S128, P256);
    cudaFuncSetAttribute(fused_kernel, cudaFuncAttributeMaxDynamicSharedMemorySize, SMEM_BYTES);
    cudaGetSymbolAddress(&scr, g_scr);
    init = true;
  }
  fused_kernel<<<NCTA, 384, SMEM_BYTES>>>((const bf16*)d_in[0], (const bf16*)d_in[10], (const bf16*)d_in[11], (bf16*)d_out, (Scratch*)scr, tms);
}

}

extern "C" void kernel_launch(void* const* d_in, const int* in_sizes, int n_in, void* d_out, int out_size) {
  static int big = -1;
  if (big < 0) big = v9::fits();
  if (big) v9::launch(d_in, d_out); else v8::launch(d_in, d_out);
}
```

```cpp
#include <cuda_runtime.h>
#include <cuda_bf16.h>
#include <cuda.h>
#include <stdint.h>
#include <stdio.h>
#include <stdlib.h>

typedef CUresult (*EncFn)(CUtensorMap*, CUtensorMapDataType, cuuint32_t, void*, const cuuint64_t*, const cuuint64_t*,
                          const cuuint32_t*, const cuuint32_t*, CUtensorMapInterleave, CUtensorMapSwizzle,
                          CUtensorMapL2promotion, CUtensorMapFloatOOBfill);

static void enc3d(EncFn fn, CUtensorMap* tm, void* p, uint64_t d0, uint64_t d1, uint64_t d2, uint64_t s1, uint64_t s2, uint32_t b0,
                  uint32_t b1, uint32_t b2, CUtensorMapSwizzle sw, CUtensorMapL2promotion pr) {
  cuuint64_t gd[3] = {d0, d1, d2}, gs[2] = {s1, s2};
  cuuint32_t bx[3] = {b0, b1, b2}, es[3] = {1, 1, 1};
  fn(tm, CU_TENSOR_MAP_DATA_TYPE_BFLOAT16, 3, p, gd, gs, bx, es, CU_TENSOR_MAP_INTERLEAVE_NONE, sw, pr, CU_TENSOR_MAP_FLOAT_OOB_FILL_NONE);
}

namespace v9 {
typedef __nv_bfloat16 bf16;
#define SK 32768
#define SPIN_MAX (1 << 20)
template <int N> struct IC { static constexpr int value = N; };

__device__ __forceinline__ uint32_t s2u(const void* p) { return (uint32_t)__cvta_generic_to_shared(p); }
__device__ __forceinline__ float bflo(uint32_t u) { return __uint_as_float(u << 16); }
__device__ __forceinline__ float bfhi(uint32_t u) { return __uint_as_float(u & 0xffff0000u); }
__device__ __forceinline__ float u2f(uint32_t u) { return __uint_as_float(u); }
__device__ __forceinline__ void fma8(float* acc, uint4 v, float s) {
  acc[0] += s * bflo(v.x); acc[1] += s * bfhi(v.x); acc[2] += s * bflo(v.y); acc[3] += s * bfhi(v.y);
  acc[4] += s * bflo(v.z); acc[5] += s * bfhi(v.z); acc[6] += s * bflo(v.w); acc[7] += s * bfhi(v.w);
}
__device__ __forceinline__ uint32_t pack2(float a, float b) {
  __nv_bfloat162 p = __floats2bfloat162_rn(a, b); return *(uint32_t*)&p;
}
__device__ __forceinline__ float bfr(float v) { return bfhi(pack2(v, v)); }
__device__ __forceinline__ float silu_bf(float c) { return bfr(__fdividef(c, 1.f + __expf(-c))); }
#define fbits(v) ((__float_as_uint(v) & ~1u) | par)
__device__ __forceinline__ uint32_t pack2t(float a, float b, unsigned par) {
  const uint32_t ua = ((__float_as_uint(a) + ((par ^ 1) << 16)) & 0xFFFE0000u) | (par << 16);
  return __byte_perm(ua, pack2(b, b), 0x7632);
}
__device__ __forceinline__ void nbar(int id, int n) { asm volatile("bar.sync %0, %1;" ::"r"(id), "r"(n) : "memory"); }
__device__ __forceinline__ void nbar_arrive(int id, int n) { asm volatile("bar.arrive %0, %1;" ::"r"(id), "r"(n) : "memory"); }
__device__ __forceinline__ uint4 ldc16(const void* p) {
  uint4 v; asm volatile("ld.relaxed.cta.global.v4.u32 {%0,%1,%2,%3}, [%4];" : "=r"(v.x), "=r"(v.y), "=r"(v.z), "=r"(v.w) : "l"(p) : "memory"); return v;
}
__device__ __forceinline__ unsigned ldc4(const void* p) {
  unsigned v; asm volatile("ld.relaxed.cta.global.u32 %0, [%1];" : "=r"(v) : "l"(p) : "memory"); return v;
}
__device__ __forceinline__ uint4 ldx16(const void* p) {
  uint4 v; asm volatile("ld.relaxed.gpu.global.v4.u32 {%0,%1,%2,%3}, [%4];" : "=r"(v.x), "=r"(v.y), "=r"(v.z), "=r"(v.w) : "l"(p) : "memory"); return v;
}
__device__ __forceinline__ unsigned ldx4(const void* p) {
  unsigned v; asm volatile("ld.relaxed.gpu.global.u32 %0, [%1];" : "=r"(v) : "l"(p) : "memory"); return v;
}
__device__ __forceinline__ unsigned long long ldx64(const void* p) {
  unsigned long long v; asm volatile("ld.relaxed.gpu.global.u64 %0, [%1];" : "=l"(v) : "l"(p) : "memory"); return v;
}
__device__ __forceinline__ void stx16(void* p, uint4 v) {
  asm volatile("st.relaxed.gpu.global.v4.u32 [%0], {%1,%2,%3,%4};" ::"l"(p), "r"(v.x), "r"(v.y), "r"(v.z), "r"(v.w) : "memory");
}
__device__ __forceinline__ void stx8(void* p, uint2 v) { asm volatile("st.relaxed.gpu.global.v2.u32 [%0], {%1,%2};" ::"l"(p), "r"(v.x), "r"(v.y) : "memory"); }
__device__ __forceinline__ void stx4(void* p, unsigned v) { asm volatile("st.relaxed.gpu.global.u32 [%0], %1;" ::"l"(p), "r"(v) : "memory"); }
__device__ __forceinline__ void pub4(void* p, unsigned v) { asm volatile("red.relaxed.gpu.global.xor.b32 [%0], %1;" ::"l"(p), "r"(v) : "memory"); }
__device__ __forceinline__ void pub8(void* p, unsigned lo, unsigned hi) {
  asm volatile("{.reg .b64 t; mov.b64 t, {%1, %2}; red.relaxed.gpu.global.xor.b64 [%0], t;}" ::"l"(p), "r"(lo), "r"(hi) : "memory");
}
__device__ __forceinline__ unsigned lop_x3(unsigned a, unsigned b, unsigned c) {
  unsigned d; asm("lop3.b32 %0, %1, %2, %3, 0x7E;" : "=r"(d) : "r"(a), "r"(b), "r"(c)); return d; }
__device__ __forceinline__ unsigned or3(unsigned a, unsigned b, unsigned c) {
  unsigned d; asm("lop3.b32 %0, %1, %2, %3, 0xFE;" : "=r"(d) : "r"(a), "r"(b), "r"(c)); return d; }
__device__ __forceinline__ unsigned and3(unsigned a, unsigned b, unsigned c) {
  unsigned d; asm("lop3.b32 %0, %1, %2, %3, 0x80;" : "=r"(d) : "r"(a), "r"(b), "r"(c)); return d; }
__device__ __forceinline__ unsigned dep16(const uint32_t* f) {
  unsigned d = 0;
#pragma unroll
  for (int i = 0; i < 8; i++) d = or3(d, f[8 * i], f[8 * i + 4]);
  return d;
}
__device__ __forceinline__ uint2 ldx8(const void* p) {
  uint2 v; asm volatile("{.reg .b64 t; ld.relaxed.gpu.global.b64 t, [%2]; mov.b64 {%0, %1}, t;}" : "=r"(v.x), "=r"(v.y) : "l"(p) : "memory"); return v;
}
__device__ __forceinline__ float lds4(uint32_t a) { float v; asm volatile("ld.shared.f32 %0, [%1];" : "=f"(v) : "r"(a) : "memory"); return v; }
__device__ __forceinline__ float shx(float v, int m) {
  float r; asm volatile("shfl.sync.bfly.b32 %0, %1, %2, 0x1f, 0xffffffff;" : "=f"(r) : "f"(v), "r"(m)); return r;
}
__device__ __forceinline__ uint32_t mbar_test(uint32_t bar, uint32_t ph) {
  uint32_t ok;
  asm volatile("{.reg .pred p; mbarrier.test_wait.parity.shared::cta.b64 p, [%1], %2; vote.sync.all.pred p, p, 0xffffffff; selp.u32 %0, 1, 0, p;}"
               : "=r"(ok) : "r"(bar), "r"(ph) : "memory");
  return ok;
}
#define X16(v) (lop_x3(v.x, v.y, par) | lop_x3(v.z, v.w, par))
#define RETRY(bad) if (!__any_sync(~0u, (bad) & 1) || ++it_ >= SPIN_MAX) break;
#define POLL _Pragma("unroll 1") for (int it_ = 0;;)
__device__ __forceinline__ void mbar_wait(uint32_t bar, uint32_t ph = 0) {
  asm volatile("{.reg .pred p; .reg .u32 n; mov.u32 n, 0;\n"
               "W%=: mbarrier.try_wait.parity.shared::cta.b64 p, [%0], %1; add.u32 n, n, 1; setp.lt.and.u32 p, n, 0x100000, !p; @p bra W%=;}"
               ::"r"(bar), "r"(ph) : "memory");
}
__device__ __forceinline__ float ex2(float v) { float r; asm("ex2.approx.ftz.f32 %0, %1;" : "=f"(r) : "f"(v)); return r; }
__device__ __forceinline__ float rcp(float v) { float r; asm("rcp.approx.ftz.f32 %0, %1;" : "=f"(r) : "f"(v)); return r; }
__device__ __forceinline__ void mma16(float* d, const uint32_t* a, uint32_t b0, uint32_t b1) {
  asm volatile("mma.sync.aligned.m16n8k16.row.col.f32.bf16.bf16.f32 {%0,%1,%2,%3}, {%4,%5,%6,%7}, {%8,%9}, {%0,%1,%2,%3};"
               : "+f"(d[0]), "+f"(d[1]), "+f"(d[2]), "+f"(d[3]) : "r"(a[0]), "r"(a[1]), "r"(a[2]), "r"(a[3]), "r"(b0), "r"(b1));
}
__device__ __forceinline__ void mma16c(float* d, const uint32_t* a, uint32_t b0, uint32_t b1, const float* c) {
  asm volatile("mma.sync.aligned.m16n8k16.row.col.f32.bf16.bf16.f32 {%0,%1,%2,%3}, {%4,%5,%6,%7}, {%8,%9}, {%10,%11,%12,%13};"
               : "=f"(d[0]), "=f"(d[1]), "=f"(d[2]), "=f"(d[3])
               : "r"(a[0]), "r"(a[1]), "r"(a[2]), "r"(a[3]), "r"(b0), "r"(b1), "f"(c[0]), "f"(c[1]), "f"(c[2]), "f"(c[3]));
}
__device__ __forceinline__ float4 lds16(uint32_t a) {
  float4 v; asm volatile("ld.shared.v4.f32 {%0,%1,%2,%3}, [%4];" : "=f"(v.x), "=f"(v.y), "=f"(v.z), "=f"(v.w) : "r"(a) : "memory"); return v;
}
__device__ __forceinline__ uint4 ldsv16(uint32_t a) {
  uint4 v; asm volatile("ld.relaxed.cluster.shared.v4.u32 {%0,%1,%2,%3}, [%4];" : "=r"(v.x), "=r"(v.y), "=r"(v.z), "=r"(v.w) : "r"(a) : "memory"); return v;
}
__device__ __forceinline__ void sts4(uint32_t a, float v) { asm volatile("st.shared.f32 [%0], %1;" ::"r"(a), "f"(v) : "memory"); }
__device__ __forceinline__ void sts16(uint32_t a, uint4 v) {
  asm volatile("st.shared.v4.b32 [%0], {%1,%2,%3,%4};" ::"r"(a), "r"(v.x), "r"(v.y), "r"(v.z), "r"(v.w) : "memory");
}
__device__ __forceinline__ void ldsm_t(uint32_t* r, uint32_t a) {
  asm volatile("ldmatrix.sync.aligned.m8n8.x4.trans.shared.b16 {%0,%1,%2,%3}, [%4];" : "=r"(r[0]), "=r"(r[1]), "=r"(r[2]), "=r"(r[3]) : "r"(a) : "memory");
}
__device__ __forceinline__ void ldsm(uint32_t* r, uint32_t a) {
  asm volatile("ldmatrix.sync.aligned.m8n8.x4.shared.b16 {%0,%1,%2,%3}, [%4];" : "=r"(r[0]), "=r"(r[1]), "=r"(r[2]), "=r"(r[3]) : "r"(a) : "memory");
}
__device__ __forceinline__ uint32_t mapa(uint32_t a, uint32_t r) {
  uint32_t v; asm volatile("mapa.shared::cluster.u32 %0, %1, %2;" : "=r"(v) : "r"(a), "r"(r)); return v;
}
__device__ __forceinline__ unsigned long long mapg(uint32_t a, uint32_t r) {
  unsigned long long v;
  asm volatile("{.reg .u32 t; .reg .u64 u; mapa.shared::cluster.u32 t, %1, %2; cvt.u64.u32 u, t; cvta.shared::cluster.u64 %0, u;}" : "=l"(v) : "r"(a), "r"(r));
  return v;
}
template <int N>
__device__ __forceinline__ void tred(float* a, int lane, int m) {
  const bool hi = lane & m;
#pragma unroll
  for (int i = 0; i < N; i++) {
    float send = hi ? a[i] : a[i + N], keep = hi ? a[i + N] : a[i];
    a[i] = keep + __shfl_xor_sync(~0u, send, m);
  }
}
template <int N>
__device__ __forceinline__ void tmax(float* a, int lane, int m) {
  const bool hi = lane & m;
#pragma unroll
  for (int i = 0; i < N; i++) {
    float send = hi ? a[i] : a[i + N], keep = hi ? a[i + N] : a[i];
    a[i] = fmaxf(keep, __shfl_xor_sync(~0u, send, m));
  }
}
__device__ __forceinline__ void arrive_n(uint32_t bar, bool on, int cnt) {
  asm volatile("{.reg .pred p; setp.ne.s32 p, %1, 0; @p mbarrier.arrive.shared::cta.b64 _, [%0], %2;}" ::"r"(bar), "r"((int)on), "r"(cnt) : "memory");
}
__device__ __forceinline__ unsigned long long stream_policy() {
  unsigned long long p;
  asm volatile("createpolicy.fractional.L2::evict_first.b64 %0, 1.0;" : "=l"(p));
  return p;
}
__device__ __forceinline__ void tma3d(uint32_t dst, const CUtensorMap* tm, uint32_t bar, int c0, int c1, int c2) {
  asm volatile("cp.async.bulk.tensor.3d.shared::cluster.global.mbarrier::complete_tx::bytes.L2::cache_hint [%0], [%1, {%3, %4, %5}], [%2], %6;"
               ::"r"(dst), "l"(tm), "r"(bar), "r"(c0), "r"(c1), "r"(c2), "l"(stream_policy()) : "memory");
}
__device__ __forceinline__ void spin_until(unsigned t) { while ((int)((unsigned)clock() - t) < 0) {} }
__device__ __forceinline__ void wait_until(unsigned t) {
  unsigned now;
  do { asm volatile("mov.u32 %0, %%globaltimer_lo;" : "=r"(now)); } while ((int)(now - t) < 0);
}
__device__ __forceinline__ void sleep_until(unsigned t) {
  unsigned now;
#pragma unroll 1
  do {
    __nanosleep(200);
    asm volatile("mov.u32 %0, %%globaltimer_lo;" : "=r"(now));
  } while ((int)(now - t) < 0);
}
#define PIN(x) asm volatile("" : "+r"(x))
#define PINL(x) asm volatile("" : "+l"(x))
#define BAR_ARRIVE(i) asm volatile("mbarrier.arrive.shared::cta.b64 _, [%0];" ::"r"(bar0 + 8 * (i)) : "memory")
#define LANE0(op, p, c, v) asm volatile("{.reg .pred q; setp.eq.s32 q, %2, 0; @q " op " [%0], %1;}" ::"l"((p) + lane), c(v), "r"(lane) : "memory")
#define CNT_ADD(c) LANE0("red.relaxed.gpu.global.add.u32", scr->cnt + (c), "r", 1)
#define BAR_INIT(i, cnt) asm volatile("mbarrier.init.shared::cta.b64 [%0], %1;" ::"r"(bar0 + 8 * (i)), "r"(cnt) : "memory")
#define BAR_ARM(i, bytes) asm volatile("mbarrier.arrive.expect_tx.shared::cta.b64 _, [%0], %1;" ::"r"(bar0 + 8 * (i)), "r"(bytes) : "memory")
struct TMaps { CUtensorMap m[9]; };

#define NCTA9 120
#define TAU 20
#define NSL 100
#define NPE 1
#define QN 4
#define FDLY 60
#define VJ 1
#define NPO 3
#define VDLY 150
#define O_Q 131072
#define O_LZ 163840
#define O_CTX 196608
#define O_HZ 198656
#define O_HW 200704
#define O_X 201728
#define O_P 218112
#define O_B 222208
#define O_R 224512
#define O_SILU 228608
#define O_SM 229632
#define O_BAR 231424
#define O_EP (O_BAR + 256)
#define O_DBG (O_EP + 16)
#define SMEM9 (O_DBG + 144)
#define B_FULL 0
#define B_FM 8
#define B_EMPTY 10
#define B_EM 18
#define B_LZ 18
#define B_Q2 19
#define B_H 20
#define B_QF 21
#define B_TAB 22
#define B_W 23
#define B_ST 24
#define B_HZ 25
#define B_WZ 26
#define B_G2 28
#define B_G 27
enum { T_WQ, T_WUK, T_KV, T_MOD, T_UV, T_WO, T_GU, T_DN = 8 };
#define NBIG 40
struct Sched { unsigned zero, dth; uint2 r[3][8]; unsigned nr[3], nt[3], dt, t4, d4, d6, wt, pad; };

struct __align__(128) Scratch {
  unsigned cnt[8 * 32];
  uint2 rec[32 * 4 * 8 * 64];
  uint2 hdr[32 * 16];
  unsigned h[8 * 256];
  uint4 qa[2048];
  unsigned xao[8 * 512];
  unsigned xab[8 * 256];
  unsigned xm[2048];
};
__device__ Scratch g_scr;
#define SMEM_BASE 1024u
#define DSC ((SMEM_BASE >> 4) | (1u << 16))
#define HI128 (64u | (1u << 30))
#define HI64 (32u | (2u << 30))
template <int TA, int TB, unsigned HIA, unsigned HIB>
__device__ __forceinline__ void wgmma32(float* d, uint32_t da, uint32_t db, int acc) {
  asm volatile("{.reg .pred p; .reg .b64 da, db; setp.ne.b32 p, %18, 0; mov.b64 da, {%16, %21}; mov.b64 db, {%17, %22};\n"
               "wgmma.mma_async.sync.aligned.m64n32k16.f32.bf16.bf16 "
               "{%0,%1,%2,%3,%4,%5,%6,%7,%8,%9,%10,%11,%12,%13,%14,%15}, da, db, p, 1, 1, %19, %20;}"
               : "+f"(d[0]), "+f"(d[1]), "+f"(d[2]), "+f"(d[3]), "+f"(d[4]), "+f"(d[5]), "+f"(d[6]), "+f"(d[7]),
                 "+f"(d[8]), "+f"(d[9]), "+f"(d[10]), "+f"(d[11]), "+f"(d[12]), "+f"(d[13]), "+f"(d[14]), "+f"(d[15])
               : "r"(da), "r"(db), "r"(acc), "n"(TA), "n"(TB), "n"(HIA), "n"(HIB));
}
__device__ __forceinline__ void wgmma32r(float* d, const uint32_t* a, uint32_t db) {
  asm volatile("{.reg .b64 db; mov.b64 db, {%20, %21};\n"
               "wgmma.mma_async.sync.aligned.m64n32k16.f32.bf16.bf16 "
               "{%0,%1,%2,%3,%4,%5,%6,%7,%8,%9,%10,%11,%12,%13,%14,%15}, {%16,%17,%18,%19}, db, 1, 1, 1, 1;}"
               : "+f"(d[0]), "+f"(d[1]), "+f"(d[2]), "+f"(d[3]), "+f"(d[4]), "+f"(d[5]), "+f"(d[6]), "+f"(d[7]),
                 "+f"(d[8]), "+f"(d[9]), "+f"(d[10]), "+f"(d[11]), "+f"(d[12]), "+f"(d[13]), "+f"(d[14]), "+f"(d[15])
               : "r"(a[0]), "r"(a[1]), "r"(a[2]), "r"(a[3]), "r"(db), "n"(HI64));
}
template <int N> __device__ __forceinline__ void wg_wait(float* a) {
  asm volatile("wgmma.wait_group.sync.aligned %16;"
               : "+f"(a[0]), "+f"(a[1]), "+f"(a[2]), "+f"(a[3]), "+f"(a[4]), "+f"(a[5]), "+f"(a[6]), "+f"(a[7]), "+f"(a[8]), "+f"(a[9]), "+f"(a[10]),
                 "+f"(a[11]), "+f"(a[12]), "+f"(a[13]), "+f"(a[14]), "+f"(a[15]) : "n"(N) : "memory");
}
__device__ __forceinline__ float sum8(uint32_t a) {
  const float4 p = lds16(a), q = lds16(a + 1024);
  return ((p.x + p.y) + (p.z + p.w)) + ((q.x + q.y) + (q.z + q.w));
}
__device__ __forceinline__ int posof(int c) { return (c & ~14) + 2 * (c & 6) + ((c >> 2) & 2); }

__global__ void __cluster_dims__(8, 1, 1) __launch_bounds__(384, 1)
fused_kernel(const bf16* __restrict__ x, const bf16* __restrict__ cvec, const bf16* __restrict__ w_mod, bf16* __restrict__ out,
             Scratch* __restrict__ scr, const __grid_constant__ Sched sch, const __grid_constant__ TMaps tms) {
  extern __shared__ __align__(1024) unsigned char smem[];
  const int tid = threadIdx.x, warp = __shfl_sync(~0u, tid >> 5, 0), lane = tid & 31;
  const int b = blockIdx.x, cl = b >> 3, rn = b & 7, rk = b & 1, hd = b >> 1, f = b - 64;
  const bool isA = b < 64;
  uint32_t sb = s2u(smem), bar0 = sb + O_BAR;
  unsigned gt_start;
  asm volatile("mov.u32 %0, %%globaltimer_lo;" : "=r"(gt_start));
  const int g = lane >> 2, tq = lane & 3;
  const int arow = 64 * rn + ((tid & 255) >> 4);
  uint4 wm[4];
  uint32_t cw, xw;
  if (warp < 8 && isA) {
    const bf16* wa = w_mod + (size_t)arow * 3072 + (lane & 8) * 64 + 64 * cl + 8 * (lane & 7);
#pragma unroll
    for (int i = 0; i < 4; i++) wm[i] = ldx16(wa + i * 16 * 3072);
    cw = ldc4(cvec + (arow & ~1) + 16 * tq);
    if (warp < 2) xw = ldc4(x + 64 * cl + (tid & 62));
  }
  if (warp == 11) {
    if (lane == 0) {
#pragma unroll
      for (int i = 0; i < B_EMPTY; i++) BAR_INIT(i, 1);
    }
    __syncwarp();
    asm volatile("fence.mbarrier_init.release.cluster;" ::: "memory");
    asm volatile("barrier.cluster.arrive.relaxed.aligned;" ::: "memory");
    if (isA) {
#pragma unroll 1
      for (int i = 0; i < 8; i++) {
        if (i >= 6) mbar_wait(bar0 + 8 * (i - 6));
        wait_until(gt_start + ((64 * i + b) * sch.dth >> 8));
        if (lane == 0) {
          BAR_ARM(i, 16384);
          tma3d(sb + i * 16384, &tms.m[i >> 2], bar0 + 8 * i, 0, i < 4 ? 128 * i : 256 * rk + 64 * (i - 4), i < 4 ? b : b & ~1);
        }
        __syncwarp();
      }
    }
  }
  if (warp == 10) {
    const unsigned ep = ldc4(&scr->cnt[0]);
    if (isA) {
      const uint4 xa = ldc16(x + 16 * lane), xb = ldc16(x + 16 * lane + 8);
      float xv[16] = {bflo(xa.x), bfhi(xa.x), bflo(xa.y), bfhi(xa.y), bflo(xa.z), bfhi(xa.z), bflo(xa.w), bfhi(xa.w),
                      bflo(xb.x), bfhi(xb.x), bflo(xb.y), bfhi(xb.y), bflo(xb.z), bfhi(xb.z), bflo(xb.w), bfhi(xb.w)};
      const float x0 = __shfl_sync(~0u, xv[0], 0);
      float s = 0, q = 0;
#pragma unroll
      for (int i = 0; i < 16; i++) { xv[i] -= x0; s += xv[i]; q += xv[i] * xv[i]; }
#pragma unroll
      for (int o = 16; o; o >>= 1) { s += __shfl_xor_sync(~0u, s, o); q += __shfl_xor_sync(~0u, q, o); }
      s *= 1.f / 512.f;
      float rstd;
      asm("rsqrt.approx.ftz.f32 %0, %1;" : "=f"(rstd) : "f"(fmaxf(q * (1.f / 512.f) - s * s, 0.f) + 1e-5f));
      *(float2*)(smem + O_SM + 1024) = make_float2(s + x0, rstd);
    }
    if (lane == 0) *(volatile unsigned*)(smem + O_EP) = ep;
    nbar_arrive(1, 288);
  }
  const int cls = isA ? (b >= NBIG) : 2, v0 = isA ? 2 : 0;
  if (warp >= 8) {
    asm volatile("setmaxnreg.dec.sync.aligned.u32 56;");
    if (warp == 8) {
      if (lane < 8) asm volatile("prefetch.tensormap [%0];" ::"l"(&tms.m[lane + 1]) : "memory");
      if ((sb & 0xFFFFFF) != SMEM_BASE) __trap();
    } else if (warp == 9) {
      if (lane == 0) {
#pragma unroll
        for (int i = B_EMPTY; i < B_EM; i++) BAR_INIT(i, 8);
        BAR_INIT(B_LZ, 8); BAR_INIT(B_Q2, 9); BAR_ARM(B_Q2, 1024);
        BAR_INIT(B_H, 1); BAR_INIT(B_QF, 1); BAR_ARM(B_QF, 32768);
        BAR_INIT(B_TAB, 1); BAR_INIT(B_W, 1); BAR_INIT(B_ST, 8); BAR_INIT(B_WZ, 1); BAR_INIT(B_G, 1); BAR_INIT(B_G2, 1);
      }

    }
    if (warp != 11) {
      __syncwarp();
      asm volatile("fence.mbarrier_init.release.cluster;" ::: "memory");
      __threadfence_block();
      asm volatile("barrier.cluster.arrive.relaxed.aligned;" ::: "memory");
    }
    asm volatile("barrier.cluster.wait.acquire.aligned;" ::: "memory");
    if (warp == 8) {
      const int nr = sch.nr[cls], vl = v0 + sch.nt[cls] - 1;
      unsigned long long hist = 0;
      int v = v0;
#pragma unroll 1
      for (int rd = 0; rd < nr; rd++) {
        const uint2 e = sch.r[cls][rd];
        const int type = e.y & 15, win = (e.y >> 4) & 15, pos = b + 64 - (int)((e.y >> 8) & 255), tile = e.y >> 16;
        const bool mod = type == T_MOD;
        const int ni = mod ? 1 : type == T_DN ? 2 : 4;
        unsigned t = gt_start + (e.x & 0xffff) + (pos * sch.dt >> 8);
        const int c0 = mod ? 1024 + 32 * b : type == T_WO || type == T_DN ? 64 * rn : type == T_GU ? 32 * f : 0;
        int c1 = type == T_KV ? 64 * (tile + pos) : 0;
        int c2 = mod ? tile : type == T_WO ? 4 * cl : type == T_DN ? 2 * cl - 16 : type == T_UV ? b : 0;
        const int i1 = type == T_UV ? 128 : 0;
#pragma unroll 1
        for (int j = 0; j < ni; j++) {
          const int slot = mod ? B_FM + tile : (v & 1) * 4 + j;
          if (mod ? tile : v >= 2) mbar_wait(bar0 + 8 * (B_EMPTY + (mod ? (vl & 1) * 4 : slot)), mod ? (vl >> 1) & 1 : ((v >> 1) - 1) & 1);
          const int hw = (int)(hist >> (6 * (win - 1))) & 63;
          if (hw) mbar_wait(bar0 + 8 * (hw & 15), (hw >> 4) & 1);
          wait_until(t);
          if (lane == 0) {
            BAR_ARM(slot, 16384);
            tma3d(sb + (mod ? (tile ? O_Q : O_X) : slot * 16384), &tms.m[type == T_GU ? type + (j & 1) : type], bar0 + 8 * slot, c0, c1, c2);
          }
          __syncwarp();
          hist = hist << 6 | (32 | (mod ? 0 : (v & 2) << 3) | slot);
          t += e.x >> 16; c1 += i1;
          c2 += type == T_KV ? 2 : type == T_WO || type == T_DN ? 1 : type == T_GU ? j & 1 : 0;
        }
        v += !mod;
      }
      return;
    }
    const unsigned epoch = *(volatile unsigned*)(smem + O_EP), par = (epoch + 1) & 1;
    if (warp == 10) {
      if (isA) {
        for (int it = 0; ldx4(scr->cnt + 1) != (epoch + 1) * 128 && it < SPIN_MAX; it++) {}
        if (lane == 0) BAR_ARRIVE(B_H);
      } else mbar_wait(bar0);
      if (!(rn & (QN - 1))) {
        for (int it = 0; ldx4(scr->cnt + 32 + 32 * (rn >> 2)) != (epoch + 1) * 32 && it < SPIN_MAX; it++) {}
        if (lane == 0)
          asm volatile("cp.async.bulk.shared::cluster.global.mbarrier::complete_tx::bytes.multicast::cluster [%0], [%1], %4, [%2], %3;"
                       ::"r"(sb + O_Q + rn * 4096), "l"(scr->qa + rn * 256), "r"(bar0 + 8 * B_QF), "h"((unsigned short)0xff), "n"(4096 * QN) : "memory");
      }
      const unsigned dl = isA ? sch.d4 : sch.d6;
      unsigned tw = gt_start + sch.t4;
      if (!isA) {
        const int nt = sch.nt[2];
#pragma unroll 1
        for (int t = 0; t < nt; t++) mbar_wait(bar0 + 8 * B_EMPTY + (t & 1) * 32, (t >> 1) & 1);
        unsigned long long now;
        asm volatile("mov.u64 %0, %%globaltimer;" : "=l"(now));
        LANE0("red.relaxed.gpu.global.max.u64", scr->cnt + 130, "l", now);
        CNT_ADD(128);
        tw = (unsigned)now + 1700;
      }
      sleep_until(tw);
      uint4 an;
      for (int it = 0; an = ldx16(scr->cnt + 128), an.x != (epoch + 1) * 56 && it < SPIN_MAX; it++) {}
      wait_until(an.z + (dl >> 16));
      if (lane == 0) BAR_ARRIVE(B_G2);
      wait_until(an.z + (dl & 0xffff));
      if (lane == 0) BAR_ARRIVE(B_G);
    } else if (warp == 11) {
      {
        uint2* ph = scr->hdr + ((lane & 24) + 2 * tq + (g & 1)) * 16 + cl;
        const bool own = (lane >> 4) * 4 + tq == rn;
        if (own) { stx8(ph, make_uint2(par ^ 1, 0)); if (cl == 14) stx8(ph + 1, make_uint2(0, 0)); }
        uint32_t a_w = sb + O_HW + ((lane >> 4) * 4 + tq) * 128 + (g & 1) * 64 + ((lane >> 1) & 4);
        PIN(a_w); PINL(ph);
        const int vt = v0 + sch.nt[cls];
#pragma unroll 1
        for (int t = 0; t < vt; t++) mbar_wait(bar0 + 8 * B_EMPTY + (t & 1) * 32, (t >> 1) & 1);
        float hz[8], M;
        uint32_t wp[4];
#pragma unroll 1
        for (int e = 0; e < 2; e++) {
          POLL {
            unsigned ok = 1;
#pragma unroll
            for (int u = 0; u < 8; u++)
              asm volatile("ld.relaxed.cluster.shared.f32 %0, [%1];" : "=f"(hz[u]) : "r"(sb + O_HZ + e * 1024 + u * 128 + lane * 4) : "memory");
#pragma unroll
            for (int u = 0; u < 4; u++) ok = and3(ok, __float_as_uint(hz[u]), __float_as_uint(hz[u + 4]));
            RETRY(~ok)
          }
          if (e) break;
          M = fmaxf(fmaxf(fmaxf(hz[0], hz[1]), fmaxf(hz[2], hz[3])), fmaxf(fmaxf(hz[4], hz[5]), fmaxf(hz[6], hz[7])));
          M = u2f(fbits(M));
#pragma unroll
          for (int u = 0; u < 4; u++) {
            wp[u] = pack2(ex2(hz[u] - M), ex2(hz[u + 4] - M));
            sts4(a_w + ((rn - u) & 3) * 8, u2f(wp[u])); sts4(a_w + ((rn - u) & 3) * 8 + 32, u2f(wp[u]));
          }
          __syncwarp();
          if (lane == 0) BAR_ARRIVE(B_WZ);
        }
        float L = 0.f;
#pragma unroll
        for (int u = 0; u < 4; u++) L += bflo(wp[u]) * hz[u] + bfhi(wp[u]) * hz[u + 4];
        if (own) pub8(ph, __float_as_uint(M) | 1u, __float_as_uint(L));
      }
      if (isA) {
        mbar_wait(bar0 + 8 * B_G2);
        unsigned long long hh;
        POLL { hh = ldx64(scr->hdr + hd * 16 + (lane & 15)); RETRY((lane & 15) == 15 ? 0u : (unsigned)hh ^ par) }
        const float m = (lane & 15) == 15 ? -1e30f : u2f((unsigned)hh);
        int mi = __float_as_int(m);
        mi ^= (mi >> 31) & 0x7fffffff;
        mi = __reduce_max_sync(~0u, mi);
        mi ^= (mi >> 31) & 0x7fffffff;
        const float w = ex2(m - __int_as_float(mi));
        float L = w * u2f(hh >> 32);
#pragma unroll
        for (int o2 = 8; o2; o2 >>= 1) L += __shfl_xor_sync(~0u, L, o2);
        sts4(sb + O_SM + (384 + 2 * (lane & 6) + ((lane >> 2) & 2) + (lane & 1)) * 4, w * rcp(L));
        __syncwarp();
        if (lane == 0) BAR_ARRIVE(B_W);
      }
    } else {
#pragma unroll 4
      for (int i = 0; i < 72; i++) sts16(sb + O_LZ + i * 512 + lane * 16, make_uint4(0, 0, 0, 0));
      __syncwarp();
      if (lane < 8) asm volatile("mbarrier.arrive.release.cluster.shared::cluster.b64 _, [%0];" ::"r"(mapa(bar0 + 8 * B_LZ, lane)) : "memory");
      if (isA) {
        mbar_wait(bar0 + 8 * B_QF);
#pragma unroll 2
        for (int k = 0; k < 8; k++) {
          const uint32_t cp = ldc4(cvec + 2 * (lane + 32 * k));
          *(uint32_t*)(smem + O_SILU + (lane + 32 * k) * 4) = pack2(silu_bf(bflo(cp)), silu_bf(bfhi(cp)));
        }
        __syncwarp();
        uint32_t ab = sb + O_X + (8 * (lane >> 4) + (lane & 7)) * 64 + ((((lane >> 3) & 1) ^ ((lane >> 1) & 3)) << 4);
        float d[4][4] = {};
#pragma unroll 1
        for (int jm = 0; jm < 2; jm++) {
          mbar_wait(bar0 + 8 * (B_FM + jm));
#pragma unroll 2
          for (int s2 = 0; s2 < 8; s2++)
#pragma unroll
            for (int s = 0; s < 2; s++) {
              uint32_t a0[4], a1[4];
              const uint32_t* ps = (const uint32_t*)(smem + O_SILU) + 128 * jm + 16 * s2 + 8 * s + tq;
              ldsm_t(a0, ab + (2 * s2 + s) * 1024); ldsm_t(a1, (ab + (2 * s2 + s) * 1024) ^ 32);
              mma16(d[s], a0, ps[0], ps[4]); mma16(d[2 + s], a1, ps[0], ps[4]);
            }
          ab -= O_X - O_Q;
        }
        const float t0 = (tq & 1) ? d[0][2] + d[1][2] : d[0][0] + d[1][0], t1 = (tq & 1) ? d[2][2] + d[3][2] : d[2][0] + d[3][0];
        stx4(scr->xm + b * 32 + posof(8 * tq + g), fbits(bfr(bfr((tq & 2) ? t1 : t0) + ((b >> 4) == 2 ? 1.f : 0.f))));
        __syncwarp();
        CNT_ADD(96);
      } else sleep_until(gt_start + sch.t4);
      for (int it = 0; ldx4(scr->cnt + 96) != (epoch + 1) * 64 && it < SPIN_MAX; it++) __nanosleep(NSL);
      if (isA) {
        unsigned long long ga;
        POLL { ga = ldx64(scr->xm + 64 * rn + 2 * lane); RETRY(lop_x3((unsigned)ga, ga >> 32, par)) }
        *(float2*)(smem + O_SM + (320 + 2 * lane) * 4) = make_float2(bfhi((unsigned)ga), bfhi(ga >> 32));
      }
      __syncwarp();
      if (lane == 0) BAR_ARRIVE(B_TAB);
    }
    return;
  }

  float* s_sm = (float*)(smem + O_SM);
  unsigned par, epoch;
  asm volatile("barrier.cluster.arrive.relaxed.aligned;" ::: "memory");
  if (isA) {
    float* s_r = (float*)(smem + O_R);
    float acc[8] = {0, 0, 0, 0, 0, 0, 0, 0};
    const float sl = silu_bf((arow & 1) ? bfhi(cw) : bflo(cw));
#pragma unroll
    for (int i = 0; i < 4; i++) fma8(acc, wm[i], __shfl_sync(~0u, sl, i, 4));
    tred<4>(acc, lane, 16);
    *(float4*)(s_r + warp * 128 + 8 * (lane & 15) + ((lane >> 2) & 4)) = make_float4(acc[0], acc[1], acc[2], acc[3]);
    nbar(1, 288);
    epoch = *(volatile unsigned*)(smem + O_EP);
    par = (epoch + 1) & 1;
    if (warp < 2) {
      float t = 0.f, ca = rn == 0 ? 1.f : 0.f;
#pragma unroll
      for (int w = 0; w < 8; w++) { t += s_r[w * 128 + tid]; ca += s_r[w * 128 + 64 + tid]; }
      t += ca * ((((tid & 1) ? bfhi(xw) : bflo(xw)) - s_sm[256]) * s_sm[257]);
      const float nb = __shfl_down_sync(~0u, t, 1);
      const uint32_t w0 = lane < 8 ? pack2t(t, nb, par) : pack2(t, nb);
      const uint32_t w1 = __shfl_down_sync(~0u, w0, 8), w2 = __shfl_down_sync(~0u, w0, 16), w3 = __shfl_down_sync(~0u, w0, 24);
      if (lane < 8 && !(lane & 1)) stx16(scr->h + (rn >> 1) * 512 + (2 * cl + warp) * 32 + rk * 16 + 2 * lane, make_uint4(w0, w1, w2, w3));
      __syncwarp();
      CNT_ADD(1);
    }
    asm volatile("barrier.cluster.wait.acquire.aligned;" ::: "memory");
    const uint32_t rsb = mapa(sb, rn ^ 1);
    {
      uint32_t a[4][4][4];
      mbar_wait(bar0 + 8 * (warp >> 1));
      const uint32_t ab = sb + (64 * warp + 8 * (lane >> 4) + (lane & 7)) * 128;
#pragma unroll
      for (int s = 0; s < 4; s++)
#pragma unroll
        for (int mt = 0; mt < 4; mt++) ldsm_t(a[s][mt], ab + s * 2048 + (((2 * mt + ((lane >> 3) & 1)) ^ (lane & 7)) << 4));
      arrive_n(bar0 + 8 * (B_EMPTY + (warp >> 1)), lane == 0, 4 + (dep16(&a[0][0][0]) & sch.zero));
      uint4 v0, v1;
      const unsigned* ph = scr->h + (g >> 1) * 512 + 64 * warp + 4 * (lane & 7);
      uint32_t off = O_B + warp * 272 + (32 * rk + 8 * tq + (lane & 4)) * 4;
      PIN(off); PINL(ph);
      mbar_wait(bar0 + 8 * B_H);
      POLL { v0 = ldx16(ph); v1 = ldx16(ph + 32); RETRY(lop_x3(v0.x, v1.x, par)) }
      float d[4][4] = {};
#pragma unroll
      for (int mt = 0; mt < 4; mt++) {
        mma16(d[mt], a[0][mt], v0.x, v0.y); mma16(d[mt], a[1][mt], v0.z, v0.w);
        mma16(d[mt], a[2][mt], v1.x, v1.y); mma16(d[mt], a[3][mt], v1.z, v1.w);
      }
      float r[8];
#pragma unroll
      for (int mt = 0; mt < 4; mt++) { r[2 * mt] = d[mt][0] + d[mt][1]; r[2 * mt + 1] = d[mt][2] + d[mt][3]; }
      tred<4>(r, lane, 2); tred<2>(r, lane, 1);
      const float rc = __shfl_xor_sync(~0u, (lane & 4) ? r[0] : r[1], 4);
      const uint32_t wd = (lane & 4) ? pack2(rc, r[1]) : pack2(r[0], rc);
      const uint32_t w1 = __shfl_down_sync(~0u, wd, 8), w2 = __shfl_down_sync(~0u, wd, 16), w3 = __shfl_down_sync(~0u, wd, 24);
      asm volatile("{.reg .pred p; setp.lt.s32 p, %7, 8; @p st.shared.v4.b32 [%0], {%2,%3,%4,%5};\n"
                   "@p st.async.shared::cluster.mbarrier::complete_tx::bytes.v4.b32 [%1], {%2,%3,%4,%5}, [%6];}"
                   ::"r"(sb + off), "r"(rsb + off), "r"(wd), "r"(w1), "r"(w2), "r"(w3), "r"(rsb + O_BAR + 8 * B_Q2), "r"(lane) : "memory");
      __syncwarp();
      arrive_n(bar0 + 8 * B_Q2, lane == 0, 1);
    }
    {
      uint32_t a[2][8][4];
      uint32_t a_bq = sb + O_B + (lane & 7) * 272 + (lane >> 3) * 16;
      uint4* p_qa = scr->qa + (4 * rk + (warp >> 1)) * 256 + hd * 8 + ((4 * (warp & 1) + tq) ^ (hd & 7));
      PIN(a_bq); PINL(p_qa);
      mbar_wait(bar0 + 8 * (4 + (warp >> 1)));
      const uint32_t ab = sb + 65536 + (warp >> 1) * 16384 + (32 * (warp & 1) + (lane & 15)) * 128;
#pragma unroll
      for (int i = 0; i < 16; i++) ldsm(a[i >> 3][i & 7], ab + (i >> 3) * 2048 + ((i >> 2) & 1) * 8192 + (((2 * (i & 3) + (lane >> 4)) ^ (lane & 7)) << 4));
      arrive_n(bar0 + 8 * (B_EMPTY + 4 + (warp >> 1)), lane == 0, 4 + (dep16(&a[0][0][0]) & sch.zero));
      mbar_wait(bar0 + 8 * B_Q2);
      float d[4][4] = {};
#pragma unroll
      for (int y = 0; y < 4; y++) {
        uint32_t bq[4];
        ldsm(bq, a_bq + 64 * y);
#pragma unroll
        for (int mt = 0; mt < 2; mt++) { mma16(d[2 * mt], a[mt][2 * y], bq[0], bq[1]); mma16(d[2 * mt + 1], a[mt][2 * y + 1], bq[2], bq[3]); }
      }
      float r[4];
#pragma unroll
      for (int i = 0; i < 4; i++) r[i] = (d[i & 2][2 * (i & 1)] + d[i & 2][2 * (i & 1) + 1]) + (d[(i & 2) + 1][2 * (i & 1)] + d[(i & 2) + 1][2 * (i & 1) + 1]);
      tred<2>(r, lane, 2); tred<1>(r, lane, 1);
      const float nb = __shfl_xor_sync(~0u, r[0], 4);
      const uint32_t w0 = (lane >> 3) == (hd & 3) ? pack2t(r[0], nb, par) : pack2(r[0], nb);
      const uint32_t w1 = __shfl_down_sync(~0u, w0, 8), w2 = __shfl_down_sync(~0u, w0, 16), w3 = __shfl_down_sync(~0u, w0, 24);
      if (lane < 4) stx16(p_qa, make_uint4(w0, w1, w2, w3));
      if (warp) nbar_arrive(3, 256); else { nbar(3, 256); CNT_ADD(32 + 32 * rk); }
    }
  } else {
    nbar(1, 288);
    epoch = *(volatile unsigned*)(smem + O_EP);
    par = (epoch + 1) & 1;
    asm volatile("barrier.cluster.wait.acquire.aligned;" ::: "memory");
    mbar_wait(bar0);
  }
  asm volatile("setmaxnreg.inc.sync.aligned.u32 224;");
  uint2* p_rec = scr->rec + ((16 * (warp >> 2) + 2 * (warp & 3) + (g & 1) + 4 * (tq & 2)) * 32 + 4 * rn + (tq & 1)) * 64 + cl * 4 + (g >> 1);
  PINL(p_rec);
  {
    const unsigned inv = par ^ 1;
#pragma unroll
    for (int q = 0; q < 2; q++) { stx8(p_rec + q * 128, make_uint2(inv, 0)); if (cl == 14) stx8(p_rec + q * 128 + 4, make_uint2(0, 0)); }
    if (isA) { if (warp < 2) { stx4(scr->xao + b * 64 + tid, inv); stx4(scr->xab + cl * 256 + (2 * (rn & 3) + warp) * 32 + (rn >> 2) * 16 + (lane >> 1), inv); } }
    else if (f == 0) { stx4(out + 2 * tid, 0); __threadfence(); }
  }
  sb = __shfl_sync(~0u, sb, 0); bar0 = sb + O_BAR;
  const int nt = sch.nt[cls], wg = warp >> 2;
  uint32_t a_z[4];
#pragma unroll
  for (int u = 0; u < 4; u++) {
    const int s3 = (rn - u - (lane >> 1 & 1)) & 3;
    a_z[u] = sb + O_LZ + (s3 + 4 * (lane & 1)) * 4096 + wg * 512 + g * 64 + (((warp & 3) ^ (s3 & 1) ^ (2 * (lane & 1))) << 4);
    PIN(a_z[u]);
  }
  uint32_t z[4][4], a_w = sb + O_HW + warp * 128 + (g & 1) * 64 + (tq & 1) * 8;
  PIN(a_w);
  {
    const float sc = 0.08838834764831845f * 1.4426950408889634f;
    float mrun = -1e30f;
    float o[4][16], sx[16], mref[8];
#pragma unroll
    for (int k = 0; k < 16; k++) { o[0][k] = o[1][k] = o[2][k] = o[3][k] = sx[k] = 0.f; mref[k >> 1] = -1e30f; }
    const int key = 16 * warp + (lane & 15);
    uint32_t a_p = sb + O_P + key * 64 + (((lane >> 4) ^ ((key >> 1) & 3)) << 4);
    uint32_t a_v = sb + wg * 32768 + (8 * (lane >> 4) + (lane & 7)) * 128 + (((2 * (warp & 3) + ((lane >> 3) & 1)) ^ (lane & 7)) << 4);
    const int rot = rn + warp;
    unsigned long long dst[4];
#pragma unroll
    for (int q = 0; q < 4; q++) {
      dst[q] = mapg(sb + O_LZ + rn * 4096 + (warp & 3) * 1024 + g * 64 + ((tq ^ (rn & 1) ^ ((rn >> 1) & 2)) << 4), 4 * wg + ((q + rot) & 3));
      PINL(dst[q]);
    }
    unsigned long long a_h = mapg(sb + O_HZ + wg * 1024 + rn * 128 + lane * 4, 2 * (warp & 3));
    unsigned long long a_h1 = mapg(sb + O_HZ + wg * 1024 + rn * 128 + lane * 4, 2 * (warp & 3) + 1);
    PIN(a_p); PIN(a_v); PINL(a_h); PINL(a_h1);
    uint32_t rel = lane < 4 && lane >= 2 * wg ? 2 - (tq >> 1) : 0;
    PIN(rel);
    uint32_t ones[4] = {0x3F803F80u, 0x3F803F80u, 0x3F803F80u, 0x3F803F80u};
    PIN(ones[0]); PIN(ones[1]); PIN(ones[2]); PIN(ones[3]);
    {
      asm volatile("{.reg .pred p; .reg .u32 n; mov.u32 n, 0;\n"
                   "W%=: mbarrier.try_wait.parity.acquire.cluster.shared::cta.b64 p, [%0], 0; add.u32 n, n, 1; setp.lt.and.u32 p, n, 0x100000, !p; @p bra W%=;}"
                   ::"r"(bar0 + 8 * B_LZ) : "memory");
      mbar_wait(bar0 + 8 * B_QF);
      unsigned bad = 0;
#pragma unroll
      for (int k = 0; k < 8; k++) bad |= __float_as_uint(lds4(sb + O_Q + k * 4096 + tid * 16 + (lane >> 3) * 4)) ^ par;
      if (__builtin_expect(__any_sync(~0u, bad & 1), 0)) {
#pragma unroll 1
        for (int k = 0; k < 8; k++) {
          uint4 v;
          POLL { v = ldx16(scr->qa + k * 256 + tid); RETRY(((lane & 16) ? ((lane & 8) ? v.w : v.z) : ((lane & 8) ? v.y : v.x)) ^ par) }
          sts16(sb + O_Q + k * 4096 + tid * 16, v);
        }
        asm volatile("fence.proxy.async.shared::cta;" ::: "memory");
      }
      if (warp >= 4) nbar_arrive(1, 256); else nbar(1, 256);
    }
#pragma unroll 1
    for (int t = 0; t < nt; t++) {
      const int v = v0 + t;
      const uint32_t fb = bar0 + (v & 1) * 32, ph = (v >> 1) & 1, av = a_v + (v & 1) * 65536;
      uint32_t vf[4][4][4], cnt;
      auto landed = [&]() {
        cnt = rel + (dep16(&vf[0][0][0]) & (nt >> 8));
        PIN(cnt);
      };
      if (wg == 0) {
        const uint32_t da = DSC + (v & 1) * 4096, db = DSC + O_Q / 16;
#pragma unroll 1
        for (int j = 0; j < 4; j++) {
          mbar_wait(fb + 8 * j, ph);
          asm volatile("wgmma.fence.sync.aligned;" ::: "memory");
#pragma unroll
          for (int k = 0; k < 8; k++)
            wgmma32<0, 0, HI128, HI128>(sx, da + j * 1024 + (k >> 2) * 512 + (k & 3) * 2, db + j * 512 + (k >> 2) * 256 + (k & 3) * 2, k ? 1 : j);
          asm volatile("wgmma.commit_group.sync.aligned;" ::: "memory");
          if (j == VJ) {
#pragma unroll
            for (int i = 0; i < 16; i++) ldsm_t(vf[i >> 2][i & 3], av + (((i >> 2) + rot) & 3) * 8192 + (i & 3) * 2048);
            nbar(5, 256);
            landed();
          }
        }
      } else {
        nbar_arrive(5, 256);
#pragma unroll 1
        for (int j = 0; j < 2; j++) {
          mbar_wait(fb + 16 + 8 * j, ph);
          if (j) spin_until(clock() + VDLY);
#pragma unroll
          for (int q = 0; q < 4; q++)
            if (((q + rot) & 2) == 2 * j)
#pragma unroll
              for (int k = 0; k < 4; k++) ldsm_t(vf[q][k], av + ((q + rot) & 3) * 8192 + k * 2048);
        }
        cnt = 0;
      }
      wg_wait<0>(sx);
      asm volatile("{.reg .pred p; setp.ne.s32 p, %1, 0; @p mbarrier.arrive.shared::cta.b64 _, [%0], %1;}" ::"r"(fb + 8 * B_EMPTY + 8 * tq), "r"(cnt) : "memory");
#pragma unroll 1
      for (int pass = 0;; pass++) {
        int ex = !(t | pass);
        if (wg == 0 && (t | pass)) {
          uint32_t pk[8];
#pragma unroll
          for (int i = 0; i < 8; i++) pk[i] = pack2(ex2(sx[2 * i] * sc - mref[i & 6]), ex2(sx[2 * i + 1] * sc - mref[(i & 6) + 1]));
          asm volatile("stmatrix.sync.aligned.m8n8.x4.shared.b16 [%0], {%2,%3,%4,%5};\n"
                       "stmatrix.sync.aligned.m8n8.x4.shared.b16 [%1], {%6,%7,%8,%9};"
                       ::"r"(a_p), "r"(a_p ^ 32), "r"(pk[0]), "r"(pk[1]), "r"(pk[2]), "r"(pk[3]), "r"(pk[4]), "r"(pk[5]), "r"(pk[6]), "r"(pk[7]) : "memory");
          const uint32_t mx = __vmaxu2(__vmaxu2(__vmaxu2(pk[0], pk[1]), __vmaxu2(pk[2], pk[3])), __vmaxu2(__vmaxu2(pk[4], pk[5]), __vmaxu2(pk[6], pk[7])));
          ex = max(mx, mx << 16) > (127u + TAU) << 23;
          asm volatile("fence.proxy.async.shared::cta;" ::: "memory");
        }
        asm volatile("{.reg .pred p, q; setp.ne.s32 q, %0, 0; bar.red.or.pred p, 4, 256, q; selp.s32 %0, 1, 0, p;}" : "+r"(ex)::"memory");
        if (!ex || pass) break;
        int ln;
        asm volatile("mov.u32 %0, %%laneid;" : "=r"(ln));
        const uint32_t a_pm = sb + O_SM + ln * 16;
        if (wg == 0) {
          float cm[8];
#pragma unroll
          for (int i = 0; i < 8; i++) cm[i] = fmaxf(sx[2 * (i & 6) + (i & 1)], sx[2 * (i & 6) + (i & 1) + 2]);
          tmax<4>(cm, lane, 16); tmax<2>(cm, lane, 8); tmax<1>(cm, lane, 4);
          sts4(a_pm + warp * 4, cm[0] * sc);
        }
        nbar(4, 256);
        const float4 pm = lds16(a_pm);
        const float mn = u2f(__float_as_uint(fmaxf(fmaxf(fmaxf(pm.x, pm.y), fmaxf(pm.z, pm.w)), mrun)) | 1u), al = ex2(mrun - mn);
        mrun = mn;
#pragma unroll
        for (int i = 0; i < 8; i++) {
          const float a = __shfl_sync(~0u, al, 4 * i + (ln & 3)), aw = wg ? a : 1.f;
          mref[i] = __shfl_sync(~0u, mn, 4 * i + (ln & 3));
#pragma unroll
          for (int e = 0; e < 2; e++) {
            const int k = 2 * (i & 6) + (i & 1) + 2 * e;
            o[0][k] *= a; o[1][k] *= a; o[2][k] *= a; o[3][k] *= a; sx[k] *= aw;
          }
        }
      }
      float hv = mrun;
      if (wg) {
        asm volatile("wgmma.fence.sync.aligned;" ::: "memory");
#pragma unroll
        for (int k = 0; k < 4; k++) wgmma32r(sx, ones, DSC + O_P / 16 + k * 64);
        asm volatile("wgmma.commit_group.sync.aligned;" ::: "memory");
        landed();
        asm volatile("{.reg .pred p; setp.ne.s32 p, %1, 0; @p mbarrier.arrive.shared::cta.b64 _, [%0], %1;}" ::"r"(fb + 8 * B_EMPTY + 8 * tq), "r"(cnt) : "memory");
        wg_wait<0>(sx);
        float lv[4];
#pragma unroll
        for (int j = 0; j < 4; j++) lv[j] = (lane & 4) ? sx[4 * j + 1] : sx[4 * j];
        hv = (lane & 16) ? ((lane & 8) ? lv[3] : lv[2]) : ((lane & 8) ? lv[1] : lv[0]);
      }
      asm volatile("{.reg .pred p; setp.eq.s32 p, %3, %4; @p st.relaxed.cluster.b32 [%0], %1; @p st.relaxed.cluster.b32 [%2], %1;}"
                   ::"l"(a_h), "r"(__float_as_uint(hv) | 1u), "l"(a_h1), "r"(t), "r"(nt - 1) : "memory");
#pragma unroll
      for (int q = 0; q < 4; q++) {
        asm volatile("wgmma.fence.sync.aligned;" ::: "memory");
#pragma unroll
        for (int k = 0; k < 4; k++) wgmma32r(o[q], vf[q][k], DSC + O_P / 16 + k * 64);
        asm volatile("wgmma.commit_group.sync.aligned;" ::: "memory");
        if (q == 3) {
#pragma unroll
          for (int u = 0; u < 4; u++) ldsm_t(z[u], a_z[u] + u * 1024);
        }
        wg_wait<0>(o[q]);
#pragma unroll
        for (int j = 0; j < 2; j++)
          asm volatile("{.reg .pred p; setp.eq.s32 p, %5, %6; @p st.relaxed.cluster.v4.b32 [%0], {%1,%2,%3,%4};}"
                       ::"l"(dst[q] + j * 512), "r"(pack2t(o[q][8 * j], o[q][8 * j + 1], 1)), "r"(pack2(o[q][8 * j + 2], o[q][8 * j + 3])),
                         "r"(pack2(o[q][8 * j + 4], o[q][8 * j + 5])), "r"(pack2(o[q][8 * j + 6], o[q][8 * j + 7])), "r"(t), "r"(nt - 1) : "memory");
      }
    }
  }
  {
    uint32_t wx[4][4];
    mbar_wait(bar0 + 8 * B_WZ);
#pragma unroll
    for (int u = 0; u < 4; u++) {
      uint2 wp;
      asm volatile("ld.shared.v2.u32 {%0, %1}, [%2];" : "=r"(wp.x), "=r"(wp.y) : "r"(a_w + u * 8) : "memory");
      const bool lo = (g >> 1) == (tq >> 1), hi = (g >> 1) == 2 + (tq >> 1);
      wx[u][0] = lo ? wp.x : 0u; wx[u][1] = lo ? wp.y : 0u; wx[u][2] = hi ? wp.x : 0u; wx[u][3] = hi ? wp.y : 0u;
    }
    auto bad = [&]() {
      const unsigned ok = and3(and3(and3(z[0][0], z[0][1], z[0][2]), and3(z[0][3], z[1][0], z[1][1]), and3(z[1][2], z[1][3], z[2][0])),
                               and3(and3(z[2][1], z[2][2], z[2][3]), and3(z[3][0], z[3][1], z[3][2]), z[3][3]), 0x10001u);
      return __any_sync(~0u, g == 0 && ok != 0x10001u);
    };
    POLL {
      if (it_)
#pragma unroll
        for (int u = 0; u < 4; u++) ldsm_t(z[u], a_z[u] + u * 1024);
      if (!bad() || ++it_ >= SPIN_MAX) break;
    }
    float d0[8][4] = {}, d[8][4], r[8];
#pragma unroll
    for (int i = 0; i < 8; i++) mma16(d0[i], wx[i >> 1], z[i >> 1][2 * (i & 1)], z[i >> 1][2 * (i & 1) + 1]);
    POLL {
#pragma unroll
      for (int u = 0; u < 4; u++) ldsm_t(z[u], a_z[u ^ 2] + u * 1024);
#pragma unroll
      for (int i = 0; i < 8; i++) mma16c(d[i], wx[(i >> 1) ^ 2], z[i >> 1][2 * (i & 1)], z[i >> 1][2 * (i & 1) + 1], d0[i]);
      if (!bad() || ++it_ >= SPIN_MAX) break;
    }
#pragma unroll
    for (int i = 0; i < 8; i++) r[i] = (tq & 2) ? ((g & 1) ? d[i][3] : d[i][2]) : ((g & 1) ? d[i][1] : d[i][0]);
#pragma unroll
    for (int q = 0; q < 2; q++) pub8(p_rec + q * 128, pack2t(r[4 * q], r[4 * q + 1], par) | 1u, pack2(r[4 * q + 2], r[4 * q + 3]));
  }
  const int vt = v0 + nt;
  const uint32_t bufa = sb + (vt & 1) * 65536, fulla = bar0 + (vt & 1) * 32, pha = (vt >> 1) & 1, phb = ((vt + 1) >> 1) & 1;
  const uint32_t bufo = sb + ((vt + 1) & 1) * 65536, fullb = bar0 + ((vt + 1) & 1) * 32;
  uint32_t a_rs = sb + O_R + (warp >> 2) * 1024 + (16 * tq + g) * 16 + ((warp + tq) & 3) * 4;
  if (isA) {
    const int row = 16 * (warp & 6) + 8 * (warp & 1) + (lane & 16) + ((lane & 7) >> 1) + 4 * (lane & 1);
    uint32_t ab = bufa + row * 128 + ((((lane >> 3) & 1) ^ (row & 7)) << 4);
    const uint2* pr = scr->rec + (hd * 32 + warp) * 64 + lane;
    unsigned long long a_c0 = mapg(sb + O_CTX + (64 * rn + 32 * (warp & 1) + posof(lane)) * 4, warp & 6);
    unsigned long long a_c1 = mapg(sb + O_CTX + (64 * rn + 32 * (warp & 1) + posof(lane)) * 4, warp | 1);
    uint32_t a_rl = sb + O_R + (32 * (warp & 1) + lane) * 16;
    uint32_t ao = bufo + (16 * warp + 8 * (lane >> 4) + (lane & 7)) * 128 + ((((lane >> 3) & 1) ^ (lane & 7)) << 4);
    uint32_t a_cx = sb + O_CTX + (16 * warp + 4 * tq) * 4, a_ga = sb + O_SM + (320 + posof(tid & 63)) * 4;
    unsigned* p_ao = scr->xao + b * 64 + (tid & 63);
    unsigned* p_ab = scr->xab + cl * 256 + (2 * (rn & 3) + (warp & 1)) * 32 + (rn >> 2) * 16 + (lane >> 1);
    float xv = cl == 0 ? __bfloat162float(x[64 * rn + (tid & 63)]) : 0.f;
    unsigned p2 = lane >= 28 ? 0 : par;
    PIN(ab); PINL(pr); PINL(a_c0); PINL(a_c1); PIN(a_rl); PIN(a_rs); PIN(ao); PIN(a_cx); PIN(a_ga); PINL(p_ao); PINL(p_ab); PIN(p2);
    asm volatile("" : "+f"(xv));
    uint32_t aw[4][4][4];
    auto wo = [&](const int j) {
      mbar_wait(fullb + 8 * j, phb);
#pragma unroll
      for (int mt = 0; mt < 4; mt++) ldsm_t(aw[j][mt], (ao + j * 16384) ^ (mt << 5));
    };
    {
      uint32_t a[4][4][4];
      uint2 z[4], y[4] = {};
      float d[4][4] = {}, r[8];
      mbar_wait(fulla, pha);
      POLL {
#pragma unroll
        for (int q = 0; q < 4; q++) z[q] = ldx8(pr + q * 512);
        RETRY(lop_x3(z[0].x, z[1].x, par) | lop_x3(z[2].x, z[3].x, par))
      }
#pragma unroll
      for (int q = 0; q < 4; q++) {
        if (q == 3) {
          mbar_wait(bar0 + 8 * B_G);
          if (lane < 28)
#pragma unroll
            for (int u = 0; u < 4; u++) y[u] = ldx8(pr + u * 512 + 32);
          __syncwarp();
        }
        mbar_wait(fulla + 8 * q, pha);
#pragma unroll
        for (int mt = 0; mt < 4; mt++) ldsm_t(a[q][mt], (ab + q * 16384) ^ (mt << 5));
#pragma unroll
        for (int mt = 0; mt < 4; mt++) mma16(d[mt], a[q][mt], z[q].x, z[q].y);
      }
      mbar_wait(bar0 + 8 * B_W);
      const float4 W = lds16(sb + O_SM + (384 + 4 * tq) * 4);
#pragma unroll
      for (int i = 0; i < 8; i++) { r[i] = W.x * d[i >> 1][2 * (i & 1)] + W.y * d[i >> 1][2 * (i & 1) + 1]; asm volatile("" : "+f"(r[i])); }
#pragma unroll
      for (int j = 0; j < NPE; j++) wo(j);
      POLL {
        if (it_)
#pragma unroll
          for (int u = 0; u < 4; u++) y[u] = ldx8(pr + u * 512 + 32);
#pragma unroll
        for (int mt = 0; mt < 4; mt++) d[mt][0] = d[mt][1] = d[mt][2] = d[mt][3] = 0.f;
#pragma unroll
        for (int q = 0; q < 4; q++)
#pragma unroll
          for (int mt = 0; mt < 4; mt++) mma16(d[mt], a[q][mt], y[q].x, y[q].y);
        RETRY(or3(lop_x3(y[0].x, y[1].x, p2), lop_x3(y[2].x, y[3].x, p2), 0))
      }
#pragma unroll
      for (int i = 0; i < 8; i++) r[i] = W.w * d[i >> 1][2 * (i & 1) + 1] + (W.z * d[i >> 1][2 * (i & 1)] + r[i]);
      tred<4>(r, lane, 2); tred<2>(r, lane, 1);
      sts4(a_rs, r[0]); sts4(a_rs + 128, r[1]);
      nbar(1, 256);
      const uint32_t cv = __float_as_uint(sum8(a_rl)) | 1u;
      asm volatile("st.relaxed.cluster.b32 [%0], %2; st.relaxed.cluster.b32 [%1], %2;" ::"l"(a_c0), "l"(a_c1), "r"(cv) : "memory");
    }
    {
#pragma unroll
      for (int j = NPE; j < NPO; j++) wo(j);
      uint4 c[4];
      POLL {
#pragma unroll
        for (int j = 0; j < 4; j++) c[j] = ldsv16(a_cx + j * 512);
        RETRY(~and3(and3(and3(c[0].x, c[0].y, c[0].z), and3(c[1].x, c[1].y, c[1].z), and3(c[0].w, c[1].w, c[2].x)),
                    and3(and3(c[2].y, c[2].z, c[2].w), and3(c[3].x, c[3].y, c[3].z), c[3].w), ~0u))
      }
      float d[4][4] = {};
#pragma unroll
      for (int j = 0; j < 4; j++) {
        if (j + 1 >= NPO && j < 3) wo(j + 1);
        const uint32_t b0 = pack2(u2f(c[j].x), u2f(c[j].y)), b1 = pack2(u2f(c[j].z), u2f(c[j].w));
#pragma unroll
        for (int mt = 0; mt < 4; mt++) mma16(d[mt], aw[j][mt], b0, b1);
      }
      const float r0 = (tq & 2) ? ((tq & 1) ? d[3][0] : d[2][0]) : ((tq & 1) ? d[1][0] : d[0][0]);
      const float r1 = (tq & 2) ? ((tq & 1) ? d[3][2] : d[2][2]) : ((tq & 1) ? d[1][2] : d[0][2]);
      sts4(a_rs + 2048, r0); sts4(a_rs + 2048 + 128, r1);
      if (warp >= 2) nbar_arrive(2, 256);
      else {
        mbar_wait(bar0 + 8 * B_TAB);
        const float gav = lds4(a_ga);
        nbar(2, 256);
        const float t = gav * sum8(a_rl + 2048) + xv;
        asm volatile("{.reg .pred p; setp.eq.s32 p, %2, 0; @p red.relaxed.gpu.global.xor.b32 [%0], %1;}"
                     ::"l"(p_ab), "r"(pack2t(t, __shfl_down_sync(~0u, t, 1), par) | 1u), "r"(lane & 1) : "memory");
        pub4(p_ao, __float_as_uint(t) | 1u);
      }
    }
  } else {
    uint32_t af[4][4][4];
    uint32_t ab = bufa + (32 * warp + 8 * (lane >> 4) + (lane & 7)) * 64 + ((((lane >> 3) & 1) ^ ((lane >> 1) & 3)) << 4);
    uint32_t a_d = bufo + (8 * (lane >> 4) + (lane & 7)) * 128 + (((2 * (warp & 3) + ((lane >> 3) & 1)) ^ (lane & 7)) << 4);
    uint32_t a_rl = sb + O_R + lane * 16, a_st = sb + O_SM + (352 + 8 * (lane >> 4) + warp) * 4;
    const unsigned* pa = scr->xab + tid;
    unsigned long long a_h = mapg(sb + O_CTX + rn * 64 + (lane & 6) * 8 + (lane >> 3) * 4, 2 * (warp & 3) + (lane & 1));
    const int col = 64 * rn + 16 * (warp & 3) + 8 * (tq & 1) + g;
    uint32_t a_hl = sb + O_CTX + tq * 16;
    const unsigned* px = scr->xao + (tq & 2) * 1024 + col;
    bf16* po = out + col;
    PIN(ab); PIN(a_d); PIN(a_rl); PINL(pa); PIN(a_rs); PIN(a_st); PINL(po); PINL(a_h); PIN(a_hl); PINL(px);
    mbar_wait(bar0 + 8 * B_TAB);
    uint2 cf;
    uint2 bb[4];
    unsigned gbw;
    POLL {
      unsigned bad = 0;
      cf = ldx8(scr->xm + 1024 + (lane & 16) * 16 + 32 * warp + posof(2 * (lane & 15)));
#pragma unroll
      for (int s = 0; s < 4; s++) {
        const uint4 w = ldx16(scr->xm + 1024 - (g & 1) * 512 + 256 * (s >> 1) + 32 * warp + 16 * (s & 1) + 4 * tq);
        bb[s] = make_uint2(__byte_perm(w.x, w.y, 0x7632), __byte_perm(w.z, w.w, 0x7632));
        bad = or3(bad, lop_x3(w.x, w.y, par), lop_x3(w.z, w.w, par));
      }
      gbw = ldx4(scr->xm + 1536 + posof(col));
      RETRY(or3(bad, lop_x3(cf.x, cf.y, par), gbw ^ par))
    }
    const float gbv = bfhi(gbw);
    float e[4][4] = {};
    unsigned v[8];
    auto item = [&](const int it) {
      mbar_wait(fulla + 8 * it, pha);
#pragma unroll
      for (int i = 0; i < 4; i++) ldsm_t(af[it][i], (ab + it * 16384 + (i >> 1) * 1024) ^ ((i & 1) << 5));
    };
    auto item_mma = [&](const int it) {
#pragma unroll
      for (int i = 0; i < 4; i++) mma16(e[2 * (it & 1) + (i & 1)], af[it][i], bb[(it & 2) + (i >> 1)].x, bb[(it & 2) + (i >> 1)].y);
    };
    unsigned t3 = sch.wt;
    PIN(t3);
    item(0); item_mma(0); item(1); item_mma(1);
    mbar_wait(bar0 + 8 * B_G);
#pragma unroll
    for (int i = 0; i < 8; i++) v[i] = ldx4(pa + i * 256);
    t3 += clock();
    uint32_t have2, have3 = 0;
    do have2 = mbar_test(fulla + 16, pha); while (!have2 && (int)((unsigned)clock() - t3) < 0);
    if (have2) {
      item(2); item_mma(2);
      do have3 = mbar_test(fulla + 24, pha); while (!have3 && (int)((unsigned)clock() - t3) < 0);
      if (have3) { item(3); item_mma(3); }
    }
    float y0, y1, df[4][4], st[2];
    uint32_t bz[4][2] = {};
    auto mm = [&](const int it, const int i) { mma16(df[2 * (it & 1) + (i & 1)], af[it][i], bz[(it & 2) + (i >> 1)][0], bz[(it & 2) + (i >> 1)][1]); };
    POLL {
      if (it_)
#pragma unroll
        for (int i = 0; i < 8; i++) v[i] = ldx4(pa + i * 256);
      y0 = ((bflo(v[0]) + bflo(v[1])) + (bflo(v[2]) + bflo(v[3]))) + ((bflo(v[4]) + bflo(v[5])) + (bflo(v[6]) + bflo(v[7])));
      y1 = ((bfhi(v[0]) + bfhi(v[1])) + (bfhi(v[2]) + bfhi(v[3]))) + ((bfhi(v[4]) + bfhi(v[5])) + (bfhi(v[6]) + bfhi(v[7])));
      const uint32_t zb = pack2(y0 * u2f(cf.x), y1 * u2f(cf.y));
#pragma unroll
      for (int s = 0; s < 4; s++) {
        const uint32_t w = __shfl_sync(~0u, zb, 8 * s + (lane & 7));
        bz[s][0] = (lane & 4) ? 0u : w; bz[s][1] = (lane & 4) ? w : 0u;
      }
      st[0] = y0 + y1; st[1] = y0 * y0 + y1 * y1;
      tred<1>(st, lane, 16);
#pragma unroll
      for (int i = 0; i < 4; i++) df[i][0] = df[i][1] = df[i][2] = df[i][3] = 0.f;
      mm(0, 0); mm(0, 1); mm(1, 0); mm(1, 1);
      st[0] += shx(st[0], 8);
      mm(0, 2); mm(0, 3); mm(1, 2); mm(1, 3);
      RETRY(or3(or3(lop_x3(v[0], v[1], par), lop_x3(v[2], v[3], par), lop_x3(v[4], v[5], par)), lop_x3(v[6], v[7], par), 0))
    }
    unsigned xq[4];
    if (wg == 0)
#pragma unroll
      for (int i = 0; i < 4; i++) xq[i] = ldx4(px + i * 512);
    if (have2) { mm(2, 0); mm(2, 1); mm(2, 2); mm(2, 3); }
    st[0] += shx(st[0], 4);
    st[0] += shx(st[0], 2);
    st[0] += shx(st[0], 1);
    sts4(a_st, st[0]);
    __syncwarp();
    arrive_n(bar0 + 8 * B_ST, lane == 0, 1);
    if (!have2) { item(2); item_mma(2); mm(2, 0); mm(2, 1); mm(2, 2); mm(2, 3); }
    if (!have3) { item(3); item_mma(3); }
    mm(3, 0); mm(3, 1); mm(3, 2); mm(3, 3);
    mbar_wait(bar0 + 8 * B_ST);
    float mean, rstd;
    {
      float4 u[4];
#pragma unroll
      for (int i = 0; i < 4; i++) u[i] = lds16(sb + O_SM + (352 + 4 * i) * 4);
      mean = (((u[0].x + u[0].y) + (u[0].z + u[0].w)) + ((u[1].x + u[1].y) + (u[1].z + u[1].w))) * (1.f / 512.f);
      const float sq = (((u[2].x + u[2].y) + (u[2].z + u[2].w)) + ((u[3].x + u[3].y) + (u[3].z + u[3].w))) * (1.f / 512.f);
      asm("rsqrt.approx.ftz.f32 %0, %1;" : "=f"(rstd) : "f"(fmaxf(sq - mean * mean, 0.f) + 1e-5f));
    }
    float A[4], r[4];
#pragma unroll
    for (int i = 0; i < 4; i++) {
      A[i] = (tq & 2) ? ((tq & 1) ? e[3][i] : e[2][i]) : ((tq & 1) ? e[1][i] : e[0][i]);
      r[i] = (tq & 2) ? ((tq & 1) ? df[3][i] : df[2][i]) : ((tq & 1) ? df[1][i] : df[0][i]);
    }
    sts4(a_rs, rstd * (r[0] + r[1]) + (A[1] - rstd * mean * A[0])); sts4(a_rs + 128, rstd * (r[2] + r[3]) + (A[3] - rstd * mean * A[2]));
    nbar(1, 256);
    if (wg) {
      const float4 g0 = lds16(a_rl), g1 = lds16(a_rl + 1024), u0 = lds16(a_rl + 512), u1 = lds16(a_rl + 1536);
      const float gg = bfr(((g0.x + g0.y) + (g0.z + g0.w)) + ((g1.x + g1.y) + (g1.z + g1.w)));
      const float uu = bfr(((u0.x + u0.y) + (u0.z + u0.w)) + ((u1.x + u1.y) + (u1.z + u1.w)));
      const float hh = bfr(gg * rcp(1.f + ex2(gg * (-2.302208198f - 0.1029432397f * gg * gg)))) * uu, hn = __shfl_xor_sync(~0u, hh, 1);
      asm volatile("st.relaxed.cluster.b32 [%0], %1;" ::"l"(a_h), "r"(pack2t((lane & 1) ? hn : hh, (lane & 1) ? hh : hn, 1)) : "memory");
    } else {
      uint32_t ad[16][4];
      spin_until(clock() + FDLY);
#pragma unroll
      for (int j = 0; j < 2; j++) {
        mbar_wait(fullb + 8 * j, phb);
#pragma unroll
        for (int i = 0; i < 8; i++) ldsm_t(ad[8 * j + i], a_d + (8 * j + i) * 2048);
      }
      POLL {
        if (it_)
#pragma unroll
          for (int i = 0; i < 4; i++) xq[i] = ldx4(px + i * 512);
        RETRY(lop_x3(xq[0], xq[1], par) | lop_x3(xq[2], xq[3], par))
      }
      float x7 = (u2f(xq[0]) + u2f(xq[1])) + (u2f(xq[2]) + u2f(xq[3]));
      x7 = (x7 + __shfl_xor_sync(~0u, x7, 2)) * (1.f / 7.f);
      uint4 hb[8];
      POLL {
        unsigned ok[8];
#pragma unroll
        for (int i = 0; i < 8; i++) { hb[i] = ldsv16(a_hl + i * 64); ok[i] = and3(hb[i].x, hb[i].y, hb[i].z); }
        RETRY(~and3(and3(and3(ok[0], ok[1], ok[2]), and3(ok[3], ok[4], ok[5]), and3(ok[6], ok[7], hb[0].w)),
                    and3(and3(hb[1].w, hb[2].w, hb[3].w), and3(hb[4].w, hb[5].w, hb[6].w), hb[7].w), 1))
      }
      float dd[4][4] = {};
#pragma unroll
      for (int i = 0; i < 8; i++) { mma16(dd[(2 * i) & 3], ad[2 * i], hb[i].x, hb[i].y); mma16(dd[(2 * i + 1) & 3], ad[2 * i + 1], hb[i].z, hb[i].w); }
      const float t = gbv * ((tq & 1) ? (dd[0][2] + dd[1][2]) + (dd[2][2] + dd[3][2]) : (dd[0][0] + dd[1][0]) + (dd[2][0] + dd[3][0])) + x7;
      asm volatile("{.reg .pred p; setp.eq.s32 p, %2, 0; @p red.relaxed.gpu.global.add.noftz.bf16x2 [%0], %1;}"
                   ::"l"(po), "r"(pack2(t, __shfl_down_sync(~0u, t, 4))), "r"(lane & 6) : "memory");
      if (f == 0 && tid == 0) stx4(&scr->cnt[0], epoch + 1);
    }
  }
}

static void make_sched(Sched& s) {
  const char* order = "FFAAbcFmmvog..d";
  const double dt = 5010 * 1e-3, dth = 4850 * 1e-3;
  const int nbig = NBIG;
  s.zero = 0; s.dth = (unsigned)(dth * 256 + 0.5);
  double t = 512 * dth + 80;
  int tile = 0, jm = 0;
  for (int i = 0; i < 3; i++) s.nr[i] = s.nt[i] = 0;
  auto add = [&](int c, int type, double step, int win, int b0, int tl) {
    s.r[c][s.nr[c]++] = make_uint2((unsigned)(t + 0.5) | (unsigned)(step + 0.5) << 16, type | win << 4 | (b0 + 64) << 8 | tl << 16);
    if (type == T_KV) s.nt[c]++;
  };
  const int w1 = 6, w2 = 4, wt = 6;
  for (const char* p = order; *p; p++) {
    const char c = *p;
    if (c == 'v' || c == 'o' || c == 'm') {
      const int ty = c == 'v' ? T_UV : c == 'o' ? T_WO : T_MOD;
      const double d = (c == 'm' ? 5010 : c == 'v' ? 5500 : 5500) * 1e-3;
      add(0, ty, 64 * d, wt, 0, c == 'm' ? jm : 0); add(1, ty, 64 * d, wt, 0, c == 'm' ? jm : 0);
      t += (c == 'm' ? 64 : 256) * d; jm += c == 'm';
    } else if (c == 'g' || c == 'd') {
      const double d = (c == 'g' ? 5500 : 5500) * 1e-3;
      add(2, c == 'g' ? T_GU : T_DN, 56 * d, wt, 64, 0);
      t += (c == 'g' ? 224 : 112) * d;
    } else if (c == '.') t += 100;
    else if (c == '-') t -= 100;
    else {
      const int na = c == 'F' ? 0 : c == 'C' || c == 'c' || c == 'a' ? nbig : 64, nf = c == 'A' || c == 'a' ? 0 : 56, n = na + nf;
      const int w = na && nf ? w2 : w1;
      const bool ff = c == 'b' || c == 'c';
      const int cf = c == 'c' ? 40 : 0, ca = cf * 7 / 5;
      t += 3 * ca;
      if (na) add(0, T_KV, n * dt - ca, w, ff ? -56 : 0, tile);
      t -= 3 * ca;
      if (na == 64) add(1, T_KV, n * dt, w, ff ? -56 : 0, tile);
      if (nf) add(2, T_KV, n * dt - cf, w, ff ? 64 : 64 - na, tile);
      tile += n; t += 4 * n * dt;
      s.t4 = (unsigned)t + 600;
    }
  }
  s.dt = (unsigned)(dt * 256 + 0.5); s.d4 = 1550 | 1200 << 16; s.d6 = 3180; s.wt = 250;
}

static void launch(void* const* d_in, void* d_out) {
  static TMaps tms;
  static Sched sch;
  static bool init = false;
  static void* scr = nullptr;
  if (!init) {
    void* fn = nullptr; cudaDriverEntryPointQueryResult qr;
    cudaGetDriverEntryPoint("cuTensorMapEncodeTiled", &fn, cudaEnableDefault, &qr);
    EncFn f = (EncFn)fn;
    const CUtensorMapSwizzle S64 = CU_TENSOR_MAP_SWIZZLE_64B, S128 = CU_TENSOR_MAP_SWIZZLE_128B;
    const CUtensorMapL2promotion P256 = CU_TENSOR_MAP_L2_PROMOTION_L2_256B;
    enc3d(f, &tms.m[0], d_in[2], 64, 512, 64, 8192, 128, 64, 128, 1, S128, CU_TENSOR_MAP_L2_PROMOTION_L2_128B);
    enc3d(f, &tms.m[1], d_in[3], 64, 512, 64, 8192, 128, 64, 64, 2, S128, P256);
    enc3d(f, &tms.m[2], d_in[1], 64, SK, 8, 1024, 128, 64, 64, 2, S128, P256);
    enc3d(f, &tms.m[3], d_in[11], 3072, 256, 2, 6144, 256 * 6144, 32, 256, 1, S64, CU_TENSOR_MAP_L2_PROMOTION_L2_128B);
    enc3d(f, &tms.m[4], d_in[4], 64, 512, 64, 8192, 128, 64, 128, 1, S128, CU_TENSOR_MAP_L2_PROMOTION_L2_128B);
    enc3d(f, &tms.m[5], d_in[5], 512, 128, 32, 1024, 128 * 1024, 64, 128, 1, S128, CU_TENSOR_MAP_L2_PROMOTION_L2_128B);
    enc3d(f, &tms.m[6], d_in[7], 1792, 256, 2, 3584, 256 * 3584, 32, 256, 1, S64, CU_TENSOR_MAP_L2_PROMOTION_L2_128B);
    enc3d(f, &tms.m[7], d_in[8], 1792, 256, 2, 3584, 256 * 3584, 32, 256, 1, S64, CU_TENSOR_MAP_L2_PROMOTION_L2_128B);
    enc3d(f, &tms.m[8], d_in[9], 512, 128, 14, 1024, 128 * 1024, 64, 128, 1, S128, CU_TENSOR_MAP_L2_PROMOTION_L2_128B);
    cudaFuncSetAttribute(fused_kernel, cudaFuncAttributeMaxDynamicSharedMemorySize, SMEM9);
    cudaGetSymbolAddress(&scr, g_scr);
    make_sched(sch);
    init = true;
  }
  fused_kernel<<<NCTA9, 384, SMEM9>>>((const bf16*)d_in[0], (const bf16*)d_in[10], (const bf16*)d_in[11], (bf16*)d_out, (Scratch*)scr, sch, tms);
}

static bool fits() {
  cudaFuncSetAttribute(fused_kernel, cudaFuncAttributeMaxDynamicSharedMemorySize, SMEM9);
  cudaLaunchConfig_t cfg = {};
  cfg.gridDim = dim3(NCTA9); cfg.blockDim = dim3(384); cfg.dynamicSmemBytes = SMEM9;
  cudaLaunchAttribute at[1];
  at[0].id = cudaLaunchAttributeClusterDimension; at[0].val.clusterDim.x = 8; at[0].val.clusterDim.y = 1; at[0].val.clusterDim.z = 1;
  cfg.attrs = at; cfg.numAttrs = 1;
  int n = 0;
  if (cudaOccupancyMaxActiveClusters(&n, fused_kernel, &cfg) != cudaSuccess) { (void)cudaGetLastError(); return false; }
  return n >= NCTA9 / 8;
}
}
#undef BAR_ARM
#undef BAR_ARRIVE
#undef BAR_INIT
#undef B_EM
#undef B_EMPTY
#undef B_FM
#undef B_FULL
#undef B_G
#undef B_G2
#undef B_H
#undef B_HZ
#undef B_LZ
#undef B_Q2
#undef B_QF
#undef B_ST
#undef B_TAB
#undef B_W
#undef B_WZ
#undef CNT_ADD
#undef DSC
#undef FDLY
#undef HI128
#undef HI64
#undef LANE0
#undef NBIG
#undef NCTA9
#undef NPE
#undef NPO
#undef NSL
#undef O_B
#undef O_BAR
#undef O_CTX
#undef O_DBG
#undef O_EP
#undef O_HW
#undef O_HZ
#undef O_LZ
#undef O_P
#undef O_Q
#undef O_R
#undef O_SILU
#undef O_SM
#undef O_X
#undef PIN
#undef PINL
#undef POLL
#undef QN
#undef RETRY
#undef SK
#undef SMEM9
#undef SMEM_BASE
#undef SPIN_MAX
#undef TAU
#undef VDLY
#undef VJ
#undef X16
#undef fbits

namespace v8 {
typedef __nv_bfloat16 bf16;
#define NCTA 128
#define SK 32768
#define SLOT 32768
#define NSLOT 6
#define OFF_WQ (2 * SLOT)
#define OFF_WUK (4 * SLOT)
#define OFF_Q 196608
#define OFF_P (OFF_Q + 16384)
#define OFF_B (OFF_P + 4096)
#define OFF_R4 (OFF_B + 2304)
#define OFF_SILU (OFF_R4 + 4096)
#define OFF_RA (OFF_SILU + 1024)
#define OFF_SM (OFF_RA + 1024)
#define OFF_BP (OFF_SM + 1792)
#define OFF_CO (OFF_BP + 1024)
#define OFF_BAR (OFF_CO + 1280)
#define OFF_MASK (OFF_BAR + 512)
#define OFF_DBG (OFF_MASK + 16)
#define SMEM_BYTES (OFF_DBG + 128)
#define OFF_MOD OFF_Q
#define OFF_UV (4 * SLOT)
#define OFF_O (5 * SLOT)
#define OFF_G 0
#define OFF_U 16384
#define OFF_D SLOT
#define OFF_XO (OFF_D + 16384)
#define FB_UK 4
#define FB_KV 6
#define FB_MOD 22
#define FB_UV 23
#define FB_O 25
#define FB_G 27
#define FB_D 29
#define EB 30
#define QB 50
#define XB 51
#define SPIN_MAX (1 << 20)
#define BACKOFF 40
#define RATE_NS 652
#define RATE_T0 200
#define RATE_TL 300
#define WINS 0x3222333
#define KVWIN 4
#define RATE_H 650
#define RATE_E 650
#define SMUL 9
#define NPRE0 1
#define NPRE1 3
#define HWIN 4
#define EWIN 3
#define WTEST 450
#define DLY5 650
#define DLY6 600
#define DLY7 600
#define P12(a, b, c, d, e, f, g, h, i, j, k, l) ((unsigned long long)(a) | (b) << 5 | (c) << 10 | (d) << 15 | (e) << 20 | (f) << 25 | \
  (unsigned long long)(g) << 30 | (unsigned long long)(h) << 35 | (unsigned long long)(i) << 40 | (unsigned long long)(j) << 45 | \
  (unsigned long long)(k) << 50 | (unsigned long long)(l) << 55)
#define ORDER0 P12(0, 1, 2, 3, 4, 5, 16, 6, 7, 8, 9, 10)
#define ORDER1 P12(11, 12, 13, 14, 15, 17, 18, 19, 20, 23, 21, 22)
#define TAIL_K 17
#define RS 16
template <int N> struct IC { static constexpr int value = N; };
struct TMaps { CUtensorMap m[9]; };

struct __align__(128) Scratch {
  uint4 xo[128 * 64 * RS];
  uint2 ml[32 * 64];
  unsigned h[8 * 256];
  unsigned qa[32 * 256];
  unsigned xc[128 * 64];
  unsigned xao[8 * 512];
  unsigned xf[112 * 512];
  unsigned xm[2048];
  unsigned cnt[5 * 32];
};
__device__ Scratch g_scr;
#define g_xo scr->xo
#define g_ml scr->ml
#define g_h scr->h
#define g_qa scr->qa
#define g_xc scr->xc
#define g_xao scr->xao
#define g_xf scr->xf
#define g_xm scr->xm
#define g_epoch scr->cnt[0]

__device__ __forceinline__ uint32_t s2u(const void* p) { return (uint32_t)__cvta_generic_to_shared(p); }
__device__ __forceinline__ float bflo(uint32_t u) { return __uint_as_float(u << 16); }
__device__ __forceinline__ float bfhi(uint32_t u) { return __uint_as_float(u & 0xffff0000u); }
__device__ __forceinline__ float u2f(uint32_t u) { return __uint_as_float(u); }
__device__ __forceinline__ void fma8(float* acc, uint4 v, float s) {
  acc[0] += s * bflo(v.x); acc[1] += s * bfhi(v.x); acc[2] += s * bflo(v.y); acc[3] += s * bfhi(v.y);
  acc[4] += s * bflo(v.z); acc[5] += s * bfhi(v.z); acc[6] += s * bflo(v.w); acc[7] += s * bfhi(v.w);
}
__device__ __forceinline__ uint32_t pack2(float a, float b) {
  __nv_bfloat162 p = __floats2bfloat162_rn(a, b); return *(uint32_t*)&p;
}
__device__ __forceinline__ float bfr(float v) { return bfhi(pack2(v, v)); }
__device__ __forceinline__ float silu_bf(float c) { return bfr(__fdividef(c, 1.f + __expf(-c))); }
#define fbits(v) ((__float_as_uint(v) & ~1u) | par)
__device__ __forceinline__ uint32_t pack2t(float a, float b, unsigned par) {
  const uint32_t ua = ((__float_as_uint(a) + ((par ^ 1) << 16)) & 0xFFFE0000u) | (par << 16);
  return __byte_perm(ua, pack2(b, b), 0x7632);
}
__device__ __forceinline__ void nbar(int id, int n) { asm volatile("bar.sync %0, %1;" ::"r"(id), "r"(n) : "memory"); }
__device__ __forceinline__ void nbar_arrive(int id, int n) { asm volatile("bar.arrive %0, %1;" ::"r"(id), "r"(n) : "memory"); }
__device__ __forceinline__ uint4 ldc16(const void* p) {
  uint4 v; asm volatile("ld.relaxed.cta.global.v4.u32 {%0,%1,%2,%3}, [%4];" : "=r"(v.x), "=r"(v.y), "=r"(v.z), "=r"(v.w) : "l"(p) : "memory"); return v;
}
__device__ __forceinline__ unsigned ldc4(const void* p) {
  unsigned v; asm volatile("ld.relaxed.cta.global.u32 %0, [%1];" : "=r"(v) : "l"(p) : "memory"); return v;
}
__device__ __forceinline__ uint4 ldx16(const void* p) {
  uint4 v; asm volatile("ld.relaxed.gpu.global.v4.u32 {%0,%1,%2,%3}, [%4];" : "=r"(v.x), "=r"(v.y), "=r"(v.z), "=r"(v.w) : "l"(p) : "memory"); return v;
}
__device__ __forceinline__ unsigned ldx4(const void* p) {
  unsigned v; asm volatile("ld.relaxed.gpu.global.u32 %0, [%1];" : "=r"(v) : "l"(p) : "memory"); return v;
}
__device__ __forceinline__ unsigned long long ldx64(const void* p) {
  unsigned long long v; asm volatile("ld.relaxed.gpu.global.u64 %0, [%1];" : "=l"(v) : "l"(p) : "memory"); return v;
}
__device__ __forceinline__ void stx16(void* p, uint4 v) {
  asm volatile("st.relaxed.gpu.global.v4.u32 [%0], {%1,%2,%3,%4};" ::"l"(p), "r"(v.x), "r"(v.y), "r"(v.z), "r"(v.w) : "memory");
}
__device__ __forceinline__ void stx8(void* p, uint2 v) { asm volatile("st.relaxed.gpu.global.v2.u32 [%0], {%1,%2};" ::"l"(p), "r"(v.x), "r"(v.y) : "memory"); }
__device__ __forceinline__ void stx4(void* p, unsigned v) { asm volatile("st.relaxed.gpu.global.u32 [%0], %1;" ::"l"(p), "r"(v) : "memory"); }
__device__ __forceinline__ unsigned lop_x3(unsigned a, unsigned b, unsigned c) {
  unsigned d; asm("lop3.b32 %0, %1, %2, %3, 0x7E;" : "=r"(d) : "r"(a), "r"(b), "r"(c)); return d; }
#define X16(v) (lop_x3(v.x, v.y, par) | lop_x3(v.z, v.w, par))
#define X8(v) lop_x3(v.x, v.y, par)
#define RETRY(bad) if (!__any_sync(~0u, (bad) & 1) || ++it_ >= SPIN_MAX) break; __nanosleep(BACKOFF);
#define POLL _Pragma("unroll 1") for (int it_ = 0;;)
__device__ __forceinline__ void mbar_wait(uint32_t bar) {
  uint32_t ok; int it = 0;
  do {
    asm volatile("{.reg .pred p; mbarrier.try_wait.parity.shared::cta.b64 p, [%1], 0; selp.u32 %0,1,0,p;}"
                 : "=r"(ok) : "r"(bar) : "memory");
  } while (!ok && ++it < SPIN_MAX);
}
__device__ __forceinline__ float ex2(float v) { float r; asm("ex2.approx.ftz.f32 %0, %1;" : "=f"(r) : "f"(v)); return r; }
__device__ __forceinline__ float rcp(float v) { float r; asm("rcp.approx.ftz.f32 %0, %1;" : "=f"(r) : "f"(v)); return r; }
__device__ __forceinline__ void mma16(float* d, const uint32_t* a, uint32_t b0, uint32_t b1) {
  asm volatile("mma.sync.aligned.m16n8k16.row.col.f32.bf16.bf16.f32 {%0,%1,%2,%3}, {%4,%5,%6,%7}, {%8,%9}, {%0,%1,%2,%3};"
               : "+f"(d[0]), "+f"(d[1]), "+f"(d[2]), "+f"(d[3]) : "r"(a[0]), "r"(a[1]), "r"(a[2]), "r"(a[3]), "r"(b0), "r"(b1));
}
__device__ __forceinline__ float4 lds16(uint32_t a) {
  float4 v; asm volatile("ld.shared.v4.f32 {%0,%1,%2,%3}, [%4];" : "=f"(v.x), "=f"(v.y), "=f"(v.z), "=f"(v.w) : "r"(a) : "memory"); return v;
}
__device__ __forceinline__ void ldsm_t(uint32_t* r, uint32_t a) {
  asm volatile("ldmatrix.sync.aligned.m8n8.x4.trans.shared.b16 {%0,%1,%2,%3}, [%4];" : "=r"(r[0]), "=r"(r[1]), "=r"(r[2]), "=r"(r[3]) : "r"(a) : "memory");
}
__device__ __forceinline__ void ldsm(uint32_t* r, uint32_t a) {
  asm volatile("ldmatrix.sync.aligned.m8n8.x4.shared.b16 {%0,%1,%2,%3}, [%4];" : "=r"(r[0]), "=r"(r[1]), "=r"(r[2]), "=r"(r[3]) : "r"(a) : "memory");
}
template <int N>
__device__ __forceinline__ void tred(float* a, int lane, int m) {
  const bool hi = lane & m;
#pragma unroll
  for (int i = 0; i < N; i++) {
    float send = hi ? a[i] : a[i + N], keep = hi ? a[i + N] : a[i];
    a[i] = keep + __shfl_xor_sync(~0u, send, m);
  }
}
template <int N>
__device__ __forceinline__ void tmax(float* a, int lane, int m) {
  const bool hi = lane & m;
#pragma unroll
  for (int i = 0; i < N; i++) {
    float send = hi ? a[i] : a[i + N], keep = hi ? a[i + N] : a[i];
    a[i] = fmaxf(keep, __shfl_xor_sync(~0u, send, m));
  }
}
__device__ __forceinline__ void arrive2(uint32_t bar, uint32_t rbar, bool local, bool remote) {
  asm volatile("{.reg .pred p, q; setp.ne.s32 p, %2, 0; setp.ne.s32 q, %3, 0; @p mbarrier.arrive.shared::cta.b64 _, [%0];\n"
               "@q mbarrier.arrive.relaxed.cluster.shared::cluster.b64 _, [%1];}" ::"r"(bar), "r"(rbar), "r"((int)local), "r"((int)remote) : "memory");
}
__device__ __forceinline__ unsigned long long stream_policy() {
  unsigned long long p;
  asm volatile("createpolicy.fractional.L2::evict_first.b64 %0, 1.0;" : "=l"(p));
  return p;
}
__device__ __forceinline__ void tma3d(uint32_t dst, const CUtensorMap* tm, uint32_t bar, int c0, int c1, int c2) {
  asm volatile("cp.async.bulk.tensor.3d.shared::cluster.global.mbarrier::complete_tx::bytes.L2::cache_hint [%0], [%1, {%3, %4, %5}], [%2], %6;"
               ::"r"(dst), "l"(tm), "r"(bar), "r"(c0), "r"(c1), "r"(c2), "l"(stream_policy()) : "memory");
}
__device__ __forceinline__ void st_async2(uint32_t dst, uint32_t bar, float v0, float v1) {
  asm volatile("st.async.shared::cluster.mbarrier::complete_tx::bytes.v2.f32 [%0], {%1, %2}, [%3];" ::"r"(dst), "f"(v0), "f"(v1), "r"(bar) : "memory");
}
__device__ __forceinline__ void st_pair(int mode, uint32_t dst, uint32_t bar, float v0, float v1) {
  asm volatile("{.reg .pred p, q; setp.eq.s32 p, %4, 1; setp.eq.s32 q, %4, 2; @p st.shared.v2.f32 [%0], {%1, %2};\n"
               "@q st.async.shared::cluster.mbarrier::complete_tx::bytes.v2.f32 [%0], {%1, %2}, [%3];}"
               ::"r"(dst), "f"(v0), "f"(v1), "r"(bar), "r"(mode) : "memory");
}
__device__ __forceinline__ void spin_until(unsigned t) { while ((int)((unsigned)clock() - t) < 0) {} }
__device__ __forceinline__ unsigned wait_until(unsigned t) {
  unsigned now;
  for (;;) {
    asm volatile("mov.u32 %0, %%globaltimer_lo;" : "=r"(now));
    if ((int)(now - t) >= 0) break;
  }
  return now;
}
#define PIN(x) asm volatile("" : "+r"(x))
#define PINL(x) asm volatile("" : "+l"(x))
#define BAR_ARRIVE(i) asm volatile("mbarrier.arrive.shared::cta.b64 _, [%0];" ::"r"(bar0 + 8 * (i)) : "memory")
#define CNT_ADD(c) asm volatile("red.relaxed.gpu.global.add.u32 [%0], 1;" ::"l"(scr->cnt + (c)) : "memory")
#define BAR_INIT(i, cnt) asm volatile("mbarrier.init.shared::cta.b64 [%0], %1;" ::"r"(bar0 + 8 * (i)), "r"(cnt) : "memory")
#define BAR_ARM(i, bytes) asm volatile("mbarrier.arrive.expect_tx.shared::cta.b64 _, [%0], %1;" ::"r"(bar0 + 8 * (i)), "r"(bytes) : "memory")

__device__ __forceinline__ void tail(unsigned char* smem, Scratch* __restrict__ scr, const bf16* __restrict__ x, bf16* __restrict__ out,
                                     const unsigned par, const unsigned epoch, const int warp) {
  int tid, b;
  asm volatile("mov.u32 %0, %%tid.x;" : "=r"(tid));
  asm volatile("mov.u32 %0, %%ctaid.x;" : "=r"(b));
  const int lane = tid & 31, g = lane >> 2, tq = lane & 3;
  const uint32_t sb = __shfl_sync(~0u, s2u(smem), 0), bar0 = sb + OFF_BAR;
  float* s_sm = (float*)(smem + OFF_SM);
  const int prow = 4 * (lane >> 4) + ((lane & 7) >> 1) + 8 * (lane & 1);
  const float* s_co = (const float*)(smem + OFF_CO);
  const int opos = (b & 15) * 32 + (lane & 16) + 2 * (lane & 6) + ((lane >> 2) & 2) + (lane & 1);
  const float xv = b < 16 ? __bfloat162float(x[(b & 15) * 32 + lane]) : 0.f;
  const int rk = b & 1, ob = 32 * rk + ((b >> 1) & 31);
  uint32_t psb;
  asm volatile("mapa.shared::cluster.u32 %0, %1, %2;" : "=r"(psb) : "r"(sb), "r"(rk ^ 1));
  {
    uint32_t a[8][4];
    {
      const int rg = tid >> 4;
      const uint4* src = g_xo + ((size_t)b * 64 + rg) * RS;
      const uint32_t dst = sb + OFF_XO + rg * 256 + (((tid & 15) ^ (rg & 7)) << 4);
      unsigned long long todo = 0x0001000100010001ull;
#pragma unroll 1
      for (int it = 0; it < SPIN_MAX * 16; it++) {
        unsigned long long mk = *(volatile unsigned long long*)(smem + OFF_MASK);
        const unsigned long long nw = (mk >> rg) & todo;
        todo ^= nw;
#pragma unroll
        for (int i = 0; i < 4; i++)
          if (nw >> (16 * i) & 1)
            asm volatile("cp.async.cg.shared.global [%0], [%1], 16;" ::"r"(dst + i * 4096), "l"(src + i * 16 * RS + (tid & 15)) : "memory");
        if (!__any_sync(~0u, todo != 0)) break;
      }
      asm volatile("cp.async.mbarrier.arrive.noinc.shared::cta.b64 [%0];" ::"r"(bar0 + 8 * (XB + 2)) : "memory");
    }
    mbar_wait(bar0 + 8 * FB_UV); mbar_wait(bar0 + 8 * (FB_UV + 1));
    const uint32_t ab = sb + OFF_UV + (warp >> 2) * 8192 + (8 * (lane >> 4) + (lane & 7)) * 128 + (((2 * (warp & 3) + ((lane >> 3) & 1)) ^ (lane & 7)) << 4);
#pragma unroll
    for (int s = 0; s < 8; s++) ldsm_t(a[s], ab + (s >> 2) * 16384 + (s & 3) * 2048);
    const int chn = 2 * warp + (tq & 1);
    uint32_t a_b = sb + OFF_B + (tq >> 1) * 272 + (32 * (chn >> 2) + 8 * (g >> 1) + 2 * (chn & 3) + (g & 1)) * 2;
    uint32_t a_bq = sb + OFF_B + (lane & 1) * 272 + (lane >> 3) * 16;
    unsigned* p_c = g_xc + (b >> 2) * 256 + warp * 32 + (b & 3) * 8 + (g & 3) * 2 + (g >> 2);
    PIN(a_b); PIN(a_bq); PINL(p_c);
    mbar_wait(bar0 + 8 * (XB + 6));
    uint32_t wb[8];
#pragma unroll
    for (int s = 0; s < 8; s++) wb[s] = *(const uint32_t*)(smem + OFF_RA + (4 * s + tq) * 4);
    const float invL = *(const float*)(smem + OFF_RA + 128);
    float ov;
    POLL {
      mbar_wait(bar0 + 8 * (XB + 2));
      uint32_t ao[4][4];
#pragma unroll
      for (int s = 0; s < 4; s++)
        ldsm_t(ao[s], sb + OFF_XO + (16 * s + 8 * (lane >> 4) + (lane & 7)) * 256 + (((2 * warp + ((lane >> 3) & 1)) ^ (lane & 7)) << 4));
      float d[4][4] = {};
#pragma unroll
      for (int s = 0; s < 4; s++) mma16(d[s], ao[s], wb[2 * s], wb[2 * s + 1]);
      const unsigned p2 = par * 0x10001u;
      unsigned bad = 0;
#pragma unroll
      for (int s = 0; s < 4; s++) bad |= lop_x3(ao[s][0], ao[s][1], p2) | lop_x3(ao[s][2], ao[s][3], p2);
      bad = g == 0 ? bad | (bad >> 16) : 0u;
      ov = (tq & 1) ? (d[0][2] + d[1][2]) + (d[2][2] + d[3][2]) : (d[0][0] + d[1][0]) + (d[2][0] + d[3][0]);
      if (__builtin_expect(!__any_sync(~0u, bad & 1) || ++it_ >= SPIN_MAX, 1)) break;
#pragma unroll
      for (int i = 0; i < 4; i++)
        asm volatile("cp.async.cg.shared.global [%0], [%1], 16;"
                     ::"r"(sb + OFF_XO + ((lane >> 1) + 16 * i) * 256 + (((2 * warp + (lane & 1)) ^ ((lane >> 1) & 7)) << 4)),
                       "l"(g_xo + ((size_t)b * 64 + (lane >> 1) + 16 * i) * RS + 2 * warp + (lane & 1)) : "memory");
      asm volatile("cp.async.wait_all;" ::: "memory");
      __syncwarp();
    }
    {
      const float lo = ov - bfhi(__float_as_uint(ov));
      asm volatile("st.shared.u16 [%0], %1;" ::"r"(a_b), "h"((unsigned short)((tq & 2) ? pack2(lo, lo) : __float_as_uint(ov) >> 16)) : "memory");
    }
    nbar(1, 256);
    float d[4][4] = {};
#pragma unroll
    for (int y = 0; y < 4; y++) {
      uint32_t bq[4];
      ldsm(bq, a_bq + 64 * y);
      mma16(d[(2 * y) & 3], a[2 * y], bq[0], bq[1]); mma16(d[(2 * y + 1) & 3], a[2 * y + 1], bq[2], bq[3]);
    }
    const float r0 = ((d[0][0] + d[0][1]) + (d[1][0] + d[1][1])) + ((d[2][0] + d[2][1]) + (d[3][0] + d[3][1]));
    const float r1 = ((d[0][2] + d[0][3]) + (d[1][2] + d[1][3])) + ((d[2][2] + d[2][3]) + (d[3][2] + d[3][3]));
    if (tq == 0) stx4(p_c, pack2t(r0 * invL, r1 * invL, par));
  }
  unsigned tpub = clock();
  mbar_wait(bar0 + 8 * (XB + 4));
  const float gav = s_co[256 + (opos & 31)];
  const float gbv = s_co[288 + (lane & 4) + 2 * (lane & 1) + ((lane >> 1) & 1)];
  float4 cf[2];
#pragma unroll
  for (int s = 0; s < 2; s++) cf[s] = *(const float4*)(s_co + 32 * warp + 16 * s + 4 * tq);
  {
    uint32_t a[2][4][4];
    mbar_wait(bar0 + 8 * (FB_O + (warp >> 2)));
    const uint32_t ab = sb + OFF_O + (32 * warp + prow) * 128 + ((((lane >> 3) & 1) ^ (prow & 7)) << 4);
#pragma unroll
    for (int i = 0; i < 8; i++) ldsm_t(a[i >> 2][i & 3], (ab + (i >> 2) * 2048) ^ ((i & 3) << 5));
    uint4 v;
    const unsigned* pc = g_xc + (4 * (b >> 4) + 2 * rk + (warp >> 2)) * 256 + 64 * (warp & 3) + 2 * lane;
    uint32_t ro = ((tq >> 1) == rk ? sb : psb) + OFF_P + (8 * (tq & 1) + g) * 144 + (8 * rk + warp) * 8;
    uint32_t a_q = sb + OFF_P + (8 * (lane >> 4) + (lane & 7)) * 144;
    unsigned* p_ao = g_xao + (b >> 5) * 1024 + (opos >> 4) * 32 + (b & 16) + (opos & 15);
    PIN(ro); PIN(a_q); PINL(p_ao); PINL(pc);
    spin_until(tpub + DLY5);
    POLL {
      const unsigned long long u0 = ldx64(pc);
      v.x = (unsigned)u0; v.y = u0 >> 32;
      RETRY(X8(v))
    }
    v.z = lane & 16 ? v.x : 0u; v.w = lane & 16 ? v.y : 0u;
    if (lane & 16) v.x = v.y = 0u;
    float d[4][4] = {};
#pragma unroll
    for (int mt = 0; mt < 4; mt++) mma16(d[mt], a[0][mt], v.x, v.y);
#pragma unroll
    for (int mt = 0; mt < 4; mt++) mma16(d[mt], a[1][mt], v.z, v.w);
    float r[8];
#pragma unroll
    for (int i = 0; i < 8; i++) r[i] = d[i >> 1][2 * (i & 1)] + d[i >> 1][2 * (i & 1) + 1];
    tred<4>(r, lane, 2); tred<2>(r, lane, 1);
    st_pair((tq >> 1) == rk ? 1 : 2, ro, psb + OFF_BAR + 8 * (XB + 3), r[0], r[1]);
    __syncwarp();
    if (lane == 0) BAR_ARRIVE(XB + 3);
    if (warp == 0) {
      mbar_wait(bar0 + 8 * (XB + 3));
      float p[8];
#pragma unroll
      for (int i = 0; i < 8; i++) {
        const float4 q = lds16(a_q + i * 16);
        p[i] = (lane & 8) ? q.y + q.w : q.x + q.z;
      }
      const float t = ((p[0] + p[1]) + (p[2] + p[3])) + ((p[4] + p[5]) + (p[6] + p[7]));
      stx4(p_ao, fbits(gav * t + xv));
    }
  }
  tpub = clock();
  if (b < 112) {
    uint32_t af[2][4][4], ad[4][4];
    const uint32_t ab = sb + (32 * warp + 8 * (lane >> 4) + (lane & 7)) * 64 + ((((lane >> 3) & 1) ^ ((lane >> 1) & 3)) << 4);
    uint32_t ro = ((tq & 1) == rk ? sb : psb) + OFF_R4 + (8 * (tq >> 1) + g) * 176 + (10 * rk + warp) * 8;
    uint32_t a_q = sb + OFF_R4 + (8 * (lane >> 4) + (lane & 7)) * 176 + (lane & 8) * 10;
    uint32_t a_d = sb + OFF_D + warp * 2048 + (8 * (lane >> 4) + (lane & 7)) * 128 + ((((lane >> 3) & 1) ^ (lane & 7)) << 4);
    unsigned* p_f = g_xf + b * 512 + 64 * warp + 16 * tq + 2 * g;
    const unsigned* pa = g_xao + (g >> 1) * 1024 + 512 * rk + 64 * warp + 4 * (lane & 7);
    PIN(ro); PIN(a_q); PIN(a_d); PINL(p_f); PINL(pa);
    spin_until(tpub + DLY6);
    uint4 v[2];
    {
      bool have = false;
      POLL {
        v[0] = ldx16(pa); v[1] = ldx16(pa + 32);
        const unsigned t1 = (unsigned)clock() + WTEST;
        while (!have && (int)((unsigned)clock() - t1) < 0) {
          uint32_t ok;
          asm volatile("{.reg .pred p, q; mbarrier.test_wait.parity.shared::cta.b64 p, [%1], 0; mbarrier.test_wait.parity.shared::cta.b64 q, [%1+8], 0;\n"
                       "and.pred p, p, q; vote.sync.all.pred p, p, 0xffffffff; selp.u32 %0, 1, 0, p;}" : "=r"(ok) : "r"(bar0 + 8 * FB_G) : "memory");
          if (ok) {
#pragma unroll
            for (int i = 0; i < 8; i++) ldsm_t(af[i >> 2][i & 3], (ab + ((i & 2) ? OFF_U : OFF_G) + (i >> 2) * 1024) ^ ((i & 1) << 5));
            have = true;
          }
        }
        if (!__any_sync(~0u, (X16(v[0]) | X16(v[1])) & 1) || ++it_ >= SPIN_MAX) break;
      }
      float df[4][4] = {}, dg[2][4] = {};
      uint32_t zb[4];
      const uint32_t one = g == 0 ? 0x3F803F80u : 0u;
#pragma unroll
      for (int s = 0; s < 2; s++) {
        const uint32_t y0 = pack2(u2f(v[s].x), u2f(v[s].y)), y1 = pack2(u2f(v[s].z), u2f(v[s].w));
        const uint32_t ya[4] = {y0, one, y1, one};
        mma16(dg[s], ya, y0, y1);
        zb[2 * s] = pack2(u2f(v[s].x) * cf[s].x, u2f(v[s].y) * cf[s].y); zb[2 * s + 1] = pack2(u2f(v[s].z) * cf[s].z, u2f(v[s].w) * cf[s].w);
      }
      float st[2] = {(dg[0][2] + dg[0][3]) + (dg[1][2] + dg[1][3]), (dg[0][0] + dg[0][1]) + (dg[1][0] + dg[1][1])};
      if (!have) {
        mbar_wait(bar0 + 8 * FB_G); mbar_wait(bar0 + 8 * (FB_G + 1));
#pragma unroll
        for (int i = 0; i < 8; i++) ldsm_t(af[i >> 2][i & 3], (ab + ((i & 2) ? OFF_U : OFF_G) + (i >> 2) * 1024) ^ ((i & 1) << 5));
      }
#pragma unroll
      for (int i = 0; i < 8; i++) mma16(df[i & 3], af[i >> 2][i & 3], zb[2 * (i >> 2)], zb[2 * (i >> 2) + 1]);
#pragma unroll
      for (int o2 = 1; o2 < 4; o2 <<= 1) { st[0] += __shfl_xor_sync(~0u, st[0], o2); st[1] += __shfl_xor_sync(~0u, st[1], o2); }
#pragma unroll
      for (int o2 = 4; o2 < 32; o2 <<= 1) st[1] += __shfl_xor_sync(~0u, st[1], o2);
      float r[8];
#pragma unroll
      for (int i = 0; i < 8; i++) r[i] = df[i >> 1][2 * (i & 1)] + df[i >> 1][2 * (i & 1) + 1];
      tred<4>(r, lane, 2); tred<2>(r, lane, 1);
      const int md = (tq & 1) == rk ? 1 : 2;
      st_pair(md, ro, psb + OFF_BAR + 8 * (XB + 5), r[0], r[1]);
      st_pair(lane < 2 ? md : 0, ro + 16 * 176, psb + OFF_BAR + 8 * (XB + 5), st[0], st[1]);
      __syncwarp();
      if (lane == 0) BAR_ARRIVE(XB + 5);
      mbar_wait(bar0 + 8 * FB_D);
#pragma unroll
      for (int mt = 0; mt < 4; mt++)
        ldsm_t(ad[mt], a_d ^ (mt << 5));
    }
    mbar_wait(bar0 + 8 * (XB + 5));
    {
      float4 q[5], u[8];
#pragma unroll
      for (int i = 0; i < 5; i++) q[i] = lds16(a_q + i * 16);
#pragma unroll
      for (int i = 0; i < 8; i++) u[i] = *(const float4*)(smem + OFF_R4 + 16 * 176 + (i >> 2) * 80 + (i & 3) * 16);
      float p[6] = {((q[0].x + q[0].z) + (q[1].x + q[1].z)) + ((q[2].x + q[2].z) + (q[3].x + q[3].z)), q[4].x, q[4].z,
                    ((q[0].y + q[0].w) + (q[1].y + q[1].w)) + ((q[2].y + q[2].w) + (q[3].y + q[3].w)), q[4].y, q[4].w};
      tred<3>(p, lane, 8);
      const float P = p[0], A1 = p[1], A2 = p[2];
      const float mean = (((u[0].x + u[0].z) + (u[1].x + u[1].z)) + ((u[2].x + u[2].z) + (u[3].x + u[3].z)) +
                          ((u[4].x + u[4].z) + (u[5].x + u[5].z)) + ((u[6].x + u[6].z) + (u[7].x + u[7].z))) * (1.f / 512.f);
      const float sq = (((u[0].y + u[0].w) + (u[1].y + u[1].w)) + ((u[2].y + u[2].w) + (u[3].y + u[3].w)) +
                         ((u[4].y + u[4].w) + (u[5].y + u[5].w)) + ((u[6].y + u[6].w) + (u[7].y + u[7].w))) * (1.f / 512.f);
      float rstd;
      asm("rsqrt.approx.ftz.f32 %0, %1;" : "=f"(rstd) : "f"(fmaxf(sq - mean * mean, 0.f) + 1e-5f));
      const float gg = bfr(rstd * (P - mean * A1) + A2);
      const float uu = __shfl_xor_sync(~0u, gg, 16);
      const float hh = bfr(gg * rcp(1.f + ex2(gg * (-2.302208198f - 0.1029432397f * gg * gg)))) * uu;
      const uint32_t hw = pack2(hh, __shfl_down_sync(~0u, hh, 1));
      const uint32_t b0 = __shfl_sync(~0u, hw, 2 * tq), b1 = __shfl_sync(~0u, hw, 2 * tq + 8);
      float f0 = 0, f1 = 0;
#pragma unroll
      for (int mt = 0; mt < 4; mt++) {
        float dd[4] = {0, 0, 0, 0};
        mma16(dd, ad[mt], b0, b1);
        if (tq == mt) { f0 = dd[0]; f1 = dd[2]; }
      }
      stx8(p_f, make_uint2(fbits(f0), fbits(f1)));
    }
    tpub = clock();
    if (b < 64 && warp == (b >> 3)) {
      const uint4 y = (b & 4) ? v[1] : v[0];
      float a4[4] = {u2f(y.x), u2f(y.y), u2f(y.z), u2f(y.w)};
      tred<2>(a4, lane, 16); tred<1>(a4, lane, 8);
      a4[0] += __shfl_xor_sync(~0u, a4[0], 4);
      if (!(lane & 4)) s_sm[416 + 8 * (lane >> 4) + 2 * tq + ((lane >> 3) & 1)] = a4[0];
      if (warp == 7) nbar_arrive(2, 256);
    } else if (b < 64 && warp == 7) nbar_arrive(2, 256);
    if (b < 64 && warp < 7) {
      uint4 v;
      const unsigned* pf = g_xf + (tid >> 1) * 512 + 8 * ob + 4 * (tid & 1);
      const int col = 16 * (ob >> 1) + 4 * (ob & 1) + ((tid >> 1) & 3) + 8 * (tid & 1);
      bf16* po = out + col;
      PINL(po); PINL(pf);
      spin_until(tpub + DLY7);
      POLL { v = ldx16(pf); RETRY(X16(v)) }
      float f[4] = {u2f(v.x), u2f(v.y), u2f(v.z), u2f(v.w)};
      tred<2>(f, lane, 16); tred<1>(f, lane, 8);
      f[0] += __shfl_xor_sync(~0u, f[0], 4); f[0] += __shfl_xor_sync(~0u, f[0], 2);
      if (!(lane & 6)) s_sm[352 + warp * 8 + 4 * (lane & 1) + (lane >> 3)] = f[0];
      nbar(2, 256);
      if (tid < 8) {
        const float* q = s_sm + 352 + tid;
        const float t = ((q[0] + q[8]) + (q[16] + q[24])) + ((q[32] + q[40]) + q[48]);
        *po = __float2bfloat16(s_sm[416 + (col & 15)] + bfr(gbv * bfr(t)));
        if (b == 0 && tid == 0) stx4(&g_epoch, epoch + 1);
      }
    }
  }
}

__global__ void __cluster_dims__(2, 1, 1) __launch_bounds__(384, 1)
fused_kernel(const bf16* __restrict__ x, const bf16* __restrict__ cvec, const bf16* __restrict__ w_mod, bf16* __restrict__ out,
             Scratch* __restrict__ scr, const __grid_constant__ TMaps tms) {
  extern __shared__ __align__(1024) unsigned char smem[];
  const int tid = threadIdx.x, warp = __shfl_sync(~0u, tid >> 5, 0), lane = tid & 31;
  const int b = blockIdx.x, rk = b & 1, pr = b >> 1, hd = b >> 2;
  uint32_t sb = s2u(smem), bar0 = sb + OFF_BAR;

  unsigned gt_start;
  asm volatile("mov.u32 %0, %%globaltimer_lo;" : "=r"(gt_start));
  const int g = lane >> 2, tq = lane & 3;
  const int arow = 64 * (b >> 4) + ((tid & 255) >> 3);
  uint4 wm0, wm1;
  uint32_t c0w, c1w;
  if (warp < 8) {
    const bf16* wa = w_mod + (size_t)arow * 3072 + (lane & 4) * 128 + 32 * (b & 15) + 8 * tq;
    wm0 = ldx16(wa); wm1 = ldx16(wa + 32 * 3072);
    c0w = ldc4(cvec + (arow & ~1)); c1w = ldc4(cvec + (arow & ~1) + 32);
  }
  const unsigned t_off = gt_start + RATE_T0;
  if (warp == 11) {
    if (lane == 0) {
#pragma unroll
      for (int i = 0; i < FB_KV; i++) { BAR_INIT(i, 1); BAR_ARM(i, 16384); }
    }
    __syncwarp();
    asm volatile("fence.mbarrier_init.release.cluster;" ::: "memory");
    asm volatile("barrier.cluster.arrive.relaxed.aligned;" ::: "memory");
#pragma unroll 1
    for (int i = 0; i < FB_KV; i++) {
      if (i >= HWIN) mbar_wait(bar0 + 8 * (i - HWIN));
      wait_until(t_off + (i < 4 ? 2 * i + ((b >> 1) & 1) : 4 * i - 8 + (b & 3)) * (RATE_H / 4));
      if (lane == 0) {
        if (i < 4) tma3d(sb + OFF_WQ + i * 16384, &tms.m[0], bar0 + 8 * i, 0, i * 128, 2 * hd + rk);
        else tma3d(sb + OFF_WQ + i * 16384, &tms.m[1], bar0 + 8 * i, 0, (b & 3) * 128 + (i - 4) * 64, 2 * hd);
      }
      __syncwarp();
    }
  }
  if (warp == 10) {
    const uint4 xa = ldc16(x + 16 * lane), xb = ldc16(x + 16 * lane + 8);
    const unsigned ep = ldc4(&g_epoch);
    float xv[16] = {bflo(xa.x), bfhi(xa.x), bflo(xa.y), bfhi(xa.y), bflo(xa.z), bfhi(xa.z), bflo(xa.w), bfhi(xa.w),
                    bflo(xb.x), bfhi(xb.x), bflo(xb.y), bfhi(xb.y), bflo(xb.z), bfhi(xb.z), bflo(xb.w), bfhi(xb.w)};
    float s = 0;
#pragma unroll
    for (int i = 0; i < 16; i++) s += xv[i];
#pragma unroll
    for (int o = 16; o; o >>= 1) s += __shfl_xor_sync(~0u, s, o);
    const float mean = s * (1.f / 512.f);
    s = 0;
#pragma unroll
    for (int i = 0; i < 16; i++) { xv[i] -= mean; s += xv[i] * xv[i]; }
#pragma unroll
    for (int o = 16; o; o >>= 1) s += __shfl_xor_sync(~0u, s, o);
    const float rstd = rsqrtf(s * (1.f / 512.f) + 1e-5f);
    if ((lane >> 1) == (b & 15))
#pragma unroll
      for (int i = 0; i < 4; i++)
        *(float4*)(smem + OFF_SM + (256 + (lane & 1) * 16 + 4 * i) * 4) = make_float4(xv[4 * i] * rstd, xv[4 * i + 1] * rstd, xv[4 * i + 2] * rstd, xv[4 * i + 3] * rstd);
    if (lane == 0) *(volatile unsigned*)(smem + OFF_MASK + 8) = ep;
    nbar_arrive(1, 288);
  }
  if (warp >= 8) {
    asm volatile("setmaxnreg.dec.sync.aligned.u32 72;");
    if (tid == 288) {
#pragma unroll
      for (int q = FB_KV; q < FB_KV + 16; q++) { BAR_INIT(q, 1); BAR_ARM(q, 32768); }
    }
    if (tid == 320) {
#pragma unroll
      for (int q = 0; q <= 13 + NSLOT; q++) BAR_INIT(EB + q, q == 0 ? 4 : q < 5 ? 16 : q < 16 ? 12 : 6);
    }
    if (tid == 256) {
#pragma unroll
      for (int q = FB_MOD; q <= FB_D; q++) { BAR_INIT(q, 1); BAR_ARM(q, 16384); }
      BAR_INIT(QB, 9); BAR_ARM(QB, 1024);
#pragma unroll
      for (int q = 0; q < 7; q++) BAR_INIT(XB + q, q == 2 ? 256 : q == 5 || q == 3 ? 9 : 1);
      BAR_ARM(XB + 3, 1024);
      BAR_ARM(XB + 5, 1024 + 64 + 512);
      *(volatile unsigned long long*)(smem + OFF_MASK) = 0;
    }
    if (warp != 11) {
      __syncwarp();
      asm volatile("fence.mbarrier_init.release.cluster;" ::: "memory");
      __threadfence_block();
      asm volatile("barrier.cluster.arrive.relaxed.aligned;" ::: "memory");
    }
    if (warp == 11) {
      asm volatile("barrier.cluster.wait.acquire.aligned;" ::: "memory");
      const unsigned epoch = *(volatile unsigned*)(smem + OFF_MASK + 8), par = (epoch + 1) & 1;
      mbar_wait(bar0 + 8 * (FB_KV + 15));
      for (int it = 0; ldx4(scr->cnt + 96 + 32 * (b >> 6)) != (epoch + 1) * 64 && it < SPIN_MAX; it++) {}
      uint4 hh;
      POLL { hh = ldx16(g_ml + (b >> 2) * 64 + 2 * lane); RETRY(X16(hh)) }
      int mi = __float_as_int(fmaxf(u2f(hh.x), u2f(hh.z)));
      mi ^= (mi >> 31) & 0x7fffffff;
      mi = __reduce_max_sync(~0u, mi);
      mi ^= (mi >> 31) & 0x7fffffff;
      const float M = __int_as_float(mi);
      const uint32_t wp = pack2(ex2(u2f(hh.x) - M), ex2(u2f(hh.z) - M));
      float L = bflo(wp) * u2f(hh.y) + bfhi(wp) * u2f(hh.w);
#pragma unroll
      for (int o2 = 16; o2; o2 >>= 1) L += __shfl_xor_sync(~0u, L, o2);
      *(uint32_t*)(smem + OFF_RA + lane * 4) = wp;
      if (lane == 0) *(float*)(smem + OFF_RA + 128) = rcp(L);
      __syncwarp();
      if (lane == 0) BAR_ARRIVE(XB + 6);
    }
    if (warp == 10) {
      if (lane < 8) asm volatile("prefetch.tensormap [%0];" ::"l"(&tms.m[lane + 1]) : "memory");
      asm volatile("barrier.cluster.wait.acquire.aligned;" ::: "memory");
      const unsigned epoch = *(volatile unsigned*)(smem + OFF_MASK + 8);
#pragma unroll 1
      for (int e = 0; e < 2; e++) {
        for (int it = 0; ldx4(scr->cnt + (e ? 2 + rk : 1)) != (epoch + 1) * (e ? 64 : 128) && it < SPIN_MAX; it++) {}
        if (lane == 0) BAR_ARRIVE(XB + e);
      }
      mbar_wait(bar0 + 8 * (FB_KV + 14));
      unsigned long long m = 0;
#pragma unroll 1
      for (int it = 0; ~m && it < SPIN_MAX; it++) {
        m = ldx64(scr->cnt + 32 + 32 * (b >> 6)) ^ ((epoch & 1) ? ~0ull : 0ull);
        if (lane == 0) *(volatile unsigned long long*)(smem + OFF_MASK) = m;
      }
    }
    if (warp == 9) {
      asm volatile("barrier.cluster.wait.acquire.aligned;" ::: "memory");
      const unsigned epoch = *(volatile unsigned*)(smem + OFF_MASK + 8);
      const unsigned par = (epoch + 1) & 1, inv = par ^ 1;
      const uint4 inv4 = make_uint4(inv, inv, inv, inv);
      mbar_wait(bar0 + 8 * FB_KV);
#pragma unroll 2
      for (int k = 0; k < 8; k++) {
        const uint32_t cp = ldc4(cvec + 2 * (lane + 32 * k));
        *(uint32_t*)(smem + OFF_SILU + (lane + 32 * k) * 4) = pack2(silu_bf(bflo(cp)), silu_bf(bfhi(cp)));
      }
      __syncwarp();
      mbar_wait(bar0 + 8 * FB_MOD);
      const uint32_t ab = sb + OFF_MOD + (8 * (lane >> 4) + (lane & 7)) * 32 + ((((lane >> 3) ^ (lane >> 2)) & 1) << 4);
      float d[4][4] = {};
#pragma unroll 2
      for (int s4 = 0; s4 < 8; s4++)
#pragma unroll
        for (int s = 0; s < 4; s++) {
          uint32_t a[4];
          const uint32_t* ps = (const uint32_t*)(smem + OFF_SILU) + 32 * s4 + 8 * s + tq;
          ldsm_t(a, ab + (4 * s4 + s) * 512); mma16(d[s], a, ps[0], ps[4]);
        }
      const float t = (tq & 1) ? (d[0][2] + d[1][2]) + (d[2][2] + d[3][2]) : (d[0][0] + d[1][0]) + (d[2][0] + d[3][0]);
      if (tq < 2) stx4(g_xm + b * 16 + 2 * (g & 6) + 2 * tq + (g & 1), fbits(bfr(t)));
      __syncwarp();
      if (lane == 0) CNT_ADD(6);
      mbar_wait(bar0 + 8 * (FB_KV + 8));
      if (lane < 16) stx16(g_xc + (b >> 2) * 256 + (lane >> 1) * 32 + (b & 3) * 8 + (lane & 1) * 4, inv4);
      if (lane < 8) stx16(g_xao + (b >> 5) * 1024 + (b & 15) * 64 + (lane & 4) * 8 + (b & 16) + (lane & 3) * 4, inv4);
      if (b < 112)
#pragma unroll 1
        for (int k = 0; k < 4; k++) stx16(g_xf + b * 512 + (lane + 32 * k) * 4, inv4);
      nbar_arrive(2, 288);
      for (int it = 0; ldx4(scr->cnt + 6) != (epoch + 1) * 128 && it < SPIN_MAX; it++) __nanosleep(100);
      {
        uint4 sv[2], cb[2];
        unsigned ga, gb;
        POLL {
#pragma unroll
          for (int k = 0; k < 2; k++) { sv[k] = ldx16(g_xm + 512 + 256 * rk + 4 * (lane + 32 * k)); cb[k] = ldx16(g_xm + 1024 + 256 * rk + 4 * (lane + 32 * k)); }
          ga = ldx4(g_xm + (b & 15) * 32 + lane); gb = ldx4(g_xm + 1536 + 256 * rk + 8 * (pr & 31) + (lane & 7));
          RETRY(X16(sv[0]) | X16(sv[1]) | X16(cb[0]) | X16(cb[1]) | lop_x3(ga, gb, par))
        }
#pragma unroll
        for (int k = 0; k < 2; k++) {
          const float c0 = bfr(1.f + bfhi(cb[k].x)), c1 = bfr(1.f + bfhi(cb[k].y)), c2 = bfr(1.f + bfhi(cb[k].z)), c3 = bfr(1.f + bfhi(cb[k].w));
          *(float4*)(smem + OFF_CO + (lane + 32 * k) * 16) = make_float4(c0, c1, c2, c3);
          uint2* pb = (uint2*)(smem + OFF_BP) + lane + 32 * k;
          pb[0] = make_uint2(pack2(c0, c1), pack2(c2, c3));
          pb[64] = make_uint2(__byte_perm(sv[k].x, sv[k].y, 0x7632), __byte_perm(sv[k].z, sv[k].w, 0x7632));
        }
        *(float*)(smem + OFF_CO + 1024 + lane * 4) = bfhi(ga);
        *(float*)(smem + OFF_CO + 1152 + lane * 4) = bfhi(gb);
      }
      __syncwarp();
      if (lane == 0) BAR_ARRIVE(XB + 4);
    }
    if (warp == 8) {
      const unsigned stag = ((pr * SMUL) & 63) * RATE_NS >> 6;
      unsigned tnext = t_off + 4 * RATE_H;
      asm volatile("barrier.cluster.wait.acquire.aligned;" ::: "memory");
#pragma unroll 1
      for (int k = 0; k < 24; k++) {
        const int code = (k < 12 ? ORDER0 >> (5 * k) : ORDER1 >> (5 * (k - 12))) & 31;
        const bool kv = code < 16;
        const int n = code, w = code - 16;
        if (!kv && w >= 5 && b >= 112) break;
        if (kv) mbar_wait(bar0 + 8 * (FB_KV + n - (n < 6 ? EWIN : KVWIN)));
        if (k >= TAIL_K) mbar_wait(bar0 + 8 * (FB_KV + (int)((ORDER1 >> (5 * (k - 12 - ((WINS >> (4 * (k - TAIL_K))) & 15)))) & 31)));
        const int e = kv ? (n == 3 ? 2 : n == 5 ? 1 : n) : w == 0 ? 0 : w < 5 ? 16 + ((w - 1) >> 1) : w == 7 ? 19 : 18;
        if (e != 1 && k) mbar_wait(bar0 + 8 * (EB + e));
        wait_until(tnext + stag);
        tnext += k > TAIL_K ? RATE_TL : k < 4 ? RATE_E : RATE_NS;
        if (lane == 0) {
          if (kv)
            asm volatile("cp.async.bulk.tensor.3d.shared::cluster.global.mbarrier::complete_tx::bytes.multicast::cluster.L2::cache_hint [%0], [%1, {%3, %4, %5}], [%2], %6, %7;"
                         ::"r"(sb + (n % NSLOT) * SLOT + rk * 16384), "l"(&tms.m[2]), "r"(bar0 + 8 * (FB_KV + n)), "r"(0), "r"(((n >> 1) * 64 + pr) * 64),
                           "r"(4 * (n & 1) + 2 * rk), "h"((unsigned short)3), "l"(stream_policy()) : "memory");
          else {
            tma3d(sb + (w == 0 ? OFF_MOD : w < 5 ? OFF_UV + (w - 1) * 16384 : w == 5 ? OFF_G : w == 6 ? OFF_U : OFF_D),
                  &tms.m[w == 0 ? 3 : w < 3 ? 4 : w < 5 ? 5 : w + 1], bar0 + 8 * (FB_MOD + w),
                  w == 0 ? 1024 + b * 16 : w < 3 || w == 7 ? 0 : w < 5 ? (pr & 7) * 64 : pr * 32, w == 7 ? b * 16 : w == 1 || w == 2 ? (b & 3) * 128 + (w - 1) * 64 : 0,
                  w == 1 || w == 2 ? 2 * hd : w == 3 || w == 4 ? (b >> 4) * 4 + 2 * rk + w - 3 : w == 5 || w == 6 ? rk : 0);
          }
        }
        __syncwarp();
      }
    }
    if (b < 112) {
      const int mt = warp & 1, dd = (warp >> 1) & 1;
      mbar_wait(bar0 + 8 * (XB + 4));
      const uint32_t ab = sb + (mt ? OFF_U : OFF_G) + (8 * (lane >> 4) + (lane & 7)) * 64 + (((2 * dd + ((lane >> 3) & 1)) ^ ((lane >> 1) & 3)) << 4);
      uint32_t base;
      asm volatile("mapa.shared::cluster.u32 %0, %1, %2;" : "=r"(base) : "r"(sb), "r"(dd));
      uint2 bb[16];
#pragma unroll
      for (int s = 0; s < 16; s++) bb[s] = *(const uint2*)(smem + OFF_BP + (g & 1) * 512 + (4 * s + tq) * 8);
      mbar_wait(bar0 + 8 * (FB_G + mt));
      float e[4][4] = {};
#pragma unroll
      for (int s = 0; s < 16; s++) { uint32_t a[4]; ldsm_t(a, ab + s * 1024); mma16(e[s & 3], a, bb[s].x, bb[s].y); }
      float r[4];
#pragma unroll
      for (int i = 0; i < 4; i++) r[i] = (e[0][i] + e[1][i]) + (e[2][i] + e[3][i]);
      if (tq < 2) st_async2(base + OFF_R4 + (8 * mt + g) * 176 + (10 * rk + 8 + tq) * 8, base + OFF_BAR + 8 * (XB + 5), tq ? r[1] : r[0], tq ? r[3] : r[2]);
    }
    return;
  }

  float* s_sm = (float*)(smem + OFF_SM);
  unsigned par, epoch;
  uint32_t rsb;
  {
    float* s_r4 = (float*)(smem + OFF_R4);
    asm volatile("barrier.cluster.arrive.relaxed.aligned;" ::: "memory");
    asm volatile("mapa.shared::cluster.u32 %0, %1, %2;" : "=r"(rsb) : "r"(sb), "r"(rk ^ 1));
    const float c0 = (arow & 1) ? bfhi(c0w) : bflo(c0w), c1 = (arow & 1) ? bfhi(c1w) : bflo(c1w);
    float acc[8] = {0, 0, 0, 0, 0, 0, 0, 0};
    fma8(acc, wm0, silu_bf(c0)); fma8(acc, wm1, silu_bf(c1));
    tred<4>(acc, lane, 8); tred<2>(acc, lane, 16);
    *(float2*)(s_r4 + warp * 64 + 8 * (lane & 7) + ((lane >> 1) & 4) + ((lane >> 3) & 2)) = make_float2(acc[0], acc[1]);
    nbar(1, 288);
    epoch = *(volatile unsigned*)(smem + OFF_MASK + 8);
    par = (epoch + 1) & 1;
    if (warp == 0) {
      float t = 0.f, ca = b < 16 ? 1.f : 0.f;
#pragma unroll
      for (int w = 0; w < 8; w++) { t += s_r4[w * 64 + lane]; ca += s_r4[w * 64 + 32 + lane]; }
      t += ca * s_sm[256 + lane];
      const float nb = __shfl_down_sync(~0u, t, 1);
      const uint32_t w0 = lane < 8 ? pack2t(t, nb, par) : pack2(t, nb);
      const uint32_t w1 = __shfl_down_sync(~0u, w0, 8), w2 = __shfl_down_sync(~0u, w0, 16), w3 = __shfl_down_sync(~0u, w0, 24);
      if (lane < 8 && !(lane & 1)) stx16(g_h + (b >> 5) * 512 + (b & 15) * 32 + (b & 16) + 2 * lane, make_uint4(w0, w1, w2, w3));
      __syncwarp();
      if (lane == 0) CNT_ADD(1);
    }
  }
  asm volatile("barrier.cluster.wait.acquire.aligned;" ::: "memory");
  {
    uint32_t a[4][4][4];
    mbar_wait(bar0 + 8 * (warp >> 1));
    const uint32_t ab = sb + OFF_WQ + (64 * warp + 8 * (lane >> 4) + (lane & 7)) * 128;
#pragma unroll
    for (int s = 0; s < 4; s++)
#pragma unroll
      for (int mt = 0; mt < 4; mt++) ldsm_t(a[s][mt], ab + s * 2048 + (((2 * mt + ((lane >> 3) & 1)) ^ (lane & 7)) << 4));
    uint4 v0, v1;
    const unsigned* ph = g_h + (g >> 1) * 512 + 64 * warp + 4 * (lane & 7);
    uint32_t off = OFF_B + warp * 272 + (32 * rk + 8 * tq + (lane & 4)) * 4;
    PIN(off); PINL(ph);
    mbar_wait(bar0 + 8 * XB);
    POLL { v0 = ldx16(ph); v1 = ldx16(ph + 32); RETRY(lop_x3(v0.x, v1.x, par)) }
    float d[4][4] = {};
#pragma unroll
    for (int mt = 0; mt < 4; mt++) {
      mma16(d[mt], a[0][mt], v0.x, v0.y); mma16(d[mt], a[1][mt], v0.z, v0.w);
      mma16(d[mt], a[2][mt], v1.x, v1.y); mma16(d[mt], a[3][mt], v1.z, v1.w);
    }
    float r[8];
#pragma unroll
    for (int mt = 0; mt < 4; mt++) { r[2 * mt] = d[mt][0] + d[mt][1]; r[2 * mt + 1] = d[mt][2] + d[mt][3]; }
    tred<4>(r, lane, 2); tred<2>(r, lane, 1);
    const float rc = __shfl_xor_sync(~0u, (lane & 4) ? r[0] : r[1], 4);
    const uint32_t wd = (lane & 4) ? pack2(rc, r[1]) : pack2(r[0], rc);
    const uint32_t w1 = __shfl_down_sync(~0u, wd, 8), w2 = __shfl_down_sync(~0u, wd, 16), w3 = __shfl_down_sync(~0u, wd, 24);
    asm volatile("{.reg .pred p; setp.lt.s32 p, %7, 8; @p st.shared.v4.b32 [%0], {%2,%3,%4,%5};\n"
                 "@p st.async.shared::cluster.mbarrier::complete_tx::bytes.v4.b32 [%1], {%2,%3,%4,%5}, [%6];}"
                 ::"r"(sb + off), "r"(rsb + off), "r"(wd), "r"(w1), "r"(w2), "r"(w3), "r"(rsb + OFF_BAR + 8 * QB), "r"(lane) : "memory");
    __syncwarp();
    arrive2(bar0 + 8 * QB, 0, lane == 0, false);
    arrive2(bar0 + 8 * (EB + 2), rsb + OFF_BAR + 8 * (EB + 2), lane == 0, lane == 0);
  }
  {
    uint32_t a[8][4];
    uint32_t a_bq = sb + OFF_B + (lane & 7) * 272 + (lane >> 3) * 16;
    unsigned* p_qa = g_qa + b * 64 + 8 * warp + 4 * lane;
    PIN(a_bq); PINL(p_qa);
    mbar_wait(bar0 + 8 * (FB_UK + (warp >> 2)));
    const uint32_t ab = sb + OFF_WUK + (warp >> 2) * 16384 + (16 * (warp & 3) + (lane & 15)) * 128;
#pragma unroll
    for (int s = 0; s < 8; s++) ldsm(a[s], ab + (s >> 2) * 8192 + (((2 * (s & 3) + (lane >> 4)) ^ (lane & 7)) << 4));
    mbar_wait(bar0 + 8 * QB);
    float d[4][4] = {};
#pragma unroll
    for (int y = 0; y < 4; y++) {
      uint32_t bq[4];
      ldsm(bq, a_bq + 64 * y);
      mma16(d[(2 * y) & 3], a[2 * y], bq[0], bq[1]); mma16(d[(2 * y + 1) & 3], a[2 * y + 1], bq[2], bq[3]);
    }
    float r[2] = {((d[0][0] + d[0][1]) + (d[1][0] + d[1][1])) + ((d[2][0] + d[2][1]) + (d[3][0] + d[3][1])),
                  ((d[0][2] + d[0][3]) + (d[1][2] + d[1][3])) + ((d[2][2] + d[2][3]) + (d[3][2] + d[3][3]))};
    tred<1>(r, lane, 1);
    r[0] += __shfl_xor_sync(~0u, r[0], 2);
    const float nb = __shfl_xor_sync(~0u, r[0], 4);
    const uint32_t w0 = lane < 8 ? pack2t(r[0], nb, par) : pack2(r[0], nb);
    const uint32_t w1 = __shfl_down_sync(~0u, w0, 8), w2 = __shfl_down_sync(~0u, w0, 16), w3 = __shfl_down_sync(~0u, w0, 24);
    if (lane < 2) stx16(p_qa, make_uint4(w0, w1, w2, w3));
    arrive2(bar0 + 8 * (EB + 4), rsb + OFF_BAR + 8 * (EB + 4), lane == 0, lane == 0);
  }
  {
    if (warp) nbar_arrive(3, 256); else { nbar(3, 256); if (lane == 0) CNT_ADD(2 + (b >> 6)); }
    asm volatile("setmaxnreg.inc.sync.aligned.u32 216;");
    const unsigned* pq = g_qa + rk * 4096 + tid * 4;
    uint32_t a_q = sb + OFF_Q + ((tid & 63) >> 3) * 2048 + (tid >> 6) * 128 + (((tid & 7) ^ (tid >> 6)) << 4);
    PINL(pq); PIN(a_q);
    mbar_wait(bar0 + 8 * (XB + 1));
    uint4 v[4];
    POLL {
#pragma unroll
      for (int k = 0; k < 4; k++) v[k] = ldx16(pq + 1024 * k);
      RETRY(lop_x3(v[0].x, v[1].x, par) | lop_x3(v[2].x, v[3].x, par))
    }
#pragma unroll
    for (int k = 0; k < 4; k++)
      asm volatile("st.shared.v4.b32 [%0], {%1,%2,%3,%4};" ::"r"((a_q + k * 512) ^ ((k & 1) << 6)), "r"(v[k].x), "r"(v[k].y), "r"(v[k].z), "r"(v[k].w) : "memory");
    if (warp >= 4) nbar_arrive(1, 256); else nbar(1, 256);
  }
  sb = __shfl_sync(~0u, sb, 0); bar0 = sb + OFF_BAR;
  if (warp < 4) {
    uint32_t qf[32][4];
#pragma unroll
    for (int s = 0; s < 32; s++) ldsm(qf[s], sb + OFF_Q + (s >> 2) * 2048 + (lane & 15) * 128 + (((2 * (s & 3) + (lane >> 4)) ^ (lane & 7)) << 4));
    float l0 = 0.f, l1 = 0.f, m0 = -1e30f, m1 = -1e30f;
    const float sc = 0.08838834764831845f * 1.4426950408889634f;
    const uint32_t kofs = (16 * warp + 8 * (lane >> 4) + (lane & 7)) * 128 + ((((lane >> 3) & 1) ^ (lane & 7)) << 4);
    uint32_t st = sb;
#pragma unroll 1
    for (int t = 0; t < 8; t++) {
      float sa[4][4] = {};
#pragma unroll
      for (int hf = 0; hf < 2; hf++) {
        const int n = 2 * t + hf;
        mbar_wait(bar0 + 8 * (FB_KV + n));
        uint32_t kf[16][4];
#pragma unroll
        for (int y = 0; y < 16; y++) ldsm(kf[y], st + (y >> 2) * 8192 + (kofs ^ ((y & 3) << 5)));
#pragma unroll
        for (int y = 0; y < 16; y++) {
          mma16(sa[(2 * y) & 3], qf[16 * hf + y], kf[y][0], kf[y][1]); mma16(sa[((2 * y) & 3) + 1], qf[16 * hf + y], kf[y][2], kf[y][3]);
        }
        __syncwarp();
        arrive2(bar0 + 8 * (EB + NSLOT + n), rsb + OFF_BAR + 8 * (EB + NSLOT + n), lane == 0 && n < 14, lane == 0 && n < 16 - NSLOT);
        if (hf == 0) arrive2(bar0 + 8 * EB, 0, lane == 0 && t == 0, false);
        st = st + SLOT == sb + NSLOT * SLOT ? sb : st + SLOT;
      }
#pragma unroll
      for (int i = 0; i < 4; i++) { sa[0][i] = (sa[0][i] + sa[2][i]) * sc; sa[1][i] = (sa[1][i] + sa[3][i]) * sc; }
      float cm[2] = {fmaxf(fmaxf(sa[0][0], sa[0][1]), fmaxf(sa[1][0], sa[1][1])), fmaxf(fmaxf(sa[0][2], sa[0][3]), fmaxf(sa[1][2], sa[1][3]))};
      tmax<1>(cm, lane, 1);
      cm[0] = fmaxf(cm[0], __shfl_xor_sync(~0u, cm[0], 2));
      float* pm = s_sm + (t & 1) * 64;
      if (tq < 2) pm[(g + 8 * tq) * 4 + warp] = cm[0];
      if (t >= 2) nbar(6 + (t & 1), 256); else nbar(3, 128);
      const float4 a0 = *(const float4*)(pm + g * 4), b0 = *(const float4*)(pm + g * 4 + 32);
      const float n0 = fmaxf(fmaxf(fmaxf(a0.x, a0.y), fmaxf(a0.z, a0.w)), m0), n1 = fmaxf(fmaxf(fmaxf(b0.x, b0.y), fmaxf(b0.z, b0.w)), m1);
      uint32_t pk[4];
#pragma unroll
      for (int i = 0; i < 2; i++) { pk[2 * i] = pack2(ex2(sa[i][0] - n0), ex2(sa[i][1] - n0)); pk[2 * i + 1] = pack2(ex2(sa[i][2] - n1), ex2(sa[i][3] - n1)); }
      *(uint4*)(smem + OFF_P + (t & 1) * 2048 + tid * 16) = make_uint4(pk[0], pk[1], pk[2], pk[3]);
      const float al0 = ex2(m0 - n0), al1 = ex2(m1 - n1);
      if (tid < 32 && tq == 0) *(float2*)(s_sm + 192 + (t & 1) * 16 + 2 * g) = make_float2(al0, al1);
      nbar_arrive(4 + (t & 1), 256);
      m0 = n0; m1 = n1;
      l0 = l0 * al0 + (bflo(pk[0]) + bfhi(pk[0])) + (bflo(pk[2]) + bfhi(pk[2]));
      l1 = l1 * al1 + (bflo(pk[1]) + bfhi(pk[1])) + (bflo(pk[3]) + bfhi(pk[3]));
    }
    float lr[2] = {l0, l1};
    tred<1>(lr, lane, 1);
    lr[0] += __shfl_xor_sync(~0u, lr[0], 2);
    if (tq < 2) s_sm[128 + (g + 8 * tq) * 4 + warp] = lr[0];
    nbar(3, 128);
    if (warp == 0 && tq < 2) {
      const float4 a0 = *(const float4*)(s_sm + 128 + (g + 8 * tq) * 4);
      stx8(g_ml + (16 * rk + g + 8 * tq) * 64 + pr, make_uint2(fbits(tq ? m1 : m0), fbits((a0.x + a0.y) + (a0.z + a0.w))));
    }
    if (warp == 0) { __syncwarp(); if (lane == 0) CNT_ADD(96 + 32 * rk); }
    nbar(2, 288);
    if (tid == 0) asm volatile("red.relaxed.gpu.global.xor.b64 [%0], %1;" ::"l"(scr->cnt + 32 + 32 * rk), "l"(1ull << pr) : "memory");
  } else {
    float o[16][4] = {};
    const uint32_t vofs = (warp & 1) * 16384 + (lane & 15) * 128 + (((lane >> 4) ^ (lane & 7)) << 4);
    const int hf = (warp >> 1) & 1;
    uint32_t st = sb + hf * SLOT;
    auto pv = [&](const int t, auto np) {
      constexpr int npre = decltype(np)::value;
      uint32_t vf[4][8][4];
      const int n = 2 * t + hf;
      mbar_wait(bar0 + 8 * (FB_KV + n));
#pragma unroll
      for (int s = 0; s < npre; s++)
#pragma unroll
        for (int y = 0; y < 8; y++) ldsm_t(vf[s][y], st + (y >> 2) * 8192 + s * 2048 + (vofs ^ ((y & 3) << 5)));
      nbar(4 + (t & 1), 256);
      const float2 al = *(const float2*)(s_sm + 192 + (t & 1) * 16 + 2 * g);
      uint4 pf[4];
#pragma unroll
      for (int s = 0; s < 4; s++) pf[s] = *(const uint4*)(smem + OFF_P + (t & 1) * 2048 + s * 512 + lane * 16);
      if (t < 6) nbar_arrive(6 + (t & 1), 256);
#pragma unroll
      for (int s = npre; s < 4; s++)
#pragma unroll
        for (int y = 0; y < 8; y++) ldsm_t(vf[s][y], st + (y >> 2) * 8192 + s * 2048 + (vofs ^ ((y & 3) << 5)));
#pragma unroll
      for (int nt = 0; nt < 16; nt++) { o[nt][0] *= al.x; o[nt][1] *= al.x; o[nt][2] *= al.y; o[nt][3] *= al.y; }
#pragma unroll
      for (int s = 0; s < 4; s++) {
        const uint32_t pa[4] = {pf[s].x, pf[s].y, pf[s].z, pf[s].w};
#pragma unroll
        for (int y = 0; y < 8; y++) { mma16(o[2 * y], pa, vf[s][y][0], vf[s][y][1]); mma16(o[2 * y + 1], pa, vf[s][y][2], vf[s][y][3]); }
      }
      __syncwarp();
      arrive2(bar0 + 8 * (EB + NSLOT + n), rsb + OFF_BAR + 8 * (EB + NSLOT + n), lane == 0 && n < 14, lane == 0 && n < 16 - NSLOT);
      st = st + 2 * SLOT >= sb + NSLOT * SLOT ? st - (NSLOT - 2) * SLOT : st + 2 * SLOT;
    };
#pragma unroll 1
    for (int t = 0; t < 7; t++) pv(t, IC<NPRE0>());
    pv(7, IC<NPRE1>());
    uint4* po = g_xo + ((size_t)((16 * rk + (g & 6)) * 4 + warp - 4) * 64 + pr) * RS + (lane & 7);
    const bool odd = lane & 4;
#pragma unroll
    for (int e = 0; e < 2; e++)
#pragma unroll
      for (int j2 = 0; j2 < 2; j2++) {
        uint32_t c0[4], c1[4];
#pragma unroll
        for (int i = 0; i < 4; i++) {
          c0[i] = i ? pack2(o[8 * j2 + i][2 * e], o[8 * j2 + i][2 * e + 1]) : pack2t(o[8 * j2][2 * e], o[8 * j2][2 * e + 1], par);
          c1[i] = i ? pack2(o[8 * j2 + 4 + i][2 * e], o[8 * j2 + 4 + i][2 * e + 1]) : pack2t(o[8 * j2 + 4][2 * e], o[8 * j2 + 4][2 * e + 1], par);
          const uint32_t r = __shfl_xor_sync(~0u, odd ? c0[i] : c1[i], 4);
          if (odd) c0[i] = r; else c1[i] = r;
        }
        stx16(po + e * 8 * 4 * 64 * RS + 8 * j2, make_uint4(c0[0], c0[1], c0[2], c0[3]));
        stx16(po + (e * 8 + 1) * 4 * 64 * RS + 8 * j2, make_uint4(c1[0], c1[1], c1[2], c1[3]));
      }
    nbar_arrive(2, 288);
  }
  tail(smem, scr, x, out, par, epoch, warp);
}

static void launch(void* const* d_in, void* d_out) {
  static TMaps tms;
  static bool init = false;
  static void* scr = nullptr;
  if (!init) {
    void* fn = nullptr; cudaDriverEntryPointQueryResult qr;
    cudaGetDriverEntryPoint("cuTensorMapEncodeTiled", &fn, cudaEnableDefault, &qr);
    EncFn f = (EncFn)fn;
    const CUtensorMapSwizzle S32 = CU_TENSOR_MAP_SWIZZLE_32B, S64 = CU_TENSOR_MAP_SWIZZLE_64B, S128 = CU_TENSOR_MAP_SWIZZLE_128B;
    const CUtensorMapL2promotion P128 = CU_TENSOR_MAP_L2_PROMOTION_L2_128B, P256 = CU_TENSOR_MAP_L2_PROMOTION_L2_256B;
    enc3d(f, &tms.m[0], d_in[2], 64, 512, 64, 8192, 128, 64, 128, 1, S128, P128);
    enc3d(f, &tms.m[1], d_in[3], 64, 512, 64, 8192, 128, 64, 64, 2, S128, P256);
    enc3d(f, &tms.m[2], d_in[1], 64, SK, 8, 1024, 128, 64, 64, 2, S128, P256);
    enc3d(f, &tms.m[3], d_in[11], 3072, 256, 2, 6144, 256 * 6144, 16, 256, 2, S32, P128);
    enc3d(f, &tms.m[4], d_in[4], 64, 512, 64, 8192, 128, 64, 64, 2, S128, P256);
    enc3d(f, &tms.m[5], d_in[5], 512, 128, 32, 1024, 128 * 1024, 64, 128, 1, S128, P128);
    enc3d(f, &tms.m[6], d_in[7], 1792, 256, 2, 3584, 256 * 3584, 32, 256, 1, S64, P128);
    enc3d(f, &tms.m[7], d_in[8], 1792, 256, 2, 3584, 256 * 3584, 32, 256, 1, S64, P128);
    enc3d(f, &tms.m[8], d_in[9], 64, 1792, 8, 1024, 128, 64, 16, 8, S128, P256);
    cudaFuncSetAttribute(fused_kernel, cudaFuncAttributeMaxDynamicSharedMemorySize, SMEM_BYTES);
    cudaGetSymbolAddress(&scr, g_scr);
    init = true;
  }
  fused_kernel<<<NCTA, 384, SMEM_BYTES>>>((const bf16*)d_in[0], (const bf16*)d_in[10], (const bf16*)d_in[11], (bf16*)d_out, (Scratch*)scr, tms);
}

}

extern "C" void kernel_launch(void* const* d_in, const int* in_sizes, int n_in, void* d_out, int out_size) {
  static int big = -1;
  if (big < 0) big = v9::fits();
  if (big) v9::launch(d_in, d_out); else v8::launch(d_in, d_out);
}
```

```cpp
#include <cuda_runtime.h>
#include <cuda_bf16.h>
#include <cuda.h>
#include <stdint.h>
#include <stdio.h>
#include <stdlib.h>

typedef CUresult (*EncFn)(CUtensorMap*, CUtensorMapDataType, cuuint32_t, void*, const cuuint64_t*, const cuuint64_t*,
                          const cuuint32_t*, const cuuint32_t*, CUtensorMapInterleave, CUtensorMapSwizzle,
                          CUtensorMapL2promotion, CUtensorMapFloatOOBfill);

static void enc3d(EncFn fn, CUtensorMap* tm, void* p, uint64_t d0, uint64_t d1, uint64_t d2, uint64_t s1, uint64_t s2, uint32_t b0,
                  uint32_t b1, uint32_t b2, CUtensorMapSwizzle sw, CUtensorMapL2promotion pr) {
  cuuint64_t gd[3] = {d0, d1, d2}, gs[2] = {s1, s2};
  cuuint32_t bx[3] = {b0, b1, b2}, es[3] = {1, 1, 1};
  fn(tm, CU_TENSOR_MAP_DATA_TYPE_BFLOAT16, 3, p, gd, gs, bx, es, CU_TENSOR_MAP_INTERLEAVE_NONE, sw, pr, CU_TENSOR_MAP_FLOAT_OOB_FILL_NONE);
}

namespace v9 {
typedef __nv_bfloat16 bf16;
#define SK 32768
#define SPIN_MAX (1 << 20)
template <int N> struct IC { static constexpr int value = N; };

__device__ __forceinline__ uint32_t s2u(const void* p) { return (uint32_t)__cvta_generic_to_shared(p); }
__device__ __forceinline__ float bflo(uint32_t u) { return __uint_as_float(u << 16); }
__device__ __forceinline__ float bfhi(uint32_t u) { return __uint_as_float(u & 0xffff0000u); }
__device__ __forceinline__ float u2f(uint32_t u) { return __uint_as_float(u); }
__device__ __forceinline__ void fma8(float* acc, uint4 v, float s) {
  acc[0] += s * bflo(v.x); acc[1] += s * bfhi(v.x); acc[2] += s * bflo(v.y); acc[3] += s * bfhi(v.y);
  acc[4] += s * bflo(v.z); acc[5] += s * bfhi(v.z); acc[6] += s * bflo(v.w); acc[7] += s * bfhi(v.w);
}
__device__ __forceinline__ uint32_t pack2(float a, float b) {
  __nv_bfloat162 p = __floats2bfloat162_rn(a, b); return *(uint32_t*)&p;
}
__device__ __forceinline__ float bfr(float v) { return bfhi(pack2(v, v)); }
__device__ __forceinline__ float silu_bf(float c) { return bfr(__fdividef(c, 1.f + __expf(-c))); }
#define fbits(v) ((__float_as_uint(v) & ~1u) | par)
__device__ __forceinline__ uint32_t pack2t(float a, float b, unsigned par) {
  const uint32_t ua = ((__float_as_uint(a) + ((par ^ 1) << 16)) & 0xFFFE0000u) | (par << 16);
  return __byte_perm(ua, pack2(b, b), 0x7632);
}
__device__ __forceinline__ void nbar(int id, int n) { asm volatile("bar.sync %0, %1;" ::"r"(id), "r"(n) : "memory"); }
__device__ __forceinline__ void nbar_arrive(int id, int n) { asm volatile("bar.arrive %0, %1;" ::"r"(id), "r"(n) : "memory"); }
__device__ __forceinline__ uint4 ldc16(const void* p) {
  uint4 v; asm volatile("ld.relaxed.cta.global.v4.u32 {%0,%1,%2,%3}, [%4];" : "=r"(v.x), "=r"(v.y), "=r"(v.z), "=r"(v.w) : "l"(p) : "memory"); return v;
}
__device__ __forceinline__ unsigned ldc4(const void* p) {
  unsigned v; asm volatile("ld.relaxed.cta.global.u32 %0, [%1];" : "=r"(v) : "l"(p) : "memory"); return v;
}
__device__ __forceinline__ uint4 ldx16(const void* p) {
  uint4 v; asm volatile("ld.relaxed.gpu.global.v4.u32 {%0,%1,%2,%3}, [%4];" : "=r"(v.x), "=r"(v.y), "=r"(v.z), "=r"(v.w) : "l"(p) : "memory"); return v;
}
__device__ __forceinline__ unsigned ldx4(const void* p) {
  unsigned v; asm volatile("ld.relaxed.gpu.global.u32 %0, [%1];" : "=r"(v) : "l"(p) : "memory"); return v;
}
__device__ __forceinline__ unsigned long long ldx64(const void* p) {
  unsigned long long v; asm volatile("ld.relaxed.gpu.global.u64 %0, [%1];" : "=l"(v) : "l"(p) : "memory"); return v;
}
__device__ __forceinline__ void stx16(void* p, uint4 v) {
  asm volatile("st.relaxed.gpu.global.v4.u32 [%0], {%1,%2,%3,%4};" ::"l"(p), "r"(v.x), "r"(v.y), "r"(v.z), "r"(v.w) : "memory");
}
__device__ __forceinline__ void stx8(void* p, uint2 v) { asm volatile("st.relaxed.gpu.global.v2.u32 [%0], {%1,%2};" ::"l"(p), "r"(v.x), "r"(v.y) : "memory"); }
__device__ __forceinline__ void stx4(void* p, unsigned v) { asm volatile("st.relaxed.gpu.global.u32 [%0], %1;" ::"l"(p), "r"(v) : "memory"); }
__device__ __forceinline__ void pub4(void* p, unsigned v) { asm volatile("red.relaxed.gpu.global.xor.b32 [%0], %1;" ::"l"(p), "r"(v) : "memory"); }
__device__ __forceinline__ void pub8(void* p, unsigned lo, unsigned hi) {
  asm volatile("{.reg .b64 t; mov.b64 t, {%1, %2}; red.relaxed.gpu.global.xor.b64 [%0], t;}" ::"l"(p), "r"(lo), "r"(hi) : "memory");
}
__device__ __forceinline__ unsigned lop_x3(unsigned a, unsigned b, unsigned c) {
  unsigned d; asm("lop3.b32 %0, %1, %2, %3, 0x7E;" : "=r"(d) : "r"(a), "r"(b), "r"(c)); return d; }
__device__ __forceinline__ unsigned or3(unsigned a, unsigned b, unsigned c) {
  unsigned d; asm("lop3.b32 %0, %1, %2, %3, 0xFE;" : "=r"(d) : "r"(a), "r"(b), "r"(c)); return d; }
__device__ __forceinline__ unsigned and3(unsigned a, unsigned b, unsigned c) {
  unsigned d; asm("lop3.b32 %0, %1, %2, %3, 0x80;" : "=r"(d) : "r"(a), "r"(b), "r"(c)); return d; }
__device__ __forceinline__ unsigned dep16(const uint32_t* f) {
  unsigned d = 0;
#pragma unroll
  for (int i = 0; i < 8; i++) d = or3(d, f[8 * i], f[8 * i + 4]);
  return d;
}
__device__ __forceinline__ uint2 ldx8(const void* p) {
  uint2 v; asm volatile("{.reg .b64 t; ld.relaxed.gpu.global.b64 t, [%2]; mov.b64 {%0, %1}, t;}" : "=r"(v.x), "=r"(v.y) : "l"(p) : "memory"); return v;
}
__device__ __forceinline__ float lds4(uint32_t a) { float v; asm volatile("ld.shared.f32 %0, [%1];" : "=f"(v) : "r"(a) : "memory"); return v; }
__device__ __forceinline__ float shx(float v, int m) {
  float r; asm volatile("shfl.sync.bfly.b32 %0, %1, %2, 0x1f, 0xffffffff;" : "=f"(r) : "f"(v), "r"(m)); return r;
}
__device__ __forceinline__ uint32_t mbar_test(uint32_t bar, uint32_t ph) {
  uint32_t ok;
  asm volatile("{.reg .pred p; mbarrier.test_wait.parity.shared::cta.b64 p, [%1], %2; vote.sync.all.pred p, p, 0xffffffff; selp.u32 %0, 1, 0, p;}"
               : "=r"(ok) : "r"(bar), "r"(ph) : "memory");
  return ok;
}
#define X16(v) (lop_x3(v.x, v.y, par) | lop_x3(v.z, v.w, par))
#define RETRY(bad) if (!__any_sync(~0u, (bad) & 1) || ++it_ >= SPIN_MAX) break;
#define POLL _Pragma("unroll 1") for (int it_ = 0;;)
__device__ __forceinline__ void mbar_wait(uint32_t bar, uint32_t ph = 0) {
  asm volatile("{.reg .pred p; .reg .u32 n; mov.u32 n, 0;\n"
               "W%=: mbarrier.try_wait.parity.shared::cta.b64 p, [%0], %1; add.u32 n, n, 1; setp.lt.and.u32 p, n, 0x100000, !p; @p bra W%=;}"
               ::"r"(bar), "r"(ph) : "memory");
}
__device__ __forceinline__ float ex2(float v) { float r; asm("ex2.approx.ftz.f32 %0, %1;" : "=f"(r) : "f"(v)); return r; }
__device__ __forceinline__ float rcp(float v) { float r; asm("rcp.approx.ftz.f32 %0, %1;" : "=f"(r) : "f"(v)); return r; }
__device__ __forceinline__ void mma16(float* d, const uint32_t* a, uint32_t b0, uint32_t b1) {
  asm volatile("mma.sync.aligned.m16n8k16.row.col.f32.bf16.bf16.f32 {%0,%1,%2,%3}, {%4,%5,%6,%7}, {%8,%9}, {%0,%1,%2,%3};"
               : "+f"(d[0]), "+f"(d[1]), "+f"(d[2]), "+f"(d[3]) : "r"(a[0]), "r"(a[1]), "r"(a[2]), "r"(a[3]), "r"(b0), "r"(b1));
}
__device__ __forceinline__ void mma16c(float* d, const uint32_t* a, uint32_t b0, uint32_t b1, const float* c) {
  asm volatile("mma.sync.aligned.m16n8k16.row.col.f32.bf16.bf16.f32 {%0,%1,%2,%3}, {%4,%5,%6,%7}, {%8,%9}, {%10,%11,%12,%13};"
               : "=f"(d[0]), "=f"(d[1]), "=f"(d[2]), "=f"(d[3])
               : "r"(a[0]), "r"(a[1]), "r"(a[2]), "r"(a[3]), "r"(b0), "r"(b1), "f"(c[0]), "f"(c[1]), "f"(c[2]), "f"(c[3]));
}
__device__ __forceinline__ float4 lds16(uint32_t a) {
  float4 v; asm volatile("ld.shared.v4.f32 {%0,%1,%2,%3}, [%4];" : "=f"(v.x), "=f"(v.y), "=f"(v.z), "=f"(v.w) : "r"(a) : "memory"); return v;
}
__device__ __forceinline__ void sts4(uint32_t a, float v) { asm volatile("st.shared.f32 [%0], %1;" ::"r"(a), "f"(v) : "memory"); }
__device__ __forceinline__ void sts16(uint32_t a, uint4 v) {
  asm volatile("st.shared.v4.b32 [%0], {%1,%2,%3,%4};" ::"r"(a), "r"(v.x), "r"(v.y), "r"(v.z), "r"(v.w) : "memory");
}
__device__ __forceinline__ void ldsm_t(uint32_t* r, uint32_t a) {
  asm volatile("ldmatrix.sync.aligned.m8n8.x4.trans.shared.b16 {%0,%1,%2,%3}, [%4];" : "=r"(r[0]), "=r"(r[1]), "=r"(r[2]), "=r"(r[3]) : "r"(a) : "memory");
}
__device__ __forceinline__ void ldsm(uint32_t* r, uint32_t a) {
  asm volatile("ldmatrix.sync.aligned.m8n8.x4.shared.b16 {%0,%1,%2,%3}, [%4];" : "=r"(r[0]), "=r"(r[1]), "=r"(r[2]), "=r"(r[3]) : "r"(a) : "memory");
}
__device__ __forceinline__ uint32_t mapa(uint32_t a, uint32_t r) {
  uint32_t v; asm volatile("mapa.shared::cluster.u32 %0, %1, %2;" : "=r"(v) : "r"(a), "r"(r)); return v;
}
__device__ __forceinline__ unsigned long long mapg(uint32_t a, uint32_t r) {
  unsigned long long v;
  asm volatile("{.reg .u32 t; .reg .u64 u; mapa.shared::cluster.u32 t, %1, %2; cvt.u64.u32 u, t; cvta.shared::cluster.u64 %0, u;}" : "=l"(v) : "r"(a), "r"(r));
  return v;
}
template <int N>
__device__ __forceinline__ void tred(float* a, int lane, int m) {
  const bool hi = lane & m;
#pragma unroll
  for (int i = 0; i < N; i++) {
    float send = hi ? a[i] : a[i + N], keep = hi ? a[i + N] : a[i];
    a[i] = keep + __shfl_xor_sync(~0u, send, m);
  }
}
template <int N>
__device__ __forceinline__ void tmax(float* a, int lane, int m) {
  const bool hi = lane & m;
#pragma unroll
  for (int i = 0; i < N; i++) {
    float send = hi ? a[i] : a[i + N], keep = hi ? a[i + N] : a[i];
    a[i] = fmaxf(keep, __shfl_xor_sync(~0u, send, m));
  }
}
__device__ __forceinline__ void arrive_n(uint32_t bar, bool on, int cnt) {
  asm volatile("{.reg .pred p; setp.ne.s32 p, %1, 0; @p mbarrier.arrive.shared::cta.b64 _, [%0], %2;}" ::"r"(bar), "r"((int)on), "r"(cnt) : "memory");
}
__device__ __forceinline__ unsigned long long stream_policy() {
  unsigned long long p;
  asm volatile("createpolicy.fractional.L2::evict_first.b64 %0, 1.0;" : "=l"(p));
  return p;
}
__device__ __forceinline__ void tma3d(uint32_t dst, const CUtensorMap* tm, uint32_t bar, int c0, int c1, int c2) {
  asm volatile("cp.async.bulk.tensor.3d.shared::cluster.global.mbarrier::complete_tx::bytes.L2::cache_hint [%0], [%1, {%3, %4, %5}], [%2], %6;"
               ::"r"(dst), "l"(tm), "r"(bar), "r"(c0), "r"(c1), "r"(c2), "l"(stream_policy()) : "memory");
}
__device__ __forceinline__ void spin_until(unsigned t) { while ((int)((unsigned)clock() - t) < 0) {} }
__device__ __forceinline__ void wait_until(unsigned t) {
  unsigned now;
  do { asm volatile("mov.u32 %0, %%globaltimer_lo;" : "=r"(now)); } while ((int)(now - t) < 0);
}
__device__ __forceinline__ void sleep_until(unsigned t) {
  unsigned now;
#pragma unroll 1
  do {
    __nanosleep(200);
    asm volatile("mov.u32 %0, %%globaltimer_lo;" : "=r"(now));
  } while ((int)(now - t) < 0);
}
#define PIN(x) asm volatile("" : "+r"(x))
#define PINL(x) asm volatile("" : "+l"(x))
#define BAR_ARRIVE(i) asm volatile("mbarrier.arrive.shared::cta.b64 _, [%0];" ::"r"(bar0 + 8 * (i)) : "memory")
#define LANE0(op, p, c, v) asm volatile("{.reg .pred q; setp.eq.s32 q, %2, 0; @q " op " [%0], %1;}" ::"l"((p) + lane), c(v), "r"(lane) : "memory")
#define CNT_ADD(c) LANE0("red.relaxed.gpu.global.add.u32", scr->cnt + (c), "r", 1)
#define BAR_INIT(i, cnt) asm volatile("mbarrier.init.shared::cta.b64 [%0], %1;" ::"r"(bar0 + 8 * (i)), "r"(cnt) : "memory")
#define BAR_ARM(i, bytes) asm volatile("mbarrier.arrive.expect_tx.shared::cta.b64 _, [%0], %1;" ::"r"(bar0 + 8 * (i)), "r"(bytes) : "memory")
struct TMaps { CUtensorMap m[9]; };

#define NCTA9 120
#define TAU 20
#define NSL 100
#define NPE 1
#define QN 4
#define FDLY 60
#define VJ 1
#define NPO 3
#define VDLY 150
#define O_Q 131072
#define O_LZ 163840
#define O_CTX 196608
#define O_HZ 198656
#define O_HW 200704
#define O_X 201728
#define O_P 218112
#define O_B 222208
#define O_R 224512
#define O_SILU 228608
#define O_SM 229632
#define O_BAR 231424
#define O_EP (O_BAR + 256)
#define O_DBG (O_EP + 16)
#define SMEM9 (O_DBG + 144)
#define B_FULL 0
#define B_FM 8
#define B_EMPTY 10
#define B_EM 18
#define B_LZ 18
#define B_Q2 19
#define B_H 20
#define B_QF 21
#define B_TAB 22
#define B_W 23
#define B_ST 24
#define B_HZ 25
#define B_WZ 26
#define B_G2 28
#define B_G 27
enum { T_WQ, T_WUK, T_KV, T_MOD, T_UV, T_WO, T_GU, T_DN = 8 };
#define NBIG 40
struct Sched { unsigned zero, dth; uint2 r[3][8]; unsigned nr[3], nt[3], dt, t4, d4, d6, wt, pad; };

struct __align__(128) Scratch {
  unsigned cnt[8 * 32];
  uint2 rec[32 * 4 * 8 * 64];
  uint2 hdr[32 * 16];
  unsigned h[8 * 256];
  uint4 qa[2048];
  unsigned xao[8 * 512];
  unsigned xab[8 * 256];
  unsigned xm[2048];
};
__device__ Scratch g_scr;
#define SMEM_BASE 1024u
#define DSC ((SMEM_BASE >> 4) | (1u << 16))
#define HI128 (64u | (1u << 30))
#define HI64 (32u | (2u << 30))
template <int TA, int TB, unsigned HIA, unsigned HIB>
__device__ __forceinline__ void wgmma32(float* d, uint32_t da, uint32_t db, int acc) {
  asm volatile("{.reg .pred p; .reg .b64 da, db; setp.ne.b32 p, %18, 0; mov.b64 da, {%16, %21}; mov.b64 db, {%17, %22};\n"
               "wgmma.mma_async.sync.aligned.m64n32k16.f32.bf16.bf16 "
               "{%0,%1,%2,%3,%4,%5,%6,%7,%8,%9,%10,%11,%12,%13,%14,%15}, da, db, p, 1, 1, %19, %20;}"
               : "+f"(d[0]), "+f"(d[1]), "+f"(d[2]), "+f"(d[3]), "+f"(d[4]), "+f"(d[5]), "+f"(d[6]), "+f"(d[7]),
                 "+f"(d[8]), "+f"(d[9]), "+f"(d[10]), "+f"(d[11]), "+f"(d[12]), "+f"(d[13]), "+f"(d[14]), "+f"(d[15])
               : "r"(da), "r"(db), "r"(acc), "n"(TA), "n"(TB), "n"(HIA), "n"(HIB));
}
__device__ __forceinline__ void wgmma32r(float* d, const uint32_t* a, uint32_t db) {
  asm volatile("{.reg .b64 db; mov.b64 db, {%20, %21};\n"
               "wgmma.mma_async.sync.aligned.m64n32k16.f32.bf16.bf16 "
               "{%0,%1,%2,%3,%4,%5,%6,%7,%8,%9,%10,%11,%12,%13,%14,%15}, {%16,%17,%18,%19}, db, 1, 1, 1, 1;}"
               : "+f"(d[0]), "+f"(d[1]), "+f"(d[2]), "+f"(d[3]), "+f"(d[4]), "+f"(d[5]), "+f"(d[6]), "+f"(d[7]),
                 "+f"(d[8]), "+f"(d[9]), "+f"(d[10]), "+f"(d[11]), "+f"(d[12]), "+f"(d[13]), "+f"(d[14]), "+f"(d[15])
               : "r"(a[0]), "r"(a[1]), "r"(a[2]), "r"(a[3]), "r"(db), "n"(HI64));
}
template <int N> __device__ __forceinline__ void wg_wait(float* a) {
  asm volatile("wgmma.wait_group.sync.aligned %16;"
               : "+f"(a[0]), "+f"(a[1]), "+f"(a[2]), "+f"(a[3]), "+f"(a[4]), "+f"(a[5]), "+f"(a[6]), "+f"(a[7]), "+f"(a[8]), "+f"(a[9]), "+f"(a[10]),
                 "+f"(a[11]), "+f"(a[12]), "+f"(a[13]), "+f"(a[14]), "+f"(a[15]) : "n"(N) : "memory");
}
__device__ __forceinline__ void send32(uint32_t a, uint32_t bar, float v, int lane) {
  const uint32_t w = pack2(v, __shfl_down_sync(~0u, v, 1));
  const int s = 2 * (lane & 3);
  asm volatile("{.reg .pred p; setp.eq.s32 p, %6, 0; @p st.async.shared::cluster.mbarrier::complete_tx::bytes.v4.b32 [%0], {%1,%2,%3,%4}, [%5];}"
               ::"r"(a), "r"(__shfl_sync(~0u, w, s)), "r"(__shfl_sync(~0u, w, s + 8)), "r"(__shfl_sync(~0u, w, s + 16)), "r"(__shfl_sync(~0u, w, s + 24)),
                 "r"(bar), "r"(lane & 12) : "memory");
}
__device__ __forceinline__ float sum8(uint32_t a) {
  const float4 p = lds16(a), q = lds16(a + 1024);
  return ((p.x + p.y) + (p.z + p.w)) + ((q.x + q.y) + (q.z + q.w));
}
__device__ __forceinline__ int posof(int c) { return (c & ~14) + 2 * (c & 6) + ((c >> 2) & 2); }

__global__ void __cluster_dims__(8, 1, 1) __launch_bounds__(384, 1)
fused_kernel(const bf16* __restrict__ x, const bf16* __restrict__ cvec, const bf16* __restrict__ w_mod, bf16* __restrict__ out,
             Scratch* __restrict__ scr, const __grid_constant__ Sched sch, const __grid_constant__ TMaps tms) {
  extern __shared__ __align__(1024) unsigned char smem[];
  const int tid = threadIdx.x, warp = __shfl_sync(~0u, tid >> 5, 0), lane = tid & 31;
  const int b = blockIdx.x, cl = b >> 3, rn = b & 7, rk = b & 1, hd = b >> 1, f = b - 64;
  const bool isA = b < 64;
  uint32_t sb = s2u(smem), bar0 = sb + O_BAR;
  unsigned gt_start;
  asm volatile("mov.u32 %0, %%globaltimer_lo;" : "=r"(gt_start));
  const int g = lane >> 2, tq = lane & 3;
  const int arow = 64 * rn + ((tid & 255) >> 4);
  uint4 wm[4];
  uint32_t cw, xw;
  if (warp < 8 && isA) {
    const bf16* wa = w_mod + (size_t)arow * 3072 + (lane & 8) * 64 + 64 * cl + 8 * (lane & 7);
#pragma unroll
    for (int i = 0; i < 4; i++) wm[i] = ldx16(wa + i * 16 * 3072);
    cw = ldc4(cvec + (arow & ~1) + 16 * tq);
    if (warp < 2) xw = ldc4(x + 64 * cl + (tid & 62));
  }
  if (warp == 11) {
    if (lane == 0) {
#pragma unroll
      for (int i = 0; i < B_EMPTY; i++) BAR_INIT(i, 1);
    }
    __syncwarp();
    asm volatile("fence.mbarrier_init.release.cluster;" ::: "memory");
    asm volatile("barrier.cluster.arrive.relaxed.aligned;" ::: "memory");
    if (isA) {
#pragma unroll 1
      for (int i = 0; i < 8; i++) {
        if (i >= 6) mbar_wait(bar0 + 8 * (i - 6));
        wait_until(gt_start + ((64 * i + b) * sch.dth >> 8));
        if (lane == 0) {
          BAR_ARM(i, 16384);
          tma3d(sb + i * 16384, &tms.m[i >> 2], bar0 + 8 * i, 0, i < 4 ? 128 * i : 256 * rk + 64 * (i - 4), i < 4 ? b : b & ~1);
        }
        __syncwarp();
      }
    }
  }
  if (warp == 10) {
    const unsigned ep = ldc4(&scr->cnt[0]);
    if (isA) {
      const uint4 xa = ldc16(x + 16 * lane), xb = ldc16(x + 16 * lane + 8);
      float xv[16] = {bflo(xa.x), bfhi(xa.x), bflo(xa.y), bfhi(xa.y), bflo(xa.z), bfhi(xa.z), bflo(xa.w), bfhi(xa.w),
                      bflo(xb.x), bfhi(xb.x), bflo(xb.y), bfhi(xb.y), bflo(xb.z), bfhi(xb.z), bflo(xb.w), bfhi(xb.w)};
      const float x0 = __shfl_sync(~0u, xv[0], 0);
      float s = 0, q = 0;
#pragma unroll
      for (int i = 0; i < 16; i++) { xv[i] -= x0; s += xv[i]; q += xv[i] * xv[i]; }
#pragma unroll
      for (int o = 16; o; o >>= 1) { s += __shfl_xor_sync(~0u, s, o); q += __shfl_xor_sync(~0u, q, o); }
      s *= 1.f / 512.f;
      float rstd;
      asm("rsqrt.approx.ftz.f32 %0, %1;" : "=f"(rstd) : "f"(fmaxf(q * (1.f / 512.f) - s * s, 0.f) + 1e-5f));
      *(float2*)(smem + O_SM + 1024) = make_float2(s + x0, rstd);
    }
    if (lane == 0) *(volatile unsigned*)(smem + O_EP) = ep;
    nbar_arrive(1, 288);
  }
  const int cls = isA ? (b >= NBIG) : 2, v0 = isA ? 2 : 0;
  if (warp >= 8) {
    asm volatile("setmaxnreg.dec.sync.aligned.u32 56;");
    if (warp == 8) {
      if (lane < 8) asm volatile("prefetch.tensormap [%0];" ::"l"(&tms.m[lane + 1]) : "memory");
      if ((sb & 0xFFFFFF) != SMEM_BASE) __trap();
    } else if (warp == 9) {
      if (lane == 0) {
#pragma unroll
        for (int i = B_EMPTY; i < B_EM; i++) BAR_INIT(i, 8);
        BAR_INIT(B_LZ, 8); BAR_INIT(B_Q2, 9); BAR_ARM(B_Q2, 1024);
        BAR_INIT(B_H, 1); BAR_INIT(B_QF, 1); BAR_ARM(B_QF, 32768);
        BAR_INIT(B_TAB, 1); BAR_INIT(B_W, 1); BAR_INIT(B_ST, 8); BAR_INIT(B_WZ, 1); BAR_INIT(B_HZ, 1); BAR_ARM(B_HZ, isA ? 1024 : 512); BAR_INIT(B_G, 1); BAR_INIT(B_G2, 1);
      }

    }
    if (warp != 11) {
      __syncwarp();
      asm volatile("fence.mbarrier_init.release.cluster;" ::: "memory");
      __threadfence_block();
      asm volatile("barrier.cluster.arrive.relaxed.aligned;" ::: "memory");
    }
    asm volatile("barrier.cluster.wait.acquire.aligned;" ::: "memory");
    if (warp == 8) {
      const int nr = sch.nr[cls], vl = v0 + sch.nt[cls] - 1;
      unsigned long long hist = 0;
      int v = v0;
#pragma unroll 1
      for (int rd = 0; rd < nr; rd++) {
        const uint2 e = sch.r[cls][rd];
        const int type = e.y & 15, win = (e.y >> 4) & 15, pos = b + 64 - (int)((e.y >> 8) & 255), tile = e.y >> 16;
        const bool mod = type == T_MOD;
        const int ni = mod ? 1 : type == T_DN ? 2 : 4;
        unsigned t = gt_start + (e.x & 0xffff) + (pos * sch.dt >> 8);
        const int c0 = mod ? 1024 + 32 * b : type == T_WO || type == T_DN ? 64 * rn : type == T_GU ? 32 * f : 0;
        int c1 = type == T_KV ? 64 * (tile + pos) : 0;
        int c2 = mod ? tile : type == T_WO ? 4 * cl : type == T_DN ? 2 * cl - 16 : type == T_UV ? b : 0;
        const int i1 = type == T_UV ? 128 : 0;
#pragma unroll 1
        for (int j = 0; j < ni; j++) {
          const int slot = mod ? B_FM + tile : (v & 1) * 4 + j;
          if (mod ? tile : v >= 2) mbar_wait(bar0 + 8 * (B_EMPTY + (mod ? (vl & 1) * 4 : slot)), mod ? (vl >> 1) & 1 : ((v >> 1) - 1) & 1);
          const int hw = (int)(hist >> (6 * (win - 1))) & 63;
          if (hw) mbar_wait(bar0 + 8 * (hw & 15), (hw >> 4) & 1);
          wait_until(t);
          if (lane == 0) {
            BAR_ARM(slot, 16384);
            tma3d(sb + (mod ? (tile ? O_Q : O_X) : slot * 16384), &tms.m[type == T_GU ? type + (j & 1) : type], bar0 + 8 * slot, c0, c1, c2);
          }
          __syncwarp();
          hist = hist << 6 | (32 | (mod ? 0 : (v & 2) << 3) | slot);
          t += e.x >> 16; c1 += i1;
          c2 += type == T_KV ? 2 : type == T_WO || type == T_DN ? 1 : type == T_GU ? j & 1 : 0;
        }
        v += !mod;
      }
      return;
    }
    const unsigned epoch = *(volatile unsigned*)(smem + O_EP), par = (epoch + 1) & 1;
    if (warp == 10) {
      if (isA) {
        for (int it = 0; ldx4(scr->cnt + 1) != (epoch + 1) * 128 && it < SPIN_MAX; it++) {}
        if (lane == 0) BAR_ARRIVE(B_H);
      } else mbar_wait(bar0);
      if (!(rn & (QN - 1))) {
        for (int it = 0; ldx4(scr->cnt + 32 + 32 * (rn >> 2)) != (epoch + 1) * 32 && it < SPIN_MAX; it++) {}
        if (lane == 0)
          asm volatile("cp.async.bulk.shared::cluster.global.mbarrier::complete_tx::bytes.multicast::cluster [%0], [%1], %4, [%2], %3;"
                       ::"r"(sb + O_Q + rn * 4096), "l"(scr->qa + rn * 256), "r"(bar0 + 8 * B_QF), "h"((unsigned short)0xff), "n"(4096 * QN) : "memory");
      }
      const unsigned dl = isA ? sch.d4 : sch.d6;
      unsigned tw = gt_start + sch.t4;
      if (!isA) {
        const int nt = sch.nt[2];
#pragma unroll 1
        for (int t = 0; t < nt; t++) mbar_wait(bar0 + 8 * B_EMPTY + (t & 1) * 32, (t >> 1) & 1);
        unsigned long long now;
        asm volatile("mov.u64 %0, %%globaltimer;" : "=l"(now));
        LANE0("red.relaxed.gpu.global.max.u64", scr->cnt + 130, "l", now);
        CNT_ADD(128);
        tw = (unsigned)now + 1700;
      }
      sleep_until(tw);
      uint4 an;
      for (int it = 0; an = ldx16(scr->cnt + 128), an.x != (epoch + 1) * 56 && it < SPIN_MAX; it++) {}
      wait_until(an.z + (dl >> 16));
      if (lane == 0) BAR_ARRIVE(B_G2);
      wait_until(an.z + (dl & 0xffff));
      if (lane == 0) BAR_ARRIVE(B_G);
    } else if (warp == 11) {
      {
        uint2* ph = scr->hdr + ((lane & 24) + 2 * tq + (g & 1)) * 16 + cl;
        const bool own = (lane >> 4) * 4 + tq == rn;
        if (own) { stx8(ph, make_uint2(par ^ 1, 0)); if (cl == 14) stx8(ph + 1, make_uint2(0, 0)); }
        uint32_t a_w = sb + O_HW + ((lane >> 4) * 4 + tq) * 128 + (g & 1) * 64 + ((lane >> 1) & 4);
        PIN(a_w); PINL(ph);
        const int vt = v0 + sch.nt[cls];
#pragma unroll 1
        for (int t = 0; t < vt; t++) mbar_wait(bar0 + 8 * B_EMPTY + (t & 1) * 32, (t >> 1) & 1);
        float hz[8], M;
        uint32_t wp[4];
#pragma unroll 1
        for (int e = 0; e < 2; e++) {
          POLL {
            unsigned ok = 1;
#pragma unroll
            for (int u = 0; u < 8; u++)
              asm volatile("ld.relaxed.cluster.shared.f32 %0, [%1];" : "=f"(hz[u]) : "r"(sb + O_HZ + e * 1024 + u * 128 + lane * 4) : "memory");
#pragma unroll
            for (int u = 0; u < 4; u++) ok = and3(ok, __float_as_uint(hz[u]), __float_as_uint(hz[u + 4]));
            RETRY(~ok)
          }
          if (e) break;
          M = fmaxf(fmaxf(fmaxf(hz[0], hz[1]), fmaxf(hz[2], hz[3])), fmaxf(fmaxf(hz[4], hz[5]), fmaxf(hz[6], hz[7])));
          M = u2f(fbits(M));
#pragma unroll
          for (int u = 0; u < 4; u++) {
            wp[u] = pack2(ex2(hz[u] - M), ex2(hz[u + 4] - M));
            sts4(a_w + ((rn - u) & 3) * 8, u2f(wp[u])); sts4(a_w + ((rn - u) & 3) * 8 + 32, u2f(wp[u]));
          }
          __syncwarp();
          if (lane == 0) BAR_ARRIVE(B_WZ);
        }
        float L = 0.f;
#pragma unroll
        for (int u = 0; u < 4; u++) L += bflo(wp[u]) * hz[u] + bfhi(wp[u]) * hz[u + 4];
        if (own) pub8(ph, __float_as_uint(M) | 1u, __float_as_uint(L));
      }
      if (isA) {
        mbar_wait(bar0 + 8 * B_G2);
        unsigned long long hh;
        POLL { hh = ldx64(scr->hdr + hd * 16 + (lane & 15)); RETRY((lane & 15) == 15 ? 0u : (unsigned)hh ^ par) }
        const float m = (lane & 15) == 15 ? -1e30f : u2f((unsigned)hh);
        int mi = __float_as_int(m);
        mi ^= (mi >> 31) & 0x7fffffff;
        mi = __reduce_max_sync(~0u, mi);
        mi ^= (mi >> 31) & 0x7fffffff;
        const float w = ex2(m - __int_as_float(mi));
        float L = w * u2f(hh >> 32);
#pragma unroll
        for (int o2 = 8; o2; o2 >>= 1) L += __shfl_xor_sync(~0u, L, o2);
        sts4(sb + O_SM + (384 + 2 * (lane & 6) + ((lane >> 2) & 2) + (lane & 1)) * 4, w * rcp(L));
        __syncwarp();
        if (lane == 0) BAR_ARRIVE(B_W);
      }
    } else {
#pragma unroll 4
      for (int i = 0; i < 72; i++) sts16(sb + O_LZ + i * 512 + lane * 16, make_uint4(0, 0, 0, 0));
      __syncwarp();
      if (lane < 8) asm volatile("mbarrier.arrive.release.cluster.shared::cluster.b64 _, [%0];" ::"r"(mapa(bar0 + 8 * B_LZ, lane)) : "memory");
      if (isA) {
        mbar_wait(bar0 + 8 * B_QF);
#pragma unroll 2
        for (int k = 0; k < 8; k++) {
          const uint32_t cp = ldc4(cvec + 2 * (lane + 32 * k));
          *(uint32_t*)(smem + O_SILU + (lane + 32 * k) * 4) = pack2(silu_bf(bflo(cp)), silu_bf(bfhi(cp)));
        }
        __syncwarp();
        uint32_t ab = sb + O_X + (8 * (lane >> 4) + (lane & 7)) * 64 + ((((lane >> 3) & 1) ^ ((lane >> 1) & 3)) << 4);
        float d[4][4] = {};
#pragma unroll 1
        for (int jm = 0; jm < 2; jm++) {
          mbar_wait(bar0 + 8 * (B_FM + jm));
#pragma unroll 2
          for (int s2 = 0; s2 < 8; s2++)
#pragma unroll
            for (int s = 0; s < 2; s++) {
              uint32_t a0[4], a1[4];
              const uint32_t* ps = (const uint32_t*)(smem + O_SILU) + 128 * jm + 16 * s2 + 8 * s + tq;
              ldsm_t(a0, ab + (2 * s2 + s) * 1024); ldsm_t(a1, (ab + (2 * s2 + s) * 1024) ^ 32);
              mma16(d[s], a0, ps[0], ps[4]); mma16(d[2 + s], a1, ps[0], ps[4]);
            }
          ab -= O_X - O_Q;
        }
        const float t0 = (tq & 1) ? d[0][2] + d[1][2] : d[0][0] + d[1][0], t1 = (tq & 1) ? d[2][2] + d[3][2] : d[2][0] + d[3][0];
        stx4(scr->xm + b * 32 + posof(8 * tq + g), fbits(bfr(bfr((tq & 2) ? t1 : t0) + ((b >> 4) == 2 ? 1.f : 0.f))));
        __syncwarp();
        CNT_ADD(96);
      } else sleep_until(gt_start + sch.t4);
      for (int it = 0; ldx4(scr->cnt + 96) != (epoch + 1) * 64 && it < SPIN_MAX; it++) __nanosleep(NSL);
      if (isA) {
        unsigned long long ga;
        POLL { ga = ldx64(scr->xm + 64 * rn + 2 * lane); RETRY(lop_x3((unsigned)ga, ga >> 32, par)) }
        *(float2*)(smem + O_SM + (320 + 2 * lane) * 4) = make_float2(bfhi((unsigned)ga), bfhi(ga >> 32));
      }
      __syncwarp();
      if (lane == 0) BAR_ARRIVE(B_TAB);
    }
    return;
  }

  float* s_sm = (float*)(smem + O_SM);
  unsigned par, epoch;
  asm volatile("barrier.cluster.arrive.relaxed.aligned;" ::: "memory");
  if (isA) {
    float* s_r = (float*)(smem + O_R);
    float acc[8] = {0, 0, 0, 0, 0, 0, 0, 0};
    const float sl = silu_bf((arow & 1) ? bfhi(cw) : bflo(cw));
#pragma unroll
    for (int i = 0; i < 4; i++) fma8(acc, wm[i], __shfl_sync(~0u, sl, i, 4));
    tred<4>(acc, lane, 16);
    *(float4*)(s_r + warp * 128 + 8 * (lane & 15) + ((lane >> 2) & 4)) = make_float4(acc[0], acc[1], acc[2], acc[3]);
    nbar(1, 288);
    epoch = *(volatile unsigned*)(smem + O_EP);
    par = (epoch + 1) & 1;
    if (warp < 2) {
      float t = 0.f, ca = rn == 0 ? 1.f : 0.f;
#pragma unroll
      for (int w = 0; w < 8; w++) { t += s_r[w * 128 + tid]; ca += s_r[w * 128 + 64 + tid]; }
      t += ca * ((((tid & 1) ? bfhi(xw) : bflo(xw)) - s_sm[256]) * s_sm[257]);
      const float nb = __shfl_down_sync(~0u, t, 1);
      const uint32_t w0 = lane < 8 ? pack2t(t, nb, par) : pack2(t, nb);
      const uint32_t w1 = __shfl_down_sync(~0u, w0, 8), w2 = __shfl_down_sync(~0u, w0, 16), w3 = __shfl_down_sync(~0u, w0, 24);
      if (lane < 8 && !(lane & 1)) stx16(scr->h + (rn >> 1) * 512 + (2 * cl + warp) * 32 + rk * 16 + 2 * lane, make_uint4(w0, w1, w2, w3));
      __syncwarp();
      CNT_ADD(1);
    }
    asm volatile("barrier.cluster.wait.acquire.aligned;" ::: "memory");
    const uint32_t rsb = mapa(sb, rn ^ 1);
    {
      uint32_t a[4][4][4];
      mbar_wait(bar0 + 8 * (warp >> 1));
      const uint32_t ab = sb + (64 * warp + 8 * (lane >> 4) + (lane & 7)) * 128;
#pragma unroll
      for (int s = 0; s < 4; s++)
#pragma unroll
        for (int mt = 0; mt < 4; mt++) ldsm_t(a[s][mt], ab + s * 2048 + (((2 * mt + ((lane >> 3) & 1)) ^ (lane & 7)) << 4));
      arrive_n(bar0 + 8 * (B_EMPTY + (warp >> 1)), lane == 0, 4 + (dep16(&a[0][0][0]) & sch.zero));
      uint4 v0, v1;
      const unsigned* ph = scr->h + (g >> 1) * 512 + 64 * warp + 4 * (lane & 7);
      uint32_t off = O_B + warp * 272 + (32 * rk + 8 * tq + (lane & 4)) * 4;
      PIN(off); PINL(ph);
      mbar_wait(bar0 + 8 * B_H);
      POLL { v0 = ldx16(ph); v1 = ldx16(ph + 32); RETRY(lop_x3(v0.x, v1.x, par)) }
      float d[4][4] = {};
#pragma unroll
      for (int mt = 0; mt < 4; mt++) {
        mma16(d[mt], a[0][mt], v0.x, v0.y); mma16(d[mt], a[1][mt], v0.z, v0.w);
        mma16(d[mt], a[2][mt], v1.x, v1.y); mma16(d[mt], a[3][mt], v1.z, v1.w);
      }
      float r[8];
#pragma unroll
      for (int mt = 0; mt < 4; mt++) { r[2 * mt] = d[mt][0] + d[mt][1]; r[2 * mt + 1] = d[mt][2] + d[mt][3]; }
      tred<4>(r, lane, 2); tred<2>(r, lane, 1);
      const float rc = __shfl_xor_sync(~0u, (lane & 4) ? r[0] : r[1], 4);
      const uint32_t wd = (lane & 4) ? pack2(rc, r[1]) : pack2(r[0], rc);
      const uint32_t w1 = __shfl_down_sync(~0u, wd, 8), w2 = __shfl_down_sync(~0u, wd, 16), w3 = __shfl_down_sync(~0u, wd, 24);
      asm volatile("{.reg .pred p; setp.lt.s32 p, %7, 8; @p st.shared.v4.b32 [%0], {%2,%3,%4,%5};\n"
                   "@p st.async.shared::cluster.mbarrier::complete_tx::bytes.v4.b32 [%1], {%2,%3,%4,%5}, [%6];}"
                   ::"r"(sb + off), "r"(rsb + off), "r"(wd), "r"(w1), "r"(w2), "r"(w3), "r"(rsb + O_BAR + 8 * B_Q2), "r"(lane) : "memory");
      __syncwarp();
      arrive_n(bar0 + 8 * B_Q2, lane == 0, 1);
    }
    {
      uint32_t a[2][8][4];
      uint32_t a_bq = sb + O_B + (lane & 7) * 272 + (lane >> 3) * 16;
      uint4* p_qa = scr->qa + (4 * rk + (warp >> 1)) * 256 + hd * 8 + ((4 * (warp & 1) + tq) ^ (hd & 7));
      PIN(a_bq); PINL(p_qa);
      mbar_wait(bar0 + 8 * (4 + (warp >> 1)));
      const uint32_t ab = sb + 65536 + (warp >> 1) * 16384 + (32 * (warp & 1) + (lane & 15)) * 128;
#pragma unroll
      for (int i = 0; i < 16; i++) ldsm(a[i >> 3][i & 7], ab + (i >> 3) * 2048 + ((i >> 2) & 1) * 8192 + (((2 * (i & 3) + (lane >> 4)) ^ (lane & 7)) << 4));
      arrive_n(bar0 + 8 * (B_EMPTY + 4 + (warp >> 1)), lane == 0, 4 + (dep16(&a[0][0][0]) & sch.zero));
      mbar_wait(bar0 + 8 * B_Q2);
      float d[4][4] = {};
#pragma unroll
      for (int y = 0; y < 4; y++) {
        uint32_t bq[4];
        ldsm(bq, a_bq + 64 * y);
#pragma unroll
        for (int mt = 0; mt < 2; mt++) { mma16(d[2 * mt], a[mt][2 * y], bq[0], bq[1]); mma16(d[2 * mt + 1], a[mt][2 * y + 1], bq[2], bq[3]); }
      }
      float r[4];
#pragma unroll
      for (int i = 0; i < 4; i++) r[i] = (d[i & 2][2 * (i & 1)] + d[i & 2][2 * (i & 1) + 1]) + (d[(i & 2) + 1][2 * (i & 1)] + d[(i & 2) + 1][2 * (i & 1) + 1]);
      tred<2>(r, lane, 2); tred<1>(r, lane, 1);
      const float nb = __shfl_xor_sync(~0u, r[0], 4);
      const uint32_t w0 = (lane >> 3) == (hd & 3) ? pack2t(r[0], nb, par) : pack2(r[0], nb);
      const uint32_t w1 = __shfl_down_sync(~0u, w0, 8), w2 = __shfl_down_sync(~0u, w0, 16), w3 = __shfl_down_sync(~0u, w0, 24);
      if (lane < 4) stx16(p_qa, make_uint4(w0, w1, w2, w3));
      if (warp) nbar_arrive(3, 256); else { nbar(3, 256); CNT_ADD(32 + 32 * rk); }
    }
  } else {
    nbar(1, 288);
    epoch = *(volatile unsigned*)(smem + O_EP);
    par = (epoch + 1) & 1;
    asm volatile("barrier.cluster.wait.acquire.aligned;" ::: "memory");
    mbar_wait(bar0);
  }
  asm volatile("setmaxnreg.inc.sync.aligned.u32 224;");
  uint2* p_rec = scr->rec + ((16 * (warp >> 2) + 2 * (warp & 3) + (g & 1) + 4 * (tq & 2)) * 32 + 4 * rn + (tq & 1)) * 64 + cl * 4 + (g >> 1);
  PINL(p_rec);
  {
    const unsigned inv = par ^ 1;
#pragma unroll
    for (int q = 0; q < 2; q++) { stx8(p_rec + q * 128, make_uint2(inv, 0)); if (cl == 14) stx8(p_rec + q * 128 + 4, make_uint2(0, 0)); }
    if (isA) { if (warp < 2) { stx4(scr->xao + b * 64 + tid, inv); stx4(scr->xab + cl * 256 + (2 * (rn & 3) + warp) * 32 + (rn >> 2) * 16 + (lane >> 1), inv); } }
    else if (f == 0) { stx4(out + 2 * tid, 0); __threadfence(); }
  }
  sb = __shfl_sync(~0u, sb, 0); bar0 = sb + O_BAR;
  const int nt = sch.nt[cls], wg = warp >> 2;
  uint32_t a_z[4];
#pragma unroll
  for (int u = 0; u < 4; u++) {
    const int s3 = (rn - u - (lane >> 1 & 1)) & 3;
    a_z[u] = sb + O_LZ + (s3 + 4 * (lane & 1)) * 4096 + wg * 512 + g * 64 + (((warp & 3) ^ (s3 & 1) ^ (2 * (lane & 1))) << 4);
    PIN(a_z[u]);
  }
  uint32_t z[4][4], a_w = sb + O_HW + warp * 128 + (g & 1) * 64 + (tq & 1) * 8;
  PIN(a_w);
  {
    const float sc = 0.08838834764831845f * 1.4426950408889634f;
    float mrun = -1e30f;
    float o[4][16], sx[16], mref[8];
#pragma unroll
    for (int k = 0; k < 16; k++) { o[0][k] = o[1][k] = o[2][k] = o[3][k] = sx[k] = 0.f; mref[k >> 1] = -1e30f; }
    const int key = 16 * warp + (lane & 15);
    uint32_t a_p = sb + O_P + key * 64 + (((lane >> 4) ^ ((key >> 1) & 3)) << 4);
    uint32_t a_v = sb + wg * 32768 + (8 * (lane >> 4) + (lane & 7)) * 128 + (((2 * (warp & 3) + ((lane >> 3) & 1)) ^ (lane & 7)) << 4);
    const int rot = rn + warp;
    unsigned long long dst[4];
#pragma unroll
    for (int q = 0; q < 4; q++) {
      dst[q] = mapg(sb + O_LZ + rn * 4096 + (warp & 3) * 1024 + g * 64 + ((tq ^ (rn & 1) ^ ((rn >> 1) & 2)) << 4), 4 * wg + ((q + rot) & 3));
      PINL(dst[q]);
    }
    unsigned long long a_h = mapg(sb + O_HZ + wg * 1024 + rn * 128 + lane * 4, 2 * (warp & 3));
    unsigned long long a_h1 = mapg(sb + O_HZ + wg * 1024 + rn * 128 + lane * 4, 2 * (warp & 3) + 1);
    PIN(a_p); PIN(a_v); PINL(a_h); PINL(a_h1);
    uint32_t rel = lane < 4 && lane >= 2 * wg ? 2 - (tq >> 1) : 0;
    PIN(rel);
    uint32_t ones[4] = {0x3F803F80u, 0x3F803F80u, 0x3F803F80u, 0x3F803F80u};
    PIN(ones[0]); PIN(ones[1]); PIN(ones[2]); PIN(ones[3]);
    {
      asm volatile("{.reg .pred p; .reg .u32 n; mov.u32 n, 0;\n"
                   "W%=: mbarrier.try_wait.parity.acquire.cluster.shared::cta.b64 p, [%0], 0; add.u32 n, n, 1; setp.lt.and.u32 p, n, 0x100000, !p; @p bra W%=;}"
                   ::"r"(bar0 + 8 * B_LZ) : "memory");
      mbar_wait(bar0 + 8 * B_QF);
      unsigned bad = 0;
#pragma unroll
      for (int k = 0; k < 8; k++) bad |= __float_as_uint(lds4(sb + O_Q + k * 4096 + tid * 16 + (lane >> 3) * 4)) ^ par;
      if (__builtin_expect(__any_sync(~0u, bad & 1), 0)) {
#pragma unroll 1
        for (int k = 0; k < 8; k++) {
          uint4 v;
          POLL { v = ldx16(scr->qa + k * 256 + tid); RETRY(((lane & 16) ? ((lane & 8) ? v.w : v.z) : ((lane & 8) ? v.y : v.x)) ^ par) }
          sts16(sb + O_Q + k * 4096 + tid * 16, v);
        }
        asm volatile("fence.proxy.async.shared::cta;" ::: "memory");
      }
      if (warp >= 4) nbar_arrive(1, 256); else nbar(1, 256);
    }
#pragma unroll 1
    for (int t = 0; t < nt; t++) {
      const int v = v0 + t;
      const uint32_t fb = bar0 + (v & 1) * 32, ph = (v >> 1) & 1, av = a_v + (v & 1) * 65536;
      uint32_t vf[4][4][4], cnt;
      auto landed = [&]() {
        cnt = rel + (dep16(&vf[0][0][0]) & (nt >> 8));
        PIN(cnt);
      };
      if (wg == 0) {
        const uint32_t da = DSC + (v & 1) * 4096, db = DSC + O_Q / 16;
#pragma unroll 1
        for (int j = 0; j < 4; j++) {
          mbar_wait(fb + 8 * j, ph);
          asm volatile("wgmma.fence.sync.aligned;" ::: "memory");
#pragma unroll
          for (int k = 0; k < 8; k++)
            wgmma32<0, 0, HI128, HI128>(sx, da + j * 1024 + (k >> 2) * 512 + (k & 3) * 2, db + j * 512 + (k >> 2) * 256 + (k & 3) * 2, k ? 1 : j);
          asm volatile("wgmma.commit_group.sync.aligned;" ::: "memory");
          if (j == VJ) {
#pragma unroll
            for (int i = 0; i < 16; i++) ldsm_t(vf[i >> 2][i & 3], av + (((i >> 2) + rot) & 3) * 8192 + (i & 3) * 2048);
            nbar(5, 256);
            landed();
          }
        }
      } else {
        nbar_arrive(5, 256);
#pragma unroll 1
        for (int j = 0; j < 2; j++) {
          mbar_wait(fb + 16 + 8 * j, ph);
          if (j) spin_until(clock() + VDLY);
#pragma unroll
          for (int q = 0; q < 4; q++)
            if (((q + rot) & 2) == 2 * j)
#pragma unroll
              for (int k = 0; k < 4; k++) ldsm_t(vf[q][k], av + ((q + rot) & 3) * 8192 + k * 2048);
        }
        cnt = 0;
      }
      wg_wait<0>(sx);
      asm volatile("{.reg .pred p; setp.ne.s32 p, %1, 0; @p mbarrier.arrive.shared::cta.b64 _, [%0], %1;}" ::"r"(fb + 8 * B_EMPTY + 8 * tq), "r"(cnt) : "memory");
#pragma unroll 1
      for (int pass = 0;; pass++) {
        int ex = !(t | pass);
        if (wg == 0 && (t | pass)) {
          uint32_t pk[8];
#pragma unroll
          for (int i = 0; i < 8; i++) pk[i] = pack2(ex2(sx[2 * i] * sc - mref[i & 6]), ex2(sx[2 * i + 1] * sc - mref[(i & 6) + 1]));
          asm volatile("stmatrix.sync.aligned.m8n8.x4.shared.b16 [%0], {%2,%3,%4,%5};\n"
                       "stmatrix.sync.aligned.m8n8.x4.shared.b16 [%1], {%6,%7,%8,%9};"
                       ::"r"(a_p), "r"(a_p ^ 32), "r"(pk[0]), "r"(pk[1]), "r"(pk[2]), "r"(pk[3]), "r"(pk[4]), "r"(pk[5]), "r"(pk[6]), "r"(pk[7]) : "memory");
          const uint32_t mx = __vmaxu2(__vmaxu2(__vmaxu2(pk[0], pk[1]), __vmaxu2(pk[2], pk[3])), __vmaxu2(__vmaxu2(pk[4], pk[5]), __vmaxu2(pk[6], pk[7])));
          ex = max(mx, mx << 16) > (127u + TAU) << 23;
          asm volatile("fence.proxy.async.shared::cta;" ::: "memory");
        }
        asm volatile("{.reg .pred p, q; setp.ne.s32 q, %0, 0; bar.red.or.pred p, 4, 256, q; selp.s32 %0, 1, 0, p;}" : "+r"(ex)::"memory");
        if (!ex || pass) break;
        int ln;
        asm volatile("mov.u32 %0, %%laneid;" : "=r"(ln));
        const uint32_t a_pm = sb + O_SM + ln * 16;
        if (wg == 0) {
          float cm[8];
#pragma unroll
          for (int i = 0; i < 8; i++) cm[i] = fmaxf(sx[2 * (i & 6) + (i & 1)], sx[2 * (i & 6) + (i & 1) + 2]);
          tmax<4>(cm, lane, 16); tmax<2>(cm, lane, 8); tmax<1>(cm, lane, 4);
          sts4(a_pm + warp * 4, cm[0] * sc);
        }
        nbar(4, 256);
        const float4 pm = lds16(a_pm);
        const float mn = u2f(__float_as_uint(fmaxf(fmaxf(fmaxf(pm.x, pm.y), fmaxf(pm.z, pm.w)), mrun)) | 1u), al = ex2(mrun - mn);
        mrun = mn;
#pragma unroll
        for (int i = 0; i < 8; i++) {
          const float a = __shfl_sync(~0u, al, 4 * i + (ln & 3)), aw = wg ? a : 1.f;
          mref[i] = __shfl_sync(~0u, mn, 4 * i + (ln & 3));
#pragma unroll
          for (int e = 0; e < 2; e++) {
            const int k = 2 * (i & 6) + (i & 1) + 2 * e;
            o[0][k] *= a; o[1][k] *= a; o[2][k] *= a; o[3][k] *= a; sx[k] *= aw;
          }
        }
      }
      float hv = mrun;
      if (wg) {
        asm volatile("wgmma.fence.sync.aligned;" ::: "memory");
#pragma unroll
        for (int k = 0; k < 4; k++) wgmma32r(sx, ones, DSC + O_P / 16 + k * 64);
        asm volatile("wgmma.commit_group.sync.aligned;" ::: "memory");
        landed();
        asm volatile("{.reg .pred p; setp.ne.s32 p, %1, 0; @p mbarrier.arrive.shared::cta.b64 _, [%0], %1;}" ::"r"(fb + 8 * B_EMPTY + 8 * tq), "r"(cnt) : "memory");
        wg_wait<0>(sx);
        float lv[4];
#pragma unroll
        for (int j = 0; j < 4; j++) lv[j] = (lane & 4) ? sx[4 * j + 1] : sx[4 * j];
        hv = (lane & 16) ? ((lane & 8) ? lv[3] : lv[2]) : ((lane & 8) ? lv[1] : lv[0]);
      }
      asm volatile("{.reg .pred p; setp.eq.s32 p, %3, %4; @p st.relaxed.cluster.b32 [%0], %1; @p st.relaxed.cluster.b32 [%2], %1;}"
                   ::"l"(a_h), "r"(__float_as_uint(hv) | 1u), "l"(a_h1), "r"(t), "r"(nt - 1) : "memory");
#pragma unroll
      for (int q = 0; q < 4; q++) {
        asm volatile("wgmma.fence.sync.aligned;" ::: "memory");
#pragma unroll
        for (int k = 0; k < 4; k++) wgmma32r(o[q], vf[q][k], DSC + O_P / 16 + k * 64);
        asm volatile("wgmma.commit_group.sync.aligned;" ::: "memory");
        if (q == 3) {
#pragma unroll
          for (int u = 0; u < 4; u++) ldsm_t(z[u], a_z[u] + u * 1024);
        }
        wg_wait<0>(o[q]);
#pragma unroll
        for (int j = 0; j < 2; j++)
          asm volatile("{.reg .pred p; setp.eq.s32 p, %5, %6; @p st.relaxed.cluster.v4.b32 [%0], {%1,%2,%3,%4};}"
                       ::"l"(dst[q] + j * 512), "r"(pack2t(o[q][8 * j], o[q][8 * j + 1], 1)), "r"(pack2(o[q][8 * j + 2], o[q][8 * j + 3])),
                         "r"(pack2(o[q][8 * j + 4], o[q][8 * j + 5])), "r"(pack2(o[q][8 * j + 6], o[q][8 * j + 7])), "r"(t), "r"(nt - 1) : "memory");
      }
    }
  }
  {
    uint32_t wx[4][4];
    mbar_wait(bar0 + 8 * B_WZ);
#pragma unroll
    for (int u = 0; u < 4; u++) {
      uint2 wp;
      asm volatile("ld.shared.v2.u32 {%0, %1}, [%2];" : "=r"(wp.x), "=r"(wp.y) : "r"(a_w + u * 8) : "memory");
      const bool lo = (g >> 1) == (tq >> 1), hi = (g >> 1) == 2 + (tq >> 1);
      wx[u][0] = lo ? wp.x : 0u; wx[u][1] = lo ? wp.y : 0u; wx[u][2] = hi ? wp.x : 0u; wx[u][3] = hi ? wp.y : 0u;
    }
    auto bad = [&]() {
      const unsigned ok = and3(and3(and3(z[0][0], z[0][1], z[0][2]), and3(z[0][3], z[1][0], z[1][1]), and3(z[1][2], z[1][3], z[2][0])),
                               and3(and3(z[2][1], z[2][2], z[2][3]), and3(z[3][0], z[3][1], z[3][2]), z[3][3]), 0x10001u);
      return __any_sync(~0u, g == 0 && ok != 0x10001u);
    };
    POLL {
      if (it_)
#pragma unroll
        for (int u = 0; u < 4; u++) ldsm_t(z[u], a_z[u] + u * 1024);
      if (!bad() || ++it_ >= SPIN_MAX) break;
    }
    float d0[8][4] = {}, d[8][4], r[8];
#pragma unroll
    for (int i = 0; i < 8; i++) mma16(d0[i], wx[i >> 1], z[i >> 1][2 * (i & 1)], z[i >> 1][2 * (i & 1) + 1]);
    POLL {
#pragma unroll
      for (int u = 0; u < 4; u++) ldsm_t(z[u], a_z[u ^ 2] + u * 1024);
#pragma unroll
      for (int i = 0; i < 8; i++) mma16c(d[i], wx[(i >> 1) ^ 2], z[i >> 1][2 * (i & 1)], z[i >> 1][2 * (i & 1) + 1], d0[i]);
      if (!bad() || ++it_ >= SPIN_MAX) break;
    }
#pragma unroll
    for (int i = 0; i < 8; i++) r[i] = (tq & 2) ? ((g & 1) ? d[i][3] : d[i][2]) : ((g & 1) ? d[i][1] : d[i][0]);
#pragma unroll
    for (int q = 0; q < 2; q++) pub8(p_rec + q * 128, pack2t(r[4 * q], r[4 * q + 1], par) | 1u, pack2(r[4 * q + 2], r[4 * q + 3]));
  }
  const int vt = v0 + nt;
  const uint32_t bufa = sb + (vt & 1) * 65536, fulla = bar0 + (vt & 1) * 32, pha = (vt >> 1) & 1, phb = ((vt + 1) >> 1) & 1;
  const uint32_t bufo = sb + ((vt + 1) & 1) * 65536, fullb = bar0 + ((vt + 1) & 1) * 32;
  uint32_t a_rs = sb + O_R + (warp >> 2) * 1024 + (16 * tq + g) * 16 + ((warp + tq) & 3) * 4;
  if (isA) {
    const int row = 16 * (warp & 6) + 8 * (warp & 1) + (lane & 16) + ((lane & 7) >> 1) + 4 * (lane & 1);
    uint32_t ab = bufa + row * 128 + ((((lane >> 3) & 1) ^ (row & 7)) << 4);
    const uint2* pr = scr->rec + (hd * 32 + warp) * 64 + lane;
    uint32_t a_cb = mapa(bar0 + 8 * B_HZ, (warp & 6) + (lane >> 4)), a_c = a_cb - (O_BAR + 8 * B_HZ - O_CTX) + (2 * rn + (warp & 1)) * 64 + tq * 16;
    uint32_t a_rl = sb + O_R + (32 * (warp & 1) + lane) * 16;
    uint32_t ao = bufo + (16 * warp + 8 * (lane >> 4) + (lane & 7)) * 128 + ((((lane >> 3) & 1) ^ (lane & 7)) << 4);
    uint32_t a_cx = sb + O_CTX + (warp >> 1) * 64 + tq * 16 + (warp & 1) * 8, a_ga = sb + O_SM + (320 + posof(tid & 63)) * 4;
    unsigned* p_ao = scr->xao + b * 64 + (tid & 63);
    unsigned* p_ab = scr->xab + cl * 256 + (2 * (rn & 3) + (warp & 1)) * 32 + (rn >> 2) * 16 + (lane >> 1);
    float xv = cl == 0 ? __bfloat162float(x[64 * rn + (tid & 63)]) : 0.f;
    unsigned p2 = lane >= 28 ? 0 : par;
    PIN(ab); PINL(pr); PIN(a_cb); PIN(a_c); PIN(a_rl); PIN(a_rs); PIN(ao); PIN(a_cx); PIN(a_ga); PINL(p_ao); PINL(p_ab); PIN(p2);
    asm volatile("" : "+f"(xv));
    uint32_t aw[4][4][4];
    auto wo = [&](const int j) {
      mbar_wait(fullb + 8 * j, phb);
#pragma unroll
      for (int mt = 0; mt < 4; mt++) ldsm_t(aw[j][mt], (ao + j * 16384) ^ (mt << 5));
    };
    {
      uint32_t a[4][4][4];
      uint2 z[4], y[4] = {};
      float d[4][4] = {}, r[8];
      mbar_wait(fulla, pha);
      POLL {
#pragma unroll
        for (int q = 0; q < 4; q++) z[q] = ldx8(pr + q * 512);
        RETRY(lop_x3(z[0].x, z[1].x, par) | lop_x3(z[2].x, z[3].x, par))
      }
#pragma unroll
      for (int q = 0; q < 4; q++) {
        if (q == 3) {
          mbar_wait(bar0 + 8 * B_G);
          if (lane < 28)
#pragma unroll
            for (int u = 0; u < 4; u++) y[u] = ldx8(pr + u * 512 + 32);
          __syncwarp();
        }
        mbar_wait(fulla + 8 * q, pha);
#pragma unroll
        for (int mt = 0; mt < 4; mt++) ldsm_t(a[q][mt], (ab + q * 16384) ^ (mt << 5));
#pragma unroll
        for (int mt = 0; mt < 4; mt++) mma16(d[mt], a[q][mt], z[q].x, z[q].y);
      }
      mbar_wait(bar0 + 8 * B_W);
      const float4 W = lds16(sb + O_SM + (384 + 4 * tq) * 4);
#pragma unroll
      for (int i = 0; i < 8; i++) { r[i] = W.x * d[i >> 1][2 * (i & 1)] + W.y * d[i >> 1][2 * (i & 1) + 1]; asm volatile("" : "+f"(r[i])); }
#pragma unroll
      for (int j = 0; j < NPE; j++) wo(j);
      POLL {
        if (it_)
#pragma unroll
          for (int u = 0; u < 4; u++) y[u] = ldx8(pr + u * 512 + 32);
#pragma unroll
        for (int mt = 0; mt < 4; mt++) d[mt][0] = d[mt][1] = d[mt][2] = d[mt][3] = 0.f;
#pragma unroll
        for (int q = 0; q < 4; q++)
#pragma unroll
          for (int mt = 0; mt < 4; mt++) mma16(d[mt], a[q][mt], y[q].x, y[q].y);
        RETRY(or3(lop_x3(y[0].x, y[1].x, p2), lop_x3(y[2].x, y[3].x, p2), 0))
      }
#pragma unroll
      for (int i = 0; i < 8; i++) r[i] = W.w * d[i >> 1][2 * (i & 1) + 1] + (W.z * d[i >> 1][2 * (i & 1)] + r[i]);
      tred<4>(r, lane, 2); tred<2>(r, lane, 1);
      sts4(a_rs, r[0]); sts4(a_rs + 128, r[1]);
      nbar(1, 256);
      send32(a_c, a_cb, sum8(a_rl), lane);
    }
    {
#pragma unroll
      for (int j = NPE; j < NPO; j++) wo(j);
      uint2 c[4];
      mbar_wait(bar0 + 8 * B_HZ);
#pragma unroll
      for (int j = 0; j < 4; j++) asm volatile("ld.shared.v2.u32 {%0, %1}, [%2];" : "=r"(c[j].x), "=r"(c[j].y) : "r"(a_cx + j * 256) : "memory");
      float d[4][4] = {};
#pragma unroll
      for (int j = 0; j < 4; j++) {
        if (j + 1 >= NPO && j < 3) wo(j + 1);
#pragma unroll
        for (int mt = 0; mt < 4; mt++) mma16(d[mt], aw[j][mt], c[j].x, c[j].y);
      }
      const float r0 = (tq & 2) ? ((tq & 1) ? d[3][0] : d[2][0]) : ((tq & 1) ? d[1][0] : d[0][0]);
      const float r1 = (tq & 2) ? ((tq & 1) ? d[3][2] : d[2][2]) : ((tq & 1) ? d[1][2] : d[0][2]);
      sts4(a_rs + 2048, r0); sts4(a_rs + 2048 + 128, r1);
      if (warp >= 2) nbar_arrive(2, 256);
      else {
        mbar_wait(bar0 + 8 * B_TAB);
        const float gav = lds4(a_ga);
        nbar(2, 256);
        const float t = gav * sum8(a_rl + 2048) + xv;
        asm volatile("{.reg .pred p; setp.eq.s32 p, %2, 0; @p red.relaxed.gpu.global.xor.b32 [%0], %1;}"
                     ::"l"(p_ab), "r"(pack2t(t, __shfl_down_sync(~0u, t, 1), par) | 1u), "r"(lane & 1) : "memory");
        pub4(p_ao, __float_as_uint(t) | 1u);
      }
    }
  } else {
    uint32_t af[4][4][4];
    uint32_t ab = bufa + (32 * warp + 8 * (lane >> 4) + (lane & 7)) * 64 + ((((lane >> 3) & 1) ^ ((lane >> 1) & 3)) << 4);
    uint32_t a_d = bufo + (8 * (lane >> 4) + (lane & 7)) * 128 + (((2 * (warp & 3) + ((lane >> 3) & 1)) ^ (lane & 7)) << 4);
    uint32_t a_rl = sb + O_R + lane * 16, a_st = sb + O_SM + (352 + 8 * (lane >> 4) + warp) * 4;
    const unsigned* pa = scr->xab + tid;
    uint32_t a_hb = mapa(bar0 + 8 * B_HZ, 2 * (warp & 3) + (lane >> 4)), a_h = a_hb - (O_BAR + 8 * B_HZ - O_CTX) + rn * 64 + tq * 16;
    PIN(a_hb); PIN(a_h);
    const int col = 64 * rn + 16 * (warp & 3) + 8 * (tq & 1) + g;
    uint32_t a_hl = sb + O_CTX + tq * 16;
    const unsigned* px = scr->xao + (tq & 2) * 1024 + col;
    bf16* po = out + col;
    PIN(ab); PIN(a_d); PIN(a_rl); PINL(pa); PIN(a_rs); PIN(a_st); PINL(po); PIN(a_hl); PINL(px);
    mbar_wait(bar0 + 8 * B_TAB);
    uint2 cf;
    uint2 bb[4];
    unsigned gbw;
    POLL {
      unsigned bad = 0;
      cf = ldx8(scr->xm + 1024 + (lane & 16) * 16 + 32 * warp + posof(2 * (lane & 15)));
#pragma unroll
      for (int s = 0; s < 4; s++) {
        const uint4 w = ldx16(scr->xm + 1024 - (g & 1) * 512 + 256 * (s >> 1) + 32 * warp + 16 * (s & 1) + 4 * tq);
        bb[s] = make_uint2(__byte_perm(w.x, w.y, 0x7632), __byte_perm(w.z, w.w, 0x7632));
        bad = or3(bad, lop_x3(w.x, w.y, par), lop_x3(w.z, w.w, par));
      }
      gbw = ldx4(scr->xm + 1536 + posof(col));
      RETRY(or3(bad, lop_x3(cf.x, cf.y, par), gbw ^ par))
    }
    const float gbv = bfhi(gbw);
    float e[4][4] = {};
    unsigned v[8];
    auto item = [&](const int it) {
      mbar_wait(fulla + 8 * it, pha);
#pragma unroll
      for (int i = 0; i < 4; i++) ldsm_t(af[it][i], (ab + it * 16384 + (i >> 1) * 1024) ^ ((i & 1) << 5));
    };
    auto item_mma = [&](const int it) {
#pragma unroll
      for (int i = 0; i < 4; i++) mma16(e[2 * (it & 1) + (i & 1)], af[it][i], bb[(it & 2) + (i >> 1)].x, bb[(it & 2) + (i >> 1)].y);
    };
    unsigned t3 = sch.wt;
    PIN(t3);
    item(0); item_mma(0); item(1); item_mma(1);
    mbar_wait(bar0 + 8 * B_G);
#pragma unroll
    for (int i = 0; i < 8; i++) v[i] = ldx4(pa + i * 256);
    t3 += clock();
    uint32_t have2, have3 = 0;
    do have2 = mbar_test(fulla + 16, pha); while (!have2 && (int)((unsigned)clock() - t3) < 0);
    if (have2) {
      item(2); item_mma(2);
      do have3 = mbar_test(fulla + 24, pha); while (!have3 && (int)((unsigned)clock() - t3) < 0);
      if (have3) { item(3); item_mma(3); }
    }
    float y0, y1, df[4][4], st[2];
    uint32_t bz[4][2] = {};
    auto mm = [&](const int it, const int i) { mma16(df[2 * (it & 1) + (i & 1)], af[it][i], bz[(it & 2) + (i >> 1)][0], bz[(it & 2) + (i >> 1)][1]); };
    POLL {
      if (it_)
#pragma unroll
        for (int i = 0; i < 8; i++) v[i] = ldx4(pa + i * 256);
      y0 = ((bflo(v[0]) + bflo(v[1])) + (bflo(v[2]) + bflo(v[3]))) + ((bflo(v[4]) + bflo(v[5])) + (bflo(v[6]) + bflo(v[7])));
      y1 = ((bfhi(v[0]) + bfhi(v[1])) + (bfhi(v[2]) + bfhi(v[3]))) + ((bfhi(v[4]) + bfhi(v[5])) + (bfhi(v[6]) + bfhi(v[7])));
      const uint32_t zb = pack2(y0 * u2f(cf.x), y1 * u2f(cf.y));
#pragma unroll
      for (int s = 0; s < 4; s++) {
        const uint32_t w = __shfl_sync(~0u, zb, 8 * s + (lane & 7));
        bz[s][0] = (lane & 4) ? 0u : w; bz[s][1] = (lane & 4) ? w : 0u;
      }
      st[0] = y0 + y1; st[1] = y0 * y0 + y1 * y1;
      tred<1>(st, lane, 16);
#pragma unroll
      for (int i = 0; i < 4; i++) df[i][0] = df[i][1] = df[i][2] = df[i][3] = 0.f;
      mm(0, 0); mm(0, 1); mm(1, 0); mm(1, 1);
      st[0] += shx(st[0], 8);
      mm(0, 2); mm(0, 3); mm(1, 2); mm(1, 3);
      RETRY(or3(or3(lop_x3(v[0], v[1], par), lop_x3(v[2], v[3], par), lop_x3(v[4], v[5], par)), lop_x3(v[6], v[7], par), 0))
    }
    unsigned xq[4];
    if (wg == 0)
#pragma unroll
      for (int i = 0; i < 4; i++) xq[i] = ldx4(px + i * 512);
    if (have2) { mm(2, 0); mm(2, 1); mm(2, 2); mm(2, 3); }
    st[0] += shx(st[0], 4);
    st[0] += shx(st[0], 2);
    st[0] += shx(st[0], 1);
    sts4(a_st, st[0]);
    __syncwarp();
    arrive_n(bar0 + 8 * B_ST, lane == 0, 1);
    if (!have2) { item(2); item_mma(2); mm(2, 0); mm(2, 1); mm(2, 2); mm(2, 3); }
    if (!have3) { item(3); item_mma(3); }
    mm(3, 0); mm(3, 1); mm(3, 2); mm(3, 3);
    mbar_wait(bar0 + 8 * B_ST);
    float mean, rstd;
    {
      float4 u[4];
#pragma unroll
      for (int i = 0; i < 4; i++) u[i] = lds16(sb + O_SM + (352 + 4 * i) * 4);
      mean = (((u[0].x + u[0].y) + (u[0].z + u[0].w)) + ((u[1].x + u[1].y) + (u[1].z + u[1].w))) * (1.f / 512.f);
      const float sq = (((u[2].x + u[2].y) + (u[2].z + u[2].w)) + ((u[3].x + u[3].y) + (u[3].z + u[3].w))) * (1.f / 512.f);
      asm("rsqrt.approx.ftz.f32 %0, %1;" : "=f"(rstd) : "f"(fmaxf(sq - mean * mean, 0.f) + 1e-5f));
    }
    float A[4], r[4];
#pragma unroll
    for (int i = 0; i < 4; i++) {
      A[i] = (tq & 2) ? ((tq & 1) ? e[3][i] : e[2][i]) : ((tq & 1) ? e[1][i] : e[0][i]);
      r[i] = (tq & 2) ? ((tq & 1) ? df[3][i] : df[2][i]) : ((tq & 1) ? df[1][i] : df[0][i]);
    }
    sts4(a_rs, rstd * (r[0] + r[1]) + (A[1] - rstd * mean * A[0])); sts4(a_rs + 128, rstd * (r[2] + r[3]) + (A[3] - rstd * mean * A[2]));
    nbar(1, 256);
    if (wg) {
      const float4 g0 = lds16(a_rl), g1 = lds16(a_rl + 1024), u0 = lds16(a_rl + 512), u1 = lds16(a_rl + 1536);
      const float gg = bfr(((g0.x + g0.y) + (g0.z + g0.w)) + ((g1.x + g1.y) + (g1.z + g1.w)));
      const float uu = bfr(((u0.x + u0.y) + (u0.z + u0.w)) + ((u1.x + u1.y) + (u1.z + u1.w)));
      const float hh = bfr(gg * rcp(1.f + ex2(gg * (-2.302208198f - 0.1029432397f * gg * gg)))) * uu;
      send32(a_h, a_hb, hh, lane);
    } else {
      uint32_t ad[16][4];
      spin_until(clock() + FDLY);
#pragma unroll
      for (int j = 0; j < 2; j++) {
        mbar_wait(fullb + 8 * j, phb);
#pragma unroll
        for (int i = 0; i < 8; i++) ldsm_t(ad[8 * j + i], a_d + (8 * j + i) * 2048);
      }
      POLL {
        if (it_)
#pragma unroll
          for (int i = 0; i < 4; i++) xq[i] = ldx4(px + i * 512);
        RETRY(lop_x3(xq[0], xq[1], par) | lop_x3(xq[2], xq[3], par))
      }
      float x7 = (u2f(xq[0]) + u2f(xq[1])) + (u2f(xq[2]) + u2f(xq[3]));
      x7 = (x7 + __shfl_xor_sync(~0u, x7, 2)) * (1.f / 7.f);
      uint4 hb[8];
      mbar_wait(bar0 + 8 * B_HZ);
#pragma unroll
      for (int i = 0; i < 8; i++) { const float4 q = lds16(a_hl + i * 64); hb[i] = *(const uint4*)&q; }
      float dd[4][4] = {};
#pragma unroll
      for (int i = 0; i < 8; i++) { mma16(dd[(2 * i) & 3], ad[2 * i], hb[i].x, hb[i].y); mma16(dd[(2 * i + 1) & 3], ad[2 * i + 1], hb[i].z, hb[i].w); }
      const float t = gbv * ((tq & 1) ? (dd[0][2] + dd[1][2]) + (dd[2][2] + dd[3][2]) : (dd[0][0] + dd[1][0]) + (dd[2][0] + dd[3][0])) + x7;
      asm volatile("{.reg .pred p; setp.eq.s32 p, %2, 0; @p red.relaxed.gpu.global.add.noftz.bf16x2 [%0], %1;}"
                   ::"l"(po), "r"(pack2(t, __shfl_down_sync(~0u, t, 4))), "r"(lane & 6) : "memory");
      if (f == 0 && tid == 0) stx4(&scr->cnt[0], epoch + 1);
    }
  }
}

static void make_sched(Sched& s) {
  const char* order = "FFAAbcFmmvog..d";
  const double dt = 5010 * 1e-3, dth = 4850 * 1e-3;
  const int nbig = NBIG;
  s.zero = 0; s.dth = (unsigned)(dth * 256 + 0.5);
  double t = 512 * dth + 80;
  int tile = 0, jm = 0;
  for (int i = 0; i < 3; i++) s.nr[i] = s.nt[i] = 0;
  auto add = [&](int c, int type, double step, int win, int b0, int tl) {
    s.r[c][s.nr[c]++] = make_uint2((unsigned)(t + 0.5) | (unsigned)(step + 0.5) << 16, type | win << 4 | (b0 + 64) << 8 | tl << 16);
    if (type == T_KV) s.nt[c]++;
  };
  const int w1 = 6, w2 = 4, wt = 6;
  for (const char* p = order; *p; p++) {
    const char c = *p;
    if (c == 'v' || c == 'o' || c == 'm') {
      const int ty = c == 'v' ? T_UV : c == 'o' ? T_WO : T_MOD;
      const double d = (c == 'm' ? 5010 : c == 'v' ? 5500 : 5500) * 1e-3;
      add(0, ty, 64 * d, wt, 0, c == 'm' ? jm : 0); add(1, ty, 64 * d, wt, 0, c == 'm' ? jm : 0);
      t += (c == 'm' ? 64 : 256) * d; jm += c == 'm';
    } else if (c == 'g' || c == 'd') {
      const double d = (c == 'g' ? 5500 : 5500) * 1e-3;
      add(2, c == 'g' ? T_GU : T_DN, 56 * d, wt, 64, 0);
      t += (c == 'g' ? 224 : 112) * d;
    } else if (c == '.') t += 100;
    else if (c == '-') t -= 100;
    else {
      const int na = c == 'F' ? 0 : c == 'C' || c == 'c' || c == 'a' ? nbig : 64, nf = c == 'A' || c == 'a' ? 0 : 56, n = na + nf;
      const int w = na && nf ? w2 : w1;
      const bool ff = c == 'b' || c == 'c';
      const int cf = c == 'c' ? 60 : 0, ca = cf * 7 / 5;
      t += 3 * ca;
      if (na) add(0, T_KV, n * dt - ca, w, ff ? -56 : 0, tile);
      t -= 3 * ca;
      if (na == 64) add(1, T_KV, n * dt, w, ff ? -56 : 0, tile);
      if (nf) add(2, T_KV, n * dt - cf, w, ff ? 64 : 64 - na, tile);
      tile += n; t += 4 * n * dt;
      s.t4 = (unsigned)t + 600;
    }
  }
  s.dt = (unsigned)(dt * 256 + 0.5); s.d4 = 1550 | 1200 << 16; s.d6 = 3180; s.wt = 250;
}

static void launch(void* const* d_in, void* d_out) {
  static TMaps tms;
  static Sched sch;
  static bool init = false;
  static void* scr = nullptr;
  if (!init) {
    void* fn = nullptr; cudaDriverEntryPointQueryResult qr;
    cudaGetDriverEntryPoint("cuTensorMapEncodeTiled", &fn, cudaEnableDefault, &qr);
    EncFn f = (EncFn)fn;
    const CUtensorMapSwizzle S64 = CU_TENSOR_MAP_SWIZZLE_64B, S128 = CU_TENSOR_MAP_SWIZZLE_128B;
    const CUtensorMapL2promotion P256 = CU_TENSOR_MAP_L2_PROMOTION_L2_256B;
    enc3d(f, &tms.m[0], d_in[2], 64, 512, 64, 8192, 128, 64, 128, 1, S128, CU_TENSOR_MAP_L2_PROMOTION_L2_128B);
    enc3d(f, &tms.m[1], d_in[3], 64, 512, 64, 8192, 128, 64, 64, 2, S128, P256);
    enc3d(f, &tms.m[2], d_in[1], 64, SK, 8, 1024, 128, 64, 64, 2, S128, P256);
    enc3d(f, &tms.m[3], d_in[11], 3072, 256, 2, 6144, 256 * 6144, 32, 256, 1, S64, CU_TENSOR_MAP_L2_PROMOTION_L2_128B);
    enc3d(f, &tms.m[4], d_in[4], 64, 512, 64, 8192, 128, 64, 128, 1, S128, CU_TENSOR_MAP_L2_PROMOTION_L2_128B);
    enc3d(f, &tms.m[5], d_in[5], 512, 128, 32, 1024, 128 * 1024, 64, 128, 1, S128, CU_TENSOR_MAP_L2_PROMOTION_L2_128B);
    enc3d(f, &tms.m[6], d_in[7], 1792, 256, 2, 3584, 256 * 3584, 32, 256, 1, S64, CU_TENSOR_MAP_L2_PROMOTION_L2_128B);
    enc3d(f, &tms.m[7], d_in[8], 1792, 256, 2, 3584, 256 * 3584, 32, 256, 1, S64, CU_TENSOR_MAP_L2_PROMOTION_L2_128B);
    enc3d(f, &tms.m[8], d_in[9], 512, 128, 14, 1024, 128 * 1024, 64, 128, 1, S128, CU_TENSOR_MAP_L2_PROMOTION_L2_128B);
    cudaFuncSetAttribute(fused_kernel, cudaFuncAttributeMaxDynamicSharedMemorySize, SMEM9);
    cudaGetSymbolAddress(&scr, g_scr);
    make_sched(sch);
    init = true;
  }
  fused_kernel<<<NCTA9, 384, SMEM9>>>((const bf16*)d_in[0], (const bf16*)d_in[10], (const bf16*)d_in[11], (bf16*)d_out, (Scratch*)scr, sch, tms);
}

static bool fits() {
  cudaFuncSetAttribute(fused_kernel, cudaFuncAttributeMaxDynamicSharedMemorySize, SMEM9);
  cudaLaunchConfig_t cfg = {};
  cfg.gridDim = dim3(NCTA9); cfg.blockDim = dim3(384); cfg.dynamicSmemBytes = SMEM9;
  cudaLaunchAttribute at[1];
  at[0].id = cudaLaunchAttributeClusterDimension; at[0].val.clusterDim.x = 8; at[0].val.clusterDim.y = 1; at[0].val.clusterDim.z = 1;
  cfg.attrs = at; cfg.numAttrs = 1;
  int n = 0;
  if (cudaOccupancyMaxActiveClusters(&n, fused_kernel, &cfg) != cudaSuccess) { (void)cudaGetLastError(); return false; }
  return n >= NCTA9 / 8;
}
}
#undef BAR_ARM
#undef BAR_ARRIVE
#undef BAR_INIT
#undef B_EM
#undef B_EMPTY
#undef B_FM
#undef B_FULL
#undef B_G
#undef B_G2
#undef B_H
#undef B_HZ
#undef B_LZ
#undef B_Q2
#undef B_QF
#undef B_ST
#undef B_TAB
#undef B_W
#undef B_WZ
#undef CNT_ADD
#undef DSC
#undef FDLY
#undef HI128
#undef HI64
#undef LANE0
#undef NBIG
#undef NCTA9
#undef NPE
#undef NPO
#undef NSL
#undef O_B
#undef O_BAR
#undef O_CTX
#undef O_DBG
#undef O_EP
#undef O_HW
#undef O_HZ
#undef O_LZ
#undef O_P
#undef O_Q
#undef O_R
#undef O_SILU
#undef O_SM
#undef O_X
#undef PIN
#undef PINL
#undef POLL
#undef QN
#undef RETRY
#undef SK
#undef SMEM9
#undef SMEM_BASE
#undef SPIN_MAX
#undef TAU
#undef VDLY
#undef VJ
#undef X16
#undef fbits

namespace v8 {
typedef __nv_bfloat16 bf16;
#define NCTA 128
#define SK 32768
#define SLOT 32768
#define NSLOT 6
#define OFF_WQ (2 * SLOT)
#define OFF_WUK (4 * SLOT)
#define OFF_Q 196608
#define OFF_P (OFF_Q + 16384)
#define OFF_B (OFF_P + 4096)
#define OFF_R4 (OFF_B + 2304)
#define OFF_SILU (OFF_R4 + 4096)
#define OFF_RA (OFF_SILU + 1024)
#define OFF_SM (OFF_RA + 1024)
#define OFF_BP (OFF_SM + 1792)
#define OFF_CO (OFF_BP + 1024)
#define OFF_BAR (OFF_CO + 1280)
#define OFF_MASK (OFF_BAR + 512)
#define OFF_DBG (OFF_MASK + 16)
#define SMEM_BYTES (OFF_DBG + 128)
#define OFF_MOD OFF_Q
#define OFF_UV (4 * SLOT)
#define OFF_O (5 * SLOT)
#define OFF_G 0
#define OFF_U 16384
#define OFF_D SLOT
#define OFF_XO (OFF_D + 16384)
#define FB_UK 4
#define FB_KV 6
#define FB_MOD 22
#define FB_UV 23
#define FB_O 25
#define FB_G 27
#define FB_D 29
#define EB 30
#define QB 50
#define XB 51
#define SPIN_MAX (1 << 20)
#define BACKOFF 40
#define RATE_NS 652
#define RATE_T0 200
#define RATE_TL 300
#define WINS 0x3222333
#define KVWIN 4
#define RATE_H 650
#define RATE_E 650
#define SMUL 9
#define NPRE0 1
#define NPRE1 3
#define HWIN 4
#define EWIN 3
#define WTEST 450
#define DLY5 650
#define DLY6 600
#define DLY7 600
#define P12(a, b, c, d, e, f, g, h, i, j, k, l) ((unsigned long long)(a) | (b) << 5 | (c) << 10 | (d) << 15 | (e) << 20 | (f) << 25 | \
  (unsigned long long)(g) << 30 | (unsigned long long)(h) << 35 | (unsigned long long)(i) << 40 | (unsigned long long)(j) << 45 | \
  (unsigned long long)(k) << 50 | (unsigned long long)(l) << 55)
#define ORDER0 P12(0, 1, 2, 3, 4, 5, 16, 6, 7, 8, 9, 10)
#define ORDER1 P12(11, 12, 13, 14, 15, 17, 18, 19, 20, 23, 21, 22)
#define TAIL_K 17
#define RS 16
template <int N> struct IC { static constexpr int value = N; };
struct TMaps { CUtensorMap m[9]; };

struct __align__(128) Scratch {
  uint4 xo[128 * 64 * RS];
  uint2 ml[32 * 64];
  unsigned h[8 * 256];
  unsigned qa[32 * 256];
  unsigned xc[128 * 64];
  unsigned xao[8 * 512];
  unsigned xf[112 * 512];
  unsigned xm[2048];
  unsigned cnt[5 * 32];
};
__device__ Scratch g_scr;
#define g_xo scr->xo
#define g_ml scr->ml
#define g_h scr->h
#define g_qa scr->qa
#define g_xc scr->xc
#define g_xao scr->xao
#define g_xf scr->xf
#define g_xm scr->xm
#define g_epoch scr->cnt[0]

__device__ __forceinline__ uint32_t s2u(const void* p) { return (uint32_t)__cvta_generic_to_shared(p); }
__device__ __forceinline__ float bflo(uint32_t u) { return __uint_as_float(u << 16); }
__device__ __forceinline__ float bfhi(uint32_t u) { return __uint_as_float(u & 0xffff0000u); }
__device__ __forceinline__ float u2f(uint32_t u) { return __uint_as_float(u); }
__device__ __forceinline__ void fma8(float* acc, uint4 v, float s) {
  acc[0] += s * bflo(v.x); acc[1] += s * bfhi(v.x); acc[2] += s * bflo(v.y); acc[3] += s * bfhi(v.y);
  acc[4] += s * bflo(v.z); acc[5] += s * bfhi(v.z); acc[6] += s * bflo(v.w); acc[7] += s * bfhi(v.w);
}
__device__ __forceinline__ uint32_t pack2(float a, float b) {
  __nv_bfloat162 p = __floats2bfloat162_rn(a, b); return *(uint32_t*)&p;
}
__device__ __forceinline__ float bfr(float v) { return bfhi(pack2(v, v)); }
__device__ __forceinline__ float silu_bf(float c) { return bfr(__fdividef(c, 1.f + __expf(-c))); }
#define fbits(v) ((__float_as_uint(v) & ~1u) | par)
__device__ __forceinline__ uint32_t pack2t(float a, float b, unsigned par) {
  const uint32_t ua = ((__float_as_uint(a) + ((par ^ 1) << 16)) & 0xFFFE0000u) | (par << 16);
  return __byte_perm(ua, pack2(b, b), 0x7632);
}
__device__ __forceinline__ void nbar(int id, int n) { asm volatile("bar.sync %0, %1;" ::"r"(id), "r"(n) : "memory"); }
__device__ __forceinline__ void nbar_arrive(int id, int n) { asm volatile("bar.arrive %0, %1;" ::"r"(id), "r"(n) : "memory"); }
__device__ __forceinline__ uint4 ldc16(const void* p) {
  uint4 v; asm volatile("ld.relaxed.cta.global.v4.u32 {%0,%1,%2,%3}, [%4];" : "=r"(v.x), "=r"(v.y), "=r"(v.z), "=r"(v.w) : "l"(p) : "memory"); return v;
}
__device__ __forceinline__ unsigned ldc4(const void* p) {
  unsigned v; asm volatile("ld.relaxed.cta.global.u32 %0, [%1];" : "=r"(v) : "l"(p) : "memory"); return v;
}
__device__ __forceinline__ uint4 ldx16(const void* p) {
  uint4 v; asm volatile("ld.relaxed.gpu.global.v4.u32 {%0,%1,%2,%3}, [%4];" : "=r"(v.x), "=r"(v.y), "=r"(v.z), "=r"(v.w) : "l"(p) : "memory"); return v;
}
__device__ __forceinline__ unsigned ldx4(const void* p) {
  unsigned v; asm volatile("ld.relaxed.gpu.global.u32 %0, [%1];" : "=r"(v) : "l"(p) : "memory"); return v;
}
__device__ __forceinline__ unsigned long long ldx64(const void* p) {
  unsigned long long v; asm volatile("ld.relaxed.gpu.global.u64 %0, [%1];" : "=l"(v) : "l"(p) : "memory"); return v;
}
__device__ __forceinline__ void stx16(void* p, uint4 v) {
  asm volatile("st.relaxed.gpu.global.v4.u32 [%0], {%1,%2,%3,%4};" ::"l"(p), "r"(v.x), "r"(v.y), "r"(v.z), "r"(v.w) : "memory");
}
__device__ __forceinline__ void stx8(void* p, uint2 v) { asm volatile("st.relaxed.gpu.global.v2.u32 [%0], {%1,%2};" ::"l"(p), "r"(v.x), "r"(v.y) : "memory"); }
__device__ __forceinline__ void stx4(void* p, unsigned v) { asm volatile("st.relaxed.gpu.global.u32 [%0], %1;" ::"l"(p), "r"(v) : "memory"); }
__device__ __forceinline__ unsigned lop_x3(unsigned a, unsigned b, unsigned c) {
  unsigned d; asm("lop3.b32 %0, %1, %2, %3, 0x7E;" : "=r"(d) : "r"(a), "r"(b), "r"(c)); return d; }
#define X16(v) (lop_x3(v.x, v.y, par) | lop_x3(v.z, v.w, par))
#define X8(v) lop_x3(v.x, v.y, par)
#define RETRY(bad) if (!__any_sync(~0u, (bad) & 1) || ++it_ >= SPIN_MAX) break; __nanosleep(BACKOFF);
#define POLL _Pragma("unroll 1") for (int it_ = 0;;)
__device__ __forceinline__ void mbar_wait(uint32_t bar) {
  uint32_t ok; int it = 0;
  do {
    asm volatile("{.reg .pred p; mbarrier.try_wait.parity.shared::cta.b64 p, [%1], 0; selp.u32 %0,1,0,p;}"
                 : "=r"(ok) : "r"(bar) : "memory");
  } while (!ok && ++it < SPIN_MAX);
}
__device__ __forceinline__ float ex2(float v) { float r; asm("ex2.approx.ftz.f32 %0, %1;" : "=f"(r) : "f"(v)); return r; }
__device__ __forceinline__ float rcp(float v) { float r; asm("rcp.approx.ftz.f32 %0, %1;" : "=f"(r) : "f"(v)); return r; }
__device__ __forceinline__ void mma16(float* d, const uint32_t* a, uint32_t b0, uint32_t b1) {
  asm volatile("mma.sync.aligned.m16n8k16.row.col.f32.bf16.bf16.f32 {%0,%1,%2,%3}, {%4,%5,%6,%7}, {%8,%9}, {%0,%1,%2,%3};"
               : "+f"(d[0]), "+f"(d[1]), "+f"(d[2]), "+f"(d[3]) : "r"(a[0]), "r"(a[1]), "r"(a[2]), "r"(a[3]), "r"(b0), "r"(b1));
}
__device__ __forceinline__ float4 lds16(uint32_t a) {
  float4 v; asm volatile("ld.shared.v4.f32 {%0,%1,%2,%3}, [%4];" : "=f"(v.x), "=f"(v.y), "=f"(v.z), "=f"(v.w) : "r"(a) : "memory"); return v;
}
__device__ __forceinline__ void ldsm_t(uint32_t* r, uint32_t a) {
  asm volatile("ldmatrix.sync.aligned.m8n8.x4.trans.shared.b16 {%0,%1,%2,%3}, [%4];" : "=r"(r[0]), "=r"(r[1]), "=r"(r[2]), "=r"(r[3]) : "r"(a) : "memory");
}
__device__ __forceinline__ void ldsm(uint32_t* r, uint32_t a) {
  asm volatile("ldmatrix.sync.aligned.m8n8.x4.shared.b16 {%0,%1,%2,%3}, [%4];" : "=r"(r[0]), "=r"(r[1]), "=r"(r[2]), "=r"(r[3]) : "r"(a) : "memory");
}
template <int N>
__device__ __forceinline__ void tred(float* a, int lane, int m) {
  const bool hi = lane & m;
#pragma unroll
  for (int i = 0; i < N; i++) {
    float send = hi ? a[i] : a[i + N], keep = hi ? a[i + N] : a[i];
    a[i] = keep + __shfl_xor_sync(~0u, send, m);
  }
}
template <int N>
__device__ __forceinline__ void tmax(float* a, int lane, int m) {
  const bool hi = lane & m;
#pragma unroll
  for (int i = 0; i < N; i++) {
    float send = hi ? a[i] : a[i + N], keep = hi ? a[i + N] : a[i];
    a[i] = fmaxf(keep, __shfl_xor_sync(~0u, send, m));
  }
}
__device__ __forceinline__ void arrive2(uint32_t bar, uint32_t rbar, bool local, bool remote) {
  asm volatile("{.reg .pred p, q; setp.ne.s32 p, %2, 0; setp.ne.s32 q, %3, 0; @p mbarrier.arrive.shared::cta.b64 _, [%0];\n"
               "@q mbarrier.arrive.relaxed.cluster.shared::cluster.b64 _, [%1];}" ::"r"(bar), "r"(rbar), "r"((int)local), "r"((int)remote) : "memory");
}
__device__ __forceinline__ unsigned long long stream_policy() {
  unsigned long long p;
  asm volatile("createpolicy.fractional.L2::evict_first.b64 %0, 1.0;" : "=l"(p));
  return p;
}
__device__ __forceinline__ void tma3d(uint32_t dst, const CUtensorMap* tm, uint32_t bar, int c0, int c1, int c2) {
  asm volatile("cp.async.bulk.tensor.3d.shared::cluster.global.mbarrier::complete_tx::bytes.L2::cache_hint [%0], [%1, {%3, %4, %5}], [%2], %6;"
               ::"r"(dst), "l"(tm), "r"(bar), "r"(c0), "r"(c1), "r"(c2), "l"(stream_policy()) : "memory");
}
__device__ __forceinline__ void st_async2(uint32_t dst, uint32_t bar, float v0, float v1) {
  asm volatile("st.async.shared::cluster.mbarrier::complete_tx::bytes.v2.f32 [%0], {%1, %2}, [%3];" ::"r"(dst), "f"(v0), "f"(v1), "r"(bar) : "memory");
}
__device__ __forceinline__ void st_pair(int mode, uint32_t dst, uint32_t bar, float v0, float v1) {
  asm volatile("{.reg .pred p, q; setp.eq.s32 p, %4, 1; setp.eq.s32 q, %4, 2; @p st.shared.v2.f32 [%0], {%1, %2};\n"
               "@q st.async.shared::cluster.mbarrier::complete_tx::bytes.v2.f32 [%0], {%1, %2}, [%3];}"
               ::"r"(dst), "f"(v0), "f"(v1), "r"(bar), "r"(mode) : "memory");
}
__device__ __forceinline__ void spin_until(unsigned t) { while ((int)((unsigned)clock() - t) < 0) {} }
__device__ __forceinline__ unsigned wait_until(unsigned t) {
  unsigned now;
  for (;;) {
    asm volatile("mov.u32 %0, %%globaltimer_lo;" : "=r"(now));
    if ((int)(now - t) >= 0) break;
  }
  return now;
}
#define PIN(x) asm volatile("" : "+r"(x))
#define PINL(x) asm volatile("" : "+l"(x))
#define BAR_ARRIVE(i) asm volatile("mbarrier.arrive.shared::cta.b64 _, [%0];" ::"r"(bar0 + 8 * (i)) : "memory")
#define CNT_ADD(c) asm volatile("red.relaxed.gpu.global.add.u32 [%0], 1;" ::"l"(scr->cnt + (c)) : "memory")
#define BAR_INIT(i, cnt) asm volatile("mbarrier.init.shared::cta.b64 [%0], %1;" ::"r"(bar0 + 8 * (i)), "r"(cnt) : "memory")
#define BAR_ARM(i, bytes) asm volatile("mbarrier.arrive.expect_tx.shared::cta.b64 _, [%0], %1;" ::"r"(bar0 + 8 * (i)), "r"(bytes) : "memory")

__device__ __forceinline__ void tail(unsigned char* smem, Scratch* __restrict__ scr, const bf16* __restrict__ x, bf16* __restrict__ out,
                                     const unsigned par, const unsigned epoch, const int warp) {
  int tid, b;
  asm volatile("mov.u32 %0, %%tid.x;" : "=r"(tid));
  asm volatile("mov.u32 %0, %%ctaid.x;" : "=r"(b));
  const int lane = tid & 31, g = lane >> 2, tq = lane & 3;
  const uint32_t sb = __shfl_sync(~0u, s2u(smem), 0), bar0 = sb + OFF_BAR;
  float* s_sm = (float*)(smem + OFF_SM);
  const int prow = 4 * (lane >> 4) + ((lane & 7) >> 1) + 8 * (lane & 1);
  const float* s_co = (const float*)(smem + OFF_CO);
  const int opos = (b & 15) * 32 + (lane & 16) + 2 * (lane & 6) + ((lane >> 2) & 2) + (lane & 1);
  const float xv = b < 16 ? __bfloat162float(x[(b & 15) * 32 + lane]) : 0.f;
  const int rk = b & 1, ob = 32 * rk + ((b >> 1) & 31);
  uint32_t psb;
  asm volatile("mapa.shared::cluster.u32 %0, %1, %2;" : "=r"(psb) : "r"(sb), "r"(rk ^ 1));
  {
    uint32_t a[8][4];
    {
      const int rg = tid >> 4;
      const uint4* src = g_xo + ((size_t)b * 64 + rg) * RS;
      const uint32_t dst = sb + OFF_XO + rg * 256 + (((tid & 15) ^ (rg & 7)) << 4);
      unsigned long long todo = 0x0001000100010001ull;
#pragma unroll 1
      for (int it = 0; it < SPIN_MAX * 16; it++) {
        unsigned long long mk = *(volatile unsigned long long*)(smem + OFF_MASK);
        const unsigned long long nw = (mk >> rg) & todo;
        todo ^= nw;
#pragma unroll
        for (int i = 0; i < 4; i++)
          if (nw >> (16 * i) & 1)
            asm volatile("cp.async.cg.shared.global [%0], [%1], 16;" ::"r"(dst + i * 4096), "l"(src + i * 16 * RS + (tid & 15)) : "memory");
        if (!__any_sync(~0u, todo != 0)) break;
      }
      asm volatile("cp.async.mbarrier.arrive.noinc.shared::cta.b64 [%0];" ::"r"(bar0 + 8 * (XB + 2)) : "memory");
    }
    mbar_wait(bar0 + 8 * FB_UV); mbar_wait(bar0 + 8 * (FB_UV + 1));
    const uint32_t ab = sb + OFF_UV + (warp >> 2) * 8192 + (8 * (lane >> 4) + (lane & 7)) * 128 + (((2 * (warp & 3) + ((lane >> 3) & 1)) ^ (lane & 7)) << 4);
#pragma unroll
    for (int s = 0; s < 8; s++) ldsm_t(a[s], ab + (s >> 2) * 16384 + (s & 3) * 2048);
    const int chn = 2 * warp + (tq & 1);
    uint32_t a_b = sb + OFF_B + (tq >> 1) * 272 + (32 * (chn >> 2) + 8 * (g >> 1) + 2 * (chn & 3) + (g & 1)) * 2;
    uint32_t a_bq = sb + OFF_B + (lane & 1) * 272 + (lane >> 3) * 16;
    unsigned* p_c = g_xc + (b >> 2) * 256 + warp * 32 + (b & 3) * 8 + (g & 3) * 2 + (g >> 2);
    PIN(a_b); PIN(a_bq); PINL(p_c);
    mbar_wait(bar0 + 8 * (XB + 6));
    uint32_t wb[8];
#pragma unroll
    for (int s = 0; s < 8; s++) wb[s] = *(const uint32_t*)(smem + OFF_RA + (4 * s + tq) * 4);
    const float invL = *(const float*)(smem + OFF_RA + 128);
    float ov;
    POLL {
      mbar_wait(bar0 + 8 * (XB + 2));
      uint32_t ao[4][4];
#pragma unroll
      for (int s = 0; s < 4; s++)
        ldsm_t(ao[s], sb + OFF_XO + (16 * s + 8 * (lane >> 4) + (lane & 7)) * 256 + (((2 * warp + ((lane >> 3) & 1)) ^ (lane & 7)) << 4));
      float d[4][4] = {};
#pragma unroll
      for (int s = 0; s < 4; s++) mma16(d[s], ao[s], wb[2 * s], wb[2 * s + 1]);
      const unsigned p2 = par * 0x10001u;
      unsigned bad = 0;
#pragma unroll
      for (int s = 0; s < 4; s++) bad |= lop_x3(ao[s][0], ao[s][1], p2) | lop_x3(ao[s][2], ao[s][3], p2);
      bad = g == 0 ? bad | (bad >> 16) : 0u;
      ov = (tq & 1) ? (d[0][2] + d[1][2]) + (d[2][2] + d[3][2]) : (d[0][0] + d[1][0]) + (d[2][0] + d[3][0]);
      if (__builtin_expect(!__any_sync(~0u, bad & 1) || ++it_ >= SPIN_MAX, 1)) break;
#pragma unroll
      for (int i = 0; i < 4; i++)
        asm volatile("cp.async.cg.shared.global [%0], [%1], 16;"
                     ::"r"(sb + OFF_XO + ((lane >> 1) + 16 * i) * 256 + (((2 * warp + (lane & 1)) ^ ((lane >> 1) & 7)) << 4)),
                       "l"(g_xo + ((size_t)b * 64 + (lane >> 1) + 16 * i) * RS + 2 * warp + (lane & 1)) : "memory");
      asm volatile("cp.async.wait_all;" ::: "memory");
      __syncwarp();
    }
    {
      const float lo = ov - bfhi(__float_as_uint(ov));
      asm volatile("st.shared.u16 [%0], %1;" ::"r"(a_b), "h"((unsigned short)((tq & 2) ? pack2(lo, lo) : __float_as_uint(ov) >> 16)) : "memory");
    }
    nbar(1, 256);
    float d[4][4] = {};
#pragma unroll
    for (int y = 0; y < 4; y++) {
      uint32_t bq[4];
      ldsm(bq, a_bq + 64 * y);
      mma16(d[(2 * y) & 3], a[2 * y], bq[0], bq[1]); mma16(d[(2 * y + 1) & 3], a[2 * y + 1], bq[2], bq[3]);
    }
    const float r0 = ((d[0][0] + d[0][1]) + (d[1][0] + d[1][1])) + ((d[2][0] + d[2][1]) + (d[3][0] + d[3][1]));
    const float r1 = ((d[0][2] + d[0][3]) + (d[1][2] + d[1][3])) + ((d[2][2] + d[2][3]) + (d[3][2] + d[3][3]));
    if (tq == 0) stx4(p_c, pack2t(r0 * invL, r1 * invL, par));
  }
  unsigned tpub = clock();
  mbar_wait(bar0 + 8 * (XB + 4));
  const float gav = s_co[256 + (opos & 31)];
  const float gbv = s_co[288 + (lane & 4) + 2 * (lane & 1) + ((lane >> 1) & 1)];
  float4 cf[2];
#pragma unroll
  for (int s = 0; s < 2; s++) cf[s] = *(const float4*)(s_co + 32 * warp + 16 * s + 4 * tq);
  {
    uint32_t a[2][4][4];
    mbar_wait(bar0 + 8 * (FB_O + (warp >> 2)));
    const uint32_t ab = sb + OFF_O + (32 * warp + prow) * 128 + ((((lane >> 3) & 1) ^ (prow & 7)) << 4);
#pragma unroll
    for (int i = 0; i < 8; i++) ldsm_t(a[i >> 2][i & 3], (ab + (i >> 2) * 2048) ^ ((i & 3) << 5));
    uint4 v;
    const unsigned* pc = g_xc + (4 * (b >> 4) + 2 * rk + (warp >> 2)) * 256 + 64 * (warp & 3) + 2 * lane;
    uint32_t ro = ((tq >> 1) == rk ? sb : psb) + OFF_P + (8 * (tq & 1) + g) * 144 + (8 * rk + warp) * 8;
    uint32_t a_q = sb + OFF_P + (8 * (lane >> 4) + (lane & 7)) * 144;
    unsigned* p_ao = g_xao + (b >> 5) * 1024 + (opos >> 4) * 32 + (b & 16) + (opos & 15);
    PIN(ro); PIN(a_q); PINL(p_ao); PINL(pc);
    spin_until(tpub + DLY5);
    POLL {
      const unsigned long long u0 = ldx64(pc);
      v.x = (unsigned)u0; v.y = u0 >> 32;
      RETRY(X8(v))
    }
    v.z = lane & 16 ? v.x : 0u; v.w = lane & 16 ? v.y : 0u;
    if (lane & 16) v.x = v.y = 0u;
    float d[4][4] = {};
#pragma unroll
    for (int mt = 0; mt < 4; mt++) mma16(d[mt], a[0][mt], v.x, v.y);
#pragma unroll
    for (int mt = 0; mt < 4; mt++) mma16(d[mt], a[1][mt], v.z, v.w);
    float r[8];
#pragma unroll
    for (int i = 0; i < 8; i++) r[i] = d[i >> 1][2 * (i & 1)] + d[i >> 1][2 * (i & 1) + 1];
    tred<4>(r, lane, 2); tred<2>(r, lane, 1);
    st_pair((tq >> 1) == rk ? 1 : 2, ro, psb + OFF_BAR + 8 * (XB + 3), r[0], r[1]);
    __syncwarp();
    if (lane == 0) BAR_ARRIVE(XB + 3);
    if (warp == 0) {
      mbar_wait(bar0 + 8 * (XB + 3));
      float p[8];
#pragma unroll
      for (int i = 0; i < 8; i++) {
        const float4 q = lds16(a_q + i * 16);
        p[i] = (lane & 8) ? q.y + q.w : q.x + q.z;
      }
      const float t = ((p[0] + p[1]) + (p[2] + p[3])) + ((p[4] + p[5]) + (p[6] + p[7]));
      stx4(p_ao, fbits(gav * t + xv));
    }
  }
  tpub = clock();
  if (b < 112) {
    uint32_t af[2][4][4], ad[4][4];
    const uint32_t ab = sb + (32 * warp + 8 * (lane >> 4) + (lane & 7)) * 64 + ((((lane >> 3) & 1) ^ ((lane >> 1) & 3)) << 4);
    uint32_t ro = ((tq & 1) == rk ? sb : psb) + OFF_R4 + (8 * (tq >> 1) + g) * 176 + (10 * rk + warp) * 8;
    uint32_t a_q = sb + OFF_R4 + (8 * (lane >> 4) + (lane & 7)) * 176 + (lane & 8) * 10;
    uint32_t a_d = sb + OFF_D + warp * 2048 + (8 * (lane >> 4) + (lane & 7)) * 128 + ((((lane >> 3) & 1) ^ (lane & 7)) << 4);
    unsigned* p_f = g_xf + b * 512 + 64 * warp + 16 * tq + 2 * g;
    const unsigned* pa = g_xao + (g >> 1) * 1024 + 512 * rk + 64 * warp + 4 * (lane & 7);
    PIN(ro); PIN(a_q); PIN(a_d); PINL(p_f); PINL(pa);
    spin_until(tpub + DLY6);
    uint4 v[2];
    {
      bool have = false;
      POLL {
        v[0] = ldx16(pa); v[1] = ldx16(pa + 32);
        const unsigned t1 = (unsigned)clock() + WTEST;
        while (!have && (int)((unsigned)clock() - t1) < 0) {
          uint32_t ok;
          asm volatile("{.reg .pred p, q; mbarrier.test_wait.parity.shared::cta.b64 p, [%1], 0; mbarrier.test_wait.parity.shared::cta.b64 q, [%1+8], 0;\n"
                       "and.pred p, p, q; vote.sync.all.pred p, p, 0xffffffff; selp.u32 %0, 1, 0, p;}" : "=r"(ok) : "r"(bar0 + 8 * FB_G) : "memory");
          if (ok) {
#pragma unroll
            for (int i = 0; i < 8; i++) ldsm_t(af[i >> 2][i & 3], (ab + ((i & 2) ? OFF_U : OFF_G) + (i >> 2) * 1024) ^ ((i & 1) << 5));
            have = true;
          }
        }
        if (!__any_sync(~0u, (X16(v[0]) | X16(v[1])) & 1) || ++it_ >= SPIN_MAX) break;
      }
      float df[4][4] = {}, dg[2][4] = {};
      uint32_t zb[4];
      const uint32_t one = g == 0 ? 0x3F803F80u : 0u;
#pragma unroll
      for (int s = 0; s < 2; s++) {
        const uint32_t y0 = pack2(u2f(v[s].x), u2f(v[s].y)), y1 = pack2(u2f(v[s].z), u2f(v[s].w));
        const uint32_t ya[4] = {y0, one, y1, one};
        mma16(dg[s], ya, y0, y1);
        zb[2 * s] = pack2(u2f(v[s].x) * cf[s].x, u2f(v[s].y) * cf[s].y); zb[2 * s + 1] = pack2(u2f(v[s].z) * cf[s].z, u2f(v[s].w) * cf[s].w);
      }
      float st[2] = {(dg[0][2] + dg[0][3]) + (dg[1][2] + dg[1][3]), (dg[0][0] + dg[0][1]) + (dg[1][0] + dg[1][1])};
      if (!have) {
        mbar_wait(bar0 + 8 * FB_G); mbar_wait(bar0 + 8 * (FB_G + 1));
#pragma unroll
        for (int i = 0; i < 8; i++) ldsm_t(af[i >> 2][i & 3], (ab + ((i & 2) ? OFF_U : OFF_G) + (i >> 2) * 1024) ^ ((i & 1) << 5));
      }
#pragma unroll
      for (int i = 0; i < 8; i++) mma16(df[i & 3], af[i >> 2][i & 3], zb[2 * (i >> 2)], zb[2 * (i >> 2) + 1]);
#pragma unroll
      for (int o2 = 1; o2 < 4; o2 <<= 1) { st[0] += __shfl_xor_sync(~0u, st[0], o2); st[1] += __shfl_xor_sync(~0u, st[1], o2); }
#pragma unroll
      for (int o2 = 4; o2 < 32; o2 <<= 1) st[1] += __shfl_xor_sync(~0u, st[1], o2);
      float r[8];
#pragma unroll
      for (int i = 0; i < 8; i++) r[i] = df[i >> 1][2 * (i & 1)] + df[i >> 1][2 * (i & 1) + 1];
      tred<4>(r, lane, 2); tred<2>(r, lane, 1);
      const int md = (tq & 1) == rk ? 1 : 2;
      st_pair(md, ro, psb + OFF_BAR + 8 * (XB + 5), r[0], r[1]);
      st_pair(lane < 2 ? md : 0, ro + 16 * 176, psb + OFF_BAR + 8 * (XB + 5), st[0], st[1]);
      __syncwarp();
      if (lane == 0) BAR_ARRIVE(XB + 5);
      mbar_wait(bar0 + 8 * FB_D);
#pragma unroll
      for (int mt = 0; mt < 4; mt++)
        ldsm_t(ad[mt], a_d ^ (mt << 5));
    }
    mbar_wait(bar0 + 8 * (XB + 5));
    {
      float4 q[5], u[8];
#pragma unroll
      for (int i = 0; i < 5; i++) q[i] = lds16(a_q + i * 16);
#pragma unroll
      for (int i = 0; i < 8; i++) u[i] = *(const float4*)(smem + OFF_R4 + 16 * 176 + (i >> 2) * 80 + (i & 3) * 16);
      float p[6] = {((q[0].x + q[0].z) + (q[1].x + q[1].z)) + ((q[2].x + q[2].z) + (q[3].x + q[3].z)), q[4].x, q[4].z,
                    ((q[0].y + q[0].w) + (q[1].y + q[1].w)) + ((q[2].y + q[2].w) + (q[3].y + q[3].w)), q[4].y, q[4].w};
      tred<3>(p, lane, 8);
      const float P = p[0], A1 = p[1], A2 = p[2];
      const float mean = (((u[0].x + u[0].z) + (u[1].x + u[1].z)) + ((u[2].x + u[2].z) + (u[3].x + u[3].z)) +
                          ((u[4].x + u[4].z) + (u[5].x + u[5].z)) + ((u[6].x + u[6].z) + (u[7].x + u[7].z))) * (1.f / 512.f);
      const float sq = (((u[0].y + u[0].w) + (u[1].y + u[1].w)) + ((u[2].y + u[2].w) + (u[3].y + u[3].w)) +
                         ((u[4].y + u[4].w) + (u[5].y + u[5].w)) + ((u[6].y + u[6].w) + (u[7].y + u[7].w))) * (1.f / 512.f);
      float rstd;
      asm("rsqrt.approx.ftz.f32 %0, %1;" : "=f"(rstd) : "f"(fmaxf(sq - mean * mean, 0.f) + 1e-5f));
      const float gg = bfr(rstd * (P - mean * A1) + A2);
      const float uu = __shfl_xor_sync(~0u, gg, 16);
      const float hh = bfr(gg * rcp(1.f + ex2(gg * (-2.302208198f - 0.1029432397f * gg * gg)))) * uu;
      const uint32_t hw = pack2(hh, __shfl_down_sync(~0u, hh, 1));
      const uint32_t b0 = __shfl_sync(~0u, hw, 2 * tq), b1 = __shfl_sync(~0u, hw, 2 * tq + 8);
      float f0 = 0, f1 = 0;
#pragma unroll
      for (int mt = 0; mt < 4; mt++) {
        float dd[4] = {0, 0, 0, 0};
        mma16(dd, ad[mt], b0, b1);
        if (tq == mt) { f0 = dd[0]; f1 = dd[2]; }
      }
      stx8(p_f, make_uint2(fbits(f0), fbits(f1)));
    }
    tpub = clock();
    if (b < 64 && warp == (b >> 3)) {
      const uint4 y = (b & 4) ? v[1] : v[0];
      float a4[4] = {u2f(y.x), u2f(y.y), u2f(y.z), u2f(y.w)};
      tred<2>(a4, lane, 16); tred<1>(a4, lane, 8);
      a4[0] += __shfl_xor_sync(~0u, a4[0], 4);
      if (!(lane & 4)) s_sm[416 + 8 * (lane >> 4) + 2 * tq + ((lane >> 3) & 1)] = a4[0];
      if (warp == 7) nbar_arrive(2, 256);
    } else if (b < 64 && warp == 7) nbar_arrive(2, 256);
    if (b < 64 && warp < 7) {
      uint4 v;
      const unsigned* pf = g_xf + (tid >> 1) * 512 + 8 * ob + 4 * (tid & 1);
      const int col = 16 * (ob >> 1) + 4 * (ob & 1) + ((tid >> 1) & 3) + 8 * (tid & 1);
      bf16* po = out + col;
      PINL(po); PINL(pf);
      spin_until(tpub + DLY7);
      POLL { v = ldx16(pf); RETRY(X16(v)) }
      float f[4] = {u2f(v.x), u2f(v.y), u2f(v.z), u2f(v.w)};
      tred<2>(f, lane, 16); tred<1>(f, lane, 8);
      f[0] += __shfl_xor_sync(~0u, f[0], 4); f[0] += __shfl_xor_sync(~0u, f[0], 2);
      if (!(lane & 6)) s_sm[352 + warp * 8 + 4 * (lane & 1) + (lane >> 3)] = f[0];
      nbar(2, 256);
      if (tid < 8) {
        const float* q = s_sm + 352 + tid;
        const float t = ((q[0] + q[8]) + (q[16] + q[24])) + ((q[32] + q[40]) + q[48]);
        *po = __float2bfloat16(s_sm[416 + (col & 15)] + bfr(gbv * bfr(t)));
        if (b == 0 && tid == 0) stx4(&g_epoch, epoch + 1);
      }
    }
  }
}

__global__ void __cluster_dims__(2, 1, 1) __launch_bounds__(384, 1)
fused_kernel(const bf16* __restrict__ x, const bf16* __restrict__ cvec, const bf16* __restrict__ w_mod, bf16* __restrict__ out,
             Scratch* __restrict__ scr, const __grid_constant__ TMaps tms) {
  extern __shared__ __align__(1024) unsigned char smem[];
  const int tid = threadIdx.x, warp = __shfl_sync(~0u, tid >> 5, 0), lane = tid & 31;
  const int b = blockIdx.x, rk = b & 1, pr = b >> 1, hd = b >> 2;
  uint32_t sb = s2u(smem), bar0 = sb + OFF_BAR;

  unsigned gt_start;
  asm volatile("mov.u32 %0, %%globaltimer_lo;" : "=r"(gt_start));
  const int g = lane >> 2, tq = lane & 3;
  const int arow = 64 * (b >> 4) + ((tid & 255) >> 3);
  uint4 wm0, wm1;
  uint32_t c0w, c1w;
  if (warp < 8) {
    const bf16* wa = w_mod + (size_t)arow * 3072 + (lane & 4) * 128 + 32 * (b & 15) + 8 * tq;
    wm0 = ldx16(wa); wm1 = ldx16(wa + 32 * 3072);
    c0w = ldc4(cvec + (arow & ~1)); c1w = ldc4(cvec + (arow & ~1) + 32);
  }
  const unsigned t_off = gt_start + RATE_T0;
  if (warp == 11) {
    if (lane == 0) {
#pragma unroll
      for (int i = 0; i < FB_KV; i++) { BAR_INIT(i, 1); BAR_ARM(i, 16384); }
    }
    __syncwarp();
    asm volatile("fence.mbarrier_init.release.cluster;" ::: "memory");
    asm volatile("barrier.cluster.arrive.relaxed.aligned;" ::: "memory");
#pragma unroll 1
    for (int i = 0; i < FB_KV; i++) {
      if (i >= HWIN) mbar_wait(bar0 + 8 * (i - HWIN));
      wait_until(t_off + (i < 4 ? 2 * i + ((b >> 1) & 1) : 4 * i - 8 + (b & 3)) * (RATE_H / 4));
      if (lane == 0) {
        if (i < 4) tma3d(sb + OFF_WQ + i * 16384, &tms.m[0], bar0 + 8 * i, 0, i * 128, 2 * hd + rk);
        else tma3d(sb + OFF_WQ + i * 16384, &tms.m[1], bar0 + 8 * i, 0, (b & 3) * 128 + (i - 4) * 64, 2 * hd);
      }
      __syncwarp();
    }
  }
  if (warp == 10) {
    const uint4 xa = ldc16(x + 16 * lane), xb = ldc16(x + 16 * lane + 8);
    const unsigned ep = ldc4(&g_epoch);
    float xv[16] = {bflo(xa.x), bfhi(xa.x), bflo(xa.y), bfhi(xa.y), bflo(xa.z), bfhi(xa.z), bflo(xa.w), bfhi(xa.w),
                    bflo(xb.x), bfhi(xb.x), bflo(xb.y), bfhi(xb.y), bflo(xb.z), bfhi(xb.z), bflo(xb.w), bfhi(xb.w)};
    float s = 0;
#pragma unroll
    for (int i = 0; i < 16; i++) s += xv[i];
#pragma unroll
    for (int o = 16; o; o >>= 1) s += __shfl_xor_sync(~0u, s, o);
    const float mean = s * (1.f / 512.f);
    s = 0;
#pragma unroll
    for (int i = 0; i < 16; i++) { xv[i] -= mean; s += xv[i] * xv[i]; }
#pragma unroll
    for (int o = 16; o; o >>= 1) s += __shfl_xor_sync(~0u, s, o);
    const float rstd = rsqrtf(s * (1.f / 512.f) + 1e-5f);
    if ((lane >> 1) == (b & 15))
#pragma unroll
      for (int i = 0; i < 4; i++)
        *(float4*)(smem + OFF_SM + (256 + (lane & 1) * 16 + 4 * i) * 4) = make_float4(xv[4 * i] * rstd, xv[4 * i + 1] * rstd, xv[4 * i + 2] * rstd, xv[4 * i + 3] * rstd);
    if (lane == 0) *(volatile unsigned*)(smem + OFF_MASK + 8) = ep;
    nbar_arrive(1, 288);
  }
  if (warp >= 8) {
    asm volatile("setmaxnreg.dec.sync.aligned.u32 72;");
    if (tid == 288) {
#pragma unroll
      for (int q = FB_KV; q < FB_KV + 16; q++) { BAR_INIT(q, 1); BAR_ARM(q, 32768); }
    }
    if (tid == 320) {
#pragma unroll
      for (int q = 0; q <= 13 + NSLOT; q++) BAR_INIT(EB + q, q == 0 ? 4 : q < 5 ? 16 : q < 16 ? 12 : 6);
    }
    if (tid == 256) {
#pragma unroll
      for (int q = FB_MOD; q <= FB_D; q++) { BAR_INIT(q, 1); BAR_ARM(q, 16384); }
      BAR_INIT(QB, 9); BAR_ARM(QB, 1024);
#pragma unroll
      for (int q = 0; q < 7; q++) BAR_INIT(XB + q, q == 2 ? 256 : q == 5 || q == 3 ? 9 : 1);
      BAR_ARM(XB + 3, 1024);
      BAR_ARM(XB + 5, 1024 + 64 + 512);
      *(volatile unsigned long long*)(smem + OFF_MASK) = 0;
    }
    if (warp != 11) {
      __syncwarp();
      asm volatile("fence.mbarrier_init.release.cluster;" ::: "memory");
      __threadfence_block();
      asm volatile("barrier.cluster.arrive.relaxed.aligned;" ::: "memory");
    }
    if (warp == 11) {
      asm volatile("barrier.cluster.wait.acquire.aligned;" ::: "memory");
      const unsigned epoch = *(volatile unsigned*)(smem + OFF_MASK + 8), par = (epoch + 1) & 1;
      mbar_wait(bar0 + 8 * (FB_KV + 15));
      for (int it = 0; ldx4(scr->cnt + 96 + 32 * (b >> 6)) != (epoch + 1) * 64 && it < SPIN_MAX; it++) {}
      uint4 hh;
      POLL { hh = ldx16(g_ml + (b >> 2) * 64 + 2 * lane); RETRY(X16(hh)) }
      int mi = __float_as_int(fmaxf(u2f(hh.x), u2f(hh.z)));
      mi ^= (mi >> 31) & 0x7fffffff;
      mi = __reduce_max_sync(~0u, mi);
      mi ^= (mi >> 31) & 0x7fffffff;
      const float M = __int_as_float(mi);
      const uint32_t wp = pack2(ex2(u2f(hh.x) - M), ex2(u2f(hh.z) - M));
      float L = bflo(wp) * u2f(hh.y) + bfhi(wp) * u2f(hh.w);
#pragma unroll
      for (int o2 = 16; o2; o2 >>= 1) L += __shfl_xor_sync(~0u, L, o2);
      *(uint32_t*)(smem + OFF_RA + lane * 4) = wp;
      if (lane == 0) *(float*)(smem + OFF_RA + 128) = rcp(L);
      __syncwarp();
      if (lane == 0) BAR_ARRIVE(XB + 6);
    }
    if (warp == 10) {
      if (lane < 8) asm volatile("prefetch.tensormap [%0];" ::"l"(&tms.m[lane + 1]) : "memory");
      asm volatile("barrier.cluster.wait.acquire.aligned;" ::: "memory");
      const unsigned epoch = *(volatile unsigned*)(smem + OFF_MASK + 8);
#pragma unroll 1
      for (int e = 0; e < 2; e++) {
        for (int it = 0; ldx4(scr->cnt + (e ? 2 + rk : 1)) != (epoch + 1) * (e ? 64 : 128) && it < SPIN_MAX; it++) {}
        if (lane == 0) BAR_ARRIVE(XB + e);
      }
      mbar_wait(bar0 + 8 * (FB_KV + 14));
      unsigned long long m = 0;
#pragma unroll 1
      for (int it = 0; ~m && it < SPIN_MAX; it++) {
        m = ldx64(scr->cnt + 32 + 32 * (b >> 6)) ^ ((epoch & 1) ? ~0ull : 0ull);
        if (lane == 0) *(volatile unsigned long long*)(smem + OFF_MASK) = m;
      }
    }
    if (warp == 9) {
      asm volatile("barrier.cluster.wait.acquire.aligned;" ::: "memory");
      const unsigned epoch = *(volatile unsigned*)(smem + OFF_MASK + 8);
      const unsigned par = (epoch + 1) & 1, inv = par ^ 1;
      const uint4 inv4 = make_uint4(inv, inv, inv, inv);
      mbar_wait(bar0 + 8 * FB_KV);
#pragma unroll 2
      for (int k = 0; k < 8; k++) {
        const uint32_t cp = ldc4(cvec + 2 * (lane + 32 * k));
        *(uint32_t*)(smem + OFF_SILU + (lane + 32 * k) * 4) = pack2(silu_bf(bflo(cp)), silu_bf(bfhi(cp)));
      }
      __syncwarp();
      mbar_wait(bar0 + 8 * FB_MOD);
      const uint32_t ab = sb + OFF_MOD + (8 * (lane >> 4) + (lane & 7)) * 32 + ((((lane >> 3) ^ (lane >> 2)) & 1) << 4);
      float d[4][4] = {};
#pragma unroll 2
      for (int s4 = 0; s4 < 8; s4++)
#pragma unroll
        for (int s = 0; s < 4; s++) {
          uint32_t a[4];
          const uint32_t* ps = (const uint32_t*)(smem + OFF_SILU) + 32 * s4 + 8 * s + tq;
          ldsm_t(a, ab + (4 * s4 + s) * 512); mma16(d[s], a, ps[0], ps[4]);
        }
      const float t = (tq & 1) ? (d[0][2] + d[1][2]) + (d[2][2] + d[3][2]) : (d[0][0] + d[1][0]) + (d[2][0] + d[3][0]);
      if (tq < 2) stx4(g_xm + b * 16 + 2 * (g & 6) + 2 * tq + (g & 1), fbits(bfr(t)));
      __syncwarp();
      if (lane == 0) CNT_ADD(6);
      mbar_wait(bar0 + 8 * (FB_KV + 8));
      if (lane < 16) stx16(g_xc + (b >> 2) * 256 + (lane >> 1) * 32 + (b & 3) * 8 + (lane & 1) * 4, inv4);
      if (lane < 8) stx16(g_xao + (b >> 5) * 1024 + (b & 15) * 64 + (lane & 4) * 8 + (b & 16) + (lane & 3) * 4, inv4);
      if (b < 112)
#pragma unroll 1
        for (int k = 0; k < 4; k++) stx16(g_xf + b * 512 + (lane + 32 * k) * 4, inv4);
      nbar_arrive(2, 288);
      for (int it = 0; ldx4(scr->cnt + 6) != (epoch + 1) * 128 && it < SPIN_MAX; it++) __nanosleep(100);
      {
        uint4 sv[2], cb[2];
        unsigned ga, gb;
        POLL {
#pragma unroll
          for (int k = 0; k < 2; k++) { sv[k] = ldx16(g_xm + 512 + 256 * rk + 4 * (lane + 32 * k)); cb[k] = ldx16(g_xm + 1024 + 256 * rk + 4 * (lane + 32 * k)); }
          ga = ldx4(g_xm + (b & 15) * 32 + lane); gb = ldx4(g_xm + 1536 + 256 * rk + 8 * (pr & 31) + (lane & 7));
          RETRY(X16(sv[0]) | X16(sv[1]) | X16(cb[0]) | X16(cb[1]) | lop_x3(ga, gb, par))
        }
#pragma unroll
        for (int k = 0; k < 2; k++) {
          const float c0 = bfr(1.f + bfhi(cb[k].x)), c1 = bfr(1.f + bfhi(cb[k].y)), c2 = bfr(1.f + bfhi(cb[k].z)), c3 = bfr(1.f + bfhi(cb[k].w));
          *(float4*)(smem + OFF_CO + (lane + 32 * k) * 16) = make_float4(c0, c1, c2, c3);
          uint2* pb = (uint2*)(smem + OFF_BP) + lane + 32 * k;
          pb[0] = make_uint2(pack2(c0, c1), pack2(c2, c3));
          pb[64] = make_uint2(__byte_perm(sv[k].x, sv[k].y, 0x7632), __byte_perm(sv[k].z, sv[k].w, 0x7632));
        }
        *(float*)(smem + OFF_CO + 1024 + lane * 4) = bfhi(ga);
        *(float*)(smem + OFF_CO + 1152 + lane * 4) = bfhi(gb);
      }
      __syncwarp();
      if (lane == 0) BAR_ARRIVE(XB + 4);
    }
    if (warp == 8) {
      const unsigned stag = ((pr * SMUL) & 63) * RATE_NS >> 6;
      unsigned tnext = t_off + 4 * RATE_H;
      asm volatile("barrier.cluster.wait.acquire.aligned;" ::: "memory");
#pragma unroll 1
      for (int k = 0; k < 24; k++) {
        const int code = (k < 12 ? ORDER0 >> (5 * k) : ORDER1 >> (5 * (k - 12))) & 31;
        const bool kv = code < 16;
        const int n = code, w = code - 16;
        if (!kv && w >= 5 && b >= 112) break;
        if (kv) mbar_wait(bar0 + 8 * (FB_KV + n - (n < 6 ? EWIN : KVWIN)));
        if (k >= TAIL_K) mbar_wait(bar0 + 8 * (FB_KV + (int)((ORDER1 >> (5 * (k - 12 - ((WINS >> (4 * (k - TAIL_K))) & 15)))) & 31)));
        const int e = kv ? (n == 3 ? 2 : n == 5 ? 1 : n) : w == 0 ? 0 : w < 5 ? 16 + ((w - 1) >> 1) : w == 7 ? 19 : 18;
        if (e != 1 && k) mbar_wait(bar0 + 8 * (EB + e));
        wait_until(tnext + stag);
        tnext += k > TAIL_K ? RATE_TL : k < 4 ? RATE_E : RATE_NS;
        if (lane == 0) {
          if (kv)
            asm volatile("cp.async.bulk.tensor.3d.shared::cluster.global.mbarrier::complete_tx::bytes.multicast::cluster.L2::cache_hint [%0], [%1, {%3, %4, %5}], [%2], %6, %7;"
                         ::"r"(sb + (n % NSLOT) * SLOT + rk * 16384), "l"(&tms.m[2]), "r"(bar0 + 8 * (FB_KV + n)), "r"(0), "r"(((n >> 1) * 64 + pr) * 64),
                           "r"(4 * (n & 1) + 2 * rk), "h"((unsigned short)3), "l"(stream_policy()) : "memory");
          else {
            tma3d(sb + (w == 0 ? OFF_MOD : w < 5 ? OFF_UV + (w - 1) * 16384 : w == 5 ? OFF_G : w == 6 ? OFF_U : OFF_D),
                  &tms.m[w == 0 ? 3 : w < 3 ? 4 : w < 5 ? 5 : w + 1], bar0 + 8 * (FB_MOD + w),
                  w == 0 ? 1024 + b * 16 : w < 3 || w == 7 ? 0 : w < 5 ? (pr & 7) * 64 : pr * 32, w == 7 ? b * 16 : w == 1 || w == 2 ? (b & 3) * 128 + (w - 1) * 64 : 0,
                  w == 1 || w == 2 ? 2 * hd : w == 3 || w == 4 ? (b >> 4) * 4 + 2 * rk + w - 3 : w == 5 || w == 6 ? rk : 0);
          }
        }
        __syncwarp();
      }
    }
    if (b < 112) {
      const int mt = warp & 1, dd = (warp >> 1) & 1;
      mbar_wait(bar0 + 8 * (XB + 4));
      const uint32_t ab = sb + (mt ? OFF_U : OFF_G) + (8 * (lane >> 4) + (lane & 7)) * 64 + (((2 * dd + ((lane >> 3) & 1)) ^ ((lane >> 1) & 3)) << 4);
      uint32_t base;
      asm volatile("mapa.shared::cluster.u32 %0, %1, %2;" : "=r"(base) : "r"(sb), "r"(dd));
      uint2 bb[16];
#pragma unroll
      for (int s = 0; s < 16; s++) bb[s] = *(const uint2*)(smem + OFF_BP + (g & 1) * 512 + (4 * s + tq) * 8);
      mbar_wait(bar0 + 8 * (FB_G + mt));
      float e[4][4] = {};
#pragma unroll
      for (int s = 0; s < 16; s++) { uint32_t a[4]; ldsm_t(a, ab + s * 1024); mma16(e[s & 3], a, bb[s].x, bb[s].y); }
      float r[4];
#pragma unroll
      for (int i = 0; i < 4; i++) r[i] = (e[0][i] + e[1][i]) + (e[2][i] + e[3][i]);
      if (tq < 2) st_async2(base + OFF_R4 + (8 * mt + g) * 176 + (10 * rk + 8 + tq) * 8, base + OFF_BAR + 8 * (XB + 5), tq ? r[1] : r[0], tq ? r[3] : r[2]);
    }
    return;
  }

  float* s_sm = (float*)(smem + OFF_SM);
  unsigned par, epoch;
  uint32_t rsb;
  {
    float* s_r4 = (float*)(smem + OFF_R4);
    asm volatile("barrier.cluster.arrive.relaxed.aligned;" ::: "memory");
    asm volatile("mapa.shared::cluster.u32 %0, %1, %2;" : "=r"(rsb) : "r"(sb), "r"(rk ^ 1));
    const float c0 = (arow & 1) ? bfhi(c0w) : bflo(c0w), c1 = (arow & 1) ? bfhi(c1w) : bflo(c1w);
    float acc[8] = {0, 0, 0, 0, 0, 0, 0, 0};
    fma8(acc, wm0, silu_bf(c0)); fma8(acc, wm1, silu_bf(c1));
    tred<4>(acc, lane, 8); tred<2>(acc, lane, 16);
    *(float2*)(s_r4 + warp * 64 + 8 * (lane & 7) + ((lane >> 1) & 4) + ((lane >> 3) & 2)) = make_float2(acc[0], acc[1]);
    nbar(1, 288);
    epoch = *(volatile unsigned*)(smem + OFF_MASK + 8);
    par = (epoch + 1) & 1;
    if (warp == 0) {
      float t = 0.f, ca = b < 16 ? 1.f : 0.f;
#pragma unroll
      for (int w = 0; w < 8; w++) { t += s_r4[w * 64 + lane]; ca += s_r4[w * 64 + 32 + lane]; }
      t += ca * s_sm[256 + lane];
      const float nb = __shfl_down_sync(~0u, t, 1);
      const uint32_t w0 = lane < 8 ? pack2t(t, nb, par) : pack2(t, nb);
      const uint32_t w1 = __shfl_down_sync(~0u, w0, 8), w2 = __shfl_down_sync(~0u, w0, 16), w3 = __shfl_down_sync(~0u, w0, 24);
      if (lane < 8 && !(lane & 1)) stx16(g_h + (b >> 5) * 512 + (b & 15) * 32 + (b & 16) + 2 * lane, make_uint4(w0, w1, w2, w3));
      __syncwarp();
      if (lane == 0) CNT_ADD(1);
    }
  }
  asm volatile("barrier.cluster.wait.acquire.aligned;" ::: "memory");
  {
    uint32_t a[4][4][4];
    mbar_wait(bar0 + 8 * (warp >> 1));
    const uint32_t ab = sb + OFF_WQ + (64 * warp + 8 * (lane >> 4) + (lane & 7)) * 128;
#pragma unroll
    for (int s = 0; s < 4; s++)
#pragma unroll
      for (int mt = 0; mt < 4; mt++) ldsm_t(a[s][mt], ab + s * 2048 + (((2 * mt + ((lane >> 3) & 1)) ^ (lane & 7)) << 4));
    uint4 v0, v1;
    const unsigned* ph = g_h + (g >> 1) * 512 + 64 * warp + 4 * (lane & 7);
    uint32_t off = OFF_B + warp * 272 + (32 * rk + 8 * tq + (lane & 4)) * 4;
    PIN(off); PINL(ph);
    mbar_wait(bar0 + 8 * XB);
    POLL { v0 = ldx16(ph); v1 = ldx16(ph + 32); RETRY(lop_x3(v0.x, v1.x, par)) }
    float d[4][4] = {};
#pragma unroll
    for (int mt = 0; mt < 4; mt++) {
      mma16(d[mt], a[0][mt], v0.x, v0.y); mma16(d[mt], a[1][mt], v0.z, v0.w);
      mma16(d[mt], a[2][mt], v1.x, v1.y); mma16(d[mt], a[3][mt], v1.z, v1.w);
    }
    float r[8];
#pragma unroll
    for (int mt = 0; mt < 4; mt++) { r[2 * mt] = d[mt][0] + d[mt][1]; r[2 * mt + 1] = d[mt][2] + d[mt][3]; }
    tred<4>(r, lane, 2); tred<2>(r, lane, 1);
    const float rc = __shfl_xor_sync(~0u, (lane & 4) ? r[0] : r[1], 4);
    const uint32_t wd = (lane & 4) ? pack2(rc, r[1]) : pack2(r[0], rc);
    const uint32_t w1 = __shfl_down_sync(~0u, wd, 8), w2 = __shfl_down_sync(~0u, wd, 16), w3 = __shfl_down_sync(~0u, wd, 24);
    asm volatile("{.reg .pred p; setp.lt.s32 p, %7, 8; @p st.shared.v4.b32 [%0], {%2,%3,%4,%5};\n"
                 "@p st.async.shared::cluster.mbarrier::complete_tx::bytes.v4.b32 [%1], {%2,%3,%4,%5}, [%6];}"
                 ::"r"(sb + off), "r"(rsb + off), "r"(wd), "r"(w1), "r"(w2), "r"(w3), "r"(rsb + OFF_BAR + 8 * QB), "r"(lane) : "memory");
    __syncwarp();
    arrive2(bar0 + 8 * QB, 0, lane == 0, false);
    arrive2(bar0 + 8 * (EB + 2), rsb + OFF_BAR + 8 * (EB + 2), lane == 0, lane == 0);
  }
  {
    uint32_t a[8][4];
    uint32_t a_bq = sb + OFF_B + (lane & 7) * 272 + (lane >> 3) * 16;
    unsigned* p_qa = g_qa + b * 64 + 8 * warp + 4 * lane;
    PIN(a_bq); PINL(p_qa);
    mbar_wait(bar0 + 8 * (FB_UK + (warp >> 2)));
    const uint32_t ab = sb + OFF_WUK + (warp >> 2) * 16384 + (16 * (warp & 3) + (lane & 15)) * 128;
#pragma unroll
    for (int s = 0; s < 8; s++) ldsm(a[s], ab + (s >> 2) * 8192 + (((2 * (s & 3) + (lane >> 4)) ^ (lane & 7)) << 4));
    mbar_wait(bar0 + 8 * QB);
    float d[4][4] = {};
#pragma unroll
    for (int y = 0; y < 4; y++) {
      uint32_t bq[4];
      ldsm(bq, a_bq + 64 * y);
      mma16(d[(2 * y) & 3], a[2 * y], bq[0], bq[1]); mma16(d[(2 * y + 1) & 3], a[2 * y + 1], bq[2], bq[3]);
    }
    float r[2] = {((d[0][0] + d[0][1]) + (d[1][0] + d[1][1])) + ((d[2][0] + d[2][1]) + (d[3][0] + d[3][1])),
                  ((d[0][2] + d[0][3]) + (d[1][2] + d[1][3])) + ((d[2][2] + d[2][3]) + (d[3][2] + d[3][3]))};
    tred<1>(r, lane, 1);
    r[0] += __shfl_xor_sync(~0u, r[0], 2);
    const float nb = __shfl_xor_sync(~0u, r[0], 4);
    const uint32_t w0 = lane < 8 ? pack2t(r[0], nb, par) : pack2(r[0], nb);
    const uint32_t w1 = __shfl_down_sync(~0u, w0, 8), w2 = __shfl_down_sync(~0u, w0, 16), w3 = __shfl_down_sync(~0u, w0, 24);
    if (lane < 2) stx16(p_qa, make_uint4(w0, w1, w2, w3));
    arrive2(bar0 + 8 * (EB + 4), rsb + OFF_BAR + 8 * (EB + 4), lane == 0, lane == 0);
  }
  {
    if (warp) nbar_arrive(3, 256); else { nbar(3, 256); if (lane == 0) CNT_ADD(2 + (b >> 6)); }
    asm volatile("setmaxnreg.inc.sync.aligned.u32 216;");
    const unsigned* pq = g_qa + rk * 4096 + tid * 4;
    uint32_t a_q = sb + OFF_Q + ((tid & 63) >> 3) * 2048 + (tid >> 6) * 128 + (((tid & 7) ^ (tid >> 6)) << 4);
    PINL(pq); PIN(a_q);
    mbar_wait(bar0 + 8 * (XB + 1));
    uint4 v[4];
    POLL {
#pragma unroll
      for (int k = 0; k < 4; k++) v[k] = ldx16(pq + 1024 * k);
      RETRY(lop_x3(v[0].x, v[1].x, par) | lop_x3(v[2].x, v[3].x, par))
    }
#pragma unroll
    for (int k = 0; k < 4; k++)
      asm volatile("st.shared.v4.b32 [%0], {%1,%2,%3,%4};" ::"r"((a_q + k * 512) ^ ((k & 1) << 6)), "r"(v[k].x), "r"(v[k].y), "r"(v[k].z), "r"(v[k].w) : "memory");
    if (warp >= 4) nbar_arrive(1, 256); else nbar(1, 256);
  }
  sb = __shfl_sync(~0u, sb, 0); bar0 = sb + OFF_BAR;
  if (warp < 4) {
    uint32_t qf[32][4];
#pragma unroll
    for (int s = 0; s < 32; s++) ldsm(qf[s], sb + OFF_Q + (s >> 2) * 2048 + (lane & 15) * 128 + (((2 * (s & 3) + (lane >> 4)) ^ (lane & 7)) << 4));
    float l0 = 0.f, l1 = 0.f, m0 = -1e30f, m1 = -1e30f;
    const float sc = 0.08838834764831845f * 1.4426950408889634f;
    const uint32_t kofs = (16 * warp + 8 * (lane >> 4) + (lane & 7)) * 128 + ((((lane >> 3) & 1) ^ (lane & 7)) << 4);
    uint32_t st = sb;
#pragma unroll 1
    for (int t = 0; t < 8; t++) {
      float sa[4][4] = {};
#pragma unroll
      for (int hf = 0; hf < 2; hf++) {
        const int n = 2 * t + hf;
        mbar_wait(bar0 + 8 * (FB_KV + n));
        uint32_t kf[16][4];
#pragma unroll
        for (int y = 0; y < 16; y++) ldsm(kf[y], st + (y >> 2) * 8192 + (kofs ^ ((y & 3) << 5)));
#pragma unroll
        for (int y = 0; y < 16; y++) {
          mma16(sa[(2 * y) & 3], qf[16 * hf + y], kf[y][0], kf[y][1]); mma16(sa[((2 * y) & 3) + 1], qf[16 * hf + y], kf[y][2], kf[y][3]);
        }
        __syncwarp();
        arrive2(bar0 + 8 * (EB + NSLOT + n), rsb + OFF_BAR + 8 * (EB + NSLOT + n), lane == 0 && n < 14, lane == 0 && n < 16 - NSLOT);
        if (hf == 0) arrive2(bar0 + 8 * EB, 0, lane == 0 && t == 0, false);
        st = st + SLOT == sb + NSLOT * SLOT ? sb : st + SLOT;
      }
#pragma unroll
      for (int i = 0; i < 4; i++) { sa[0][i] = (sa[0][i] + sa[2][i]) * sc; sa[1][i] = (sa[1][i] + sa[3][i]) * sc; }
      float cm[2] = {fmaxf(fmaxf(sa[0][0], sa[0][1]), fmaxf(sa[1][0], sa[1][1])), fmaxf(fmaxf(sa[0][2], sa[0][3]), fmaxf(sa[1][2], sa[1][3]))};
      tmax<1>(cm, lane, 1);
      cm[0] = fmaxf(cm[0], __shfl_xor_sync(~0u, cm[0], 2));
      float* pm = s_sm + (t & 1) * 64;
      if (tq < 2) pm[(g + 8 * tq) * 4 + warp] = cm[0];
      if (t >= 2) nbar(6 + (t & 1), 256); else nbar(3, 128);
      const float4 a0 = *(const float4*)(pm + g * 4), b0 = *(const float4*)(pm + g * 4 + 32);
      const float n0 = fmaxf(fmaxf(fmaxf(a0.x, a0.y), fmaxf(a0.z, a0.w)), m0), n1 = fmaxf(fmaxf(fmaxf(b0.x, b0.y), fmaxf(b0.z, b0.w)), m1);
      uint32_t pk[4];
#pragma unroll
      for (int i = 0; i < 2; i++) { pk[2 * i] = pack2(ex2(sa[i][0] - n0), ex2(sa[i][1] - n0)); pk[2 * i + 1] = pack2(ex2(sa[i][2] - n1), ex2(sa[i][3] - n1)); }
      *(uint4*)(smem + OFF_P + (t & 1) * 2048 + tid * 16) = make_uint4(pk[0], pk[1], pk[2], pk[3]);
      const float al0 = ex2(m0 - n0), al1 = ex2(m1 - n1);
      if (tid < 32 && tq == 0) *(float2*)(s_sm + 192 + (t & 1) * 16 + 2 * g) = make_float2(al0, al1);
      nbar_arrive(4 + (t & 1), 256);
      m0 = n0; m1 = n1;
      l0 = l0 * al0 + (bflo(pk[0]) + bfhi(pk[0])) + (bflo(pk[2]) + bfhi(pk[2]));
      l1 = l1 * al1 + (bflo(pk[1]) + bfhi(pk[1])) + (bflo(pk[3]) + bfhi(pk[3]));
    }
    float lr[2] = {l0, l1};
    tred<1>(lr, lane, 1);
    lr[0] += __shfl_xor_sync(~0u, lr[0], 2);
    if (tq < 2) s_sm[128 + (g + 8 * tq) * 4 + warp] = lr[0];
    nbar(3, 128);
    if (warp == 0 && tq < 2) {
      const float4 a0 = *(const float4*)(s_sm + 128 + (g + 8 * tq) * 4);
      stx8(g_ml + (16 * rk + g + 8 * tq) * 64 + pr, make_uint2(fbits(tq ? m1 : m0), fbits((a0.x + a0.y) + (a0.z + a0.w))));
    }
    if (warp == 0) { __syncwarp(); if (lane == 0) CNT_ADD(96 + 32 * rk); }
    nbar(2, 288);
    if (tid == 0) asm volatile("red.relaxed.gpu.global.xor.b64 [%0], %1;" ::"l"(scr->cnt + 32 + 32 * rk), "l"(1ull << pr) : "memory");
  } else {
    float o[16][4] = {};
    const uint32_t vofs = (warp & 1) * 16384 + (lane & 15) * 128 + (((lane >> 4) ^ (lane & 7)) << 4);
    const int hf = (warp >> 1) & 1;
    uint32_t st = sb + hf * SLOT;
    auto pv = [&](const int t, auto np) {
      constexpr int npre = decltype(np)::value;
      uint32_t vf[4][8][4];
      const int n = 2 * t + hf;
      mbar_wait(bar0 + 8 * (FB_KV + n));
#pragma unroll
      for (int s = 0; s < npre; s++)
#pragma unroll
        for (int y = 0; y < 8; y++) ldsm_t(vf[s][y], st + (y >> 2) * 8192 + s * 2048 + (vofs ^ ((y & 3) << 5)));
      nbar(4 + (t & 1), 256);
      const float2 al = *(const float2*)(s_sm + 192 + (t & 1) * 16 + 2 * g);
      uint4 pf[4];
#pragma unroll
      for (int s = 0; s < 4; s++) pf[s] = *(const uint4*)(smem + OFF_P + (t & 1) * 2048 + s * 512 + lane * 16);
      if (t < 6) nbar_arrive(6 + (t & 1), 256);
#pragma unroll
      for (int s = npre; s < 4; s++)
#pragma unroll
        for (int y = 0; y < 8; y++) ldsm_t(vf[s][y], st + (y >> 2) * 8192 + s * 2048 + (vofs ^ ((y & 3) << 5)));
#pragma unroll
      for (int nt = 0; nt < 16; nt++) { o[nt][0] *= al.x; o[nt][1] *= al.x; o[nt][2] *= al.y; o[nt][3] *= al.y; }
#pragma unroll
      for (int s = 0; s < 4; s++) {
        const uint32_t pa[4] = {pf[s].x, pf[s].y, pf[s].z, pf[s].w};
#pragma unroll
        for (int y = 0; y < 8; y++) { mma16(o[2 * y], pa, vf[s][y][0], vf[s][y][1]); mma16(o[2 * y + 1], pa, vf[s][y][2], vf[s][y][3]); }
      }
      __syncwarp();
      arrive2(bar0 + 8 * (EB + NSLOT + n), rsb + OFF_BAR + 8 * (EB + NSLOT + n), lane == 0 && n < 14, lane == 0 && n < 16 - NSLOT);
      st = st + 2 * SLOT >= sb + NSLOT * SLOT ? st - (NSLOT - 2) * SLOT : st + 2 * SLOT;
    };
#pragma unroll 1
    for (int t = 0; t < 7; t++) pv(t, IC<NPRE0>());
    pv(7, IC<NPRE1>());
    uint4* po = g_xo + ((size_t)((16 * rk + (g & 6)) * 4 + warp - 4) * 64 + pr) * RS + (lane & 7);
    const bool odd = lane & 4;
#pragma unroll
    for (int e = 0; e < 2; e++)
#pragma unroll
      for (int j2 = 0; j2 < 2; j2++) {
        uint32_t c0[4], c1[4];
#pragma unroll
        for (int i = 0; i < 4; i++) {
          c0[i] = i ? pack2(o[8 * j2 + i][2 * e], o[8 * j2 + i][2 * e + 1]) : pack2t(o[8 * j2][2 * e], o[8 * j2][2 * e + 1], par);
          c1[i] = i ? pack2(o[8 * j2 + 4 + i][2 * e], o[8 * j2 + 4 + i][2 * e + 1]) : pack2t(o[8 * j2 + 4][2 * e], o[8 * j2 + 4][2 * e + 1], par);
          const uint32_t r = __shfl_xor_sync(~0u, odd ? c0[i] : c1[i], 4);
          if (odd) c0[i] = r; else c1[i] = r;
        }
        stx16(po + e * 8 * 4 * 64 * RS + 8 * j2, make_uint4(c0[0], c0[1], c0[2], c0[3]));
        stx16(po + (e * 8 + 1) * 4 * 64 * RS + 8 * j2, make_uint4(c1[0], c1[1], c1[2], c1[3]));
      }
    nbar_arrive(2, 288);
  }
  tail(smem, scr, x, out, par, epoch, warp);
}

static void launch(void* const* d_in, void* d_out) {
  static TMaps tms;
  static bool init = false;
  static void* scr = nullptr;
  if (!init) {
    void* fn = nullptr; cudaDriverEntryPointQueryResult qr;
    cudaGetDriverEntryPoint("cuTensorMapEncodeTiled", &fn, cudaEnableDefault, &qr);
    EncFn f = (EncFn)fn;
    const CUtensorMapSwizzle S32 = CU_TENSOR_MAP_SWIZZLE_32B, S64 = CU_TENSOR_MAP_SWIZZLE_64B, S128 = CU_TENSOR_MAP_SWIZZLE_128B;
    const CUtensorMapL2promotion P128 = CU_TENSOR_MAP_L2_PROMOTION_L2_128B, P256 = CU_TENSOR_MAP_L2_PROMOTION_L2_256B;
    enc3d(f, &tms.m[0], d_in[2], 64, 512, 64, 8192, 128, 64, 128, 1, S128, P128);
    enc3d(f, &tms.m[1], d_in[3], 64, 512, 64, 8192, 128, 64, 64, 2, S128, P256);
    enc3d(f, &tms.m[2], d_in[1], 64, SK, 8, 1024, 128, 64, 64, 2, S128, P256);
    enc3d(f, &tms.m[3], d_in[11], 3072, 256, 2, 6144, 256 * 6144, 16, 256, 2, S32, P128);
    enc3d(f, &tms.m[4], d_in[4], 64, 512, 64, 8192, 128, 64, 64, 2, S128, P256);
    enc3d(f, &tms.m[5], d_in[5], 512, 128, 32, 1024, 128 * 1024, 64, 128, 1, S128, P128);
    enc3d(f, &tms.m[6], d_in[7], 1792, 256, 2, 3584, 256 * 3584, 32, 256, 1, S64, P128);
    enc3d(f, &tms.m[7], d_in[8], 1792, 256, 2, 3584, 256 * 3584, 32, 256, 1, S64, P128);
    enc3d(f, &tms.m[8], d_in[9], 64, 1792, 8, 1024, 128, 64, 16, 8, S128, P256);
    cudaFuncSetAttribute(fused_kernel, cudaFuncAttributeMaxDynamicSharedMemorySize, SMEM_BYTES);
    cudaGetSymbolAddress(&scr, g_scr);
    init = true;
  }
  fused_kernel<<<NCTA, 384, SMEM_BYTES>>>((const bf16*)d_in[0], (const bf16*)d_in[10], (const bf16*)d_in[11], (bf16*)d_out, (Scratch*)scr, tms);
}

}

extern "C" void kernel_launch(void* const* d_in, const int* in_sizes, int n_in, void* d_out, int out_size) {
  static int big = -1;
  if (big < 0) big = v9::fits();
  if (big) v9::launch(d_in, d_out); else v8::launch(d_in, d_out);
}
```

```cpp
#include <cuda_runtime.h>
#include <cuda_bf16.h>
#include <cuda.h>
#include <stdint.h>
#include <stdio.h>
#include <stdlib.h>

typedef CUresult (*EncFn)(CUtensorMap*, CUtensorMapDataType, cuuint32_t, void*, const cuuint64_t*, const cuuint64_t*,
                          const cuuint32_t*, const cuuint32_t*, CUtensorMapInterleave, CUtensorMapSwizzle,
                          CUtensorMapL2promotion, CUtensorMapFloatOOBfill);

static void enc3d(EncFn fn, CUtensorMap* tm, void* p, uint64_t d0, uint64_t d1, uint64_t d2, uint64_t s1, uint64_t s2, uint32_t b0,
                  uint32_t b1, uint32_t b2, CUtensorMapSwizzle sw, CUtensorMapL2promotion pr) {
  cuuint64_t gd[3] = {d0, d1, d2}, gs[2] = {s1, s2};
  cuuint32_t bx[3] = {b0, b1, b2}, es[3] = {1, 1, 1};
  fn(tm, CU_TENSOR_MAP_DATA_TYPE_BFLOAT16, 3, p, gd, gs, bx, es, CU_TENSOR_MAP_INTERLEAVE_NONE, sw, pr, CU_TENSOR_MAP_FLOAT_OOB_FILL_NONE);
}

namespace v9 {
typedef __nv_bfloat16 bf16;
#define SK 32768
#define SPIN_MAX (1 << 20)
template <int N> struct IC { static constexpr int value = N; };

__device__ __forceinline__ uint32_t s2u(const void* p) { return (uint32_t)__cvta_generic_to_shared(p); }
__device__ __forceinline__ float bflo(uint32_t u) { return __uint_as_float(u << 16); }
__device__ __forceinline__ float bfhi(uint32_t u) { return __uint_as_float(u & 0xffff0000u); }
__device__ __forceinline__ float u2f(uint32_t u) { return __uint_as_float(u); }
__device__ __forceinline__ void fma8(float* acc, uint4 v, float s) {
  acc[0] += s * bflo(v.x); acc[1] += s * bfhi(v.x); acc[2] += s * bflo(v.y); acc[3] += s * bfhi(v.y);
  acc[4] += s * bflo(v.z); acc[5] += s * bfhi(v.z); acc[6] += s * bflo(v.w); acc[7] += s * bfhi(v.w);
}
__device__ __forceinline__ uint32_t pack2(float a, float b) {
  __nv_bfloat162 p = __floats2bfloat162_rn(a, b); return *(uint32_t*)&p;
}
__device__ __forceinline__ float bfr(float v) { return bfhi(pack2(v, v)); }
__device__ __forceinline__ float silu_bf(float c) { return bfr(__fdividef(c, 1.f + __expf(-c))); }
#define fbits(v) ((__float_as_uint(v) & ~1u) | par)
__device__ __forceinline__ uint32_t pack2t(float a, float b, unsigned par) {
  const uint32_t ua = ((__float_as_uint(a) + ((par ^ 1) << 16)) & 0xFFFE0000u) | (par << 16);
  return __byte_perm(ua, pack2(b, b), 0x7632);
}
__device__ __forceinline__ void nbar(int id, int n) { asm volatile("bar.sync %0, %1;" ::"r"(id), "r"(n) : "memory"); }
__device__ __forceinline__ void nbar_arrive(int id, int n) { asm volatile("bar.arrive %0, %1;" ::"r"(id), "r"(n) : "memory"); }
__device__ __forceinline__ uint4 ldc16(const void* p) {
  uint4 v; asm volatile("ld.relaxed.cta.global.v4.u32 {%0,%1,%2,%3}, [%4];" : "=r"(v.x), "=r"(v.y), "=r"(v.z), "=r"(v.w) : "l"(p) : "memory"); return v;
}
__device__ __forceinline__ unsigned ldc4(const void* p) {
  unsigned v; asm volatile("ld.relaxed.cta.global.u32 %0, [%1];" : "=r"(v) : "l"(p) : "memory"); return v;
}
__device__ __forceinline__ uint4 ldx16(const void* p) {
  uint4 v; asm volatile("ld.relaxed.gpu.global.v4.u32 {%0,%1,%2,%3}, [%4];" : "=r"(v.x), "=r"(v.y), "=r"(v.z), "=r"(v.w) : "l"(p) : "memory"); return v;
}
__device__ __forceinline__ unsigned ldx4(const void* p) {
  unsigned v; asm volatile("ld.relaxed.gpu.global.u32 %0, [%1];" : "=r"(v) : "l"(p) : "memory"); return v;
}
__device__ __forceinline__ unsigned long long ldx64(const void* p) {
  unsigned long long v; asm volatile("ld.relaxed.gpu.global.u64 %0, [%1];" : "=l"(v) : "l"(p) : "memory"); return v;
}
__device__ __forceinline__ void stx16(void* p, uint4 v) {
  asm volatile("st.relaxed.gpu.global.v4.u32 [%0], {%1,%2,%3,%4};" ::"l"(p), "r"(v.x), "r"(v.y), "r"(v.z), "r"(v.w) : "memory");
}
__device__ __forceinline__ void stx8(void* p, uint2 v) { asm volatile("st.relaxed.gpu.global.v2.u32 [%0], {%1,%2};" ::"l"(p), "r"(v.x), "r"(v.y) : "memory"); }
__device__ __forceinline__ void stx4(void* p, unsigned v) { asm volatile("st.relaxed.gpu.global.u32 [%0], %1;" ::"l"(p), "r"(v) : "memory"); }
__device__ __forceinline__ void pub4(void* p, unsigned v) { asm volatile("red.relaxed.gpu.global.xor.b32 [%0], %1;" ::"l"(p), "r"(v) : "memory"); }
__device__ __forceinline__ void pub8(void* p, unsigned lo, unsigned hi) {
  asm volatile("{.reg .b64 t; mov.b64 t, {%1, %2}; red.relaxed.gpu.global.xor.b64 [%0], t;}" ::"l"(p), "r"(lo), "r"(hi) : "memory");
}
__device__ __forceinline__ unsigned lop_x3(unsigned a, unsigned b, unsigned c) {
  unsigned d; asm("lop3.b32 %0, %1, %2, %3, 0x7E;" : "=r"(d) : "r"(a), "r"(b), "r"(c)); return d; }
__device__ __forceinline__ unsigned or3(unsigned a, unsigned b, unsigned c) {
  unsigned d; asm("lop3.b32 %0, %1, %2, %3, 0xFE;" : "=r"(d) : "r"(a), "r"(b), "r"(c)); return d; }
__device__ __forceinline__ unsigned and3(unsigned a, unsigned b, unsigned c) {
  unsigned d; asm("lop3.b32 %0, %1, %2, %3, 0x80;" : "=r"(d) : "r"(a), "r"(b), "r"(c)); return d; }
__device__ __forceinline__ unsigned dep16(const uint32_t* f) {
  unsigned d = 0;
#pragma unroll
  for (int i = 0; i < 8; i++) d = or3(d, f[8 * i], f[8 * i + 4]);
  return d;
}
__device__ __forceinline__ uint2 ldx8(const void* p) {
  uint2 v; asm volatile("{.reg .b64 t; ld.relaxed.gpu.global.b64 t, [%2]; mov.b64 {%0, %1}, t;}" : "=r"(v.x), "=r"(v.y) : "l"(p) : "memory"); return v;
}
__device__ __forceinline__ float lds4(uint32_t a) { float v; asm volatile("ld.shared.f32 %0, [%1];" : "=f"(v) : "r"(a) : "memory"); return v; }
__device__ __forceinline__ float shx(float v, int m) {
  float r; asm volatile("shfl.sync.bfly.b32 %0, %1, %2, 0x1f, 0xffffffff;" : "=f"(r) : "f"(v), "r"(m)); return r;
}
__device__ __forceinline__ uint32_t mbar_test(uint32_t bar, uint32_t ph) {
  uint32_t ok;
  asm volatile("{.reg .pred p; mbarrier.test_wait.parity.shared::cta.b64 p, [%1], %2; vote.sync.all.pred p, p, 0xffffffff; selp.u32 %0, 1, 0, p;}"
               : "=r"(ok) : "r"(bar), "r"(ph) : "memory");
  return ok;
}
#define X16(v) (lop_x3(v.x, v.y, par) | lop_x3(v.z, v.w, par))
#define RETRY(bad) if (!__any_sync(~0u, (bad) & 1) || ++it_ >= SPIN_MAX) break;
#define POLL _Pragma("unroll 1") for (int it_ = 0;;)
__device__ __forceinline__ void mbar_wait(uint32_t bar, uint32_t ph = 0) {
  asm volatile("{.reg .pred p; .reg .u32 n; mov.u32 n, 0;\n"
               "W%=: mbarrier.try_wait.parity.shared::cta.b64 p, [%0], %1; add.u32 n, n, 1; setp.lt.and.u32 p, n, 0x100000, !p; @p bra W%=;}"
               ::"r"(bar), "r"(ph) : "memory");
}
__device__ __forceinline__ float ex2(float v) { float r; asm("ex2.approx.ftz.f32 %0, %1;" : "=f"(r) : "f"(v)); return r; }
__device__ __forceinline__ float rcp(float v) { float r; asm("rcp.approx.ftz.f32 %0, %1;" : "=f"(r) : "f"(v)); return r; }
__device__ __forceinline__ void mma16(float* d, const uint32_t* a, uint32_t b0, uint32_t b1) {
  asm volatile("mma.sync.aligned.m16n8k16.row.col.f32.bf16.bf16.f32 {%0,%1,%2,%3}, {%4,%5,%6,%7}, {%8,%9}, {%0,%1,%2,%3};"
               : "+f"(d[0]), "+f"(d[1]), "+f"(d[2]), "+f"(d[3]) : "r"(a[0]), "r"(a[1]), "r"(a[2]), "r"(a[3]), "r"(b0), "r"(b1));
}
__device__ __forceinline__ void mma16c(float* d, const uint32_t* a, uint32_t b0, uint32_t b1, const float* c) {
  asm volatile("mma.sync.aligned.m16n8k16.row.col.f32.bf16.bf16.f32 {%0,%1,%2,%3}, {%4,%5,%6,%7}, {%8,%9}, {%10,%11,%12,%13};"
               : "=f"(d[0]), "=f"(d[1]), "=f"(d[2]), "=f"(d[3])
               : "r"(a[0]), "r"(a[1]), "r"(a[2]), "r"(a[3]), "r"(b0), "r"(b1), "f"(c[0]), "f"(c[1]), "f"(c[2]), "f"(c[3]));
}
__device__ __forceinline__ float4 lds16(uint32_t a) {
  float4 v; asm volatile("ld.shared.v4.f32 {%0,%1,%2,%3}, [%4];" : "=f"(v.x), "=f"(v.y), "=f"(v.z), "=f"(v.w) : "r"(a) : "memory"); return v;
}
__device__ __forceinline__ void sts4(uint32_t a, float v) { asm volatile("st.shared.f32 [%0], %1;" ::"r"(a), "f"(v) : "memory"); }
__device__ __forceinline__ void sts16(uint32_t a, uint4 v) {
  asm volatile("st.shared.v4.b32 [%0], {%1,%2,%3,%4};" ::"r"(a), "r"(v.x), "r"(v.y), "r"(v.z), "r"(v.w) : "memory");
}
__device__ __forceinline__ void ldsm_t(uint32_t* r, uint32_t a) {
  asm volatile("ldmatrix.sync.aligned.m8n8.x4.trans.shared.b16 {%0,%1,%2,%3}, [%4];" : "=r"(r[0]), "=r"(r[1]), "=r"(r[2]), "=r"(r[3]) : "r"(a) : "memory");
}
__device__ __forceinline__ void ldsm(uint32_t* r, uint32_t a) {
  asm volatile("ldmatrix.sync.aligned.m8n8.x4.shared.b16 {%0,%1,%2,%3}, [%4];" : "=r"(r[0]), "=r"(r[1]), "=r"(r[2]), "=r"(r[3]) : "r"(a) : "memory");
}
__device__ __forceinline__ uint32_t mapa(uint32_t a, uint32_t r) {
  uint32_t v; asm volatile("mapa.shared::cluster.u32 %0, %1, %2;" : "=r"(v) : "r"(a), "r"(r)); return v;
}
__device__ __forceinline__ unsigned long long mapg(uint32_t a, uint32_t r) {
  unsigned long long v;
  asm volatile("{.reg .u32 t; .reg .u64 u; mapa.shared::cluster.u32 t, %1, %2; cvt.u64.u32 u, t; cvta.shared::cluster.u64 %0, u;}" : "=l"(v) : "r"(a), "r"(r));
  return v;
}
template <int N>
__device__ __forceinline__ void tred(float* a, int lane, int m) {
  const bool hi = lane & m;
#pragma unroll
  for (int i = 0; i < N; i++) {
    float send = hi ? a[i] : a[i + N], keep = hi ? a[i + N] : a[i];
    a[i] = keep + __shfl_xor_sync(~0u, send, m);
  }
}
template <int N>
__device__ __forceinline__ void tmax(float* a, int lane, int m) {
  const bool hi = lane & m;
#pragma unroll
  for (int i = 0; i < N; i++) {
    float send = hi ? a[i] : a[i + N], keep = hi ? a[i + N] : a[i];
    a[i] = fmaxf(keep, __shfl_xor_sync(~0u, send, m));
  }
}
__device__ __forceinline__ void arrive_n(uint32_t bar, bool on, int cnt) {
  asm volatile("{.reg .pred p; setp.ne.s32 p, %1, 0; @p mbarrier.arrive.shared::cta.b64 _, [%0], %2;}" ::"r"(bar), "r"((int)on), "r"(cnt) : "memory");
}
__device__ __forceinline__ unsigned long long stream_policy() {
  unsigned long long p;
  asm volatile("createpolicy.fractional.L2::evict_first.b64 %0, 1.0;" : "=l"(p));
  return p;
}
__device__ __forceinline__ void tma3d(uint32_t dst, const CUtensorMap* tm, uint32_t bar, int c0, int c1, int c2) {
  asm volatile("cp.async.bulk.tensor.3d.shared::cluster.global.mbarrier::complete_tx::bytes.L2::cache_hint [%0], [%1, {%3, %4, %5}], [%2], %6;"
               ::"r"(dst), "l"(tm), "r"(bar), "r"(c0), "r"(c1), "r"(c2), "l"(stream_policy()) : "memory");
}
__device__ __forceinline__ void spin_until(unsigned t) { while ((int)((unsigned)clock() - t) < 0) {} }
__device__ __forceinline__ void wait_until(unsigned t) {
  unsigned now;
  do { asm volatile("mov.u32 %0, %%globaltimer_lo;" : "=r"(now)); } while ((int)(now - t) < 0);
}
__device__ __forceinline__ void sleep_until(unsigned t) {
  unsigned now;
#pragma unroll 1
  do {
    __nanosleep(200);
    asm volatile("mov.u32 %0, %%globaltimer_lo;" : "=r"(now));
  } while ((int)(now - t) < 0);
}
#define PIN(x) asm volatile("" : "+r"(x))
#define PINL(x) asm volatile("" : "+l"(x))
#define BAR_ARRIVE(i) asm volatile("mbarrier.arrive.shared::cta.b64 _, [%0];" ::"r"(bar0 + 8 * (i)) : "memory")
#define LANE0(op, p, c, v) asm volatile("{.reg .pred q; setp.eq.s32 q, %2, 0; @q " op " [%0], %1;}" ::"l"((p) + lane), c(v), "r"(lane) : "memory")
#define CNT_ADD(c) LANE0("red.relaxed.gpu.global.add.u32", scr->cnt + (c), "r", 1)
#define BAR_INIT(i, cnt) asm volatile("mbarrier.init.shared::cta.b64 [%0], %1;" ::"r"(bar0 + 8 * (i)), "r"(cnt) : "memory")
#define BAR_ARM(i, bytes) asm volatile("mbarrier.arrive.expect_tx.shared::cta.b64 _, [%0], %1;" ::"r"(bar0 + 8 * (i)), "r"(bytes) : "memory")
struct TMaps { CUtensorMap m[9]; };

#define NCTA9 120
#define TAU 20
#define NSL 100
#define NPE 1
#define QN 4
#define FDLY 60
#define VJ 1
#define NPO 3
#define VDLY 150
#define O_Q 131072
#define O_LZ 163840
#define O_CTX 196608
#define O_HZ 198656
#define O_HW 200704
#define O_X 201728
#define O_P 218112
#define O_B 222208
#define O_R 224512
#define O_SILU 228608
#define O_SM 229632
#define O_BAR 231424
#define O_EP (O_BAR + 256)
#define O_DBG (O_EP + 16)
#define SMEM9 (O_DBG + 144)
#define B_FULL 0
#define B_FM 8
#define B_EMPTY 10
#define B_EM 18
#define B_LZ 18
#define B_Q2 19
#define B_H 20
#define B_QF 21
#define B_TAB 22
#define B_W 23
#define B_ST 24
#define B_HZ 25
#define B_WZ 26
#define B_G2 28
#define B_G 27
enum { T_WQ, T_WUK, T_KV, T_MOD, T_UV, T_WO, T_GU, T_DN = 8 };
#define NBIG 40
struct Sched { unsigned zero, dth; uint2 r[3][8]; unsigned nr[3], nt[3], dt, t4, d4, d6, wt, pad; };

struct __align__(128) Scratch {
  unsigned cnt[8 * 32];
  uint2 rec[32 * 4 * 8 * 64];
  uint2 hdr[32 * 16];
  unsigned h[8 * 256];
  uint4 qa[2048];
  unsigned xao[8 * 512];
  unsigned xab[8 * 256];
  unsigned xm[2048];
};
__device__ Scratch g_scr;
#define SMEM_BASE 1024u
#define DSC ((SMEM_BASE >> 4) | (1u << 16))
#define HI128 (64u | (1u << 30))
#define HI64 (32u | (2u << 30))
template <int TA, int TB, unsigned HIA, unsigned HIB>
__device__ __forceinline__ void wgmma32(float* d, uint32_t da, uint32_t db, int acc) {
  asm volatile("{.reg .pred p; .reg .b64 da, db; setp.ne.b32 p, %18, 0; mov.b64 da, {%16, %21}; mov.b64 db, {%17, %22};\n"
               "wgmma.mma_async.sync.aligned.m64n32k16.f32.bf16.bf16 "
               "{%0,%1,%2,%3,%4,%5,%6,%7,%8,%9,%10,%11,%12,%13,%14,%15}, da, db, p, 1, 1, %19, %20;}"
               : "+f"(d[0]), "+f"(d[1]), "+f"(d[2]), "+f"(d[3]), "+f"(d[4]), "+f"(d[5]), "+f"(d[6]), "+f"(d[7]),
                 "+f"(d[8]), "+f"(d[9]), "+f"(d[10]), "+f"(d[11]), "+f"(d[12]), "+f"(d[13]), "+f"(d[14]), "+f"(d[15])
               : "r"(da), "r"(db), "r"(acc), "n"(TA), "n"(TB), "n"(HIA), "n"(HIB));
}
__device__ __forceinline__ void wgmma32r(float* d, const uint32_t* a, uint32_t db) {
  asm volatile("{.reg .b64 db; mov.b64 db, {%20, %21};\n"
               "wgmma.mma_async.sync.aligned.m64n32k16.f32.bf16.bf16 "
               "{%0,%1,%2,%3,%4,%5,%6,%7,%8,%9,%10,%11,%12,%13,%14,%15}, {%16,%17,%18,%19}, db, 1, 1, 1, 1;}"
               : "+f"(d[0]), "+f"(d[1]), "+f"(d[2]), "+f"(d[3]), "+f"(d[4]), "+f"(d[5]), "+f"(d[6]), "+f"(d[7]),
                 "+f"(d[8]), "+f"(d[9]), "+f"(d[10]), "+f"(d[11]), "+f"(d[12]), "+f"(d[13]), "+f"(d[14]), "+f"(d[15])
               : "r"(a[0]), "r"(a[1]), "r"(a[2]), "r"(a[3]), "r"(db), "n"(HI64));
}
template <int N> __device__ __forceinline__ void wg_wait(float* a) {
  asm volatile("wgmma.wait_group.sync.aligned %16;"
               : "+f"(a[0]), "+f"(a[1]), "+f"(a[2]), "+f"(a[3]), "+f"(a[4]), "+f"(a[5]), "+f"(a[6]), "+f"(a[7]), "+f"(a[8]), "+f"(a[9]), "+f"(a[10]),
                 "+f"(a[11]), "+f"(a[12]), "+f"(a[13]), "+f"(a[14]), "+f"(a[15]) : "n"(N) : "memory");
}
__device__ __forceinline__ void send32(uint32_t a, uint32_t bar, float v, int lane) {
  const uint32_t w = pack2(v, __shfl_down_sync(~0u, v, 1));
  const int s = 2 * (lane & 3);
  asm volatile("{.reg .pred p; setp.eq.s32 p, %6, 0; @p st.async.shared::cluster.mbarrier::complete_tx::bytes.v4.b32 [%0], {%1,%2,%3,%4}, [%5];}"
               ::"r"(a), "r"(__shfl_sync(~0u, w, s)), "r"(__shfl_sync(~0u, w, s + 8)), "r"(__shfl_sync(~0u, w, s + 16)), "r"(__shfl_sync(~0u, w, s + 24)),
                 "r"(bar), "r"(lane & 12) : "memory");
}
__device__ __forceinline__ float sum8(uint32_t a) {
  const float4 p = lds16(a), q = lds16(a + 1024);
  return ((p.x + p.y) + (p.z + p.w)) + ((q.x + q.y) + (q.z + q.w));
}
__device__ __forceinline__ int posof(int c) { return (c & ~14) + 2 * (c & 6) + ((c >> 2) & 2); }

__global__ void __cluster_dims__(8, 1, 1) __launch_bounds__(384, 1)
fused_kernel(const bf16* __restrict__ x, const bf16* __restrict__ cvec, const bf16* __restrict__ w_mod, bf16* __restrict__ out,
             Scratch* __restrict__ scr, const __grid_constant__ Sched sch, const __grid_constant__ TMaps tms) {
  extern __shared__ __align__(1024) unsigned char smem[];
  const int tid = threadIdx.x, warp = __shfl_sync(~0u, tid >> 5, 0), lane = tid & 31;
  const int b = blockIdx.x, cl = b >> 3, rn = b & 7, rk = b & 1, hd = b >> 1, f = b - 64;
  const bool isA = b < 64;
  uint32_t sb = s2u(smem), bar0 = sb + O_BAR;
  unsigned gt_start;
  asm volatile("mov.u32 %0, %%globaltimer_lo;" : "=r"(gt_start));
  const int g = lane >> 2, tq = lane & 3;
  const int arow = 64 * rn + ((tid & 255) >> 4);
  uint4 wm[4];
  uint32_t cw, xw;
  if (warp < 8 && isA) {
    const bf16* wa = w_mod + (size_t)arow * 3072 + (lane & 8) * 64 + 64 * cl + 8 * (lane & 7);
#pragma unroll
    for (int i = 0; i < 4; i++) wm[i] = ldx16(wa + i * 16 * 3072);
    cw = ldc4(cvec + (arow & ~1) + 16 * tq);
    if (warp < 2) xw = ldc4(x + 64 * cl + (tid & 62));
  }
  if (warp == 11) {
    if (lane == 0) {
#pragma unroll
      for (int i = 0; i < B_EMPTY; i++) BAR_INIT(i, 1);
    }
    __syncwarp();
    asm volatile("fence.mbarrier_init.release.cluster;" ::: "memory");
    asm volatile("barrier.cluster.arrive.relaxed.aligned;" ::: "memory");
    if (isA) {
#pragma unroll 1
      for (int i = 0; i < 8; i++) {
        if (i >= 6) mbar_wait(bar0 + 8 * (i - 6));
        wait_until(gt_start + ((64 * i + b) * sch.dth >> 8));
        if (lane == 0) {
          BAR_ARM(i, 16384);
          tma3d(sb + i * 16384, &tms.m[i >> 2], bar0 + 8 * i, 0, i < 4 ? 128 * i : 256 * rk + 64 * (i - 4), i < 4 ? b : b & ~1);
        }
        __syncwarp();
      }
    }
  }
  if (warp == 10) {
    const unsigned ep = ldc4(&scr->cnt[0]);
    if (isA) {
      const uint4 xa = ldc16(x + 16 * lane), xb = ldc16(x + 16 * lane + 8);
      float xv[16] = {bflo(xa.x), bfhi(xa.x), bflo(xa.y), bfhi(xa.y), bflo(xa.z), bfhi(xa.z), bflo(xa.w), bfhi(xa.w),
                      bflo(xb.x), bfhi(xb.x), bflo(xb.y), bfhi(xb.y), bflo(xb.z), bfhi(xb.z), bflo(xb.w), bfhi(xb.w)};
      const float x0 = __shfl_sync(~0u, xv[0], 0);
      float s = 0, q = 0;
#pragma unroll
      for (int i = 0; i < 16; i++) { xv[i] -= x0; s += xv[i]; q += xv[i] * xv[i]; }
#pragma unroll
      for (int o = 16; o; o >>= 1) { s += __shfl_xor_sync(~0u, s, o); q += __shfl_xor_sync(~0u, q, o); }
      s *= 1.f / 512.f;
      float rstd;
      asm("rsqrt.approx.ftz.f32 %0, %1;" : "=f"(rstd) : "f"(fmaxf(q * (1.f / 512.f) - s * s, 0.f) + 1e-5f));
      *(float2*)(smem + O_SM + 1024) = make_float2(s + x0, rstd);
    }
    if (lane == 0) *(volatile unsigned*)(smem + O_EP) = ep;
    nbar_arrive(1, 288);
  }
  const int cls = isA ? (b >= NBIG) : 2, v0 = isA ? 2 : 0;
  if (warp >= 8) {
    asm volatile("setmaxnreg.dec.sync.aligned.u32 56;");
    if (warp == 8) {
      if (lane < 8) asm volatile("prefetch.tensormap [%0];" ::"l"(&tms.m[lane + 1]) : "memory");
      if ((sb & 0xFFFFFF) != SMEM_BASE) __trap();
    } else if (warp == 9) {
      if (lane == 0) {
#pragma unroll
        for (int i = B_EMPTY; i < B_EM; i++) BAR_INIT(i, 8);
        BAR_INIT(B_LZ, 8); BAR_INIT(B_Q2, 9); BAR_ARM(B_Q2, 1024);
        BAR_INIT(B_H, 1); BAR_INIT(B_QF, 1); BAR_ARM(B_QF, 32768);
        BAR_INIT(B_TAB, 1); BAR_INIT(B_W, 1); BAR_INIT(B_ST, 8); BAR_INIT(B_WZ, 1); BAR_INIT(B_HZ, 1); BAR_ARM(B_HZ, isA ? 1024 : 512); BAR_INIT(B_G, 1); BAR_INIT(B_G2, 1);
      }

    }
    if (warp != 11) {
      __syncwarp();
      asm volatile("fence.mbarrier_init.release.cluster;" ::: "memory");
      __threadfence_block();
      asm volatile("barrier.cluster.arrive.relaxed.aligned;" ::: "memory");
    }
    asm volatile("barrier.cluster.wait.acquire.aligned;" ::: "memory");
    if (warp == 8) {
      const int nr = sch.nr[cls], vl = v0 + sch.nt[cls] - 1;
      unsigned long long hist = 0;
      int v = v0;
#pragma unroll 1
      for (int rd = 0; rd < nr; rd++) {
        const uint2 e = sch.r[cls][rd];
        const int type = e.y & 15, win = (e.y >> 4) & 15, pos = b + 64 - (int)((e.y >> 8) & 255), tile = e.y >> 16;
        const bool mod = type == T_MOD;
        const int ni = mod ? 1 : type == T_DN ? 2 : 4;
        unsigned t = gt_start + (e.x & 0xffff) + (pos * sch.dt >> 8);
        const int c0 = mod ? 1024 + 32 * b : type == T_WO || type == T_DN ? 64 * rn : type == T_GU ? 32 * f : 0;
        int c1 = type == T_KV ? 64 * (tile + pos) : 0;
        int c2 = mod ? tile : type == T_WO ? 4 * cl : type == T_DN ? 2 * cl - 16 : type == T_UV ? b : 0;
        const int i1 = type == T_UV ? 128 : 0;
#pragma unroll 1
        for (int j = 0; j < ni; j++) {
          const int slot = mod ? B_FM + tile : (v & 1) * 4 + j;
          if (mod ? tile : v >= 2) mbar_wait(bar0 + 8 * (B_EMPTY + (mod ? (vl & 1) * 4 : slot)), mod ? (vl >> 1) & 1 : ((v >> 1) - 1) & 1);
          const int hw = (int)(hist >> (6 * (win - 1))) & 63;
          if (hw) mbar_wait(bar0 + 8 * (hw & 15), (hw >> 4) & 1);
          wait_until(t);
          if (lane == 0) {
            BAR_ARM(slot, 16384);
            tma3d(sb + (mod ? (tile ? O_Q : O_X) : slot * 16384), &tms.m[type == T_GU ? type + (j & 1) : type], bar0 + 8 * slot, c0, c1, c2);
          }
          __syncwarp();
          hist = hist << 6 | (32 | (mod ? 0 : (v & 2) << 3) | slot);
          t += e.x >> 16; c1 += i1;
          c2 += type == T_KV ? 2 : type == T_WO || type == T_DN ? 1 : type == T_GU ? j & 1 : 0;
        }
        v += !mod;
      }
      return;
    }
    const unsigned epoch = *(volatile unsigned*)(smem + O_EP), par = (epoch + 1) & 1;
    if (warp == 10) {
      if (isA) {
        for (int it = 0; ldx4(scr->cnt + 1) != (epoch + 1) * 128 && it < SPIN_MAX; it++) {}
        if (lane == 0) BAR_ARRIVE(B_H);
      } else mbar_wait(bar0);
      if (!(rn & (QN - 1))) {
        for (int it = 0; ldx4(scr->cnt + 32 + 32 * (rn >> 2)) != (epoch + 1) * 32 && it < SPIN_MAX; it++) {}
        if (lane == 0)
          asm volatile("cp.async.bulk.shared::cluster.global.mbarrier::complete_tx::bytes.multicast::cluster [%0], [%1], %4, [%2], %3;"
                       ::"r"(sb + O_Q + rn * 4096), "l"(scr->qa + rn * 256), "r"(bar0 + 8 * B_QF), "h"((unsigned short)0xff), "n"(4096 * QN) : "memory");
      }
      const unsigned dl = isA ? sch.d4 : sch.d6;
      unsigned tw = gt_start + sch.t4;
      if (!isA) {
        const int nt = sch.nt[2];
#pragma unroll 1
        for (int t = 0; t < nt; t++) mbar_wait(bar0 + 8 * B_EMPTY + (t & 1) * 32, (t >> 1) & 1);
        unsigned long long now;
        asm volatile("mov.u64 %0, %%globaltimer;" : "=l"(now));
        LANE0("red.relaxed.gpu.global.max.u64", scr->cnt + 130, "l", now);
        CNT_ADD(128);
        tw = (unsigned)now + 1700;
      }
      sleep_until(tw);
      uint4 an;
      for (int it = 0; an = ldx16(scr->cnt + 128), an.x != (epoch + 1) * 56 && it < SPIN_MAX; it++) {}
      wait_until(an.z + (dl >> 16));
      if (lane == 0) BAR_ARRIVE(B_G2);
      wait_until(an.z + (dl & 0xffff));
      if (lane == 0) BAR_ARRIVE(B_G);
    } else if (warp == 11) {
      {
        uint2* ph = scr->hdr + ((lane & 24) + 2 * tq + (g & 1)) * 16 + cl;
        const bool own = (lane >> 4) * 4 + tq == rn;
        if (own) { stx8(ph, make_uint2(par ^ 1, 0)); if (cl == 14) stx8(ph + 1, make_uint2(0, 0)); }
        uint32_t a_w = sb + O_HW + ((lane >> 4) * 4 + tq) * 128 + (g & 1) * 64 + ((lane >> 1) & 4);
        PIN(a_w); PINL(ph);
        const int vt = v0 + sch.nt[cls];
#pragma unroll 1
        for (int t = 0; t < vt; t++) mbar_wait(bar0 + 8 * B_EMPTY + (t & 1) * 32, (t >> 1) & 1);
        float hz[8], M;
        uint32_t wp[4];
#pragma unroll 1
        for (int e = 0; e < 2; e++) {
          POLL {
            unsigned ok = 1;
#pragma unroll
            for (int u = 0; u < 8; u++)
              asm volatile("ld.relaxed.cluster.shared.f32 %0, [%1];" : "=f"(hz[u]) : "r"(sb + O_HZ + e * 1024 + u * 128 + lane * 4) : "memory");
#pragma unroll
            for (int u = 0; u < 4; u++) ok = and3(ok, __float_as_uint(hz[u]), __float_as_uint(hz[u + 4]));
            RETRY(~ok)
          }
          if (e) break;
          M = fmaxf(fmaxf(fmaxf(hz[0], hz[1]), fmaxf(hz[2], hz[3])), fmaxf(fmaxf(hz[4], hz[5]), fmaxf(hz[6], hz[7])));
          M = u2f(fbits(M));
#pragma unroll
          for (int u = 0; u < 4; u++) {
            wp[u] = pack2(ex2(hz[u] - M), ex2(hz[u + 4] - M));
            sts4(a_w + ((rn - u) & 3) * 8, u2f(wp[u])); sts4(a_w + ((rn - u) & 3) * 8 + 32, u2f(wp[u]));
          }
          __syncwarp();
          if (lane == 0) BAR_ARRIVE(B_WZ);
        }
        float L = 0.f;
#pragma unroll
        for (int u = 0; u < 4; u++) L += bflo(wp[u]) * hz[u] + bfhi(wp[u]) * hz[u + 4];
        if (own) pub8(ph, __float_as_uint(M) | 1u, __float_as_uint(L));
      }
      if (isA) {
        mbar_wait(bar0 + 8 * B_G2);
        unsigned long long hh;
        POLL { hh = ldx64(scr->hdr + hd * 16 + (lane & 15)); RETRY((lane & 15) == 15 ? 0u : (unsigned)hh ^ par) }
        const float m = (lane & 15) == 15 ? -1e30f : u2f((unsigned)hh);
        int mi = __float_as_int(m);
        mi ^= (mi >> 31) & 0x7fffffff;
        mi = __reduce_max_sync(~0u, mi);
        mi ^= (mi >> 31) & 0x7fffffff;
        const float w = ex2(m - __int_as_float(mi));
        float L = w * u2f(hh >> 32);
#pragma unroll
        for (int o2 = 8; o2; o2 >>= 1) L += __shfl_xor_sync(~0u, L, o2);
        sts4(sb + O_SM + (384 + 2 * (lane & 6) + ((lane >> 2) & 2) + (lane & 1)) * 4, w * rcp(L));
        __syncwarp();
        if (lane == 0) BAR_ARRIVE(B_W);
      }
    } else {
#pragma unroll 4
      for (int i = 0; i < 72; i++) sts16(sb + O_LZ + i * 512 + lane * 16, make_uint4(0, 0, 0, 0));
      __syncwarp();
      if (lane < 8) asm volatile("mbarrier.arrive.release.cluster.shared::cluster.b64 _, [%0];" ::"r"(mapa(bar0 + 8 * B_LZ, lane)) : "memory");
      if (isA) {
        mbar_wait(bar0 + 8 * B_QF);
#pragma unroll 2
        for (int k = 0; k < 8; k++) {
          const uint32_t cp = ldc4(cvec + 2 * (lane + 32 * k));
          *(uint32_t*)(smem + O_SILU + (lane + 32 * k) * 4) = pack2(silu_bf(bflo(cp)), silu_bf(bfhi(cp)));
        }
        __syncwarp();
        uint32_t ab = sb + O_X + (8 * (lane >> 4) + (lane & 7)) * 64 + ((((lane >> 3) & 1) ^ ((lane >> 1) & 3)) << 4);
        float d[4][4] = {};
#pragma unroll 1
        for (int jm = 0; jm < 2; jm++) {
          mbar_wait(bar0 + 8 * (B_FM + jm));
#pragma unroll 2
          for (int s2 = 0; s2 < 8; s2++)
#pragma unroll
            for (int s = 0; s < 2; s++) {
              uint32_t a0[4], a1[4];
              const uint32_t* ps = (const uint32_t*)(smem + O_SILU) + 128 * jm + 16 * s2 + 8 * s + tq;
              ldsm_t(a0, ab + (2 * s2 + s) * 1024); ldsm_t(a1, (ab + (2 * s2 + s) * 1024) ^ 32);
              mma16(d[s], a0, ps[0], ps[4]); mma16(d[2 + s], a1, ps[0], ps[4]);
            }
          ab -= O_X - O_Q;
        }
        const float t0 = (tq & 1) ? d[0][2] + d[1][2] : d[0][0] + d[1][0], t1 = (tq & 1) ? d[2][2] + d[3][2] : d[2][0] + d[3][0];
        stx4(scr->xm + b * 32 + posof(8 * tq + g), fbits(bfr(bfr((tq & 2) ? t1 : t0) + ((b >> 4) == 2 ? 1.f : 0.f))));
        __syncwarp();
        CNT_ADD(96);
      } else sleep_until(gt_start + sch.t4);
      for (int it = 0; ldx4(scr->cnt + 96) != (epoch + 1) * 64 && it < SPIN_MAX; it++) __nanosleep(NSL);
      if (isA) {
        unsigned long long ga;
        POLL { ga = ldx64(scr->xm + 64 * rn + 2 * lane); RETRY(lop_x3((unsigned)ga, ga >> 32, par)) }
        *(float2*)(smem + O_SM + (320 + 2 * lane) * 4) = make_float2(bfhi((unsigned)ga), bfhi(ga >> 32));
      }
      __syncwarp();
      if (lane == 0) BAR_ARRIVE(B_TAB);
    }
    return;
  }

  float* s_sm = (float*)(smem + O_SM);
  unsigned par, epoch;
  asm volatile("barrier.cluster.arrive.relaxed.aligned;" ::: "memory");
  if (isA) {
    float* s_r = (float*)(smem + O_R);
    float acc[8] = {0, 0, 0, 0, 0, 0, 0, 0};
    const float sl = silu_bf((arow & 1) ? bfhi(cw) : bflo(cw));
#pragma unroll
    for (int i = 0; i < 4; i++) fma8(acc, wm[i], __shfl_sync(~0u, sl, i, 4));
    tred<4>(acc, lane, 16);
    *(float4*)(s_r + warp * 128 + 8 * (lane & 15) + ((lane >> 2) & 4)) = make_float4(acc[0], acc[1], acc[2], acc[3]);
    nbar(1, 288);
    epoch = *(volatile unsigned*)(smem + O_EP);
    par = (epoch + 1) & 1;
    if (warp < 2) {
      float t = 0.f, ca = rn == 0 ? 1.f : 0.f;
#pragma unroll
      for (int w = 0; w < 8; w++) { t += s_r[w * 128 + tid]; ca += s_r[w * 128 + 64 + tid]; }
      t += ca * ((((tid & 1) ? bfhi(xw) : bflo(xw)) - s_sm[256]) * s_sm[257]);
      const float nb = __shfl_down_sync(~0u, t, 1);
      const uint32_t w0 = lane < 8 ? pack2t(t, nb, par) : pack2(t, nb);
      const uint32_t w1 = __shfl_down_sync(~0u, w0, 8), w2 = __shfl_down_sync(~0u, w0, 16), w3 = __shfl_down_sync(~0u, w0, 24);
      if (lane < 8 && !(lane & 1)) stx16(scr->h + (rn >> 1) * 512 + (2 * cl + warp) * 32 + rk * 16 + 2 * lane, make_uint4(w0, w1, w2, w3));
      __syncwarp();
      CNT_ADD(1);
    }
    asm volatile("barrier.cluster.wait.acquire.aligned;" ::: "memory");
    const uint32_t rsb = mapa(sb, rn ^ 1);
    {
      uint32_t a[4][4][4];
      mbar_wait(bar0 + 8 * (warp >> 1));
      const uint32_t ab = sb + (64 * warp + 8 * (lane >> 4) + (lane & 7)) * 128;
#pragma unroll
      for (int s = 0; s < 4; s++)
#pragma unroll
        for (int mt = 0; mt < 4; mt++) ldsm_t(a[s][mt], ab + s * 2048 + (((2 * mt + ((lane >> 3) & 1)) ^ (lane & 7)) << 4));
      arrive_n(bar0 + 8 * (B_EMPTY + (warp >> 1)), lane == 0, 4 + (dep16(&a[0][0][0]) & sch.zero));
      uint4 v0, v1;
      const unsigned* ph = scr->h + (g >> 1) * 512 + 64 * warp + 4 * (lane & 7);
      uint32_t off = O_B + warp * 272 + (32 * rk + 8 * tq + (lane & 4)) * 4;
      PIN(off); PINL(ph);
      mbar_wait(bar0 + 8 * B_H);
      POLL { v0 = ldx16(ph); v1 = ldx16(ph + 32); RETRY(lop_x3(v0.x, v1.x, par)) }
      float d[4][4] = {};
#pragma unroll
      for (int mt = 0; mt < 4; mt++) {
        mma16(d[mt], a[0][mt], v0.x, v0.y); mma16(d[mt], a[1][mt], v0.z, v0.w);
        mma16(d[mt], a[2][mt], v1.x, v1.y); mma16(d[mt], a[3][mt], v1.z, v1.w);
      }
      float r[8];
#pragma unroll
      for (int mt = 0; mt < 4; mt++) { r[2 * mt] = d[mt][0] + d[mt][1]; r[2 * mt + 1] = d[mt][2] + d[mt][3]; }
      tred<4>(r, lane, 2); tred<2>(r, lane, 1);
      const float rc = __shfl_xor_sync(~0u, (lane & 4) ? r[0] : r[1], 4);
      const uint32_t wd = (lane & 4) ? pack2(rc, r[1]) : pack2(r[0], rc);
      const uint32_t w1 = __shfl_down_sync(~0u, wd, 8), w2 = __shfl_down_sync(~0u, wd, 16), w3 = __shfl_down_sync(~0u, wd, 24);
      asm volatile("{.reg .pred p; setp.lt.s32 p, %7, 8; @p st.shared.v4.b32 [%0], {%2,%3,%4,%5};\n"
                   "@p st.async.shared::cluster.mbarrier::complete_tx::bytes.v4.b32 [%1], {%2,%3,%4,%5}, [%6];}"
                   ::"r"(sb + off), "r"(rsb + off), "r"(wd), "r"(w1), "r"(w2), "r"(w3), "r"(rsb + O_BAR + 8 * B_Q2), "r"(lane) : "memory");
      __syncwarp();
      arrive_n(bar0 + 8 * B_Q2, lane == 0, 1);
    }
    {
      uint32_t a[2][8][4];
      uint32_t a_bq = sb + O_B + (lane & 7) * 272 + (lane >> 3) * 16;
      uint4* p_qa = scr->qa + (4 * rk + (warp >> 1)) * 256 + hd * 8 + ((4 * (warp & 1) + tq) ^ (hd & 7));
      PIN(a_bq); PINL(p_qa);
      mbar_wait(bar0 + 8 * (4 + (warp >> 1)));
      const uint32_t ab = sb + 65536 + (warp >> 1) * 16384 + (32 * (warp & 1) + (lane & 15)) * 128;
#pragma unroll
      for (int i = 0; i < 16; i++) ldsm(a[i >> 3][i & 7], ab + (i >> 3) * 2048 + ((i >> 2) & 1) * 8192 + (((2 * (i & 3) + (lane >> 4)) ^ (lane & 7)) << 4));
      arrive_n(bar0 + 8 * (B_EMPTY + 4 + (warp >> 1)), lane == 0, 4 + (dep16(&a[0][0][0]) & sch.zero));
      mbar_wait(bar0 + 8 * B_Q2);
      float d[4][4] = {};
#pragma unroll
      for (int y = 0; y < 4; y++) {
        uint32_t bq[4];
        ldsm(bq, a_bq + 64 * y);
#pragma unroll
        for (int mt = 0; mt < 2; mt++) { mma16(d[2 * mt], a[mt][2 * y], bq[0], bq[1]); mma16(d[2 * mt + 1], a[mt][2 * y + 1], bq[2], bq[3]); }
      }
      float r[4];
#pragma unroll
      for (int i = 0; i < 4; i++) r[i] = (d[i & 2][2 * (i & 1)] + d[i & 2][2 * (i & 1) + 1]) + (d[(i & 2) + 1][2 * (i & 1)] + d[(i & 2) + 1][2 * (i & 1) + 1]);
      tred<2>(r, lane, 2); tred<1>(r, lane, 1);
      const float nb = __shfl_xor_sync(~0u, r[0], 4);
      const uint32_t w0 = (lane >> 3) == (hd & 3) ? pack2t(r[0], nb, par) : pack2(r[0], nb);
      const uint32_t w1 = __shfl_down_sync(~0u, w0, 8), w2 = __shfl_down_sync(~0u, w0, 16), w3 = __shfl_down_sync(~0u, w0, 24);
      if (lane < 4) stx16(p_qa, make_uint4(w0, w1, w2, w3));
      if (warp) nbar_arrive(3, 256); else { nbar(3, 256); CNT_ADD(32 + 32 * rk); }
    }
  } else {
    nbar(1, 288);
    epoch = *(volatile unsigned*)(smem + O_EP);
    par = (epoch + 1) & 1;
    asm volatile("barrier.cluster.wait.acquire.aligned;" ::: "memory");
    mbar_wait(bar0);
  }
  asm volatile("setmaxnreg.inc.sync.aligned.u32 224;");
  uint2* p_rec = scr->rec + ((16 * (warp >> 2) + 2 * (warp & 3) + (g & 1) + 4 * (tq & 2)) * 32 + 4 * rn + (tq & 1)) * 64 + cl * 4 + (g >> 1);
  PINL(p_rec);
  {
    const unsigned inv = par ^ 1;
#pragma unroll
    for (int q = 0; q < 2; q++) { stx8(p_rec + q * 128, make_uint2(inv, 0)); if (cl == 14) stx8(p_rec + q * 128 + 4, make_uint2(0, 0)); }
    if (isA) { if (warp < 2) { stx4(scr->xao + b * 64 + tid, inv); stx4(scr->xab + cl * 256 + (2 * (rn & 3) + warp) * 32 + (rn >> 2) * 16 + (lane >> 1), inv); } }
    else if (f == 0) { stx4(out + 2 * tid, 0); __threadfence(); }
  }
  sb = __shfl_sync(~0u, sb, 0); bar0 = sb + O_BAR;
  const int nt = sch.nt[cls], wg = warp >> 2;
  uint32_t a_z[4];
#pragma unroll
  for (int u = 0; u < 4; u++) {
    const int s3 = (rn - u - (lane >> 1 & 1)) & 3;
    a_z[u] = sb + O_LZ + (s3 + 4 * (lane & 1)) * 4096 + wg * 512 + g * 64 + (((warp & 3) ^ (s3 & 1) ^ (2 * (lane & 1))) << 4);
    PIN(a_z[u]);
  }
  uint32_t z[4][4], a_w = sb + O_HW + warp * 128 + (g & 1) * 64 + (tq & 1) * 8;
  PIN(a_w);
  {
    const float sc = 0.08838834764831845f * 1.4426950408889634f;
    float mrun = -1e30f;
    float o[4][16], sx[16], mref[8];
#pragma unroll
    for (int k = 0; k < 16; k++) { o[0][k] = o[1][k] = o[2][k] = o[3][k] = sx[k] = 0.f; mref[k >> 1] = -1e30f; }
    const int key = 16 * warp + (lane & 15);
    uint32_t a_p = sb + O_P + key * 64 + (((lane >> 4) ^ ((key >> 1) & 3)) << 4);
    uint32_t a_v = sb + wg * 32768 + (8 * (lane >> 4) + (lane & 7)) * 128 + (((2 * (warp & 3) + ((lane >> 3) & 1)) ^ (lane & 7)) << 4);
    const int rot = rn + warp;
    const int qown = wg == (rn >> 2) ? -warp & 3 : -1;
    uint32_t a_own = sb + O_LZ + rn * 4096 + (warp & 3) * 1024 + g * 64 + ((tq ^ (rn & 1) ^ ((rn >> 1) & 2)) << 4);
    PIN(a_own);
    unsigned long long dst[4];
#pragma unroll
    for (int q = 0; q < 4; q++) {
      dst[q] = mapg(a_own, 4 * wg + ((q + rot) & 3));
      PINL(dst[q]);
    }
    unsigned long long a_h = mapg(sb + O_HZ + wg * 1024 + rn * 128 + lane * 4, 2 * (warp & 3));
    unsigned long long a_h1 = mapg(sb + O_HZ + wg * 1024 + rn * 128 + lane * 4, 2 * (warp & 3) + 1);
    PIN(a_p); PIN(a_v); PINL(a_h); PINL(a_h1);
    uint32_t rel = lane < 4 && lane >= 2 * wg ? 2 - (tq >> 1) : 0;
    PIN(rel);
    uint32_t ones[4] = {0x3F803F80u, 0x3F803F80u, 0x3F803F80u, 0x3F803F80u};
    PIN(ones[0]); PIN(ones[1]); PIN(ones[2]); PIN(ones[3]);
    {
      asm volatile("{.reg .pred p; .reg .u32 n; mov.u32 n, 0;\n"
                   "W%=: mbarrier.try_wait.parity.acquire.cluster.shared::cta.b64 p, [%0], 0; add.u32 n, n, 1; setp.lt.and.u32 p, n, 0x100000, !p; @p bra W%=;}"
                   ::"r"(bar0 + 8 * B_LZ) : "memory");
      mbar_wait(bar0 + 8 * B_QF);
      unsigned bad = 0;
#pragma unroll
      for (int k = 0; k < 8; k++) bad |= __float_as_uint(lds4(sb + O_Q + k * 4096 + tid * 16 + (lane >> 3) * 4)) ^ par;
      if (__builtin_expect(__any_sync(~0u, bad & 1), 0)) {
#pragma unroll 1
        for (int k = 0; k < 8; k++) {
          uint4 v;
          POLL { v = ldx16(scr->qa + k * 256 + tid); RETRY(((lane & 16) ? ((lane & 8) ? v.w : v.z) : ((lane & 8) ? v.y : v.x)) ^ par) }
          sts16(sb + O_Q + k * 4096 + tid * 16, v);
        }
        asm volatile("fence.proxy.async.shared::cta;" ::: "memory");
      }
      if (warp >= 4) nbar_arrive(1, 256); else nbar(1, 256);
    }
#pragma unroll 1
    for (int t = 0; t < nt; t++) {
      const int v = v0 + t;
      const uint32_t fb = bar0 + (v & 1) * 32, ph = (v >> 1) & 1, av = a_v + (v & 1) * 65536;
      uint32_t vf[4][4][4], cnt;
      auto landed = [&]() {
        cnt = rel + (dep16(&vf[0][0][0]) & (nt >> 8));
        PIN(cnt);
      };
      if (wg == 0) {
        const uint32_t da = DSC + (v & 1) * 4096, db = DSC + O_Q / 16;
#pragma unroll 1
        for (int j = 0; j < 4; j++) {
          mbar_wait(fb + 8 * j, ph);
          asm volatile("wgmma.fence.sync.aligned;" ::: "memory");
#pragma unroll
          for (int k = 0; k < 8; k++)
            wgmma32<0, 0, HI128, HI128>(sx, da + j * 1024 + (k >> 2) * 512 + (k & 3) * 2, db + j * 512 + (k >> 2) * 256 + (k & 3) * 2, k ? 1 : j);
          asm volatile("wgmma.commit_group.sync.aligned;" ::: "memory");
          if (j == VJ) {
#pragma unroll
            for (int i = 0; i < 16; i++) ldsm_t(vf[i >> 2][i & 3], av + (((i >> 2) + rot) & 3) * 8192 + (i & 3) * 2048);
            nbar(5, 256);
            landed();
          }
        }
      } else {
        nbar_arrive(5, 256);
#pragma unroll 1
        for (int j = 0; j < 2; j++) {
          mbar_wait(fb + 16 + 8 * j, ph);
          if (j) spin_until(clock() + VDLY);
#pragma unroll
          for (int q = 0; q < 4; q++)
            if (((q + rot) & 2) == 2 * j)
#pragma unroll
              for (int k = 0; k < 4; k++) ldsm_t(vf[q][k], av + ((q + rot) & 3) * 8192 + k * 2048);
        }
        cnt = 0;
      }
      wg_wait<0>(sx);
      asm volatile("{.reg .pred p; setp.ne.s32 p, %1, 0; @p mbarrier.arrive.shared::cta.b64 _, [%0], %1;}" ::"r"(fb + 8 * B_EMPTY + 8 * tq), "r"(cnt) : "memory");
#pragma unroll 1
      for (int pass = 0;; pass++) {
        int ex = !(t | pass);
        if (wg == 0 && (t | pass)) {
          uint32_t pk[8];
#pragma unroll
          for (int i = 0; i < 8; i++) pk[i] = pack2(ex2(sx[2 * i] * sc - mref[i & 6]), ex2(sx[2 * i + 1] * sc - mref[(i & 6) + 1]));
          asm volatile("stmatrix.sync.aligned.m8n8.x4.shared.b16 [%0], {%2,%3,%4,%5};\n"
                       "stmatrix.sync.aligned.m8n8.x4.shared.b16 [%1], {%6,%7,%8,%9};"
                       ::"r"(a_p), "r"(a_p ^ 32), "r"(pk[0]), "r"(pk[1]), "r"(pk[2]), "r"(pk[3]), "r"(pk[4]), "r"(pk[5]), "r"(pk[6]), "r"(pk[7]) : "memory");
          const uint32_t mx = __vmaxu2(__vmaxu2(__vmaxu2(pk[0], pk[1]), __vmaxu2(pk[2], pk[3])), __vmaxu2(__vmaxu2(pk[4], pk[5]), __vmaxu2(pk[6], pk[7])));
          ex = max(mx, mx << 16) > (127u + TAU) << 23;
          asm volatile("fence.proxy.async.shared::cta;" ::: "memory");
        }
        asm volatile("{.reg .pred p, q; setp.ne.s32 q, %0, 0; bar.red.or.pred p, 4, 256, q; selp.s32 %0, 1, 0, p;}" : "+r"(ex)::"memory");
        if (!ex || pass) break;
        int ln;
        asm volatile("mov.u32 %0, %%laneid;" : "=r"(ln));
        const uint32_t a_pm = sb + O_SM + ln * 16;
        if (wg == 0) {
          float cm[8];
#pragma unroll
          for (int i = 0; i < 8; i++) cm[i] = fmaxf(sx[2 * (i & 6) + (i & 1)], sx[2 * (i & 6) + (i & 1) + 2]);
          tmax<4>(cm, lane, 16); tmax<2>(cm, lane, 8); tmax<1>(cm, lane, 4);
          sts4(a_pm + warp * 4, cm[0] * sc);
        }
        nbar(4, 256);
        const float4 pm = lds16(a_pm);
        const float mn = u2f(__float_as_uint(fmaxf(fmaxf(fmaxf(pm.x, pm.y), fmaxf(pm.z, pm.w)), mrun)) | 1u), al = ex2(mrun - mn);
        mrun = mn;
#pragma unroll
        for (int i = 0; i < 8; i++) {
          const float a = __shfl_sync(~0u, al, 4 * i + (ln & 3)), aw = wg ? a : 1.f;
          mref[i] = __shfl_sync(~0u, mn, 4 * i + (ln & 3));
#pragma unroll
          for (int e = 0; e < 2; e++) {
            const int k = 2 * (i & 6) + (i & 1) + 2 * e;
            o[0][k] *= a; o[1][k] *= a; o[2][k] *= a; o[3][k] *= a; sx[k] *= aw;
          }
        }
      }
      float hv = mrun;
      if (wg) {
        asm volatile("wgmma.fence.sync.aligned;" ::: "memory");
#pragma unroll
        for (int k = 0; k < 4; k++) wgmma32r(sx, ones, DSC + O_P / 16 + k * 64);
        asm volatile("wgmma.commit_group.sync.aligned;" ::: "memory");
        landed();
        asm volatile("{.reg .pred p; setp.ne.s32 p, %1, 0; @p mbarrier.arrive.shared::cta.b64 _, [%0], %1;}" ::"r"(fb + 8 * B_EMPTY + 8 * tq), "r"(cnt) : "memory");
        wg_wait<0>(sx);
        float lv[4];
#pragma unroll
        for (int j = 0; j < 4; j++) lv[j] = (lane & 4) ? sx[4 * j + 1] : sx[4 * j];
        hv = (lane & 16) ? ((lane & 8) ? lv[3] : lv[2]) : ((lane & 8) ? lv[1] : lv[0]);
      }
      asm volatile("{.reg .pred p; setp.eq.s32 p, %3, %4; @p st.relaxed.cluster.b32 [%0], %1; @p st.relaxed.cluster.b32 [%2], %1;}"
                   ::"l"(a_h), "r"(__float_as_uint(hv) | 1u), "l"(a_h1), "r"(t), "r"(nt - 1) : "memory");
#pragma unroll
      for (int q = 0; q < 4; q++) {
        asm volatile("wgmma.fence.sync.aligned;" ::: "memory");
#pragma unroll
        for (int k = 0; k < 4; k++) wgmma32r(o[q], vf[q][k], DSC + O_P / 16 + k * 64);
        asm volatile("wgmma.commit_group.sync.aligned;" ::: "memory");
        if (q == 3) {
#pragma unroll
          for (int u = 0; u < 4; u++) ldsm_t(z[u], a_z[u] + u * 1024);
        }
        wg_wait<0>(o[q]);
#pragma unroll
        for (int j = 0; j < 2; j++)
          asm volatile("{.reg .pred p, q, r; setp.eq.s32 p, %5, %6; setp.eq.and.s32 q|r, %7, %8, p; @r st.relaxed.cluster.v4.b32 [%0], {%1,%2,%3,%4};\n"
                       "@q st.shared.v4.b32 [%9], {%1,%2,%3,%4};}"
                       ::"l"(dst[q] + j * 512), "r"(pack2t(o[q][8 * j], o[q][8 * j + 1], 1)), "r"(pack2(o[q][8 * j + 2], o[q][8 * j + 3])),
                         "r"(pack2(o[q][8 * j + 4], o[q][8 * j + 5])), "r"(pack2(o[q][8 * j + 6], o[q][8 * j + 7])), "r"(t), "r"(nt - 1),
                         "r"(qown), "r"(q), "r"(a_own + j * 512) : "memory");
      }
    }
  }
  {
    uint32_t wx[4][4];
    mbar_wait(bar0 + 8 * B_WZ);
#pragma unroll
    for (int u = 0; u < 4; u++) {
      uint2 wp;
      asm volatile("ld.shared.v2.u32 {%0, %1}, [%2];" : "=r"(wp.x), "=r"(wp.y) : "r"(a_w + u * 8) : "memory");
      const bool lo = (g >> 1) == (tq >> 1), hi = (g >> 1) == 2 + (tq >> 1);
      wx[u][0] = lo ? wp.x : 0u; wx[u][1] = lo ? wp.y : 0u; wx[u][2] = hi ? wp.x : 0u; wx[u][3] = hi ? wp.y : 0u;
    }
    auto bad = [&]() {
      const unsigned ok = and3(and3(and3(z[0][0], z[0][1], z[0][2]), and3(z[0][3], z[1][0], z[1][1]), and3(z[1][2], z[1][3], z[2][0])),
                               and3(and3(z[2][1], z[2][2], z[2][3]), and3(z[3][0], z[3][1], z[3][2]), z[3][3]), 0x10001u);
      return __any_sync(~0u, g == 0 && ok != 0x10001u);
    };
    POLL {
      if (it_)
#pragma unroll
        for (int u = 0; u < 4; u++) ldsm_t(z[u], a_z[u] + u * 1024);
      if (!bad() || ++it_ >= SPIN_MAX) break;
    }
    float d0[8][4] = {}, d[8][4], r[8];
#pragma unroll
    for (int i = 0; i < 8; i++) mma16(d0[i], wx[i >> 1], z[i >> 1][2 * (i & 1)], z[i >> 1][2 * (i & 1) + 1]);
    POLL {
#pragma unroll
      for (int u = 0; u < 4; u++) ldsm_t(z[u], a_z[u ^ 2] + u * 1024);
#pragma unroll
      for (int i = 0; i < 8; i++) mma16c(d[i], wx[(i >> 1) ^ 2], z[i >> 1][2 * (i & 1)], z[i >> 1][2 * (i & 1) + 1], d0[i]);
      if (!bad() || ++it_ >= SPIN_MAX) break;
    }
#pragma unroll
    for (int i = 0; i < 8; i++) r[i] = (tq & 2) ? ((g & 1) ? d[i][3] : d[i][2]) : ((g & 1) ? d[i][1] : d[i][0]);
#pragma unroll
    for (int q = 0; q < 2; q++) pub8(p_rec + q * 128, pack2t(r[4 * q], r[4 * q + 1], par) | 1u, pack2(r[4 * q + 2], r[4 * q + 3]));
  }
  const int vt = v0 + nt;
  const uint32_t bufa = sb + (vt & 1) * 65536, fulla = bar0 + (vt & 1) * 32, pha = (vt >> 1) & 1, phb = ((vt + 1) >> 1) & 1;
  const uint32_t bufo = sb + ((vt + 1) & 1) * 65536, fullb = bar0 + ((vt + 1) & 1) * 32;
  uint32_t a_rs = sb + O_R + (warp >> 2) * 1024 + (16 * tq + g) * 16 + ((warp + tq) & 3) * 4;
  if (isA) {
    const int row = 16 * (warp & 6) + 8 * (warp & 1) + (lane & 16) + ((lane & 7) >> 1) + 4 * (lane & 1);
    uint32_t ab = bufa + row * 128 + ((((lane >> 3) & 1) ^ (row & 7)) << 4);
    const uint2* pr = scr->rec + (hd * 32 + warp) * 64 + lane;
    uint32_t a_cb = mapa(bar0 + 8 * B_HZ, (warp & 6) + (lane >> 4)), a_c = a_cb - (O_BAR + 8 * B_HZ - O_CTX) + (2 * rn + (warp & 1)) * 64 + tq * 16;
    uint32_t a_rl = sb + O_R + (32 * (warp & 1) + lane) * 16;
    uint32_t ao = bufo + (16 * warp + 8 * (lane >> 4) + (lane & 7)) * 128 + ((((lane >> 3) & 1) ^ (lane & 7)) << 4);
    uint32_t a_cx = sb + O_CTX + (warp >> 1) * 64 + tq * 16 + (warp & 1) * 8, a_ga = sb + O_SM + (320 + posof(tid & 63)) * 4;
    unsigned* p_ao = scr->xao + b * 64 + (tid & 63);
    unsigned* p_ab = scr->xab + cl * 256 + (2 * (rn & 3) + (warp & 1)) * 32 + (rn >> 2) * 16 + (lane >> 1);
    float xv = cl == 0 ? __bfloat162float(x[64 * rn + (tid & 63)]) : 0.f;
    unsigned p2 = lane >= 28 ? 0 : par;
    PIN(ab); PINL(pr); PIN(a_cb); PIN(a_c); PIN(a_rl); PIN(a_rs); PIN(ao); PIN(a_cx); PIN(a_ga); PINL(p_ao); PINL(p_ab); PIN(p2);
    asm volatile("" : "+f"(xv));
    uint32_t aw[4][4][4];
    auto wo = [&](const int j) {
      mbar_wait(fullb + 8 * j, phb);
#pragma unroll
      for (int mt = 0; mt < 4; mt++) ldsm_t(aw[j][mt], (ao + j * 16384) ^ (mt << 5));
    };
    {
      uint32_t a[4][4][4];
      uint2 z[4], y[4] = {};
      float d[4][4] = {}, r[8];
      mbar_wait(fulla, pha);
      POLL {
#pragma unroll
        for (int q = 0; q < 4; q++) z[q] = ldx8(pr + q * 512);
        RETRY(lop_x3(z[0].x, z[1].x, par) | lop_x3(z[2].x, z[3].x, par))
      }
#pragma unroll
      for (int q = 0; q < 4; q++) {
        if (q == 3) {
          mbar_wait(bar0 + 8 * B_G);
          if (lane < 28)
#pragma unroll
            for (int u = 0; u < 4; u++) y[u] = ldx8(pr + u * 512 + 32);
          __syncwarp();
        }
        mbar_wait(fulla + 8 * q, pha);
#pragma unroll
        for (int mt = 0; mt < 4; mt++) ldsm_t(a[q][mt], (ab + q * 16384) ^ (mt << 5));
#pragma unroll
        for (int mt = 0; mt < 4; mt++) mma16(d[mt], a[q][mt], z[q].x, z[q].y);
      }
      mbar_wait(bar0 + 8 * B_W);
      const float4 W = lds16(sb + O_SM + (384 + 4 * tq) * 4);
#pragma unroll
      for (int i = 0; i < 8; i++) { r[i] = W.x * d[i >> 1][2 * (i & 1)] + W.y * d[i >> 1][2 * (i & 1) + 1]; asm volatile("" : "+f"(r[i])); }
#pragma unroll
      for (int j = 0; j < NPE; j++) wo(j);
      POLL {
        if (it_)
#pragma unroll
          for (int u = 0; u < 4; u++) y[u] = ldx8(pr + u * 512 + 32);
#pragma unroll
        for (int mt = 0; mt < 4; mt++) d[mt][0] = d[mt][1] = d[mt][2] = d[mt][3] = 0.f;
#pragma unroll
        for (int q = 0; q < 4; q++)
#pragma unroll
          for (int mt = 0; mt < 4; mt++) mma16(d[mt], a[q][mt], y[q].x, y[q].y);
        RETRY(or3(lop_x3(y[0].x, y[1].x, p2), lop_x3(y[2].x, y[3].x, p2), 0))
      }
#pragma unroll
      for (int i = 0; i < 8; i++) r[i] = W.w * d[i >> 1][2 * (i & 1) + 1] + (W.z * d[i >> 1][2 * (i & 1)] + r[i]);
      tred<4>(r, lane, 2); tred<2>(r, lane, 1);
      sts4(a_rs, r[0]); sts4(a_rs + 128, r[1]);
      nbar(1, 256);
      send32(a_c, a_cb, sum8(a_rl), lane);
    }
    {
#pragma unroll
      for (int j = NPE; j < NPO; j++) wo(j);
      uint2 c[4];
      mbar_wait(bar0 + 8 * B_HZ);
#pragma unroll
      for (int j = 0; j < 4; j++) asm volatile("ld.shared.v2.u32 {%0, %1}, [%2];" : "=r"(c[j].x), "=r"(c[j].y) : "r"(a_cx + j * 256) : "memory");
      float d[4][4] = {};
#pragma unroll
      for (int j = 0; j < 4; j++) {
        if (j + 1 >= NPO && j < 3) wo(j + 1);
#pragma unroll
        for (int mt = 0; mt < 4; mt++) mma16(d[mt], aw[j][mt], c[j].x, c[j].y);
      }
      const float r0 = (tq & 2) ? ((tq & 1) ? d[3][0] : d[2][0]) : ((tq & 1) ? d[1][0] : d[0][0]);
      const float r1 = (tq & 2) ? ((tq & 1) ? d[3][2] : d[2][2]) : ((tq & 1) ? d[1][2] : d[0][2]);
      sts4(a_rs + 2048, r0); sts4(a_rs + 2048 + 128, r1);
      if (warp >= 2) nbar_arrive(2, 256);
      else {
        mbar_wait(bar0 + 8 * B_TAB);
        const float gav = lds4(a_ga);
        nbar(2, 256);
        const float t = gav * sum8(a_rl + 2048) + xv;
        asm volatile("{.reg .pred p; setp.eq.s32 p, %2, 0; @p red.relaxed.gpu.global.xor.b32 [%0], %1;}"
                     ::"l"(p_ab), "r"(pack2t(t, __shfl_down_sync(~0u, t, 1), par) | 1u), "r"(lane & 1) : "memory");
        pub4(p_ao, __float_as_uint(t) | 1u);
      }
    }
  } else {
    uint32_t af[4][4][4];
    uint32_t ab = bufa + (32 * warp + 8 * (lane >> 4) + (lane & 7)) * 64 + ((((lane >> 3) & 1) ^ ((lane >> 1) & 3)) << 4);
    uint32_t a_d = bufo + (8 * (lane >> 4) + (lane & 7)) * 128 + (((2 * (warp & 3) + ((lane >> 3) & 1)) ^ (lane & 7)) << 4);
    uint32_t a_rl = sb + O_R + lane * 16, a_st = sb + O_SM + (352 + 8 * (lane >> 4) + warp) * 4;
    const unsigned* pa = scr->xab + tid;
    uint32_t a_hb = mapa(bar0 + 8 * B_HZ, 2 * (warp & 3) + (lane >> 4)), a_h = a_hb - (O_BAR + 8 * B_HZ - O_CTX) + rn * 64 + tq * 16;
    PIN(a_hb); PIN(a_h);
    const int col = 64 * rn + 16 * (warp & 3) + 8 * (tq & 1) + g;
    uint32_t a_hl = sb + O_CTX + tq * 16;
    const unsigned* px = scr->xao + (tq & 2) * 1024 + col;
    bf16* po = out + col;
    PIN(ab); PIN(a_d); PIN(a_rl); PINL(pa); PIN(a_rs); PIN(a_st); PINL(po); PIN(a_hl); PINL(px);
    mbar_wait(bar0 + 8 * B_TAB);
    uint2 cf;
    uint2 bb[4];
    unsigned gbw;
    POLL {
      unsigned bad = 0;
      cf = ldx8(scr->xm + 1024 + (lane & 16) * 16 + 32 * warp + posof(2 * (lane & 15)));
#pragma unroll
      for (int s = 0; s < 4; s++) {
        const uint4 w = ldx16(scr->xm + 1024 - (g & 1) * 512 + 256 * (s >> 1) + 32 * warp + 16 * (s & 1) + 4 * tq);
        bb[s] = make_uint2(__byte_perm(w.x, w.y, 0x7632), __byte_perm(w.z, w.w, 0x7632));
        bad = or3(bad, lop_x3(w.x, w.y, par), lop_x3(w.z, w.w, par));
      }
      gbw = ldx4(scr->xm + 1536 + posof(col));
      RETRY(or3(bad, lop_x3(cf.x, cf.y, par), gbw ^ par))
    }
    const float gbv = bfhi(gbw);
    float e[4][4] = {};
    unsigned v[8];
    auto item = [&](const int it) {
      mbar_wait(fulla + 8 * it, pha);
#pragma unroll
      for (int i = 0; i < 4; i++) ldsm_t(af[it][i], (ab + it * 16384 + (i >> 1) * 1024) ^ ((i & 1) << 5));
    };
    auto item_mma = [&](const int it) {
#pragma unroll
      for (int i = 0; i < 4; i++) mma16(e[2 * (it & 1) + (i & 1)], af[it][i], bb[(it & 2) + (i >> 1)].x, bb[(it & 2) + (i >> 1)].y);
    };
    unsigned t3 = sch.wt;
    PIN(t3);
    item(0); item_mma(0); item(1); item_mma(1);
    mbar_wait(bar0 + 8 * B_G);
#pragma unroll
    for (int i = 0; i < 8; i++) v[i] = ldx4(pa + i * 256);
    t3 += clock();
    uint32_t have2, have3 = 0;
    do have2 = mbar_test(fulla + 16, pha); while (!have2 && (int)((unsigned)clock() - t3) < 0);
    if (have2) {
      item(2); item_mma(2);
      do have3 = mbar_test(fulla + 24, pha); while (!have3 && (int)((unsigned)clock() - t3) < 0);
      if (have3) { item(3); item_mma(3); }
    }
    float y0, y1, df[4][4], st[2];
    uint32_t bz[4][2] = {};
    auto mm = [&](const int it, const int i) { mma16(df[2 * (it & 1) + (i & 1)], af[it][i], bz[(it & 2) + (i >> 1)][0], bz[(it & 2) + (i >> 1)][1]); };
    POLL {
      if (it_)
#pragma unroll
        for (int i = 0; i < 8; i++) v[i] = ldx4(pa + i * 256);
      y0 = ((bflo(v[0]) + bflo(v[1])) + (bflo(v[2]) + bflo(v[3]))) + ((bflo(v[4]) + bflo(v[5])) + (bflo(v[6]) + bflo(v[7])));
      y1 = ((bfhi(v[0]) + bfhi(v[1])) + (bfhi(v[2]) + bfhi(v[3]))) + ((bfhi(v[4]) + bfhi(v[5])) + (bfhi(v[6]) + bfhi(v[7])));
      const uint32_t zb = pack2(y0 * u2f(cf.x), y1 * u2f(cf.y));
#pragma unroll
      for (int s = 0; s < 4; s++) {
        const uint32_t w = __shfl_sync(~0u, zb, 8 * s + (lane & 7));
        bz[s][0] = (lane & 4) ? 0u : w; bz[s][1] = (lane & 4) ? w : 0u;
      }
      st[0] = y0 + y1; st[1] = y0 * y0 + y1 * y1;
      tred<1>(st, lane, 16);
#pragma unroll
      for (int i = 0; i < 4; i++) df[i][0] = df[i][1] = df[i][2] = df[i][3] = 0.f;
      mm(0, 0); mm(0, 1); mm(1, 0); mm(1, 1);
      st[0] += shx(st[0], 8);
      mm(0, 2); mm(0, 3); mm(1, 2); mm(1, 3);
      RETRY(or3(or3(lop_x3(v[0], v[1], par), lop_x3(v[2], v[3], par), lop_x3(v[4], v[5], par)), lop_x3(v[6], v[7], par), 0))
    }
    unsigned xq[4];
    if (wg == 0)
#pragma unroll
      for (int i = 0; i < 4; i++) xq[i] = ldx4(px + i * 512);
    if (have2) { mm(2, 0); mm(2, 1); mm(2, 2); mm(2, 3); }
    st[0] += shx(st[0], 4);
    st[0] += shx(st[0], 2);
    st[0] += shx(st[0], 1);
    sts4(a_st, st[0]);
    __syncwarp();
    arrive_n(bar0 + 8 * B_ST, lane == 0, 1);
    if (!have2) { item(2); item_mma(2); mm(2, 0); mm(2, 1); mm(2, 2); mm(2, 3); }
    if (!have3) { item(3); item_mma(3); }
    mm(3, 0); mm(3, 1); mm(3, 2); mm(3, 3);
    mbar_wait(bar0 + 8 * B_ST);
    float mean, rstd;
    {
      float4 u[4];
#pragma unroll
      for (int i = 0; i < 4; i++) u[i] = lds16(sb + O_SM + (352 + 4 * i) * 4);
      mean = (((u[0].x + u[0].y) + (u[0].z + u[0].w)) + ((u[1].x + u[1].y) + (u[1].z + u[1].w))) * (1.f / 512.f);
      const float sq = (((u[2].x + u[2].y) + (u[2].z + u[2].w)) + ((u[3].x + u[3].y) + (u[3].z + u[3].w))) * (1.f / 512.f);
      asm("rsqrt.approx.ftz.f32 %0, %1;" : "=f"(rstd) : "f"(fmaxf(sq - mean * mean, 0.f) + 1e-5f));
    }
    float A[4], r[4];
#pragma unroll
    for (int i = 0; i < 4; i++) {
      A[i] = (tq & 2) ? ((tq & 1) ? e[3][i] : e[2][i]) : ((tq & 1) ? e[1][i] : e[0][i]);
      r[i] = (tq & 2) ? ((tq & 1) ? df[3][i] : df[2][i]) : ((tq & 1) ? df[1][i] : df[0][i]);
    }
    sts4(a_rs, rstd * (r[0] + r[1]) + (A[1] - rstd * mean * A[0])); sts4(a_rs + 128, rstd * (r[2] + r[3]) + (A[3] - rstd * mean * A[2]));
    nbar(1, 256);
    if (wg) {
      const float4 g0 = lds16(a_rl), g1 = lds16(a_rl + 1024), u0 = lds16(a_rl + 512), u1 = lds16(a_rl + 1536);
      const float gg = bfr(((g0.x + g0.y) + (g0.z + g0.w)) + ((g1.x + g1.y) + (g1.z + g1.w)));
      const float uu = bfr(((u0.x + u0.y) + (u0.z + u0.w)) + ((u1.x + u1.y) + (u1.z + u1.w)));
      const float hh = bfr(gg * rcp(1.f + ex2(gg * (-2.302208198f - 0.1029432397f * gg * gg)))) * uu;
      send32(a_h, a_hb, hh, lane);
    } else {
      uint32_t ad[16][4];
      spin_until(clock() + FDLY);
#pragma unroll
      for (int j = 0; j < 2; j++) {
        mbar_wait(fullb + 8 * j, phb);
#pragma unroll
        for (int i = 0; i < 8; i++) ldsm_t(ad[8 * j + i], a_d + (8 * j + i) * 2048);
      }
      POLL {
        if (it_)
#pragma unroll
          for (int i = 0; i < 4; i++) xq[i] = ldx4(px + i * 512);
        RETRY(lop_x3(xq[0], xq[1], par) | lop_x3(xq[2], xq[3], par))
      }
      float x7 = (u2f(xq[0]) + u2f(xq[1])) + (u2f(xq[2]) + u2f(xq[3]));
      x7 = (x7 + __shfl_xor_sync(~0u, x7, 2)) * (1.f / 7.f);
      uint4 hb[8];
      mbar_wait(bar0 + 8 * B_HZ);
#pragma unroll
      for (int i = 0; i < 8; i++) { const float4 q = lds16(a_hl + i * 64); hb[i] = *(const uint4*)&q; }
      float dd[4][4] = {};
#pragma unroll
      for (int i = 0; i < 8; i++) { mma16(dd[(2 * i) & 3], ad[2 * i], hb[i].x, hb[i].y); mma16(dd[(2 * i + 1) & 3], ad[2 * i + 1], hb[i].z, hb[i].w); }
      const float t = gbv * ((tq & 1) ? (dd[0][2] + dd[1][2]) + (dd[2][2] + dd[3][2]) : (dd[0][0] + dd[1][0]) + (dd[2][0] + dd[3][0])) + x7;
      asm volatile("{.reg .pred p; setp.eq.s32 p, %2, 0; @p red.relaxed.gpu.global.add.noftz.bf16x2 [%0], %1;}"
                   ::"l"(po), "r"(pack2(t, __shfl_down_sync(~0u, t, 4))), "r"(lane & 6) : "memory");
      if (f == 0 && tid == 0) stx4(&scr->cnt[0], epoch + 1);
    }
  }
}

static void make_sched(Sched& s) {
  const char* order = "FFAAbcFmmvog..d";
  const double dt = 5010 * 1e-3, dth = 4850 * 1e-3;
  const int nbig = NBIG;
  s.zero = 0; s.dth = (unsigned)(dth * 256 + 0.5);
  double t = 512 * dth + 80;
  int tile = 0, jm = 0;
  for (int i = 0; i < 3; i++) s.nr[i] = s.nt[i] = 0;
  auto add = [&](int c, int type, double step, int win, int b0, int tl) {
    s.r[c][s.nr[c]++] = make_uint2((unsigned)(t + 0.5) | (unsigned)(step + 0.5) << 16, type | win << 4 | (b0 + 64) << 8 | tl << 16);
    if (type == T_KV) s.nt[c]++;
  };
  const int w1 = 6, w2 = 4, wt = 6;
  for (const char* p = order; *p; p++) {
    const char c = *p;
    if (c == 'v' || c == 'o' || c == 'm') {
      const int ty = c == 'v' ? T_UV : c == 'o' ? T_WO : T_MOD;
      const double d = (c == 'm' ? 5010 : c == 'v' ? 5500 : 5500) * 1e-3;
      add(0, ty, 64 * d, wt, 0, c == 'm' ? jm : 0); add(1, ty, 64 * d, wt, 0, c == 'm' ? jm : 0);
      t += (c == 'm' ? 64 : 256) * d; jm += c == 'm';
    } else if (c == 'g' || c == 'd') {
      const double d = (c == 'g' ? 5500 : 5500) * 1e-3;
      add(2, c == 'g' ? T_GU : T_DN, 56 * d, wt, 64, 0);
      t += (c == 'g' ? 224 : 112) * d;
    } else if (c == '.') t += 100;
    else if (c == '-') t -= 100;
    else {
      const int na = c == 'F' ? 0 : c == 'C' || c == 'c' || c == 'a' ? nbig : 64, nf = c == 'A' || c == 'a' ? 0 : 56, n = na + nf;
      const int w = na && nf ? w2 : w1;
      const bool ff = c == 'b' || c == 'c';
      const int cf = c == 'c' ? 60 : 0, ca = cf * 7 / 5;
      t += 3 * ca;
      if (na) add(0, T_KV, n * dt - ca, w, ff ? -56 : 0, tile);
      t -= 3 * ca;
      if (na == 64) add(1, T_KV, n * dt, w, ff ? -56 : 0, tile);
      if (nf) add(2, T_KV, n * dt - cf, w, ff ? 64 : 64 - na, tile);
      tile += n; t += 4 * n * dt;
      s.t4 = (unsigned)t + 600;
    }
  }
  s.dt = (unsigned)(dt * 256 + 0.5); s.d4 = 1530 | 1200 << 16; s.d6 = 3160; s.wt = 250;
}

static void launch(void* const* d_in, void* d_out) {
  static TMaps tms;
  static Sched sch;
  static bool init = false;
  static void* scr = nullptr;
  if (!init) {
    void* fn = nullptr; cudaDriverEntryPointQueryResult qr;
    cudaGetDriverEntryPoint("cuTensorMapEncodeTiled", &fn, cudaEnableDefault, &qr);
    EncFn f = (EncFn)fn;
    const CUtensorMapSwizzle S64 = CU_TENSOR_MAP_SWIZZLE_64B, S128 = CU_TENSOR_MAP_SWIZZLE_128B;
    const CUtensorMapL2promotion P256 = CU_TENSOR_MAP_L2_PROMOTION_L2_256B;
    enc3d(f, &tms.m[0], d_in[2], 64, 512, 64, 8192, 128, 64, 128, 1, S128, CU_TENSOR_MAP_L2_PROMOTION_L2_128B);
    enc3d(f, &tms.m[1], d_in[3], 64, 512, 64, 8192, 128, 64, 64, 2, S128, P256);
    enc3d(f, &tms.m[2], d_in[1], 64, SK, 8, 1024, 128, 64, 64, 2, S128, P256);
    enc3d(f, &tms.m[3], d_in[11], 3072, 256, 2, 6144, 256 * 6144, 32, 256, 1, S64, CU_TENSOR_MAP_L2_PROMOTION_L2_128B);
    enc3d(f, &tms.m[4], d_in[4], 64, 512, 64, 8192, 128, 64, 128, 1, S128, CU_TENSOR_MAP_L2_PROMOTION_L2_128B);
    enc3d(f, &tms.m[5], d_in[5], 512, 128, 32, 1024, 128 * 1024, 64, 128, 1, S128, CU_TENSOR_MAP_L2_PROMOTION_L2_128B);
    enc3d(f, &tms.m[6], d_in[7], 1792, 256, 2, 3584, 256 * 3584, 32, 256, 1, S64, CU_TENSOR_MAP_L2_PROMOTION_L2_128B);
    enc3d(f, &tms.m[7], d_in[8], 1792, 256, 2, 3584, 256 * 3584, 32, 256, 1, S64, CU_TENSOR_MAP_L2_PROMOTION_L2_128B);
    enc3d(f, &tms.m[8], d_in[9], 512, 128, 14, 1024, 128 * 1024, 64, 128, 1, S128, CU_TENSOR_MAP_L2_PROMOTION_L2_128B);
    cudaFuncSetAttribute(fused_kernel, cudaFuncAttributeMaxDynamicSharedMemorySize, SMEM9);
    cudaGetSymbolAddress(&scr, g_scr);
    make_sched(sch);
    init = true;
  }
  fused_kernel<<<NCTA9, 384, SMEM9>>>((const bf16*)d_in[0], (const bf16*)d_in[10], (const bf16*)d_in[11], (bf16*)d_out, (Scratch*)scr, sch, tms);
}

static bool fits() {
  cudaFuncSetAttribute(fused_kernel, cudaFuncAttributeMaxDynamicSharedMemorySize, SMEM9);
  cudaLaunchConfig_t cfg = {};
  cfg.gridDim = dim3(NCTA9); cfg.blockDim = dim3(384); cfg.dynamicSmemBytes = SMEM9;
  cudaLaunchAttribute at[1];
  at[0].id = cudaLaunchAttributeClusterDimension; at[0].val.clusterDim.x = 8; at[0].val.clusterDim.y = 1; at[0].val.clusterDim.z = 1;
  cfg.attrs = at; cfg.numAttrs = 1;
  int n = 0;
  if (cudaOccupancyMaxActiveClusters(&n, fused_kernel, &cfg) != cudaSuccess) { (void)cudaGetLastError(); return false; }
  return n >= NCTA9 / 8;
}
}
#undef BAR_ARM
#undef BAR_ARRIVE
#undef BAR_INIT
#undef B_EM
#undef B_EMPTY
#undef B_FM
#undef B_FULL
#undef B_G
#undef B_G2
#undef B_H
#undef B_HZ
#undef B_LZ
#undef B_Q2
#undef B_QF
#undef B_ST
#undef B_TAB
#undef B_W
#undef B_WZ
#undef CNT_ADD
#undef DSC
#undef FDLY
#undef HI128
#undef HI64
#undef LANE0
#undef NBIG
#undef NCTA9
#undef NPE
#undef NPO
#undef NSL
#undef O_B
#undef O_BAR
#undef O_CTX
#undef O_DBG
#undef O_EP
#undef O_HW
#undef O_HZ
#undef O_LZ
#undef O_P
#undef O_Q
#undef O_R
#undef O_SILU
#undef O_SM
#undef O_X
#undef PIN
#undef PINL
#undef POLL
#undef QN
#undef RETRY
#undef SK
#undef SMEM9
#undef SMEM_BASE
#undef SPIN_MAX
#undef TAU
#undef VDLY
#undef VJ
#undef X16
#undef fbits

namespace v8 {
typedef __nv_bfloat16 bf16;
#define NCTA 128
#define SK 32768
#define SLOT 32768
#define NSLOT 6
#define OFF_WQ (2 * SLOT)
#define OFF_WUK (4 * SLOT)
#define OFF_Q 196608
#define OFF_P (OFF_Q + 16384)
#define OFF_B (OFF_P + 4096)
#define OFF_R4 (OFF_B + 2304)
#define OFF_SILU (OFF_R4 + 4096)
#define OFF_RA (OFF_SILU + 1024)
#define OFF_SM (OFF_RA + 1024)
#define OFF_BP (OFF_SM + 1792)
#define OFF_CO (OFF_BP + 1024)
#define OFF_BAR (OFF_CO + 1280)
#define OFF_MASK (OFF_BAR + 512)
#define OFF_DBG (OFF_MASK + 16)
#define SMEM_BYTES (OFF_DBG + 128)
#define OFF_MOD OFF_Q
#define OFF_UV (4 * SLOT)
#define OFF_O (5 * SLOT)
#define OFF_G 0
#define OFF_U 16384
#define OFF_D SLOT
#define OFF_XO (OFF_D + 16384)
#define FB_UK 4
#define FB_KV 6
#define FB_MOD 22
#define FB_UV 23
#define FB_O 25
#define FB_G 27
#define FB_D 29
#define EB 30
#define QB 50
#define XB 51
#define SPIN_MAX (1 << 20)
#define BACKOFF 40
#define RATE_NS 652
#define RATE_T0 200
#define RATE_TL 300
#define WINS 0x3222333
#define KVWIN 4
#define RATE_H 650
#define RATE_E 650
#define SMUL 9
#define NPRE0 1
#define NPRE1 3
#define HWIN 4
#define EWIN 3
#define WTEST 450
#define DLY5 650
#define DLY6 600
#define DLY7 600
#define P12(a, b, c, d, e, f, g, h, i, j, k, l) ((unsigned long long)(a) | (b) << 5 | (c) << 10 | (d) << 15 | (e) << 20 | (f) << 25 | \
  (unsigned long long)(g) << 30 | (unsigned long long)(h) << 35 | (unsigned long long)(i) << 40 | (unsigned long long)(j) << 45 | \
  (unsigned long long)(k) << 50 | (unsigned long long)(l) << 55)
#define ORDER0 P12(0, 1, 2, 3, 4, 5, 16, 6, 7, 8, 9, 10)
#define ORDER1 P12(11, 12, 13, 14, 15, 17, 18, 19, 20, 23, 21, 22)
#define TAIL_K 17
#define RS 16
template <int N> struct IC { static constexpr int value = N; };
struct TMaps { CUtensorMap m[9]; };

struct __align__(128) Scratch {
  uint4 xo[128 * 64 * RS];
  uint2 ml[32 * 64];
  unsigned h[8 * 256];
  unsigned qa[32 * 256];
  unsigned xc[128 * 64];
  unsigned xao[8 * 512];
  unsigned xf[112 * 512];
  unsigned xm[2048];
  unsigned cnt[5 * 32];
};
__device__ Scratch g_scr;
#define g_xo scr->xo
#define g_ml scr->ml
#define g_h scr->h
#define g_qa scr->qa
#define g_xc scr->xc
#define g_xao scr->xao
#define g_xf scr->xf
#define g_xm scr->xm
#define g_epoch scr->cnt[0]

__device__ __forceinline__ uint32_t s2u(const void* p) { return (uint32_t)__cvta_generic_to_shared(p); }
__device__ __forceinline__ float bflo(uint32_t u) { return __uint_as_float(u << 16); }
__device__ __forceinline__ float bfhi(uint32_t u) { return __uint_as_float(u & 0xffff0000u); }
__device__ __forceinline__ float u2f(uint32_t u) { return __uint_as_float(u); }
__device__ __forceinline__ void fma8(float* acc, uint4 v, float s) {
  acc[0] += s * bflo(v.x); acc[1] += s * bfhi(v.x); acc[2] += s * bflo(v.y); acc[3] += s * bfhi(v.y);
  acc[4] += s * bflo(v.z); acc[5] += s * bfhi(v.z); acc[6] += s * bflo(v.w); acc[7] += s * bfhi(v.w);
}
__device__ __forceinline__ uint32_t pack2(float a, float b) {
  __nv_bfloat162 p = __floats2bfloat162_rn(a, b); return *(uint32_t*)&p;
}
__device__ __forceinline__ float bfr(float v) { return bfhi(pack2(v, v)); }
__device__ __forceinline__ float silu_bf(float c) { return bfr(__fdividef(c, 1.f + __expf(-c))); }
#define fbits(v) ((__float_as_uint(v) & ~1u) | par)
__device__ __forceinline__ uint32_t pack2t(float a, float b, unsigned par) {
  const uint32_t ua = ((__float_as_uint(a) + ((par ^ 1) << 16)) & 0xFFFE0000u) | (par << 16);
  return __byte_perm(ua, pack2(b, b), 0x7632);
}
__device__ __forceinline__ void nbar(int id, int n) { asm volatile("bar.sync %0, %1;" ::"r"(id), "r"(n) : "memory"); }
__device__ __forceinline__ void nbar_arrive(int id, int n) { asm volatile("bar.arrive %0, %1;" ::"r"(id), "r"(n) : "memory"); }
__device__ __forceinline__ uint4 ldc16(const void* p) {
  uint4 v; asm volatile("ld.relaxed.cta.global.v4.u32 {%0,%1,%2,%3}, [%4];" : "=r"(v.x), "=r"(v.y), "=r"(v.z), "=r"(v.w) : "l"(p) : "memory"); return v;
}
__device__ __forceinline__ unsigned ldc4(const void* p) {
  unsigned v; asm volatile("ld.relaxed.cta.global.u32 %0, [%1];" : "=r"(v) : "l"(p) : "memory"); return v;
}
__device__ __forceinline__ uint4 ldx16(const void* p) {
  uint4 v; asm volatile("ld.relaxed.gpu.global.v4.u32 {%0,%1,%2,%3}, [%4];" : "=r"(v.x), "=r"(v.y), "=r"(v.z), "=r"(v.w) : "l"(p) : "memory"); return v;
}
__device__ __forceinline__ unsigned ldx4(const void* p) {
  unsigned v; asm volatile("ld.relaxed.gpu.global.u32 %0, [%1];" : "=r"(v) : "l"(p) : "memory"); return v;
}
__device__ __forceinline__ unsigned long long ldx64(const void* p) {
  unsigned long long v; asm volatile("ld.relaxed.gpu.global.u64 %0, [%1];" : "=l"(v) : "l"(p) : "memory"); return v;
}
__device__ __forceinline__ void stx16(void* p, uint4 v) {
  asm volatile("st.relaxed.gpu.global.v4.u32 [%0], {%1,%2,%3,%4};" ::"l"(p), "r"(v.x), "r"(v.y), "r"(v.z), "r"(v.w) : "memory");
}
__device__ __forceinline__ void stx8(void* p, uint2 v) { asm volatile("st.relaxed.gpu.global.v2.u32 [%0], {%1,%2};" ::"l"(p), "r"(v.x), "r"(v.y) : "memory"); }
__device__ __forceinline__ void stx4(void* p, unsigned v) { asm volatile("st.relaxed.gpu.global.u32 [%0], %1;" ::"l"(p), "r"(v) : "memory"); }
__device__ __forceinline__ unsigned lop_x3(unsigned a, unsigned b, unsigned c) {
  unsigned d; asm("lop3.b32 %0, %1, %2, %3, 0x7E;" : "=r"(d) : "r"(a), "r"(b), "r"(c)); return d; }
#define X16(v) (lop_x3(v.x, v.y, par) | lop_x3(v.z, v.w, par))
#define X8(v) lop_x3(v.x, v.y, par)
#define RETRY(bad) if (!__any_sync(~0u, (bad) & 1) || ++it_ >= SPIN_MAX) break; __nanosleep(BACKOFF);
#define POLL _Pragma("unroll 1") for (int it_ = 0;;)
__device__ __forceinline__ void mbar_wait(uint32_t bar) {
  uint32_t ok; int it = 0;
  do {
    asm volatile("{.reg .pred p; mbarrier.try_wait.parity.shared::cta.b64 p, [%1], 0; selp.u32 %0,1,0,p;}"
                 : "=r"(ok) : "r"(bar) : "memory");
  } while (!ok && ++it < SPIN_MAX);
}
__device__ __forceinline__ float ex2(float v) { float r; asm("ex2.approx.ftz.f32 %0, %1;" : "=f"(r) : "f"(v)); return r; }
__device__ __forceinline__ float rcp(float v) { float r; asm("rcp.approx.ftz.f32 %0, %1;" : "=f"(r) : "f"(v)); return r; }
__device__ __forceinline__ void mma16(float* d, const uint32_t* a, uint32_t b0, uint32_t b1) {
  asm volatile("mma.sync.aligned.m16n8k16.row.col.f32.bf16.bf16.f32 {%0,%1,%2,%3}, {%4,%5,%6,%7}, {%8,%9}, {%0,%1,%2,%3};"
               : "+f"(d[0]), "+f"(d[1]), "+f"(d[2]), "+f"(d[3]) : "r"(a[0]), "r"(a[1]), "r"(a[2]), "r"(a[3]), "r"(b0), "r"(b1));
}
__device__ __forceinline__ float4 lds16(uint32_t a) {
  float4 v; asm volatile("ld.shared.v4.f32 {%0,%1,%2,%3}, [%4];" : "=f"(v.x), "=f"(v.y), "=f"(v.z), "=f"(v.w) : "r"(a) : "memory"); return v;
}
__device__ __forceinline__ void ldsm_t(uint32_t* r, uint32_t a) {
  asm volatile("ldmatrix.sync.aligned.m8n8.x4.trans.shared.b16 {%0,%1,%2,%3}, [%4];" : "=r"(r[0]), "=r"(r[1]), "=r"(r[2]), "=r"(r[3]) : "r"(a) : "memory");
}
__device__ __forceinline__ void ldsm(uint32_t* r, uint32_t a) {
  asm volatile("ldmatrix.sync.aligned.m8n8.x4.shared.b16 {%0,%1,%2,%3}, [%4];" : "=r"(r[0]), "=r"(r[1]), "=r"(r[2]), "=r"(r[3]) : "r"(a) : "memory");
}
template <int N>
__device__ __forceinline__ void tred(float* a, int lane, int m) {
  const bool hi = lane & m;
#pragma unroll
  for (int i = 0; i < N; i++) {
    float send = hi ? a[i] : a[i + N], keep = hi ? a[i + N] : a[i];
    a[i] = keep + __shfl_xor_sync(~0u, send, m);
  }
}
template <int N>
__device__ __forceinline__ void tmax(float* a, int lane, int m) {
  const bool hi = lane & m;
#pragma unroll
  for (int i = 0; i < N; i++) {
    float send = hi ? a[i] : a[i + N], keep = hi ? a[i + N] : a[i];
    a[i] = fmaxf(keep, __shfl_xor_sync(~0u, send, m));
  }
}
__device__ __forceinline__ void arrive2(uint32_t bar, uint32_t rbar, bool local, bool remote) {
  asm volatile("{.reg .pred p, q; setp.ne.s32 p, %2, 0; setp.ne.s32 q, %3, 0; @p mbarrier.arrive.shared::cta.b64 _, [%0];\n"
               "@q mbarrier.arrive.relaxed.cluster.shared::cluster.b64 _, [%1];}" ::"r"(bar), "r"(rbar), "r"((int)local), "r"((int)remote) : "memory");
}
__device__ __forceinline__ unsigned long long stream_policy() {
  unsigned long long p;
  asm volatile("createpolicy.fractional.L2::evict_first.b64 %0, 1.0;" : "=l"(p));
  return p;
}
__device__ __forceinline__ void tma3d(uint32_t dst, const CUtensorMap* tm, uint32_t bar, int c0, int c1, int c2) {
  asm volatile("cp.async.bulk.tensor.3d.shared::cluster.global.mbarrier::complete_tx::bytes.L2::cache_hint [%0], [%1, {%3, %4, %5}], [%2], %6;"
               ::"r"(dst), "l"(tm), "r"(bar), "r"(c0), "r"(c1), "r"(c2), "l"(stream_policy()) : "memory");
}
__device__ __forceinline__ void st_async2(uint32_t dst, uint32_t bar, float v0, float v1) {
  asm volatile("st.async.shared::cluster.mbarrier::complete_tx::bytes.v2.f32 [%0], {%1, %2}, [%3];" ::"r"(dst), "f"(v0), "f"(v1), "r"(bar) : "memory");
}
__device__ __forceinline__ void st_pair(int mode, uint32_t dst, uint32_t bar, float v0, float v1) {
  asm volatile("{.reg .pred p, q; setp.eq.s32 p, %4, 1; setp.eq.s32 q, %4, 2; @p st.shared.v2.f32 [%0], {%1, %2};\n"
               "@q st.async.shared::cluster.mbarrier::complete_tx::bytes.v2.f32 [%0], {%1, %2}, [%3];}"
               ::"r"(dst), "f"(v0), "f"(v1), "r"(bar), "r"(mode) : "memory");
}
__device__ __forceinline__ void spin_until(unsigned t) { while ((int)((unsigned)clock() - t) < 0) {} }
__device__ __forceinline__ unsigned wait_until(unsigned t) {
  unsigned now;
  for (;;) {
    asm volatile("mov.u32 %0, %%globaltimer_lo;" : "=r"(now));
    if ((int)(now - t) >= 0) break;
  }
  return now;
}
#define PIN(x) asm volatile("" : "+r"(x))
#define PINL(x) asm volatile("" : "+l"(x))
#define BAR_ARRIVE(i) asm volatile("mbarrier.arrive.shared::cta.b64 _, [%0];" ::"r"(bar0 + 8 * (i)) : "memory")
#define CNT_ADD(c) asm volatile("red.relaxed.gpu.global.add.u32 [%0], 1;" ::"l"(scr->cnt + (c)) : "memory")
#define BAR_INIT(i, cnt) asm volatile("mbarrier.init.shared::cta.b64 [%0], %1;" ::"r"(bar0 + 8 * (i)), "r"(cnt) : "memory")
#define BAR_ARM(i, bytes) asm volatile("mbarrier.arrive.expect_tx.shared::cta.b64 _, [%0], %1;" ::"r"(bar0 + 8 * (i)), "r"(bytes) : "memory")

__device__ __forceinline__ void tail(unsigned char* smem, Scratch* __restrict__ scr, const bf16* __restrict__ x, bf16* __restrict__ out,
                                     const unsigned par, const unsigned epoch, const int warp) {
  int tid, b;
  asm volatile("mov.u32 %0, %%tid.x;" : "=r"(tid));
  asm volatile("mov.u32 %0, %%ctaid.x;" : "=r"(b));
  const int lane = tid & 31, g = lane >> 2, tq = lane & 3;
  const uint32_t sb = __shfl_sync(~0u, s2u(smem), 0), bar0 = sb + OFF_BAR;
  float* s_sm = (float*)(smem + OFF_SM);
  const int prow = 4 * (lane >> 4) + ((lane & 7) >> 1) + 8 * (lane & 1);
  const float* s_co = (const float*)(smem + OFF_CO);
  const int opos = (b & 15) * 32 + (lane & 16) + 2 * (lane & 6) + ((lane >> 2) & 2) + (lane & 1);
  const float xv = b < 16 ? __bfloat162float(x[(b & 15) * 32 + lane]) : 0.f;
  const int rk = b & 1, ob = 32 * rk + ((b >> 1) & 31);
  uint32_t psb;
  asm volatile("mapa.shared::cluster.u32 %0, %1, %2;" : "=r"(psb) : "r"(sb), "r"(rk ^ 1));
  {
    uint32_t a[8][4];
    {
      const int rg = tid >> 4;
      const uint4* src = g_xo + ((size_t)b * 64 + rg) * RS;
      const uint32_t dst = sb + OFF_XO + rg * 256 + (((tid & 15) ^ (rg & 7)) << 4);
      unsigned long long todo = 0x0001000100010001ull;
#pragma unroll 1
      for (int it = 0; it < SPIN_MAX * 16; it++) {
        unsigned long long mk = *(volatile unsigned long long*)(smem + OFF_MASK);
        const unsigned long long nw = (mk >> rg) & todo;
        todo ^= nw;
#pragma unroll
        for (int i = 0; i < 4; i++)
          if (nw >> (16 * i) & 1)
            asm volatile("cp.async.cg.shared.global [%0], [%1], 16;" ::"r"(dst + i * 4096), "l"(src + i * 16 * RS + (tid & 15)) : "memory");
        if (!__any_sync(~0u, todo != 0)) break;
      }
      asm volatile("cp.async.mbarrier.arrive.noinc.shared::cta.b64 [%0];" ::"r"(bar0 + 8 * (XB + 2)) : "memory");
    }
    mbar_wait(bar0 + 8 * FB_UV); mbar_wait(bar0 + 8 * (FB_UV + 1));
    const uint32_t ab = sb + OFF_UV + (warp >> 2) * 8192 + (8 * (lane >> 4) + (lane & 7)) * 128 + (((2 * (warp & 3) + ((lane >> 3) & 1)) ^ (lane & 7)) << 4);
#pragma unroll
    for (int s = 0; s < 8; s++) ldsm_t(a[s], ab + (s >> 2) * 16384 + (s & 3) * 2048);
    const int chn = 2 * warp + (tq & 1);
    uint32_t a_b = sb + OFF_B + (tq >> 1) * 272 + (32 * (chn >> 2) + 8 * (g >> 1) + 2 * (chn & 3) + (g & 1)) * 2;
    uint32_t a_bq = sb + OFF_B + (lane & 1) * 272 + (lane >> 3) * 16;
    unsigned* p_c = g_xc + (b >> 2) * 256 + warp * 32 + (b & 3) * 8 + (g & 3) * 2 + (g >> 2);
    PIN(a_b); PIN(a_bq); PINL(p_c);
    mbar_wait(bar0 + 8 * (XB + 6));
    uint32_t wb[8];
#pragma unroll
    for (int s = 0; s < 8; s++) wb[s] = *(const uint32_t*)(smem + OFF_RA + (4 * s + tq) * 4);
    const float invL = *(const float*)(smem + OFF_RA + 128);
    float ov;
    POLL {
      mbar_wait(bar0 + 8 * (XB + 2));
      uint32_t ao[4][4];
#pragma unroll
      for (int s = 0; s < 4; s++)
        ldsm_t(ao[s], sb + OFF_XO + (16 * s + 8 * (lane >> 4) + (lane & 7)) * 256 + (((2 * warp + ((lane >> 3) & 1)) ^ (lane & 7)) << 4));
      float d[4][4] = {};
#pragma unroll
      for (int s = 0; s < 4; s++) mma16(d[s], ao[s], wb[2 * s], wb[2 * s + 1]);
      const unsigned p2 = par * 0x10001u;
      unsigned bad = 0;
#pragma unroll
      for (int s = 0; s < 4; s++) bad |= lop_x3(ao[s][0], ao[s][1], p2) | lop_x3(ao[s][2], ao[s][3], p2);
      bad = g == 0 ? bad | (bad >> 16) : 0u;
      ov = (tq & 1) ? (d[0][2] + d[1][2]) + (d[2][2] + d[3][2]) : (d[0][0] + d[1][0]) + (d[2][0] + d[3][0]);
      if (__builtin_expect(!__any_sync(~0u, bad & 1) || ++it_ >= SPIN_MAX, 1)) break;
#pragma unroll
      for (int i = 0; i < 4; i++)
        asm volatile("cp.async.cg.shared.global [%0], [%1], 16;"
                     ::"r"(sb + OFF_XO + ((lane >> 1) + 16 * i) * 256 + (((2 * warp + (lane & 1)) ^ ((lane >> 1) & 7)) << 4)),
                       "l"(g_xo + ((size_t)b * 64 + (lane >> 1) + 16 * i) * RS + 2 * warp + (lane & 1)) : "memory");
      asm volatile("cp.async.wait_all;" ::: "memory");
      __syncwarp();
    }
    {
      const float lo = ov - bfhi(__float_as_uint(ov));
      asm volatile("st.shared.u16 [%0], %1;" ::"r"(a_b), "h"((unsigned short)((tq & 2) ? pack2(lo, lo) : __float_as_uint(ov) >> 16)) : "memory");
    }
    nbar(1, 256);
    float d[4][4] = {};
#pragma unroll
    for (int y = 0; y < 4; y++) {
      uint32_t bq[4];
      ldsm(bq, a_bq + 64 * y);
      mma16(d[(2 * y) & 3], a[2 * y], bq[0], bq[1]); mma16(d[(2 * y + 1) & 3], a[2 * y + 1], bq[2], bq[3]);
    }
    const float r0 = ((d[0][0] + d[0][1]) + (d[1][0] + d[1][1])) + ((d[2][0] + d[2][1]) + (d[3][0] + d[3][1]));
    const float r1 = ((d[0][2] + d[0][3]) + (d[1][2] + d[1][3])) + ((d[2][2] + d[2][3]) + (d[3][2] + d[3][3]));
    if (tq == 0) stx4(p_c, pack2t(r0 * invL, r1 * invL, par));
  }
  unsigned tpub = clock();
  mbar_wait(bar0 + 8 * (XB + 4));
  const float gav = s_co[256 + (opos & 31)];
  const float gbv = s_co[288 + (lane & 4) + 2 * (lane & 1) + ((lane >> 1) & 1)];
  float4 cf[2];
#pragma unroll
  for (int s = 0; s < 2; s++) cf[s] = *(const float4*)(s_co + 32 * warp + 16 * s + 4 * tq);
  {
    uint32_t a[2][4][4];
    mbar_wait(bar0 + 8 * (FB_O + (warp >> 2)));
    const uint32_t ab = sb + OFF_O + (32 * warp + prow) * 128 + ((((lane >> 3) & 1) ^ (prow & 7)) << 4);
#pragma unroll
    for (int i = 0; i < 8; i++) ldsm_t(a[i >> 2][i & 3], (ab + (i >> 2) * 2048) ^ ((i & 3) << 5));
    uint4 v;
    const unsigned* pc = g_xc + (4 * (b >> 4) + 2 * rk + (warp >> 2)) * 256 + 64 * (warp & 3) + 2 * lane;
    uint32_t ro = ((tq >> 1) == rk ? sb : psb) + OFF_P + (8 * (tq & 1) + g) * 144 + (8 * rk + warp) * 8;
    uint32_t a_q = sb + OFF_P + (8 * (lane >> 4) + (lane & 7)) * 144;
    unsigned* p_ao = g_xao + (b >> 5) * 1024 + (opos >> 4) * 32 + (b & 16) + (opos & 15);
    PIN(ro); PIN(a_q); PINL(p_ao); PINL(pc);
    spin_until(tpub + DLY5);
    POLL {
      const unsigned long long u0 = ldx64(pc);
      v.x = (unsigned)u0; v.y = u0 >> 32;
      RETRY(X8(v))
    }
    v.z = lane & 16 ? v.x : 0u; v.w = lane & 16 ? v.y : 0u;
    if (lane & 16) v.x = v.y = 0u;
    float d[4][4] = {};
#pragma unroll
    for (int mt = 0; mt < 4; mt++) mma16(d[mt], a[0][mt], v.x, v.y);
#pragma unroll
    for (int mt = 0; mt < 4; mt++) mma16(d[mt], a[1][mt], v.z, v.w);
    float r[8];
#pragma unroll
    for (int i = 0; i < 8; i++) r[i] = d[i >> 1][2 * (i & 1)] + d[i >> 1][2 * (i & 1) + 1];
    tred<4>(r, lane, 2); tred<2>(r, lane, 1);
    st_pair((tq >> 1) == rk ? 1 : 2, ro, psb + OFF_BAR + 8 * (XB + 3), r[0], r[1]);
    __syncwarp();
    if (lane == 0) BAR_ARRIVE(XB + 3);
    if (warp == 0) {
      mbar_wait(bar0 + 8 * (XB + 3));
      float p[8];
#pragma unroll
      for (int i = 0; i < 8; i++) {
        const float4 q = lds16(a_q + i * 16);
        p[i] = (lane & 8) ? q.y + q.w : q.x + q.z;
      }
      const float t = ((p[0] + p[1]) + (p[2] + p[3])) + ((p[4] + p[5]) + (p[6] + p[7]));
      stx4(p_ao, fbits(gav * t + xv));
    }
  }
  tpub = clock();
  if (b < 112) {
    uint32_t af[2][4][4], ad[4][4];
    const uint32_t ab = sb + (32 * warp + 8 * (lane >> 4) + (lane & 7)) * 64 + ((((lane >> 3) & 1) ^ ((lane >> 1) & 3)) << 4);
    uint32_t ro = ((tq & 1) == rk ? sb : psb) + OFF_R4 + (8 * (tq >> 1) + g) * 176 + (10 * rk + warp) * 8;
    uint32_t a_q = sb + OFF_R4 + (8 * (lane >> 4) + (lane & 7)) * 176 + (lane & 8) * 10;
    uint32_t a_d = sb + OFF_D + warp * 2048 + (8 * (lane >> 4) + (lane & 7)) * 128 + ((((lane >> 3) & 1) ^ (lane & 7)) << 4);
    unsigned* p_f = g_xf + b * 512 + 64 * warp + 16 * tq + 2 * g;
    const unsigned* pa = g_xao + (g >> 1) * 1024 + 512 * rk + 64 * warp + 4 * (lane & 7);
    PIN(ro); PIN(a_q); PIN(a_d); PINL(p_f); PINL(pa);
    spin_until(tpub + DLY6);
    uint4 v[2];
    {
      bool have = false;
      POLL {
        v[0] = ldx16(pa); v[1] = ldx16(pa + 32);
        const unsigned t1 = (unsigned)clock() + WTEST;
        while (!have && (int)((unsigned)clock() - t1) < 0) {
          uint32_t ok;
          asm volatile("{.reg .pred p, q; mbarrier.test_wait.parity.shared::cta.b64 p, [%1], 0; mbarrier.test_wait.parity.shared::cta.b64 q, [%1+8], 0;\n"
                       "and.pred p, p, q; vote.sync.all.pred p, p, 0xffffffff; selp.u32 %0, 1, 0, p;}" : "=r"(ok) : "r"(bar0 + 8 * FB_G) : "memory");
          if (ok) {
#pragma unroll
            for (int i = 0; i < 8; i++) ldsm_t(af[i >> 2][i & 3], (ab + ((i & 2) ? OFF_U : OFF_G) + (i >> 2) * 1024) ^ ((i & 1) << 5));
            have = true;
          }
        }
        if (!__any_sync(~0u, (X16(v[0]) | X16(v[1])) & 1) || ++it_ >= SPIN_MAX) break;
      }
      float df[4][4] = {}, dg[2][4] = {};
      uint32_t zb[4];
      const uint32_t one = g == 0 ? 0x3F803F80u : 0u;
#pragma unroll
      for (int s = 0; s < 2; s++) {
        const uint32_t y0 = pack2(u2f(v[s].x), u2f(v[s].y)), y1 = pack2(u2f(v[s].z), u2f(v[s].w));
        const uint32_t ya[4] = {y0, one, y1, one};
        mma16(dg[s], ya, y0, y1);
        zb[2 * s] = pack2(u2f(v[s].x) * cf[s].x, u2f(v[s].y) * cf[s].y); zb[2 * s + 1] = pack2(u2f(v[s].z) * cf[s].z, u2f(v[s].w) * cf[s].w);
      }
      float st[2] = {(dg[0][2] + dg[0][3]) + (dg[1][2] + dg[1][3]), (dg[0][0] + dg[0][1]) + (dg[1][0] + dg[1][1])};
      if (!have) {
        mbar_wait(bar0 + 8 * FB_G); mbar_wait(bar0 + 8 * (FB_G + 1));
#pragma unroll
        for (int i = 0; i < 8; i++) ldsm_t(af[i >> 2][i & 3], (ab + ((i & 2) ? OFF_U : OFF_G) + (i >> 2) * 1024) ^ ((i & 1) << 5));
      }
#pragma unroll
      for (int i = 0; i < 8; i++) mma16(df[i & 3], af[i >> 2][i & 3], zb[2 * (i >> 2)], zb[2 * (i >> 2) + 1]);
#pragma unroll
      for (int o2 = 1; o2 < 4; o2 <<= 1) { st[0] += __shfl_xor_sync(~0u, st[0], o2); st[1] += __shfl_xor_sync(~0u, st[1], o2); }
#pragma unroll
      for (int o2 = 4; o2 < 32; o2 <<= 1) st[1] += __shfl_xor_sync(~0u, st[1], o2);
      float r[8];
#pragma unroll
      for (int i = 0; i < 8; i++) r[i] = df[i >> 1][2 * (i & 1)] + df[i >> 1][2 * (i & 1) + 1];
      tred<4>(r, lane, 2); tred<2>(r, lane, 1);
      const int md = (tq & 1) == rk ? 1 : 2;
      st_pair(md, ro, psb + OFF_BAR + 8 * (XB + 5), r[0], r[1]);
      st_pair(lane < 2 ? md : 0, ro + 16 * 176, psb + OFF_BAR + 8 * (XB + 5), st[0], st[1]);
      __syncwarp();
      if (lane == 0) BAR_ARRIVE(XB + 5);
      mbar_wait(bar0 + 8 * FB_D);
#pragma unroll
      for (int mt = 0; mt < 4; mt++)
        ldsm_t(ad[mt], a_d ^ (mt << 5));
    }
    mbar_wait(bar0 + 8 * (XB + 5));
    {
      float4 q[5], u[8];
#pragma unroll
      for (int i = 0; i < 5; i++) q[i] = lds16(a_q + i * 16);
#pragma unroll
      for (int i = 0; i < 8; i++) u[i] = *(const float4*)(smem + OFF_R4 + 16 * 176 + (i >> 2) * 80 + (i & 3) * 16);
      float p[6] = {((q[0].x + q[0].z) + (q[1].x + q[1].z)) + ((q[2].x + q[2].z) + (q[3].x + q[3].z)), q[4].x, q[4].z,
                    ((q[0].y + q[0].w) + (q[1].y + q[1].w)) + ((q[2].y + q[2].w) + (q[3].y + q[3].w)), q[4].y, q[4].w};
      tred<3>(p, lane, 8);
      const float P = p[0], A1 = p[1], A2 = p[2];
      const float mean = (((u[0].x + u[0].z) + (u[1].x + u[1].z)) + ((u[2].x + u[2].z) + (u[3].x + u[3].z)) +
                          ((u[4].x + u[4].z) + (u[5].x + u[5].z)) + ((u[6].x + u[6].z) + (u[7].x + u[7].z))) * (1.f / 512.f);
      const float sq = (((u[0].y + u[0].w) + (u[1].y + u[1].w)) + ((u[2].y + u[2].w) + (u[3].y + u[3].w)) +
                         ((u[4].y + u[4].w) + (u[5].y + u[5].w)) + ((u[6].y + u[6].w) + (u[7].y + u[7].w))) * (1.f / 512.f);
      float rstd;
      asm("rsqrt.approx.ftz.f32 %0, %1;" : "=f"(rstd) : "f"(fmaxf(sq - mean * mean, 0.f) + 1e-5f));
      const float gg = bfr(rstd * (P - mean * A1) + A2);
      const float uu = __shfl_xor_sync(~0u, gg, 16);
      const float hh = bfr(gg * rcp(1.f + ex2(gg * (-2.302208198f - 0.1029432397f * gg * gg)))) * uu;
      const uint32_t hw = pack2(hh, __shfl_down_sync(~0u, hh, 1));
      const uint32_t b0 = __shfl_sync(~0u, hw, 2 * tq), b1 = __shfl_sync(~0u, hw, 2 * tq + 8);
      float f0 = 0, f1 = 0;
#pragma unroll
      for (int mt = 0; mt < 4; mt++) {
        float dd[4] = {0, 0, 0, 0};
        mma16(dd, ad[mt], b0, b1);
        if (tq == mt) { f0 = dd[0]; f1 = dd[2]; }
      }
      stx8(p_f, make_uint2(fbits(f0), fbits(f1)));
    }
    tpub = clock();
    if (b < 64 && warp == (b >> 3)) {
      const uint4 y = (b & 4) ? v[1] : v[0];
      float a4[4] = {u2f(y.x), u2f(y.y), u2f(y.z), u2f(y.w)};
      tred<2>(a4, lane, 16); tred<1>(a4, lane, 8);
      a4[0] += __shfl_xor_sync(~0u, a4[0], 4);
      if (!(lane & 4)) s_sm[416 + 8 * (lane >> 4) + 2 * tq + ((lane >> 3) & 1)] = a4[0];
      if (warp == 7) nbar_arrive(2, 256);
    } else if (b < 64 && warp == 7) nbar_arrive(2, 256);
    if (b < 64 && warp < 7) {
      uint4 v;
      const unsigned* pf = g_xf + (tid >> 1) * 512 + 8 * ob + 4 * (tid & 1);
      const int col = 16 * (ob >> 1) + 4 * (ob & 1) + ((tid >> 1) & 3) + 8 * (tid & 1);
      bf16* po = out + col;
      PINL(po); PINL(pf);
      spin_until(tpub + DLY7);
      POLL { v = ldx16(pf); RETRY(X16(v)) }
      float f[4] = {u2f(v.x), u2f(v.y), u2f(v.z), u2f(v.w)};
      tred<2>(f, lane, 16); tred<1>(f, lane, 8);
      f[0] += __shfl_xor_sync(~0u, f[0], 4); f[0] += __shfl_xor_sync(~0u, f[0], 2);
      if (!(lane & 6)) s_sm[352 + warp * 8 + 4 * (lane & 1) + (lane >> 3)] = f[0];
      nbar(2, 256);
      if (tid < 8) {
        const float* q = s_sm + 352 + tid;
        const float t = ((q[0] + q[8]) + (q[16] + q[24])) + ((q[32] + q[40]) + q[48]);
        *po = __float2bfloat16(s_sm[416 + (col & 15)] + bfr(gbv * bfr(t)));
        if (b == 0 && tid == 0) stx4(&g_epoch, epoch + 1);
      }
    }
  }
}

__global__ void __cluster_dims__(2, 1, 1) __launch_bounds__(384, 1)
fused_kernel(const bf16* __restrict__ x, const bf16* __restrict__ cvec, const bf16* __restrict__ w_mod, bf16* __restrict__ out,
             Scratch* __restrict__ scr, const __grid_constant__ TMaps tms) {
  extern __shared__ __align__(1024) unsigned char smem[];
  const int tid = threadIdx.x, warp = __shfl_sync(~0u, tid >> 5, 0), lane = tid & 31;
  const int b = blockIdx.x, rk = b & 1, pr = b >> 1, hd = b >> 2;
  uint32_t sb = s2u(smem), bar0 = sb + OFF_BAR;

  unsigned gt_start;
  asm volatile("mov.u32 %0, %%globaltimer_lo;" : "=r"(gt_start));
  const int g = lane >> 2, tq = lane & 3;
  const int arow = 64 * (b >> 4) + ((tid & 255) >> 3);
  uint4 wm0, wm1;
  uint32_t c0w, c1w;
  if (warp < 8) {
    const bf16* wa = w_mod + (size_t)arow * 3072 + (lane & 4) * 128 + 32 * (b & 15) + 8 * tq;
    wm0 = ldx16(wa); wm1 = ldx16(wa + 32 * 3072);
    c0w = ldc4(cvec + (arow & ~1)); c1w = ldc4(cvec + (arow & ~1) + 32);
  }
  const unsigned t_off = gt_start + RATE_T0;
  if (warp == 11) {
    if (lane == 0) {
#pragma unroll
      for (int i = 0; i < FB_KV; i++) { BAR_INIT(i, 1); BAR_ARM(i, 16384); }
    }
    __syncwarp();
    asm volatile("fence.mbarrier_init.release.cluster;" ::: "memory");
    asm volatile("barrier.cluster.arrive.relaxed.aligned;" ::: "memory");
#pragma unroll 1
    for (int i = 0; i < FB_KV; i++) {
      if (i >= HWIN) mbar_wait(bar0 + 8 * (i - HWIN));
      wait_until(t_off + (i < 4 ? 2 * i + ((b >> 1) & 1) : 4 * i - 8 + (b & 3)) * (RATE_H / 4));
      if (lane == 0) {
        if (i < 4) tma3d(sb + OFF_WQ + i * 16384, &tms.m[0], bar0 + 8 * i, 0, i * 128, 2 * hd + rk);
        else tma3d(sb + OFF_WQ + i * 16384, &tms.m[1], bar0 + 8 * i, 0, (b & 3) * 128 + (i - 4) * 64, 2 * hd);
      }
      __syncwarp();
    }
  }
  if (warp == 10) {
    const uint4 xa = ldc16(x + 16 * lane), xb = ldc16(x + 16 * lane + 8);
    const unsigned ep = ldc4(&g_epoch);
    float xv[16] = {bflo(xa.x), bfhi(xa.x), bflo(xa.y), bfhi(xa.y), bflo(xa.z), bfhi(xa.z), bflo(xa.w), bfhi(xa.w),
                    bflo(xb.x), bfhi(xb.x), bflo(xb.y), bfhi(xb.y), bflo(xb.z), bfhi(xb.z), bflo(xb.w), bfhi(xb.w)};
    float s = 0;
#pragma unroll
    for (int i = 0; i < 16; i++) s += xv[i];
#pragma unroll
    for (int o = 16; o; o >>= 1) s += __shfl_xor_sync(~0u, s, o);
    const float mean = s * (1.f / 512.f);
    s = 0;
#pragma unroll
    for (int i = 0; i < 16; i++) { xv[i] -= mean; s += xv[i] * xv[i]; }
#pragma unroll
    for (int o = 16; o; o >>= 1) s += __shfl_xor_sync(~0u, s, o);
    const float rstd = rsqrtf(s * (1.f / 512.f) + 1e-5f);
    if ((lane >> 1) == (b & 15))
#pragma unroll
      for (int i = 0; i < 4; i++)
        *(float4*)(smem + OFF_SM + (256 + (lane & 1) * 16 + 4 * i) * 4) = make_float4(xv[4 * i] * rstd, xv[4 * i + 1] * rstd, xv[4 * i + 2] * rstd, xv[4 * i + 3] * rstd);
    if (lane == 0) *(volatile unsigned*)(smem + OFF_MASK + 8) = ep;
    nbar_arrive(1, 288);
  }
  if (warp >= 8) {
    asm volatile("setmaxnreg.dec.sync.aligned.u32 72;");
    if (tid == 288) {
#pragma unroll
      for (int q = FB_KV; q < FB_KV + 16; q++) { BAR_INIT(q, 1); BAR_ARM(q, 32768); }
    }
    if (tid == 320) {
#pragma unroll
      for (int q = 0; q <= 13 + NSLOT; q++) BAR_INIT(EB + q, q == 0 ? 4 : q < 5 ? 16 : q < 16 ? 12 : 6);
    }
    if (tid == 256) {
#pragma unroll
      for (int q = FB_MOD; q <= FB_D; q++) { BAR_INIT(q, 1); BAR_ARM(q, 16384); }
      BAR_INIT(QB, 9); BAR_ARM(QB, 1024);
#pragma unroll
      for (int q = 0; q < 7; q++) BAR_INIT(XB + q, q == 2 ? 256 : q == 5 || q == 3 ? 9 : 1);
      BAR_ARM(XB + 3, 1024);
      BAR_ARM(XB + 5, 1024 + 64 + 512);
      *(volatile unsigned long long*)(smem + OFF_MASK) = 0;
    }
    if (warp != 11) {
      __syncwarp();
      asm volatile("fence.mbarrier_init.release.cluster;" ::: "memory");
      __threadfence_block();
      asm volatile("barrier.cluster.arrive.relaxed.aligned;" ::: "memory");
    }
    if (warp == 11) {
      asm volatile("barrier.cluster.wait.acquire.aligned;" ::: "memory");
      const unsigned epoch = *(volatile unsigned*)(smem + OFF_MASK + 8), par = (epoch + 1) & 1;
      mbar_wait(bar0 + 8 * (FB_KV + 15));
      for (int it = 0; ldx4(scr->cnt + 96 + 32 * (b >> 6)) != (epoch + 1) * 64 && it < SPIN_MAX; it++) {}
      uint4 hh;
      POLL { hh = ldx16(g_ml + (b >> 2) * 64 + 2 * lane); RETRY(X16(hh)) }
      int mi = __float_as_int(fmaxf(u2f(hh.x), u2f(hh.z)));
      mi ^= (mi >> 31) & 0x7fffffff;
      mi = __reduce_max_sync(~0u, mi);
      mi ^= (mi >> 31) & 0x7fffffff;
      const float M = __int_as_float(mi);
      const uint32_t wp = pack2(ex2(u2f(hh.x) - M), ex2(u2f(hh.z) - M));
      float L = bflo(wp) * u2f(hh.y) + bfhi(wp) * u2f(hh.w);
#pragma unroll
      for (int o2 = 16; o2; o2 >>= 1) L += __shfl_xor_sync(~0u, L, o2);
      *(uint32_t*)(smem + OFF_RA + lane * 4) = wp;
      if (lane == 0) *(float*)(smem + OFF_RA + 128) = rcp(L);
      __syncwarp();
      if (lane == 0) BAR_ARRIVE(XB + 6);
    }
    if (warp == 10) {
      if (lane < 8) asm volatile("prefetch.tensormap [%0];" ::"l"(&tms.m[lane + 1]) : "memory");
      asm volatile("barrier.cluster.wait.acquire.aligned;" ::: "memory");
      const unsigned epoch = *(volatile unsigned*)(smem + OFF_MASK + 8);
#pragma unroll 1
      for (int e = 0; e < 2; e++) {
        for (int it = 0; ldx4(scr->cnt + (e ? 2 + rk : 1)) != (epoch + 1) * (e ? 64 : 128) && it < SPIN_MAX; it++) {}
        if (lane == 0) BAR_ARRIVE(XB + e);
      }
      mbar_wait(bar0 + 8 * (FB_KV + 14));
      unsigned long long m = 0;
#pragma unroll 1
      for (int it = 0; ~m && it < SPIN_MAX; it++) {
        m = ldx64(scr->cnt + 32 + 32 * (b >> 6)) ^ ((epoch & 1) ? ~0ull : 0ull);
        if (lane == 0) *(volatile unsigned long long*)(smem + OFF_MASK) = m;
      }
    }
    if (warp == 9) {
      asm volatile("barrier.cluster.wait.acquire.aligned;" ::: "memory");
      const unsigned epoch = *(volatile unsigned*)(smem + OFF_MASK + 8);
      const unsigned par = (epoch + 1) & 1, inv = par ^ 1;
      const uint4 inv4 = make_uint4(inv, inv, inv, inv);
      mbar_wait(bar0 + 8 * FB_KV);
#pragma unroll 2
      for (int k = 0; k < 8; k++) {
        const uint32_t cp = ldc4(cvec + 2 * (lane + 32 * k));
        *(uint32_t*)(smem + OFF_SILU + (lane + 32 * k) * 4) = pack2(silu_bf(bflo(cp)), silu_bf(bfhi(cp)));
      }
      __syncwarp();
      mbar_wait(bar0 + 8 * FB_MOD);
      const uint32_t ab = sb + OFF_MOD + (8 * (lane >> 4) + (lane & 7)) * 32 + ((((lane >> 3) ^ (lane >> 2)) & 1) << 4);
      float d[4][4] = {};
#pragma unroll 2
      for (int s4 = 0; s4 < 8; s4++)
#pragma unroll
        for (int s = 0; s < 4; s++) {
          uint32_t a[4];
          const uint32_t* ps = (const uint32_t*)(smem + OFF_SILU) + 32 * s4 + 8 * s + tq;
          ldsm_t(a, ab + (4 * s4 + s) * 512); mma16(d[s], a, ps[0], ps[4]);
        }
      const float t = (tq & 1) ? (d[0][2] + d[1][2]) + (d[2][2] + d[3][2]) : (d[0][0] + d[1][0]) + (d[2][0] + d[3][0]);
      if (tq < 2) stx4(g_xm + b * 16 + 2 * (g & 6) + 2 * tq + (g & 1), fbits(bfr(t)));
      __syncwarp();
      if (lane == 0) CNT_ADD(6);
      mbar_wait(bar0 + 8 * (FB_KV + 8));
      if (lane < 16) stx16(g_xc + (b >> 2) * 256 + (lane >> 1) * 32 + (b & 3) * 8 + (lane & 1) * 4, inv4);
      if (lane < 8) stx16(g_xao + (b >> 5) * 1024 + (b & 15) * 64 + (lane & 4) * 8 + (b & 16) + (lane & 3) * 4, inv4);
      if (b < 112)
#pragma unroll 1
        for (int k = 0; k < 4; k++) stx16(g_xf + b * 512 + (lane + 32 * k) * 4, inv4);
      nbar_arrive(2, 288);
      for (int it = 0; ldx4(scr->cnt + 6) != (epoch + 1) * 128 && it < SPIN_MAX; it++) __nanosleep(100);
      {
        uint4 sv[2], cb[2];
        unsigned ga, gb;
        POLL {
#pragma unroll
          for (int k = 0; k < 2; k++) { sv[k] = ldx16(g_xm + 512 + 256 * rk + 4 * (lane + 32 * k)); cb[k] = ldx16(g_xm + 1024 + 256 * rk + 4 * (lane + 32 * k)); }
          ga = ldx4(g_xm + (b & 15) * 32 + lane); gb = ldx4(g_xm + 1536 + 256 * rk + 8 * (pr & 31) + (lane & 7));
          RETRY(X16(sv[0]) | X16(sv[1]) | X16(cb[0]) | X16(cb[1]) | lop_x3(ga, gb, par))
        }
#pragma unroll
        for (int k = 0; k < 2; k++) {
          const float c0 = bfr(1.f + bfhi(cb[k].x)), c1 = bfr(1.f + bfhi(cb[k].y)), c2 = bfr(1.f + bfhi(cb[k].z)), c3 = bfr(1.f + bfhi(cb[k].w));
          *(float4*)(smem + OFF_CO + (lane + 32 * k) * 16) = make_float4(c0, c1, c2, c3);
          uint2* pb = (uint2*)(smem + OFF_BP) + lane + 32 * k;
          pb[0] = make_uint2(pack2(c0, c1), pack2(c2, c3));
          pb[64] = make_uint2(__byte_perm(sv[k].x, sv[k].y, 0x7632), __byte_perm(sv[k].z, sv[k].w, 0x7632));
        }
        *(float*)(smem + OFF_CO + 1024 + lane * 4) = bfhi(ga);
        *(float*)(smem + OFF_CO + 1152 + lane * 4) = bfhi(gb);
      }
      __syncwarp();
      if (lane == 0) BAR_ARRIVE(XB + 4);
    }
    if (warp == 8) {
      const unsigned stag = ((pr * SMUL) & 63) * RATE_NS >> 6;
      unsigned tnext = t_off + 4 * RATE_H;
      asm volatile("barrier.cluster.wait.acquire.aligned;" ::: "memory");
#pragma unroll 1
      for (int k = 0; k < 24; k++) {
        const int code = (k < 12 ? ORDER0 >> (5 * k) : ORDER1 >> (5 * (k - 12))) & 31;
        const bool kv = code < 16;
        const int n = code, w = code - 16;
        if (!kv && w >= 5 && b >= 112) break;
        if (kv) mbar_wait(bar0 + 8 * (FB_KV + n - (n < 6 ? EWIN : KVWIN)));
        if (k >= TAIL_K) mbar_wait(bar0 + 8 * (FB_KV + (int)((ORDER1 >> (5 * (k - 12 - ((WINS >> (4 * (k - TAIL_K))) & 15)))) & 31)));
        const int e = kv ? (n == 3 ? 2 : n == 5 ? 1 : n) : w == 0 ? 0 : w < 5 ? 16 + ((w - 1) >> 1) : w == 7 ? 19 : 18;
        if (e != 1 && k) mbar_wait(bar0 + 8 * (EB + e));
        wait_until(tnext + stag);
        tnext += k > TAIL_K ? RATE_TL : k < 4 ? RATE_E : RATE_NS;
        if (lane == 0) {
          if (kv)
            asm volatile("cp.async.bulk.tensor.3d.shared::cluster.global.mbarrier::complete_tx::bytes.multicast::cluster.L2::cache_hint [%0], [%1, {%3, %4, %5}], [%2], %6, %7;"
                         ::"r"(sb + (n % NSLOT) * SLOT + rk * 16384), "l"(&tms.m[2]), "r"(bar0 + 8 * (FB_KV + n)), "r"(0), "r"(((n >> 1) * 64 + pr) * 64),
                           "r"(4 * (n & 1) + 2 * rk), "h"((unsigned short)3), "l"(stream_policy()) : "memory");
          else {
            tma3d(sb + (w == 0 ? OFF_MOD : w < 5 ? OFF_UV + (w - 1) * 16384 : w == 5 ? OFF_G : w == 6 ? OFF_U : OFF_D),
                  &tms.m[w == 0 ? 3 : w < 3 ? 4 : w < 5 ? 5 : w + 1], bar0 + 8 * (FB_MOD + w),
                  w == 0 ? 1024 + b * 16 : w < 3 || w == 7 ? 0 : w < 5 ? (pr & 7) * 64 : pr * 32, w == 7 ? b * 16 : w == 1 || w == 2 ? (b & 3) * 128 + (w - 1) * 64 : 0,
                  w == 1 || w == 2 ? 2 * hd : w == 3 || w == 4 ? (b >> 4) * 4 + 2 * rk + w - 3 : w == 5 || w == 6 ? rk : 0);
          }
        }
        __syncwarp();
      }
    }
    if (b < 112) {
      const int mt = warp & 1, dd = (warp >> 1) & 1;
      mbar_wait(bar0 + 8 * (XB + 4));
      const uint32_t ab = sb + (mt ? OFF_U : OFF_G) + (8 * (lane >> 4) + (lane & 7)) * 64 + (((2 * dd + ((lane >> 3) & 1)) ^ ((lane >> 1) & 3)) << 4);
      uint32_t base;
      asm volatile("mapa.shared::cluster.u32 %0, %1, %2;" : "=r"(base) : "r"(sb), "r"(dd));
      uint2 bb[16];
#pragma unroll
      for (int s = 0; s < 16; s++) bb[s] = *(const uint2*)(smem + OFF_BP + (g & 1) * 512 + (4 * s + tq) * 8);
      mbar_wait(bar0 + 8 * (FB_G + mt));
      float e[4][4] = {};
#pragma unroll
      for (int s = 0; s < 16; s++) { uint32_t a[4]; ldsm_t(a, ab + s * 1024); mma16(e[s & 3], a, bb[s].x, bb[s].y); }
      float r[4];
#pragma unroll
      for (int i = 0; i < 4; i++) r[i] = (e[0][i] + e[1][i]) + (e[2][i] + e[3][i]);
      if (tq < 2) st_async2(base + OFF_R4 + (8 * mt + g) * 176 + (10 * rk + 8 + tq) * 8, base + OFF_BAR + 8 * (XB + 5), tq ? r[1] : r[0], tq ? r[3] : r[2]);
    }
    return;
  }

  float* s_sm = (float*)(smem + OFF_SM);
  unsigned par, epoch;
  uint32_t rsb;
  {
    float* s_r4 = (float*)(smem + OFF_R4);
    asm volatile("barrier.cluster.arrive.relaxed.aligned;" ::: "memory");
    asm volatile("mapa.shared::cluster.u32 %0, %1, %2;" : "=r"(rsb) : "r"(sb), "r"(rk ^ 1));
    const float c0 = (arow & 1) ? bfhi(c0w) : bflo(c0w), c1 = (arow & 1) ? bfhi(c1w) : bflo(c1w);
    float acc[8] = {0, 0, 0, 0, 0, 0, 0, 0};
    fma8(acc, wm0, silu_bf(c0)); fma8(acc, wm1, silu_bf(c1));
    tred<4>(acc, lane, 8); tred<2>(acc, lane, 16);
    *(float2*)(s_r4 + warp * 64 + 8 * (lane & 7) + ((lane >> 1) & 4) + ((lane >> 3) & 2)) = make_float2(acc[0], acc[1]);
    nbar(1, 288);
    epoch = *(volatile unsigned*)(smem + OFF_MASK + 8);
    par = (epoch + 1) & 1;
    if (warp == 0) {
      float t = 0.f, ca = b < 16 ? 1.f : 0.f;
#pragma unroll
      for (int w = 0; w < 8; w++) { t += s_r4[w * 64 + lane]; ca += s_r4[w * 64 + 32 + lane]; }
      t += ca * s_sm[256 + lane];
      const float nb = __shfl_down_sync(~0u, t, 1);
      const uint32_t w0 = lane < 8 ? pack2t(t, nb, par) : pack2(t, nb);
      const uint32_t w1 = __shfl_down_sync(~0u, w0, 8), w2 = __shfl_down_sync(~0u, w0, 16), w3 = __shfl_down_sync(~0u, w0, 24);
      if (lane < 8 && !(lane & 1)) stx16(g_h + (b >> 5) * 512 + (b & 15) * 32 + (b & 16) + 2 * lane, make_uint4(w0, w1, w2, w3));
      __syncwarp();
      if (lane == 0) CNT_ADD(1);
    }
  }
  asm volatile("barrier.cluster.wait.acquire.aligned;" ::: "memory");
  {
    uint32_t a[4][4][4];
    mbar_wait(bar0 + 8 * (warp >> 1));
    const uint32_t ab = sb + OFF_WQ + (64 * warp + 8 * (lane >> 4) + (lane & 7)) * 128;
#pragma unroll
    for (int s = 0; s < 4; s++)
#pragma unroll
      for (int mt = 0; mt < 4; mt++) ldsm_t(a[s][mt], ab + s * 2048 + (((2 * mt + ((lane >> 3) & 1)) ^ (lane & 7)) << 4));
    uint4 v0, v1;
    const unsigned* ph = g_h + (g >> 1) * 512 + 64 * warp + 4 * (lane & 7);
    uint32_t off = OFF_B + warp * 272 + (32 * rk + 8 * tq + (lane & 4)) * 4;
    PIN(off); PINL(ph);
    mbar_wait(bar0 + 8 * XB);
    POLL { v0 = ldx16(ph); v1 = ldx16(ph + 32); RETRY(lop_x3(v0.x, v1.x, par)) }
    float d[4][4] = {};
#pragma unroll
    for (int mt = 0; mt < 4; mt++) {
      mma16(d[mt], a[0][mt], v0.x, v0.y); mma16(d[mt], a[1][mt], v0.z, v0.w);
      mma16(d[mt], a[2][mt], v1.x, v1.y); mma16(d[mt], a[3][mt], v1.z, v1.w);
    }
    float r[8];
#pragma unroll
    for (int mt = 0; mt < 4; mt++) { r[2 * mt] = d[mt][0] + d[mt][1]; r[2 * mt + 1] = d[mt][2] + d[mt][3]; }
    tred<4>(r, lane, 2); tred<2>(r, lane, 1);
    const float rc = __shfl_xor_sync(~0u, (lane & 4) ? r[0] : r[1], 4);
    const uint32_t wd = (lane & 4) ? pack2(rc, r[1]) : pack2(r[0], rc);
    const uint32_t w1 = __shfl_down_sync(~0u, wd, 8), w2 = __shfl_down_sync(~0u, wd, 16), w3 = __shfl_down_sync(~0u, wd, 24);
    asm volatile("{.reg .pred p; setp.lt.s32 p, %7, 8; @p st.shared.v4.b32 [%0], {%2,%3,%4,%5};\n"
                 "@p st.async.shared::cluster.mbarrier::complete_tx::bytes.v4.b32 [%1], {%2,%3,%4,%5}, [%6];}"
                 ::"r"(sb + off), "r"(rsb + off), "r"(wd), "r"(w1), "r"(w2), "r"(w3), "r"(rsb + OFF_BAR + 8 * QB), "r"(lane) : "memory");
    __syncwarp();
    arrive2(bar0 + 8 * QB, 0, lane == 0, false);
    arrive2(bar0 + 8 * (EB + 2), rsb + OFF_BAR + 8 * (EB + 2), lane == 0, lane == 0);
  }
  {
    uint32_t a[8][4];
    uint32_t a_bq = sb + OFF_B + (lane & 7) * 272 + (lane >> 3) * 16;
    unsigned* p_qa = g_qa + b * 64 + 8 * warp + 4 * lane;
    PIN(a_bq); PINL(p_qa);
    mbar_wait(bar0 + 8 * (FB_UK + (warp >> 2)));
    const uint32_t ab = sb + OFF_WUK + (warp >> 2) * 16384 + (16 * (warp & 3) + (lane & 15)) * 128;
#pragma unroll
    for (int s = 0; s < 8; s++) ldsm(a[s], ab + (s >> 2) * 8192 + (((2 * (s & 3) + (lane >> 4)) ^ (lane & 7)) << 4));
    mbar_wait(bar0 + 8 * QB);
    float d[4][4] = {};
#pragma unroll
    for (int y = 0; y < 4; y++) {
      uint32_t bq[4];
      ldsm(bq, a_bq + 64 * y);
      mma16(d[(2 * y) & 3], a[2 * y], bq[0], bq[1]); mma16(d[(2 * y + 1) & 3], a[2 * y + 1], bq[2], bq[3]);
    }
    float r[2] = {((d[0][0] + d[0][1]) + (d[1][0] + d[1][1])) + ((d[2][0] + d[2][1]) + (d[3][0] + d[3][1])),
                  ((d[0][2] + d[0][3]) + (d[1][2] + d[1][3])) + ((d[2][2] + d[2][3]) + (d[3][2] + d[3][3]))};
    tred<1>(r, lane, 1);
    r[0] += __shfl_xor_sync(~0u, r[0], 2);
    const float nb = __shfl_xor_sync(~0u, r[0], 4);
    const uint32_t w0 = lane < 8 ? pack2t(r[0], nb, par) : pack2(r[0], nb);
    const uint32_t w1 = __shfl_down_sync(~0u, w0, 8), w2 = __shfl_down_sync(~0u, w0, 16), w3 = __shfl_down_sync(~0u, w0, 24);
    if (lane < 2) stx16(p_qa, make_uint4(w0, w1, w2, w3));
    arrive2(bar0 + 8 * (EB + 4), rsb + OFF_BAR + 8 * (EB + 4), lane == 0, lane == 0);
  }
  {
    if (warp) nbar_arrive(3, 256); else { nbar(3, 256); if (lane == 0) CNT_ADD(2 + (b >> 6)); }
    asm volatile("setmaxnreg.inc.sync.aligned.u32 216;");
    const unsigned* pq = g_qa + rk * 4096 + tid * 4;
    uint32_t a_q = sb + OFF_Q + ((tid & 63) >> 3) * 2048 + (tid >> 6) * 128 + (((tid & 7) ^ (tid >> 6)) << 4);
    PINL(pq); PIN(a_q);
    mbar_wait(bar0 + 8 * (XB + 1));
    uint4 v[4];
    POLL {
#pragma unroll
      for (int k = 0; k < 4; k++) v[k] = ldx16(pq + 1024 * k);
      RETRY(lop_x3(v[0].x, v[1].x, par) | lop_x3(v[2].x, v[3].x, par))
    }
#pragma unroll
    for (int k = 0; k < 4; k++)
      asm volatile("st.shared.v4.b32 [%0], {%1,%2,%3,%4};" ::"r"((a_q + k * 512) ^ ((k & 1) << 6)), "r"(v[k].x), "r"(v[k].y), "r"(v[k].z), "r"(v[k].w) : "memory");
    if (warp >= 4) nbar_arrive(1, 256); else nbar(1, 256);
  }
  sb = __shfl_sync(~0u, sb, 0); bar0 = sb + OFF_BAR;
  if (warp < 4) {
    uint32_t qf[32][4];
#pragma unroll
    for (int s = 0; s < 32; s++) ldsm(qf[s], sb + OFF_Q + (s >> 2) * 2048 + (lane & 15) * 128 + (((2 * (s & 3) + (lane >> 4)) ^ (lane & 7)) << 4));
    float l0 = 0.f, l1 = 0.f, m0 = -1e30f, m1 = -1e30f;
    const float sc = 0.08838834764831845f * 1.4426950408889634f;
    const uint32_t kofs = (16 * warp + 8 * (lane >> 4) + (lane & 7)) * 128 + ((((lane >> 3) & 1) ^ (lane & 7)) << 4);
    uint32_t st = sb;
#pragma unroll 1
    for (int t = 0; t < 8; t++) {
      float sa[4][4] = {};
#pragma unroll
      for (int hf = 0; hf < 2; hf++) {
        const int n = 2 * t + hf;
        mbar_wait(bar0 + 8 * (FB_KV + n));
        uint32_t kf[16][4];
#pragma unroll
        for (int y = 0; y < 16; y++) ldsm(kf[y], st + (y >> 2) * 8192 + (kofs ^ ((y & 3) << 5)));
#pragma unroll
        for (int y = 0; y < 16; y++) {
          mma16(sa[(2 * y) & 3], qf[16 * hf + y], kf[y][0], kf[y][1]); mma16(sa[((2 * y) & 3) + 1], qf[16 * hf + y], kf[y][2], kf[y][3]);
        }
        __syncwarp();
        arrive2(bar0 + 8 * (EB + NSLOT + n), rsb + OFF_BAR + 8 * (EB + NSLOT + n), lane == 0 && n < 14, lane == 0 && n < 16 - NSLOT);
        if (hf == 0) arrive2(bar0 + 8 * EB, 0, lane == 0 && t == 0, false);
        st = st + SLOT == sb + NSLOT * SLOT ? sb : st + SLOT;
      }
#pragma unroll
      for (int i = 0; i < 4; i++) { sa[0][i] = (sa[0][i] + sa[2][i]) * sc; sa[1][i] = (sa[1][i] + sa[3][i]) * sc; }
      float cm[2] = {fmaxf(fmaxf(sa[0][0], sa[0][1]), fmaxf(sa[1][0], sa[1][1])), fmaxf(fmaxf(sa[0][2], sa[0][3]), fmaxf(sa[1][2], sa[1][3]))};
      tmax<1>(cm, lane, 1);
      cm[0] = fmaxf(cm[0], __shfl_xor_sync(~0u, cm[0], 2));
      float* pm = s_sm + (t & 1) * 64;
      if (tq < 2) pm[(g + 8 * tq) * 4 + warp] = cm[0];
      if (t >= 2) nbar(6 + (t & 1), 256); else nbar(3, 128);
      const float4 a0 = *(const float4*)(pm + g * 4), b0 = *(const float4*)(pm + g * 4 + 32);
      const float n0 = fmaxf(fmaxf(fmaxf(a0.x, a0.y), fmaxf(a0.z, a0.w)), m0), n1 = fmaxf(fmaxf(fmaxf(b0.x, b0.y), fmaxf(b0.z, b0.w)), m1);
      uint32_t pk[4];
#pragma unroll
      for (int i = 0; i < 2; i++) { pk[2 * i] = pack2(ex2(sa[i][0] - n0), ex2(sa[i][1] - n0)); pk[2 * i + 1] = pack2(ex2(sa[i][2] - n1), ex2(sa[i][3] - n1)); }
      *(uint4*)(smem + OFF_P + (t & 1) * 2048 + tid * 16) = make_uint4(pk[0], pk[1], pk[2], pk[3]);
      const float al0 = ex2(m0 - n0), al1 = ex2(m1 - n1);
      if (tid < 32 && tq == 0) *(float2*)(s_sm + 192 + (t & 1) * 16 + 2 * g) = make_float2(al0, al1);
      nbar_arrive(4 + (t & 1), 256);
      m0 = n0; m1 = n1;
      l0 = l0 * al0 + (bflo(pk[0]) + bfhi(pk[0])) + (bflo(pk[2]) + bfhi(pk[2]));
      l1 = l1 * al1 + (bflo(pk[1]) + bfhi(pk[1])) + (bflo(pk[3]) + bfhi(pk[3]));
    }
    float lr[2] = {l0, l1};
    tred<1>(lr, lane, 1);
    lr[0] += __shfl_xor_sync(~0u, lr[0], 2);
    if (tq < 2) s_sm[128 + (g + 8 * tq) * 4 + warp] = lr[0];
    nbar(3, 128);
    if (warp == 0 && tq < 2) {
      const float4 a0 = *(const float4*)(s_sm + 128 + (g + 8 * tq) * 4);
      stx8(g_ml + (16 * rk + g + 8 * tq) * 64 + pr, make_uint2(fbits(tq ? m1 : m0), fbits((a0.x + a0.y) + (a0.z + a0.w))));
    }
    if (warp == 0) { __syncwarp(); if (lane == 0) CNT_ADD(96 + 32 * rk); }
    nbar(2, 288);
    if (tid == 0) asm volatile("red.relaxed.gpu.global.xor.b64 [%0], %1;" ::"l"(scr->cnt + 32 + 32 * rk), "l"(1ull << pr) : "memory");
  } else {
    float o[16][4] = {};
    const uint32_t vofs = (warp & 1) * 16384 + (lane & 15) * 128 + (((lane >> 4) ^ (lane & 7)) << 4);
    const int hf = (warp >> 1) & 1;
    uint32_t st = sb + hf * SLOT;
    auto pv = [&](const int t, auto np) {
      constexpr int npre = decltype(np)::value;
      uint32_t vf[4][8][4];
      const int n = 2 * t + hf;
      mbar_wait(bar0 + 8 * (FB_KV + n));
#pragma unroll
      for (int s = 0; s < npre; s++)
#pragma unroll
        for (int y = 0; y < 8; y++) ldsm_t(vf[s][y], st + (y >> 2) * 8192 + s * 2048 + (vofs ^ ((y & 3) << 5)));
      nbar(4 + (t & 1), 256);
      const float2 al = *(const float2*)(s_sm + 192 + (t & 1) * 16 + 2 * g);
      uint4 pf[4];
#pragma unroll
      for (int s = 0; s < 4; s++) pf[s] = *(const uint4*)(smem + OFF_P + (t & 1) * 2048 + s * 512 + lane * 16);
      if (t < 6) nbar_arrive(6 + (t & 1), 256);
#pragma unroll
      for (int s = npre; s < 4; s++)
#pragma unroll
        for (int y = 0; y < 8; y++) ldsm_t(vf[s][y], st + (y >> 2) * 8192 + s * 2048 + (vofs ^ ((y & 3) << 5)));
#pragma unroll
      for (int nt = 0; nt < 16; nt++) { o[nt][0] *= al.x; o[nt][1] *= al.x; o[nt][2] *= al.y; o[nt][3] *= al.y; }
#pragma unroll
      for (int s = 0; s < 4; s++) {
        const uint32_t pa[4] = {pf[s].x, pf[s].y, pf[s].z, pf[s].w};
#pragma unroll
        for (int y = 0; y < 8; y++) { mma16(o[2 * y], pa, vf[s][y][0], vf[s][y][1]); mma16(o[2 * y + 1], pa, vf[s][y][2], vf[s][y][3]); }
      }
      __syncwarp();
      arrive2(bar0 + 8 * (EB + NSLOT + n), rsb + OFF_BAR + 8 * (EB + NSLOT + n), lane == 0 && n < 14, lane == 0 && n < 16 - NSLOT);
      st = st + 2 * SLOT >= sb + NSLOT * SLOT ? st - (NSLOT - 2) * SLOT : st + 2 * SLOT;
    };
#pragma unroll 1
    for (int t = 0; t < 7; t++) pv(t, IC<NPRE0>());
    pv(7, IC<NPRE1>());
    uint4* po = g_xo + ((size_t)((16 * rk + (g & 6)) * 4 + warp - 4) * 64 + pr) * RS + (lane & 7);
    const bool odd = lane & 4;
#pragma unroll
    for (int e = 0; e < 2; e++)
#pragma unroll
      for (int j2 = 0; j2 < 2; j2++) {
        uint32_t c0[4], c1[4];
#pragma unroll
        for (int i = 0; i < 4; i++) {
          c0[i] = i ? pack2(o[8 * j2 + i][2 * e], o[8 * j2 + i][2 * e + 1]) : pack2t(o[8 * j2][2 * e], o[8 * j2][2 * e + 1], par);
          c1[i] = i ? pack2(o[8 * j2 + 4 + i][2 * e], o[8 * j2 + 4 + i][2 * e + 1]) : pack2t(o[8 * j2 + 4][2 * e], o[8 * j2 + 4][2 * e + 1], par);
          const uint32_t r = __shfl_xor_sync(~0u, odd ? c0[i] : c1[i], 4);
          if (odd) c0[i] = r; else c1[i] = r;
        }
        stx16(po + e * 8 * 4 * 64 * RS + 8 * j2, make_uint4(c0[0], c0[1], c0[2], c0[3]));
        stx16(po + (e * 8 + 1) * 4 * 64 * RS + 8 * j2, make_uint4(c1[0], c1[1], c1[2], c1[3]));
      }
    nbar_arrive(2, 288);
  }
  tail(smem, scr, x, out, par, epoch, warp);
}

static void launch(void* const* d_in, void* d_out) {
  static TMaps tms;
  static bool init = false;
  static void* scr = nullptr;
  if (!init) {
    void* fn = nullptr; cudaDriverEntryPointQueryResult qr;
    cudaGetDriverEntryPoint("cuTensorMapEncodeTiled", &fn, cudaEnableDefault, &qr);
    EncFn f = (EncFn)fn;
    const CUtensorMapSwizzle S32 = CU_TENSOR_MAP_SWIZZLE_32B, S64 = CU_TENSOR_MAP_SWIZZLE_64B, S128 = CU_TENSOR_MAP_SWIZZLE_128B;
    const CUtensorMapL2promotion P128 = CU_TENSOR_MAP_L2_PROMOTION_L2_128B, P256 = CU_TENSOR_MAP_L2_PROMOTION_L2_256B;
    enc3d(f, &tms.m[0], d_in[2], 64, 512, 64, 8192, 128, 64, 128, 1, S128, P128);
    enc3d(f, &tms.m[1], d_in[3], 64, 512, 64, 8192, 128, 64, 64, 2, S128, P256);
    enc3d(f, &tms.m[2], d_in[1], 64, SK, 8, 1024, 128, 64, 64, 2, S128, P256);
    enc3d(f, &tms.m[3], d_in[11], 3072, 256, 2, 6144, 256 * 6144, 16, 256, 2, S32, P128);
    enc3d(f, &tms.m[4], d_in[4], 64, 512, 64, 8192, 128, 64, 64, 2, S128, P256);
    enc3d(f, &tms.m[5], d_in[5], 512, 128, 32, 1024, 128 * 1024, 64, 128, 1, S128, P128);
    enc3d(f, &tms.m[6], d_in[7], 1792, 256, 2, 3584, 256 * 3584, 32, 256, 1, S64, P128);
    enc3d(f, &tms.m[7], d_in[8], 1792, 256, 2, 3584, 256 * 3584, 32, 256, 1, S64, P128);
    enc3d(f, &tms.m[8], d_in[9], 64, 1792, 8, 1024, 128, 64, 16, 8, S128, P256);
    cudaFuncSetAttribute(fused_kernel, cudaFuncAttributeMaxDynamicSharedMemorySize, SMEM_BYTES);
    cudaGetSymbolAddress(&scr, g_scr);
    init = true;
  }
  fused_kernel<<<NCTA, 384, SMEM_BYTES>>>((const bf16*)d_in[0], (const bf16*)d_in[10], (const bf16*)d_in[11], (bf16*)d_out, (Scratch*)scr, tms);
}

}

extern "C" void kernel_launch(void* const* d_in, const int* in_sizes, int n_in, void* d_out, int out_size) {
  static int big = -1;
  if (big < 0) big = v9::fits();
  if (big) v9::launch(d_in, d_out); else v8::launch(d_in, d_out);
}
```

```cpp
#include <cuda_runtime.h>
#include <cuda_bf16.h>
#include <cuda.h>
#include <stdint.h>
#include <stdio.h>
#include <stdlib.h>

typedef CUresult (*EncFn)(CUtensorMap*, CUtensorMapDataType, cuuint32_t, void*, const cuuint64_t*, const cuuint64_t*,
                          const cuuint32_t*, const cuuint32_t*, CUtensorMapInterleave, CUtensorMapSwizzle,
                          CUtensorMapL2promotion, CUtensorMapFloatOOBfill);

static void enc3d(EncFn fn, CUtensorMap* tm, void* p, uint64_t d0, uint64_t d1, uint64_t d2, uint64_t s1, uint64_t s2, uint32_t b0,
                  uint32_t b1, uint32_t b2, CUtensorMapSwizzle sw, CUtensorMapL2promotion pr) {
  cuuint64_t gd[3] = {d0, d1, d2}, gs[2] = {s1, s2};
  cuuint32_t bx[3] = {b0, b1, b2}, es[3] = {1, 1, 1};
  fn(tm, CU_TENSOR_MAP_DATA_TYPE_BFLOAT16, 3, p, gd, gs, bx, es, CU_TENSOR_MAP_INTERLEAVE_NONE, sw, pr, CU_TENSOR_MAP_FLOAT_OOB_FILL_NONE);
}

namespace v9 {
typedef __nv_bfloat16 bf16;
#define SK 32768
#define SPIN_MAX (1 << 20)
template <int N> struct IC { static constexpr int value = N; };

__device__ __forceinline__ uint32_t s2u(const void* p) { return (uint32_t)__cvta_generic_to_shared(p); }
__device__ __forceinline__ float bflo(uint32_t u) { return __uint_as_float(u << 16); }
__device__ __forceinline__ float bfhi(uint32_t u) { return __uint_as_float(u & 0xffff0000u); }
__device__ __forceinline__ float u2f(uint32_t u) { return __uint_as_float(u); }
__device__ __forceinline__ void fma8(float* acc, uint4 v, float s) {
  acc[0] += s * bflo(v.x); acc[1] += s * bfhi(v.x); acc[2] += s * bflo(v.y); acc[3] += s * bfhi(v.y);
  acc[4] += s * bflo(v.z); acc[5] += s * bfhi(v.z); acc[6] += s * bflo(v.w); acc[7] += s * bfhi(v.w);
}
__device__ __forceinline__ uint32_t pack2(float a, float b) {
  __nv_bfloat162 p = __floats2bfloat162_rn(a, b); return *(uint32_t*)&p;
}
__device__ __forceinline__ float bfr(float v) { return bfhi(pack2(v, v)); }
__device__ __forceinline__ float silu_bf(float c) { return bfr(__fdividef(c, 1.f + __expf(-c))); }
#define fbits(v) ((__float_as_uint(v) & ~1u) | par)
__device__ __forceinline__ uint32_t pack2t(float a, float b, unsigned par) {
  const uint32_t ua = ((__float_as_uint(a) + ((par ^ 1) << 16)) & 0xFFFE0000u) | (par << 16);
  return __byte_perm(ua, pack2(b, b), 0x7632);
}
__device__ __forceinline__ void nbar(int id, int n) { asm volatile("bar.sync %0, %1;" ::"r"(id), "r"(n) : "memory"); }
__device__ __forceinline__ void nbar_arrive(int id, int n) { asm volatile("bar.arrive %0, %1;" ::"r"(id), "r"(n) : "memory"); }
__device__ __forceinline__ uint4 ldc16(const void* p) {
  uint4 v; asm volatile("ld.relaxed.cta.global.v4.u32 {%0,%1,%2,%3}, [%4];" : "=r"(v.x), "=r"(v.y), "=r"(v.z), "=r"(v.w) : "l"(p) : "memory"); return v;
}
__device__ __forceinline__ unsigned ldc4(const void* p) {
  unsigned v; asm volatile("ld.relaxed.cta.global.u32 %0, [%1];" : "=r"(v) : "l"(p) : "memory"); return v;
}
__device__ __forceinline__ uint4 ldx16(const void* p) {
  uint4 v; asm volatile("ld.relaxed.gpu.global.v4.u32 {%0,%1,%2,%3}, [%4];" : "=r"(v.x), "=r"(v.y), "=r"(v.z), "=r"(v.w) : "l"(p) : "memory"); return v;
}
__device__ __forceinline__ unsigned ldx4(const void* p) {
  unsigned v; asm volatile("ld.relaxed.gpu.global.u32 %0, [%1];" : "=r"(v) : "l"(p) : "memory"); return v;
}
__device__ __forceinline__ unsigned long long ldx64(const void* p) {
  unsigned long long v; asm volatile("ld.relaxed.gpu.global.u64 %0, [%1];" : "=l"(v) : "l"(p) : "memory"); return v;
}
__device__ __forceinline__ void stx16(void* p, uint4 v) {
  asm volatile("st.relaxed.gpu.global.v4.u32 [%0], {%1,%2,%3,%4};" ::"l"(p), "r"(v.x), "r"(v.y), "r"(v.z), "r"(v.w) : "memory");
}
__device__ __forceinline__ void stx8(void* p, uint2 v) { asm volatile("st.relaxed.gpu.global.v2.u32 [%0], {%1,%2};" ::"l"(p), "r"(v.x), "r"(v.y) : "memory"); }
__device__ __forceinline__ void stx4(void* p, unsigned v) { asm volatile("st.relaxed.gpu.global.u32 [%0], %1;" ::"l"(p), "r"(v) : "memory"); }
__device__ __forceinline__ void pub4(void* p, unsigned v) { asm volatile("red.relaxed.gpu.global.xor.b32 [%0], %1;" ::"l"(p), "r"(v) : "memory"); }
__device__ __forceinline__ void pub8(void* p, unsigned lo, unsigned hi) {
  asm volatile("{.reg .b64 t; mov.b64 t, {%1, %2}; red.relaxed.gpu.global.xor.b64 [%0], t;}" ::"l"(p), "r"(lo), "r"(hi) : "memory");
}
__device__ __forceinline__ unsigned lop_x3(unsigned a, unsigned b, unsigned c) {
  unsigned d; asm("lop3.b32 %0, %1, %2, %3, 0x7E;" : "=r"(d) : "r"(a), "r"(b), "r"(c)); return d; }
__device__ __forceinline__ unsigned or3(unsigned a, unsigned b, unsigned c) {
  unsigned d; asm("lop3.b32 %0, %1, %2, %3, 0xFE;" : "=r"(d) : "r"(a), "r"(b), "r"(c)); return d; }
__device__ __forceinline__ unsigned and3(unsigned a, unsigned b, unsigned c) {
  unsigned d; asm("lop3.b32 %0, %1, %2, %3, 0x80;" : "=r"(d) : "r"(a), "r"(b), "r"(c)); return d; }
__device__ __forceinline__ unsigned dep16(const uint32_t* f) {
  unsigned d = 0;
#pragma unroll
  for (int i = 0; i < 8; i++) d = or3(d, f[8 * i], f[8 * i + 4]);
  return d;
}
__device__ __forceinline__ uint2 ldx8(const void* p) {
  uint2 v; asm volatile("{.reg .b64 t; ld.relaxed.gpu.global.b64 t, [%2]; mov.b64 {%0, %1}, t;}" : "=r"(v.x), "=r"(v.y) : "l"(p) : "memory"); return v;
}
__device__ __forceinline__ float lds4(uint32_t a) { float v; asm volatile("ld.shared.f32 %0, [%1];" : "=f"(v) : "r"(a) : "memory"); return v; }
__device__ __forceinline__ float shx(float v, int m) {
  float r; asm volatile("shfl.sync.bfly.b32 %0, %1, %2, 0x1f, 0xffffffff;" : "=f"(r) : "f"(v), "r"(m)); return r;
}
__device__ __forceinline__ uint32_t mbar_test(uint32_t bar, uint32_t ph) {
  uint32_t ok;
  asm volatile("{.reg .pred p; mbarrier.test_wait.parity.shared::cta.b64 p, [%1], %2; vote.sync.all.pred p, p, 0xffffffff; selp.u32 %0, 1, 0, p;}"
               : "=r"(ok) : "r"(bar), "r"(ph) : "memory");
  return ok;
}
#define X16(v) (lop_x3(v.x, v.y, par) | lop_x3(v.z, v.w, par))
#define RETRY(bad) if (!__any_sync(~0u, (bad) & 1) || ++it_ >= SPIN_MAX) break;
#define POLL _Pragma("unroll 1") for (int it_ = 0;;)
__device__ __forceinline__ void mbar_wait(uint32_t bar, uint32_t ph = 0) {
  asm volatile("{.reg .pred p; .reg .u32 n; mov.u32 n, 0;\n"
               "W%=: mbarrier.try_wait.parity.shared::cta.b64 p, [%0], %1; add.u32 n, n, 1; setp.lt.and.u32 p, n, 0x100000, !p; @p bra W%=;}"
               ::"r"(bar), "r"(ph) : "memory");
}
__device__ __forceinline__ float ex2(float v) { float r; asm("ex2.approx.ftz.f32 %0, %1;" : "=f"(r) : "f"(v)); return r; }
__device__ __forceinline__ float rcp(float v) { float r; asm("rcp.approx.ftz.f32 %0, %1;" : "=f"(r) : "f"(v)); return r; }
__device__ __forceinline__ void mma16(float* d, const uint32_t* a, uint32_t b0, uint32_t b1) {
  asm volatile("mma.sync.aligned.m16n8k16.row.col.f32.bf16.bf16.f32 {%0,%1,%2,%3}, {%4,%5,%6,%7}, {%8,%9}, {%0,%1,%2,%3};"
               : "+f"(d[0]), "+f"(d[1]), "+f"(d[2]), "+f"(d[3]) : "r"(a[0]), "r"(a[1]), "r"(a[2]), "r"(a[3]), "r"(b0), "r"(b1));
}
__device__ __forceinline__ void mma16c(float* d, const uint32_t* a, uint32_t b0, uint32_t b1, const float* c) {
  asm volatile("mma.sync.aligned.m16n8k16.row.col.f32.bf16.bf16.f32 {%0,%1,%2,%3}, {%4,%5,%6,%7}, {%8,%9}, {%10,%11,%12,%13};"
               : "=f"(d[0]), "=f"(d[1]), "=f"(d[2]), "=f"(d[3])
               : "r"(a[0]), "r"(a[1]), "r"(a[2]), "r"(a[3]), "r"(b0), "r"(b1), "f"(c[0]), "f"(c[1]), "f"(c[2]), "f"(c[3]));
}
__device__ __forceinline__ float4 lds16(uint32_t a) {
  float4 v; asm volatile("ld.shared.v4.f32 {%0,%1,%2,%3}, [%4];" : "=f"(v.x), "=f"(v.y), "=f"(v.z), "=f"(v.w) : "r"(a) : "memory"); return v;
}
__device__ __forceinline__ void sts4(uint32_t a, float v) { asm volatile("st.shared.f32 [%0], %1;" ::"r"(a), "f"(v) : "memory"); }
__device__ __forceinline__ void sts16(uint32_t a, uint4 v) {
  asm volatile("st.shared.v4.b32 [%0], {%1,%2,%3,%4};" ::"r"(a), "r"(v.x), "r"(v.y), "r"(v.z), "r"(v.w) : "memory");
}
__device__ __forceinline__ void ldsm_t(uint32_t* r, uint32_t a) {
  asm volatile("ldmatrix.sync.aligned.m8n8.x4.trans.shared.b16 {%0,%1,%2,%3}, [%4];" : "=r"(r[0]), "=r"(r[1]), "=r"(r[2]), "=r"(r[3]) : "r"(a) : "memory");
}
__device__ __forceinline__ void ldsm(uint32_t* r, uint32_t a) {
  asm volatile("ldmatrix.sync.aligned.m8n8.x4.shared.b16 {%0,%1,%2,%3}, [%4];" : "=r"(r[0]), "=r"(r[1]), "=r"(r[2]), "=r"(r[3]) : "r"(a) : "memory");
}
__device__ __forceinline__ uint32_t mapa(uint32_t a, uint32_t r) {
  uint32_t v; asm volatile("mapa.shared::cluster.u32 %0, %1, %2;" : "=r"(v) : "r"(a), "r"(r)); return v;
}
__device__ __forceinline__ unsigned long long mapg(uint32_t a, uint32_t r) {
  unsigned long long v;
  asm volatile("{.reg .u32 t; .reg .u64 u; mapa.shared::cluster.u32 t, %1, %2; cvt.u64.u32 u, t; cvta.shared::cluster.u64 %0, u;}" : "=l"(v) : "r"(a), "r"(r));
  return v;
}
template <int N>
__device__ __forceinline__ void tred(float* a, int lane, int m) {
  const bool hi = lane & m;
#pragma unroll
  for (int i = 0; i < N; i++) {
    float send = hi ? a[i] : a[i + N], keep = hi ? a[i + N] : a[i];
    a[i] = keep + __shfl_xor_sync(~0u, send, m);
  }
}
template <int N>
__device__ __forceinline__ void tmax(float* a, int lane, int m) {
  const bool hi = lane & m;
#pragma unroll
  for (int i = 0; i < N; i++) {
    float send = hi ? a[i] : a[i + N], keep = hi ? a[i + N] : a[i];
    a[i] = fmaxf(keep, __shfl_xor_sync(~0u, send, m));
  }
}
__device__ __forceinline__ void arrive_n(uint32_t bar, bool on, int cnt) {
  asm volatile("{.reg .pred p; setp.ne.s32 p, %1, 0; @p mbarrier.arrive.shared::cta.b64 _, [%0], %2;}" ::"r"(bar), "r"((int)on), "r"(cnt) : "memory");
}
__device__ __forceinline__ unsigned long long stream_policy() {
  unsigned long long p;
  asm volatile("createpolicy.fractional.L2::evict_first.b64 %0, 1.0;" : "=l"(p));
  return p;
}
__device__ __forceinline__ void tma3d(uint32_t dst, const CUtensorMap* tm, uint32_t bar, int c0, int c1, int c2) {
  asm volatile("cp.async.bulk.tensor.3d.shared::cluster.global.mbarrier::complete_tx::bytes.L2::cache_hint [%0], [%1, {%3, %4, %5}], [%2], %6;"
               ::"r"(dst), "l"(tm), "r"(bar), "r"(c0), "r"(c1), "r"(c2), "l"(stream_policy()) : "memory");
}
__device__ __forceinline__ void spin_until(unsigned t) { while ((int)((unsigned)clock() - t) < 0) {} }
__device__ __forceinline__ void wait_until(unsigned t) {
  unsigned now;
  do { asm volatile("mov.u32 %0, %%globaltimer_lo;" : "=r"(now)); } while ((int)(now - t) < 0);
}
__device__ __forceinline__ void sleep_until(unsigned t) {
  unsigned now;
#pragma unroll 1
  do {
    __nanosleep(200);
    asm volatile("mov.u32 %0, %%globaltimer_lo;" : "=r"(now));
  } while ((int)(now - t) < 0);
}
#define PIN(x) asm volatile("" : "+r"(x))
#define PINL(x) asm volatile("" : "+l"(x))
#define BAR_ARRIVE(i) asm volatile("mbarrier.arrive.shared::cta.b64 _, [%0];" ::"r"(bar0 + 8 * (i)) : "memory")
#define LANE0(op, p, c, v) asm volatile("{.reg .pred q; setp.eq.s32 q, %2, 0; @q " op " [%0], %1;}" ::"l"((p) + lane), c(v), "r"(lane) : "memory")
#define CNT_ADD(c) LANE0("red.relaxed.gpu.global.add.u32", scr->cnt + (c), "r", 1)
#define BAR_INIT(i, cnt) asm volatile("mbarrier.init.shared::cta.b64 [%0], %1;" ::"r"(bar0 + 8 * (i)), "r"(cnt) : "memory")
#define BAR_ARM(i, bytes) asm volatile("mbarrier.arrive.expect_tx.shared::cta.b64 _, [%0], %1;" ::"r"(bar0 + 8 * (i)), "r"(bytes) : "memory")
struct TMaps { CUtensorMap m[9]; };

#define NCTA9 120
#define TAU 20
#define NSL 100
#define NPE 1
#define QN 4
#define FDLY 60
#define VJ 1
#define NPO 3
#define VDLY 150
#define O_Q 131072
#define O_LZ 163840
#define O_CTX 196608
#define O_HZ 198656
#define O_HW 200704
#define O_X 201728
#define O_P 218112
#define O_B 222208
#define O_R 224512
#define O_SILU 228608
#define O_SM 229632
#define O_BAR 231424
#define O_EP (O_BAR + 256)
#define O_DBG (O_EP + 16)
#define SMEM9 (O_DBG + 144)
#define B_FULL 0
#define B_FM 8
#define B_EMPTY 10
#define B_EM 18
#define B_LZ 18
#define B_Q2 19
#define B_H 20
#define B_QF 21
#define B_TAB 22
#define B_W 23
#define B_ST 24
#define B_HZ 25
#define B_WZ 26
#define B_G2 28
#define B_G 27
enum { T_WQ, T_WUK, T_KV, T_MOD, T_UV, T_WO, T_GU, T_DN = 8 };
#define NBIG 40
struct Sched { unsigned zero, dth; uint2 r[3][8]; unsigned nr[3], nt[3], dt, t4, d4, d6, wt, pad; };

struct __align__(128) Scratch {
  unsigned cnt[8 * 32];
  uint2 rec[32 * 4 * 8 * 64];
  uint2 hdr[32 * 16];
  unsigned h[8 * 256];
  uint4 qa[2048];
  unsigned xao[8 * 512];
  unsigned xab[8 * 256];
  unsigned xm[2048];
};
__device__ Scratch g_scr;
#define SMEM_BASE 1024u
#define DSC ((SMEM_BASE >> 4) | (1u << 16))
#define HI128 (64u | (1u << 30))
#define HI64 (32u | (2u << 30))
template <int TA, int TB, unsigned HIA, unsigned HIB>
__device__ __forceinline__ void wgmma32(float* d, uint32_t da, uint32_t db, int acc) {
  asm volatile("{.reg .pred p; .reg .b64 da, db; setp.ne.b32 p, %18, 0; mov.b64 da, {%16, %21}; mov.b64 db, {%17, %22};\n"
               "wgmma.mma_async.sync.aligned.m64n32k16.f32.bf16.bf16 "
               "{%0,%1,%2,%3,%4,%5,%6,%7,%8,%9,%10,%11,%12,%13,%14,%15}, da, db, p, 1, 1, %19, %20;}"
               : "+f"(d[0]), "+f"(d[1]), "+f"(d[2]), "+f"(d[3]), "+f"(d[4]), "+f"(d[5]), "+f"(d[6]), "+f"(d[7]),
                 "+f"(d[8]), "+f"(d[9]), "+f"(d[10]), "+f"(d[11]), "+f"(d[12]), "+f"(d[13]), "+f"(d[14]), "+f"(d[15])
               : "r"(da), "r"(db), "r"(acc), "n"(TA), "n"(TB), "n"(HIA), "n"(HIB));
}
__device__ __forceinline__ void wgmma32r(float* d, const uint32_t* a, uint32_t db) {
  asm volatile("{.reg .b64 db; mov.b64 db, {%20, %21};\n"
               "wgmma.mma_async.sync.aligned.m64n32k16.f32.bf16.bf16 "
               "{%0,%1,%2,%3,%4,%5,%6,%7,%8,%9,%10,%11,%12,%13,%14,%15}, {%16,%17,%18,%19}, db, 1, 1, 1, 1;}"
               : "+f"(d[0]), "+f"(d[1]), "+f"(d[2]), "+f"(d[3]), "+f"(d[4]), "+f"(d[5]), "+f"(d[6]), "+f"(d[7]),
                 "+f"(d[8]), "+f"(d[9]), "+f"(d[10]), "+f"(d[11]), "+f"(d[12]), "+f"(d[13]), "+f"(d[14]), "+f"(d[15])
               : "r"(a[0]), "r"(a[1]), "r"(a[2]), "r"(a[3]), "r"(db), "n"(HI64));
}
template <int N> __device__ __forceinline__ void wg_wait(float* a) {
  asm volatile("wgmma.wait_group.sync.aligned %16;"
               : "+f"(a[0]), "+f"(a[1]), "+f"(a[2]), "+f"(a[3]), "+f"(a[4]), "+f"(a[5]), "+f"(a[6]), "+f"(a[7]), "+f"(a[8]), "+f"(a[9]), "+f"(a[10]),
                 "+f"(a[11]), "+f"(a[12]), "+f"(a[13]), "+f"(a[14]), "+f"(a[15]) : "n"(N) : "memory");
}
__device__ __forceinline__ void send32(uint32_t a, uint32_t bar, float v, int lane) {
  const uint32_t w = pack2(v, __shfl_down_sync(~0u, v, 1));
  const int s = 2 * (lane & 3);
  asm volatile("{.reg .pred p; setp.eq.s32 p, %6, 0; @p st.async.shared::cluster.mbarrier::complete_tx::bytes.v4.b32 [%0], {%1,%2,%3,%4}, [%5];}"
               ::"r"(a), "r"(__shfl_sync(~0u, w, s)), "r"(__shfl_sync(~0u, w, s + 8)), "r"(__shfl_sync(~0u, w, s + 16)), "r"(__shfl_sync(~0u, w, s + 24)),
                 "r"(bar), "r"(lane & 12) : "memory");
}
__device__ __forceinline__ float sum8(uint32_t a) {
  const float4 p = lds16(a), q = lds16(a + 1024);
  return ((p.x + p.y) + (p.z + p.w)) + ((q.x + q.y) + (q.z + q.w));
}
__device__ __forceinline__ int posof(int c) { return (c & ~14) + 2 * (c & 6) + ((c >> 2) & 2); }

__global__ void __cluster_dims__(8, 1, 1) __launch_bounds__(384, 1)
fused_kernel(const bf16* __restrict__ x, const bf16* __restrict__ cvec, const bf16* __restrict__ w_mod, bf16* __restrict__ out,
             Scratch* __restrict__ scr, const __grid_constant__ Sched sch, const __grid_constant__ TMaps tms) {
  extern __shared__ __align__(1024) unsigned char smem[];
  const int tid = threadIdx.x, warp = __shfl_sync(~0u, tid >> 5, 0), lane = tid & 31;
  const int b = blockIdx.x, cl = b >> 3, rn = b & 7, rk = b & 1, hd = b >> 1, f = b - 64;
  const bool isA = b < 64;
  uint32_t sb = s2u(smem), bar0 = sb + O_BAR;
  unsigned gt_start;
  asm volatile("mov.u32 %0, %%globaltimer_lo;" : "=r"(gt_start));
  const int g = lane >> 2, tq = lane & 3;
  const int arow = 64 * rn + ((tid & 255) >> 4);
  uint4 wm[4];
  uint32_t cw, xw;
  if (warp < 8 && isA) {
    const bf16* wa = w_mod + (size_t)arow * 3072 + (lane & 8) * 64 + 64 * cl + 8 * (lane & 7);
#pragma unroll
    for (int i = 0; i < 4; i++) wm[i] = ldx16(wa + i * 16 * 3072);
    cw = ldc4(cvec + (arow & ~1) + 16 * tq);
    if (warp < 2) xw = ldc4(x + 64 * cl + (tid & 62));
  }
  if (warp == 11) {
    if (lane == 0) {
#pragma unroll
      for (int i = 0; i < B_EMPTY; i++) BAR_INIT(i, 1);
    }
    __syncwarp();
    asm volatile("fence.mbarrier_init.release.cluster;" ::: "memory");
    asm volatile("barrier.cluster.arrive.relaxed.aligned;" ::: "memory");
    if (isA) {
#pragma unroll 1
      for (int i = 0; i < 8; i++) {
        if (i >= 6) mbar_wait(bar0 + 8 * (i - 6));
        wait_until(gt_start + ((64 * i + b) * sch.dth >> 8));
        if (lane == 0) {
          BAR_ARM(i, 16384);
          tma3d(sb + i * 16384, &tms.m[i >> 2], bar0 + 8 * i, 0, i < 4 ? 128 * i : 256 * rk + 64 * (i - 4), i < 4 ? b : b & ~1);
        }
        __syncwarp();
      }
    }
  }
  if (warp == 10) {
    const unsigned ep = ldc4(&scr->cnt[0]);
    if (isA) {
      const uint4 xa = ldc16(x + 16 * lane), xb = ldc16(x + 16 * lane + 8);
      float xv[16] = {bflo(xa.x), bfhi(xa.x), bflo(xa.y), bfhi(xa.y), bflo(xa.z), bfhi(xa.z), bflo(xa.w), bfhi(xa.w),
                      bflo(xb.x), bfhi(xb.x), bflo(xb.y), bfhi(xb.y), bflo(xb.z), bfhi(xb.z), bflo(xb.w), bfhi(xb.w)};
      const float x0 = __shfl_sync(~0u, xv[0], 0);
      float s = 0, q = 0;
#pragma unroll
      for (int i = 0; i < 16; i++) { xv[i] -= x0; s += xv[i]; q += xv[i] * xv[i]; }
#pragma unroll
      for (int o = 16; o; o >>= 1) { s += __shfl_xor_sync(~0u, s, o); q += __shfl_xor_sync(~0u, q, o); }
      s *= 1.f / 512.f;
      float rstd;
      asm("rsqrt.approx.ftz.f32 %0, %1;" : "=f"(rstd) : "f"(fmaxf(q * (1.f / 512.f) - s * s, 0.f) + 1e-5f));
      *(float2*)(smem + O_SM + 1024) = make_float2(s + x0, rstd);
    }
    if (lane == 0) *(volatile unsigned*)(smem + O_EP) = ep;
    nbar_arrive(1, 288);
  }
  const int cls = isA ? (b >= NBIG) : 2, v0 = isA ? 2 : 0;
  if (warp >= 8) {
    asm volatile("setmaxnreg.dec.sync.aligned.u32 56;");
    if (warp == 8) {
      if (lane < 8) asm volatile("prefetch.tensormap [%0];" ::"l"(&tms.m[lane + 1]) : "memory");
      if ((sb & 0xFFFFFF) != SMEM_BASE) __trap();
    } else if (warp == 9) {
      if (lane == 0) {
#pragma unroll
        for (int i = B_EMPTY; i < B_EM; i++) BAR_INIT(i, 8);
        BAR_INIT(B_LZ, 8); BAR_INIT(B_Q2, 9); BAR_ARM(B_Q2, 1024);
        BAR_INIT(B_H, 1); BAR_INIT(B_QF, 1); BAR_ARM(B_QF, 32768);
        BAR_INIT(B_TAB, 1); BAR_INIT(B_W, 1); BAR_INIT(B_ST, 8); BAR_INIT(B_WZ, 1); BAR_INIT(B_HZ, 1); BAR_ARM(B_HZ, isA ? 1024 : 512); BAR_INIT(B_G, 1); BAR_INIT(B_G2, 1);
      }

    }
    if (warp != 11) {
      __syncwarp();
      asm volatile("fence.mbarrier_init.release.cluster;" ::: "memory");
      __threadfence_block();
      asm volatile("barrier.cluster.arrive.relaxed.aligned;" ::: "memory");
    }
    asm volatile("barrier.cluster.wait.acquire.aligned;" ::: "memory");
    if (warp == 8) {
      const int nr = sch.nr[cls], vl = v0 + sch.nt[cls] - 1;
      unsigned long long hist = 0;
      int v = v0;
#pragma unroll 1
      for (int rd = 0; rd < nr; rd++) {
        const uint2 e = sch.r[cls][rd];
        const int type = e.y & 15, win = (e.y >> 4) & 15, pos = b + 64 - (int)((e.y >> 8) & 255), tile = e.y >> 16;
        const bool mod = type == T_MOD;
        const int ni = mod ? 1 : type == T_DN ? 2 : 4;
        unsigned t = gt_start + (e.x & 0xffff) + (pos * sch.dt >> 8);
        const int c0 = mod ? 1024 + 32 * b : type == T_WO || type == T_DN ? 64 * rn : type == T_GU ? 32 * f : 0;
        int c1 = type == T_KV ? 64 * (tile + pos) : 0;
        int c2 = mod ? tile : type == T_WO ? 4 * cl : type == T_DN ? 2 * cl - 16 : type == T_UV ? b : 0;
        const int i1 = type == T_UV ? 128 : 0;
#pragma unroll 1
        for (int j = 0; j < ni; j++) {
          const int slot = mod ? B_FM + tile : (v & 1) * 4 + j;
          if (mod ? tile : v >= 2) mbar_wait(bar0 + 8 * (B_EMPTY + (mod ? (vl & 1) * 4 : slot)), mod ? (vl >> 1) & 1 : ((v >> 1) - 1) & 1);
          const int hw = (int)(hist >> (6 * (win - 1))) & 63;
          if (hw) mbar_wait(bar0 + 8 * (hw & 15), (hw >> 4) & 1);
          wait_until(t);
          if (lane == 0) {
            BAR_ARM(slot, 16384);
            tma3d(sb + (mod ? (tile ? O_Q : O_X) : slot * 16384), &tms.m[type == T_GU ? type + (j & 1) : type], bar0 + 8 * slot, c0, c1, c2);
          }
          __syncwarp();
          hist = hist << 6 | (32 | (mod ? 0 : (v & 2) << 3) | slot);
          t += e.x >> 16; c1 += i1;
          c2 += type == T_KV ? 2 : type == T_WO || type == T_DN ? 1 : type == T_GU ? j & 1 : 0;
        }
        v += !mod;
      }
      return;
    }
    const unsigned epoch = *(volatile unsigned*)(smem + O_EP), par = (epoch + 1) & 1;
    if (warp == 10) {
      if (isA) {
        for (int it = 0; ldx4(scr->cnt + 1) != (epoch + 1) * 128 && it < SPIN_MAX; it++) {}
        if (lane == 0) BAR_ARRIVE(B_H);
      } else mbar_wait(bar0);
      if (!(rn & (QN - 1))) {
        for (int it = 0; ldx4(scr->cnt + 32 + 32 * (rn >> 2)) != (epoch + 1) * 32 && it < SPIN_MAX; it++) {}
        if (lane == 0)
          asm volatile("cp.async.bulk.shared::cluster.global.mbarrier::complete_tx::bytes.multicast::cluster [%0], [%1], %4, [%2], %3;"
                       ::"r"(sb + O_Q + rn * 4096), "l"(scr->qa + rn * 256), "r"(bar0 + 8 * B_QF), "h"((unsigned short)0xff), "n"(4096 * QN) : "memory");
      }
      const unsigned dl = isA ? sch.d4 : sch.d6;
      unsigned tw = gt_start + sch.t4;
      if (!isA) {
        const int nt = sch.nt[2];
#pragma unroll 1
        for (int t = 0; t < nt; t++) mbar_wait(bar0 + 8 * B_EMPTY + (t & 1) * 32, (t >> 1) & 1);
        unsigned long long now;
        asm volatile("mov.u64 %0, %%globaltimer;" : "=l"(now));
        LANE0("red.relaxed.gpu.global.max.u64", scr->cnt + 130, "l", now);
        CNT_ADD(128);
        tw = (unsigned)now + 1700;
      }
      sleep_until(tw);
      uint4 an;
      for (int it = 0; an = ldx16(scr->cnt + 128), an.x != (epoch + 1) * 56 && it < SPIN_MAX; it++) {}
      wait_until(an.z + (dl >> 16));
      if (lane == 0) BAR_ARRIVE(B_G2);
      wait_until(an.z + (dl & 0xffff));
      if (lane == 0) BAR_ARRIVE(B_G);
    } else if (warp == 11) {
      {
        uint2* ph = scr->hdr + ((lane & 24) + 2 * tq + (g & 1)) * 16 + cl;
        const bool own = (lane >> 4) * 4 + tq == rn;
        if (own) { stx8(ph, make_uint2(par ^ 1, 0)); if (cl == 14) stx8(ph + 1, make_uint2(0, 0)); }
        uint32_t a_w = sb + O_HW + ((lane >> 4) * 4 + tq) * 128 + (g & 1) * 64 + ((lane >> 1) & 4);
        PIN(a_w); PINL(ph);
        const int vt = v0 + sch.nt[cls];
#pragma unroll 1
        for (int t = 0; t < vt; t++) mbar_wait(bar0 + 8 * B_EMPTY + (t & 1) * 32, (t >> 1) & 1);
        float hz[8], M;
        uint32_t wp[4];
#pragma unroll 1
        for (int e = 0; e < 2; e++) {
          POLL {
            unsigned ok = 1;
#pragma unroll
            for (int u = 0; u < 8; u++)
              asm volatile("ld.relaxed.cluster.shared.f32 %0, [%1];" : "=f"(hz[u]) : "r"(sb + O_HZ + e * 1024 + u * 128 + lane * 4) : "memory");
#pragma unroll
            for (int u = 0; u < 4; u++) ok = and3(ok, __float_as_uint(hz[u]), __float_as_uint(hz[u + 4]));
            RETRY(~ok)
          }
          if (e) break;
          M = fmaxf(fmaxf(fmaxf(hz[0], hz[1]), fmaxf(hz[2], hz[3])), fmaxf(fmaxf(hz[4], hz[5]), fmaxf(hz[6], hz[7])));
          M = u2f(fbits(M));
#pragma unroll
          for (int u = 0; u < 4; u++) {
            wp[u] = pack2(ex2(hz[u] - M), ex2(hz[u + 4] - M));
            sts4(a_w + ((rn - u) & 3) * 8, u2f(wp[u])); sts4(a_w + ((rn - u) & 3) * 8 + 32, u2f(wp[u]));
          }
          __syncwarp();
          if (lane == 0) BAR_ARRIVE(B_WZ);
        }
        float L = 0.f;
#pragma unroll
        for (int u = 0; u < 4; u++) L += bflo(wp[u]) * hz[u] + bfhi(wp[u]) * hz[u + 4];
        if (own) pub8(ph, __float_as_uint(M) | 1u, __float_as_uint(L));
      }
      if (isA) {
        mbar_wait(bar0 + 8 * B_G2);
        unsigned long long hh;
        POLL { hh = ldx64(scr->hdr + hd * 16 + (lane & 15)); RETRY((lane & 15) == 15 ? 0u : (unsigned)hh ^ par) }
        const float m = (lane & 15) == 15 ? -1e30f : u2f((unsigned)hh);
        int mi = __float_as_int(m);
        mi ^= (mi >> 31) & 0x7fffffff;
        mi = __reduce_max_sync(~0u, mi);
        mi ^= (mi >> 31) & 0x7fffffff;
        const float w = ex2(m - __int_as_float(mi));
        float L = w * u2f(hh >> 32);
#pragma unroll
        for (int o2 = 8; o2; o2 >>= 1) L += __shfl_xor_sync(~0u, L, o2);
        sts4(sb + O_SM + (384 + 2 * (lane & 6) + ((lane >> 2) & 2) + (lane & 1)) * 4, w * rcp(L));
        __syncwarp();
        if (lane == 0) BAR_ARRIVE(B_W);
      }
    } else {
#pragma unroll 4
      for (int i = 0; i < 72; i++) sts16(sb + O_LZ + i * 512 + lane * 16, make_uint4(0, 0, 0, 0));
      __syncwarp();
      if (lane < 8) asm volatile("mbarrier.arrive.release.cluster.shared::cluster.b64 _, [%0];" ::"r"(mapa(bar0 + 8 * B_LZ, lane)) : "memory");
      if (isA) {
        mbar_wait(bar0 + 8 * B_QF);
#pragma unroll 2
        for (int k = 0; k < 8; k++) {
          const uint32_t cp = ldc4(cvec + 2 * (lane + 32 * k));
          *(uint32_t*)(smem + O_SILU + (lane + 32 * k) * 4) = pack2(silu_bf(bflo(cp)), silu_bf(bfhi(cp)));
        }
        __syncwarp();
        uint32_t ab = sb + O_X + (8 * (lane >> 4) + (lane & 7)) * 64 + ((((lane >> 3) & 1) ^ ((lane >> 1) & 3)) << 4);
        float d[4][4] = {};
#pragma unroll 1
        for (int jm = 0; jm < 2; jm++) {
          mbar_wait(bar0 + 8 * (B_FM + jm));
#pragma unroll 2
          for (int s2 = 0; s2 < 8; s2++)
#pragma unroll
            for (int s = 0; s < 2; s++) {
              uint32_t a0[4], a1[4];
              const uint32_t* ps = (const uint32_t*)(smem + O_SILU) + 128 * jm + 16 * s2 + 8 * s + tq;
              ldsm_t(a0, ab + (2 * s2 + s) * 1024); ldsm_t(a1, (ab + (2 * s2 + s) * 1024) ^ 32);
              mma16(d[s], a0, ps[0], ps[4]); mma16(d[2 + s], a1, ps[0], ps[4]);
            }
          ab -= O_X - O_Q;
        }
        const float t0 = (tq & 1) ? d[0][2] + d[1][2] : d[0][0] + d[1][0], t1 = (tq & 1) ? d[2][2] + d[3][2] : d[2][0] + d[3][0];
        stx4(scr->xm + b * 32 + posof(8 * tq + g), fbits(bfr(bfr((tq & 2) ? t1 : t0) + ((b >> 4) == 2 ? 1.f : 0.f))));
        __syncwarp();
        CNT_ADD(96);
      } else sleep_until(gt_start + sch.t4);
      for (int it = 0; ldx4(scr->cnt + 96) != (epoch + 1) * 64 && it < SPIN_MAX; it++) __nanosleep(NSL);
      if (isA) {
        unsigned long long ga;
        POLL { ga = ldx64(scr->xm + 64 * rn + 2 * lane); RETRY(lop_x3((unsigned)ga, ga >> 32, par)) }
        *(float2*)(smem + O_SM + (320 + 2 * lane) * 4) = make_float2(bfhi((unsigned)ga), bfhi(ga >> 32));
      }
      __syncwarp();
      if (lane == 0) BAR_ARRIVE(B_TAB);
    }
    return;
  }

  float* s_sm = (float*)(smem + O_SM);
  unsigned par, epoch;
  asm volatile("barrier.cluster.arrive.relaxed.aligned;" ::: "memory");
  if (isA) {
    float* s_r = (float*)(smem + O_R);
    float acc[8] = {0, 0, 0, 0, 0, 0, 0, 0};
    const float sl = silu_bf((arow & 1) ? bfhi(cw) : bflo(cw));
#pragma unroll
    for (int i = 0; i < 4; i++) fma8(acc, wm[i], __shfl_sync(~0u, sl, i, 4));
    tred<4>(acc, lane, 16);
    *(float4*)(s_r + warp * 128 + 8 * (lane & 15) + ((lane >> 2) & 4)) = make_float4(acc[0], acc[1], acc[2], acc[3]);
    nbar(1, 288);
    epoch = *(volatile unsigned*)(smem + O_EP);
    par = (epoch + 1) & 1;
    if (warp < 2) {
      float t = 0.f, ca = rn == 0 ? 1.f : 0.f;
#pragma unroll
      for (int w = 0; w < 8; w++) { t += s_r[w * 128 + tid]; ca += s_r[w * 128 + 64 + tid]; }
      t += ca * ((((tid & 1) ? bfhi(xw) : bflo(xw)) - s_sm[256]) * s_sm[257]);
      const float nb = __shfl_down_sync(~0u, t, 1);
      const uint32_t w0 = lane < 8 ? pack2t(t, nb, par) : pack2(t, nb);
      const uint32_t w1 = __shfl_down_sync(~0u, w0, 8), w2 = __shfl_down_sync(~0u, w0, 16), w3 = __shfl_down_sync(~0u, w0, 24);
      if (lane < 8 && !(lane & 1)) stx16(scr->h + (rn >> 1) * 512 + (2 * cl + warp) * 32 + rk * 16 + 2 * lane, make_uint4(w0, w1, w2, w3));
      __syncwarp();
      CNT_ADD(1);
    }
    asm volatile("barrier.cluster.wait.acquire.aligned;" ::: "memory");
    const uint32_t rsb = mapa(sb, rn ^ 1);
    {
      uint32_t a[4][4][4];
      mbar_wait(bar0 + 8 * (warp >> 1));
      const uint32_t ab = sb + (64 * warp + 8 * (lane >> 4) + (lane & 7)) * 128;
#pragma unroll
      for (int s = 0; s < 4; s++)
#pragma unroll
        for (int mt = 0; mt < 4; mt++) ldsm_t(a[s][mt], ab + s * 2048 + (((2 * mt + ((lane >> 3) & 1)) ^ (lane & 7)) << 4));
      arrive_n(bar0 + 8 * (B_EMPTY + (warp >> 1)), lane == 0, 4 + (dep16(&a[0][0][0]) & sch.zero));
      uint4 v0, v1;
      const unsigned* ph = scr->h + (g >> 1) * 512 + 64 * warp + 4 * (lane & 7);
      uint32_t off = O_B + warp * 272 + (32 * rk + 8 * tq + (lane & 4)) * 4;
      PIN(off); PINL(ph);
      mbar_wait(bar0 + 8 * B_H);
      POLL { v0 = ldx16(ph); v1 = ldx16(ph + 32); RETRY(lop_x3(v0.x, v1.x, par)) }
      float d[4][4] = {};
#pragma unroll
      for (int mt = 0; mt < 4; mt++) {
        mma16(d[mt], a[0][mt], v0.x, v0.y); mma16(d[mt], a[1][mt], v0.z, v0.w);
        mma16(d[mt], a[2][mt], v1.x, v1.y); mma16(d[mt], a[3][mt], v1.z, v1.w);
      }
      float r[8];
#pragma unroll
      for (int mt = 0; mt < 4; mt++) { r[2 * mt] = d[mt][0] + d[mt][1]; r[2 * mt + 1] = d[mt][2] + d[mt][3]; }
      tred<4>(r, lane, 2); tred<2>(r, lane, 1);
      const float rc = __shfl_xor_sync(~0u, (lane & 4) ? r[0] : r[1], 4);
      const uint32_t wd = (lane & 4) ? pack2(rc, r[1]) : pack2(r[0], rc);
      const uint32_t w1 = __shfl_down_sync(~0u, wd, 8), w2 = __shfl_down_sync(~0u, wd, 16), w3 = __shfl_down_sync(~0u, wd, 24);
      asm volatile("{.reg .pred p; setp.lt.s32 p, %7, 8; @p st.shared.v4.b32 [%0], {%2,%3,%4,%5};\n"
                   "@p st.async.shared::cluster.mbarrier::complete_tx::bytes.v4.b32 [%1], {%2,%3,%4,%5}, [%6];}"
                   ::"r"(sb + off), "r"(rsb + off), "r"(wd), "r"(w1), "r"(w2), "r"(w3), "r"(rsb + O_BAR + 8 * B_Q2), "r"(lane) : "memory");
      __syncwarp();
      arrive_n(bar0 + 8 * B_Q2, lane == 0, 1);
    }
    {
      uint32_t a[2][8][4];
      uint32_t a_bq = sb + O_B + (lane & 7) * 272 + (lane >> 3) * 16;
      uint4* p_qa = scr->qa + (4 * rk + (warp >> 1)) * 256 + hd * 8 + ((4 * (warp & 1) + tq) ^ (hd & 7));
      PIN(a_bq); PINL(p_qa);
      mbar_wait(bar0 + 8 * (4 + (warp >> 1)));
      const uint32_t ab = sb + 65536 + (warp >> 1) * 16384 + (32 * (warp & 1) + (lane & 15)) * 128;
#pragma unroll
      for (int i = 0; i < 16; i++) ldsm(a[i >> 3][i & 7], ab + (i >> 3) * 2048 + ((i >> 2) & 1) * 8192 + (((2 * (i & 3) + (lane >> 4)) ^ (lane & 7)) << 4));
      arrive_n(bar0 + 8 * (B_EMPTY + 4 + (warp >> 1)), lane == 0, 4 + (dep16(&a[0][0][0]) & sch.zero));
      mbar_wait(bar0 + 8 * B_Q2);
      float d[4][4] = {};
#pragma unroll
      for (int y = 0; y < 4; y++) {
        uint32_t bq[4];
        ldsm(bq, a_bq + 64 * y);
#pragma unroll
        for (int mt = 0; mt < 2; mt++) { mma16(d[2 * mt], a[mt][2 * y], bq[0], bq[1]); mma16(d[2 * mt + 1], a[mt][2 * y + 1], bq[2], bq[3]); }
      }
      float r[4];
#pragma unroll
      for (int i = 0; i < 4; i++) r[i] = (d[i & 2][2 * (i & 1)] + d[i & 2][2 * (i & 1) + 1]) + (d[(i & 2) + 1][2 * (i & 1)] + d[(i & 2) + 1][2 * (i & 1) + 1]);
      tred<2>(r, lane, 2); tred<1>(r, lane, 1);
      const float nb = __shfl_xor_sync(~0u, r[0], 4);
      const uint32_t w0 = (lane >> 3) == (hd & 3) ? pack2t(r[0], nb, par) : pack2(r[0], nb);
      const uint32_t w1 = __shfl_down_sync(~0u, w0, 8), w2 = __shfl_down_sync(~0u, w0, 16), w3 = __shfl_down_sync(~0u, w0, 24);
      if (lane < 4) stx16(p_qa, make_uint4(w0, w1, w2, w3));
      if (warp) nbar_arrive(3, 256); else { nbar(3, 256); CNT_ADD(32 + 32 * rk); }
    }
  } else {
    nbar(1, 288);
    epoch = *(volatile unsigned*)(smem + O_EP);
    par = (epoch + 1) & 1;
    asm volatile("barrier.cluster.wait.acquire.aligned;" ::: "memory");
    mbar_wait(bar0);
  }
  asm volatile("setmaxnreg.inc.sync.aligned.u32 224;");
  uint2* p_rec = scr->rec + ((16 * (warp >> 2) + 2 * (warp & 3) + (g & 1) + 4 * (tq & 2)) * 32 + 4 * rn + (tq & 1)) * 64 + cl * 4 + (g >> 1);
  PINL(p_rec);
  {
    const unsigned inv = par ^ 1;
#pragma unroll
    for (int q = 0; q < 2; q++) { stx8(p_rec + q * 128, make_uint2(inv, 0)); if (cl == 14) stx8(p_rec + q * 128 + 4, make_uint2(0, 0)); }
    if (isA) { if (warp < 2) { stx4(scr->xao + b * 64 + tid, inv); stx4(scr->xab + cl * 256 + (2 * (rn & 3) + warp) * 32 + (rn >> 2) * 16 + (lane >> 1), inv); } }
    else if (f == 0) { stx4(out + 2 * tid, 0); __threadfence(); }
  }
  sb = __shfl_sync(~0u, sb, 0); bar0 = sb + O_BAR;
  const int nt = sch.nt[cls], wg = warp >> 2;
  uint32_t a_z[4];
#pragma unroll
  for (int u = 0; u < 4; u++) {
    const int s3 = (rn - u - (lane >> 1 & 1)) & 3;
    a_z[u] = sb + O_LZ + (s3 + 4 * (lane & 1)) * 4096 + wg * 512 + g * 64 + (((warp & 3) ^ (s3 & 1) ^ (2 * (lane & 1))) << 4);
    PIN(a_z[u]);
  }
  uint32_t z[4][4], a_w = sb + O_HW + warp * 128 + (g & 1) * 64 + (tq & 1) * 8;
  PIN(a_w);
  {
    const float sc = 0.08838834764831845f * 1.4426950408889634f;
    float mrun = -1e30f;
    float o[4][16], sx[16], mref[8];
#pragma unroll
    for (int k = 0; k < 16; k++) { o[0][k] = o[1][k] = o[2][k] = o[3][k] = sx[k] = 0.f; mref[k >> 1] = -1e30f; }
    const int key = 16 * warp + (lane & 15);
    uint32_t a_p = sb + O_P + key * 64 + (((lane >> 4) ^ ((key >> 1) & 3)) << 4);
    uint32_t a_v = sb + wg * 32768 + (8 * (lane >> 4) + (lane & 7)) * 128 + (((2 * (warp & 3) + ((lane >> 3) & 1)) ^ (lane & 7)) << 4);
    const int rot = rn + warp;
    const int qown = wg == (rn >> 2) ? -warp & 3 : -1;
    uint32_t a_own = sb + O_LZ + rn * 4096 + (warp & 3) * 1024 + g * 64 + ((tq ^ (rn & 1) ^ ((rn >> 1) & 2)) << 4);
    PIN(a_own);
    unsigned long long dst[4];
#pragma unroll
    for (int q = 0; q < 4; q++) {
      dst[q] = mapg(a_own, 4 * wg + ((q + rot) & 3));
      PINL(dst[q]);
    }
    unsigned long long a_h = mapg(sb + O_HZ + wg * 1024 + rn * 128 + lane * 4, 2 * (warp & 3));
    unsigned long long a_h1 = mapg(sb + O_HZ + wg * 1024 + rn * 128 + lane * 4, 2 * (warp & 3) + 1);
    PIN(a_p); PIN(a_v); PINL(a_h); PINL(a_h1);
    uint32_t rel = lane < 4 && lane >= 2 * wg ? 2 - (tq >> 1) : 0;
    PIN(rel);
    uint32_t ones[4] = {0x3F803F80u, 0x3F803F80u, 0x3F803F80u, 0x3F803F80u};
    PIN(ones[0]); PIN(ones[1]); PIN(ones[2]); PIN(ones[3]);
    {
      asm volatile("{.reg .pred p; .reg .u32 n; mov.u32 n, 0;\n"
                   "W%=: mbarrier.try_wait.parity.acquire.cluster.shared::cta.b64 p, [%0], 0; add.u32 n, n, 1; setp.lt.and.u32 p, n, 0x100000, !p; @p bra W%=;}"
                   ::"r"(bar0 + 8 * B_LZ) : "memory");
      mbar_wait(bar0 + 8 * B_QF);
      unsigned bad = 0;
#pragma unroll
      for (int k = 0; k < 8; k++) bad |= __float_as_uint(lds4(sb + O_Q + k * 4096 + tid * 16 + (lane >> 3) * 4)) ^ par;
      if (__builtin_expect(__any_sync(~0u, bad & 1), 0)) {
#pragma unroll 1
        for (int k = 0; k < 8; k++) {
          uint4 v;
          POLL { v = ldx16(scr->qa + k * 256 + tid); RETRY(((lane & 16) ? ((lane & 8) ? v.w : v.z) : ((lane & 8) ? v.y : v.x)) ^ par) }
          sts16(sb + O_Q + k * 4096 + tid * 16, v);
        }
        asm volatile("fence.proxy.async.shared::cta;" ::: "memory");
      }
      if (warp >= 4) nbar_arrive(1, 256); else nbar(1, 256);
    }
#pragma unroll 1
    for (int t = 0; t < nt; t++) {
      const int v = v0 + t;
      const uint32_t fb = bar0 + (v & 1) * 32, ph = (v >> 1) & 1, av = a_v + (v & 1) * 65536;
      uint32_t vf[4][4][4], cnt;
      auto landed = [&]() {
        cnt = rel + (dep16(&vf[0][0][0]) & (nt >> 8));
        PIN(cnt);
      };
      if (wg == 0) {
        const uint32_t da = DSC + (v & 1) * 4096, db = DSC + O_Q / 16;
#pragma unroll 1
        for (int j = 0; j < 4; j++) {
          mbar_wait(fb + 8 * j, ph);
          asm volatile("wgmma.fence.sync.aligned;" ::: "memory");
#pragma unroll
          for (int k = 0; k < 8; k++)
            wgmma32<0, 0, HI128, HI128>(sx, da + j * 1024 + (k >> 2) * 512 + (k & 3) * 2, db + j * 512 + (k >> 2) * 256 + (k & 3) * 2, k ? 1 : j);
          asm volatile("wgmma.commit_group.sync.aligned;" ::: "memory");
          if (j == VJ) {
#pragma unroll
            for (int i = 0; i < 16; i++) ldsm_t(vf[i >> 2][i & 3], av + (((i >> 2) + rot) & 3) * 8192 + (i & 3) * 2048);
            nbar(5, 256);
            landed();
          }
        }
      } else {
        nbar_arrive(5, 256);
#pragma unroll 1
        for (int j = 0; j < 2; j++) {
          mbar_wait(fb + 16 + 8 * j, ph);
          if (j) spin_until(clock() + VDLY);
#pragma unroll
          for (int q = 0; q < 4; q++)
            if (((q + rot) & 2) == 2 * j)
#pragma unroll
              for (int k = 0; k < 4; k++) ldsm_t(vf[q][k], av + ((q + rot) & 3) * 8192 + k * 2048);
        }
        cnt = 0;
      }
      wg_wait<0>(sx);
      asm volatile("{.reg .pred p; setp.ne.s32 p, %1, 0; @p mbarrier.arrive.shared::cta.b64 _, [%0], %1;}" ::"r"(fb + 8 * B_EMPTY + 8 * tq), "r"(cnt) : "memory");
#pragma unroll 1
      for (int pass = 0;; pass++) {
        int ex = !(t | pass);
        if (wg == 0 && (t | pass)) {
          uint32_t pk[8];
#pragma unroll
          for (int i = 0; i < 8; i++) pk[i] = pack2(ex2(sx[2 * i] * sc - mref[i & 6]), ex2(sx[2 * i + 1] * sc - mref[(i & 6) + 1]));
          asm volatile("stmatrix.sync.aligned.m8n8.x4.shared.b16 [%0], {%2,%3,%4,%5};\n"
                       "stmatrix.sync.aligned.m8n8.x4.shared.b16 [%1], {%6,%7,%8,%9};"
                       ::"r"(a_p), "r"(a_p ^ 32), "r"(pk[0]), "r"(pk[1]), "r"(pk[2]), "r"(pk[3]), "r"(pk[4]), "r"(pk[5]), "r"(pk[6]), "r"(pk[7]) : "memory");
          const uint32_t mx = __vmaxu2(__vmaxu2(__vmaxu2(pk[0], pk[1]), __vmaxu2(pk[2], pk[3])), __vmaxu2(__vmaxu2(pk[4], pk[5]), __vmaxu2(pk[6], pk[7])));
          ex = max(mx, mx << 16) > (127u + TAU) << 23;
          asm volatile("fence.proxy.async.shared::cta;" ::: "memory");
        }
        asm volatile("{.reg .pred p, q; setp.ne.s32 q, %0, 0; bar.red.or.pred p, 4, 256, q; selp.s32 %0, 1, 0, p;}" : "+r"(ex)::"memory");
        if (!ex || pass) break;
        int ln;
        asm volatile("mov.u32 %0, %%laneid;" : "=r"(ln));
        const uint32_t a_pm = sb + O_SM + ln * 16;
        if (wg == 0) {
          float cm[8];
#pragma unroll
          for (int i = 0; i < 8; i++) cm[i] = fmaxf(sx[2 * (i & 6) + (i & 1)], sx[2 * (i & 6) + (i & 1) + 2]);
          tmax<4>(cm, lane, 16); tmax<2>(cm, lane, 8); tmax<1>(cm, lane, 4);
          sts4(a_pm + warp * 4, cm[0] * sc);
        }
        nbar(4, 256);
        const float4 pm = lds16(a_pm);
        const float mn = u2f(__float_as_uint(fmaxf(fmaxf(fmaxf(pm.x, pm.y), fmaxf(pm.z, pm.w)), mrun)) | 1u), al = ex2(mrun - mn);
        mrun = mn;
#pragma unroll
        for (int i = 0; i < 8; i++) {
          const float a = __shfl_sync(~0u, al, 4 * i + (ln & 3)), aw = wg ? a : 1.f;
          mref[i] = __shfl_sync(~0u, mn, 4 * i + (ln & 3));
#pragma unroll
          for (int e = 0; e < 2; e++) {
            const int k = 2 * (i & 6) + (i & 1) + 2 * e;
            o[0][k] *= a; o[1][k] *= a; o[2][k] *= a; o[3][k] *= a; sx[k] *= aw;
          }
        }
      }
      float hv = mrun;
      if (wg) {
        asm volatile("wgmma.fence.sync.aligned;" ::: "memory");
#pragma unroll
        for (int k = 0; k < 4; k++) wgmma32r(sx, ones, DSC + O_P / 16 + k * 64);
        asm volatile("wgmma.commit_group.sync.aligned;" ::: "memory");
        landed();
        asm volatile("{.reg .pred p; setp.ne.s32 p, %1, 0; @p mbarrier.arrive.shared::cta.b64 _, [%0], %1;}" ::"r"(fb + 8 * B_EMPTY + 8 * tq), "r"(cnt) : "memory");
        wg_wait<0>(sx);
        float lv[4];
#pragma unroll
        for (int j = 0; j < 4; j++) lv[j] = (lane & 4) ? sx[4 * j + 1] : sx[4 * j];
        hv = (lane & 16) ? ((lane & 8) ? lv[3] : lv[2]) : ((lane & 8) ? lv[1] : lv[0]);
      }
      asm volatile("{.reg .pred p; setp.eq.s32 p, %3, %4; @p st.relaxed.cluster.b32 [%0], %1; @p st.relaxed.cluster.b32 [%2], %1;}"
                   ::"l"(a_h), "r"(__float_as_uint(hv) | 1u), "l"(a_h1), "r"(t), "r"(nt - 1) : "memory");
#pragma unroll
      for (int q = 0; q < 4; q++) {
        asm volatile("wgmma.fence.sync.aligned;" ::: "memory");
#pragma unroll
        for (int k = 0; k < 4; k++) wgmma32r(o[q], vf[q][k], DSC + O_P / 16 + k * 64);
        asm volatile("wgmma.commit_group.sync.aligned;" ::: "memory");
        if (q == 3) {
#pragma unroll
          for (int u = 0; u < 4; u++) ldsm_t(z[u], a_z[u] + u * 1024);
        }
        wg_wait<0>(o[q]);
#pragma unroll
        for (int j = 0; j < 2; j++)
          asm volatile("{.reg .pred p, q, r; setp.eq.s32 p, %5, %6; setp.eq.and.s32 q|r, %7, %8, p; @r st.relaxed.cluster.v4.b32 [%0], {%1,%2,%3,%4};\n"
                       "@q st.shared.v4.b32 [%9], {%1,%2,%3,%4};}"
                       ::"l"(dst[q] + j * 512), "r"(pack2t(o[q][8 * j], o[q][8 * j + 1], 1)), "r"(pack2(o[q][8 * j + 2], o[q][8 * j + 3])),
                         "r"(pack2(o[q][8 * j + 4], o[q][8 * j + 5])), "r"(pack2(o[q][8 * j + 6], o[q][8 * j + 7])), "r"(t), "r"(nt - 1),
                         "r"(qown), "r"(q), "r"(a_own + j * 512) : "memory");
      }
    }
  }
  {
    uint32_t wx[4][4];
    mbar_wait(bar0 + 8 * B_WZ);
#pragma unroll
    for (int u = 0; u < 4; u++) {
      uint2 wp;
      asm volatile("ld.shared.v2.u32 {%0, %1}, [%2];" : "=r"(wp.x), "=r"(wp.y) : "r"(a_w + u * 8) : "memory");
      const bool lo = (g >> 1) == (tq >> 1), hi = (g >> 1) == 2 + (tq >> 1);
      wx[u][0] = lo ? wp.x : 0u; wx[u][1] = lo ? wp.y : 0u; wx[u][2] = hi ? wp.x : 0u; wx[u][3] = hi ? wp.y : 0u;
    }
    auto bad = [&]() {
      const unsigned ok = and3(and3(and3(z[0][0], z[0][1], z[0][2]), and3(z[0][3], z[1][0], z[1][1]), and3(z[1][2], z[1][3], z[2][0])),
                               and3(and3(z[2][1], z[2][2], z[2][3]), and3(z[3][0], z[3][1], z[3][2]), z[3][3]), 0x10001u);
      return __any_sync(~0u, g == 0 && ok != 0x10001u);
    };
    POLL {
      if (it_)
#pragma unroll
        for (int u = 0; u < 4; u++) ldsm_t(z[u], a_z[u] + u * 1024);
      if (!bad() || ++it_ >= SPIN_MAX) break;
    }
    float d0[8][4] = {}, d[8][4], r[8];
#pragma unroll
    for (int i = 0; i < 8; i++) mma16(d0[i], wx[i >> 1], z[i >> 1][2 * (i & 1)], z[i >> 1][2 * (i & 1) + 1]);
    POLL {
#pragma unroll
      for (int u = 0; u < 4; u++) ldsm_t(z[u], a_z[u ^ 2] + u * 1024);
#pragma unroll
      for (int i = 0; i < 8; i++) mma16c(d[i], wx[(i >> 1) ^ 2], z[i >> 1][2 * (i & 1)], z[i >> 1][2 * (i & 1) + 1], d0[i]);
      if (!bad() || ++it_ >= SPIN_MAX) break;
    }
#pragma unroll
    for (int i = 0; i < 8; i++) r[i] = (tq & 2) ? ((g & 1) ? d[i][3] : d[i][2]) : ((g & 1) ? d[i][1] : d[i][0]);
#pragma unroll
    for (int q = 0; q < 2; q++) pub8(p_rec + q * 128, pack2t(r[4 * q], r[4 * q + 1], par) | 1u, pack2(r[4 * q + 2], r[4 * q + 3]));
  }
  const int vt = v0 + nt;
  const uint32_t bufa = sb + (vt & 1) * 65536, fulla = bar0 + (vt & 1) * 32, pha = (vt >> 1) & 1, phb = ((vt + 1) >> 1) & 1;
  const uint32_t bufo = sb + ((vt + 1) & 1) * 65536, fullb = bar0 + ((vt + 1) & 1) * 32;
  uint32_t a_rs = sb + O_R + (warp >> 2) * 1024 + (16 * tq + g) * 16 + ((warp + tq) & 3) * 4;
  if (isA) {
    const int row = 16 * (warp & 6) + 8 * (warp & 1) + (lane & 16) + ((lane & 7) >> 1) + 4 * (lane & 1);
    uint32_t ab = bufa + row * 128 + ((((lane >> 3) & 1) ^ (row & 7)) << 4);
    const uint2* pr = scr->rec + (hd * 32 + warp) * 64 + lane;
    uint32_t a_cb = mapa(bar0 + 8 * B_HZ, (warp & 6) + (lane >> 4)), a_c = a_cb - (O_BAR + 8 * B_HZ - O_CTX) + (2 * rn + (warp & 1)) * 64 + tq * 16;
    uint32_t a_rl = sb + O_R + (32 * (warp & 1) + lane) * 16;
    uint32_t ao = bufo + (16 * warp + 8 * (lane >> 4) + (lane & 7)) * 128 + ((((lane >> 3) & 1) ^ (lane & 7)) << 4);
    uint32_t a_cx = sb + O_CTX + (warp >> 1) * 64 + tq * 16 + (warp & 1) * 8, a_ga = sb + O_SM + (320 + posof(tid & 63)) * 4;
    unsigned* p_ao = scr->xao + b * 64 + (tid & 63);
    unsigned* p_ab = scr->xab + cl * 256 + (2 * (rn & 3) + (warp & 1)) * 32 + (rn >> 2) * 16 + (lane >> 1);
    float xv = cl == 0 ? __bfloat162float(x[64 * rn + (tid & 63)]) : 0.f;
    unsigned p2 = lane >= 28 ? 0 : par;
    PIN(ab); PINL(pr); PIN(a_cb); PIN(a_c); PIN(a_rl); PIN(a_rs); PIN(ao); PIN(a_cx); PIN(a_ga); PINL(p_ao); PINL(p_ab); PIN(p2);
    asm volatile("" : "+f"(xv));
    uint32_t aw[4][4][4];
    auto wo = [&](const int j) {
      mbar_wait(fullb + 8 * j, phb);
#pragma unroll
      for (int mt = 0; mt < 4; mt++) ldsm_t(aw[j][mt], (ao + j * 16384) ^ (mt << 5));
    };
    {
      uint32_t a[4][4][4];
      uint2 z[4], y[4] = {};
      float d[4][4] = {}, r[8];
      mbar_wait(fulla, pha);
      POLL {
#pragma unroll
        for (int q = 0; q < 4; q++) z[q] = ldx8(pr + q * 512);
        RETRY(lop_x3(z[0].x, z[1].x, par) | lop_x3(z[2].x, z[3].x, par))
      }
#pragma unroll
      for (int q = 0; q < 4; q++) {
        if (q == 3) {
          mbar_wait(bar0 + 8 * B_G);
          if (lane < 28)
#pragma unroll
            for (int u = 0; u < 4; u++) y[u] = ldx8(pr + u * 512 + 32);
          __syncwarp();
        }
        mbar_wait(fulla + 8 * q, pha);
#pragma unroll
        for (int mt = 0; mt < 4; mt++) ldsm_t(a[q][mt], (ab + q * 16384) ^ (mt << 5));
#pragma unroll
        for (int mt = 0; mt < 4; mt++) mma16(d[mt], a[q][mt], z[q].x, z[q].y);
      }
      mbar_wait(bar0 + 8 * B_W);
      const float4 W = lds16(sb + O_SM + (384 + 4 * tq) * 4);
#pragma unroll
      for (int i = 0; i < 8; i++) { r[i] = W.x * d[i >> 1][2 * (i & 1)] + W.y * d[i >> 1][2 * (i & 1) + 1]; asm volatile("" : "+f"(r[i])); }
#pragma unroll
      for (int j = 0; j < NPE; j++) wo(j);
      POLL {
        if (it_)
#pragma unroll
          for (int u = 0; u < 4; u++) y[u] = ldx8(pr + u * 512 + 32);
#pragma unroll
        for (int mt = 0; mt < 4; mt++) d[mt][0] = d[mt][1] = d[mt][2] = d[mt][3] = 0.f;
#pragma unroll
        for (int q = 0; q < 4; q++)
#pragma unroll
          for (int mt = 0; mt < 4; mt++) mma16(d[mt], a[q][mt], y[q].x, y[q].y);
        RETRY(or3(lop_x3(y[0].x, y[1].x, p2), lop_x3(y[2].x, y[3].x, p2), 0))
      }
#pragma unroll
      for (int i = 0; i < 8; i++) r[i] = W.w * d[i >> 1][2 * (i & 1) + 1] + (W.z * d[i >> 1][2 * (i & 1)] + r[i]);
      tred<4>(r, lane, 2); tred<2>(r, lane, 1);
      sts4(a_rs, r[0]); sts4(a_rs + 128, r[1]);
      nbar(1, 256);
      send32(a_c, a_cb, sum8(a_rl), lane);
    }
    {
#pragma unroll
      for (int j = NPE; j < NPO; j++) wo(j);
      uint2 c[4];
      mbar_wait(bar0 + 8 * B_HZ);
#pragma unroll
      for (int j = 0; j < 4; j++) asm volatile("ld.shared.v2.u32 {%0, %1}, [%2];" : "=r"(c[j].x), "=r"(c[j].y) : "r"(a_cx + j * 256) : "memory");
      float d[4][4] = {};
#pragma unroll
      for (int j = 0; j < 4; j++) {
        if (j + 1 >= NPO && j < 3) wo(j + 1);
#pragma unroll
        for (int mt = 0; mt < 4; mt++) mma16(d[mt], aw[j][mt], c[j].x, c[j].y);
      }
      const float r0 = (tq & 2) ? ((tq & 1) ? d[3][0] : d[2][0]) : ((tq & 1) ? d[1][0] : d[0][0]);
      const float r1 = (tq & 2) ? ((tq & 1) ? d[3][2] : d[2][2]) : ((tq & 1) ? d[1][2] : d[0][2]);
      sts4(a_rs + 2048, r0); sts4(a_rs + 2048 + 128, r1);
      if (warp >= 2) nbar_arrive(2, 256);
      else {
        mbar_wait(bar0 + 8 * B_TAB);
        const float gav = lds4(a_ga);
        nbar(2, 256);
        const float t = gav * sum8(a_rl + 2048) + xv;
        asm volatile("{.reg .pred p; setp.eq.s32 p, %2, 0; @p red.relaxed.gpu.global.xor.b32 [%0], %1;}"
                     ::"l"(p_ab), "r"(pack2t(t, __shfl_down_sync(~0u, t, 1), par) | 1u), "r"(lane & 1) : "memory");
        pub4(p_ao, __float_as_uint(t) | 1u);
      }
    }
  } else {
    uint32_t af[4][4][4];
    uint32_t ab = bufa + (32 * warp + 8 * (lane >> 4) + (lane & 7)) * 64 + ((((lane >> 3) & 1) ^ ((lane >> 1) & 3)) << 4);
    uint32_t a_d = bufo + wg * 16384 + (8 * (lane >> 4) + (lane & 7)) * 128 + (((2 * (warp & 3) + ((lane >> 3) & 1)) ^ (lane & 7)) << 4);
    uint32_t a_rl = sb + O_R + lane * 16, a_st = sb + O_SM + (352 + 8 * (lane >> 4) + warp) * 4;
    const unsigned* pa = scr->xab + tid;
    uint32_t a_hb = mapa(bar0 + 8 * B_HZ, 2 * (warp & 3) + (lane >> 4)), a_h = a_hb - (O_BAR + 8 * B_HZ - O_CTX) + rn * 64 + tq * 16;
    PIN(a_hb); PIN(a_h);
    uint32_t a_hl = sb + O_CTX + wg * 256 + tq * 16, a_t = sb + O_SM + (16 * warp + 8 * (tq & 1) + g) * 4;
    const unsigned* px = scr->xao + 64 * rn + 2 * lane;
    bf16* po = out + 64 * rn + 2 * lane;
    PIN(ab); PIN(a_d); PIN(a_rl); PINL(pa); PIN(a_rs); PIN(a_st); PINL(po); PIN(a_hl); PINL(px); PIN(a_t);
    mbar_wait(bar0 + 8 * B_TAB);
    uint2 cf;
    uint2 bb[4];
    uint2 gbw;
    POLL {
      unsigned bad = 0;
      cf = ldx8(scr->xm + 1024 + (lane & 16) * 16 + 32 * warp + posof(2 * (lane & 15)));
#pragma unroll
      for (int s = 0; s < 4; s++) {
        const uint4 w = ldx16(scr->xm + 1024 - (g & 1) * 512 + 256 * (s >> 1) + 32 * warp + 16 * (s & 1) + 4 * tq);
        bb[s] = make_uint2(__byte_perm(w.x, w.y, 0x7632), __byte_perm(w.z, w.w, 0x7632));
        bad = or3(bad, lop_x3(w.x, w.y, par), lop_x3(w.z, w.w, par));
      }
      gbw = ldx8(scr->xm + 1536 + 64 * rn + posof(2 * lane));
      RETRY(or3(bad, lop_x3(cf.x, cf.y, par), lop_x3(gbw.x, gbw.y, par)))
    }
    float e[4][4] = {};
    unsigned v[8];
    auto item = [&](const int it) {
      mbar_wait(fulla + 8 * it, pha);
#pragma unroll
      for (int i = 0; i < 4; i++) ldsm_t(af[it][i], (ab + it * 16384 + (i >> 1) * 1024) ^ ((i & 1) << 5));
    };
    auto item_mma = [&](const int it) {
#pragma unroll
      for (int i = 0; i < 4; i++) mma16(e[2 * (it & 1) + (i & 1)], af[it][i], bb[(it & 2) + (i >> 1)].x, bb[(it & 2) + (i >> 1)].y);
    };
    unsigned t3 = sch.wt;
    PIN(t3);
    item(0); item_mma(0); item(1); item_mma(1);
    mbar_wait(bar0 + 8 * B_G);
#pragma unroll
    for (int i = 0; i < 8; i++) v[i] = ldx4(pa + i * 256);
    t3 += clock();
    uint32_t have2, have3 = 0;
    do have2 = mbar_test(fulla + 16, pha); while (!have2 && (int)((unsigned)clock() - t3) < 0);
    if (have2) {
      item(2); item_mma(2);
      do have3 = mbar_test(fulla + 24, pha); while (!have3 && (int)((unsigned)clock() - t3) < 0);
      if (have3) { item(3); item_mma(3); }
    }
    float y0, y1, df[4][4], st[2];
    uint32_t bz[4][2] = {};
    auto mm = [&](const int it, const int i) { mma16(df[2 * (it & 1) + (i & 1)], af[it][i], bz[(it & 2) + (i >> 1)][0], bz[(it & 2) + (i >> 1)][1]); };
    POLL {
      if (it_)
#pragma unroll
        for (int i = 0; i < 8; i++) v[i] = ldx4(pa + i * 256);
      y0 = ((bflo(v[0]) + bflo(v[1])) + (bflo(v[2]) + bflo(v[3]))) + ((bflo(v[4]) + bflo(v[5])) + (bflo(v[6]) + bflo(v[7])));
      y1 = ((bfhi(v[0]) + bfhi(v[1])) + (bfhi(v[2]) + bfhi(v[3]))) + ((bfhi(v[4]) + bfhi(v[5])) + (bfhi(v[6]) + bfhi(v[7])));
      const uint32_t zb = pack2(y0 * u2f(cf.x), y1 * u2f(cf.y));
#pragma unroll
      for (int s = 0; s < 4; s++) {
        const uint32_t w = __shfl_sync(~0u, zb, 8 * s + (lane & 7));
        bz[s][0] = (lane & 4) ? 0u : w; bz[s][1] = (lane & 4) ? w : 0u;
      }
      st[0] = y0 + y1; st[1] = y0 * y0 + y1 * y1;
      tred<1>(st, lane, 16);
#pragma unroll
      for (int i = 0; i < 4; i++) df[i][0] = df[i][1] = df[i][2] = df[i][3] = 0.f;
      mm(0, 0); mm(0, 1); mm(1, 0); mm(1, 1);
      st[0] += shx(st[0], 8);
      mm(0, 2); mm(0, 3); mm(1, 2); mm(1, 3);
      RETRY(or3(or3(lop_x3(v[0], v[1], par), lop_x3(v[2], v[3], par), lop_x3(v[4], v[5], par)), lop_x3(v[6], v[7], par), 0))
    }
    uint2 xq[8];
    if (warp == 0)
#pragma unroll
      for (int i = 0; i < 8; i++) xq[i] = ldx8(px + i * 512);
    if (have2) { mm(2, 0); mm(2, 1); mm(2, 2); mm(2, 3); }
    st[0] += shx(st[0], 4);
    st[0] += shx(st[0], 2);
    st[0] += shx(st[0], 1);
    sts4(a_st, st[0]);
    __syncwarp();
    arrive_n(bar0 + 8 * B_ST, lane == 0, 1);
    if (!have2) { item(2); item_mma(2); mm(2, 0); mm(2, 1); mm(2, 2); mm(2, 3); }
    if (!have3) { item(3); item_mma(3); }
    mm(3, 0); mm(3, 1); mm(3, 2); mm(3, 3);
    mbar_wait(bar0 + 8 * B_ST);
    float mean, rstd;
    {
      float4 u[4];
#pragma unroll
      for (int i = 0; i < 4; i++) u[i] = lds16(sb + O_SM + (352 + 4 * i) * 4);
      mean = (((u[0].x + u[0].y) + (u[0].z + u[0].w)) + ((u[1].x + u[1].y) + (u[1].z + u[1].w))) * (1.f / 512.f);
      const float sq = (((u[2].x + u[2].y) + (u[2].z + u[2].w)) + ((u[3].x + u[3].y) + (u[3].z + u[3].w))) * (1.f / 512.f);
      asm("rsqrt.approx.ftz.f32 %0, %1;" : "=f"(rstd) : "f"(fmaxf(sq - mean * mean, 0.f) + 1e-5f));
    }
    float A[4], r[4];
#pragma unroll
    for (int i = 0; i < 4; i++) {
      A[i] = (tq & 2) ? ((tq & 1) ? e[3][i] : e[2][i]) : ((tq & 1) ? e[1][i] : e[0][i]);
      r[i] = (tq & 2) ? ((tq & 1) ? df[3][i] : df[2][i]) : ((tq & 1) ? df[1][i] : df[0][i]);
    }
    sts4(a_rs, rstd * (r[0] + r[1]) + (A[1] - rstd * mean * A[0])); sts4(a_rs + 128, rstd * (r[2] + r[3]) + (A[3] - rstd * mean * A[2]));
    nbar(1, 256);
    if (wg) {
      const float4 g0 = lds16(a_rl), g1 = lds16(a_rl + 1024), u0 = lds16(a_rl + 512), u1 = lds16(a_rl + 1536);
      const float gg = bfr(((g0.x + g0.y) + (g0.z + g0.w)) + ((g1.x + g1.y) + (g1.z + g1.w)));
      const float uu = bfr(((u0.x + u0.y) + (u0.z + u0.w)) + ((u1.x + u1.y) + (u1.z + u1.w)));
      const float hh = bfr(gg * rcp(1.f + ex2(gg * (-2.302208198f - 0.1029432397f * gg * gg)))) * uu;
      send32(a_h, a_hb, hh, lane);
    } else spin_until(clock() + FDLY);
    uint32_t ad[8][4];
    mbar_wait(fullb + 8 * wg, phb);
#pragma unroll
    for (int i = 0; i < 8; i++) ldsm_t(ad[i], a_d + i * 2048);
    float x0, x1;
    if (warp == 0) {
      POLL {
        if (it_)
#pragma unroll
          for (int i = 0; i < 8; i++) xq[i] = ldx8(px + i * 512);
        unsigned bad = 0;
#pragma unroll
        for (int i = 0; i < 4; i++) bad = or3(bad, lop_x3(xq[i].x, xq[i].y, par), lop_x3(xq[i + 4].x, xq[i + 4].y, par));
        RETRY(bad)
      }
      x0 = x1 = 0.f;
#pragma unroll
      for (int i = 0; i < 8; i++) { x0 += u2f(xq[i].x); x1 += u2f(xq[i].y); }
      x0 *= 1.f / 7.f; x1 *= 1.f / 7.f;
    }
    mbar_wait(bar0 + 8 * B_HZ);
    float dd[4][4] = {};
#pragma unroll
    for (int i = 0; i < 4; i++) {
      const float4 hb = lds16(a_hl + i * 64);
      mma16(dd[(2 * i) & 3], ad[2 * i], __float_as_uint(hb.x), __float_as_uint(hb.y));
      mma16(dd[(2 * i + 1) & 3], ad[2 * i + 1], __float_as_uint(hb.z), __float_as_uint(hb.w));
    }
    sts4(a_t, (tq & 1) ? (dd[0][2] + dd[1][2]) + (dd[2][2] + dd[3][2]) : (dd[0][0] + dd[1][0]) + (dd[2][0] + dd[3][0]));
    if (warp) nbar_arrive(2, 256);
    else {
      nbar(2, 256);
      float t0, t1, t2, t3b;
      asm volatile("ld.shared.v2.f32 {%0, %1}, [%4]; ld.shared.v2.f32 {%2, %3}, [%4 + 256];"
                   : "=f"(t0), "=f"(t1), "=f"(t2), "=f"(t3b) : "r"(sb + O_SM + lane * 8) : "memory");
      t0 = bfhi(gbw.x) * (t0 + t2) + x0; t1 = bfhi(gbw.y) * (t1 + t3b) + x1;
      asm volatile("red.relaxed.gpu.global.add.noftz.bf16x2 [%0], %1;" ::"l"(po), "r"(pack2(t0, t1)) : "memory");
      if (f == 0 && tid == 0) stx4(&scr->cnt[0], epoch + 1);
    }
  }
}

static void make_sched(Sched& s) {
  const char* order = "FFAAbcFmmvog..d";
  const double dt = 5010 * 1e-3, dth = 4850 * 1e-3;
  const int nbig = NBIG;
  s.zero = 0; s.dth = (unsigned)(dth * 256 + 0.5);
  double t = 512 * dth + 80;
  int tile = 0, jm = 0;
  for (int i = 0; i < 3; i++) s.nr[i] = s.nt[i] = 0;
  auto add = [&](int c, int type, double step, int win, int b0, int tl) {
    s.r[c][s.nr[c]++] = make_uint2((unsigned)(t + 0.5) | (unsigned)(step + 0.5) << 16, type | win << 4 | (b0 + 64) << 8 | tl << 16);
    if (type == T_KV) s.nt[c]++;
  };
  const int w1 = 6, w2 = 4, wt = 6;
  for (const char* p = order; *p; p++) {
    const char c = *p;
    if (c == 'v' || c == 'o' || c == 'm') {
      const int ty = c == 'v' ? T_UV : c == 'o' ? T_WO : T_MOD;
      const double d = (c == 'm' ? 5010 : c == 'v' ? 5600 : 5600) * 1e-3;
      add(0, ty, 64 * d, wt, 0, c == 'm' ? jm : 0); add(1, ty, 64 * d, wt, 0, c == 'm' ? jm : 0);
      t += (c == 'm' ? 64 : 256) * d; jm += c == 'm';
    } else if (c == 'g' || c == 'd') {
      const double d = (c == 'g' ? 5400 : 5500) * 1e-3;
      add(2, c == 'g' ? T_GU : T_DN, 56 * d, wt, 64, 0);
      t += (c == 'g' ? 224 : 112) * d;
    } else if (c == '.') t += 100;
    else if (c == '-') t -= 100;
    else {
      const int na = c == 'F' ? 0 : c == 'C' || c == 'c' || c == 'a' ? nbig : 64, nf = c == 'A' || c == 'a' ? 0 : 56, n = na + nf;
      const int w = na && nf ? w2 : w1;
      const bool ff = c == 'b' || c == 'c';
      const int cf = c == 'c' ? 60 : 0, ca = cf * 7 / 5;
      t += 3 * ca;
      if (na) add(0, T_KV, n * dt - ca, w, ff ? -56 : 0, tile);
      t -= 3 * ca;
      if (na == 64) add(1, T_KV, n * dt, w, ff ? -56 : 0, tile);
      if (nf) add(2, T_KV, n * dt - cf, w, ff ? 64 : 64 - na, tile);
      tile += n; t += 4 * n * dt;
      s.t4 = (unsigned)t + 600;
    }
  }
  s.dt = (unsigned)(dt * 256 + 0.5); s.d4 = 1560 | 1200 << 16; s.d6 = 3190; s.wt = 250;
}

static void launch(void* const* d_in, void* d_out) {
  static TMaps tms;
  static Sched sch;
  static bool init = false;
  static void* scr = nullptr;
  if (!init) {
    void* fn = nullptr; cudaDriverEntryPointQueryResult qr;
    cudaGetDriverEntryPoint("cuTensorMapEncodeTiled", &fn, cudaEnableDefault, &qr);
    EncFn f = (EncFn)fn;
    const CUtensorMapSwizzle S64 = CU_TENSOR_MAP_SWIZZLE_64B, S128 = CU_TENSOR_MAP_SWIZZLE_128B;
    const CUtensorMapL2promotion P256 = CU_TENSOR_MAP_L2_PROMOTION_L2_256B;
    enc3d(f, &tms.m[0], d_in[2], 64, 512, 64, 8192, 128, 64, 128, 1, S128, CU_TENSOR_MAP_L2_PROMOTION_L2_128B);
    enc3d(f, &tms.m[1], d_in[3], 64, 512, 64, 8192, 128, 64, 64, 2, S128, P256);
    enc3d(f, &tms.m[2], d_in[1], 64, SK, 8, 1024, 128, 64, 64, 2, S128, P256);
    enc3d(f, &tms.m[3], d_in[11], 3072, 256, 2, 6144, 256 * 6144, 32, 256, 1, S64, CU_TENSOR_MAP_L2_PROMOTION_L2_128B);
    enc3d(f, &tms.m[4], d_in[4], 64, 512, 64, 8192, 128, 64, 128, 1, S128, CU_TENSOR_MAP_L2_PROMOTION_L2_128B);
    enc3d(f, &tms.m[5], d_in[5], 512, 128, 32, 1024, 128 * 1024, 64, 128, 1, S128, CU_TENSOR_MAP_L2_PROMOTION_L2_128B);
    enc3d(f, &tms.m[6], d_in[7], 1792, 256, 2, 3584, 256 * 3584, 32, 256, 1, S64, CU_TENSOR_MAP_L2_PROMOTION_L2_128B);
    enc3d(f, &tms.m[7], d_in[8], 1792, 256, 2, 3584, 256 * 3584, 32, 256, 1, S64, CU_TENSOR_MAP_L2_PROMOTION_L2_128B);
    enc3d(f, &tms.m[8], d_in[9], 512, 128, 14, 1024, 128 * 1024, 64, 128, 1, S128, CU_TENSOR_MAP_L2_PROMOTION_L2_128B);
    cudaFuncSetAttribute(fused_kernel, cudaFuncAttributeMaxDynamicSharedMemorySize, SMEM9);
    cudaGetSymbolAddress(&scr, g_scr);
    make_sched(sch);
    init = true;
  }
  fused_kernel<<<NCTA9, 384, SMEM9>>>((const bf16*)d_in[0], (const bf16*)d_in[10], (const bf16*)d_in[11], (bf16*)d_out, (Scratch*)scr, sch, tms);
}

static bool fits() {
  cudaFuncSetAttribute(fused_kernel, cudaFuncAttributeMaxDynamicSharedMemorySize, SMEM9);
  cudaLaunchConfig_t cfg = {};
  cfg.gridDim = dim3(NCTA9); cfg.blockDim = dim3(384); cfg.dynamicSmemBytes = SMEM9;
  cudaLaunchAttribute at[1];
  at[0].id = cudaLaunchAttributeClusterDimension; at[0].val.clusterDim.x = 8; at[0].val.clusterDim.y = 1; at[0].val.clusterDim.z = 1;
  cfg.attrs = at; cfg.numAttrs = 1;
  int n = 0;
  if (cudaOccupancyMaxActiveClusters(&n, fused_kernel, &cfg) != cudaSuccess) { (void)cudaGetLastError(); return false; }
  return n >= NCTA9 / 8;
}
}
#undef BAR_ARM
#undef BAR_ARRIVE
#undef BAR_INIT
#undef B_EM
#undef B_EMPTY
#undef B_FM
#undef B_FULL
#undef B_G
#undef B_G2
#undef B_H
#undef B_HZ
#undef B_LZ
#undef B_Q2
#undef B_QF
#undef B_ST
#undef B_TAB
#undef B_W
#undef B_WZ
#undef CNT_ADD
#undef DSC
#undef FDLY
#undef HI128
#undef HI64
#undef LANE0
#undef NBIG
#undef NCTA9
#undef NPE
#undef NPO
#undef NSL
#undef O_B
#undef O_BAR
#undef O_CTX
#undef O_DBG
#undef O_EP
#undef O_HW
#undef O_HZ
#undef O_LZ
#undef O_P
#undef O_Q
#undef O_R
#undef O_SILU
#undef O_SM
#undef O_X
#undef PIN
#undef PINL
#undef POLL
#undef QN
#undef RETRY
#undef SK
#undef SMEM9
#undef SMEM_BASE
#undef SPIN_MAX
#undef TAU
#undef VDLY
#undef VJ
#undef X16
#undef fbits

namespace v8 {
typedef __nv_bfloat16 bf16;
#define NCTA 128
#define SK 32768
#define SLOT 32768
#define NSLOT 6
#define OFF_WQ (2 * SLOT)
#define OFF_WUK (4 * SLOT)
#define OFF_Q 196608
#define OFF_P (OFF_Q + 16384)
#define OFF_B (OFF_P + 4096)
#define OFF_R4 (OFF_B + 2304)
#define OFF_SILU (OFF_R4 + 4096)
#define OFF_RA (OFF_SILU + 1024)
#define OFF_SM (OFF_RA + 1024)
#define OFF_BP (OFF_SM + 1792)
#define OFF_CO (OFF_BP + 1024)
#define OFF_BAR (OFF_CO + 1280)
#define OFF_MASK (OFF_BAR + 512)
#define OFF_DBG (OFF_MASK + 16)
#define SMEM_BYTES (OFF_DBG + 128)
#define OFF_MOD OFF_Q
#define OFF_UV (4 * SLOT)
#define OFF_O (5 * SLOT)
#define OFF_G 0
#define OFF_U 16384
#define OFF_D SLOT
#define OFF_XO (OFF_D + 16384)
#define FB_UK 4
#define FB_KV 6
#define FB_MOD 22
#define FB_UV 23
#define FB_O 25
#define FB_G 27
#define FB_D 29
#define EB 30
#define QB 50
#define XB 51
#define SPIN_MAX (1 << 20)
#define BACKOFF 40
#define RATE_NS 652
#define RATE_T0 200
#define RATE_TL 300
#define WINS 0x3222333
#define KVWIN 4
#define RATE_H 650
#define RATE_E 650
#define SMUL 9
#define NPRE0 1
#define NPRE1 3
#define HWIN 4
#define EWIN 3
#define WTEST 450
#define DLY5 650
#define DLY6 600
#define DLY7 600
#define P12(a, b, c, d, e, f, g, h, i, j, k, l) ((unsigned long long)(a) | (b) << 5 | (c) << 10 | (d) << 15 | (e) << 20 | (f) << 25 | \
  (unsigned long long)(g) << 30 | (unsigned long long)(h) << 35 | (unsigned long long)(i) << 40 | (unsigned long long)(j) << 45 | \
  (unsigned long long)(k) << 50 | (unsigned long long)(l) << 55)
#define ORDER0 P12(0, 1, 2, 3, 4, 5, 16, 6, 7, 8, 9, 10)
#define ORDER1 P12(11, 12, 13, 14, 15, 17, 18, 19, 20, 23, 21, 22)
#define TAIL_K 17
#define RS 16
template <int N> struct IC { static constexpr int value = N; };
struct TMaps { CUtensorMap m[9]; };

struct __align__(128) Scratch {
  uint4 xo[128 * 64 * RS];
  uint2 ml[32 * 64];
  unsigned h[8 * 256];
  unsigned qa[32 * 256];
  unsigned xc[128 * 64];
  unsigned xao[8 * 512];
  unsigned xf[112 * 512];
  unsigned xm[2048];
  unsigned cnt[5 * 32];
};
__device__ Scratch g_scr;
#define g_xo scr->xo
#define g_ml scr->ml
#define g_h scr->h
#define g_qa scr->qa
#define g_xc scr->xc
#define g_xao scr->xao
#define g_xf scr->xf
#define g_xm scr->xm
#define g_epoch scr->cnt[0]

__device__ __forceinline__ uint32_t s2u(const void* p) { return (uint32_t)__cvta_generic_to_shared(p); }
__device__ __forceinline__ float bflo(uint32_t u) { return __uint_as_float(u << 16); }
__device__ __forceinline__ float bfhi(uint32_t u) { return __uint_as_float(u & 0xffff0000u); }
__device__ __forceinline__ float u2f(uint32_t u) { return __uint_as_float(u); }
__device__ __forceinline__ void fma8(float* acc, uint4 v, float s) {
  acc[0] += s * bflo(v.x); acc[1] += s * bfhi(v.x); acc[2] += s * bflo(v.y); acc[3] += s * bfhi(v.y);
  acc[4] += s * bflo(v.z); acc[5] += s * bfhi(v.z); acc[6] += s * bflo(v.w); acc[7] += s * bfhi(v.w);
}
__device__ __forceinline__ uint32_t pack2(float a, float b) {
  __nv_bfloat162 p = __floats2bfloat162_rn(a, b); return *(uint32_t*)&p;
}
__device__ __forceinline__ float bfr(float v) { return bfhi(pack2(v, v)); }
__device__ __forceinline__ float silu_bf(float c) { return bfr(__fdividef(c, 1.f + __expf(-c))); }
#define fbits(v) ((__float_as_uint(v) & ~1u) | par)
__device__ __forceinline__ uint32_t pack2t(float a, float b, unsigned par) {
  const uint32_t ua = ((__float_as_uint(a) + ((par ^ 1) << 16)) & 0xFFFE0000u) | (par << 16);
  return __byte_perm(ua, pack2(b, b), 0x7632);
}
__device__ __forceinline__ void nbar(int id, int n) { asm volatile("bar.sync %0, %1;" ::"r"(id), "r"(n) : "memory"); }
__device__ __forceinline__ void nbar_arrive(int id, int n) { asm volatile("bar.arrive %0, %1;" ::"r"(id), "r"(n) : "memory"); }
__device__ __forceinline__ uint4 ldc16(const void* p) {
  uint4 v; asm volatile("ld.relaxed.cta.global.v4.u32 {%0,%1,%2,%3}, [%4];" : "=r"(v.x), "=r"(v.y), "=r"(v.z), "=r"(v.w) : "l"(p) : "memory"); return v;
}
__device__ __forceinline__ unsigned ldc4(const void* p) {
  unsigned v; asm volatile("ld.relaxed.cta.global.u32 %0, [%1];" : "=r"(v) : "l"(p) : "memory"); return v;
}
__device__ __forceinline__ uint4 ldx16(const void* p) {
  uint4 v; asm volatile("ld.relaxed.gpu.global.v4.u32 {%0,%1,%2,%3}, [%4];" : "=r"(v.x), "=r"(v.y), "=r"(v.z), "=r"(v.w) : "l"(p) : "memory"); return v;
}
__device__ __forceinline__ unsigned ldx4(const void* p) {
  unsigned v; asm volatile("ld.relaxed.gpu.global.u32 %0, [%1];" : "=r"(v) : "l"(p) : "memory"); return v;
}
__device__ __forceinline__ unsigned long long ldx64(const void* p) {
  unsigned long long v; asm volatile("ld.relaxed.gpu.global.u64 %0, [%1];" : "=l"(v) : "l"(p) : "memory"); return v;
}
__device__ __forceinline__ void stx16(void* p, uint4 v) {
  asm volatile("st.relaxed.gpu.global.v4.u32 [%0], {%1,%2,%3,%4};" ::"l"(p), "r"(v.x), "r"(v.y), "r"(v.z), "r"(v.w) : "memory");
}
__device__ __forceinline__ void stx8(void* p, uint2 v) { asm volatile("st.relaxed.gpu.global.v2.u32 [%0], {%1,%2};" ::"l"(p), "r"(v.x), "r"(v.y) : "memory"); }
__device__ __forceinline__ void stx4(void* p, unsigned v) { asm volatile("st.relaxed.gpu.global.u32 [%0], %1;" ::"l"(p), "r"(v) : "memory"); }
__device__ __forceinline__ unsigned lop_x3(unsigned a, unsigned b, unsigned c) {
  unsigned d; asm("lop3.b32 %0, %1, %2, %3, 0x7E;" : "=r"(d) : "r"(a), "r"(b), "r"(c)); return d; }
#define X16(v) (lop_x3(v.x, v.y, par) | lop_x3(v.z, v.w, par))
#define X8(v) lop_x3(v.x, v.y, par)
#define RETRY(bad) if (!__any_sync(~0u, (bad) & 1) || ++it_ >= SPIN_MAX) break; __nanosleep(BACKOFF);
#define POLL _Pragma("unroll 1") for (int it_ = 0;;)
__device__ __forceinline__ void mbar_wait(uint32_t bar) {
  uint32_t ok; int it = 0;
  do {
    asm volatile("{.reg .pred p; mbarrier.try_wait.parity.shared::cta.b64 p, [%1], 0; selp.u32 %0,1,0,p;}"
                 : "=r"(ok) : "r"(bar) : "memory");
  } while (!ok && ++it < SPIN_MAX);
}
__device__ __forceinline__ float ex2(float v) { float r; asm("ex2.approx.ftz.f32 %0, %1;" : "=f"(r) : "f"(v)); return r; }
__device__ __forceinline__ float rcp(float v) { float r; asm("rcp.approx.ftz.f32 %0, %1;" : "=f"(r) : "f"(v)); return r; }
__device__ __forceinline__ void mma16(float* d, const uint32_t* a, uint32_t b0, uint32_t b1) {
  asm volatile("mma.sync.aligned.m16n8k16.row.col.f32.bf16.bf16.f32 {%0,%1,%2,%3}, {%4,%5,%6,%7}, {%8,%9}, {%0,%1,%2,%3};"
               : "+f"(d[0]), "+f"(d[1]), "+f"(d[2]), "+f"(d[3]) : "r"(a[0]), "r"(a[1]), "r"(a[2]), "r"(a[3]), "r"(b0), "r"(b1));
}
__device__ __forceinline__ float4 lds16(uint32_t a) {
  float4 v; asm volatile("ld.shared.v4.f32 {%0,%1,%2,%3}, [%4];" : "=f"(v.x), "=f"(v.y), "=f"(v.z), "=f"(v.w) : "r"(a) : "memory"); return v;
}
__device__ __forceinline__ void ldsm_t(uint32_t* r, uint32_t a) {
  asm volatile("ldmatrix.sync.aligned.m8n8.x4.trans.shared.b16 {%0,%1,%2,%3}, [%4];" : "=r"(r[0]), "=r"(r[1]), "=r"(r[2]), "=r"(r[3]) : "r"(a) : "memory");
}
__device__ __forceinline__ void ldsm(uint32_t* r, uint32_t a) {
  asm volatile("ldmatrix.sync.aligned.m8n8.x4.shared.b16 {%0,%1,%2,%3}, [%4];" : "=r"(r[0]), "=r"(r[1]), "=r"(r[2]), "=r"(r[3]) : "r"(a) : "memory");
}
template <int N>
__device__ __forceinline__ void tred(float* a, int lane, int m) {
  const bool hi = lane & m;
#pragma unroll
  for (int i = 0; i < N; i++) {
    float send = hi ? a[i] : a[i + N], keep = hi ? a[i + N] : a[i];
    a[i] = keep + __shfl_xor_sync(~0u, send, m);
  }
}
template <int N>
__device__ __forceinline__ void tmax(float* a, int lane, int m) {
  const bool hi = lane & m;
#pragma unroll
  for (int i = 0; i < N; i++) {
    float send = hi ? a[i] : a[i + N], keep = hi ? a[i + N] : a[i];
    a[i] = fmaxf(keep, __shfl_xor_sync(~0u, send, m));
  }
}
__device__ __forceinline__ void arrive2(uint32_t bar, uint32_t rbar, bool local, bool remote) {
  asm volatile("{.reg .pred p, q; setp.ne.s32 p, %2, 0; setp.ne.s32 q, %3, 0; @p mbarrier.arrive.shared::cta.b64 _, [%0];\n"
               "@q mbarrier.arrive.relaxed.cluster.shared::cluster.b64 _, [%1];}" ::"r"(bar), "r"(rbar), "r"((int)local), "r"((int)remote) : "memory");
}
__device__ __forceinline__ unsigned long long stream_policy() {
  unsigned long long p;
  asm volatile("createpolicy.fractional.L2::evict_first.b64 %0, 1.0;" : "=l"(p));
  return p;
}
__device__ __forceinline__ void tma3d(uint32_t dst, const CUtensorMap* tm, uint32_t bar, int c0, int c1, int c2) {
  asm volatile("cp.async.bulk.tensor.3d.shared::cluster.global.mbarrier::complete_tx::bytes.L2::cache_hint [%0], [%1, {%3, %4, %5}], [%2], %6;"
               ::"r"(dst), "l"(tm), "r"(bar), "r"(c0), "r"(c1), "r"(c2), "l"(stream_policy()) : "memory");
}
__device__ __forceinline__ void st_async2(uint32_t dst, uint32_t bar, float v0, float v1) {
  asm volatile("st.async.shared::cluster.mbarrier::complete_tx::bytes.v2.f32 [%0], {%1, %2}, [%3];" ::"r"(dst), "f"(v0), "f"(v1), "r"(bar) : "memory");
}
__device__ __forceinline__ void st_pair(int mode, uint32_t dst, uint32_t bar, float v0, float v1) {
  asm volatile("{.reg .pred p, q; setp.eq.s32 p, %4, 1; setp.eq.s32 q, %4, 2; @p st.shared.v2.f32 [%0], {%1, %2};\n"
               "@q st.async.shared::cluster.mbarrier::complete_tx::bytes.v2.f32 [%0], {%1, %2}, [%3];}"
               ::"r"(dst), "f"(v0), "f"(v1), "r"(bar), "r"(mode) : "memory");
}
__device__ __forceinline__ void spin_until(unsigned t) { while ((int)((unsigned)clock() - t) < 0) {} }
__device__ __forceinline__ unsigned wait_until(unsigned t) {
  unsigned now;
  for (;;) {
    asm volatile("mov.u32 %0, %%globaltimer_lo;" : "=r"(now));
    if ((int)(now - t) >= 0) break;
  }
  return now;
}
#define PIN(x) asm volatile("" : "+r"(x))
#define PINL(x) asm volatile("" : "+l"(x))
#define BAR_ARRIVE(i) asm volatile("mbarrier.arrive.shared::cta.b64 _, [%0];" ::"r"(bar0 + 8 * (i)) : "memory")
#define CNT_ADD(c) asm volatile("red.relaxed.gpu.global.add.u32 [%0], 1;" ::"l"(scr->cnt + (c)) : "memory")
#define BAR_INIT(i, cnt) asm volatile("mbarrier.init.shared::cta.b64 [%0], %1;" ::"r"(bar0 + 8 * (i)), "r"(cnt) : "memory")
#define BAR_ARM(i, bytes) asm volatile("mbarrier.arrive.expect_tx.shared::cta.b64 _, [%0], %1;" ::"r"(bar0 + 8 * (i)), "r"(bytes) : "memory")

__device__ __forceinline__ void tail(unsigned char* smem, Scratch* __restrict__ scr, const bf16* __restrict__ x, bf16* __restrict__ out,
                                     const unsigned par, const unsigned epoch, const int warp) {
  int tid, b;
  asm volatile("mov.u32 %0, %%tid.x;" : "=r"(tid));
  asm volatile("mov.u32 %0, %%ctaid.x;" : "=r"(b));
  const int lane = tid & 31, g = lane >> 2, tq = lane & 3;
  const uint32_t sb = __shfl_sync(~0u, s2u(smem), 0), bar0 = sb + OFF_BAR;
  float* s_sm = (float*)(smem + OFF_SM);
  const int prow = 4 * (lane >> 4) + ((lane & 7) >> 1) + 8 * (lane & 1);
  const float* s_co = (const float*)(smem + OFF_CO);
  const int opos = (b & 15) * 32 + (lane & 16) + 2 * (lane & 6) + ((lane >> 2) & 2) + (lane & 1);
  const float xv = b < 16 ? __bfloat162float(x[(b & 15) * 32 + lane]) : 0.f;
  const int rk = b & 1, ob = 32 * rk + ((b >> 1) & 31);
  uint32_t psb;
  asm volatile("mapa.shared::cluster.u32 %0, %1, %2;" : "=r"(psb) : "r"(sb), "r"(rk ^ 1));
  {
    uint32_t a[8][4];
    {
      const int rg = tid >> 4;
      const uint4* src = g_xo + ((size_t)b * 64 + rg) * RS;
      const uint32_t dst = sb + OFF_XO + rg * 256 + (((tid & 15) ^ (rg & 7)) << 4);
      unsigned long long todo = 0x0001000100010001ull;
#pragma unroll 1
      for (int it = 0; it < SPIN_MAX * 16; it++) {
        unsigned long long mk = *(volatile unsigned long long*)(smem + OFF_MASK);
        const unsigned long long nw = (mk >> rg) & todo;
        todo ^= nw;
#pragma unroll
        for (int i = 0; i < 4; i++)
          if (nw >> (16 * i) & 1)
            asm volatile("cp.async.cg.shared.global [%0], [%1], 16;" ::"r"(dst + i * 4096), "l"(src + i * 16 * RS + (tid & 15)) : "memory");
        if (!__any_sync(~0u, todo != 0)) break;
      }
      asm volatile("cp.async.mbarrier.arrive.noinc.shared::cta.b64 [%0];" ::"r"(bar0 + 8 * (XB + 2)) : "memory");
    }
    mbar_wait(bar0 + 8 * FB_UV); mbar_wait(bar0 + 8 * (FB_UV + 1));
    const uint32_t ab = sb + OFF_UV + (warp >> 2) * 8192 + (8 * (lane >> 4) + (lane & 7)) * 128 + (((2 * (warp & 3) + ((lane >> 3) & 1)) ^ (lane & 7)) << 4);
#pragma unroll
    for (int s = 0; s < 8; s++) ldsm_t(a[s], ab + (s >> 2) * 16384 + (s & 3) * 2048);
    const int chn = 2 * warp + (tq & 1);
    uint32_t a_b = sb + OFF_B + (tq >> 1) * 272 + (32 * (chn >> 2) + 8 * (g >> 1) + 2 * (chn & 3) + (g & 1)) * 2;
    uint32_t a_bq = sb + OFF_B + (lane & 1) * 272 + (lane >> 3) * 16;
    unsigned* p_c = g_xc + (b >> 2) * 256 + warp * 32 + (b & 3) * 8 + (g & 3) * 2 + (g >> 2);
    PIN(a_b); PIN(a_bq); PINL(p_c);
    mbar_wait(bar0 + 8 * (XB + 6));
    uint32_t wb[8];
#pragma unroll
    for (int s = 0; s < 8; s++) wb[s] = *(const uint32_t*)(smem + OFF_RA + (4 * s + tq) * 4);
    const float invL = *(const float*)(smem + OFF_RA + 128);
    float ov;
    POLL {
      mbar_wait(bar0 + 8 * (XB + 2));
      uint32_t ao[4][4];
#pragma unroll
      for (int s = 0; s < 4; s++)
        ldsm_t(ao[s], sb + OFF_XO + (16 * s + 8 * (lane >> 4) + (lane & 7)) * 256 + (((2 * warp + ((lane >> 3) & 1)) ^ (lane & 7)) << 4));
      float d[4][4] = {};
#pragma unroll
      for (int s = 0; s < 4; s++) mma16(d[s], ao[s], wb[2 * s], wb[2 * s + 1]);
      const unsigned p2 = par * 0x10001u;
      unsigned bad = 0;
#pragma unroll
      for (int s = 0; s < 4; s++) bad |= lop_x3(ao[s][0], ao[s][1], p2) | lop_x3(ao[s][2], ao[s][3], p2);
      bad = g == 0 ? bad | (bad >> 16) : 0u;
      ov = (tq & 1) ? (d[0][2] + d[1][2]) + (d[2][2] + d[3][2]) : (d[0][0] + d[1][0]) + (d[2][0] + d[3][0]);
      if (__builtin_expect(!__any_sync(~0u, bad & 1) || ++it_ >= SPIN_MAX, 1)) break;
#pragma unroll
      for (int i = 0; i < 4; i++)
        asm volatile("cp.async.cg.shared.global [%0], [%1], 16;"
                     ::"r"(sb + OFF_XO + ((lane >> 1) + 16 * i) * 256 + (((2 * warp + (lane & 1)) ^ ((lane >> 1) & 7)) << 4)),
                       "l"(g_xo + ((size_t)b * 64 + (lane >> 1) + 16 * i) * RS + 2 * warp + (lane & 1)) : "memory");
      asm volatile("cp.async.wait_all;" ::: "memory");
      __syncwarp();
    }
    {
      const float lo = ov - bfhi(__float_as_uint(ov));
      asm volatile("st.shared.u16 [%0], %1;" ::"r"(a_b), "h"((unsigned short)((tq & 2) ? pack2(lo, lo) : __float_as_uint(ov) >> 16)) : "memory");
    }
    nbar(1, 256);
    float d[4][4] = {};
#pragma unroll
    for (int y = 0; y < 4; y++) {
      uint32_t bq[4];
      ldsm(bq, a_bq + 64 * y);
      mma16(d[(2 * y) & 3], a[2 * y], bq[0], bq[1]); mma16(d[(2 * y + 1) & 3], a[2 * y + 1], bq[2], bq[3]);
    }
    const float r0 = ((d[0][0] + d[0][1]) + (d[1][0] + d[1][1])) + ((d[2][0] + d[2][1]) + (d[3][0] + d[3][1]));
    const float r1 = ((d[0][2] + d[0][3]) + (d[1][2] + d[1][3])) + ((d[2][2] + d[2][3]) + (d[3][2] + d[3][3]));
    if (tq == 0) stx4(p_c, pack2t(r0 * invL, r1 * invL, par));
  }
  unsigned tpub = clock();
  mbar_wait(bar0 + 8 * (XB + 4));
  const float gav = s_co[256 + (opos & 31)];
  const float gbv = s_co[288 + (lane & 4) + 2 * (lane & 1) + ((lane >> 1) & 1)];
  float4 cf[2];
#pragma unroll
  for (int s = 0; s < 2; s++) cf[s] = *(const float4*)(s_co + 32 * warp + 16 * s + 4 * tq);
  {
    uint32_t a[2][4][4];
    mbar_wait(bar0 + 8 * (FB_O + (warp >> 2)));
    const uint32_t ab = sb + OFF_O + (32 * warp + prow) * 128 + ((((lane >> 3) & 1) ^ (prow & 7)) << 4);
#pragma unroll
    for (int i = 0; i < 8; i++) ldsm_t(a[i >> 2][i & 3], (ab + (i >> 2) * 2048) ^ ((i & 3) << 5));
    uint4 v;
    const unsigned* pc = g_xc + (4 * (b >> 4) + 2 * rk + (warp >> 2)) * 256 + 64 * (warp & 3) + 2 * lane;
    uint32_t ro = ((tq >> 1) == rk ? sb : psb) + OFF_P + (8 * (tq & 1) + g) * 144 + (8 * rk + warp) * 8;
    uint32_t a_q = sb + OFF_P + (8 * (lane >> 4) + (lane & 7)) * 144;
    unsigned* p_ao = g_xao + (b >> 5) * 1024 + (opos >> 4) * 32 + (b & 16) + (opos & 15);
    PIN(ro); PIN(a_q); PINL(p_ao); PINL(pc);
    spin_until(tpub + DLY5);
    POLL {
      const unsigned long long u0 = ldx64(pc);
      v.x = (unsigned)u0; v.y = u0 >> 32;
      RETRY(X8(v))
    }
    v.z = lane & 16 ? v.x : 0u; v.w = lane & 16 ? v.y : 0u;
    if (lane & 16) v.x = v.y = 0u;
    float d[4][4] = {};
#pragma unroll
    for (int mt = 0; mt < 4; mt++) mma16(d[mt], a[0][mt], v.x, v.y);
#pragma unroll
    for (int mt = 0; mt < 4; mt++) mma16(d[mt], a[1][mt], v.z, v.w);
    float r[8];
#pragma unroll
    for (int i = 0; i < 8; i++) r[i] = d[i >> 1][2 * (i & 1)] + d[i >> 1][2 * (i & 1) + 1];
    tred<4>(r, lane, 2); tred<2>(r, lane, 1);
    st_pair((tq >> 1) == rk ? 1 : 2, ro, psb + OFF_BAR + 8 * (XB + 3), r[0], r[1]);
    __syncwarp();
    if (lane == 0) BAR_ARRIVE(XB + 3);
    if (warp == 0) {
      mbar_wait(bar0 + 8 * (XB + 3));
      float p[8];
#pragma unroll
      for (int i = 0; i < 8; i++) {
        const float4 q = lds16(a_q + i * 16);
        p[i] = (lane & 8) ? q.y + q.w : q.x + q.z;
      }
      const float t = ((p[0] + p[1]) + (p[2] + p[3])) + ((p[4] + p[5]) + (p[6] + p[7]));
      stx4(p_ao, fbits(gav * t + xv));
    }
  }
  tpub = clock();
  if (b < 112) {
    uint32_t af[2][4][4], ad[4][4];
    const uint32_t ab = sb + (32 * warp + 8 * (lane >> 4) + (lane & 7)) * 64 + ((((lane >> 3) & 1) ^ ((lane >> 1) & 3)) << 4);
    uint32_t ro = ((tq & 1) == rk ? sb : psb) + OFF_R4 + (8 * (tq >> 1) + g) * 176 + (10 * rk + warp) * 8;
    uint32_t a_q = sb + OFF_R4 + (8 * (lane >> 4) + (lane & 7)) * 176 + (lane & 8) * 10;
    uint32_t a_d = sb + OFF_D + warp * 2048 + (8 * (lane >> 4) + (lane & 7)) * 128 + ((((lane >> 3) & 1) ^ (lane & 7)) << 4);
    unsigned* p_f = g_xf + b * 512 + 64 * warp + 16 * tq + 2 * g;
    const unsigned* pa = g_xao + (g >> 1) * 1024 + 512 * rk + 64 * warp + 4 * (lane & 7);
    PIN(ro); PIN(a_q); PIN(a_d); PINL(p_f); PINL(pa);
    spin_until(tpub + DLY6);
    uint4 v[2];
    {
      bool have = false;
      POLL {
        v[0] = ldx16(pa); v[1] = ldx16(pa + 32);
        const unsigned t1 = (unsigned)clock() + WTEST;
        while (!have && (int)((unsigned)clock() - t1) < 0) {
          uint32_t ok;
          asm volatile("{.reg .pred p, q; mbarrier.test_wait.parity.shared::cta.b64 p, [%1], 0; mbarrier.test_wait.parity.shared::cta.b64 q, [%1+8], 0;\n"
                       "and.pred p, p, q; vote.sync.all.pred p, p, 0xffffffff; selp.u32 %0, 1, 0, p;}" : "=r"(ok) : "r"(bar0 + 8 * FB_G) : "memory");
          if (ok) {
#pragma unroll
            for (int i = 0; i < 8; i++) ldsm_t(af[i >> 2][i & 3], (ab + ((i & 2) ? OFF_U : OFF_G) + (i >> 2) * 1024) ^ ((i & 1) << 5));
            have = true;
          }
        }
        if (!__any_sync(~0u, (X16(v[0]) | X16(v[1])) & 1) || ++it_ >= SPIN_MAX) break;
      }
      float df[4][4] = {}, dg[2][4] = {};
      uint32_t zb[4];
      const uint32_t one = g == 0 ? 0x3F803F80u : 0u;
#pragma unroll
      for (int s = 0; s < 2; s++) {
        const uint32_t y0 = pack2(u2f(v[s].x), u2f(v[s].y)), y1 = pack2(u2f(v[s].z), u2f(v[s].w));
        const uint32_t ya[4] = {y0, one, y1, one};
        mma16(dg[s], ya, y0, y1);
        zb[2 * s] = pack2(u2f(v[s].x) * cf[s].x, u2f(v[s].y) * cf[s].y); zb[2 * s + 1] = pack2(u2f(v[s].z) * cf[s].z, u2f(v[s].w) * cf[s].w);
      }
      float st[2] = {(dg[0][2] + dg[0][3]) + (dg[1][2] + dg[1][3]), (dg[0][0] + dg[0][1]) + (dg[1][0] + dg[1][1])};
      if (!have) {
        mbar_wait(bar0 + 8 * FB_G); mbar_wait(bar0 + 8 * (FB_G + 1));
#pragma unroll
        for (int i = 0; i < 8; i++) ldsm_t(af[i >> 2][i & 3], (ab + ((i & 2) ? OFF_U : OFF_G) + (i >> 2) * 1024) ^ ((i & 1) << 5));
      }
#pragma unroll
      for (int i = 0; i < 8; i++) mma16(df[i & 3], af[i >> 2][i & 3], zb[2 * (i >> 2)], zb[2 * (i >> 2) + 1]);
#pragma unroll
      for (int o2 = 1; o2 < 4; o2 <<= 1) { st[0] += __shfl_xor_sync(~0u, st[0], o2); st[1] += __shfl_xor_sync(~0u, st[1], o2); }
#pragma unroll
      for (int o2 = 4; o2 < 32; o2 <<= 1) st[1] += __shfl_xor_sync(~0u, st[1], o2);
      float r[8];
#pragma unroll
      for (int i = 0; i < 8; i++) r[i] = df[i >> 1][2 * (i & 1)] + df[i >> 1][2 * (i & 1) + 1];
      tred<4>(r, lane, 2); tred<2>(r, lane, 1);
      const int md = (tq & 1) == rk ? 1 : 2;
      st_pair(md, ro, psb + OFF_BAR + 8 * (XB + 5), r[0], r[1]);
      st_pair(lane < 2 ? md : 0, ro + 16 * 176, psb + OFF_BAR + 8 * (XB + 5), st[0], st[1]);
      __syncwarp();
      if (lane == 0) BAR_ARRIVE(XB + 5);
      mbar_wait(bar0 + 8 * FB_D);
#pragma unroll
      for (int mt = 0; mt < 4; mt++)
        ldsm_t(ad[mt], a_d ^ (mt << 5));
    }
    mbar_wait(bar0 + 8 * (XB + 5));
    {
      float4 q[5], u[8];
#pragma unroll
      for (int i = 0; i < 5; i++) q[i] = lds16(a_q + i * 16);
#pragma unroll
      for (int i = 0; i < 8; i++) u[i] = *(const float4*)(smem + OFF_R4 + 16 * 176 + (i >> 2) * 80 + (i & 3) * 16);
      float p[6] = {((q[0].x + q[0].z) + (q[1].x + q[1].z)) + ((q[2].x + q[2].z) + (q[3].x + q[3].z)), q[4].x, q[4].z,
                    ((q[0].y + q[0].w) + (q[1].y + q[1].w)) + ((q[2].y + q[2].w) + (q[3].y + q[3].w)), q[4].y, q[4].w};
      tred<3>(p, lane, 8);
      const float P = p[0], A1 = p[1], A2 = p[2];
      const float mean = (((u[0].x + u[0].z) + (u[1].x + u[1].z)) + ((u[2].x + u[2].z) + (u[3].x + u[3].z)) +
                          ((u[4].x + u[4].z) + (u[5].x + u[5].z)) + ((u[6].x + u[6].z) + (u[7].x + u[7].z))) * (1.f / 512.f);
      const float sq = (((u[0].y + u[0].w) + (u[1].y + u[1].w)) + ((u[2].y + u[2].w) + (u[3].y + u[3].w)) +
                         ((u[4].y + u[4].w) + (u[5].y + u[5].w)) + ((u[6].y + u[6].w) + (u[7].y + u[7].w))) * (1.f / 512.f);
      float rstd;
      asm("rsqrt.approx.ftz.f32 %0, %1;" : "=f"(rstd) : "f"(fmaxf(sq - mean * mean, 0.f) + 1e-5f));
      const float gg = bfr(rstd * (P - mean * A1) + A2);
      const float uu = __shfl_xor_sync(~0u, gg, 16);
      const float hh = bfr(gg * rcp(1.f + ex2(gg * (-2.302208198f - 0.1029432397f * gg * gg)))) * uu;
      const uint32_t hw = pack2(hh, __shfl_down_sync(~0u, hh, 1));
      const uint32_t b0 = __shfl_sync(~0u, hw, 2 * tq), b1 = __shfl_sync(~0u, hw, 2 * tq + 8);
      float f0 = 0, f1 = 0;
#pragma unroll
      for (int mt = 0; mt < 4; mt++) {
        float dd[4] = {0, 0, 0, 0};
        mma16(dd, ad[mt], b0, b1);
        if (tq == mt) { f0 = dd[0]; f1 = dd[2]; }
      }
      stx8(p_f, make_uint2(fbits(f0), fbits(f1)));
    }
    tpub = clock();
    if (b < 64 && warp == (b >> 3)) {
      const uint4 y = (b & 4) ? v[1] : v[0];
      float a4[4] = {u2f(y.x), u2f(y.y), u2f(y.z), u2f(y.w)};
      tred<2>(a4, lane, 16); tred<1>(a4, lane, 8);
      a4[0] += __shfl_xor_sync(~0u, a4[0], 4);
      if (!(lane & 4)) s_sm[416 + 8 * (lane >> 4) + 2 * tq + ((lane >> 3) & 1)] = a4[0];
      if (warp == 7) nbar_arrive(2, 256);
    } else if (b < 64 && warp == 7) nbar_arrive(2, 256);
    if (b < 64 && warp < 7) {
      uint4 v;
      const unsigned* pf = g_xf + (tid >> 1) * 512 + 8 * ob + 4 * (tid & 1);
      const int col = 16 * (ob >> 1) + 4 * (ob & 1) + ((tid >> 1) & 3) + 8 * (tid & 1);
      bf16* po = out + col;
      PINL(po); PINL(pf);
      spin_until(tpub + DLY7);
      POLL { v = ldx16(pf); RETRY(X16(v)) }
      float f[4] = {u2f(v.x), u2f(v.y), u2f(v.z), u2f(v.w)};
      tred<2>(f, lane, 16); tred<1>(f, lane, 8);
      f[0] += __shfl_xor_sync(~0u, f[0], 4); f[0] += __shfl_xor_sync(~0u, f[0], 2);
      if (!(lane & 6)) s_sm[352 + warp * 8 + 4 * (lane & 1) + (lane >> 3)] = f[0];
      nbar(2, 256);
      if (tid < 8) {
        const float* q = s_sm + 352 + tid;
        const float t = ((q[0] + q[8]) + (q[16] + q[24])) + ((q[32] + q[40]) + q[48]);
        *po = __float2bfloat16(s_sm[416 + (col & 15)] + bfr(gbv * bfr(t)));
        if (b == 0 && tid == 0) stx4(&g_epoch, epoch + 1);
      }
    }
  }
}

__global__ void __cluster_dims__(2, 1, 1) __launch_bounds__(384, 1)
fused_kernel(const bf16* __restrict__ x, const bf16* __restrict__ cvec, const bf16* __restrict__ w_mod, bf16* __restrict__ out,
             Scratch* __restrict__ scr, const __grid_constant__ TMaps tms) {
  extern __shared__ __align__(1024) unsigned char smem[];
  const int tid = threadIdx.x, warp = __shfl_sync(~0u, tid >> 5, 0), lane = tid & 31;
  const int b = blockIdx.x, rk = b & 1, pr = b >> 1, hd = b >> 2;
  uint32_t sb = s2u(smem), bar0 = sb + OFF_BAR;

  unsigned gt_start;
  asm volatile("mov.u32 %0, %%globaltimer_lo;" : "=r"(gt_start));
  const int g = lane >> 2, tq = lane & 3;
  const int arow = 64 * (b >> 4) + ((tid & 255) >> 3);
  uint4 wm0, wm1;
  uint32_t c0w, c1w;
  if (warp < 8) {
    const bf16* wa = w_mod + (size_t)arow * 3072 + (lane & 4) * 128 + 32 * (b & 15) + 8 * tq;
    wm0 = ldx16(wa); wm1 = ldx16(wa + 32 * 3072);
    c0w = ldc4(cvec + (arow & ~1)); c1w = ldc4(cvec + (arow & ~1) + 32);
  }
  const unsigned t_off = gt_start + RATE_T0;
  if (warp == 11) {
    if (lane == 0) {
#pragma unroll
      for (int i = 0; i < FB_KV; i++) { BAR_INIT(i, 1); BAR_ARM(i, 16384); }
    }
    __syncwarp();
    asm volatile("fence.mbarrier_init.release.cluster;" ::: "memory");
    asm volatile("barrier.cluster.arrive.relaxed.aligned;" ::: "memory");
#pragma unroll 1
    for (int i = 0; i < FB_KV; i++) {
      if (i >= HWIN) mbar_wait(bar0 + 8 * (i - HWIN));
      wait_until(t_off + (i < 4 ? 2 * i + ((b >> 1) & 1) : 4 * i - 8 + (b & 3)) * (RATE_H / 4));
      if (lane == 0) {
        if (i < 4) tma3d(sb + OFF_WQ + i * 16384, &tms.m[0], bar0 + 8 * i, 0, i * 128, 2 * hd + rk);
        else tma3d(sb + OFF_WQ + i * 16384, &tms.m[1], bar0 + 8 * i, 0, (b & 3) * 128 + (i - 4) * 64, 2 * hd);
      }
      __syncwarp();
    }
  }
  if (warp == 10) {
    const uint4 xa = ldc16(x + 16 * lane), xb = ldc16(x + 16 * lane + 8);
    const unsigned ep = ldc4(&g_epoch);
    float xv[16] = {bflo(xa.x), bfhi(xa.x), bflo(xa.y), bfhi(xa.y), bflo(xa.z), bfhi(xa.z), bflo(xa.w), bfhi(xa.w),
                    bflo(xb.x), bfhi(xb.x), bflo(xb.y), bfhi(xb.y), bflo(xb.z), bfhi(xb.z), bflo(xb.w), bfhi(xb.w)};
    float s = 0;
#pragma unroll
    for (int i = 0; i < 16; i++) s += xv[i];
#pragma unroll
    for (int o = 16; o; o >>= 1) s += __shfl_xor_sync(~0u, s, o);
    const float mean = s * (1.f / 512.f);
    s = 0;
#pragma unroll
    for (int i = 0; i < 16; i++) { xv[i] -= mean; s += xv[i] * xv[i]; }
#pragma unroll
    for (int o = 16; o; o >>= 1) s += __shfl_xor_sync(~0u, s, o);
    const float rstd = rsqrtf(s * (1.f / 512.f) + 1e-5f);
    if ((lane >> 1) == (b & 15))
#pragma unroll
      for (int i = 0; i < 4; i++)
        *(float4*)(smem + OFF_SM + (256 + (lane & 1) * 16 + 4 * i) * 4) = make_float4(xv[4 * i] * rstd, xv[4 * i + 1] * rstd, xv[4 * i + 2] * rstd, xv[4 * i + 3] * rstd);
    if (lane == 0) *(volatile unsigned*)(smem + OFF_MASK + 8) = ep;
    nbar_arrive(1, 288);
  }
  if (warp >= 8) {
    asm volatile("setmaxnreg.dec.sync.aligned.u32 72;");
    if (tid == 288) {
#pragma unroll
      for (int q = FB_KV; q < FB_KV + 16; q++) { BAR_INIT(q, 1); BAR_ARM(q, 32768); }
    }
    if (tid == 320) {
#pragma unroll
      for (int q = 0; q <= 13 + NSLOT; q++) BAR_INIT(EB + q, q == 0 ? 4 : q < 5 ? 16 : q < 16 ? 12 : 6);
    }
    if (tid == 256) {
#pragma unroll
      for (int q = FB_MOD; q <= FB_D; q++) { BAR_INIT(q, 1); BAR_ARM(q, 16384); }
      BAR_INIT(QB, 9); BAR_ARM(QB, 1024);
#pragma unroll
      for (int q = 0; q < 7; q++) BAR_INIT(XB + q, q == 2 ? 256 : q == 5 || q == 3 ? 9 : 1);
      BAR_ARM(XB + 3, 1024);
      BAR_ARM(XB + 5, 1024 + 64 + 512);
      *(volatile unsigned long long*)(smem + OFF_MASK) = 0;
    }
    if (warp != 11) {
      __syncwarp();
      asm volatile("fence.mbarrier_init.release.cluster;" ::: "memory");
      __threadfence_block();
      asm volatile("barrier.cluster.arrive.relaxed.aligned;" ::: "memory");
    }
    if (warp == 11) {
      asm volatile("barrier.cluster.wait.acquire.aligned;" ::: "memory");
      const unsigned epoch = *(volatile unsigned*)(smem + OFF_MASK + 8), par = (epoch + 1) & 1;
      mbar_wait(bar0 + 8 * (FB_KV + 15));
      for (int it = 0; ldx4(scr->cnt + 96 + 32 * (b >> 6)) != (epoch + 1) * 64 && it < SPIN_MAX; it++) {}
      uint4 hh;
      POLL { hh = ldx16(g_ml + (b >> 2) * 64 + 2 * lane); RETRY(X16(hh)) }
      int mi = __float_as_int(fmaxf(u2f(hh.x), u2f(hh.z)));
      mi ^= (mi >> 31) & 0x7fffffff;
      mi = __reduce_max_sync(~0u, mi);
      mi ^= (mi >> 31) & 0x7fffffff;
      const float M = __int_as_float(mi);
      const uint32_t wp = pack2(ex2(u2f(hh.x) - M), ex2(u2f(hh.z) - M));
      float L = bflo(wp) * u2f(hh.y) + bfhi(wp) * u2f(hh.w);
#pragma unroll
      for (int o2 = 16; o2; o2 >>= 1) L += __shfl_xor_sync(~0u, L, o2);
      *(uint32_t*)(smem + OFF_RA + lane * 4) = wp;
      if (lane == 0) *(float*)(smem + OFF_RA + 128) = rcp(L);
      __syncwarp();
      if (lane == 0) BAR_ARRIVE(XB + 6);
    }
    if (warp == 10) {
      if (lane < 8) asm volatile("prefetch.tensormap [%0];" ::"l"(&tms.m[lane + 1]) : "memory");
      asm volatile("barrier.cluster.wait.acquire.aligned;" ::: "memory");
      const unsigned epoch = *(volatile unsigned*)(smem + OFF_MASK + 8);
#pragma unroll 1
      for (int e = 0; e < 2; e++) {
        for (int it = 0; ldx4(scr->cnt + (e ? 2 + rk : 1)) != (epoch + 1) * (e ? 64 : 128) && it < SPIN_MAX; it++) {}
        if (lane == 0) BAR_ARRIVE(XB + e);
      }
      mbar_wait(bar0 + 8 * (FB_KV + 14));
      unsigned long long m = 0;
#pragma unroll 1
      for (int it = 0; ~m && it < SPIN_MAX; it++) {
        m = ldx64(scr->cnt + 32 + 32 * (b >> 6)) ^ ((epoch & 1) ? ~0ull : 0ull);
        if (lane == 0) *(volatile unsigned long long*)(smem + OFF_MASK) = m;
      }
    }
    if (warp == 9) {
      asm volatile("barrier.cluster.wait.acquire.aligned;" ::: "memory");
      const unsigned epoch = *(volatile unsigned*)(smem + OFF_MASK + 8);
      const unsigned par = (epoch + 1) & 1, inv = par ^ 1;
      const uint4 inv4 = make_uint4(inv, inv, inv, inv);
      mbar_wait(bar0 + 8 * FB_KV);
#pragma unroll 2
      for (int k = 0; k < 8; k++) {
        const uint32_t cp = ldc4(cvec + 2 * (lane + 32 * k));
        *(uint32_t*)(smem + OFF_SILU + (lane + 32 * k) * 4) = pack2(silu_bf(bflo(cp)), silu_bf(bfhi(cp)));
      }
      __syncwarp();
      mbar_wait(bar0 + 8 * FB_MOD);
      const uint32_t ab = sb + OFF_MOD + (8 * (lane >> 4) + (lane & 7)) * 32 + ((((lane >> 3) ^ (lane >> 2)) & 1) << 4);
      float d[4][4] = {};
#pragma unroll 2
      for (int s4 = 0; s4 < 8; s4++)
#pragma unroll
        for (int s = 0; s < 4; s++) {
          uint32_t a[4];
          const uint32_t* ps = (const uint32_t*)(smem + OFF_SILU) + 32 * s4 + 8 * s + tq;
          ldsm_t(a, ab + (4 * s4 + s) * 512); mma16(d[s], a, ps[0], ps[4]);
        }
      const float t = (tq & 1) ? (d[0][2] + d[1][2]) + (d[2][2] + d[3][2]) : (d[0][0] + d[1][0]) + (d[2][0] + d[3][0]);
      if (tq < 2) stx4(g_xm + b * 16 + 2 * (g & 6) + 2 * tq + (g & 1), fbits(bfr(t)));
      __syncwarp();
      if (lane == 0) CNT_ADD(6);
      mbar_wait(bar0 + 8 * (FB_KV + 8));
      if (lane < 16) stx16(g_xc + (b >> 2) * 256 + (lane >> 1) * 32 + (b & 3) * 8 + (lane & 1) * 4, inv4);
      if (lane < 8) stx16(g_xao + (b >> 5) * 1024 + (b & 15) * 64 + (lane & 4) * 8 + (b & 16) + (lane & 3) * 4, inv4);
      if (b < 112)
#pragma unroll 1
        for (int k = 0; k < 4; k++) stx16(g_xf + b * 512 + (lane + 32 * k) * 4, inv4);
      nbar_arrive(2, 288);
      for (int it = 0; ldx4(scr->cnt + 6) != (epoch + 1) * 128 && it < SPIN_MAX; it++) __nanosleep(100);
      {
        uint4 sv[2], cb[2];
        unsigned ga, gb;
        POLL {
#pragma unroll
          for (int k = 0; k < 2; k++) { sv[k] = ldx16(g_xm + 512 + 256 * rk + 4 * (lane + 32 * k)); cb[k] = ldx16(g_xm + 1024 + 256 * rk + 4 * (lane + 32 * k)); }
          ga = ldx4(g_xm + (b & 15) * 32 + lane); gb = ldx4(g_xm + 1536 + 256 * rk + 8 * (pr & 31) + (lane & 7));
          RETRY(X16(sv[0]) | X16(sv[1]) | X16(cb[0]) | X16(cb[1]) | lop_x3(ga, gb, par))
        }
#pragma unroll
        for (int k = 0; k < 2; k++) {
          const float c0 = bfr(1.f + bfhi(cb[k].x)), c1 = bfr(1.f + bfhi(cb[k].y)), c2 = bfr(1.f + bfhi(cb[k].z)), c3 = bfr(1.f + bfhi(cb[k].w));
          *(float4*)(smem + OFF_CO + (lane + 32 * k) * 16) = make_float4(c0, c1, c2, c3);
          uint2* pb = (uint2*)(smem + OFF_BP) + lane + 32 * k;
          pb[0] = make_uint2(pack2(c0, c1), pack2(c2, c3));
          pb[64] = make_uint2(__byte_perm(sv[k].x, sv[k].y, 0x7632), __byte_perm(sv[k].z, sv[k].w, 0x7632));
        }
        *(float*)(smem + OFF_CO + 1024 + lane * 4) = bfhi(ga);
        *(float*)(smem + OFF_CO + 1152 + lane * 4) = bfhi(gb);
      }
      __syncwarp();
      if (lane == 0) BAR_ARRIVE(XB + 4);
    }
    if (warp == 8) {
      const unsigned stag = ((pr * SMUL) & 63) * RATE_NS >> 6;
      unsigned tnext = t_off + 4 * RATE_H;
      asm volatile("barrier.cluster.wait.acquire.aligned;" ::: "memory");
#pragma unroll 1
      for (int k = 0; k < 24; k++) {
        const int code = (k < 12 ? ORDER0 >> (5 * k) : ORDER1 >> (5 * (k - 12))) & 31;
        const bool kv = code < 16;
        const int n = code, w = code - 16;
        if (!kv && w >= 5 && b >= 112) break;
        if (kv) mbar_wait(bar0 + 8 * (FB_KV + n - (n < 6 ? EWIN : KVWIN)));
        if (k >= TAIL_K) mbar_wait(bar0 + 8 * (FB_KV + (int)((ORDER1 >> (5 * (k - 12 - ((WINS >> (4 * (k - TAIL_K))) & 15)))) & 31)));
        const int e = kv ? (n == 3 ? 2 : n == 5 ? 1 : n) : w == 0 ? 0 : w < 5 ? 16 + ((w - 1) >> 1) : w == 7 ? 19 : 18;
        if (e != 1 && k) mbar_wait(bar0 + 8 * (EB + e));
        wait_until(tnext + stag);
        tnext += k > TAIL_K ? RATE_TL : k < 4 ? RATE_E : RATE_NS;
        if (lane == 0) {
          if (kv)
            asm volatile("cp.async.bulk.tensor.3d.shared::cluster.global.mbarrier::complete_tx::bytes.multicast::cluster.L2::cache_hint [%0], [%1, {%3, %4, %5}], [%2], %6, %7;"
                         ::"r"(sb + (n % NSLOT) * SLOT + rk * 16384), "l"(&tms.m[2]), "r"(bar0 + 8 * (FB_KV + n)), "r"(0), "r"(((n >> 1) * 64 + pr) * 64),
                           "r"(4 * (n & 1) + 2 * rk), "h"((unsigned short)3), "l"(stream_policy()) : "memory");
          else {
            tma3d(sb + (w == 0 ? OFF_MOD : w < 5 ? OFF_UV + (w - 1) * 16384 : w == 5 ? OFF_G : w == 6 ? OFF_U : OFF_D),
                  &tms.m[w == 0 ? 3 : w < 3 ? 4 : w < 5 ? 5 : w + 1], bar0 + 8 * (FB_MOD + w),
                  w == 0 ? 1024 + b * 16 : w < 3 || w == 7 ? 0 : w < 5 ? (pr & 7) * 64 : pr * 32, w == 7 ? b * 16 : w == 1 || w == 2 ? (b & 3) * 128 + (w - 1) * 64 : 0,
                  w == 1 || w == 2 ? 2 * hd : w == 3 || w == 4 ? (b >> 4) * 4 + 2 * rk + w - 3 : w == 5 || w == 6 ? rk : 0);
          }
        }
        __syncwarp();
      }
    }
    if (b < 112) {
      const int mt = warp & 1, dd = (warp >> 1) & 1;
      mbar_wait(bar0 + 8 * (XB + 4));
      const uint32_t ab = sb + (mt ? OFF_U : OFF_G) + (8 * (lane >> 4) + (lane & 7)) * 64 + (((2 * dd + ((lane >> 3) & 1)) ^ ((lane >> 1) & 3)) << 4);
      uint32_t base;
      asm volatile("mapa.shared::cluster.u32 %0, %1, %2;" : "=r"(base) : "r"(sb), "r"(dd));
      uint2 bb[16];
#pragma unroll
      for (int s = 0; s < 16; s++) bb[s] = *(const uint2*)(smem + OFF_BP + (g & 1) * 512 + (4 * s + tq) * 8);
      mbar_wait(bar0 + 8 * (FB_G + mt));
      float e[4][4] = {};
#pragma unroll
      for (int s = 0; s < 16; s++) { uint32_t a[4]; ldsm_t(a, ab + s * 1024); mma16(e[s & 3], a, bb[s].x, bb[s].y); }
      float r[4];
#pragma unroll
      for (int i = 0; i < 4; i++) r[i] = (e[0][i] + e[1][i]) + (e[2][i] + e[3][i]);
      if (tq < 2) st_async2(base + OFF_R4 + (8 * mt + g) * 176 + (10 * rk + 8 + tq) * 8, base + OFF_BAR + 8 * (XB + 5), tq ? r[1] : r[0], tq ? r[3] : r[2]);
    }
    return;
  }

  float* s_sm = (float*)(smem + OFF_SM);
  unsigned par, epoch;
  uint32_t rsb;
  {
    float* s_r4 = (float*)(smem + OFF_R4);
    asm volatile("barrier.cluster.arrive.relaxed.aligned;" ::: "memory");
    asm volatile("mapa.shared::cluster.u32 %0, %1, %2;" : "=r"(rsb) : "r"(sb), "r"(rk ^ 1));
    const float c0 = (arow & 1) ? bfhi(c0w) : bflo(c0w), c1 = (arow & 1) ? bfhi(c1w) : bflo(c1w);
    float acc[8] = {0, 0, 0, 0, 0, 0, 0, 0};
    fma8(acc, wm0, silu_bf(c0)); fma8(acc, wm1, silu_bf(c1));
    tred<4>(acc, lane, 8); tred<2>(acc, lane, 16);
    *(float2*)(s_r4 + warp * 64 + 8 * (lane & 7) + ((lane >> 1) & 4) + ((lane >> 3) & 2)) = make_float2(acc[0], acc[1]);
    nbar(1, 288);
    epoch = *(volatile unsigned*)(smem + OFF_MASK + 8);
    par = (epoch + 1) & 1;
    if (warp == 0) {
      float t = 0.f, ca = b < 16 ? 1.f : 0.f;
#pragma unroll
      for (int w = 0; w < 8; w++) { t += s_r4[w * 64 + lane]; ca += s_r4[w * 64 + 32 + lane]; }
      t += ca * s_sm[256 + lane];
      const float nb = __shfl_down_sync(~0u, t, 1);
      const uint32_t w0 = lane < 8 ? pack2t(t, nb, par) : pack2(t, nb);
      const uint32_t w1 = __shfl_down_sync(~0u, w0, 8), w2 = __shfl_down_sync(~0u, w0, 16), w3 = __shfl_down_sync(~0u, w0, 24);
      if (lane < 8 && !(lane & 1)) stx16(g_h + (b >> 5) * 512 + (b & 15) * 32 + (b & 16) + 2 * lane, make_uint4(w0, w1, w2, w3));
      __syncwarp();
      if (lane == 0) CNT_ADD(1);
    }
  }
  asm volatile("barrier.cluster.wait.acquire.aligned;" ::: "memory");
  {
    uint32_t a[4][4][4];
    mbar_wait(bar0 + 8 * (warp >> 1));
    const uint32_t ab = sb + OFF_WQ + (64 * warp + 8 * (lane >> 4) + (lane & 7)) * 128;
#pragma unroll
    for (int s = 0; s < 4; s++)
#pragma unroll
      for (int mt = 0; mt < 4; mt++) ldsm_t(a[s][mt], ab + s * 2048 + (((2 * mt + ((lane >> 3) & 1)) ^ (lane & 7)) << 4));
    uint4 v0, v1;
    const unsigned* ph = g_h + (g >> 1) * 512 + 64 * warp + 4 * (lane & 7);
    uint32_t off = OFF_B + warp * 272 + (32 * rk + 8 * tq + (lane & 4)) * 4;
    PIN(off); PINL(ph);
    mbar_wait(bar0 + 8 * XB);
    POLL { v0 = ldx16(ph); v1 = ldx16(ph + 32); RETRY(lop_x3(v0.x, v1.x, par)) }
    float d[4][4] = {};
#pragma unroll
    for (int mt = 0; mt < 4; mt++) {
      mma16(d[mt], a[0][mt], v0.x, v0.y); mma16(d[mt], a[1][mt], v0.z, v0.w);
      mma16(d[mt], a[2][mt], v1.x, v1.y); mma16(d[mt], a[3][mt], v1.z, v1.w);
    }
    float r[8];
#pragma unroll
    for (int mt = 0; mt < 4; mt++) { r[2 * mt] = d[mt][0] + d[mt][1]; r[2 * mt + 1] = d[mt][2] + d[mt][3]; }
    tred<4>(r, lane, 2); tred<2>(r, lane, 1);
    const float rc = __shfl_xor_sync(~0u, (lane & 4) ? r[0] : r[1], 4);
    const uint32_t wd = (lane & 4) ? pack2(rc, r[1]) : pack2(r[0], rc);
    const uint32_t w1 = __shfl_down_sync(~0u, wd, 8), w2 = __shfl_down_sync(~0u, wd, 16), w3 = __shfl_down_sync(~0u, wd, 24);
    asm volatile("{.reg .pred p; setp.lt.s32 p, %7, 8; @p st.shared.v4.b32 [%0], {%2,%3,%4,%5};\n"
                 "@p st.async.shared::cluster.mbarrier::complete_tx::bytes.v4.b32 [%1], {%2,%3,%4,%5}, [%6];}"
                 ::"r"(sb + off), "r"(rsb + off), "r"(wd), "r"(w1), "r"(w2), "r"(w3), "r"(rsb + OFF_BAR + 8 * QB), "r"(lane) : "memory");
    __syncwarp();
    arrive2(bar0 + 8 * QB, 0, lane == 0, false);
    arrive2(bar0 + 8 * (EB + 2), rsb + OFF_BAR + 8 * (EB + 2), lane == 0, lane == 0);
  }
  {
    uint32_t a[8][4];
    uint32_t a_bq = sb + OFF_B + (lane & 7) * 272 + (lane >> 3) * 16;
    unsigned* p_qa = g_qa + b * 64 + 8 * warp + 4 * lane;
    PIN(a_bq); PINL(p_qa);
    mbar_wait(bar0 + 8 * (FB_UK + (warp >> 2)));
    const uint32_t ab = sb + OFF_WUK + (warp >> 2) * 16384 + (16 * (warp & 3) + (lane & 15)) * 128;
#pragma unroll
    for (int s = 0; s < 8; s++) ldsm(a[s], ab + (s >> 2) * 8192 + (((2 * (s & 3) + (lane >> 4)) ^ (lane & 7)) << 4));
    mbar_wait(bar0 + 8 * QB);
    float d[4][4] = {};
#pragma unroll
    for (int y = 0; y < 4; y++) {
      uint32_t bq[4];
      ldsm(bq, a_bq + 64 * y);
      mma16(d[(2 * y) & 3], a[2 * y], bq[0], bq[1]); mma16(d[(2 * y + 1) & 3], a[2 * y + 1], bq[2], bq[3]);
    }
    float r[2] = {((d[0][0] + d[0][1]) + (d[1][0] + d[1][1])) + ((d[2][0] + d[2][1]) + (d[3][0] + d[3][1])),
                  ((d[0][2] + d[0][3]) + (d[1][2] + d[1][3])) + ((d[2][2] + d[2][3]) + (d[3][2] + d[3][3]))};
    tred<1>(r, lane, 1);
    r[0] += __shfl_xor_sync(~0u, r[0], 2);
    const float nb = __shfl_xor_sync(~0u, r[0], 4);
    const uint32_t w0 = lane < 8 ? pack2t(r[0], nb, par) : pack2(r[0], nb);
    const uint32_t w1 = __shfl_down_sync(~0u, w0, 8), w2 = __shfl_down_sync(~0u, w0, 16), w3 = __shfl_down_sync(~0u, w0, 24);
    if (lane < 2) stx16(p_qa, make_uint4(w0, w1, w2, w3));
    arrive2(bar0 + 8 * (EB + 4), rsb + OFF_BAR + 8 * (EB + 4), lane == 0, lane == 0);
  }
  {
    if (warp) nbar_arrive(3, 256); else { nbar(3, 256); if (lane == 0) CNT_ADD(2 + (b >> 6)); }
    asm volatile("setmaxnreg.inc.sync.aligned.u32 216;");
    const unsigned* pq = g_qa + rk * 4096 + tid * 4;
    uint32_t a_q = sb + OFF_Q + ((tid & 63) >> 3) * 2048 + (tid >> 6) * 128 + (((tid & 7) ^ (tid >> 6)) << 4);
    PINL(pq); PIN(a_q);
    mbar_wait(bar0 + 8 * (XB + 1));
    uint4 v[4];
    POLL {
#pragma unroll
      for (int k = 0; k < 4; k++) v[k] = ldx16(pq + 1024 * k);
      RETRY(lop_x3(v[0].x, v[1].x, par) | lop_x3(v[2].x, v[3].x, par))
    }
#pragma unroll
    for (int k = 0; k < 4; k++)
      asm volatile("st.shared.v4.b32 [%0], {%1,%2,%3,%4};" ::"r"((a_q + k * 512) ^ ((k & 1) << 6)), "r"(v[k].x), "r"(v[k].y), "r"(v[k].z), "r"(v[k].w) : "memory");
    if (warp >= 4) nbar_arrive(1, 256); else nbar(1, 256);
  }
  sb = __shfl_sync(~0u, sb, 0); bar0 = sb + OFF_BAR;
  if (warp < 4) {
    uint32_t qf[32][4];
#pragma unroll
    for (int s = 0; s < 32; s++) ldsm(qf[s], sb + OFF_Q + (s >> 2) * 2048 + (lane & 15) * 128 + (((2 * (s & 3) + (lane >> 4)) ^ (lane & 7)) << 4));
    float l0 = 0.f, l1 = 0.f, m0 = -1e30f, m1 = -1e30f;
    const float sc = 0.08838834764831845f * 1.4426950408889634f;
    const uint32_t kofs = (16 * warp + 8 * (lane >> 4) + (lane & 7)) * 128 + ((((lane >> 3) & 1) ^ (lane & 7)) << 4);
    uint32_t st = sb;
#pragma unroll 1
    for (int t = 0; t < 8; t++) {
      float sa[4][4] = {};
#pragma unroll
      for (int hf = 0; hf < 2; hf++) {
        const int n = 2 * t + hf;
        mbar_wait(bar0 + 8 * (FB_KV + n));
        uint32_t kf[16][4];
#pragma unroll
        for (int y = 0; y < 16; y++) ldsm(kf[y], st + (y >> 2) * 8192 + (kofs ^ ((y & 3) << 5)));
#pragma unroll
        for (int y = 0; y < 16; y++) {
          mma16(sa[(2 * y) & 3], qf[16 * hf + y], kf[y][0], kf[y][1]); mma16(sa[((2 * y) & 3) + 1], qf[16 * hf + y], kf[y][2], kf[y][3]);
        }
        __syncwarp();
        arrive2(bar0 + 8 * (EB + NSLOT + n), rsb + OFF_BAR + 8 * (EB + NSLOT + n), lane == 0 && n < 14, lane == 0 && n < 16 - NSLOT);
        if (hf == 0) arrive2(bar0 + 8 * EB, 0, lane == 0 && t == 0, false);
        st = st + SLOT == sb + NSLOT * SLOT ? sb : st + SLOT;
      }
#pragma unroll
      for (int i = 0; i < 4; i++) { sa[0][i] = (sa[0][i] + sa[2][i]) * sc; sa[1][i] = (sa[1][i] + sa[3][i]) * sc; }
      float cm[2] = {fmaxf(fmaxf(sa[0][0], sa[0][1]), fmaxf(sa[1][0], sa[1][1])), fmaxf(fmaxf(sa[0][2], sa[0][3]), fmaxf(sa[1][2], sa[1][3]))};
      tmax<1>(cm, lane, 1);
      cm[0] = fmaxf(cm[0], __shfl_xor_sync(~0u, cm[0], 2));
      float* pm = s_sm + (t & 1) * 64;
      if (tq < 2) pm[(g + 8 * tq) * 4 + warp] = cm[0];
      if (t >= 2) nbar(6 + (t & 1), 256); else nbar(3, 128);
      const float4 a0 = *(const float4*)(pm + g * 4), b0 = *(const float4*)(pm + g * 4 + 32);
      const float n0 = fmaxf(fmaxf(fmaxf(a0.x, a0.y), fmaxf(a0.z, a0.w)), m0), n1 = fmaxf(fmaxf(fmaxf(b0.x, b0.y), fmaxf(b0.z, b0.w)), m1);
      uint32_t pk[4];
#pragma unroll
      for (int i = 0; i < 2; i++) { pk[2 * i] = pack2(ex2(sa[i][0] - n0), ex2(sa[i][1] - n0)); pk[2 * i + 1] = pack2(ex2(sa[i][2] - n1), ex2(sa[i][3] - n1)); }
      *(uint4*)(smem + OFF_P + (t & 1) * 2048 + tid * 16) = make_uint4(pk[0], pk[1], pk[2], pk[3]);
      const float al0 = ex2(m0 - n0), al1 = ex2(m1 - n1);
      if (tid < 32 && tq == 0) *(float2*)(s_sm + 192 + (t & 1) * 16 + 2 * g) = make_float2(al0, al1);
      nbar_arrive(4 + (t & 1), 256);
      m0 = n0; m1 = n1;
      l0 = l0 * al0 + (bflo(pk[0]) + bfhi(pk[0])) + (bflo(pk[2]) + bfhi(pk[2]));
      l1 = l1 * al1 + (bflo(pk[1]) + bfhi(pk[1])) + (bflo(pk[3]) + bfhi(pk[3]));
    }
    float lr[2] = {l0, l1};
    tred<1>(lr, lane, 1);
    lr[0] += __shfl_xor_sync(~0u, lr[0], 2);
    if (tq < 2) s_sm[128 + (g + 8 * tq) * 4 + warp] = lr[0];
    nbar(3, 128);
    if (warp == 0 && tq < 2) {
      const float4 a0 = *(const float4*)(s_sm + 128 + (g + 8 * tq) * 4);
      stx8(g_ml + (16 * rk + g + 8 * tq) * 64 + pr, make_uint2(fbits(tq ? m1 : m0), fbits((a0.x + a0.y) + (a0.z + a0.w))));
    }
    if (warp == 0) { __syncwarp(); if (lane == 0) CNT_ADD(96 + 32 * rk); }
    nbar(2, 288);
    if (tid == 0) asm volatile("red.relaxed.gpu.global.xor.b64 [%0], %1;" ::"l"(scr->cnt + 32 + 32 * rk), "l"(1ull << pr) : "memory");
  } else {
    float o[16][4] = {};
    const uint32_t vofs = (warp & 1) * 16384 + (lane & 15) * 128 + (((lane >> 4) ^ (lane & 7)) << 4);
    const int hf = (warp >> 1) & 1;
    uint32_t st = sb + hf * SLOT;
    auto pv = [&](const int t, auto np) {
      constexpr int npre = decltype(np)::value;
      uint32_t vf[4][8][4];
      const int n = 2 * t + hf;
      mbar_wait(bar0 + 8 * (FB_KV + n));
#pragma unroll
      for (int s = 0; s < npre; s++)
#pragma unroll
        for (int y = 0; y < 8; y++) ldsm_t(vf[s][y], st + (y >> 2) * 8192 + s * 2048 + (vofs ^ ((y & 3) << 5)));
      nbar(4 + (t & 1), 256);
      const float2 al = *(const float2*)(s_sm + 192 + (t & 1) * 16 + 2 * g);
      uint4 pf[4];
#pragma unroll
      for (int s = 0; s < 4; s++) pf[s] = *(const uint4*)(smem + OFF_P + (t & 1) * 2048 + s * 512 + lane * 16);
      if (t < 6) nbar_arrive(6 + (t & 1), 256);
#pragma unroll
      for (int s = npre; s < 4; s++)
#pragma unroll
        for (int y = 0; y < 8; y++) ldsm_t(vf[s][y], st + (y >> 2) * 8192 + s * 2048 + (vofs ^ ((y & 3) << 5)));
#pragma unroll
      for (int nt = 0; nt < 16; nt++) { o[nt][0] *= al.x; o[nt][1] *= al.x; o[nt][2] *= al.y; o[nt][3] *= al.y; }
#pragma unroll
      for (int s = 0; s < 4; s++) {
        const uint32_t pa[4] = {pf[s].x, pf[s].y, pf[s].z, pf[s].w};
#pragma unroll
        for (int y = 0; y < 8; y++) { mma16(o[2 * y], pa, vf[s][y][0], vf[s][y][1]); mma16(o[2 * y + 1], pa, vf[s][y][2], vf[s][y][3]); }
      }
      __syncwarp();
      arrive2(bar0 + 8 * (EB + NSLOT + n), rsb + OFF_BAR + 8 * (EB + NSLOT + n), lane == 0 && n < 14, lane == 0 && n < 16 - NSLOT);
      st = st + 2 * SLOT >= sb + NSLOT * SLOT ? st - (NSLOT - 2) * SLOT : st + 2 * SLOT;
    };
#pragma unroll 1
    for (int t = 0; t < 7; t++) pv(t, IC<NPRE0>());
    pv(7, IC<NPRE1>());
    uint4* po = g_xo + ((size_t)((16 * rk + (g & 6)) * 4 + warp - 4) * 64 + pr) * RS + (lane & 7);
    const bool odd = lane & 4;
#pragma unroll
    for (int e = 0; e < 2; e++)
#pragma unroll
      for (int j2 = 0; j2 < 2; j2++) {
        uint32_t c0[4], c1[4];
#pragma unroll
        for (int i = 0; i < 4; i++) {
          c0[i] = i ? pack2(o[8 * j2 + i][2 * e], o[8 * j2 + i][2 * e + 1]) : pack2t(o[8 * j2][2 * e], o[8 * j2][2 * e + 1], par);
          c1[i] = i ? pack2(o[8 * j2 + 4 + i][2 * e], o[8 * j2 + 4 + i][2 * e + 1]) : pack2t(o[8 * j2 + 4][2 * e], o[8 * j2 + 4][2 * e + 1], par);
          const uint32_t r = __shfl_xor_sync(~0u, odd ? c0[i] : c1[i], 4);
          if (odd) c0[i] = r; else c1[i] = r;
        }
        stx16(po + e * 8 * 4 * 64 * RS + 8 * j2, make_uint4(c0[0], c0[1], c0[2], c0[3]));
        stx16(po + (e * 8 + 1) * 4 * 64 * RS + 8 * j2, make_uint4(c1[0], c1[1], c1[2], c1[3]));
      }
    nbar_arrive(2, 288);
  }
  tail(smem, scr, x, out, par, epoch, warp);
}

static void launch(void* const* d_in, void* d_out) {
  static TMaps tms;
  static bool init = false;
  static void* scr = nullptr;
  if (!init) {
    void* fn = nullptr; cudaDriverEntryPointQueryResult qr;
    cudaGetDriverEntryPoint("cuTensorMapEncodeTiled", &fn, cudaEnableDefault, &qr);
    EncFn f = (EncFn)fn;
    const CUtensorMapSwizzle S32 = CU_TENSOR_MAP_SWIZZLE_32B, S64 = CU_TENSOR_MAP_SWIZZLE_64B, S128 = CU_TENSOR_MAP_SWIZZLE_128B;
    const CUtensorMapL2promotion P128 = CU_TENSOR_MAP_L2_PROMOTION_L2_128B, P256 = CU_TENSOR_MAP_L2_PROMOTION_L2_256B;
    enc3d(f, &tms.m[0], d_in[2], 64, 512, 64, 8192, 128, 64, 128, 1, S128, P128);
    enc3d(f, &tms.m[1], d_in[3], 64, 512, 64, 8192, 128, 64, 64, 2, S128, P256);
    enc3d(f, &tms.m[2], d_in[1], 64, SK, 8, 1024, 128, 64, 64, 2, S128, P256);
    enc3d(f, &tms.m[3], d_in[11], 3072, 256, 2, 6144, 256 * 6144, 16, 256, 2, S32, P128);
    enc3d(f, &tms.m[4], d_in[4], 64, 512, 64, 8192, 128, 64, 64, 2, S128, P256);
    enc3d(f, &tms.m[5], d_in[5], 512, 128, 32, 1024, 128 * 1024, 64, 128, 1, S128, P128);
    enc3d(f, &tms.m[6], d_in[7], 1792, 256, 2, 3584, 256 * 3584, 32, 256, 1, S64, P128);
    enc3d(f, &tms.m[7], d_in[8], 1792, 256, 2, 3584, 256 * 3584, 32, 256, 1, S64, P128);
    enc3d(f, &tms.m[8], d_in[9], 64, 1792, 8, 1024, 128, 64, 16, 8, S128, P256);
    cudaFuncSetAttribute(fused_kernel, cudaFuncAttributeMaxDynamicSharedMemorySize, SMEM_BYTES);
    cudaGetSymbolAddress(&scr, g_scr);
    init = true;
  }
  fused_kernel<<<NCTA, 384, SMEM_BYTES>>>((const bf16*)d_in[0], (const bf16*)d_in[10], (const bf16*)d_in[11], (bf16*)d_out, (Scratch*)scr, tms);
}

}

extern "C" void kernel_launch(void* const* d_in, const int* in_sizes, int n_in, void* d_out, int out_size) {
  static int big = -1;
  if (big < 0) big = v9::fits();
  if (big) v9::launch(d_in, d_out); else v8::launch(d_in, d_out);
}
```

```cpp
#include <cuda_runtime.h>
#include <cuda_bf16.h>
#include <cuda.h>
#include <stdint.h>
#include <stdio.h>
#include <stdlib.h>

typedef CUresult (*EncFn)(CUtensorMap*, CUtensorMapDataType, cuuint32_t, void*, const cuuint64_t*, const cuuint64_t*,
                          const cuuint32_t*, const cuuint32_t*, CUtensorMapInterleave, CUtensorMapSwizzle,
                          CUtensorMapL2promotion, CUtensorMapFloatOOBfill);

static void enc3d(EncFn fn, CUtensorMap* tm, void* p, uint64_t d0, uint64_t d1, uint64_t d2, uint64_t s1, uint64_t s2, uint32_t b0,
                  uint32_t b1, uint32_t b2, CUtensorMapSwizzle sw, CUtensorMapL2promotion pr) {
  cuuint64_t gd[3] = {d0, d1, d2}, gs[2] = {s1, s2};
  cuuint32_t bx[3] = {b0, b1, b2}, es[3] = {1, 1, 1};
  fn(tm, CU_TENSOR_MAP_DATA_TYPE_BFLOAT16, 3, p, gd, gs, bx, es, CU_TENSOR_MAP_INTERLEAVE_NONE, sw, pr, CU_TENSOR_MAP_FLOAT_OOB_FILL_NONE);
}

namespace v9 {
typedef __nv_bfloat16 bf16;
#define SK 32768
#define SPIN_MAX (1 << 20)
template <int N> struct IC { static constexpr int value = N; };

__device__ __forceinline__ uint32_t s2u(const void* p) { return (uint32_t)__cvta_generic_to_shared(p); }
__device__ __forceinline__ float bflo(uint32_t u) { return __uint_as_float(u << 16); }
__device__ __forceinline__ float bfhi(uint32_t u) { return __uint_as_float(u & 0xffff0000u); }
__device__ __forceinline__ float u2f(uint32_t u) { return __uint_as_float(u); }
__device__ __forceinline__ void fma8(float* acc, uint4 v, float s) {
  acc[0] += s * bflo(v.x); acc[1] += s * bfhi(v.x); acc[2] += s * bflo(v.y); acc[3] += s * bfhi(v.y);
  acc[4] += s * bflo(v.z); acc[5] += s * bfhi(v.z); acc[6] += s * bflo(v.w); acc[7] += s * bfhi(v.w);
}
__device__ __forceinline__ uint32_t pack2(float a, float b) {
  __nv_bfloat162 p = __floats2bfloat162_rn(a, b); return *(uint32_t*)&p;
}
__device__ __forceinline__ float bfr(float v) { return bfhi(pack2(v, v)); }
__device__ __forceinline__ float silu_bf(float c) { return bfr(__fdividef(c, 1.f + __expf(-c))); }
#define fbits(v) ((__float_as_uint(v) & ~1u) | par)
__device__ __forceinline__ uint32_t pack2t(float a, float b, unsigned par) {
  const uint32_t ua = ((__float_as_uint(a) + ((par ^ 1) << 16)) & 0xFFFE0000u) | (par << 16);
  return __byte_perm(ua, pack2(b, b), 0x7632);
}
__device__ __forceinline__ void nbar(int id, int n) { asm volatile("bar.sync %0, %1;" ::"r"(id), "r"(n) : "memory"); }
__device__ __forceinline__ void nbar_arrive(int id, int n) { asm volatile("bar.arrive %0, %1;" ::"r"(id), "r"(n) : "memory"); }
__device__ __forceinline__ uint4 ldc16(const void* p) {
  uint4 v; asm volatile("ld.relaxed.cta.global.v4.u32 {%0,%1,%2,%3}, [%4];" : "=r"(v.x), "=r"(v.y), "=r"(v.z), "=r"(v.w) : "l"(p) : "memory"); return v;
}
__device__ __forceinline__ unsigned ldc4(const void* p) {
  unsigned v; asm volatile("ld.relaxed.cta.global.u32 %0, [%1];" : "=r"(v) : "l"(p) : "memory"); return v;
}
__device__ __forceinline__ uint4 ldx16(const void* p) {
  uint4 v; asm volatile("ld.relaxed.gpu.global.v4.u32 {%0,%1,%2,%3}, [%4];" : "=r"(v.x), "=r"(v.y), "=r"(v.z), "=r"(v.w) : "l"(p) : "memory"); return v;
}
__device__ __forceinline__ unsigned ldx4(const void* p) {
  unsigned v; asm volatile("ld.relaxed.gpu.global.u32 %0, [%1];" : "=r"(v) : "l"(p) : "memory"); return v;
}
__device__ __forceinline__ unsigned long long ldx64(const void* p) {
  unsigned long long v; asm volatile("ld.relaxed.gpu.global.u64 %0, [%1];" : "=l"(v) : "l"(p) : "memory"); return v;
}
__device__ __forceinline__ void stx16(void* p, uint4 v) {
  asm volatile("st.relaxed.gpu.global.v4.u32 [%0], {%1,%2,%3,%4};" ::"l"(p), "r"(v.x), "r"(v.y), "r"(v.z), "r"(v.w) : "memory");
}
__device__ __forceinline__ void stx8(void* p, uint2 v) { asm volatile("st.relaxed.gpu.global.v2.u32 [%0], {%1,%2};" ::"l"(p), "r"(v.x), "r"(v.y) : "memory"); }
__device__ __forceinline__ void stx4(void* p, unsigned v) { asm volatile("st.relaxed.gpu.global.u32 [%0], %1;" ::"l"(p), "r"(v) : "memory"); }
__device__ __forceinline__ void pub4(void* p, unsigned v) { asm volatile("red.relaxed.gpu.global.xor.b32 [%0], %1;" ::"l"(p), "r"(v) : "memory"); }
__device__ __forceinline__ void pub8(void* p, unsigned lo, unsigned hi) {
  asm volatile("{.reg .b64 t; mov.b64 t, {%1, %2}; red.relaxed.gpu.global.xor.b64 [%0], t;}" ::"l"(p), "r"(lo), "r"(hi) : "memory");
}
__device__ __forceinline__ unsigned lop_x3(unsigned a, unsigned b, unsigned c) {
  unsigned d; asm("lop3.b32 %0, %1, %2, %3, 0x7E;" : "=r"(d) : "r"(a), "r"(b), "r"(c)); return d; }
__device__ __forceinline__ unsigned or3(unsigned a, unsigned b, unsigned c) {
  unsigned d; asm("lop3.b32 %0, %1, %2, %3, 0xFE;" : "=r"(d) : "r"(a), "r"(b), "r"(c)); return d; }
__device__ __forceinline__ unsigned and3(unsigned a, unsigned b, unsigned c) {
  unsigned d; asm("lop3.b32 %0, %1, %2, %3, 0x80;" : "=r"(d) : "r"(a), "r"(b), "r"(c)); return d; }
__device__ __forceinline__ unsigned dep16(const uint32_t* f) {
  unsigned d = 0;
#pragma unroll
  for (int i = 0; i < 8; i++) d = or3(d, f[8 * i], f[8 * i + 4]);
  return d;
}
__device__ __forceinline__ uint2 ldx8(const void* p) {
  uint2 v; asm volatile("{.reg .b64 t; ld.relaxed.gpu.global.b64 t, [%2]; mov.b64 {%0, %1}, t;}" : "=r"(v.x), "=r"(v.y) : "l"(p) : "memory"); return v;
}
__device__ __forceinline__ float lds4(uint32_t a) { float v; asm volatile("ld.shared.f32 %0, [%1];" : "=f"(v) : "r"(a) : "memory"); return v; }
__device__ __forceinline__ float shx(float v, int m) {
  float r; asm volatile("shfl.sync.bfly.b32 %0, %1, %2, 0x1f, 0xffffffff;" : "=f"(r) : "f"(v), "r"(m)); return r;
}
__device__ __forceinline__ uint32_t mbar_test(uint32_t bar, uint32_t ph) {
  uint32_t ok;
  asm volatile("{.reg .pred p; mbarrier.test_wait.parity.shared::cta.b64 p, [%1], %2; vote.sync.all.pred p, p, 0xffffffff; selp.u32 %0, 1, 0, p;}"
               : "=r"(ok) : "r"(bar), "r"(ph) : "memory");
  return ok;
}
#define X16(v) (lop_x3(v.x, v.y, par) | lop_x3(v.z, v.w, par))
#define RETRY(bad) if (!__any_sync(~0u, (bad) & 1) || ++it_ >= SPIN_MAX) break;
#define POLL _Pragma("unroll 1") for (int it_ = 0;;)
__device__ __forceinline__ void mbar_wait(uint32_t bar, uint32_t ph = 0) {
  asm volatile("{.reg .pred p; .reg .u32 n; mov.u32 n, 0;\n"
               "W%=: mbarrier.try_wait.parity.shared::cta.b64 p, [%0], %1; add.u32 n, n, 1; setp.lt.and.u32 p, n, 0x100000, !p; @p bra W%=;}"
               ::"r"(bar), "r"(ph) : "memory");
}
__device__ __forceinline__ float ex2(float v) { float r; asm("ex2.approx.ftz.f32 %0, %1;" : "=f"(r) : "f"(v)); return r; }
__device__ __forceinline__ float rcp(float v) { float r; asm("rcp.approx.ftz.f32 %0, %1;" : "=f"(r) : "f"(v)); return r; }
__device__ __forceinline__ void mma16(float* d, const uint32_t* a, uint32_t b0, uint32_t b1) {
  asm volatile("mma.sync.aligned.m16n8k16.row.col.f32.bf16.bf16.f32 {%0,%1,%2,%3}, {%4,%5,%6,%7}, {%8,%9}, {%0,%1,%2,%3};"
               : "+f"(d[0]), "+f"(d[1]), "+f"(d[2]), "+f"(d[3]) : "r"(a[0]), "r"(a[1]), "r"(a[2]), "r"(a[3]), "r"(b0), "r"(b1));
}
__device__ __forceinline__ void mma16c(float* d, const uint32_t* a, uint32_t b0, uint32_t b1, const float* c) {
  asm volatile("mma.sync.aligned.m16n8k16.row.col.f32.bf16.bf16.f32 {%0,%1,%2,%3}, {%4,%5,%6,%7}, {%8,%9}, {%10,%11,%12,%13};"
               : "=f"(d[0]), "=f"(d[1]), "=f"(d[2]), "=f"(d[3])
               : "r"(a[0]), "r"(a[1]), "r"(a[2]), "r"(a[3]), "r"(b0), "r"(b1), "f"(c[0]), "f"(c[1]), "f"(c[2]), "f"(c[3]));
}
__device__ __forceinline__ float4 lds16(uint32_t a) {
  float4 v; asm volatile("ld.shared.v4.f32 {%0,%1,%2,%3}, [%4];" : "=f"(v.x), "=f"(v.y), "=f"(v.z), "=f"(v.w) : "r"(a) : "memory"); return v;
}
__device__ __forceinline__ void sts4(uint32_t a, float v) { asm volatile("st.shared.f32 [%0], %1;" ::"r"(a), "f"(v) : "memory"); }
__device__ __forceinline__ void sts16(uint32_t a, uint4 v) {
  asm volatile("st.shared.v4.b32 [%0], {%1,%2,%3,%4};" ::"r"(a), "r"(v.x), "r"(v.y), "r"(v.z), "r"(v.w) : "memory");
}
__device__ __forceinline__ void ldsm_t(uint32_t* r, uint32_t a) {
  asm volatile("ldmatrix.sync.aligned.m8n8.x4.trans.shared.b16 {%0,%1,%2,%3}, [%4];" : "=r"(r[0]), "=r"(r[1]), "=r"(r[2]), "=r"(r[3]) : "r"(a) : "memory");
}
__device__ __forceinline__ void ldsm(uint32_t* r, uint32_t a) {
  asm volatile("ldmatrix.sync.aligned.m8n8.x4.shared.b16 {%0,%1,%2,%3}, [%4];" : "=r"(r[0]), "=r"(r[1]), "=r"(r[2]), "=r"(r[3]) : "r"(a) : "memory");
}
__device__ __forceinline__ uint32_t mapa(uint32_t a, uint32_t r) {
  uint32_t v; asm volatile("mapa.shared::cluster.u32 %0, %1, %2;" : "=r"(v) : "r"(a), "r"(r)); return v;
}
__device__ __forceinline__ unsigned long long mapg(uint32_t a, uint32_t r) {
  unsigned long long v;
  asm volatile("{.reg .u32 t; .reg .u64 u; mapa.shared::cluster.u32 t, %1, %2; cvt.u64.u32 u, t; cvta.shared::cluster.u64 %0, u;}" : "=l"(v) : "r"(a), "r"(r));
  return v;
}
template <int N>
__device__ __forceinline__ void tred(float* a, int lane, int m) {
  const bool hi = lane & m;
#pragma unroll
  for (int i = 0; i < N; i++) {
    float send = hi ? a[i] : a[i + N], keep = hi ? a[i + N] : a[i];
    a[i] = keep + __shfl_xor_sync(~0u, send, m);
  }
}
template <int N>
__device__ __forceinline__ void tmax(float* a, int lane, int m) {
  const bool hi = lane & m;
#pragma unroll
  for (int i = 0; i < N; i++) {
    float send = hi ? a[i] : a[i + N], keep = hi ? a[i + N] : a[i];
    a[i] = fmaxf(keep, __shfl_xor_sync(~0u, send, m));
  }
}
__device__ __forceinline__ void arrive_n(uint32_t bar, bool on, int cnt) {
  asm volatile("{.reg .pred p; setp.ne.s32 p, %1, 0; @p mbarrier.arrive.shared::cta.b64 _, [%0], %2;}" ::"r"(bar), "r"((int)on), "r"(cnt) : "memory");
}
__device__ __forceinline__ unsigned long long stream_policy() {
  unsigned long long p;
  asm volatile("createpolicy.fractional.L2::evict_first.b64 %0, 1.0;" : "=l"(p));
  return p;
}
__device__ __forceinline__ void tma3d(uint32_t dst, const CUtensorMap* tm, uint32_t bar, int c0, int c1, int c2) {
  asm volatile("cp.async.bulk.tensor.3d.shared::cluster.global.mbarrier::complete_tx::bytes.L2::cache_hint [%0], [%1, {%3, %4, %5}], [%2], %6;"
               ::"r"(dst), "l"(tm), "r"(bar), "r"(c0), "r"(c1), "r"(c2), "l"(stream_policy()) : "memory");
}
__device__ __forceinline__ void spin_until(unsigned t) { while ((int)((unsigned)clock() - t) < 0) {} }
__device__ __forceinline__ void wait_until(unsigned t) {
  unsigned now;
  do { asm volatile("mov.u32 %0, %%globaltimer_lo;" : "=r"(now)); } while ((int)(now - t) < 0);
}
__device__ __forceinline__ void sleep_until(unsigned t) {
  unsigned now;
#pragma unroll 1
  do {
    __nanosleep(200);
    asm volatile("mov.u32 %0, %%globaltimer_lo;" : "=r"(now));
  } while ((int)(now - t) < 0);
}
#define PIN(x) asm volatile("" : "+r"(x))
#define PINL(x) asm volatile("" : "+l"(x))
#define BAR_ARRIVE(i) asm volatile("mbarrier.arrive.shared::cta.b64 _, [%0];" ::"r"(bar0 + 8 * (i)) : "memory")
#define LANE0(op, p, c, v) asm volatile("{.reg .pred q; setp.eq.s32 q, %2, 0; @q " op " [%0], %1;}" ::"l"((p) + lane), c(v), "r"(lane) : "memory")
#define CNT_ADD(c) LANE0("red.relaxed.gpu.global.add.u32", scr->cnt + (c), "r", 1)
#define BAR_INIT(i, cnt) asm volatile("mbarrier.init.shared::cta.b64 [%0], %1;" ::"r"(bar0 + 8 * (i)), "r"(cnt) : "memory")
#define BAR_ARM(i, bytes) asm volatile("mbarrier.arrive.expect_tx.shared::cta.b64 _, [%0], %1;" ::"r"(bar0 + 8 * (i)), "r"(bytes) : "memory")
struct TMaps { CUtensorMap m[9]; };

#define NCTA9 120
#define TAU 20
#define NSL 100
#define NPE 1
#define QN 4
#define FDLY 60
#define VJ 1
#define NPO 3
#define VDLY 150
#define O_Q 131072
#define O_LZ 163840
#define O_CTX 196608
#define O_HZ 198656
#define O_HW 200704
#define O_X 201728
#define O_P 218112
#define O_B 222208
#define O_R 224512
#define O_SILU 228608
#define O_SM 229632
#define O_BAR 231424
#define O_EP (O_BAR + 256)
#define O_DBG (O_EP + 16)
#define SMEM9 (O_DBG + 144)
#define B_FULL 0
#define B_FM 8
#define B_EMPTY 10
#define B_LZ 18
#define B_Q2 19
#define B_H 20
#define B_QF 21
#define B_TAB 22
#define B_W 23
#define B_ST 24
#define B_HZ 25
#define B_WZ 26
#define B_G 27
#define B_G2 28
enum { T_WQ, T_WUK, T_KV, T_MOD, T_UV, T_WO, T_GU, T_DN = 8 };
#define NBIG 40
struct Sched { unsigned zero, dth; uint2 r[3][8]; unsigned nr[3], nt[3], dt, t4, d4, d6, wt, pad; };

struct __align__(128) Scratch {
  unsigned cnt[8 * 32];
  uint2 rec[32 * 4 * 8 * 64];
  uint2 hdr[32 * 16];
  unsigned h[8 * 256];
  uint4 qa[2048];
  unsigned xao[8 * 512];
  unsigned xab[8 * 256];
  unsigned xm[2048];
};
__device__ Scratch g_scr;
#define SMEM_BASE 1024u
#define DSC ((SMEM_BASE >> 4) | (1u << 16))
#define HI128 (64u | (1u << 30))
#define HI64 (32u | (2u << 30))
template <int TA, int TB, unsigned HIA, unsigned HIB>
__device__ __forceinline__ void wgmma32(float* d, uint32_t da, uint32_t db, int acc) {
  asm volatile("{.reg .pred p; .reg .b64 da, db; setp.ne.b32 p, %18, 0; mov.b64 da, {%16, %21}; mov.b64 db, {%17, %22};\n"
               "wgmma.mma_async.sync.aligned.m64n32k16.f32.bf16.bf16 "
               "{%0,%1,%2,%3,%4,%5,%6,%7,%8,%9,%10,%11,%12,%13,%14,%15}, da, db, p, 1, 1, %19, %20;}"
               : "+f"(d[0]), "+f"(d[1]), "+f"(d[2]), "+f"(d[3]), "+f"(d[4]), "+f"(d[5]), "+f"(d[6]), "+f"(d[7]),
                 "+f"(d[8]), "+f"(d[9]), "+f"(d[10]), "+f"(d[11]), "+f"(d[12]), "+f"(d[13]), "+f"(d[14]), "+f"(d[15])
               : "r"(da), "r"(db), "r"(acc), "n"(TA), "n"(TB), "n"(HIA), "n"(HIB));
}
__device__ __forceinline__ void wgmma32r(float* d, const uint32_t* a, uint32_t db) {
  asm volatile("{.reg .b64 db; mov.b64 db, {%20, %21};\n"
               "wgmma.mma_async.sync.aligned.m64n32k16.f32.bf16.bf16 "
               "{%0,%1,%2,%3,%4,%5,%6,%7,%8,%9,%10,%11,%12,%13,%14,%15}, {%16,%17,%18,%19}, db, 1, 1, 1, 1;}"
               : "+f"(d[0]), "+f"(d[1]), "+f"(d[2]), "+f"(d[3]), "+f"(d[4]), "+f"(d[5]), "+f"(d[6]), "+f"(d[7]),
                 "+f"(d[8]), "+f"(d[9]), "+f"(d[10]), "+f"(d[11]), "+f"(d[12]), "+f"(d[13]), "+f"(d[14]), "+f"(d[15])
               : "r"(a[0]), "r"(a[1]), "r"(a[2]), "r"(a[3]), "r"(db), "n"(HI64));
}
template <int N> __device__ __forceinline__ void wg_wait(float* a) {
  asm volatile("wgmma.wait_group.sync.aligned %16;"
               : "+f"(a[0]), "+f"(a[1]), "+f"(a[2]), "+f"(a[3]), "+f"(a[4]), "+f"(a[5]), "+f"(a[6]), "+f"(a[7]), "+f"(a[8]), "+f"(a[9]), "+f"(a[10]),
                 "+f"(a[11]), "+f"(a[12]), "+f"(a[13]), "+f"(a[14]), "+f"(a[15]) : "n"(N) : "memory");
}
__device__ __forceinline__ void send32(uint32_t a, uint32_t bar, float v, int lane) {
  const uint32_t w = pack2(v, __shfl_down_sync(~0u, v, 1));
  const int s = 2 * (lane & 3);
  asm volatile("{.reg .pred p; setp.eq.s32 p, %6, 0; @p st.async.shared::cluster.mbarrier::complete_tx::bytes.v4.b32 [%0], {%1,%2,%3,%4}, [%5];}"
               ::"r"(a), "r"(__shfl_sync(~0u, w, s)), "r"(__shfl_sync(~0u, w, s + 8)), "r"(__shfl_sync(~0u, w, s + 16)), "r"(__shfl_sync(~0u, w, s + 24)),
                 "r"(bar), "r"(lane & 12) : "memory");
}
__device__ __forceinline__ float sum8(uint32_t a) {
  const float4 p = lds16(a), q = lds16(a + 1024);
  return ((p.x + p.y) + (p.z + p.w)) + ((q.x + q.y) + (q.z + q.w));
}
__device__ __forceinline__ int posof(int c) { return (c & ~14) + 2 * (c & 6) + ((c >> 2) & 2); }

__global__ void __cluster_dims__(8, 1, 1) __launch_bounds__(384, 1)
fused_kernel(const bf16* __restrict__ x, const bf16* __restrict__ cvec, const bf16* __restrict__ w_mod, bf16* __restrict__ out,
             Scratch* __restrict__ scr, const __grid_constant__ Sched sch, const __grid_constant__ TMaps tms) {
  extern __shared__ __align__(1024) unsigned char smem[];
  const int tid = threadIdx.x, warp = __shfl_sync(~0u, tid >> 5, 0), lane = tid & 31;
  const int b = blockIdx.x, cl = b >> 3, rn = b & 7, rk = b & 1, hd = b >> 1, f = b - 64;
  const bool isA = b < 64;
  uint32_t sb = s2u(smem), bar0 = sb + O_BAR;
  unsigned gt_start;
  asm volatile("mov.u32 %0, %%globaltimer_lo;" : "=r"(gt_start));
  const int g = lane >> 2, tq = lane & 3;
  const int arow = 64 * rn + ((tid & 255) >> 4);
  uint4 wm[4];
  uint32_t cw, xw;
  if (warp < 8 && isA) {
    const bf16* wa = w_mod + (size_t)arow * 3072 + (lane & 8) * 64 + 64 * cl + 8 * (lane & 7);
#pragma unroll
    for (int i = 0; i < 4; i++) wm[i] = ldx16(wa + i * 16 * 3072);
    cw = ldc4(cvec + (arow & ~1) + 16 * tq);
    if (warp < 2) xw = ldc4(x + 64 * cl + (tid & 62));
  }
  if (warp == 11) {
    if (lane == 0) {
#pragma unroll
      for (int i = 0; i < B_EMPTY; i++) BAR_INIT(i, 1);
    }
    __syncwarp();
    asm volatile("fence.mbarrier_init.release.cluster;" ::: "memory");
    asm volatile("barrier.cluster.arrive.relaxed.aligned;" ::: "memory");
    if (isA) {
#pragma unroll 1
      for (int i = 0; i < 8; i++) {
        if (i >= 6) mbar_wait(bar0 + 8 * (i - 6));
        wait_until(gt_start + ((64 * i + b) * sch.dth >> 8));
        if (lane == 0) {
          BAR_ARM(i, 16384);
          tma3d(sb + i * 16384, &tms.m[i >> 2], bar0 + 8 * i, 0, i < 4 ? 128 * i : 256 * rk + 64 * (i - 4), i < 4 ? b : b & ~1);
        }
        __syncwarp();
      }
    }
  }
  if (warp == 10) {
    const unsigned ep = ldc4(&scr->cnt[0]);
    if (isA) {
      const uint4 xa = ldc16(x + 16 * lane), xb = ldc16(x + 16 * lane + 8);
      float xv[16] = {bflo(xa.x), bfhi(xa.x), bflo(xa.y), bfhi(xa.y), bflo(xa.z), bfhi(xa.z), bflo(xa.w), bfhi(xa.w),
                      bflo(xb.x), bfhi(xb.x), bflo(xb.y), bfhi(xb.y), bflo(xb.z), bfhi(xb.z), bflo(xb.w), bfhi(xb.w)};
      const float x0 = __shfl_sync(~0u, xv[0], 0);
      float s = 0, q = 0;
#pragma unroll
      for (int i = 0; i < 16; i++) { xv[i] -= x0; s += xv[i]; q += xv[i] * xv[i]; }
#pragma unroll
      for (int o = 16; o; o >>= 1) { s += __shfl_xor_sync(~0u, s, o); q += __shfl_xor_sync(~0u, q, o); }
      s *= 1.f / 512.f;
      float rstd;
      asm("rsqrt.approx.ftz.f32 %0, %1;" : "=f"(rstd) : "f"(fmaxf(q * (1.f / 512.f) - s * s, 0.f) + 1e-5f));
      *(float2*)(smem + O_SM + 1024) = make_float2(s + x0, rstd);
    }
    if (lane == 0) *(volatile unsigned*)(smem + O_EP) = ep;
    nbar_arrive(1, 288);
  }
  const int cls = isA ? (b >= NBIG) : 2, v0 = isA ? 2 : 0;
  if (warp >= 8) {
    asm volatile("setmaxnreg.dec.sync.aligned.u32 56;");
    if (warp == 8) {
      if (lane < 8) asm volatile("prefetch.tensormap [%0];" ::"l"(&tms.m[lane + 1]) : "memory");
      if ((sb & 0xFFFFFF) != SMEM_BASE) __trap();
    } else if (warp == 9) {
      if (lane == 0) {
#pragma unroll
        for (int i = B_EMPTY; i < B_LZ; i++) BAR_INIT(i, 8);
        BAR_INIT(B_LZ, 8); BAR_INIT(B_Q2, 9); BAR_ARM(B_Q2, 1024);
        BAR_INIT(B_H, 1); BAR_INIT(B_QF, 1); BAR_ARM(B_QF, 32768);
        BAR_INIT(B_TAB, 1); BAR_INIT(B_W, 1); BAR_INIT(B_ST, 8); BAR_INIT(B_WZ, 1); BAR_INIT(B_HZ, 1); BAR_ARM(B_HZ, isA ? 1024 : 512); BAR_INIT(B_G, 1); BAR_INIT(B_G2, 1);
      }

    }
    if (warp != 11) {
      __syncwarp();
      asm volatile("fence.mbarrier_init.release.cluster;" ::: "memory");
      __threadfence_block();
      asm volatile("barrier.cluster.arrive.relaxed.aligned;" ::: "memory");
    }
    asm volatile("barrier.cluster.wait.acquire.aligned;" ::: "memory");
    if (warp == 8) {
      const int nr = sch.nr[cls], vl = v0 + sch.nt[cls] - 1;
      unsigned long long hist = 0;
      int v = v0;
#pragma unroll 1
      for (int rd = 0; rd < nr; rd++) {
        const uint2 e = sch.r[cls][rd];
        const int type = e.y & 15, win = (e.y >> 4) & 15, pos = b + 64 - (int)((e.y >> 8) & 255), tile = e.y >> 16;
        const bool mod = type == T_MOD;
        const int ni = mod ? 1 : type == T_DN ? 2 : 4;
        unsigned t = gt_start + (e.x & 0xffff) + (pos * sch.dt >> 8);
        const int c0 = mod ? 1024 + 32 * b : type == T_WO || type == T_DN ? 64 * rn : type == T_GU ? 32 * f : 0;
        int c1 = type == T_KV ? 64 * (tile + pos) : 0;
        int c2 = mod ? tile : type == T_WO ? 4 * cl : type == T_DN ? 2 * cl - 16 : type == T_UV ? b : 0;
        const int i1 = type == T_UV ? 128 : 0;
#pragma unroll 1
        for (int j = 0; j < ni; j++) {
          const int slot = mod ? B_FM + tile : (v & 1) * 4 + j;
          if (mod ? tile : v >= 2) mbar_wait(bar0 + 8 * (B_EMPTY + (mod ? (vl & 1) * 4 : slot)), mod ? (vl >> 1) & 1 : ((v >> 1) - 1) & 1);
          const int hw = (int)(hist >> (6 * (win - 1))) & 63;
          if (hw) mbar_wait(bar0 + 8 * (hw & 15), (hw >> 4) & 1);
          wait_until(t);
          if (lane == 0) {
            BAR_ARM(slot, 16384);
            tma3d(sb + (mod ? (tile ? O_Q : O_X) : slot * 16384), &tms.m[type == T_GU ? type + (j & 1) : type], bar0 + 8 * slot, c0, c1, c2);
          }
          __syncwarp();
          hist = hist << 6 | (32 | (mod ? 0 : (v & 2) << 3) | slot);
          t += e.x >> 16; c1 += i1;
          c2 += type == T_KV ? 2 : type == T_WO || type == T_DN ? 1 : type == T_GU ? j & 1 : 0;
        }
        v += !mod;
      }
      return;
    }
    const unsigned epoch = *(volatile unsigned*)(smem + O_EP), par = (epoch + 1) & 1;
    if (warp == 10) {
      if (isA) {
        for (int it = 0; ldx4(scr->cnt + 1) != (epoch + 1) * 128 && it < SPIN_MAX; it++) {}
        if (lane == 0) BAR_ARRIVE(B_H);
      } else mbar_wait(bar0);
      if (!(rn & (QN - 1))) {
        for (int it = 0; ldx4(scr->cnt + 32 + 32 * (rn >> 2)) != (epoch + 1) * 32 && it < SPIN_MAX; it++) {}
        if (lane == 0)
          asm volatile("cp.async.bulk.shared::cluster.global.mbarrier::complete_tx::bytes.multicast::cluster [%0], [%1], %4, [%2], %3;"
                       ::"r"(sb + O_Q + rn * 4096), "l"(scr->qa + rn * 256), "r"(bar0 + 8 * B_QF), "h"((unsigned short)0xff), "n"(4096 * QN) : "memory");
      }
      const unsigned dl = isA ? sch.d4 : sch.d6;
      unsigned tw = gt_start + sch.t4;
      if (!isA) {
        const int nt = sch.nt[2];
#pragma unroll 1
        for (int t = 0; t < nt; t++) mbar_wait(bar0 + 8 * B_EMPTY + (t & 1) * 32, (t >> 1) & 1);
        unsigned long long now;
        asm volatile("mov.u64 %0, %%globaltimer;" : "=l"(now));
        LANE0("red.relaxed.gpu.global.max.u64", scr->cnt + 130, "l", now);
        CNT_ADD(128);
        tw = (unsigned)now + 1700;
      }
      sleep_until(tw);
      uint4 an;
      for (int it = 0; an = ldx16(scr->cnt + 128), an.x != (epoch + 1) * 56 && it < SPIN_MAX; it++) {}
      wait_until(an.z + (dl >> 16));
      if (lane == 0) BAR_ARRIVE(B_G2);
      wait_until(an.z + (dl & 0xffff));
      if (lane == 0) BAR_ARRIVE(B_G);
    } else if (warp == 11) {
      {
        uint2* ph = scr->hdr + ((lane & 24) + 2 * tq + (g & 1)) * 16 + cl;
        const bool own = (lane >> 4) * 4 + tq == rn;
        if (own) { stx8(ph, make_uint2(par ^ 1, 0)); if (cl == 14) stx8(ph + 1, make_uint2(0, 0)); }
        uint32_t a_w = sb + O_HW + ((lane >> 4) * 4 + tq) * 128 + (g & 1) * 64 + ((lane >> 1) & 4);
        PIN(a_w); PINL(ph);
        const int vt = v0 + sch.nt[cls];
#pragma unroll 1
        for (int t = 0; t < vt; t++) mbar_wait(bar0 + 8 * B_EMPTY + (t & 1) * 32, (t >> 1) & 1);
        float hz[8], M;
        uint32_t wp[4];
#pragma unroll 1
        for (int e = 0; e < 2; e++) {
          POLL {
            unsigned ok = 1;
#pragma unroll
            for (int u = 0; u < 8; u++)
              asm volatile("ld.relaxed.cluster.shared.f32 %0, [%1];" : "=f"(hz[u]) : "r"(sb + O_HZ + e * 1024 + u * 128 + lane * 4) : "memory");
#pragma unroll
            for (int u = 0; u < 4; u++) ok = and3(ok, __float_as_uint(hz[u]), __float_as_uint(hz[u + 4]));
            RETRY(~ok)
          }
          if (e) break;
          M = fmaxf(fmaxf(fmaxf(hz[0], hz[1]), fmaxf(hz[2], hz[3])), fmaxf(fmaxf(hz[4], hz[5]), fmaxf(hz[6], hz[7])));
          M = u2f(fbits(M));
#pragma unroll
          for (int u = 0; u < 4; u++) {
            wp[u] = pack2(ex2(hz[u] - M), ex2(hz[u + 4] - M));
            sts4(a_w + ((rn - u) & 3) * 8, u2f(wp[u])); sts4(a_w + ((rn - u) & 3) * 8 + 32, u2f(wp[u]));
          }
          __syncwarp();
          if (lane == 0) BAR_ARRIVE(B_WZ);
        }
        float L = 0.f;
#pragma unroll
        for (int u = 0; u < 4; u++) L += bflo(wp[u]) * hz[u] + bfhi(wp[u]) * hz[u + 4];
        if (own) pub8(ph, __float_as_uint(M) | 1u, __float_as_uint(L));
      }
      if (isA) {
        mbar_wait(bar0 + 8 * B_G2);
        unsigned long long hh;
        POLL { hh = ldx64(scr->hdr + hd * 16 + (lane & 15)); RETRY((lane & 15) == 15 ? 0u : (unsigned)hh ^ par) }
        const float m = (lane & 15) == 15 ? -1e30f : u2f((unsigned)hh);
        int mi = __float_as_int(m);
        mi ^= (mi >> 31) & 0x7fffffff;
        mi = __reduce_max_sync(~0u, mi);
        mi ^= (mi >> 31) & 0x7fffffff;
        const float w = ex2(m - __int_as_float(mi));
        float L = w * u2f(hh >> 32);
#pragma unroll
        for (int o2 = 8; o2; o2 >>= 1) L += __shfl_xor_sync(~0u, L, o2);
        sts4(sb + O_SM + (384 + 2 * (lane & 6) + ((lane >> 2) & 2) + (lane & 1)) * 4, w * rcp(L));
        __syncwarp();
        if (lane == 0) BAR_ARRIVE(B_W);
      }
    } else {
#pragma unroll 4
      for (int i = 0; i < 72; i++) sts16(sb + O_LZ + i * 512 + lane * 16, make_uint4(0, 0, 0, 0));
      __syncwarp();
      if (lane < 8) asm volatile("mbarrier.arrive.release.cluster.shared::cluster.b64 _, [%0];" ::"r"(mapa(bar0 + 8 * B_LZ, lane)) : "memory");
      if (isA) {
        mbar_wait(bar0 + 8 * B_QF);
#pragma unroll 2
        for (int k = 0; k < 8; k++) {
          const uint32_t cp = ldc4(cvec + 2 * (lane + 32 * k));
          *(uint32_t*)(smem + O_SILU + (lane + 32 * k) * 4) = pack2(silu_bf(bflo(cp)), silu_bf(bfhi(cp)));
        }
        __syncwarp();
        uint32_t ab = sb + O_X + (8 * (lane >> 4) + (lane & 7)) * 64 + ((((lane >> 3) & 1) ^ ((lane >> 1) & 3)) << 4);
        float d[4][4] = {};
#pragma unroll 1
        for (int jm = 0; jm < 2; jm++) {
          mbar_wait(bar0 + 8 * (B_FM + jm));
#pragma unroll 2
          for (int s2 = 0; s2 < 8; s2++)
#pragma unroll
            for (int s = 0; s < 2; s++) {
              uint32_t a0[4], a1[4];
              const uint32_t* ps = (const uint32_t*)(smem + O_SILU) + 128 * jm + 16 * s2 + 8 * s + tq;
              ldsm_t(a0, ab + (2 * s2 + s) * 1024); ldsm_t(a1, (ab + (2 * s2 + s) * 1024) ^ 32);
              mma16(d[s], a0, ps[0], ps[4]); mma16(d[2 + s], a1, ps[0], ps[4]);
            }
          ab -= O_X - O_Q;
        }
        const float t0 = (tq & 1) ? d[0][2] + d[1][2] : d[0][0] + d[1][0], t1 = (tq & 1) ? d[2][2] + d[3][2] : d[2][0] + d[3][0];
        stx4(scr->xm + b * 32 + posof(8 * tq + g), fbits(bfr(bfr((tq & 2) ? t1 : t0) + ((b >> 4) == 2 ? 1.f : 0.f))));
        __syncwarp();
        CNT_ADD(96);
      } else sleep_until(gt_start + sch.t4);
      for (int it = 0; ldx4(scr->cnt + 96) != (epoch + 1) * 64 && it < SPIN_MAX; it++) __nanosleep(NSL);
      if (isA) {
        unsigned long long ga;
        POLL { ga = ldx64(scr->xm + 64 * rn + 2 * lane); RETRY(lop_x3((unsigned)ga, ga >> 32, par)) }
        *(float2*)(smem + O_SM + (320 + 2 * lane) * 4) = make_float2(bfhi((unsigned)ga), bfhi(ga >> 32));
      }
      __syncwarp();
      if (lane == 0) BAR_ARRIVE(B_TAB);
    }
    return;
  }

  float* s_sm = (float*)(smem + O_SM);
  unsigned par, epoch;
  asm volatile("barrier.cluster.arrive.relaxed.aligned;" ::: "memory");
  if (isA) {
    float* s_r = (float*)(smem + O_R);
    float acc[8] = {0, 0, 0, 0, 0, 0, 0, 0};
    const float sl = silu_bf((arow & 1) ? bfhi(cw) : bflo(cw));
#pragma unroll
    for (int i = 0; i < 4; i++) fma8(acc, wm[i], __shfl_sync(~0u, sl, i, 4));
    tred<4>(acc, lane, 16);
    *(float4*)(s_r + warp * 128 + 8 * (lane & 15) + ((lane >> 2) & 4)) = make_float4(acc[0], acc[1], acc[2], acc[3]);
    nbar(1, 288);
    epoch = *(volatile unsigned*)(smem + O_EP);
    par = (epoch + 1) & 1;
    if (warp < 2) {
      float t = 0.f, ca = rn == 0 ? 1.f : 0.f;
#pragma unroll
      for (int w = 0; w < 8; w++) { t += s_r[w * 128 + tid]; ca += s_r[w * 128 + 64 + tid]; }
      t += ca * ((((tid & 1) ? bfhi(xw) : bflo(xw)) - s_sm[256]) * s_sm[257]);
      const float nb = __shfl_down_sync(~0u, t, 1);
      const uint32_t w0 = lane < 8 ? pack2t(t, nb, par) : pack2(t, nb);
      const uint32_t w1 = __shfl_down_sync(~0u, w0, 8), w2 = __shfl_down_sync(~0u, w0, 16), w3 = __shfl_down_sync(~0u, w0, 24);
      if (lane < 8 && !(lane & 1)) stx16(scr->h + (rn >> 1) * 512 + (2 * cl + warp) * 32 + rk * 16 + 2 * lane, make_uint4(w0, w1, w2, w3));
      __syncwarp();
      CNT_ADD(1);
    }
    asm volatile("barrier.cluster.wait.acquire.aligned;" ::: "memory");
    const uint32_t rsb = mapa(sb, rn ^ 1);
    {
      uint32_t a[4][4][4];
      mbar_wait(bar0 + 8 * (warp >> 1));
      const uint32_t ab = sb + (64 * warp + 8 * (lane >> 4) + (lane & 7)) * 128;
#pragma unroll
      for (int s = 0; s < 4; s++)
#pragma unroll
        for (int mt = 0; mt < 4; mt++) ldsm_t(a[s][mt], ab + s * 2048 + (((2 * mt + ((lane >> 3) & 1)) ^ (lane & 7)) << 4));
      arrive_n(bar0 + 8 * (B_EMPTY + (warp >> 1)), lane == 0, 4 + (dep16(&a[0][0][0]) & sch.zero));
      uint4 v0, v1;
      const unsigned* ph = scr->h + (g >> 1) * 512 + 64 * warp + 4 * (lane & 7);
      uint32_t off = O_B + warp * 272 + (32 * rk + 8 * tq + (lane & 4)) * 4;
      PIN(off); PINL(ph);
      mbar_wait(bar0 + 8 * B_H);
      POLL { v0 = ldx16(ph); v1 = ldx16(ph + 32); RETRY(lop_x3(v0.x, v1.x, par)) }
      float d[4][4] = {};
#pragma unroll
      for (int mt = 0; mt < 4; mt++) {
        mma16(d[mt], a[0][mt], v0.x, v0.y); mma16(d[mt], a[1][mt], v0.z, v0.w);
        mma16(d[mt], a[2][mt], v1.x, v1.y); mma16(d[mt], a[3][mt], v1.z, v1.w);
      }
      float r[8];
#pragma unroll
      for (int mt = 0; mt < 4; mt++) { r[2 * mt] = d[mt][0] + d[mt][1]; r[2 * mt + 1] = d[mt][2] + d[mt][3]; }
      tred<4>(r, lane, 2); tred<2>(r, lane, 1);
      const float rc = __shfl_xor_sync(~0u, (lane & 4) ? r[0] : r[1], 4);
      const uint32_t wd = (lane & 4) ? pack2(rc, r[1]) : pack2(r[0], rc);
      const uint32_t w1 = __shfl_down_sync(~0u, wd, 8), w2 = __shfl_down_sync(~0u, wd, 16), w3 = __shfl_down_sync(~0u, wd, 24);
      asm volatile("{.reg .pred p; setp.lt.s32 p, %7, 8; @p st.shared.v4.b32 [%0], {%2,%3,%4,%5};\n"
                   "@p st.async.shared::cluster.mbarrier::complete_tx::bytes.v4.b32 [%1], {%2,%3,%4,%5}, [%6];}"
                   ::"r"(sb + off), "r"(rsb + off), "r"(wd), "r"(w1), "r"(w2), "r"(w3), "r"(rsb + O_BAR + 8 * B_Q2), "r"(lane) : "memory");
      __syncwarp();
      arrive_n(bar0 + 8 * B_Q2, lane == 0, 1);
    }
    {
      uint32_t a[2][8][4];
      uint32_t a_bq = sb + O_B + (lane & 7) * 272 + (lane >> 3) * 16;
      uint4* p_qa = scr->qa + (4 * rk + (warp >> 1)) * 256 + hd * 8 + ((4 * (warp & 1) + tq) ^ (hd & 7));
      PIN(a_bq); PINL(p_qa);
      mbar_wait(bar0 + 8 * (4 + (warp >> 1)));
      const uint32_t ab = sb + 65536 + (warp >> 1) * 16384 + (32 * (warp & 1) + (lane & 15)) * 128;
#pragma unroll
      for (int i = 0; i < 16; i++) ldsm(a[i >> 3][i & 7], ab + (i >> 3) * 2048 + ((i >> 2) & 1) * 8192 + (((2 * (i & 3) + (lane >> 4)) ^ (lane & 7)) << 4));
      arrive_n(bar0 + 8 * (B_EMPTY + 4 + (warp >> 1)), lane == 0, 4 + (dep16(&a[0][0][0]) & sch.zero));
      mbar_wait(bar0 + 8 * B_Q2);
      float d[4][4] = {};
#pragma unroll
      for (int y = 0; y < 4; y++) {
        uint32_t bq[4];
        ldsm(bq, a_bq + 64 * y);
#pragma unroll
        for (int mt = 0; mt < 2; mt++) { mma16(d[2 * mt], a[mt][2 * y], bq[0], bq[1]); mma16(d[2 * mt + 1], a[mt][2 * y + 1], bq[2], bq[3]); }
      }
      float r[4];
#pragma unroll
      for (int i = 0; i < 4; i++) r[i] = (d[i & 2][2 * (i & 1)] + d[i & 2][2 * (i & 1) + 1]) + (d[(i & 2) + 1][2 * (i & 1)] + d[(i & 2) + 1][2 * (i & 1) + 1]);
      tred<2>(r, lane, 2); tred<1>(r, lane, 1);
      const float nb = __shfl_xor_sync(~0u, r[0], 4);
      const uint32_t w0 = (lane >> 3) == (hd & 3) ? pack2t(r[0], nb, par) : pack2(r[0], nb);
      const uint32_t w1 = __shfl_down_sync(~0u, w0, 8), w2 = __shfl_down_sync(~0u, w0, 16), w3 = __shfl_down_sync(~0u, w0, 24);
      if (lane < 4) stx16(p_qa, make_uint4(w0, w1, w2, w3));
      if (warp) nbar_arrive(3, 256); else { nbar(3, 256); CNT_ADD(32 + 32 * rk); }
    }
  } else {
    nbar(1, 288);
    epoch = *(volatile unsigned*)(smem + O_EP);
    par = (epoch + 1) & 1;
    asm volatile("barrier.cluster.wait.acquire.aligned;" ::: "memory");
    mbar_wait(bar0);
  }
  asm volatile("setmaxnreg.inc.sync.aligned.u32 224;");
  uint2* p_rec = scr->rec + ((16 * (warp >> 2) + 2 * (warp & 3) + (g & 1) + 4 * (tq & 2)) * 32 + 4 * rn + (tq & 1)) * 64 + cl * 4 + (g >> 1);
  PINL(p_rec);
  {
    const unsigned inv = par ^ 1;
#pragma unroll
    for (int q = 0; q < 2; q++) { stx8(p_rec + q * 128, make_uint2(inv, 0)); if (cl == 14) stx8(p_rec + q * 128 + 4, make_uint2(0, 0)); }
    if (isA) { if (warp < 2) { stx4(scr->xao + b * 64 + tid, inv); stx4(scr->xab + cl * 256 + (2 * (rn & 3) + warp) * 32 + (rn >> 2) * 16 + (lane >> 1), inv); } }
    else if (f == 0) { stx4(out + 2 * tid, 0); __threadfence(); }
  }
  sb = __shfl_sync(~0u, sb, 0); bar0 = sb + O_BAR;
  const int nt = sch.nt[cls], wg = warp >> 2;
  uint32_t a_z[4];
#pragma unroll
  for (int u = 0; u < 4; u++) {
    const int s3 = (rn - u - (lane >> 1 & 1)) & 3;
    a_z[u] = sb + O_LZ + (s3 + 4 * (lane & 1)) * 4096 + wg * 512 + g * 64 + (((warp & 3) ^ (s3 & 1) ^ (2 * (lane & 1))) << 4);
    PIN(a_z[u]);
  }
  uint32_t z[4][4], a_w = sb + O_HW + warp * 128 + (g & 1) * 64 + (tq & 1) * 8;
  PIN(a_w);
  {
    const float sc = 0.08838834764831845f * 1.4426950408889634f;
    float mrun = -1e30f;
    float o[4][16], sx[16], mref[8];
#pragma unroll
    for (int k = 0; k < 16; k++) { o[0][k] = o[1][k] = o[2][k] = o[3][k] = sx[k] = 0.f; mref[k >> 1] = -1e30f; }
    const int key = 16 * warp + (lane & 15);
    uint32_t a_p = sb + O_P + key * 64 + (((lane >> 4) ^ ((key >> 1) & 3)) << 4);
    uint32_t a_v = sb + wg * 32768 + (8 * (lane >> 4) + (lane & 7)) * 128 + (((2 * (warp & 3) + ((lane >> 3) & 1)) ^ (lane & 7)) << 4);
    const int rot = rn + warp;
    const int qown = wg == (rn >> 2) ? -warp & 3 : -1;
    uint32_t a_own = sb + O_LZ + rn * 4096 + (warp & 3) * 1024 + g * 64 + ((tq ^ (rn & 1) ^ ((rn >> 1) & 2)) << 4);
    PIN(a_own);
    unsigned long long dst[4];
#pragma unroll
    for (int q = 0; q < 4; q++) {
      dst[q] = mapg(a_own, 4 * wg + ((q + rot) & 3));
      PINL(dst[q]);
    }
    unsigned long long a_h = mapg(sb + O_HZ + wg * 1024 + rn * 128 + lane * 4, 2 * (warp & 3));
    unsigned long long a_h1 = mapg(sb + O_HZ + wg * 1024 + rn * 128 + lane * 4, 2 * (warp & 3) + 1);
    PIN(a_p); PIN(a_v); PINL(a_h); PINL(a_h1);
    uint32_t rel = lane < 4 && lane >= 2 * wg ? 2 - (tq >> 1) : 0;
    PIN(rel);
    uint32_t ones[4] = {0x3F803F80u, 0x3F803F80u, 0x3F803F80u, 0x3F803F80u};
    PIN(ones[0]); PIN(ones[1]); PIN(ones[2]); PIN(ones[3]);
    {
      asm volatile("{.reg .pred p; .reg .u32 n; mov.u32 n, 0;\n"
                   "W%=: mbarrier.try_wait.parity.acquire.cluster.shared::cta.b64 p, [%0], 0; add.u32 n, n, 1; setp.lt.and.u32 p, n, 0x100000, !p; @p bra W%=;}"
                   ::"r"(bar0 + 8 * B_LZ) : "memory");
      mbar_wait(bar0 + 8 * B_QF);
      unsigned bad = 0;
#pragma unroll
      for (int k = 0; k < 8; k++) bad |= __float_as_uint(lds4(sb + O_Q + k * 4096 + tid * 16 + (lane >> 3) * 4)) ^ par;
      if (__builtin_expect(__any_sync(~0u, bad & 1), 0)) {
#pragma unroll 1
        for (int k = 0; k < 8; k++) {
          uint4 v;
          POLL { v = ldx16(scr->qa + k * 256 + tid); RETRY(((lane & 16) ? ((lane & 8) ? v.w : v.z) : ((lane & 8) ? v.y : v.x)) ^ par) }
          sts16(sb + O_Q + k * 4096 + tid * 16, v);
        }
        asm volatile("fence.proxy.async.shared::cta;" ::: "memory");
      }
      if (warp >= 4) nbar_arrive(1, 256); else nbar(1, 256);
    }
#pragma unroll 1
    for (int t = 0; t < nt; t++) {
      const int v = v0 + t;
      const uint32_t fb = bar0 + (v & 1) * 32, ph = (v >> 1) & 1, av = a_v + (v & 1) * 65536;
      uint32_t vf[4][4][4], cnt;
      auto landed = [&]() {
        cnt = rel + (dep16(&vf[0][0][0]) & (nt >> 8));
        PIN(cnt);
      };
      if (wg == 0) {
        const uint32_t da = DSC + (v & 1) * 4096, db = DSC + O_Q / 16;
#pragma unroll 1
        for (int j = 0; j < 4; j++) {
          mbar_wait(fb + 8 * j, ph);
          asm volatile("wgmma.fence.sync.aligned;" ::: "memory");
#pragma unroll
          for (int k = 0; k < 8; k++)
            wgmma32<0, 0, HI128, HI128>(sx, da + j * 1024 + (k >> 2) * 512 + (k & 3) * 2, db + j * 512 + (k >> 2) * 256 + (k & 3) * 2, k ? 1 : j);
          asm volatile("wgmma.commit_group.sync.aligned;" ::: "memory");
          if (j == VJ) {
#pragma unroll
            for (int i = 0; i < 16; i++) ldsm_t(vf[i >> 2][i & 3], av + (((i >> 2) + rot) & 3) * 8192 + (i & 3) * 2048);
            nbar(5, 256);
            landed();
          }
        }
      } else {
        nbar_arrive(5, 256);
#pragma unroll 1
        for (int j = 0; j < 2; j++) {
          mbar_wait(fb + 16 + 8 * j, ph);
          if (j) spin_until(clock() + VDLY);
#pragma unroll
          for (int q = 0; q < 4; q++)
            if (((q + rot) & 2) == 2 * j)
#pragma unroll
              for (int k = 0; k < 4; k++) ldsm_t(vf[q][k], av + ((q + rot) & 3) * 8192 + k * 2048);
        }
        cnt = 0;
      }
      wg_wait<0>(sx);
      asm volatile("{.reg .pred p; setp.ne.s32 p, %1, 0; @p mbarrier.arrive.shared::cta.b64 _, [%0], %1;}" ::"r"(fb + 8 * B_EMPTY + 8 * tq), "r"(cnt) : "memory");
#pragma unroll 1
      for (int pass = 0;; pass++) {
        int ex = !(t | pass);
        if (wg == 0 && (t | pass)) {
          uint32_t pk[8];
#pragma unroll
          for (int i = 0; i < 8; i++) pk[i] = pack2(ex2(sx[2 * i] * sc - mref[i & 6]), ex2(sx[2 * i + 1] * sc - mref[(i & 6) + 1]));
          asm volatile("stmatrix.sync.aligned.m8n8.x4.shared.b16 [%0], {%2,%3,%4,%5};\n"
                       "stmatrix.sync.aligned.m8n8.x4.shared.b16 [%1], {%6,%7,%8,%9};"
                       ::"r"(a_p), "r"(a_p ^ 32), "r"(pk[0]), "r"(pk[1]), "r"(pk[2]), "r"(pk[3]), "r"(pk[4]), "r"(pk[5]), "r"(pk[6]), "r"(pk[7]) : "memory");
          const uint32_t mx = __vmaxu2(__vmaxu2(__vmaxu2(pk[0], pk[1]), __vmaxu2(pk[2], pk[3])), __vmaxu2(__vmaxu2(pk[4], pk[5]), __vmaxu2(pk[6], pk[7])));
          ex = max(mx, mx << 16) > (127u + TAU) << 23;
          asm volatile("fence.proxy.async.shared::cta;" ::: "memory");
        }
        asm volatile("{.reg .pred p, q; setp.ne.s32 q, %0, 0; bar.red.or.pred p, 4, 256, q; selp.s32 %0, 1, 0, p;}" : "+r"(ex)::"memory");
        if (!ex || pass) break;
        int ln;
        asm volatile("mov.u32 %0, %%laneid;" : "=r"(ln));
        const uint32_t a_pm = sb + O_SM + ln * 16;
        if (wg == 0) {
          float cm[8];
#pragma unroll
          for (int i = 0; i < 8; i++) cm[i] = fmaxf(sx[2 * (i & 6) + (i & 1)], sx[2 * (i & 6) + (i & 1) + 2]);
          tmax<4>(cm, lane, 16); tmax<2>(cm, lane, 8); tmax<1>(cm, lane, 4);
          sts4(a_pm + warp * 4, cm[0] * sc);
        }
        nbar(4, 256);
        const float4 pm = lds16(a_pm);
        const float mn = u2f(__float_as_uint(fmaxf(fmaxf(fmaxf(pm.x, pm.y), fmaxf(pm.z, pm.w)), mrun)) | 1u), al = ex2(mrun - mn);
        mrun = mn;
#pragma unroll
        for (int i = 0; i < 8; i++) {
          const float a = __shfl_sync(~0u, al, 4 * i + (ln & 3)), aw = wg ? a : 1.f;
          mref[i] = __shfl_sync(~0u, mn, 4 * i + (ln & 3));
#pragma unroll
          for (int e = 0; e < 2; e++) {
            const int k = 2 * (i & 6) + (i & 1) + 2 * e;
            o[0][k] *= a; o[1][k] *= a; o[2][k] *= a; o[3][k] *= a; sx[k] *= aw;
          }
        }
      }
      float hv = mrun;
      if (wg) {
        asm volatile("wgmma.fence.sync.aligned;" ::: "memory");
#pragma unroll
        for (int k = 0; k < 4; k++) wgmma32r(sx, ones, DSC + O_P / 16 + k * 64);
        asm volatile("wgmma.commit_group.sync.aligned;" ::: "memory");
        landed();
        asm volatile("{.reg .pred p; setp.ne.s32 p, %1, 0; @p mbarrier.arrive.shared::cta.b64 _, [%0], %1;}" ::"r"(fb + 8 * B_EMPTY + 8 * tq), "r"(cnt) : "memory");
        wg_wait<0>(sx);
        float lv[4];
#pragma unroll
        for (int j = 0; j < 4; j++) lv[j] = (lane & 4) ? sx[4 * j + 1] : sx[4 * j];
        hv = (lane & 16) ? ((lane & 8) ? lv[3] : lv[2]) : ((lane & 8) ? lv[1] : lv[0]);
      }
      asm volatile("{.reg .pred p; setp.eq.s32 p, %3, %4; @p st.relaxed.cluster.b32 [%0], %1; @p st.relaxed.cluster.b32 [%2], %1;}"
                   ::"l"(a_h), "r"(__float_as_uint(hv) | 1u), "l"(a_h1), "r"(t), "r"(nt - 1) : "memory");
#pragma unroll
      for (int q = 0; q < 4; q++) {
        if (q < 2) {
          asm volatile("wgmma.fence.sync.aligned;" ::: "memory");
#pragma unroll
          for (int u = q; u < (q ? 4 : 1); u++) {
#pragma unroll
            for (int k = 0; k < 4; k++) wgmma32r(o[u], vf[u][k], DSC + O_P / 16 + k * 64);
            asm volatile("wgmma.commit_group.sync.aligned;" ::: "memory");
          }
        }
        if (q == 3) {
#pragma unroll
          for (int u = 0; u < 4; u++)
            asm volatile("{.reg .pred p; setp.eq.s32 p, %5, %6; @p ldmatrix.sync.aligned.m8n8.x4.trans.shared.b16 {%0,%1,%2,%3}, [%4];}"
                         : "=r"(z[u][0]), "=r"(z[u][1]), "=r"(z[u][2]), "=r"(z[u][3]) : "r"(a_z[u] + u * 1024), "r"(t), "r"(nt - 1) : "memory");
        }
        if (q == 1) wg_wait<2>(o[q]); else if (q == 2) wg_wait<1>(o[q]); else wg_wait<0>(o[q]);
        if (q == 0 || t == nt - 1)
#pragma unroll
        for (int j = 0; j < 2; j++)
          asm volatile("{.reg .pred p, q, r; setp.eq.s32 p, %5, %6; setp.eq.and.s32 q|r, %7, %8, p; @r st.relaxed.cluster.v4.b32 [%0], {%1,%2,%3,%4};\n"
                       "@q st.shared.v4.b32 [%9], {%1,%2,%3,%4};}"
                       ::"l"(dst[q] + j * 512), "r"(pack2t(o[q][8 * j], o[q][8 * j + 1], 1)), "r"(pack2(o[q][8 * j + 2], o[q][8 * j + 3])),
                         "r"(pack2(o[q][8 * j + 4], o[q][8 * j + 5])), "r"(pack2(o[q][8 * j + 6], o[q][8 * j + 7])), "r"(t), "r"(nt - 1),
                         "r"(qown), "r"(q), "r"(a_own + j * 512) : "memory");
      }
    }
  }
  {
    uint32_t wx[4][4];
    mbar_wait(bar0 + 8 * B_WZ);
#pragma unroll
    for (int u = 0; u < 4; u++) {
      uint2 wp;
      asm volatile("ld.shared.v2.u32 {%0, %1}, [%2];" : "=r"(wp.x), "=r"(wp.y) : "r"(a_w + u * 8) : "memory");
      const bool lo = (g >> 1) == (tq >> 1), hi = (g >> 1) == 2 + (tq >> 1);
      wx[u][0] = lo ? wp.x : 0u; wx[u][1] = lo ? wp.y : 0u; wx[u][2] = hi ? wp.x : 0u; wx[u][3] = hi ? wp.y : 0u;
    }
    auto bad = [&]() {
      const unsigned ok = and3(and3(and3(z[0][0], z[0][1], z[0][2]), and3(z[0][3], z[1][0], z[1][1]), and3(z[1][2], z[1][3], z[2][0])),
                               and3(and3(z[2][1], z[2][2], z[2][3]), and3(z[3][0], z[3][1], z[3][2]), z[3][3]), 0x10001u);
      return __any_sync(~0u, g == 0 && ok != 0x10001u);
    };
    POLL {
      if (it_)
#pragma unroll
        for (int u = 0; u < 4; u++) ldsm_t(z[u], a_z[u] + u * 1024);
      if (!bad() || ++it_ >= SPIN_MAX) break;
    }
    float d0[8][4] = {}, d[8][4], r[8];
#pragma unroll
    for (int i = 0; i < 8; i++) mma16(d0[i], wx[i >> 1], z[i >> 1][2 * (i & 1)], z[i >> 1][2 * (i & 1) + 1]);
    POLL {
#pragma unroll
      for (int u = 0; u < 4; u++) ldsm_t(z[u], a_z[u ^ 2] + u * 1024);
#pragma unroll
      for (int i = 0; i < 8; i++) mma16c(d[i], wx[(i >> 1) ^ 2], z[i >> 1][2 * (i & 1)], z[i >> 1][2 * (i & 1) + 1], d0[i]);
      if (!bad() || ++it_ >= SPIN_MAX) break;
    }
#pragma unroll
    for (int i = 0; i < 8; i++) r[i] = (tq & 2) ? ((g & 1) ? d[i][3] : d[i][2]) : ((g & 1) ? d[i][1] : d[i][0]);
#pragma unroll
    for (int q = 0; q < 2; q++) pub8(p_rec + q * 128, pack2t(r[4 * q], r[4 * q + 1], par) | 1u, pack2(r[4 * q + 2], r[4 * q + 3]));
  }
  const int vt = v0 + nt;
  const uint32_t bufa = sb + (vt & 1) * 65536, fulla = bar0 + (vt & 1) * 32, pha = (vt >> 1) & 1, phb = ((vt + 1) >> 1) & 1;
  const uint32_t bufo = sb + ((vt + 1) & 1) * 65536, fullb = bar0 + ((vt + 1) & 1) * 32;
  uint32_t a_rs = sb + O_R + (warp >> 2) * 1024 + (16 * tq + g) * 16 + ((warp + tq) & 3) * 4;
  if (isA) {
    const int row = 16 * (warp & 6) + 8 * (warp & 1) + (lane & 16) + ((lane & 7) >> 1) + 4 * (lane & 1);
    uint32_t ab = bufa + row * 128 + ((((lane >> 3) & 1) ^ (row & 7)) << 4);
    const uint2* pr = scr->rec + (hd * 32 + warp) * 64 + lane;
    uint32_t a_cb = mapa(bar0 + 8 * B_HZ, (warp & 6) + (lane >> 4)), a_c = a_cb - (O_BAR + 8 * B_HZ - O_CTX) + (2 * rn + (warp & 1)) * 64 + tq * 16;
    uint32_t a_rl = sb + O_R + (32 * (warp & 1) + lane) * 16;
    uint32_t ao = bufo + (16 * warp + 8 * (lane >> 4) + (lane & 7)) * 128 + ((((lane >> 3) & 1) ^ (lane & 7)) << 4);
    uint32_t a_cx = sb + O_CTX + (warp >> 1) * 64 + tq * 16 + (warp & 1) * 8, a_ga = sb + O_SM + (320 + posof(tid & 63)) * 4;
    unsigned* p_ao = scr->xao + b * 64 + (tid & 63);
    unsigned* p_ab = scr->xab + cl * 256 + (2 * (rn & 3) + (warp & 1)) * 32 + (rn >> 2) * 16 + (lane >> 1);
    float xv = cl == 0 ? __bfloat162float(x[64 * rn + (tid & 63)]) : 0.f;
    unsigned p2 = lane >= 28 ? 0 : par;
    PIN(ab); PINL(pr); PIN(a_cb); PIN(a_c); PIN(a_rl); PIN(a_rs); PIN(ao); PIN(a_cx); PIN(a_ga); PINL(p_ao); PINL(p_ab); PIN(p2);
    asm volatile("" : "+f"(xv));
    uint32_t aw[4][4][4];
    auto wo = [&](const int j) {
      mbar_wait(fullb + 8 * j, phb);
#pragma unroll
      for (int mt = 0; mt < 4; mt++) ldsm_t(aw[j][mt], (ao + j * 16384) ^ (mt << 5));
    };
    {
      uint32_t a[4][4][4];
      uint2 z[4], y[4] = {};
      float d[4][4] = {}, r[8];
      mbar_wait(fulla, pha);
      POLL {
#pragma unroll
        for (int q = 0; q < 4; q++) z[q] = ldx8(pr + q * 512);
        RETRY(lop_x3(z[0].x, z[1].x, par) | lop_x3(z[2].x, z[3].x, par))
      }
#pragma unroll
      for (int q = 0; q < 4; q++) {
        if (q == 3) {
          mbar_wait(bar0 + 8 * B_G);
          if (lane < 28)
#pragma unroll
            for (int u = 0; u < 4; u++) y[u] = ldx8(pr + u * 512 + 32);
          __syncwarp();
        }
        mbar_wait(fulla + 8 * q, pha);
#pragma unroll
        for (int mt = 0; mt < 4; mt++) ldsm_t(a[q][mt], (ab + q * 16384) ^ (mt << 5));
#pragma unroll
        for (int mt = 0; mt < 4; mt++) mma16(d[mt], a[q][mt], z[q].x, z[q].y);
      }
      mbar_wait(bar0 + 8 * B_W);
      const float4 W = lds16(sb + O_SM + (384 + 4 * tq) * 4);
#pragma unroll
      for (int i = 0; i < 8; i++) { r[i] = W.x * d[i >> 1][2 * (i & 1)] + W.y * d[i >> 1][2 * (i & 1) + 1]; asm volatile("" : "+f"(r[i])); }
#pragma unroll
      for (int j = 0; j < NPE; j++) wo(j);
      POLL {
        if (it_)
#pragma unroll
          for (int u = 0; u < 4; u++) y[u] = ldx8(pr + u * 512 + 32);
#pragma unroll
        for (int mt = 0; mt < 4; mt++) d[mt][0] = d[mt][1] = d[mt][2] = d[mt][3] = 0.f;
#pragma unroll
        for (int q = 0; q < 4; q++)
#pragma unroll
          for (int mt = 0; mt < 4; mt++) mma16(d[mt], a[q][mt], y[q].x, y[q].y);
        RETRY(or3(lop_x3(y[0].x, y[1].x, p2), lop_x3(y[2].x, y[3].x, p2), 0))
      }
#pragma unroll
      for (int i = 0; i < 8; i++) r[i] = W.w * d[i >> 1][2 * (i & 1) + 1] + (W.z * d[i >> 1][2 * (i & 1)] + r[i]);
      tred<4>(r, lane, 2); tred<2>(r, lane, 1);
      sts4(a_rs, r[0]); sts4(a_rs + 128, r[1]);
      nbar(1, 256);
      send32(a_c, a_cb, sum8(a_rl), lane);
    }
    {
#pragma unroll
      for (int j = NPE; j < NPO; j++) wo(j);
      uint2 c[4];
      mbar_wait(bar0 + 8 * B_HZ);
#pragma unroll
      for (int j = 0; j < 4; j++) asm volatile("ld.shared.v2.u32 {%0, %1}, [%2];" : "=r"(c[j].x), "=r"(c[j].y) : "r"(a_cx + j * 256) : "memory");
      float d[4][4] = {};
#pragma unroll
      for (int j = 0; j < 4; j++) {
        if (j + 1 >= NPO && j < 3) wo(j + 1);
#pragma unroll
        for (int mt = 0; mt < 4; mt++) mma16(d[mt], aw[j][mt], c[j].x, c[j].y);
      }
      const float r0 = (tq & 2) ? ((tq & 1) ? d[3][0] : d[2][0]) : ((tq & 1) ? d[1][0] : d[0][0]);
      const float r1 = (tq & 2) ? ((tq & 1) ? d[3][2] : d[2][2]) : ((tq & 1) ? d[1][2] : d[0][2]);
      sts4(a_rs + 2048, r0); sts4(a_rs + 2048 + 128, r1);
      if (warp >= 2) nbar_arrive(2, 256);
      else {
        mbar_wait(bar0 + 8 * B_TAB);
        const float gav = lds4(a_ga);
        nbar(2, 256);
        const float t = gav * sum8(a_rl + 2048) + xv;
        asm volatile("{.reg .pred p; setp.eq.s32 p, %2, 0; @p red.relaxed.gpu.global.xor.b32 [%0], %1;}"
                     ::"l"(p_ab), "r"(pack2t(t, __shfl_down_sync(~0u, t, 1), par) | 1u), "r"(lane & 1) : "memory");
        pub4(p_ao, __float_as_uint(t) | 1u);
      }
    }
  } else {
    uint32_t af[4][4][4];
    uint32_t ab = bufa + (32 * warp + 8 * (lane >> 4) + (lane & 7)) * 64 + ((((lane >> 3) & 1) ^ ((lane >> 1) & 3)) << 4);
    uint32_t a_d = bufo + wg * 16384 + (8 * (lane >> 4) + (lane & 7)) * 128 + (((2 * (warp & 3) + ((lane >> 3) & 1)) ^ (lane & 7)) << 4);
    uint32_t a_rl = sb + O_R + lane * 16, a_st = sb + O_SM + (352 + 8 * (lane >> 4) + warp) * 4;
    const unsigned* pa = scr->xab + tid;
    uint32_t a_hb = mapa(bar0 + 8 * B_HZ, 2 * (warp & 3) + (lane >> 4)), a_h = a_hb - (O_BAR + 8 * B_HZ - O_CTX) + rn * 64 + tq * 16;
    PIN(a_hb); PIN(a_h);
    uint32_t a_hl = sb + O_CTX + wg * 256 + tq * 16, a_t = sb + O_SM + (16 * warp + 8 * (tq & 1) + g) * 4;
    const unsigned* px = scr->xao + 64 * rn + 2 * lane;
    bf16* po = out + 64 * rn + 2 * lane;
    PIN(ab); PIN(a_d); PIN(a_rl); PINL(pa); PIN(a_rs); PIN(a_st); PINL(po); PIN(a_hl); PINL(px); PIN(a_t);
    mbar_wait(bar0 + 8 * B_TAB);
    uint2 cf;
    uint2 bb[4];
    uint2 gbw;
    POLL {
      unsigned bad = 0;
      cf = ldx8(scr->xm + 1024 + (lane & 16) * 16 + 32 * warp + posof(2 * (lane & 15)));
#pragma unroll
      for (int s = 0; s < 4; s++) {
        const uint4 w = ldx16(scr->xm + 1024 - (g & 1) * 512 + 256 * (s >> 1) + 32 * warp + 16 * (s & 1) + 4 * tq);
        bb[s] = make_uint2(__byte_perm(w.x, w.y, 0x7632), __byte_perm(w.z, w.w, 0x7632));
        bad = or3(bad, lop_x3(w.x, w.y, par), lop_x3(w.z, w.w, par));
      }
      gbw = ldx8(scr->xm + 1536 + 64 * rn + posof(2 * lane));
      RETRY(or3(bad, lop_x3(cf.x, cf.y, par), lop_x3(gbw.x, gbw.y, par)))
    }
    float e[4][4] = {};
    unsigned v[8];
    auto item = [&](const int it) {
      mbar_wait(fulla + 8 * it, pha);
#pragma unroll
      for (int i = 0; i < 4; i++) ldsm_t(af[it][i], (ab + it * 16384 + (i >> 1) * 1024) ^ ((i & 1) << 5));
    };
    auto item_mma = [&](const int it) {
#pragma unroll
      for (int i = 0; i < 4; i++) mma16(e[2 * (it & 1) + (i & 1)], af[it][i], bb[(it & 2) + (i >> 1)].x, bb[(it & 2) + (i >> 1)].y);
    };
    unsigned t3 = sch.wt;
    PIN(t3);
    item(0); item_mma(0); item(1); item_mma(1);
    mbar_wait(bar0 + 8 * B_G);
#pragma unroll
    for (int i = 0; i < 8; i++) v[i] = ldx4(pa + i * 256);
    t3 += clock();
    uint32_t have2, have3 = 0;
    do have2 = mbar_test(fulla + 16, pha); while (!have2 && (int)((unsigned)clock() - t3) < 0);
    if (have2) {
      item(2); item_mma(2);
      do have3 = mbar_test(fulla + 24, pha); while (!have3 && (int)((unsigned)clock() - t3) < 0);
      if (have3) { item(3); item_mma(3); }
    }
    float y0, y1, df[4][4], st[2];
    uint32_t bz[4][2] = {};
    auto mm = [&](const int it, const int i) { mma16(df[2 * (it & 1) + (i & 1)], af[it][i], bz[(it & 2) + (i >> 1)][0], bz[(it & 2) + (i >> 1)][1]); };
    POLL {
      if (it_)
#pragma unroll
        for (int i = 0; i < 8; i++) v[i] = ldx4(pa + i * 256);
      y0 = ((bflo(v[0]) + bflo(v[1])) + (bflo(v[2]) + bflo(v[3]))) + ((bflo(v[4]) + bflo(v[5])) + (bflo(v[6]) + bflo(v[7])));
      y1 = ((bfhi(v[0]) + bfhi(v[1])) + (bfhi(v[2]) + bfhi(v[3]))) + ((bfhi(v[4]) + bfhi(v[5])) + (bfhi(v[6]) + bfhi(v[7])));
      const uint32_t zb = pack2(y0 * u2f(cf.x), y1 * u2f(cf.y));
#pragma unroll
      for (int s = 0; s < 4; s++) {
        const uint32_t w = __shfl_sync(~0u, zb, 8 * s + (lane & 7));
        bz[s][0] = (lane & 4) ? 0u : w; bz[s][1] = (lane & 4) ? w : 0u;
      }
      st[0] = y0 + y1; st[1] = y0 * y0 + y1 * y1;
      tred<1>(st, lane, 16);
#pragma unroll
      for (int i = 0; i < 4; i++) df[i][0] = df[i][1] = df[i][2] = df[i][3] = 0.f;
      mm(0, 0); mm(0, 1); mm(1, 0); mm(1, 1);
      st[0] += shx(st[0], 8);
      mm(0, 2); mm(0, 3); mm(1, 2); mm(1, 3);
      RETRY(or3(or3(lop_x3(v[0], v[1], par), lop_x3(v[2], v[3], par), lop_x3(v[4], v[5], par)), lop_x3(v[6], v[7], par), 0))
    }
    uint2 xq[8];
    if (warp == 0)
#pragma unroll
      for (int i = 0; i < 8; i++) xq[i] = ldx8(px + i * 512);
    if (have2) { mm(2, 0); mm(2, 1); mm(2, 2); mm(2, 3); }
    st[0] += shx(st[0], 4);
    st[0] += shx(st[0], 2);
    st[0] += shx(st[0], 1);
    sts4(a_st, st[0]);
    __syncwarp();
    arrive_n(bar0 + 8 * B_ST, lane == 0, 1);
    if (!have2) { item(2); item_mma(2); mm(2, 0); mm(2, 1); mm(2, 2); mm(2, 3); }
    if (!have3) { item(3); item_mma(3); }
    mm(3, 0); mm(3, 1); mm(3, 2); mm(3, 3);
    mbar_wait(bar0 + 8 * B_ST);
    float mean, rstd;
    {
      float4 u[4];
#pragma unroll
      for (int i = 0; i < 4; i++) u[i] = lds16(sb + O_SM + (352 + 4 * i) * 4);
      mean = (((u[0].x + u[0].y) + (u[0].z + u[0].w)) + ((u[1].x + u[1].y) + (u[1].z + u[1].w))) * (1.f / 512.f);
      const float sq = (((u[2].x + u[2].y) + (u[2].z + u[2].w)) + ((u[3].x + u[3].y) + (u[3].z + u[3].w))) * (1.f / 512.f);
      asm("rsqrt.approx.ftz.f32 %0, %1;" : "=f"(rstd) : "f"(fmaxf(sq - mean * mean, 0.f) + 1e-5f));
    }
    float A[4], r[4];
#pragma unroll
    for (int i = 0; i < 4; i++) {
      A[i] = (tq & 2) ? ((tq & 1) ? e[3][i] : e[2][i]) : ((tq & 1) ? e[1][i] : e[0][i]);
      r[i] = (tq & 2) ? ((tq & 1) ? df[3][i] : df[2][i]) : ((tq & 1) ? df[1][i] : df[0][i]);
    }
    sts4(a_rs, rstd * (r[0] + r[1]) + (A[1] - rstd * mean * A[0])); sts4(a_rs + 128, rstd * (r[2] + r[3]) + (A[3] - rstd * mean * A[2]));
    nbar(1, 256);
    if (wg) {
      const float4 g0 = lds16(a_rl), g1 = lds16(a_rl + 1024), u0 = lds16(a_rl + 512), u1 = lds16(a_rl + 1536);
      const float gg = bfr(((g0.x + g0.y) + (g0.z + g0.w)) + ((g1.x + g1.y) + (g1.z + g1.w)));
      const float uu = bfr(((u0.x + u0.y) + (u0.z + u0.w)) + ((u1.x + u1.y) + (u1.z + u1.w)));
      const float hh = bfr(gg * rcp(1.f + ex2(gg * (-2.302208198f - 0.1029432397f * gg * gg)))) * uu;
      send32(a_h, a_hb, hh, lane);
    } else spin_until(clock() + FDLY);
    uint32_t ad[8][4];
    mbar_wait(fullb + 8 * wg, phb);
#pragma unroll
    for (int i = 0; i < 8; i++) ldsm_t(ad[i], a_d + i * 2048);
    float x0, x1;
    if (warp == 0) {
      POLL {
        if (it_)
#pragma unroll
          for (int i = 0; i < 8; i++) xq[i] = ldx8(px + i * 512);
        unsigned bad = 0;
#pragma unroll
        for (int i = 0; i < 4; i++) bad = or3(bad, lop_x3(xq[i].x, xq[i].y, par), lop_x3(xq[i + 4].x, xq[i + 4].y, par));
        RETRY(bad)
      }
      x0 = x1 = 0.f;
#pragma unroll
      for (int i = 0; i < 8; i++) { x0 += u2f(xq[i].x); x1 += u2f(xq[i].y); }
      x0 *= 1.f / 7.f; x1 *= 1.f / 7.f;
    }
    mbar_wait(bar0 + 8 * B_HZ);
    float dd[4][4] = {};
#pragma unroll
    for (int i = 0; i < 4; i++) {
      const float4 hb = lds16(a_hl + i * 64);
      mma16(dd[(2 * i) & 3], ad[2 * i], __float_as_uint(hb.x), __float_as_uint(hb.y));
      mma16(dd[(2 * i + 1) & 3], ad[2 * i + 1], __float_as_uint(hb.z), __float_as_uint(hb.w));
    }
    sts4(a_t, (tq & 1) ? (dd[0][2] + dd[1][2]) + (dd[2][2] + dd[3][2]) : (dd[0][0] + dd[1][0]) + (dd[2][0] + dd[3][0]));
    if (warp) nbar_arrive(2, 256);
    else {
      nbar(2, 256);
      float t0, t1, t2, t3b;
      asm volatile("ld.shared.v2.f32 {%0, %1}, [%4]; ld.shared.v2.f32 {%2, %3}, [%4 + 256];"
                   : "=f"(t0), "=f"(t1), "=f"(t2), "=f"(t3b) : "r"(sb + O_SM + lane * 8) : "memory");
      t0 = bfhi(gbw.x) * (t0 + t2) + x0; t1 = bfhi(gbw.y) * (t1 + t3b) + x1;
      asm volatile("red.relaxed.gpu.global.add.noftz.bf16x2 [%0], %1;" ::"l"(po), "r"(pack2(t0, t1)) : "memory");
      if (f == 0 && tid == 0) stx4(&scr->cnt[0], epoch + 1);
    }
  }
}

static void make_sched(Sched& s) {
  const char* order = "FFAAbcFmmvog..d";
  const double dt = 5010 * 1e-3, dth = 4850 * 1e-3;
  const int nbig = NBIG;
  s.zero = 0; s.dth = (unsigned)(dth * 256 + 0.5);
  double t = 512 * dth + 80;
  int tile = 0, jm = 0;
  for (int i = 0; i < 3; i++) s.nr[i] = s.nt[i] = 0;
  auto add = [&](int c, int type, double step, int win, int b0, int tl) {
    s.r[c][s.nr[c]++] = make_uint2((unsigned)(t + 0.5) | (unsigned)(step + 0.5) << 16, type | win << 4 | (b0 + 64) << 8 | tl << 16);
    if (type == T_KV) s.nt[c]++;
  };
  const int w1 = 6, w2 = 4, wt = 6;
  for (const char* p = order; *p; p++) {
    const char c = *p;
    if (c == 'v' || c == 'o' || c == 'm') {
      const int ty = c == 'v' ? T_UV : c == 'o' ? T_WO : T_MOD;
      const double d = (c == 'm' ? 5010 : c == 'v' ? 5600 : 5600) * 1e-3;
      add(0, ty, 64 * d, wt, 0, c == 'm' ? jm : 0); add(1, ty, 64 * d, wt, 0, c == 'm' ? jm : 0);
      t += (c == 'm' ? 64 : 256) * d; jm += c == 'm';
    } else if (c == 'g' || c == 'd') {
      const double d = (c == 'g' ? 5400 : 5500) * 1e-3;
      add(2, c == 'g' ? T_GU : T_DN, 56 * d, wt, 64, 0);
      t += (c == 'g' ? 224 : 112) * d;
    } else if (c == '.') t += 100;
    else if (c == '-') t -= 100;
    else {
      const int na = c == 'F' ? 0 : c == 'C' || c == 'c' || c == 'a' ? nbig : 64, nf = c == 'A' || c == 'a' ? 0 : 56, n = na + nf;
      const int w = na && nf ? w2 : w1;
      const bool ff = c == 'b' || c == 'c';
      const int cf = c == 'c' ? 60 : 0, ca = cf * 7 / 5;
      t += 3 * ca;
      if (na) add(0, T_KV, n * dt - ca, w, ff ? -56 : 0, tile);
      t -= 3 * ca;
      if (na == 64) add(1, T_KV, n * dt, w, ff ? -56 : 0, tile);
      if (nf) add(2, T_KV, n * dt - cf, w, ff ? 64 : 64 - na, tile);
      tile += n; t += 4 * n * dt;
      s.t4 = (unsigned)t + 600;
    }
  }
  s.dt = (unsigned)(dt * 256 + 0.5); s.d4 = 1560 | 1200 << 16; s.d6 = 3190; s.wt = 250;
}

static void launch(void* const* d_in, void* d_out) {
  static TMaps tms;
  static Sched sch;
  static bool init = false;
  static void* scr = nullptr;
  if (!init) {
    void* fn = nullptr; cudaDriverEntryPointQueryResult qr;
    cudaGetDriverEntryPoint("cuTensorMapEncodeTiled", &fn, cudaEnableDefault, &qr);
    EncFn f = (EncFn)fn;
    const CUtensorMapSwizzle S64 = CU_TENSOR_MAP_SWIZZLE_64B, S128 = CU_TENSOR_MAP_SWIZZLE_128B;
    const CUtensorMapL2promotion P256 = CU_TENSOR_MAP_L2_PROMOTION_L2_256B;
    enc3d(f, &tms.m[0], d_in[2], 64, 512, 64, 8192, 128, 64, 128, 1, S128, CU_TENSOR_MAP_L2_PROMOTION_L2_128B);
    enc3d(f, &tms.m[1], d_in[3], 64, 512, 64, 8192, 128, 64, 64, 2, S128, P256);
    enc3d(f, &tms.m[2], d_in[1], 64, SK, 8, 1024, 128, 64, 64, 2, S128, P256);
    enc3d(f, &tms.m[3], d_in[11], 3072, 256, 2, 6144, 256 * 6144, 32, 256, 1, S64, CU_TENSOR_MAP_L2_PROMOTION_L2_128B);
    enc3d(f, &tms.m[4], d_in[4], 64, 512, 64, 8192, 128, 64, 128, 1, S128, CU_TENSOR_MAP_L2_PROMOTION_L2_128B);
    enc3d(f, &tms.m[5], d_in[5], 512, 128, 32, 1024, 128 * 1024, 64, 128, 1, S128, CU_TENSOR_MAP_L2_PROMOTION_L2_128B);
    enc3d(f, &tms.m[6], d_in[7], 1792, 256, 2, 3584, 256 * 3584, 32, 256, 1, S64, CU_TENSOR_MAP_L2_PROMOTION_L2_128B);
    enc3d(f, &tms.m[7], d_in[8], 1792, 256, 2, 3584, 256 * 3584, 32, 256, 1, S64, CU_TENSOR_MAP_L2_PROMOTION_L2_128B);
    enc3d(f, &tms.m[8], d_in[9], 512, 128, 14, 1024, 128 * 1024, 64, 128, 1, S128, CU_TENSOR_MAP_L2_PROMOTION_L2_128B);
    cudaFuncSetAttribute(fused_kernel, cudaFuncAttributeMaxDynamicSharedMemorySize, SMEM9);
    cudaGetSymbolAddress(&scr, g_scr);
    make_sched(sch);
    init = true;
  }
  fused_kernel<<<NCTA9, 384, SMEM9>>>((const bf16*)d_in[0], (const bf16*)d_in[10], (const bf16*)d_in[11], (bf16*)d_out, (Scratch*)scr, sch, tms);
}

static bool fits() {
  cudaFuncSetAttribute(fused_kernel, cudaFuncAttributeMaxDynamicSharedMemorySize, SMEM9);
  cudaLaunchConfig_t cfg = {};
  cfg.gridDim = dim3(NCTA9); cfg.blockDim = dim3(384); cfg.dynamicSmemBytes = SMEM9;
  cudaLaunchAttribute at[1];
  at[0].id = cudaLaunchAttributeClusterDimension; at[0].val.clusterDim.x = 8; at[0].val.clusterDim.y = 1; at[0].val.clusterDim.z = 1;
  cfg.attrs = at; cfg.numAttrs = 1;
  int n = 0;
  if (cudaOccupancyMaxActiveClusters(&n, fused_kernel, &cfg) != cudaSuccess) { (void)cudaGetLastError(); return false; }
  return n >= NCTA9 / 8;
}
}
#undef BAR_ARM
#undef BAR_ARRIVE
#undef BAR_INIT
#undef B_EMPTY
#undef B_FM
#undef B_FULL
#undef B_G
#undef B_G2
#undef B_H
#undef B_HZ
#undef B_LZ
#undef B_Q2
#undef B_QF
#undef B_ST
#undef B_TAB
#undef B_W
#undef B_WZ
#undef CNT_ADD
#undef DSC
#undef FDLY
#undef HI128
#undef HI64
#undef LANE0
#undef NBIG
#undef NCTA9
#undef NPE
#undef NPO
#undef NSL
#undef O_B
#undef O_BAR
#undef O_CTX
#undef O_DBG
#undef O_EP
#undef O_HW
#undef O_HZ
#undef O_LZ
#undef O_P
#undef O_Q
#undef O_R
#undef O_SILU
#undef O_SM
#undef O_X
#undef PIN
#undef PINL
#undef POLL
#undef QN
#undef RETRY
#undef SK
#undef SMEM9
#undef SMEM_BASE
#undef SPIN_MAX
#undef TAU
#undef VDLY
#undef VJ
#undef X16
#undef fbits

namespace v8 {
typedef __nv_bfloat16 bf16;
#define NCTA 128
#define SK 32768
#define SLOT 32768
#define NSLOT 6
#define OFF_WQ (2 * SLOT)
#define OFF_WUK (4 * SLOT)
#define OFF_Q 196608
#define OFF_P (OFF_Q + 16384)
#define OFF_B (OFF_P + 4096)
#define OFF_R4 (OFF_B + 2304)
#define OFF_SILU (OFF_R4 + 4096)
#define OFF_RA (OFF_SILU + 1024)
#define OFF_SM (OFF_RA + 1024)
#define OFF_BP (OFF_SM + 1792)
#define OFF_CO (OFF_BP + 1024)
#define OFF_BAR (OFF_CO + 1280)
#define OFF_MASK (OFF_BAR + 512)
#define OFF_DBG (OFF_MASK + 16)
#define SMEM_BYTES (OFF_DBG + 128)
#define OFF_MOD OFF_Q
#define OFF_UV (4 * SLOT)
#define OFF_O (5 * SLOT)
#define OFF_G 0
#define OFF_U 16384
#define OFF_D SLOT
#define OFF_XO (OFF_D + 16384)
#define FB_UK 4
#define FB_KV 6
#define FB_MOD 22
#define FB_UV 23
#define FB_O 25
#define FB_G 27
#define FB_D 29
#define EB 30
#define QB 50
#define XB 51
#define SPIN_MAX (1 << 20)
#define BACKOFF 40
#define RATE_NS 652
#define RATE_T0 200
#define RATE_TL 300
#define WINS 0x3222333
#define KVWIN 4
#define RATE_H 650
#define RATE_E 650
#define SMUL 9
#define NPRE0 1
#define NPRE1 3
#define HWIN 4
#define EWIN 3
#define WTEST 450
#define DLY5 650
#define DLY6 600
#define DLY7 600
#define P12(a, b, c, d, e, f, g, h, i, j, k, l) ((unsigned long long)(a) | (b) << 5 | (c) << 10 | (d) << 15 | (e) << 20 | (f) << 25 | \
  (unsigned long long)(g) << 30 | (unsigned long long)(h) << 35 | (unsigned long long)(i) << 40 | (unsigned long long)(j) << 45 | \
  (unsigned long long)(k) << 50 | (unsigned long long)(l) << 55)
#define ORDER0 P12(0, 1, 2, 3, 4, 5, 16, 6, 7, 8, 9, 10)
#define ORDER1 P12(11, 12, 13, 14, 15, 17, 18, 19, 20, 23, 21, 22)
#define TAIL_K 17
#define RS 16
template <int N> struct IC { static constexpr int value = N; };
struct TMaps { CUtensorMap m[9]; };

struct __align__(128) Scratch {
  uint4 xo[128 * 64 * RS];
  uint2 ml[32 * 64];
  unsigned h[8 * 256];
  unsigned qa[32 * 256];
  unsigned xc[128 * 64];
  unsigned xao[8 * 512];
  unsigned xf[112 * 512];
  unsigned xm[2048];
  unsigned cnt[5 * 32];
};
__device__ Scratch g_scr;
#define g_xo scr->xo
#define g_ml scr->ml
#define g_h scr->h
#define g_qa scr->qa
#define g_xc scr->xc
#define g_xao scr->xao
#define g_xf scr->xf
#define g_xm scr->xm
#define g_epoch scr->cnt[0]

__device__ __forceinline__ uint32_t s2u(const void* p) { return (uint32_t)__cvta_generic_to_shared(p); }
__device__ __forceinline__ float bflo(uint32_t u) { return __uint_as_float(u << 16); }
__device__ __forceinline__ float bfhi(uint32_t u) { return __uint_as_float(u & 0xffff0000u); }
__device__ __forceinline__ float u2f(uint32_t u) { return __uint_as_float(u); }
__device__ __forceinline__ void fma8(float* acc, uint4 v, float s) {
  acc[0] += s * bflo(v.x); acc[1] += s * bfhi(v.x); acc[2] += s * bflo(v.y); acc[3] += s * bfhi(v.y);
  acc[4] += s * bflo(v.z); acc[5] += s * bfhi(v.z); acc[6] += s * bflo(v.w); acc[7] += s * bfhi(v.w);
}
__device__ __forceinline__ uint32_t pack2(float a, float b) {
  __nv_bfloat162 p = __floats2bfloat162_rn(a, b); return *(uint32_t*)&p;
}
__device__ __forceinline__ float bfr(float v) { return bfhi(pack2(v, v)); }
__device__ __forceinline__ float silu_bf(float c) { return bfr(__fdividef(c, 1.f + __expf(-c))); }
#define fbits(v) ((__float_as_uint(v) & ~1u) | par)
__device__ __forceinline__ uint32_t pack2t(float a, float b, unsigned par) {
  const uint32_t ua = ((__float_as_uint(a) + ((par ^ 1) << 16)) & 0xFFFE0000u) | (par << 16);
  return __byte_perm(ua, pack2(b, b), 0x7632);
}
__device__ __forceinline__ void nbar(int id, int n) { asm volatile("bar.sync %0, %1;" ::"r"(id), "r"(n) : "memory"); }
__device__ __forceinline__ void nbar_arrive(int id, int n) { asm volatile("bar.arrive %0, %1;" ::"r"(id), "r"(n) : "memory"); }
__device__ __forceinline__ uint4 ldc16(const void* p) {
  uint4 v; asm volatile("ld.relaxed.cta.global.v4.u32 {%0,%1,%2,%3}, [%4];" : "=r"(v.x), "=r"(v.y), "=r"(v.z), "=r"(v.w) : "l"(p) : "memory"); return v;
}
__device__ __forceinline__ unsigned ldc4(const void* p) {
  unsigned v; asm volatile("ld.relaxed.cta.global.u32 %0, [%1];" : "=r"(v) : "l"(p) : "memory"); return v;
}
__device__ __forceinline__ uint4 ldx16(const void* p) {
  uint4 v; asm volatile("ld.relaxed.gpu.global.v4.u32 {%0,%1,%2,%3}, [%4];" : "=r"(v.x), "=r"(v.y), "=r"(v.z), "=r"(v.w) : "l"(p) : "memory"); return v;
}
__device__ __forceinline__ unsigned ldx4(const void* p) {
  unsigned v; asm volatile("ld.relaxed.gpu.global.u32 %0, [%1];" : "=r"(v) : "l"(p) : "memory"); return v;
}
__device__ __forceinline__ unsigned long long ldx64(const void* p) {
  unsigned long long v; asm volatile("ld.relaxed.gpu.global.u64 %0, [%1];" : "=l"(v) : "l"(p) : "memory"); return v;
}
__device__ __forceinline__ void stx16(void* p, uint4 v) {
  asm volatile("st.relaxed.gpu.global.v4.u32 [%0], {%1,%2,%3,%4};" ::"l"(p), "r"(v.x), "r"(v.y), "r"(v.z), "r"(v.w) : "memory");
}
__device__ __forceinline__ void stx8(void* p, uint2 v) { asm volatile("st.relaxed.gpu.global.v2.u32 [%0], {%1,%2};" ::"l"(p), "r"(v.x), "r"(v.y) : "memory"); }
__device__ __forceinline__ void stx4(void* p, unsigned v) { asm volatile("st.relaxed.gpu.global.u32 [%0], %1;" ::"l"(p), "r"(v) : "memory"); }
__device__ __forceinline__ unsigned lop_x3(unsigned a, unsigned b, unsigned c) {
  unsigned d; asm("lop3.b32 %0, %1, %2, %3, 0x7E;" : "=r"(d) : "r"(a), "r"(b), "r"(c)); return d; }
#define X16(v) (lop_x3(v.x, v.y, par) | lop_x3(v.z, v.w, par))
#define X8(v) lop_x3(v.x, v.y, par)
#define RETRY(bad) if (!__any_sync(~0u, (bad) & 1) || ++it_ >= SPIN_MAX) break; __nanosleep(BACKOFF);
#define POLL _Pragma("unroll 1") for (int it_ = 0;;)
__device__ __forceinline__ void mbar_wait(uint32_t bar) {
  uint32_t ok; int it = 0;
  do {
    asm volatile("{.reg .pred p; mbarrier.try_wait.parity.shared::cta.b64 p, [%1], 0; selp.u32 %0,1,0,p;}"
                 : "=r"(ok) : "r"(bar) : "memory");
  } while (!ok && ++it < SPIN_MAX);
}
__device__ __forceinline__ float ex2(float v) { float r; asm("ex2.approx.ftz.f32 %0, %1;" : "=f"(r) : "f"(v)); return r; }
__device__ __forceinline__ float rcp(float v) { float r; asm("rcp.approx.ftz.f32 %0, %1;" : "=f"(r) : "f"(v)); return r; }
__device__ __forceinline__ void mma16(float* d, const uint32_t* a, uint32_t b0, uint32_t b1) {
  asm volatile("mma.sync.aligned.m16n8k16.row.col.f32.bf16.bf16.f32 {%0,%1,%2,%3}, {%4,%5,%6,%7}, {%8,%9}, {%0,%1,%2,%3};"
               : "+f"(d[0]), "+f"(d[1]), "+f"(d[2]), "+f"(d[3]) : "r"(a[0]), "r"(a[1]), "r"(a[2]), "r"(a[3]), "r"(b0), "r"(b1));
}
__device__ __forceinline__ float4 lds16(uint32_t a) {
  float4 v; asm volatile("ld.shared.v4.f32 {%0,%1,%2,%3}, [%4];" : "=f"(v.x), "=f"(v.y), "=f"(v.z), "=f"(v.w) : "r"(a) : "memory"); return v;
}
__device__ __forceinline__ void ldsm_t(uint32_t* r, uint32_t a) {
  asm volatile("ldmatrix.sync.aligned.m8n8.x4.trans.shared.b16 {%0,%1,%2,%3}, [%4];" : "=r"(r[0]), "=r"(r[1]), "=r"(r[2]), "=r"(r[3]) : "r"(a) : "memory");
}
__device__ __forceinline__ void ldsm(uint32_t* r, uint32_t a) {
  asm volatile("ldmatrix.sync.aligned.m8n8.x4.shared.b16 {%0,%1,%2,%3}, [%4];" : "=r"(r[0]), "=r"(r[1]), "=r"(r[2]), "=r"(r[3]) : "r"(a) : "memory");
}
template <int N>
__device__ __forceinline__ void tred(float* a, int lane, int m) {
  const bool hi = lane & m;
#pragma unroll
  for (int i = 0; i < N; i++) {
    float send = hi ? a[i] : a[i + N], keep = hi ? a[i + N] : a[i];
    a[i] = keep + __shfl_xor_sync(~0u, send, m);
  }
}
template <int N>
__device__ __forceinline__ void tmax(float* a, int lane, int m) {
  const bool hi = lane & m;
#pragma unroll
  for (int i = 0; i < N; i++) {
    float send = hi ? a[i] : a[i + N], keep = hi ? a[i + N] : a[i];
    a[i] = fmaxf(keep, __shfl_xor_sync(~0u, send, m));
  }
}
__device__ __forceinline__ void arrive2(uint32_t bar, uint32_t rbar, bool local, bool remote) {
  asm volatile("{.reg .pred p, q; setp.ne.s32 p, %2, 0; setp.ne.s32 q, %3, 0; @p mbarrier.arrive.shared::cta.b64 _, [%0];\n"
               "@q mbarrier.arrive.relaxed.cluster.shared::cluster.b64 _, [%1];}" ::"r"(bar), "r"(rbar), "r"((int)local), "r"((int)remote) : "memory");
}
__device__ __forceinline__ unsigned long long stream_policy() {
  unsigned long long p;
  asm volatile("createpolicy.fractional.L2::evict_first.b64 %0, 1.0;" : "=l"(p));
  return p;
}
__device__ __forceinline__ void tma3d(uint32_t dst, const CUtensorMap* tm, uint32_t bar, int c0, int c1, int c2) {
  asm volatile("cp.async.bulk.tensor.3d.shared::cluster.global.mbarrier::complete_tx::bytes.L2::cache_hint [%0], [%1, {%3, %4, %5}], [%2], %6;"
               ::"r"(dst), "l"(tm), "r"(bar), "r"(c0), "r"(c1), "r"(c2), "l"(stream_policy()) : "memory");
}
__device__ __forceinline__ void st_async2(uint32_t dst, uint32_t bar, float v0, float v1) {
  asm volatile("st.async.shared::cluster.mbarrier::complete_tx::bytes.v2.f32 [%0], {%1, %2}, [%3];" ::"r"(dst), "f"(v0), "f"(v1), "r"(bar) : "memory");
}
__device__ __forceinline__ void st_pair(int mode, uint32_t dst, uint32_t bar, float v0, float v1) {
  asm volatile("{.reg .pred p, q; setp.eq.s32 p, %4, 1; setp.eq.s32 q, %4, 2; @p st.shared.v2.f32 [%0], {%1, %2};\n"
               "@q st.async.shared::cluster.mbarrier::complete_tx::bytes.v2.f32 [%0], {%1, %2}, [%3];}"
               ::"r"(dst), "f"(v0), "f"(v1), "r"(bar), "r"(mode) : "memory");
}
__device__ __forceinline__ void spin_until(unsigned t) { while ((int)((unsigned)clock() - t) < 0) {} }
__device__ __forceinline__ unsigned wait_until(unsigned t) {
  unsigned now;
  for (;;) {
    asm volatile("mov.u32 %0, %%globaltimer_lo;" : "=r"(now));
    if ((int)(now - t) >= 0) break;
  }
  return now;
}
#define PIN(x) asm volatile("" : "+r"(x))
#define PINL(x) asm volatile("" : "+l"(x))
#define BAR_ARRIVE(i) asm volatile("mbarrier.arrive.shared::cta.b64 _, [%0];" ::"r"(bar0 + 8 * (i)) : "memory")
#define CNT_ADD(c) asm volatile("red.relaxed.gpu.global.add.u32 [%0], 1;" ::"l"(scr->cnt + (c)) : "memory")
#define BAR_INIT(i, cnt) asm volatile("mbarrier.init.shared::cta.b64 [%0], %1;" ::"r"(bar0 + 8 * (i)), "r"(cnt) : "memory")
#define BAR_ARM(i, bytes) asm volatile("mbarrier.arrive.expect_tx.shared::cta.b64 _, [%0], %1;" ::"r"(bar0 + 8 * (i)), "r"(bytes) : "memory")

__device__ __forceinline__ void tail(unsigned char* smem, Scratch* __restrict__ scr, const bf16* __restrict__ x, bf16* __restrict__ out,
                                     const unsigned par, const unsigned epoch, const int warp) {
  int tid, b;
  asm volatile("mov.u32 %0, %%tid.x;" : "=r"(tid));
  asm volatile("mov.u32 %0, %%ctaid.x;" : "=r"(b));
  const int lane = tid & 31, g = lane >> 2, tq = lane & 3;
  const uint32_t sb = __shfl_sync(~0u, s2u(smem), 0), bar0 = sb + OFF_BAR;
  float* s_sm = (float*)(smem + OFF_SM);
  const int prow = 4 * (lane >> 4) + ((lane & 7) >> 1) + 8 * (lane & 1);
  const float* s_co = (const float*)(smem + OFF_CO);
  const int opos = (b & 15) * 32 + (lane & 16) + 2 * (lane & 6) + ((lane >> 2) & 2) + (lane & 1);
  const float xv = b < 16 ? __bfloat162float(x[(b & 15) * 32 + lane]) : 0.f;
  const int rk = b & 1, ob = 32 * rk + ((b >> 1) & 31);
  uint32_t psb;
  asm volatile("mapa.shared::cluster.u32 %0, %1, %2;" : "=r"(psb) : "r"(sb), "r"(rk ^ 1));
  {
    uint32_t a[8][4];
    {
      const int rg = tid >> 4;
      const uint4* src = g_xo + ((size_t)b * 64 + rg) * RS;
      const uint32_t dst = sb + OFF_XO + rg * 256 + (((tid & 15) ^ (rg & 7)) << 4);
      unsigned long long todo = 0x0001000100010001ull;
#pragma unroll 1
      for (int it = 0; it < SPIN_MAX * 16; it++) {
        unsigned long long mk = *(volatile unsigned long long*)(smem + OFF_MASK);
        const unsigned long long nw = (mk >> rg) & todo;
        todo ^= nw;
#pragma unroll
        for (int i = 0; i < 4; i++)
          if (nw >> (16 * i) & 1)
            asm volatile("cp.async.cg.shared.global [%0], [%1], 16;" ::"r"(dst + i * 4096), "l"(src + i * 16 * RS + (tid & 15)) : "memory");
        if (!__any_sync(~0u, todo != 0)) break;
      }
      asm volatile("cp.async.mbarrier.arrive.noinc.shared::cta.b64 [%0];" ::"r"(bar0 + 8 * (XB + 2)) : "memory");
    }
    mbar_wait(bar0 + 8 * FB_UV); mbar_wait(bar0 + 8 * (FB_UV + 1));
    const uint32_t ab = sb + OFF_UV + (warp >> 2) * 8192 + (8 * (lane >> 4) + (lane & 7)) * 128 + (((2 * (warp & 3) + ((lane >> 3) & 1)) ^ (lane & 7)) << 4);
#pragma unroll
    for (int s = 0; s < 8; s++) ldsm_t(a[s], ab + (s >> 2) * 16384 + (s & 3) * 2048);
    const int chn = 2 * warp + (tq & 1);
    uint32_t a_b = sb + OFF_B + (tq >> 1) * 272 + (32 * (chn >> 2) + 8 * (g >> 1) + 2 * (chn & 3) + (g & 1)) * 2;
    uint32_t a_bq = sb + OFF_B + (lane & 1) * 272 + (lane >> 3) * 16;
    unsigned* p_c = g_xc + (b >> 2) * 256 + warp * 32 + (b & 3) * 8 + (g & 3) * 2 + (g >> 2);
    PIN(a_b); PIN(a_bq); PINL(p_c);
    mbar_wait(bar0 + 8 * (XB + 6));
    uint32_t wb[8];
#pragma unroll
    for (int s = 0; s < 8; s++) wb[s] = *(const uint32_t*)(smem + OFF_RA + (4 * s + tq) * 4);
    const float invL = *(const float*)(smem + OFF_RA + 128);
    float ov;
    POLL {
      mbar_wait(bar0 + 8 * (XB + 2));
      uint32_t ao[4][4];
#pragma unroll
      for (int s = 0; s < 4; s++)
        ldsm_t(ao[s], sb + OFF_XO + (16 * s + 8 * (lane >> 4) + (lane & 7)) * 256 + (((2 * warp + ((lane >> 3) & 1)) ^ (lane & 7)) << 4));
      float d[4][4] = {};
#pragma unroll
      for (int s = 0; s < 4; s++) mma16(d[s], ao[s], wb[2 * s], wb[2 * s + 1]);
      const unsigned p2 = par * 0x10001u;
      unsigned bad = 0;
#pragma unroll
      for (int s = 0; s < 4; s++) bad |= lop_x3(ao[s][0], ao[s][1], p2) | lop_x3(ao[s][2], ao[s][3], p2);
      bad = g == 0 ? bad | (bad >> 16) : 0u;
      ov = (tq & 1) ? (d[0][2] + d[1][2]) + (d[2][2] + d[3][2]) : (d[0][0] + d[1][0]) + (d[2][0] + d[3][0]);
      if (__builtin_expect(!__any_sync(~0u, bad & 1) || ++it_ >= SPIN_MAX, 1)) break;
#pragma unroll
      for (int i = 0; i < 4; i++)
        asm volatile("cp.async.cg.shared.global [%0], [%1], 16;"
                     ::"r"(sb + OFF_XO + ((lane >> 1) + 16 * i) * 256 + (((2 * warp + (lane & 1)) ^ ((lane >> 1) & 7)) << 4)),
                       "l"(g_xo + ((size_t)b * 64 + (lane >> 1) + 16 * i) * RS + 2 * warp + (lane & 1)) : "memory");
      asm volatile("cp.async.wait_all;" ::: "memory");
      __syncwarp();
    }
    {
      const float lo = ov - bfhi(__float_as_uint(ov));
      asm volatile("st.shared.u16 [%0], %1;" ::"r"(a_b), "h"((unsigned short)((tq & 2) ? pack2(lo, lo) : __float_as_uint(ov) >> 16)) : "memory");
    }
    nbar(1, 256);
    float d[4][4] = {};
#pragma unroll
    for (int y = 0; y < 4; y++) {
      uint32_t bq[4];
      ldsm(bq, a_bq + 64 * y);
      mma16(d[(2 * y) & 3], a[2 * y], bq[0], bq[1]); mma16(d[(2 * y + 1) & 3], a[2 * y + 1], bq[2], bq[3]);
    }
    const float r0 = ((d[0][0] + d[0][1]) + (d[1][0] + d[1][1])) + ((d[2][0] + d[2][1]) + (d[3][0] + d[3][1]));
    const float r1 = ((d[0][2] + d[0][3]) + (d[1][2] + d[1][3])) + ((d[2][2] + d[2][3]) + (d[3][2] + d[3][3]));
    if (tq == 0) stx4(p_c, pack2t(r0 * invL, r1 * invL, par));
  }
  unsigned tpub = clock();
  mbar_wait(bar0 + 8 * (XB + 4));
  const float gav = s_co[256 + (opos & 31)];
  const float gbv = s_co[288 + (lane & 4) + 2 * (lane & 1) + ((lane >> 1) & 1)];
  float4 cf[2];
#pragma unroll
  for (int s = 0; s < 2; s++) cf[s] = *(const float4*)(s_co + 32 * warp + 16 * s + 4 * tq);
  {
    uint32_t a[2][4][4];
    mbar_wait(bar0 + 8 * (FB_O + (warp >> 2)));
    const uint32_t ab = sb + OFF_O + (32 * warp + prow) * 128 + ((((lane >> 3) & 1) ^ (prow & 7)) << 4);
#pragma unroll
    for (int i = 0; i < 8; i++) ldsm_t(a[i >> 2][i & 3], (ab + (i >> 2) * 2048) ^ ((i & 3) << 5));
    uint4 v;
    const unsigned* pc = g_xc + (4 * (b >> 4) + 2 * rk + (warp >> 2)) * 256 + 64 * (warp & 3) + 2 * lane;
    uint32_t ro = ((tq >> 1) == rk ? sb : psb) + OFF_P + (8 * (tq & 1) + g) * 144 + (8 * rk + warp) * 8;
    uint32_t a_q = sb + OFF_P + (8 * (lane >> 4) + (lane & 7)) * 144;
    unsigned* p_ao = g_xao + (b >> 5) * 1024 + (opos >> 4) * 32 + (b & 16) + (opos & 15);
    PIN(ro); PIN(a_q); PINL(p_ao); PINL(pc);
    spin_until(tpub + DLY5);
    POLL {
      const unsigned long long u0 = ldx64(pc);
      v.x = (unsigned)u0; v.y = u0 >> 32;
      RETRY(X8(v))
    }
    v.z = lane & 16 ? v.x : 0u; v.w = lane & 16 ? v.y : 0u;
    if (lane & 16) v.x = v.y = 0u;
    float d[4][4] = {};
#pragma unroll
    for (int mt = 0; mt < 4; mt++) mma16(d[mt], a[0][mt], v.x, v.y);
#pragma unroll
    for (int mt = 0; mt < 4; mt++) mma16(d[mt], a[1][mt], v.z, v.w);
    float r[8];
#pragma unroll
    for (int i = 0; i < 8; i++) r[i] = d[i >> 1][2 * (i & 1)] + d[i >> 1][2 * (i & 1) + 1];
    tred<4>(r, lane, 2); tred<2>(r, lane, 1);
    st_pair((tq >> 1) == rk ? 1 : 2, ro, psb + OFF_BAR + 8 * (XB + 3), r[0], r[1]);
    __syncwarp();
    if (lane == 0) BAR_ARRIVE(XB + 3);
    if (warp == 0) {
      mbar_wait(bar0 + 8 * (XB + 3));
      float p[8];
#pragma unroll
      for (int i = 0; i < 8; i++) {
        const float4 q = lds16(a_q + i * 16);
        p[i] = (lane & 8) ? q.y + q.w : q.x + q.z;
      }
      const float t = ((p[0] + p[1]) + (p[2] + p[3])) + ((p[4] + p[5]) + (p[6] + p[7]));
      stx4(p_ao, fbits(gav * t + xv));
    }
  }
  tpub = clock();
  if (b < 112) {
    uint32_t af[2][4][4], ad[4][4];
    const uint32_t ab = sb + (32 * warp + 8 * (lane >> 4) + (lane & 7)) * 64 + ((((lane >> 3) & 1) ^ ((lane >> 1) & 3)) << 4);
    uint32_t ro = ((tq & 1) == rk ? sb : psb) + OFF_R4 + (8 * (tq >> 1) + g) * 176 + (10 * rk + warp) * 8;
    uint32_t a_q = sb + OFF_R4 + (8 * (lane >> 4) + (lane & 7)) * 176 + (lane & 8) * 10;
    uint32_t a_d = sb + OFF_D + warp * 2048 + (8 * (lane >> 4) + (lane & 7)) * 128 + ((((lane >> 3) & 1) ^ (lane & 7)) << 4);
    unsigned* p_f = g_xf + b * 512 + 64 * warp + 16 * tq + 2 * g;
    const unsigned* pa = g_xao + (g >> 1) * 1024 + 512 * rk + 64 * warp + 4 * (lane & 7);
    PIN(ro); PIN(a_q); PIN(a_d); PINL(p_f); PINL(pa);
    spin_until(tpub + DLY6);
    uint4 v[2];
    {
      bool have = false;
      POLL {
        v[0] = ldx16(pa); v[1] = ldx16(pa + 32);
        const unsigned t1 = (unsigned)clock() + WTEST;
        while (!have && (int)((unsigned)clock() - t1) < 0) {
          uint32_t ok;
          asm volatile("{.reg .pred p, q; mbarrier.test_wait.parity.shared::cta.b64 p, [%1], 0; mbarrier.test_wait.parity.shared::cta.b64 q, [%1+8], 0;\n"
                       "and.pred p, p, q; vote.sync.all.pred p, p, 0xffffffff; selp.u32 %0, 1, 0, p;}" : "=r"(ok) : "r"(bar0 + 8 * FB_G) : "memory");
          if (ok) {
#pragma unroll
            for (int i = 0; i < 8; i++) ldsm_t(af[i >> 2][i & 3], (ab + ((i & 2) ? OFF_U : OFF_G) + (i >> 2) * 1024) ^ ((i & 1) << 5));
            have = true;
          }
        }
        if (!__any_sync(~0u, (X16(v[0]) | X16(v[1])) & 1) || ++it_ >= SPIN_MAX) break;
      }
      float df[4][4] = {}, dg[2][4] = {};
      uint32_t zb[4];
      const uint32_t one = g == 0 ? 0x3F803F80u : 0u;
#pragma unroll
      for (int s = 0; s < 2; s++) {
        const uint32_t y0 = pack2(u2f(v[s].x), u2f(v[s].y)), y1 = pack2(u2f(v[s].z), u2f(v[s].w));
        const uint32_t ya[4] = {y0, one, y1, one};
        mma16(dg[s], ya, y0, y1);
        zb[2 * s] = pack2(u2f(v[s].x) * cf[s].x, u2f(v[s].y) * cf[s].y); zb[2 * s + 1] = pack2(u2f(v[s].z) * cf[s].z, u2f(v[s].w) * cf[s].w);
      }
      float st[2] = {(dg[0][2] + dg[0][3]) + (dg[1][2] + dg[1][3]), (dg[0][0] + dg[0][1]) + (dg[1][0] + dg[1][1])};
      if (!have) {
        mbar_wait(bar0 + 8 * FB_G); mbar_wait(bar0 + 8 * (FB_G + 1));
#pragma unroll
        for (int i = 0; i < 8; i++) ldsm_t(af[i >> 2][i & 3], (ab + ((i & 2) ? OFF_U : OFF_G) + (i >> 2) * 1024) ^ ((i & 1) << 5));
      }
#pragma unroll
      for (int i = 0; i < 8; i++) mma16(df[i & 3], af[i >> 2][i & 3], zb[2 * (i >> 2)], zb[2 * (i >> 2) + 1]);
#pragma unroll
      for (int o2 = 1; o2 < 4; o2 <<= 1) { st[0] += __shfl_xor_sync(~0u, st[0], o2); st[1] += __shfl_xor_sync(~0u, st[1], o2); }
#pragma unroll
      for (int o2 = 4; o2 < 32; o2 <<= 1) st[1] += __shfl_xor_sync(~0u, st[1], o2);
      float r[8];
#pragma unroll
      for (int i = 0; i < 8; i++) r[i] = df[i >> 1][2 * (i & 1)] + df[i >> 1][2 * (i & 1) + 1];
      tred<4>(r, lane, 2); tred<2>(r, lane, 1);
      const int md = (tq & 1) == rk ? 1 : 2;
      st_pair(md, ro, psb + OFF_BAR + 8 * (XB + 5), r[0], r[1]);
      st_pair(lane < 2 ? md : 0, ro + 16 * 176, psb + OFF_BAR + 8 * (XB + 5), st[0], st[1]);
      __syncwarp();
      if (lane == 0) BAR_ARRIVE(XB + 5);
      mbar_wait(bar0 + 8 * FB_D);
#pragma unroll
      for (int mt = 0; mt < 4; mt++)
        ldsm_t(ad[mt], a_d ^ (mt << 5));
    }
    mbar_wait(bar0 + 8 * (XB + 5));
    {
      float4 q[5], u[8];
#pragma unroll
      for (int i = 0; i < 5; i++) q[i] = lds16(a_q + i * 16);
#pragma unroll
      for (int i = 0; i < 8; i++) u[i] = *(const float4*)(smem + OFF_R4 + 16 * 176 + (i >> 2) * 80 + (i & 3) * 16);
      float p[6] = {((q[0].x + q[0].z) + (q[1].x + q[1].z)) + ((q[2].x + q[2].z) + (q[3].x + q[3].z)), q[4].x, q[4].z,
                    ((q[0].y + q[0].w) + (q[1].y + q[1].w)) + ((q[2].y + q[2].w) + (q[3].y + q[3].w)), q[4].y, q[4].w};
      tred<3>(p, lane, 8);
      const float P = p[0], A1 = p[1], A2 = p[2];
      const float mean = (((u[0].x + u[0].z) + (u[1].x + u[1].z)) + ((u[2].x + u[2].z) + (u[3].x + u[3].z)) +
                          ((u[4].x + u[4].z) + (u[5].x + u[5].z)) + ((u[6].x + u[6].z) + (u[7].x + u[7].z))) * (1.f / 512.f);
      const float sq = (((u[0].y + u[0].w) + (u[1].y + u[1].w)) + ((u[2].y + u[2].w) + (u[3].y + u[3].w)) +
                         ((u[4].y + u[4].w) + (u[5].y + u[5].w)) + ((u[6].y + u[6].w) + (u[7].y + u[7].w))) * (1.f / 512.f);
      float rstd;
      asm("rsqrt.approx.ftz.f32 %0, %1;" : "=f"(rstd) : "f"(fmaxf(sq - mean * mean, 0.f) + 1e-5f));
      const float gg = bfr(rstd * (P - mean * A1) + A2);
      const float uu = __shfl_xor_sync(~0u, gg, 16);
      const float hh = bfr(gg * rcp(1.f + ex2(gg * (-2.302208198f - 0.1029432397f * gg * gg)))) * uu;
      const uint32_t hw = pack2(hh, __shfl_down_sync(~0u, hh, 1));
      const uint32_t b0 = __shfl_sync(~0u, hw, 2 * tq), b1 = __shfl_sync(~0u, hw, 2 * tq + 8);
      float f0 = 0, f1 = 0;
#pragma unroll
      for (int mt = 0; mt < 4; mt++) {
        float dd[4] = {0, 0, 0, 0};
        mma16(dd, ad[mt], b0, b1);
        if (tq == mt) { f0 = dd[0]; f1 = dd[2]; }
      }
      stx8(p_f, make_uint2(fbits(f0), fbits(f1)));
    }
    tpub = clock();
    if (b < 64 && warp == (b >> 3)) {
      const uint4 y = (b & 4) ? v[1] : v[0];
      float a4[4] = {u2f(y.x), u2f(y.y), u2f(y.z), u2f(y.w)};
      tred<2>(a4, lane, 16); tred<1>(a4, lane, 8);
      a4[0] += __shfl_xor_sync(~0u, a4[0], 4);
      if (!(lane & 4)) s_sm[416 + 8 * (lane >> 4) + 2 * tq + ((lane >> 3) & 1)] = a4[0];
      if (warp == 7) nbar_arrive(2, 256);
    } else if (b < 64 && warp == 7) nbar_arrive(2, 256);
    if (b < 64 && warp < 7) {
      uint4 v;
      const unsigned* pf = g_xf + (tid >> 1) * 512 + 8 * ob + 4 * (tid & 1);
      const int col = 16 * (ob >> 1) + 4 * (ob & 1) + ((tid >> 1) & 3) + 8 * (tid & 1);
      bf16* po = out + col;
      PINL(po); PINL(pf);
      spin_until(tpub + DLY7);
      POLL { v = ldx16(pf); RETRY(X16(v)) }
      float f[4] = {u2f(v.x), u2f(v.y), u2f(v.z), u2f(v.w)};
      tred<2>(f, lane, 16); tred<1>(f, lane, 8);
      f[0] += __shfl_xor_sync(~0u, f[0], 4); f[0] += __shfl_xor_sync(~0u, f[0], 2);
      if (!(lane & 6)) s_sm[352 + warp * 8 + 4 * (lane & 1) + (lane >> 3)] = f[0];
      nbar(2, 256);
      if (tid < 8) {
        const float* q = s_sm + 352 + tid;
        const float t = ((q[0] + q[8]) + (q[16] + q[24])) + ((q[32] + q[40]) + q[48]);
        *po = __float2bfloat16(s_sm[416 + (col & 15)] + bfr(gbv * bfr(t)));
        if (b == 0 && tid == 0) stx4(&g_epoch, epoch + 1);
      }
    }
  }
}

__global__ void __cluster_dims__(2, 1, 1) __launch_bounds__(384, 1)
fused_kernel(const bf16* __restrict__ x, const bf16* __restrict__ cvec, const bf16* __restrict__ w_mod, bf16* __restrict__ out,
             Scratch* __restrict__ scr, const __grid_constant__ TMaps tms) {
  extern __shared__ __align__(1024) unsigned char smem[];
  const int tid = threadIdx.x, warp = __shfl_sync(~0u, tid >> 5, 0), lane = tid & 31;
  const int b = blockIdx.x, rk = b & 1, pr = b >> 1, hd = b >> 2;
  uint32_t sb = s2u(smem), bar0 = sb + OFF_BAR;

  unsigned gt_start;
  asm volatile("mov.u32 %0, %%globaltimer_lo;" : "=r"(gt_start));
  const int g = lane >> 2, tq = lane & 3;
  const int arow = 64 * (b >> 4) + ((tid & 255) >> 3);
  uint4 wm0, wm1;
  uint32_t c0w, c1w;
  if (warp < 8) {
    const bf16* wa = w_mod + (size_t)arow * 3072 + (lane & 4) * 128 + 32 * (b & 15) + 8 * tq;
    wm0 = ldx16(wa); wm1 = ldx16(wa + 32 * 3072);
    c0w = ldc4(cvec + (arow & ~1)); c1w = ldc4(cvec + (arow & ~1) + 32);
  }
  const unsigned t_off = gt_start + RATE_T0;
  if (warp == 11) {
    if (lane == 0) {
#pragma unroll
      for (int i = 0; i < FB_KV; i++) { BAR_INIT(i, 1); BAR_ARM(i, 16384); }
    }
    __syncwarp();
    asm volatile("fence.mbarrier_init.release.cluster;" ::: "memory");
    asm volatile("barrier.cluster.arrive.relaxed.aligned;" ::: "memory");
#pragma unroll 1
    for (int i = 0; i < FB_KV; i++) {
      if (i >= HWIN) mbar_wait(bar0 + 8 * (i - HWIN));
      wait_until(t_off + (i < 4 ? 2 * i + ((b >> 1) & 1) : 4 * i - 8 + (b & 3)) * (RATE_H / 4));
      if (lane == 0) {
        if (i < 4) tma3d(sb + OFF_WQ + i * 16384, &tms.m[0], bar0 + 8 * i, 0, i * 128, 2 * hd + rk);
        else tma3d(sb + OFF_WQ + i * 16384, &tms.m[1], bar0 + 8 * i, 0, (b & 3) * 128 + (i - 4) * 64, 2 * hd);
      }
      __syncwarp();
    }
  }
  if (warp == 10) {
    const uint4 xa = ldc16(x + 16 * lane), xb = ldc16(x + 16 * lane + 8);
    const unsigned ep = ldc4(&g_epoch);
    float xv[16] = {bflo(xa.x), bfhi(xa.x), bflo(xa.y), bfhi(xa.y), bflo(xa.z), bfhi(xa.z), bflo(xa.w), bfhi(xa.w),
                    bflo(xb.x), bfhi(xb.x), bflo(xb.y), bfhi(xb.y), bflo(xb.z), bfhi(xb.z), bflo(xb.w), bfhi(xb.w)};
    float s = 0;
#pragma unroll
    for (int i = 0; i < 16; i++) s += xv[i];
#pragma unroll
    for (int o = 16; o; o >>= 1) s += __shfl_xor_sync(~0u, s, o);
    const float mean = s * (1.f / 512.f);
    s = 0;
#pragma unroll
    for (int i = 0; i < 16; i++) { xv[i] -= mean; s += xv[i] * xv[i]; }
#pragma unroll
    for (int o = 16; o; o >>= 1) s += __shfl_xor_sync(~0u, s, o);
    const float rstd = rsqrtf(s * (1.f / 512.f) + 1e-5f);
    if ((lane >> 1) == (b & 15))
#pragma unroll
      for (int i = 0; i < 4; i++)
        *(float4*)(smem + OFF_SM + (256 + (lane & 1) * 16 + 4 * i) * 4) = make_float4(xv[4 * i] * rstd, xv[4 * i + 1] * rstd, xv[4 * i + 2] * rstd, xv[4 * i + 3] * rstd);
    if (lane == 0) *(volatile unsigned*)(smem + OFF_MASK + 8) = ep;
    nbar_arrive(1, 288);
  }
  if (warp >= 8) {
    asm volatile("setmaxnreg.dec.sync.aligned.u32 72;");
    if (tid == 288) {
#pragma unroll
      for (int q = FB_KV; q < FB_KV + 16; q++) { BAR_INIT(q, 1); BAR_ARM(q, 32768); }
    }
    if (tid == 320) {
#pragma unroll
      for (int q = 0; q <= 13 + NSLOT; q++) BAR_INIT(EB + q, q == 0 ? 4 : q < 5 ? 16 : q < 16 ? 12 : 6);
    }
    if (tid == 256) {
#pragma unroll
      for (int q = FB_MOD; q <= FB_D; q++) { BAR_INIT(q, 1); BAR_ARM(q, 16384); }
      BAR_INIT(QB, 9); BAR_ARM(QB, 1024);
#pragma unroll
      for (int q = 0; q < 7; q++) BAR_INIT(XB + q, q == 2 ? 256 : q == 5 || q == 3 ? 9 : 1);
      BAR_ARM(XB + 3, 1024);
      BAR_ARM(XB + 5, 1024 + 64 + 512);
      *(volatile unsigned long long*)(smem + OFF_MASK) = 0;
    }
    if (warp != 11) {
      __syncwarp();
      asm volatile("fence.mbarrier_init.release.cluster;" ::: "memory");
      __threadfence_block();
      asm volatile("barrier.cluster.arrive.relaxed.aligned;" ::: "memory");
    }
    if (warp == 11) {
      asm volatile("barrier.cluster.wait.acquire.aligned;" ::: "memory");
      const unsigned epoch = *(volatile unsigned*)(smem + OFF_MASK + 8), par = (epoch + 1) & 1;
      mbar_wait(bar0 + 8 * (FB_KV + 15));
      for (int it = 0; ldx4(scr->cnt + 96 + 32 * (b >> 6)) != (epoch + 1) * 64 && it < SPIN_MAX; it++) {}
      uint4 hh;
      POLL { hh = ldx16(g_ml + (b >> 2) * 64 + 2 * lane); RETRY(X16(hh)) }
      int mi = __float_as_int(fmaxf(u2f(hh.x), u2f(hh.z)));
      mi ^= (mi >> 31) & 0x7fffffff;
      mi = __reduce_max_sync(~0u, mi);
      mi ^= (mi >> 31) & 0x7fffffff;
      const float M = __int_as_float(mi);
      const uint32_t wp = pack2(ex2(u2f(hh.x) - M), ex2(u2f(hh.z) - M));
      float L = bflo(wp) * u2f(hh.y) + bfhi(wp) * u2f(hh.w);
#pragma unroll
      for (int o2 = 16; o2; o2 >>= 1) L += __shfl_xor_sync(~0u, L, o2);
      *(uint32_t*)(smem + OFF_RA + lane * 4) = wp;
      if (lane == 0) *(float*)(smem + OFF_RA + 128) = rcp(L);
      __syncwarp();
      if (lane == 0) BAR_ARRIVE(XB + 6);
    }
    if (warp == 10) {
      if (lane < 8) asm volatile("prefetch.tensormap [%0];" ::"l"(&tms.m[lane + 1]) : "memory");
      asm volatile("barrier.cluster.wait.acquire.aligned;" ::: "memory");
      const unsigned epoch = *(volatile unsigned*)(smem + OFF_MASK + 8);
#pragma unroll 1
      for (int e = 0; e < 2; e++) {
        for (int it = 0; ldx4(scr->cnt + (e ? 2 + rk : 1)) != (epoch + 1) * (e ? 64 : 128) && it < SPIN_MAX; it++) {}
        if (lane == 0) BAR_ARRIVE(XB + e);
      }
      mbar_wait(bar0 + 8 * (FB_KV + 14));
      unsigned long long m = 0;
#pragma unroll 1
      for (int it = 0; ~m && it < SPIN_MAX; it++) {
        m = ldx64(scr->cnt + 32 + 32 * (b >> 6)) ^ ((epoch & 1) ? ~0ull : 0ull);
        if (lane == 0) *(volatile unsigned long long*)(smem + OFF_MASK) = m;
      }
    }
    if (warp == 9) {
      asm volatile("barrier.cluster.wait.acquire.aligned;" ::: "memory");
      const unsigned epoch = *(volatile unsigned*)(smem + OFF_MASK + 8);
      const unsigned par = (epoch + 1) & 1, inv = par ^ 1;
      const uint4 inv4 = make_uint4(inv, inv, inv, inv);
      mbar_wait(bar0 + 8 * FB_KV);
#pragma unroll 2
      for (int k = 0; k < 8; k++) {
        const uint32_t cp = ldc4(cvec + 2 * (lane + 32 * k));
        *(uint32_t*)(smem + OFF_SILU + (lane + 32 * k) * 4) = pack2(silu_bf(bflo(cp)), silu_bf(bfhi(cp)));
      }
      __syncwarp();
      mbar_wait(bar0 + 8 * FB_MOD);
      const uint32_t ab = sb + OFF_MOD + (8 * (lane >> 4) + (lane & 7)) * 32 + ((((lane >> 3) ^ (lane >> 2)) & 1) << 4);
      float d[4][4] = {};
#pragma unroll 2
      for (int s4 = 0; s4 < 8; s4++)
#pragma unroll
        for (int s = 0; s < 4; s++) {
          uint32_t a[4];
          const uint32_t* ps = (const uint32_t*)(smem + OFF_SILU) + 32 * s4 + 8 * s + tq;
          ldsm_t(a, ab + (4 * s4 + s) * 512); mma16(d[s], a, ps[0], ps[4]);
        }
      const float t = (tq & 1) ? (d[0][2] + d[1][2]) + (d[2][2] + d[3][2]) : (d[0][0] + d[1][0]) + (d[2][0] + d[3][0]);
      if (tq < 2) stx4(g_xm + b * 16 + 2 * (g & 6) + 2 * tq + (g & 1), fbits(bfr(t)));
      __syncwarp();
      if (lane == 0) CNT_ADD(6);
      mbar_wait(bar0 + 8 * (FB_KV + 8));
      if (lane < 16) stx16(g_xc + (b >> 2) * 256 + (lane >> 1) * 32 + (b & 3) * 8 + (lane & 1) * 4, inv4);
      if (lane < 8) stx16(g_xao + (b >> 5) * 1024 + (b & 15) * 64 + (lane & 4) * 8 + (b & 16) + (lane & 3) * 4, inv4);
      if (b < 112)
#pragma unroll 1
        for (int k = 0; k < 4; k++) stx16(g_xf + b * 512 + (lane + 32 * k) * 4, inv4);
      nbar_arrive(2, 288);
      for (int it = 0; ldx4(scr->cnt + 6) != (epoch + 1) * 128 && it < SPIN_MAX; it++) __nanosleep(100);
      {
        uint4 sv[2], cb[2];
        unsigned ga, gb;
        POLL {
#pragma unroll
          for (int k = 0; k < 2; k++) { sv[k] = ldx16(g_xm + 512 + 256 * rk + 4 * (lane + 32 * k)); cb[k] = ldx16(g_xm + 1024 + 256 * rk + 4 * (lane + 32 * k)); }
          ga = ldx4(g_xm + (b & 15) * 32 + lane); gb = ldx4(g_xm + 1536 + 256 * rk + 8 * (pr & 31) + (lane & 7));
          RETRY(X16(sv[0]) | X16(sv[1]) | X16(cb[0]) | X16(cb[1]) | lop_x3(ga, gb, par))
        }
#pragma unroll
        for (int k = 0; k < 2; k++) {
          const float c0 = bfr(1.f + bfhi(cb[k].x)), c1 = bfr(1.f + bfhi(cb[k].y)), c2 = bfr(1.f + bfhi(cb[k].z)), c3 = bfr(1.f + bfhi(cb[k].w));
          *(float4*)(smem + OFF_CO + (lane + 32 * k) * 16) = make_float4(c0, c1, c2, c3);
          uint2* pb = (uint2*)(smem + OFF_BP) + lane + 32 * k;
          pb[0] = make_uint2(pack2(c0, c1), pack2(c2, c3));
          pb[64] = make_uint2(__byte_perm(sv[k].x, sv[k].y, 0x7632), __byte_perm(sv[k].z, sv[k].w, 0x7632));
        }
        *(float*)(smem + OFF_CO + 1024 + lane * 4) = bfhi(ga);
        *(float*)(smem + OFF_CO + 1152 + lane * 4) = bfhi(gb);
      }
      __syncwarp();
      if (lane == 0) BAR_ARRIVE(XB + 4);
    }
    if (warp == 8) {
      const unsigned stag = ((pr * SMUL) & 63) * RATE_NS >> 6;
      unsigned tnext = t_off + 4 * RATE_H;
      asm volatile("barrier.cluster.wait.acquire.aligned;" ::: "memory");
#pragma unroll 1
      for (int k = 0; k < 24; k++) {
        const int code = (k < 12 ? ORDER0 >> (5 * k) : ORDER1 >> (5 * (k - 12))) & 31;
        const bool kv = code < 16;
        const int n = code, w = code - 16;
        if (!kv && w >= 5 && b >= 112) break;
        if (kv) mbar_wait(bar0 + 8 * (FB_KV + n - (n < 6 ? EWIN : KVWIN)));
        if (k >= TAIL_K) mbar_wait(bar0 + 8 * (FB_KV + (int)((ORDER1 >> (5 * (k - 12 - ((WINS >> (4 * (k - TAIL_K))) & 15)))) & 31)));
        const int e = kv ? (n == 3 ? 2 : n == 5 ? 1 : n) : w == 0 ? 0 : w < 5 ? 16 + ((w - 1) >> 1) : w == 7 ? 19 : 18;
        if (e != 1 && k) mbar_wait(bar0 + 8 * (EB + e));
        wait_until(tnext + stag);
        tnext += k > TAIL_K ? RATE_TL : k < 4 ? RATE_E : RATE_NS;
        if (lane == 0) {
          if (kv)
            asm volatile("cp.async.bulk.tensor.3d.shared::cluster.global.mbarrier::complete_tx::bytes.multicast::cluster.L2::cache_hint [%0], [%1, {%3, %4, %5}], [%2], %6, %7;"
                         ::"r"(sb + (n % NSLOT) * SLOT + rk * 16384), "l"(&tms.m[2]), "r"(bar0 + 8 * (FB_KV + n)), "r"(0), "r"(((n >> 1) * 64 + pr) * 64),
                           "r"(4 * (n & 1) + 2 * rk), "h"((unsigned short)3), "l"(stream_policy()) : "memory");
          else {
            tma3d(sb + (w == 0 ? OFF_MOD : w < 5 ? OFF_UV + (w - 1) * 16384 : w == 5 ? OFF_G : w == 6 ? OFF_U : OFF_D),
                  &tms.m[w == 0 ? 3 : w < 3 ? 4 : w < 5 ? 5 : w + 1], bar0 + 8 * (FB_MOD + w),
                  w == 0 ? 1024 + b * 16 : w < 3 || w == 7 ? 0 : w < 5 ? (pr & 7) * 64 : pr * 32, w == 7 ? b * 16 : w == 1 || w == 2 ? (b & 3) * 128 + (w - 1) * 64 : 0,
                  w == 1 || w == 2 ? 2 * hd : w == 3 || w == 4 ? (b >> 4) * 4 + 2 * rk + w - 3 : w == 5 || w == 6 ? rk : 0);
          }
        }
        __syncwarp();
      }
    }
    if (b < 112) {
      const int mt = warp & 1, dd = (warp >> 1) & 1;
      mbar_wait(bar0 + 8 * (XB + 4));
      const uint32_t ab = sb + (mt ? OFF_U : OFF_G) + (8 * (lane >> 4) + (lane & 7)) * 64 + (((2 * dd + ((lane >> 3) & 1)) ^ ((lane >> 1) & 3)) << 4);
      uint32_t base;
      asm volatile("mapa.shared::cluster.u32 %0, %1, %2;" : "=r"(base) : "r"(sb), "r"(dd));
      uint2 bb[16];
#pragma unroll
      for (int s = 0; s < 16; s++) bb[s] = *(const uint2*)(smem + OFF_BP + (g & 1) * 512 + (4 * s + tq) * 8);
      mbar_wait(bar0 + 8 * (FB_G + mt));
      float e[4][4] = {};
#pragma unroll
      for (int s = 0; s < 16; s++) { uint32_t a[4]; ldsm_t(a, ab + s * 1024); mma16(e[s & 3], a, bb[s].x, bb[s].y); }
      float r[4];
#pragma unroll
      for (int i = 0; i < 4; i++) r[i] = (e[0][i] + e[1][i]) + (e[2][i] + e[3][i]);
      if (tq < 2) st_async2(base + OFF_R4 + (8 * mt + g) * 176 + (10 * rk + 8 + tq) * 8, base + OFF_BAR + 8 * (XB + 5), tq ? r[1] : r[0], tq ? r[3] : r[2]);
    }
    return;
  }

  float* s_sm = (float*)(smem + OFF_SM);
  unsigned par, epoch;
  uint32_t rsb;
  {
    float* s_r4 = (float*)(smem + OFF_R4);
    asm volatile("barrier.cluster.arrive.relaxed.aligned;" ::: "memory");
    asm volatile("mapa.shared::cluster.u32 %0, %1, %2;" : "=r"(rsb) : "r"(sb), "r"(rk ^ 1));
    const float c0 = (arow & 1) ? bfhi(c0w) : bflo(c0w), c1 = (arow & 1) ? bfhi(c1w) : bflo(c1w);
    float acc[8] = {0, 0, 0, 0, 0, 0, 0, 0};
    fma8(acc, wm0, silu_bf(c0)); fma8(acc, wm1, silu_bf(c1));
    tred<4>(acc, lane, 8); tred<2>(acc, lane, 16);
    *(float2*)(s_r4 + warp * 64 + 8 * (lane & 7) + ((lane >> 1) & 4) + ((lane >> 3) & 2)) = make_float2(acc[0], acc[1]);
    nbar(1, 288);
    epoch = *(volatile unsigned*)(smem + OFF_MASK + 8);
    par = (epoch + 1) & 1;
    if (warp == 0) {
      float t = 0.f, ca = b < 16 ? 1.f : 0.f;
#pragma unroll
      for (int w = 0; w < 8; w++) { t += s_r4[w * 64 + lane]; ca += s_r4[w * 64 + 32 + lane]; }
      t += ca * s_sm[256 + lane];
      const float nb = __shfl_down_sync(~0u, t, 1);
      const uint32_t w0 = lane < 8 ? pack2t(t, nb, par) : pack2(t, nb);
      const uint32_t w1 = __shfl_down_sync(~0u, w0, 8), w2 = __shfl_down_sync(~0u, w0, 16), w3 = __shfl_down_sync(~0u, w0, 24);
      if (lane < 8 && !(lane & 1)) stx16(g_h + (b >> 5) * 512 + (b & 15) * 32 + (b & 16) + 2 * lane, make_uint4(w0, w1, w2, w3));
      __syncwarp();
      if (lane == 0) CNT_ADD(1);
    }
  }
  asm volatile("barrier.cluster.wait.acquire.aligned;" ::: "memory");
  {
    uint32_t a[4][4][4];
    mbar_wait(bar0 + 8 * (warp >> 1));
    const uint32_t ab = sb + OFF_WQ + (64 * warp + 8 * (lane >> 4) + (lane & 7)) * 128;
#pragma unroll
    for (int s = 0; s < 4; s++)
#pragma unroll
      for (int mt = 0; mt < 4; mt++) ldsm_t(a[s][mt], ab + s * 2048 + (((2 * mt + ((lane >> 3) & 1)) ^ (lane & 7)) << 4));
    uint4 v0, v1;
    const unsigned* ph = g_h + (g >> 1) * 512 + 64 * warp + 4 * (lane & 7);
    uint32_t off = OFF_B + warp * 272 + (32 * rk + 8 * tq + (lane & 4)) * 4;
    PIN(off); PINL(ph);
    mbar_wait(bar0 + 8 * XB);
    POLL { v0 = ldx16(ph); v1 = ldx16(ph + 32); RETRY(lop_x3(v0.x, v1.x, par)) }
    float d[4][4] = {};
#pragma unroll
    for (int mt = 0; mt < 4; mt++) {
      mma16(d[mt], a[0][mt], v0.x, v0.y); mma16(d[mt], a[1][mt], v0.z, v0.w);
      mma16(d[mt], a[2][mt], v1.x, v1.y); mma16(d[mt], a[3][mt], v1.z, v1.w);
    }
    float r[8];
#pragma unroll
    for (int mt = 0; mt < 4; mt++) { r[2 * mt] = d[mt][0] + d[mt][1]; r[2 * mt + 1] = d[mt][2] + d[mt][3]; }
    tred<4>(r, lane, 2); tred<2>(r, lane, 1);
    const float rc = __shfl_xor_sync(~0u, (lane & 4) ? r[0] : r[1], 4);
    const uint32_t wd = (lane & 4) ? pack2(rc, r[1]) : pack2(r[0], rc);
    const uint32_t w1 = __shfl_down_sync(~0u, wd, 8), w2 = __shfl_down_sync(~0u, wd, 16), w3 = __shfl_down_sync(~0u, wd, 24);
    asm volatile("{.reg .pred p; setp.lt.s32 p, %7, 8; @p st.shared.v4.b32 [%0], {%2,%3,%4,%5};\n"
                 "@p st.async.shared::cluster.mbarrier::complete_tx::bytes.v4.b32 [%1], {%2,%3,%4,%5}, [%6];}"
                 ::"r"(sb + off), "r"(rsb + off), "r"(wd), "r"(w1), "r"(w2), "r"(w3), "r"(rsb + OFF_BAR + 8 * QB), "r"(lane) : "memory");
    __syncwarp();
    arrive2(bar0 + 8 * QB, 0, lane == 0, false);
    arrive2(bar0 + 8 * (EB + 2), rsb + OFF_BAR + 8 * (EB + 2), lane == 0, lane == 0);
  }
  {
    uint32_t a[8][4];
    uint32_t a_bq = sb + OFF_B + (lane & 7) * 272 + (lane >> 3) * 16;
    unsigned* p_qa = g_qa + b * 64 + 8 * warp + 4 * lane;
    PIN(a_bq); PINL(p_qa);
    mbar_wait(bar0 + 8 * (FB_UK + (warp >> 2)));
    const uint32_t ab = sb + OFF_WUK + (warp >> 2) * 16384 + (16 * (warp & 3) + (lane & 15)) * 128;
#pragma unroll
    for (int s = 0; s < 8; s++) ldsm(a[s], ab + (s >> 2) * 8192 + (((2 * (s & 3) + (lane >> 4)) ^ (lane & 7)) << 4));
    mbar_wait(bar0 + 8 * QB);
    float d[4][4] = {};
#pragma unroll
    for (int y = 0; y < 4; y++) {
      uint32_t bq[4];
      ldsm(bq, a_bq + 64 * y);
      mma16(d[(2 * y) & 3], a[2 * y], bq[0], bq[1]); mma16(d[(2 * y + 1) & 3], a[2 * y + 1], bq[2], bq[3]);
    }
    float r[2] = {((d[0][0] + d[0][1]) + (d[1][0] + d[1][1])) + ((d[2][0] + d[2][1]) + (d[3][0] + d[3][1])),
                  ((d[0][2] + d[0][3]) + (d[1][2] + d[1][3])) + ((d[2][2] + d[2][3]) + (d[3][2] + d[3][3]))};
    tred<1>(r, lane, 1);
    r[0] += __shfl_xor_sync(~0u, r[0], 2);
    const float nb = __shfl_xor_sync(~0u, r[0], 4);
    const uint32_t w0 = lane < 8 ? pack2t(r[0], nb, par) : pack2(r[0], nb);
    const uint32_t w1 = __shfl_down_sync(~0u, w0, 8), w2 = __shfl_down_sync(~0u, w0, 16), w3 = __shfl_down_sync(~0u, w0, 24);
    if (lane < 2) stx16(p_qa, make_uint4(w0, w1, w2, w3));
    arrive2(bar0 + 8 * (EB + 4), rsb + OFF_BAR + 8 * (EB + 4), lane == 0, lane == 0);
  }
  {
    if (warp) nbar_arrive(3, 256); else { nbar(3, 256); if (lane == 0) CNT_ADD(2 + (b >> 6)); }
    asm volatile("setmaxnreg.inc.sync.aligned.u32 216;");
    const unsigned* pq = g_qa + rk * 4096 + tid * 4;
    uint32_t a_q = sb + OFF_Q + ((tid & 63) >> 3) * 2048 + (tid >> 6) * 128 + (((tid & 7) ^ (tid >> 6)) << 4);
    PINL(pq); PIN(a_q);
    mbar_wait(bar0 + 8 * (XB + 1));
    uint4 v[4];
    POLL {
#pragma unroll
      for (int k = 0; k < 4; k++) v[k] = ldx16(pq + 1024 * k);
      RETRY(lop_x3(v[0].x, v[1].x, par) | lop_x3(v[2].x, v[3].x, par))
    }
#pragma unroll
    for (int k = 0; k < 4; k++)
      asm volatile("st.shared.v4.b32 [%0], {%1,%2,%3,%4};" ::"r"((a_q + k * 512) ^ ((k & 1) << 6)), "r"(v[k].x), "r"(v[k].y), "r"(v[k].z), "r"(v[k].w) : "memory");
    if (warp >= 4) nbar_arrive(1, 256); else nbar(1, 256);
  }
  sb = __shfl_sync(~0u, sb, 0); bar0 = sb + OFF_BAR;
  if (warp < 4) {
    uint32_t qf[32][4];
#pragma unroll
    for (int s = 0; s < 32; s++) ldsm(qf[s], sb + OFF_Q + (s >> 2) * 2048 + (lane & 15) * 128 + (((2 * (s & 3) + (lane >> 4)) ^ (lane & 7)) << 4));
    float l0 = 0.f, l1 = 0.f, m0 = -1e30f, m1 = -1e30f;
    const float sc = 0.08838834764831845f * 1.4426950408889634f;
    const uint32_t kofs = (16 * warp + 8 * (lane >> 4) + (lane & 7)) * 128 + ((((lane >> 3) & 1) ^ (lane & 7)) << 4);
    uint32_t st = sb;
#pragma unroll 1
    for (int t = 0; t < 8; t++) {
      float sa[4][4] = {};
#pragma unroll
      for (int hf = 0; hf < 2; hf++) {
        const int n = 2 * t + hf;
        mbar_wait(bar0 + 8 * (FB_KV + n));
        uint32_t kf[16][4];
#pragma unroll
        for (int y = 0; y < 16; y++) ldsm(kf[y], st + (y >> 2) * 8192 + (kofs ^ ((y & 3) << 5)));
#pragma unroll
        for (int y = 0; y < 16; y++) {
          mma16(sa[(2 * y) & 3], qf[16 * hf + y], kf[y][0], kf[y][1]); mma16(sa[((2 * y) & 3) + 1], qf[16 * hf + y], kf[y][2], kf[y][3]);
        }
        __syncwarp();
        arrive2(bar0 + 8 * (EB + NSLOT + n), rsb + OFF_BAR + 8 * (EB + NSLOT + n), lane == 0 && n < 14, lane == 0 && n < 16 - NSLOT);
        if (hf == 0) arrive2(bar0 + 8 * EB, 0, lane == 0 && t == 0, false);
        st = st + SLOT == sb + NSLOT * SLOT ? sb : st + SLOT;
      }
#pragma unroll
      for (int i = 0; i < 4; i++) { sa[0][i] = (sa[0][i] + sa[2][i]) * sc; sa[1][i] = (sa[1][i] + sa[3][i]) * sc; }
      float cm[2] = {fmaxf(fmaxf(sa[0][0], sa[0][1]), fmaxf(sa[1][0], sa[1][1])), fmaxf(fmaxf(sa[0][2], sa[0][3]), fmaxf(sa[1][2], sa[1][3]))};
      tmax<1>(cm, lane, 1);
      cm[0] = fmaxf(cm[0], __shfl_xor_sync(~0u, cm[0], 2));
      float* pm = s_sm + (t & 1) * 64;
      if (tq < 2) pm[(g + 8 * tq) * 4 + warp] = cm[0];
      if (t >= 2) nbar(6 + (t & 1), 256); else nbar(3, 128);
      const float4 a0 = *(const float4*)(pm + g * 4), b0 = *(const float4*)(pm + g * 4 + 32);
      const float n0 = fmaxf(fmaxf(fmaxf(a0.x, a0.y), fmaxf(a0.z, a0.w)), m0), n1 = fmaxf(fmaxf(fmaxf(b0.x, b0.y), fmaxf(b0.z, b0.w)), m1);
      uint32_t pk[4];
#pragma unroll
      for (int i = 0; i < 2; i++) { pk[2 * i] = pack2(ex2(sa[i][0] - n0), ex2(sa[i][1] - n0)); pk[2 * i + 1] = pack2(ex2(sa[i][2] - n1), ex2(sa[i][3] - n1)); }
      *(uint4*)(smem + OFF_P + (t & 1) * 2048 + tid * 16) = make_uint4(pk[0], pk[1], pk[2], pk[3]);
      const float al0 = ex2(m0 - n0), al1 = ex2(m1 - n1);
      if (tid < 32 && tq == 0) *(float2*)(s_sm + 192 + (t & 1) * 16 + 2 * g) = make_float2(al0, al1);
      nbar_arrive(4 + (t & 1), 256);
      m0 = n0; m1 = n1;
      l0 = l0 * al0 + (bflo(pk[0]) + bfhi(pk[0])) + (bflo(pk[2]) + bfhi(pk[2]));
      l1 = l1 * al1 + (bflo(pk[1]) + bfhi(pk[1])) + (bflo(pk[3]) + bfhi(pk[3]));
    }
    float lr[2] = {l0, l1};
    tred<1>(lr, lane, 1);
    lr[0] += __shfl_xor_sync(~0u, lr[0], 2);
    if (tq < 2) s_sm[128 + (g + 8 * tq) * 4 + warp] = lr[0];
    nbar(3, 128);
    if (warp == 0 && tq < 2) {
      const float4 a0 = *(const float4*)(s_sm + 128 + (g + 8 * tq) * 4);
      stx8(g_ml + (16 * rk + g + 8 * tq) * 64 + pr, make_uint2(fbits(tq ? m1 : m0), fbits((a0.x + a0.y) + (a0.z + a0.w))));
    }
    if (warp == 0) { __syncwarp(); if (lane == 0) CNT_ADD(96 + 32 * rk); }
    nbar(2, 288);
    if (tid == 0) asm volatile("red.relaxed.gpu.global.xor.b64 [%0], %1;" ::"l"(scr->cnt + 32 + 32 * rk), "l"(1ull << pr) : "memory");
  } else {
    float o[16][4] = {};
    const uint32_t vofs = (warp & 1) * 16384 + (lane & 15) * 128 + (((lane >> 4) ^ (lane & 7)) << 4);
    const int hf = (warp >> 1) & 1;
    uint32_t st = sb + hf * SLOT;
    auto pv = [&](const int t, auto np) {
      constexpr int npre = decltype(np)::value;
      uint32_t vf[4][8][4];
      const int n = 2 * t + hf;
      mbar_wait(bar0 + 8 * (FB_KV + n));
#pragma unroll
      for (int s = 0; s < npre; s++)
#pragma unroll
        for (int y = 0; y < 8; y++) ldsm_t(vf[s][y], st + (y >> 2) * 8192 + s * 2048 + (vofs ^ ((y & 3) << 5)));
      nbar(4 + (t & 1), 256);
      const float2 al = *(const float2*)(s_sm + 192 + (t & 1) * 16 + 2 * g);
      uint4 pf[4];
#pragma unroll
      for (int s = 0; s < 4; s++) pf[s] = *(const uint4*)(smem + OFF_P + (t & 1) * 2048 + s * 512 + lane * 16);
      if (t < 6) nbar_arrive(6 + (t & 1), 256);
#pragma unroll
      for (int s = npre; s < 4; s++)
#pragma unroll
        for (int y = 0; y < 8; y++) ldsm_t(vf[s][y], st + (y >> 2) * 8192 + s * 2048 + (vofs ^ ((y & 3) << 5)));
#pragma unroll
      for (int nt = 0; nt < 16; nt++) { o[nt][0] *= al.x; o[nt][1] *= al.x; o[nt][2] *= al.y; o[nt][3] *= al.y; }
#pragma unroll
      for (int s = 0; s < 4; s++) {
        const uint32_t pa[4] = {pf[s].x, pf[s].y, pf[s].z, pf[s].w};
#pragma unroll
        for (int y = 0; y < 8; y++) { mma16(o[2 * y], pa, vf[s][y][0], vf[s][y][1]); mma16(o[2 * y + 1], pa, vf[s][y][2], vf[s][y][3]); }
      }
      __syncwarp();
      arrive2(bar0 + 8 * (EB + NSLOT + n), rsb + OFF_BAR + 8 * (EB + NSLOT + n), lane == 0 && n < 14, lane == 0 && n < 16 - NSLOT);
      st = st + 2 * SLOT >= sb + NSLOT * SLOT ? st - (NSLOT - 2) * SLOT : st + 2 * SLOT;
    };
#pragma unroll 1
    for (int t = 0; t < 7; t++) pv(t, IC<NPRE0>());
    pv(7, IC<NPRE1>());
    uint4* po = g_xo + ((size_t)((16 * rk + (g & 6)) * 4 + warp - 4) * 64 + pr) * RS + (lane & 7);
    const bool odd = lane & 4;
#pragma unroll
    for (int e = 0; e < 2; e++)
#pragma unroll
      for (int j2 = 0; j2 < 2; j2++) {
        uint32_t c0[4], c1[4];
#pragma unroll
        for (int i = 0; i < 4; i++) {
          c0[i] = i ? pack2(o[8 * j2 + i][2 * e], o[8 * j2 + i][2 * e + 1]) : pack2t(o[8 * j2][2 * e], o[8 * j2][2 * e + 1], par);
          c1[i] = i ? pack2(o[8 * j2 + 4 + i][2 * e], o[8 * j2 + 4 + i][2 * e + 1]) : pack2t(o[8 * j2 + 4][2 * e], o[8 * j2 + 4][2 * e + 1], par);
          const uint32_t r = __shfl_xor_sync(~0u, odd ? c0[i] : c1[i], 4);
          if (odd) c0[i] = r; else c1[i] = r;
        }
        stx16(po + e * 8 * 4 * 64 * RS + 8 * j2, make_uint4(c0[0], c0[1], c0[2], c0[3]));
        stx16(po + (e * 8 + 1) * 4 * 64 * RS + 8 * j2, make_uint4(c1[0], c1[1], c1[2], c1[3]));
      }
    nbar_arrive(2, 288);
  }
  tail(smem, scr, x, out, par, epoch, warp);
}

static void launch(void* const* d_in, void* d_out) {
  static TMaps tms;
  static bool init = false;
  static void* scr = nullptr;
  if (!init) {
    void* fn = nullptr; cudaDriverEntryPointQueryResult qr;
    cudaGetDriverEntryPoint("cuTensorMapEncodeTiled", &fn, cudaEnableDefault, &qr);
    EncFn f = (EncFn)fn;
    const CUtensorMapSwizzle S32 = CU_TENSOR_MAP_SWIZZLE_32B, S64 = CU_TENSOR_MAP_SWIZZLE_64B, S128 = CU_TENSOR_MAP_SWIZZLE_128B;
    const CUtensorMapL2promotion P128 = CU_TENSOR_MAP_L2_PROMOTION_L2_128B, P256 = CU_TENSOR_MAP_L2_PROMOTION_L2_256B;
    enc3d(f, &tms.m[0], d_in[2], 64, 512, 64, 8192, 128, 64, 128, 1, S128, P128);
    enc3d(f, &tms.m[1], d_in[3], 64, 512, 64, 8192, 128, 64, 64, 2, S128, P256);
    enc3d(f, &tms.m[2], d_in[1], 64, SK, 8, 1024, 128, 64, 64, 2, S128, P256);
    enc3d(f, &tms.m[3], d_in[11], 3072, 256, 2, 6144, 256 * 6144, 16, 256, 2, S32, P128);
    enc3d(f, &tms.m[4], d_in[4], 64, 512, 64, 8192, 128, 64, 64, 2, S128, P256);
    enc3d(f, &tms.m[5], d_in[5], 512, 128, 32, 1024, 128 * 1024, 64, 128, 1, S128, P128);
    enc3d(f, &tms.m[6], d_in[7], 1792, 256, 2, 3584, 256 * 3584, 32, 256, 1, S64, P128);
    enc3d(f, &tms.m[7], d_in[8], 1792, 256, 2, 3584, 256 * 3584, 32, 256, 1, S64, P128);
    enc3d(f, &tms.m[8], d_in[9], 64, 1792, 8, 1024, 128, 64, 16, 8, S128, P256);
    cudaFuncSetAttribute(fused_kernel, cudaFuncAttributeMaxDynamicSharedMemorySize, SMEM_BYTES);
    cudaGetSymbolAddress(&scr, g_scr);
    init = true;
  }
  fused_kernel<<<NCTA, 384, SMEM_BYTES>>>((const bf16*)d_in[0], (const bf16*)d_in[10], (const bf16*)d_in[11], (bf16*)d_out, (Scratch*)scr, tms);
}

}

extern "C" void kernel_launch(void* const* d_in, const int* in_sizes, int n_in, void* d_out, int out_size) {
  static int big = -1;
  if (big < 0) big = v9::fits();
  if (big) v9::launch(d_in, d_out); else v8::launch(d_in, d_out);
}
```

```cpp
#include <cuda_runtime.h>
#include <cuda_bf16.h>
#include <cuda.h>
#include <stdint.h>
#include <stdio.h>
#include <stdlib.h>

typedef CUresult (*EncFn)(CUtensorMap*, CUtensorMapDataType, cuuint32_t, void*, const cuuint64_t*, const cuuint64_t*,
                          const cuuint32_t*, const cuuint32_t*, CUtensorMapInterleave, CUtensorMapSwizzle,
                          CUtensorMapL2promotion, CUtensorMapFloatOOBfill);

static void enc3d(EncFn fn, CUtensorMap* tm, void* p, uint64_t d0, uint64_t d1, uint64_t d2, uint64_t s1, uint64_t s2, uint32_t b0,
                  uint32_t b1, uint32_t b2, CUtensorMapSwizzle sw, CUtensorMapL2promotion pr) {
  cuuint64_t gd[3] = {d0, d1, d2}, gs[2] = {s1, s2};
  cuuint32_t bx[3] = {b0, b1, b2}, es[3] = {1, 1, 1};
  fn(tm, CU_TENSOR_MAP_DATA_TYPE_BFLOAT16, 3, p, gd, gs, bx, es, CU_TENSOR_MAP_INTERLEAVE_NONE, sw, pr, CU_TENSOR_MAP_FLOAT_OOB_FILL_NONE);
}

namespace v9 {
typedef __nv_bfloat16 bf16;
#define SK 32768
#define SPIN_MAX (1 << 20)
template <int N> struct IC { static constexpr int value = N; };

__device__ __forceinline__ uint32_t s2u(const void* p) { return (uint32_t)__cvta_generic_to_shared(p); }
__device__ __forceinline__ float bflo(uint32_t u) { return __uint_as_float(u << 16); }
__device__ __forceinline__ float bfhi(uint32_t u) { return __uint_as_float(u & 0xffff0000u); }
__device__ __forceinline__ float u2f(uint32_t u) { return __uint_as_float(u); }
__device__ __forceinline__ void fma8(float* acc, uint4 v, float s) {
  acc[0] += s * bflo(v.x); acc[1] += s * bfhi(v.x); acc[2] += s * bflo(v.y); acc[3] += s * bfhi(v.y);
  acc[4] += s * bflo(v.z); acc[5] += s * bfhi(v.z); acc[6] += s * bflo(v.w); acc[7] += s * bfhi(v.w);
}
__device__ __forceinline__ uint32_t pack2(float a, float b) {
  __nv_bfloat162 p = __floats2bfloat162_rn(a, b); return *(uint32_t*)&p;
}
__device__ __forceinline__ float bfr(float v) { return bfhi(pack2(v, v)); }
__device__ __forceinline__ float silu_bf(float c) { return bfr(__fdividef(c, 1.f + __expf(-c))); }
#define fbits(v) ((__float_as_uint(v) & ~1u) | par)
__device__ __forceinline__ uint32_t pack2t(float a, float b, unsigned par) {
  const uint32_t ua = ((__float_as_uint(a) + ((par ^ 1) << 16)) & 0xFFFE0000u) | (par << 16);
  return __byte_perm(ua, pack2(b, b), 0x7632);
}
__device__ __forceinline__ void nbar(int id, int n) { asm volatile("bar.sync %0, %1;" ::"r"(id), "r"(n) : "memory"); }
__device__ __forceinline__ void nbar_arrive(int id, int n) { asm volatile("bar.arrive %0, %1;" ::"r"(id), "r"(n) : "memory"); }
__device__ __forceinline__ uint4 ldc16(const void* p) {
  uint4 v; asm volatile("ld.relaxed.cta.global.v4.u32 {%0,%1,%2,%3}, [%4];" : "=r"(v.x), "=r"(v.y), "=r"(v.z), "=r"(v.w) : "l"(p) : "memory"); return v;
}
__device__ __forceinline__ unsigned ldc4(const void* p) {
  unsigned v; asm volatile("ld.relaxed.cta.global.u32 %0, [%1];" : "=r"(v) : "l"(p) : "memory"); return v;
}
__device__ __forceinline__ uint4 ldx16(const void* p) {
  uint4 v; asm volatile("ld.relaxed.gpu.global.v4.u32 {%0,%1,%2,%3}, [%4];" : "=r"(v.x), "=r"(v.y), "=r"(v.z), "=r"(v.w) : "l"(p) : "memory"); return v;
}
__device__ __forceinline__ unsigned ldx4(const void* p) {
  unsigned v; asm volatile("ld.relaxed.gpu.global.u32 %0, [%1];" : "=r"(v) : "l"(p) : "memory"); return v;
}
__device__ __forceinline__ unsigned long long ldx64(const void* p) {
  unsigned long long v; asm volatile("ld.relaxed.gpu.global.u64 %0, [%1];" : "=l"(v) : "l"(p) : "memory"); return v;
}
__device__ __forceinline__ void stx16(void* p, uint4 v) {
  asm volatile("st.relaxed.gpu.global.v4.u32 [%0], {%1,%2,%3,%4};" ::"l"(p), "r"(v.x), "r"(v.y), "r"(v.z), "r"(v.w) : "memory");
}
__device__ __forceinline__ void stx8(void* p, uint2 v) { asm volatile("st.relaxed.gpu.global.v2.u32 [%0], {%1,%2};" ::"l"(p), "r"(v.x), "r"(v.y) : "memory"); }
__device__ __forceinline__ void stx4(void* p, unsigned v) { asm volatile("st.relaxed.gpu.global.u32 [%0], %1;" ::"l"(p), "r"(v) : "memory"); }
__device__ __forceinline__ void pub4(void* p, unsigned v) { asm volatile("red.relaxed.gpu.global.xor.b32 [%0], %1;" ::"l"(p), "r"(v) : "memory"); }
__device__ __forceinline__ void pub8(void* p, unsigned lo, unsigned hi) {
  asm volatile("{.reg .b64 t; mov.b64 t, {%1, %2}; red.relaxed.gpu.global.xor.b64 [%0], t;}" ::"l"(p), "r"(lo), "r"(hi) : "memory");
}
__device__ __forceinline__ unsigned lop_x3(unsigned a, unsigned b, unsigned c) {
  unsigned d; asm("lop3.b32 %0, %1, %2, %3, 0x7E;" : "=r"(d) : "r"(a), "r"(b), "r"(c)); return d; }
__device__ __forceinline__ unsigned or3(unsigned a, unsigned b, unsigned c) {
  unsigned d; asm("lop3.b32 %0, %1, %2, %3, 0xFE;" : "=r"(d) : "r"(a), "r"(b), "r"(c)); return d; }
__device__ __forceinline__ unsigned and3(unsigned a, unsigned b, unsigned c) {
  unsigned d; asm("lop3.b32 %0, %1, %2, %3, 0x80;" : "=r"(d) : "r"(a), "r"(b), "r"(c)); return d; }
__device__ __forceinline__ unsigned dep16(const uint32_t* f) {
  unsigned d = 0;
#pragma unroll
  for (int i = 0; i < 8; i++) d = or3(d, f[8 * i], f[8 * i + 4]);
  return d;
}
__device__ __forceinline__ uint2 ldx8(const void* p) {
  uint2 v; asm volatile("{.reg .b64 t; ld.relaxed.gpu.global.b64 t, [%2]; mov.b64 {%0, %1}, t;}" : "=r"(v.x), "=r"(v.y) : "l"(p) : "memory"); return v;
}
__device__ __forceinline__ float lds4(uint32_t a) { float v; asm volatile("ld.shared.f32 %0, [%1];" : "=f"(v) : "r"(a) : "memory"); return v; }
__device__ __forceinline__ float shx(float v, int m) {
  float r; asm volatile("shfl.sync.bfly.b32 %0, %1, %2, 0x1f, 0xffffffff;" : "=f"(r) : "f"(v), "r"(m)); return r;
}
__device__ __forceinline__ uint32_t mbar_test(uint32_t bar, uint32_t ph) {
  uint32_t ok;
  asm volatile("{.reg .pred p; mbarrier.test_wait.parity.shared::cta.b64 p, [%1], %2; vote.sync.all.pred p, p, 0xffffffff; selp.u32 %0, 1, 0, p;}"
               : "=r"(ok) : "r"(bar), "r"(ph) : "memory");
  return ok;
}
#define X16(v) (lop_x3(v.x, v.y, par) | lop_x3(v.z, v.w, par))
#define RETRY(bad) if (!__any_sync(~0u, (bad) & 1) || ++it_ >= SPIN_MAX) break;
#define POLL _Pragma("unroll 1") for (int it_ = 0;;)
__device__ __forceinline__ void mbar_wait(uint32_t bar, uint32_t ph = 0) {
  asm volatile("{.reg .pred p; .reg .u32 n; mov.u32 n, 0;\n"
               "W%=: mbarrier.try_wait.parity.shared::cta.b64 p, [%0], %1; add.u32 n, n, 1; setp.lt.and.u32 p, n, 0x100000, !p; @p bra W%=;}"
               ::"r"(bar), "r"(ph) : "memory");
}
__device__ __forceinline__ float ex2(float v) { float r; asm("ex2.approx.ftz.f32 %0, %1;" : "=f"(r) : "f"(v)); return r; }
__device__ __forceinline__ float rcp(float v) { float r; asm("rcp.approx.ftz.f32 %0, %1;" : "=f"(r) : "f"(v)); return r; }
__device__ __forceinline__ void mma16(float* d, const uint32_t* a, uint32_t b0, uint32_t b1) {
  asm volatile("mma.sync.aligned.m16n8k16.row.col.f32.bf16.bf16.f32 {%0,%1,%2,%3}, {%4,%5,%6,%7}, {%8,%9}, {%0,%1,%2,%3};"
               : "+f"(d[0]), "+f"(d[1]), "+f"(d[2]), "+f"(d[3]) : "r"(a[0]), "r"(a[1]), "r"(a[2]), "r"(a[3]), "r"(b0), "r"(b1));
}
__device__ __forceinline__ void mma16c(float* d, const uint32_t* a, uint32_t b0, uint32_t b1, const float* c) {
  asm volatile("mma.sync.aligned.m16n8k16.row.col.f32.bf16.bf16.f32 {%0,%1,%2,%3}, {%4,%5,%6,%7}, {%8,%9}, {%10,%11,%12,%13};"
               : "=f"(d[0]), "=f"(d[1]), "=f"(d[2]), "=f"(d[3])
               : "r"(a[0]), "r"(a[1]), "r"(a[2]), "r"(a[3]), "r"(b0), "r"(b1), "f"(c[0]), "f"(c[1]), "f"(c[2]), "f"(c[3]));
}
__device__ __forceinline__ float4 lds16(uint32_t a) {
  float4 v; asm volatile("ld.shared.v4.f32 {%0,%1,%2,%3}, [%4];" : "=f"(v.x), "=f"(v.y), "=f"(v.z), "=f"(v.w) : "r"(a) : "memory"); return v;
}
__device__ __forceinline__ void sts4(uint32_t a, float v) { asm volatile("st.shared.f32 [%0], %1;" ::"r"(a), "f"(v) : "memory"); }
__device__ __forceinline__ void sts16(uint32_t a, uint4 v) {
  asm volatile("st.shared.v4.b32 [%0], {%1,%2,%3,%4};" ::"r"(a), "r"(v.x), "r"(v.y), "r"(v.z), "r"(v.w) : "memory");
}
__device__ __forceinline__ void ldsm_t(uint32_t* r, uint32_t a) {
  asm volatile("ldmatrix.sync.aligned.m8n8.x4.trans.shared.b16 {%0,%1,%2,%3}, [%4];" : "=r"(r[0]), "=r"(r[1]), "=r"(r[2]), "=r"(r[3]) : "r"(a) : "memory");
}
__device__ __forceinline__ void ldsm(uint32_t* r, uint32_t a) {
  asm volatile("ldmatrix.sync.aligned.m8n8.x4.shared.b16 {%0,%1,%2,%3}, [%4];" : "=r"(r[0]), "=r"(r[1]), "=r"(r[2]), "=r"(r[3]) : "r"(a) : "memory");
}
__device__ __forceinline__ uint32_t mapa(uint32_t a, uint32_t r) {
  uint32_t v; asm volatile("mapa.shared::cluster.u32 %0, %1, %2;" : "=r"(v) : "r"(a), "r"(r)); return v;
}
__device__ __forceinline__ unsigned long long mapg(uint32_t a, uint32_t r) {
  unsigned long long v;
  asm volatile("{.reg .u32 t; .reg .u64 u; mapa.shared::cluster.u32 t, %1, %2; cvt.u64.u32 u, t; cvta.shared::cluster.u64 %0, u;}" : "=l"(v) : "r"(a), "r"(r));
  return v;
}
template <int N>
__device__ __forceinline__ void tred(float* a, int lane, int m) {
  const bool hi = lane & m;
#pragma unroll
  for (int i = 0; i < N; i++) {
    float send = hi ? a[i] : a[i + N], keep = hi ? a[i + N] : a[i];
    a[i] = keep + __shfl_xor_sync(~0u, send, m);
  }
}
template <int N>
__device__ __forceinline__ void tmax(float* a, int lane, int m) {
  const bool hi = lane & m;
#pragma unroll
  for (int i = 0; i < N; i++) {
    float send = hi ? a[i] : a[i + N], keep = hi ? a[i + N] : a[i];
    a[i] = fmaxf(keep, __shfl_xor_sync(~0u, send, m));
  }
}
__device__ __forceinline__ void arrive_n(uint32_t bar, bool on, int cnt) {
  asm volatile("{.reg .pred p; setp.ne.s32 p, %1, 0; @p mbarrier.arrive.shared::cta.b64 _, [%0], %2;}" ::"r"(bar), "r"((int)on), "r"(cnt) : "memory");
}
__device__ __forceinline__ unsigned long long stream_policy() {
  unsigned long long p;
  asm volatile("createpolicy.fractional.L2::evict_first.b64 %0, 1.0;" : "=l"(p));
  return p;
}
__device__ __forceinline__ void tma3d(uint32_t dst, const CUtensorMap* tm, uint32_t bar, int c0, int c1, int c2) {
  asm volatile("cp.async.bulk.tensor.3d.shared::cluster.global.mbarrier::complete_tx::bytes.L2::cache_hint [%0], [%1, {%3, %4, %5}], [%2], %6;"
               ::"r"(dst), "l"(tm), "r"(bar), "r"(c0), "r"(c1), "r"(c2), "l"(stream_policy()) : "memory");
}
__device__ __forceinline__ void spin_until(unsigned t) { while ((int)((unsigned)clock() - t) < 0) {} }
__device__ __forceinline__ void wait_until(unsigned t) {
  unsigned now;
  do { asm volatile("mov.u32 %0, %%globaltimer_lo;" : "=r"(now)); } while ((int)(now - t) < 0);
}
__device__ __forceinline__ void sleep_until(unsigned t) {
  unsigned now;
#pragma unroll 1
  do {
    __nanosleep(200);
    asm volatile("mov.u32 %0, %%globaltimer_lo;" : "=r"(now));
  } while ((int)(now - t) < 0);
}
#define PIN(x) asm volatile("" : "+r"(x))
#define PINL(x) asm volatile("" : "+l"(x))
#define BAR_ARRIVE(i) asm volatile("mbarrier.arrive.shared::cta.b64 _, [%0];" ::"r"(bar0 + 8 * (i)) : "memory")
#define LANE0(op, p, c, v) asm volatile("{.reg .pred q; setp.eq.s32 q, %2, 0; @q " op " [%0], %1;}" ::"l"((p) + lane), c(v), "r"(lane) : "memory")
#define CNT_ADD(c) LANE0("red.relaxed.gpu.global.add.u32", scr->cnt + (c), "r", 1)
#define BAR_INIT(i, cnt) asm volatile("mbarrier.init.shared::cta.b64 [%0], %1;" ::"r"(bar0 + 8 * (i)), "r"(cnt) : "memory")
#define BAR_ARM(i, bytes) asm volatile("mbarrier.arrive.expect_tx.shared::cta.b64 _, [%0], %1;" ::"r"(bar0 + 8 * (i)), "r"(bytes) : "memory")
struct TMaps { CUtensorMap m[9]; };

#define NCTA9 120
#define TAU 20
#define NSL 100
#define NPE 1
#define QN 4
#define FDLY 60
#define VJ 1
#define NPO 3
#define VDLY 150
#define O_Q 131072
#define O_LZ 163840
#define O_CTX 196608
#define O_HZ 198656
#define O_HW 200704
#define O_X 201728
#define O_P 218112
#define O_B 222208
#define O_R 224512
#define O_SILU 228608
#define O_SM 229632
#define O_BAR 231424
#define O_EP (O_BAR + 256)
#define O_DBG (O_EP + 16)
#define SMEM9 (O_DBG + 144)
#define B_FULL 0
#define B_FM 8
#define B_EMPTY 10
#define B_LZ 18
#define B_Q2 19
#define B_H 20
#define B_QF 21
#define B_TAB 22
#define B_W 23
#define B_ST 24
#define B_HZ 25
#define B_WZ 26
#define B_G 27
#define B_G2 28
enum { T_WQ, T_WUK, T_KV, T_MOD, T_UV, T_WO, T_GU, T_DN = 8 };
#define NBIG 40
struct Sched { unsigned zero, dth; uint2 r[3][8]; unsigned nr[3], nt[3], dt, t4, d4, d6, wt, pad; };

struct __align__(128) Scratch {
  unsigned cnt[8 * 32];
  uint2 rec[32 * 4 * 8 * 64];
  uint2 hdr[32 * 16];
  unsigned h[8 * 256];
  uint4 qa[2048];
  unsigned xao[8 * 512];
  unsigned xab[8 * 256];
  unsigned xm[2048];
};
__device__ Scratch g_scr;
#define SMEM_BASE 1024u
#define DSC ((SMEM_BASE >> 4) | (1u << 16))
#define HI128 (64u | (1u << 30))
#define HI64 (32u | (2u << 30))
template <int TA, int TB, unsigned HIA, unsigned HIB>
__device__ __forceinline__ void wgmma32(float* d, uint32_t da, uint32_t db, int acc) {
  asm volatile("{.reg .pred p; .reg .b64 da, db; setp.ne.b32 p, %18, 0; mov.b64 da, {%16, %21}; mov.b64 db, {%17, %22};\n"
               "wgmma.mma_async.sync.aligned.m64n32k16.f32.bf16.bf16 "
               "{%0,%1,%2,%3,%4,%5,%6,%7,%8,%9,%10,%11,%12,%13,%14,%15}, da, db, p, 1, 1, %19, %20;}"
               : "+f"(d[0]), "+f"(d[1]), "+f"(d[2]), "+f"(d[3]), "+f"(d[4]), "+f"(d[5]), "+f"(d[6]), "+f"(d[7]),
                 "+f"(d[8]), "+f"(d[9]), "+f"(d[10]), "+f"(d[11]), "+f"(d[12]), "+f"(d[13]), "+f"(d[14]), "+f"(d[15])
               : "r"(da), "r"(db), "r"(acc), "n"(TA), "n"(TB), "n"(HIA), "n"(HIB));
}
__device__ __forceinline__ void wgmma32r(float* d, const uint32_t* a, uint32_t db) {
  asm volatile("{.reg .b64 db; mov.b64 db, {%20, %21};\n"
               "wgmma.mma_async.sync.aligned.m64n32k16.f32.bf16.bf16 "
               "{%0,%1,%2,%3,%4,%5,%6,%7,%8,%9,%10,%11,%12,%13,%14,%15}, {%16,%17,%18,%19}, db, 1, 1, 1, 1;}"
               : "+f"(d[0]), "+f"(d[1]), "+f"(d[2]), "+f"(d[3]), "+f"(d[4]), "+f"(d[5]), "+f"(d[6]), "+f"(d[7]),
                 "+f"(d[8]), "+f"(d[9]), "+f"(d[10]), "+f"(d[11]), "+f"(d[12]), "+f"(d[13]), "+f"(d[14]), "+f"(d[15])
               : "r"(a[0]), "r"(a[1]), "r"(a[2]), "r"(a[3]), "r"(db), "n"(HI64));
}
template <int N> __device__ __forceinline__ void wg_wait(float* a) {
  asm volatile("wgmma.wait_group.sync.aligned %16;"
               : "+f"(a[0]), "+f"(a[1]), "+f"(a[2]), "+f"(a[3]), "+f"(a[4]), "+f"(a[5]), "+f"(a[6]), "+f"(a[7]), "+f"(a[8]), "+f"(a[9]), "+f"(a[10]),
                 "+f"(a[11]), "+f"(a[12]), "+f"(a[13]), "+f"(a[14]), "+f"(a[15]) : "n"(N) : "memory");
}
__device__ __forceinline__ void send32(uint32_t a, uint32_t bar, float v, int lane) {
  const uint32_t w = pack2(v, __shfl_down_sync(~0u, v, 1));
  const int s = 2 * (lane & 3);
  asm volatile("{.reg .pred p; setp.eq.s32 p, %6, 0; @p st.async.shared::cluster.mbarrier::complete_tx::bytes.v4.b32 [%0], {%1,%2,%3,%4}, [%5];}"
               ::"r"(a), "r"(__shfl_sync(~0u, w, s)), "r"(__shfl_sync(~0u, w, s + 8)), "r"(__shfl_sync(~0u, w, s + 16)), "r"(__shfl_sync(~0u, w, s + 24)),
                 "r"(bar), "r"(lane & 12) : "memory");
}
__device__ __forceinline__ float sum8(uint32_t a) {
  const float4 p = lds16(a), q = lds16(a + 1024);
  return ((p.x + p.y) + (p.z + p.w)) + ((q.x + q.y) + (q.z + q.w));
}
__device__ __forceinline__ int posof(int c) { return (c & ~14) + 2 * (c & 6) + ((c >> 2) & 2); }

__global__ void __cluster_dims__(8, 1, 1) __launch_bounds__(384, 1)
fused_kernel(const bf16* __restrict__ x, const bf16* __restrict__ cvec, const bf16* __restrict__ w_mod, bf16* __restrict__ out,
             Scratch* __restrict__ scr, const __grid_constant__ Sched sch, const __grid_constant__ TMaps tms) {
  extern __shared__ __align__(1024) unsigned char smem[];
  const int tid = threadIdx.x, warp = __shfl_sync(~0u, tid >> 5, 0), lane = tid & 31;
  const int b = blockIdx.x, cl = b >> 3, rn = b & 7, rk = b & 1, hd = b >> 1, f = b - 64;
  const bool isA = b < 64;
  uint32_t sb = s2u(smem), bar0 = sb + O_BAR;
  unsigned gt_start;
  asm volatile("mov.u32 %0, %%globaltimer_lo;" : "=r"(gt_start));
  const int g = lane >> 2, tq = lane & 3;
  const int arow = 64 * rn + ((tid & 255) >> 4);
  uint4 wm[4];
  uint32_t cw, xw;
  if (warp < 8 && isA) {
    const bf16* wa = w_mod + (size_t)arow * 3072 + (lane & 8) * 64 + 64 * cl + 8 * (lane & 7);
#pragma unroll
    for (int i = 0; i < 4; i++) wm[i] = ldx16(wa + i * 16 * 3072);
    cw = ldc4(cvec + (arow & ~1) + 16 * tq);
    if (warp < 2) xw = ldc4(x + 64 * cl + (tid & 62));
  }
  if (warp == 11) {
    if (lane == 0) {
#pragma unroll
      for (int i = 0; i < B_EMPTY; i++) BAR_INIT(i, 1);
    }
    __syncwarp();
    asm volatile("fence.mbarrier_init.release.cluster;" ::: "memory");
    asm volatile("barrier.cluster.arrive.relaxed.aligned;" ::: "memory");
    if (isA) {
#pragma unroll 1
      for (int i = 0; i < 8; i++) {
        if (i >= 6) mbar_wait(bar0 + 8 * (i - 6));
        wait_until(gt_start + ((64 * i + b) * sch.dth >> 8));
        if (lane == 0) {
          BAR_ARM(i, 16384);
          tma3d(sb + i * 16384, &tms.m[i >> 2], bar0 + 8 * i, 0, i < 4 ? 128 * i : 256 * rk + 64 * (i - 4), i < 4 ? b : b & ~1);
        }
        __syncwarp();
      }
    }
  }
  if (warp == 10) {
    const unsigned ep = ldc4(&scr->cnt[0]);
    if (isA) {
      const uint4 xa = ldc16(x + 16 * lane), xb = ldc16(x + 16 * lane + 8);
      float xv[16] = {bflo(xa.x), bfhi(xa.x), bflo(xa.y), bfhi(xa.y), bflo(xa.z), bfhi(xa.z), bflo(xa.w), bfhi(xa.w),
                      bflo(xb.x), bfhi(xb.x), bflo(xb.y), bfhi(xb.y), bflo(xb.z), bfhi(xb.z), bflo(xb.w), bfhi(xb.w)};
      const float x0 = __shfl_sync(~0u, xv[0], 0);
      float s = 0, q = 0;
#pragma unroll
      for (int i = 0; i < 16; i++) { xv[i] -= x0; s += xv[i]; q += xv[i] * xv[i]; }
#pragma unroll
      for (int o = 16; o; o >>= 1) { s += __shfl_xor_sync(~0u, s, o); q += __shfl_xor_sync(~0u, q, o); }
      s *= 1.f / 512.f;
      float rstd;
      asm("rsqrt.approx.ftz.f32 %0, %1;" : "=f"(rstd) : "f"(fmaxf(q * (1.f / 512.f) - s * s, 0.f) + 1e-5f));
      *(float2*)(smem + O_SM + 1024) = make_float2(s + x0, rstd);
    }
    if (lane == 0) *(volatile unsigned*)(smem + O_EP) = ep;
    nbar_arrive(1, 288);
  }
  const int cls = isA ? (b >= NBIG) : 2, v0 = isA ? 2 : 0;
  if (warp >= 8) {
    asm volatile("setmaxnreg.dec.sync.aligned.u32 56;");
    if (warp == 8) {
      if (lane < 8) asm volatile("prefetch.tensormap [%0];" ::"l"(&tms.m[lane + 1]) : "memory");
      if ((sb & 0xFFFFFF) != SMEM_BASE) __trap();
    } else if (warp == 9) {
      if (lane == 0) {
#pragma unroll
        for (int i = B_EMPTY; i < B_LZ; i++) BAR_INIT(i, 8);
        BAR_INIT(B_LZ, 8); BAR_INIT(B_Q2, 9); BAR_ARM(B_Q2, 1024);
        BAR_INIT(B_H, 1); BAR_INIT(B_QF, 1); BAR_ARM(B_QF, 32768);
        BAR_INIT(B_TAB, 1); BAR_INIT(B_W, 1); BAR_INIT(B_ST, 8); BAR_INIT(B_WZ, 1); BAR_INIT(B_HZ, 1); BAR_ARM(B_HZ, isA ? 1024 : 512); BAR_INIT(B_G, 1); BAR_INIT(B_G2, 1);
      }

    }
    if (warp != 11) {
      __syncwarp();
      asm volatile("fence.mbarrier_init.release.cluster;" ::: "memory");
      __threadfence_block();
      asm volatile("barrier.cluster.arrive.relaxed.aligned;" ::: "memory");
    }
    asm volatile("barrier.cluster.wait.acquire.aligned;" ::: "memory");
    if (warp == 8) {
      const int nr = sch.nr[cls], vl = v0 + sch.nt[cls] - 1;
      unsigned long long hist = 0;
      int v = v0;
#pragma unroll 1
      for (int rd = 0; rd < nr; rd++) {
        const uint2 e = sch.r[cls][rd];
        const int type = e.y & 15, win = (e.y >> 4) & 15, pos = b + 64 - (int)((e.y >> 8) & 255), tile = e.y >> 16;
        const bool mod = type == T_MOD;
        const int ni = mod ? 1 : type == T_DN ? 2 : 4;
        unsigned t = gt_start + (e.x & 0xffff) + (pos * sch.dt >> 8);
        const int c0 = mod ? 1024 + 32 * b : type == T_WO || type == T_DN ? 64 * rn : type == T_GU ? 32 * f : 0;
        int c1 = type == T_KV ? 64 * (tile + pos) : 0;
        int c2 = mod ? tile : type == T_WO ? 4 * cl : type == T_DN ? 2 * cl - 16 : type == T_UV ? b : 0;
        const int i1 = type == T_UV ? 128 : 0;
#pragma unroll 1
        for (int j = 0; j < ni; j++) {
          const int slot = mod ? B_FM + tile : (v & 1) * 4 + j;
          if (mod ? tile : v >= 2) mbar_wait(bar0 + 8 * (B_EMPTY + (mod ? (vl & 1) * 4 : slot)), mod ? (vl >> 1) & 1 : ((v >> 1) - 1) & 1);
          const int hw = (int)(hist >> (6 * (win - 1))) & 63;
          if (hw) mbar_wait(bar0 + 8 * (hw & 15), (hw >> 4) & 1);
          wait_until(t);
          if (lane == 0) {
            BAR_ARM(slot, 16384);
            tma3d(sb + (mod ? (tile ? O_Q : O_X) : slot * 16384), &tms.m[type == T_GU ? type + (j & 1) : type], bar0 + 8 * slot, c0, c1, c2);
          }
          __syncwarp();
          hist = hist << 6 | (32 | (mod ? 0 : (v & 2) << 3) | slot);
          t += e.x >> 16; c1 += i1;
          c2 += type == T_KV ? 2 : type == T_WO || type == T_DN ? 1 : type == T_GU ? j & 1 : 0;
        }
        v += !mod;
      }
      return;
    }
    const unsigned epoch = *(volatile unsigned*)(smem + O_EP), par = (epoch + 1) & 1;
    if (warp == 10) {
      if (isA) {
        for (int it = 0; ldx4(scr->cnt + 1) != (epoch + 1) * 128 && it < SPIN_MAX; it++) {}
        if (lane == 0) BAR_ARRIVE(B_H);
      } else mbar_wait(bar0);
      if (!(rn & (QN - 1))) {
        for (int it = 0; ldx4(scr->cnt + 32 + 32 * (rn >> 2)) != (epoch + 1) * 32 && it < SPIN_MAX; it++) {}
        if (lane == 0)
          asm volatile("cp.async.bulk.shared::cluster.global.mbarrier::complete_tx::bytes.multicast::cluster [%0], [%1], %4, [%2], %3;"
                       ::"r"(sb + O_Q + rn * 4096), "l"(scr->qa + rn * 256), "r"(bar0 + 8 * B_QF), "h"((unsigned short)0xff), "n"(4096 * QN) : "memory");
      }
      const unsigned dl = isA ? sch.d4 : sch.d6;
      unsigned tw = gt_start + sch.t4;
      if (!isA) {
        const int nt = sch.nt[2];
#pragma unroll 1
        for (int t = 0; t < nt; t++) mbar_wait(bar0 + 8 * B_EMPTY + (t & 1) * 32, (t >> 1) & 1);
        unsigned long long now;
        asm volatile("mov.u64 %0, %%globaltimer;" : "=l"(now));
        LANE0("red.relaxed.gpu.global.max.u64", scr->cnt + 130, "l", now);
        CNT_ADD(128);
        tw = (unsigned)now + 1700;
      }
      sleep_until(tw);
      uint4 an;
      for (int it = 0; an = ldx16(scr->cnt + 128), an.x != (epoch + 1) * 56 && it < SPIN_MAX; it++) {}
      wait_until(an.z + (dl >> 16));
      if (lane == 0) BAR_ARRIVE(B_G2);
      wait_until(an.z + (dl & 0xffff));
      if (lane == 0) BAR_ARRIVE(B_G);
    } else if (warp == 11) {
      {
        uint2* ph = scr->hdr + ((lane & 24) + 2 * tq + (g & 1)) * 16 + cl;
        const bool own = (lane >> 4) * 4 + tq == rn;
        if (own) { stx8(ph, make_uint2(par ^ 1, 0)); if (cl == 14) stx8(ph + 1, make_uint2(0, 0)); }
        uint32_t a_w = sb + O_HW + ((lane >> 4) * 4 + tq) * 128 + (g & 1) * 64 + ((lane >> 1) & 4);
        PIN(a_w); PINL(ph);
        const int vt = v0 + sch.nt[cls];
#pragma unroll 1
        for (int t = 0; t < vt; t++) mbar_wait(bar0 + 8 * B_EMPTY + (t & 1) * 32, (t >> 1) & 1);
        float hz[8], M;
        uint32_t wp[4];
#pragma unroll 1
        for (int e = 0; e < 2; e++) {
          POLL {
            unsigned ok = 1;
#pragma unroll
            for (int u = 0; u < 8; u++)
              asm volatile("ld.relaxed.cluster.shared.f32 %0, [%1];" : "=f"(hz[u]) : "r"(sb + O_HZ + e * 1024 + u * 128 + lane * 4) : "memory");
#pragma unroll
            for (int u = 0; u < 4; u++) ok = and3(ok, __float_as_uint(hz[u]), __float_as_uint(hz[u + 4]));
            RETRY(~ok)
          }
          if (e) break;
          M = fmaxf(fmaxf(fmaxf(hz[0], hz[1]), fmaxf(hz[2], hz[3])), fmaxf(fmaxf(hz[4], hz[5]), fmaxf(hz[6], hz[7])));
          M = u2f(fbits(M));
#pragma unroll
          for (int u = 0; u < 4; u++) {
            wp[u] = pack2(ex2(hz[u] - M), ex2(hz[u + 4] - M));
            sts4(a_w + ((rn - u) & 3) * 8, u2f(wp[u])); sts4(a_w + ((rn - u) & 3) * 8 + 32, u2f(wp[u]));
          }
          __syncwarp();
          if (lane == 0) BAR_ARRIVE(B_WZ);
        }
        float L = 0.f;
#pragma unroll
        for (int u = 0; u < 4; u++) L += bflo(wp[u]) * hz[u] + bfhi(wp[u]) * hz[u + 4];
        if (own) pub8(ph, __float_as_uint(M) | 1u, __float_as_uint(L));
      }
      if (isA) {
        mbar_wait(bar0 + 8 * B_G2);
        unsigned long long hh;
        POLL { hh = ldx64(scr->hdr + hd * 16 + (lane & 15)); RETRY((lane & 15) == 15 ? 0u : (unsigned)hh ^ par) }
        const float m = (lane & 15) == 15 ? -1e30f : u2f((unsigned)hh);
        int mi = __float_as_int(m);
        mi ^= (mi >> 31) & 0x7fffffff;
        mi = __reduce_max_sync(~0u, mi);
        mi ^= (mi >> 31) & 0x7fffffff;
        const float w = ex2(m - __int_as_float(mi));
        float L = w * u2f(hh >> 32);
#pragma unroll
        for (int o2 = 8; o2; o2 >>= 1) L += __shfl_xor_sync(~0u, L, o2);
        sts4(sb + O_SM + (384 + 2 * (lane & 6) + ((lane >> 2) & 2) + (lane & 1)) * 4, w * rcp(L));
        __syncwarp();
        if (lane == 0) BAR_ARRIVE(B_W);
      }
    } else {
#pragma unroll 4
      for (int i = 0; i < 72; i++) sts16(sb + O_LZ + i * 512 + lane * 16, make_uint4(0, 0, 0, 0));
      __syncwarp();
      if (lane < 8) asm volatile("mbarrier.arrive.release.cluster.shared::cluster.b64 _, [%0];" ::"r"(mapa(bar0 + 8 * B_LZ, lane)) : "memory");
      if (isA) {
        mbar_wait(bar0 + 8 * B_QF);
#pragma unroll 2
        for (int k = 0; k < 8; k++) {
          const uint32_t cp = ldc4(cvec + 2 * (lane + 32 * k));
          *(uint32_t*)(smem + O_SILU + (lane + 32 * k) * 4) = pack2(silu_bf(bflo(cp)), silu_bf(bfhi(cp)));
        }
        __syncwarp();
        uint32_t ab = sb + O_X + (8 * (lane >> 4) + (lane & 7)) * 64 + ((((lane >> 3) & 1) ^ ((lane >> 1) & 3)) << 4);
        float d[4][4] = {};
#pragma unroll 1
        for (int jm = 0; jm < 2; jm++) {
          mbar_wait(bar0 + 8 * (B_FM + jm));
#pragma unroll 2
          for (int s2 = 0; s2 < 8; s2++)
#pragma unroll
            for (int s = 0; s < 2; s++) {
              uint32_t a0[4], a1[4];
              const uint32_t* ps = (const uint32_t*)(smem + O_SILU) + 128 * jm + 16 * s2 + 8 * s + tq;
              ldsm_t(a0, ab + (2 * s2 + s) * 1024); ldsm_t(a1, (ab + (2 * s2 + s) * 1024) ^ 32);
              mma16(d[s], a0, ps[0], ps[4]); mma16(d[2 + s], a1, ps[0], ps[4]);
            }
          ab -= O_X - O_Q;
        }
        const float t0 = (tq & 1) ? d[0][2] + d[1][2] : d[0][0] + d[1][0], t1 = (tq & 1) ? d[2][2] + d[3][2] : d[2][0] + d[3][0];
        stx4(scr->xm + b * 32 + posof(8 * tq + g), fbits(bfr(bfr((tq & 2) ? t1 : t0) + ((b >> 4) == 2 ? 1.f : 0.f))));
        __syncwarp();
        CNT_ADD(96);
      } else sleep_until(gt_start + sch.t4);
      for (int it = 0; ldx4(scr->cnt + 96) != (epoch + 1) * 64 && it < SPIN_MAX; it++) __nanosleep(NSL);
      if (isA) {
        unsigned long long ga;
        POLL { ga = ldx64(scr->xm + 64 * rn + 2 * lane); RETRY(lop_x3((unsigned)ga, ga >> 32, par)) }
        *(float2*)(smem + O_SM + (320 + 2 * lane) * 4) = make_float2(bfhi((unsigned)ga), bfhi(ga >> 32));
      }
      __syncwarp();
      if (lane == 0) BAR_ARRIVE(B_TAB);
    }
    return;
  }

  float* s_sm = (float*)(smem + O_SM);
  unsigned par, epoch;
  asm volatile("barrier.cluster.arrive.relaxed.aligned;" ::: "memory");
  if (isA) {
    float* s_r = (float*)(smem + O_R);
    float acc[8] = {0, 0, 0, 0, 0, 0, 0, 0};
    const float sl = silu_bf((arow & 1) ? bfhi(cw) : bflo(cw));
#pragma unroll
    for (int i = 0; i < 4; i++) fma8(acc, wm[i], __shfl_sync(~0u, sl, i, 4));
    tred<4>(acc, lane, 16);
    *(float4*)(s_r + warp * 128 + 8 * (lane & 15) + ((lane >> 2) & 4)) = make_float4(acc[0], acc[1], acc[2], acc[3]);
    nbar(1, 288);
    epoch = *(volatile unsigned*)(smem + O_EP);
    par = (epoch + 1) & 1;
    if (warp < 2) {
      float t = 0.f, ca = rn == 0 ? 1.f : 0.f;
#pragma unroll
      for (int w = 0; w < 8; w++) { t += s_r[w * 128 + tid]; ca += s_r[w * 128 + 64 + tid]; }
      t += ca * ((((tid & 1) ? bfhi(xw) : bflo(xw)) - s_sm[256]) * s_sm[257]);
      const float nb = __shfl_down_sync(~0u, t, 1);
      const uint32_t w0 = lane < 8 ? pack2t(t, nb, par) : pack2(t, nb);
      const uint32_t w1 = __shfl_down_sync(~0u, w0, 8), w2 = __shfl_down_sync(~0u, w0, 16), w3 = __shfl_down_sync(~0u, w0, 24);
      if (lane < 8 && !(lane & 1)) stx16(scr->h + (rn >> 1) * 512 + (2 * cl + warp) * 32 + rk * 16 + 2 * lane, make_uint4(w0, w1, w2, w3));
      __syncwarp();
      CNT_ADD(1);
    }
    asm volatile("barrier.cluster.wait.acquire.aligned;" ::: "memory");
    const uint32_t rsb = mapa(sb, rn ^ 1);
    {
      uint32_t a[4][4][4];
      mbar_wait(bar0 + 8 * (warp >> 1));
      const uint32_t ab = sb + (64 * warp + 8 * (lane >> 4) + (lane & 7)) * 128;
#pragma unroll
      for (int s = 0; s < 4; s++)
#pragma unroll
        for (int mt = 0; mt < 4; mt++) ldsm_t(a[s][mt], ab + s * 2048 + (((2 * mt + ((lane >> 3) & 1)) ^ (lane & 7)) << 4));
      arrive_n(bar0 + 8 * (B_EMPTY + (warp >> 1)), lane == 0, 4 + (dep16(&a[0][0][0]) & sch.zero));
      uint4 v0, v1;
      const unsigned* ph = scr->h + (g >> 1) * 512 + 64 * warp + 4 * (lane & 7);
      uint32_t off = O_B + warp * 272 + (32 * rk + 8 * tq + (lane & 4)) * 4;
      PIN(off); PINL(ph);
      mbar_wait(bar0 + 8 * B_H);
      POLL { v0 = ldx16(ph); v1 = ldx16(ph + 32); RETRY(lop_x3(v0.x, v1.x, par)) }
      float d[4][4] = {};
#pragma unroll
      for (int mt = 0; mt < 4; mt++) {
        mma16(d[mt], a[0][mt], v0.x, v0.y); mma16(d[mt], a[1][mt], v0.z, v0.w);
        mma16(d[mt], a[2][mt], v1.x, v1.y); mma16(d[mt], a[3][mt], v1.z, v1.w);
      }
      float r[8];
#pragma unroll
      for (int mt = 0; mt < 4; mt++) { r[2 * mt] = d[mt][0] + d[mt][1]; r[2 * mt + 1] = d[mt][2] + d[mt][3]; }
      tred<4>(r, lane, 2); tred<2>(r, lane, 1);
      const float rc = __shfl_xor_sync(~0u, (lane & 4) ? r[0] : r[1], 4);
      const uint32_t wd = (lane & 4) ? pack2(rc, r[1]) : pack2(r[0], rc);
      const uint32_t w1 = __shfl_down_sync(~0u, wd, 8), w2 = __shfl_down_sync(~0u, wd, 16), w3 = __shfl_down_sync(~0u, wd, 24);
      asm volatile("{.reg .pred p; setp.lt.s32 p, %7, 8; @p st.shared.v4.b32 [%0], {%2,%3,%4,%5};\n"
                   "@p st.async.shared::cluster.mbarrier::complete_tx::bytes.v4.b32 [%1], {%2,%3,%4,%5}, [%6];}"
                   ::"r"(sb + off), "r"(rsb + off), "r"(wd), "r"(w1), "r"(w2), "r"(w3), "r"(rsb + O_BAR + 8 * B_Q2), "r"(lane) : "memory");
      __syncwarp();
      arrive_n(bar0 + 8 * B_Q2, lane == 0, 1);
    }
    {
      uint32_t a[2][8][4];
      uint32_t a_bq = sb + O_B + (lane & 7) * 272 + (lane >> 3) * 16;
      uint4* p_qa = scr->qa + (4 * rk + (warp >> 1)) * 256 + hd * 8 + ((4 * (warp & 1) + tq) ^ (hd & 7));
      PIN(a_bq); PINL(p_qa);
      mbar_wait(bar0 + 8 * (4 + (warp >> 1)));
      const uint32_t ab = sb + 65536 + (warp >> 1) * 16384 + (32 * (warp & 1) + (lane & 15)) * 128;
#pragma unroll
      for (int i = 0; i < 16; i++) ldsm(a[i >> 3][i & 7], ab + (i >> 3) * 2048 + ((i >> 2) & 1) * 8192 + (((2 * (i & 3) + (lane >> 4)) ^ (lane & 7)) << 4));
      arrive_n(bar0 + 8 * (B_EMPTY + 4 + (warp >> 1)), lane == 0, 4 + (dep16(&a[0][0][0]) & sch.zero));
      mbar_wait(bar0 + 8 * B_Q2);
      float d[4][4] = {};
#pragma unroll
      for (int y = 0; y < 4; y++) {
        uint32_t bq[4];
        ldsm(bq, a_bq + 64 * y);
#pragma unroll
        for (int mt = 0; mt < 2; mt++) { mma16(d[2 * mt], a[mt][2 * y], bq[0], bq[1]); mma16(d[2 * mt + 1], a[mt][2 * y + 1], bq[2], bq[3]); }
      }
      float r[4];
#pragma unroll
      for (int i = 0; i < 4; i++) r[i] = (d[i & 2][2 * (i & 1)] + d[i & 2][2 * (i & 1) + 1]) + (d[(i & 2) + 1][2 * (i & 1)] + d[(i & 2) + 1][2 * (i & 1) + 1]);
      tred<2>(r, lane, 2); tred<1>(r, lane, 1);
      const float nb = __shfl_xor_sync(~0u, r[0], 4);
      const uint32_t w0 = (lane >> 3) == (hd & 3) ? pack2t(r[0], nb, par) : pack2(r[0], nb);
      const uint32_t w1 = __shfl_down_sync(~0u, w0, 8), w2 = __shfl_down_sync(~0u, w0, 16), w3 = __shfl_down_sync(~0u, w0, 24);
      if (lane < 4) stx16(p_qa, make_uint4(w0, w1, w2, w3));
      if (warp) nbar_arrive(3, 256); else { nbar(3, 256); CNT_ADD(32 + 32 * rk); }
    }
  } else {
    nbar(1, 288);
    epoch = *(volatile unsigned*)(smem + O_EP);
    par = (epoch + 1) & 1;
    asm volatile("barrier.cluster.wait.acquire.aligned;" ::: "memory");
    mbar_wait(bar0);
  }
  asm volatile("setmaxnreg.inc.sync.aligned.u32 224;");
  uint2* p_rec = scr->rec + ((16 * (warp >> 2) + 2 * (warp & 3) + (g & 1) + 4 * (tq & 2)) * 32 + 4 * rn + (tq & 1)) * 64 + cl * 4 + (g >> 1);
  PINL(p_rec);
  {
    const unsigned inv = par ^ 1;
#pragma unroll
    for (int q = 0; q < 2; q++) { stx8(p_rec + q * 128, make_uint2(inv, 0)); if (cl == 14) stx8(p_rec + q * 128 + 4, make_uint2(0, 0)); }
    if (isA) { if (warp < 2) { stx4(scr->xao + b * 64 + tid, inv); stx4(scr->xab + cl * 256 + (2 * (rn & 3) + warp) * 32 + (rn >> 2) * 16 + (lane >> 1), inv); } }
    else if (f == 0) { stx4(out + 2 * tid, 0); __threadfence(); }
  }
  sb = __shfl_sync(~0u, sb, 0); bar0 = sb + O_BAR;
  const int nt = sch.nt[cls], wg = warp >> 2;
  uint32_t a_z[4];
#pragma unroll
  for (int u = 0; u < 4; u++) {
    const int s3 = (rn - u - (lane >> 1 & 1)) & 3;
    a_z[u] = sb + O_LZ + (s3 + 4 * (lane & 1)) * 4096 + wg * 512 + g * 64 + (((warp & 3) ^ (s3 & 1) ^ (2 * (lane & 1))) << 4);
    PIN(a_z[u]);
  }
  uint32_t z[4][4], a_w = sb + O_HW + warp * 128 + (g & 1) * 64 + (tq & 1) * 8;
  PIN(a_w);
  {
    const float sc = 0.08838834764831845f * 1.4426950408889634f;
    float mrun = -1e30f;
    float o[4][16], sx[16], mref[8];
#pragma unroll
    for (int k = 0; k < 16; k++) { o[0][k] = o[1][k] = o[2][k] = o[3][k] = sx[k] = 0.f; mref[k >> 1] = -1e30f; }
    const int key = 16 * warp + (lane & 15);
    uint32_t a_p = sb + O_P + key * 64 + (((lane >> 4) ^ ((key >> 1) & 3)) << 4);
    uint32_t a_v = sb + wg * 32768 + (8 * (lane >> 4) + (lane & 7)) * 128 + (((2 * (warp & 3) + ((lane >> 3) & 1)) ^ (lane & 7)) << 4);
    const int rot = rn + warp;
    const int qown = wg == (rn >> 2) ? -warp & 3 : -1;
    uint32_t a_own = sb + O_LZ + rn * 4096 + (warp & 3) * 1024 + g * 64 + ((tq ^ (rn & 1) ^ ((rn >> 1) & 2)) << 4);
    PIN(a_own);
    unsigned long long dst[4];
#pragma unroll
    for (int q = 0; q < 4; q++) {
      dst[q] = mapg(a_own, 4 * wg + ((q + rot) & 3));
      PINL(dst[q]);
    }
    unsigned long long a_h = mapg(sb + O_HZ + wg * 1024 + rn * 128 + lane * 4, 2 * (warp & 3));
    unsigned long long a_h1 = mapg(sb + O_HZ + wg * 1024 + rn * 128 + lane * 4, 2 * (warp & 3) + 1);
    PIN(a_p); PIN(a_v); PINL(a_h); PINL(a_h1);
    uint32_t rel = lane < 4 && lane >= 2 * wg ? 2 - (tq >> 1) : 0;
    PIN(rel);
    uint32_t ones[4] = {0x3F803F80u, 0x3F803F80u, 0x3F803F80u, 0x3F803F80u};
    PIN(ones[0]); PIN(ones[1]); PIN(ones[2]); PIN(ones[3]);
    {
      asm volatile("{.reg .pred p; .reg .u32 n; mov.u32 n, 0;\n"
                   "W%=: mbarrier.try_wait.parity.acquire.cluster.shared::cta.b64 p, [%0], 0; add.u32 n, n, 1; setp.lt.and.u32 p, n, 0x100000, !p; @p bra W%=;}"
                   ::"r"(bar0 + 8 * B_LZ) : "memory");
      mbar_wait(bar0 + 8 * B_QF);
      unsigned bad = 0;
#pragma unroll
      for (int k = 0; k < 8; k++) bad |= __float_as_uint(lds4(sb + O_Q + k * 4096 + tid * 16 + (lane >> 3) * 4)) ^ par;
      if (__builtin_expect(__any_sync(~0u, bad & 1), 0)) {
#pragma unroll 1
        for (int k = 0; k < 8; k++) {
          uint4 v;
          POLL { v = ldx16(scr->qa + k * 256 + tid); RETRY(((lane & 16) ? ((lane & 8) ? v.w : v.z) : ((lane & 8) ? v.y : v.x)) ^ par) }
          sts16(sb + O_Q + k * 4096 + tid * 16, v);
        }
        asm volatile("fence.proxy.async.shared::cta;" ::: "memory");
      }
      if (warp >= 4) nbar_arrive(1, 256); else nbar(1, 256);
    }
#pragma unroll 1
    for (int t = 0; t < nt; t++) {
      const int v = v0 + t;
      const uint32_t fb = bar0 + (v & 1) * 32, ph = (v >> 1) & 1, av = a_v + (v & 1) * 65536;
      uint32_t vf[4][4][4], cnt;
      auto landed = [&]() {
        cnt = rel + (dep16(&vf[0][0][0]) & (nt >> 8));
        PIN(cnt);
      };
      if (wg == 0) {
        const uint32_t da = DSC + (v & 1) * 4096, db = DSC + O_Q / 16;
#pragma unroll 1
        for (int j = 0; j < 4; j++) {
          mbar_wait(fb + 8 * j, ph);
          asm volatile("wgmma.fence.sync.aligned;" ::: "memory");
#pragma unroll
          for (int k = 0; k < 8; k++)
            wgmma32<0, 0, HI128, HI128>(sx, da + j * 1024 + (k >> 2) * 512 + (k & 3) * 2, db + j * 512 + (k >> 2) * 256 + (k & 3) * 2, k ? 1 : j);
          asm volatile("wgmma.commit_group.sync.aligned;" ::: "memory");
          if (j == VJ) {
#pragma unroll
            for (int i = 0; i < 16; i++) ldsm_t(vf[i >> 2][i & 3], av + (((i >> 2) + rot) & 3) * 8192 + (i & 3) * 2048);
            nbar(5, 256);
            landed();
          }
        }
      } else {
        nbar_arrive(5, 256);
#pragma unroll 1
        for (int j = 0; j < 2; j++) {
          mbar_wait(fb + 16 + 8 * j, ph);
          if (j) spin_until(clock() + VDLY);
#pragma unroll
          for (int q = 0; q < 4; q++)
            if (((q + rot) & 2) == 2 * j)
#pragma unroll
              for (int k = 0; k < 4; k++) ldsm_t(vf[q][k], av + ((q + rot) & 3) * 8192 + k * 2048);
        }
        cnt = 0;
      }
      wg_wait<0>(sx);
      asm volatile("{.reg .pred p; setp.ne.s32 p, %1, 0; @p mbarrier.arrive.shared::cta.b64 _, [%0], %1;}" ::"r"(fb + 8 * B_EMPTY + 8 * tq), "r"(cnt) : "memory");
#pragma unroll 1
      for (int pass = 0;; pass++) {
        int ex = !(t | pass);
        if (wg == 0 && (t | pass)) {
          uint32_t pk[8];
#pragma unroll
          for (int i = 0; i < 8; i++) pk[i] = pack2(ex2(sx[2 * i] * sc - mref[i & 6]), ex2(sx[2 * i + 1] * sc - mref[(i & 6) + 1]));
          asm volatile("stmatrix.sync.aligned.m8n8.x4.shared.b16 [%0], {%2,%3,%4,%5};\n"
                       "stmatrix.sync.aligned.m8n8.x4.shared.b16 [%1], {%6,%7,%8,%9};"
                       ::"r"(a_p), "r"(a_p ^ 32), "r"(pk[0]), "r"(pk[1]), "r"(pk[2]), "r"(pk[3]), "r"(pk[4]), "r"(pk[5]), "r"(pk[6]), "r"(pk[7]) : "memory");
          const uint32_t mx = __vmaxu2(__vmaxu2(__vmaxu2(pk[0], pk[1]), __vmaxu2(pk[2], pk[3])), __vmaxu2(__vmaxu2(pk[4], pk[5]), __vmaxu2(pk[6], pk[7])));
          ex = max(mx, mx << 16) > (127u + TAU) << 23;
          asm volatile("fence.proxy.async.shared::cta;" ::: "memory");
        }
        asm volatile("{.reg .pred p, q; setp.ne.s32 q, %0, 0; bar.red.or.pred p, 4, 256, q; selp.s32 %0, 1, 0, p;}" : "+r"(ex)::"memory");
        if (!ex || pass) break;
        int ln;
        asm volatile("mov.u32 %0, %%laneid;" : "=r"(ln));
        const uint32_t a_pm = sb + O_SM + ln * 16;
        if (wg == 0) {
          float cm[8];
#pragma unroll
          for (int i = 0; i < 8; i++) cm[i] = fmaxf(sx[2 * (i & 6) + (i & 1)], sx[2 * (i & 6) + (i & 1) + 2]);
          tmax<4>(cm, lane, 16); tmax<2>(cm, lane, 8); tmax<1>(cm, lane, 4);
          sts4(a_pm + warp * 4, cm[0] * sc);
        }
        nbar(4, 256);
        const float4 pm = lds16(a_pm);
        const float mn = u2f(__float_as_uint(fmaxf(fmaxf(fmaxf(pm.x, pm.y), fmaxf(pm.z, pm.w)), mrun)) | 1u), al = ex2(mrun - mn);
        mrun = mn;
#pragma unroll
        for (int i = 0; i < 8; i++) {
          const float a = __shfl_sync(~0u, al, 4 * i + (ln & 3)), aw = wg ? a : 1.f;
          mref[i] = __shfl_sync(~0u, mn, 4 * i + (ln & 3));
#pragma unroll
          for (int e = 0; e < 2; e++) {
            const int k = 2 * (i & 6) + (i & 1) + 2 * e;
            o[0][k] *= a; o[1][k] *= a; o[2][k] *= a; o[3][k] *= a; sx[k] *= aw;
          }
        }
      }
      float hv = mrun;
      if (wg) {
        asm volatile("wgmma.fence.sync.aligned;" ::: "memory");
#pragma unroll
        for (int k = 0; k < 4; k++) wgmma32r(sx, ones, DSC + O_P / 16 + k * 64);
        asm volatile("wgmma.commit_group.sync.aligned;" ::: "memory");
        landed();
        asm volatile("{.reg .pred p; setp.ne.s32 p, %1, 0; @p mbarrier.arrive.shared::cta.b64 _, [%0], %1;}" ::"r"(fb + 8 * B_EMPTY + 8 * tq), "r"(cnt) : "memory");
        wg_wait<0>(sx);
        float lv[4];
#pragma unroll
        for (int j = 0; j < 4; j++) lv[j] = (lane & 4) ? sx[4 * j + 1] : sx[4 * j];
        hv = (lane & 16) ? ((lane & 8) ? lv[3] : lv[2]) : ((lane & 8) ? lv[1] : lv[0]);
      }
      asm volatile("{.reg .pred p; setp.eq.s32 p, %3, %4; @p st.relaxed.cluster.b32 [%0], %1; @p st.relaxed.cluster.b32 [%2], %1;}"
                   ::"l"(a_h), "r"(__float_as_uint(hv) | 1u), "l"(a_h1), "r"(t), "r"(nt - 1) : "memory");
#pragma unroll
      for (int q = 0; q < 4; q++) {
        if (q < 2) {
          asm volatile("wgmma.fence.sync.aligned;" ::: "memory");
#pragma unroll
          for (int u = q; u < (q ? 4 : 1); u++) {
#pragma unroll
            for (int k = 0; k < 4; k++) wgmma32r(o[u], vf[u][k], DSC + O_P / 16 + k * 64);
            asm volatile("wgmma.commit_group.sync.aligned;" ::: "memory");
          }
        }
        if (q == 3) {
#pragma unroll
          for (int u = 0; u < 4; u++)
            asm volatile("{.reg .pred p; setp.eq.s32 p, %5, %6; @p ldmatrix.sync.aligned.m8n8.x4.trans.shared.b16 {%0,%1,%2,%3}, [%4];}"
                         : "=r"(z[u][0]), "=r"(z[u][1]), "=r"(z[u][2]), "=r"(z[u][3]) : "r"(a_z[u] + u * 1024), "r"(t), "r"(nt - 1) : "memory");
        }
        if (q == 1) wg_wait<2>(o[q]); else if (q == 2) wg_wait<1>(o[q]); else wg_wait<0>(o[q]);
        if (q == 0 || t == nt - 1)
#pragma unroll
        for (int j = 0; j < 2; j++)
          asm volatile("{.reg .pred p, q, r; setp.eq.s32 p, %5, %6; setp.eq.and.s32 q|r, %7, %8, p; @r st.relaxed.cluster.v4.b32 [%0], {%1,%2,%3,%4};\n"
                       "@q st.shared.v4.b32 [%9], {%1,%2,%3,%4};}"
                       ::"l"(dst[q] + j * 512), "r"(pack2t(o[q][8 * j], o[q][8 * j + 1], 1)), "r"(pack2(o[q][8 * j + 2], o[q][8 * j + 3])),
                         "r"(pack2(o[q][8 * j + 4], o[q][8 * j + 5])), "r"(pack2(o[q][8 * j + 6], o[q][8 * j + 7])), "r"(t), "r"(nt - 1),
                         "r"(qown), "r"(q), "r"(a_own + j * 512) : "memory");
      }
    }
  }
  {
    uint32_t wx[4][4];
    mbar_wait(bar0 + 8 * B_WZ);
#pragma unroll
    for (int u = 0; u < 4; u++) {
      uint2 wp;
      asm volatile("ld.shared.v2.u32 {%0, %1}, [%2];" : "=r"(wp.x), "=r"(wp.y) : "r"(a_w + u * 8) : "memory");
      const bool lo = (g >> 1) == (tq >> 1), hi = (g >> 1) == 2 + (tq >> 1);
      wx[u][0] = lo ? wp.x : 0u; wx[u][1] = lo ? wp.y : 0u; wx[u][2] = hi ? wp.x : 0u; wx[u][3] = hi ? wp.y : 0u;
    }
    auto bad = [&]() {
      const unsigned ok = and3(and3(and3(z[0][0], z[0][1], z[0][2]), and3(z[0][3], z[1][0], z[1][1]), and3(z[1][2], z[1][3], z[2][0])),
                               and3(and3(z[2][1], z[2][2], z[2][3]), and3(z[3][0], z[3][1], z[3][2]), z[3][3]), 0x10001u);
      return __any_sync(~0u, g == 0 && ok != 0x10001u);
    };
    POLL {
      if (it_)
#pragma unroll
        for (int u = 0; u < 4; u++) ldsm_t(z[u], a_z[u] + u * 1024);
      if (!bad() || ++it_ >= SPIN_MAX) break;
    }
    float d0[8][4] = {}, d[8][4], r[8];
#pragma unroll
    for (int i = 0; i < 8; i++) mma16(d0[i], wx[i >> 1], z[i >> 1][2 * (i & 1)], z[i >> 1][2 * (i & 1) + 1]);
    POLL {
#pragma unroll
      for (int u = 0; u < 4; u++) ldsm_t(z[u], a_z[u ^ 2] + u * 1024);
#pragma unroll
      for (int i = 0; i < 8; i++) mma16c(d[i], wx[(i >> 1) ^ 2], z[i >> 1][2 * (i & 1)], z[i >> 1][2 * (i & 1) + 1], d0[i]);
      if (!bad() || ++it_ >= SPIN_MAX) break;
    }
#pragma unroll
    for (int i = 0; i < 8; i++) r[i] = (tq & 2) ? ((g & 1) ? d[i][3] : d[i][2]) : ((g & 1) ? d[i][1] : d[i][0]);
#pragma unroll
    for (int q = 0; q < 2; q++) pub8(p_rec + q * 128, pack2t(r[4 * q], r[4 * q + 1], par) | 1u, pack2(r[4 * q + 2], r[4 * q + 3]));
  }
  const int vt = v0 + nt;
  const uint32_t bufa = sb + (vt & 1) * 65536, fulla = bar0 + (vt & 1) * 32, pha = (vt >> 1) & 1, phb = ((vt + 1) >> 1) & 1;
  const uint32_t bufo = sb + ((vt + 1) & 1) * 65536, fullb = bar0 + ((vt + 1) & 1) * 32;
  uint32_t a_rs = sb + O_R + (warp >> 2) * 1024 + (16 * tq + g) * 16 + ((warp + tq) & 3) * 4;
  if (isA) {
    const int row = 16 * (warp & 6) + 8 * (warp & 1) + (lane & 16) + ((lane & 7) >> 1) + 4 * (lane & 1);
    uint32_t ab = bufa + row * 128 + ((((lane >> 3) & 1) ^ (row & 7)) << 4);
    const uint2* pr = scr->rec + (hd * 32 + warp) * 64 + lane;
    uint32_t a_cb = mapa(bar0 + 8 * B_HZ, (warp & 6) + (lane >> 4)), a_c = a_cb - (O_BAR + 8 * B_HZ - O_CTX) + (2 * rn + (warp & 1)) * 64 + tq * 16;
    uint32_t a_rl = sb + O_R + (32 * (warp & 1) + lane) * 16;
    uint32_t ao = bufo + (16 * warp + 8 * (lane >> 4) + (lane & 7)) * 128 + ((((lane >> 3) & 1) ^ (lane & 7)) << 4);
    uint32_t a_cx = sb + O_CTX + (warp >> 1) * 64 + tq * 16 + (warp & 1) * 8, a_ga = sb + O_SM + (320 + posof(tid & 63)) * 4;
    unsigned* p_ao = scr->xao + b * 64 + (tid & 63);
    unsigned* p_ab = scr->xab + cl * 256 + (2 * (rn & 3) + (warp & 1)) * 32 + (rn >> 2) * 16 + (lane >> 1);
    float xv = cl == 0 ? __bfloat162float(x[64 * rn + (tid & 63)]) : 0.f;
    unsigned p2 = lane >= 28 ? 0 : par;
    PIN(ab); PINL(pr); PIN(a_cb); PIN(a_c); PIN(a_rl); PIN(a_rs); PIN(ao); PIN(a_cx); PIN(a_ga); PINL(p_ao); PINL(p_ab); PIN(p2);
    asm volatile("" : "+f"(xv));
    uint32_t aw[4][4][4];
    auto wo = [&](const int j) {
      mbar_wait(fullb + 8 * j, phb);
#pragma unroll
      for (int mt = 0; mt < 4; mt++) ldsm_t(aw[j][mt], (ao + j * 16384) ^ (mt << 5));
    };
    {
      uint32_t a[4][4][4];
      uint2 z[4], y[4] = {};
      float d[4][4] = {}, r[8];
      mbar_wait(fulla, pha);
      POLL {
#pragma unroll
        for (int q = 0; q < 4; q++) z[q] = ldx8(pr + q * 512);
        RETRY(lop_x3(z[0].x, z[1].x, par) | lop_x3(z[2].x, z[3].x, par))
      }
#pragma unroll
      for (int q = 0; q < 4; q++) {
        if (q == 3) {
          mbar_wait(bar0 + 8 * B_G);
          if (lane < 28)
#pragma unroll
            for (int u = 0; u < 4; u++) y[u] = ldx8(pr + u * 512 + 32);
          __syncwarp();
        }
        mbar_wait(fulla + 8 * q, pha);
#pragma unroll
        for (int mt = 0; mt < 4; mt++) ldsm_t(a[q][mt], (ab + q * 16384) ^ (mt << 5));
#pragma unroll
        for (int mt = 0; mt < 4; mt++) mma16(d[mt], a[q][mt], z[q].x, z[q].y);
      }
      mbar_wait(bar0 + 8 * B_W);
      const float4 W = lds16(sb + O_SM + (384 + 4 * tq) * 4);
#pragma unroll
      for (int i = 0; i < 8; i++) { r[i] = W.x * d[i >> 1][2 * (i & 1)] + W.y * d[i >> 1][2 * (i & 1) + 1]; asm volatile("" : "+f"(r[i])); }
#pragma unroll
      for (int j = 0; j < NPE; j++) wo(j);
      POLL {
        if (it_)
#pragma unroll
          for (int u = 0; u < 4; u++) y[u] = ldx8(pr + u * 512 + 32);
#pragma unroll
        for (int mt = 0; mt < 4; mt++) d[mt][0] = d[mt][1] = d[mt][2] = d[mt][3] = 0.f;
#pragma unroll
        for (int q = 0; q < 4; q++)
#pragma unroll
          for (int mt = 0; mt < 4; mt++) mma16(d[mt], a[q][mt], y[q].x, y[q].y);
        RETRY(or3(lop_x3(y[0].x, y[1].x, p2), lop_x3(y[2].x, y[3].x, p2), 0))
      }
#pragma unroll
      for (int i = 0; i < 8; i++) r[i] = W.w * d[i >> 1][2 * (i & 1) + 1] + (W.z * d[i >> 1][2 * (i & 1)] + r[i]);
      tred<4>(r, lane, 2); tred<2>(r, lane, 1);
      sts4(a_rs, r[0]); sts4(a_rs + 128, r[1]);
      nbar(1, 256);
      send32(a_c, a_cb, sum8(a_rl), lane);
    }
    {
#pragma unroll
      for (int j = NPE; j < NPO; j++) wo(j);
      uint2 c[4];
      mbar_wait(bar0 + 8 * B_HZ);
#pragma unroll
      for (int j = 0; j < 4; j++) asm volatile("ld.shared.v2.u32 {%0, %1}, [%2];" : "=r"(c[j].x), "=r"(c[j].y) : "r"(a_cx + j * 256) : "memory");
      float d[4][4] = {};
#pragma unroll
      for (int j = 0; j < 4; j++) {
        if (j + 1 >= NPO && j < 3) wo(j + 1);
#pragma unroll
        for (int mt = 0; mt < 4; mt++) mma16(d[mt], aw[j][mt], c[j].x, c[j].y);
      }
      const float r0 = (tq & 2) ? ((tq & 1) ? d[3][0] : d[2][0]) : ((tq & 1) ? d[1][0] : d[0][0]);
      const float r1 = (tq & 2) ? ((tq & 1) ? d[3][2] : d[2][2]) : ((tq & 1) ? d[1][2] : d[0][2]);
      sts4(a_rs + 2048, r0); sts4(a_rs + 2048 + 128, r1);
      if (warp >= 2) nbar_arrive(2, 256);
      else {
        mbar_wait(bar0 + 8 * B_TAB);
        const float gav = lds4(a_ga);
        nbar(2, 256);
        const float t = gav * sum8(a_rl + 2048) + xv;
        asm volatile("{.reg .pred p; setp.eq.s32 p, %2, 0; @p red.relaxed.gpu.global.xor.b32 [%0], %1;}"
                     ::"l"(p_ab), "r"(pack2t(t, __shfl_down_sync(~0u, t, 1), par) | 1u), "r"(lane & 1) : "memory");
        pub4(p_ao, __float_as_uint(t) | 1u);
      }
    }
  } else {
    uint32_t af[4][4][4];
    uint32_t ab = bufa + (32 * warp + 8 * (lane >> 4) + (lane & 7)) * 64 + ((((lane >> 3) & 1) ^ ((lane >> 1) & 3)) << 4);
    uint32_t a_d = bufo + wg * 16384 + (8 * (lane >> 4) + (lane & 7)) * 128 + (((2 * (warp & 3) + ((lane >> 3) & 1)) ^ (lane & 7)) << 4);
    uint32_t a_rl = sb + O_R + lane * 16, a_st = sb + O_SM + (352 + 8 * (lane >> 4) + warp) * 4;
    const unsigned* pa = scr->xab + tid;
    uint32_t a_hb = mapa(bar0 + 8 * B_HZ, 2 * (warp & 3) + (lane >> 4)), a_h = a_hb - (O_BAR + 8 * B_HZ - O_CTX) + rn * 64 + tq * 16;
    PIN(a_hb); PIN(a_h);
    uint32_t a_hl = sb + O_CTX + wg * 256 + tq * 16, a_t = sb + O_SM + (16 * warp + 8 * (tq & 1) + g) * 4;
    const unsigned* px = scr->xao + 64 * rn + 2 * lane;
    bf16* po = out + 64 * rn + 2 * lane;
    PIN(ab); PIN(a_d); PIN(a_rl); PINL(pa); PIN(a_rs); PIN(a_st); PINL(po); PIN(a_hl); PINL(px); PIN(a_t);
    mbar_wait(bar0 + 8 * B_TAB);
    uint2 cf;
    uint2 bb[4];
    uint2 gbw;
    POLL {
      unsigned bad = 0;
      cf = ldx8(scr->xm + 1024 + (lane & 16) * 16 + 32 * warp + posof(2 * (lane & 15)));
#pragma unroll
      for (int s = 0; s < 4; s++) {
        const uint4 w = ldx16(scr->xm + 1024 - (g & 1) * 512 + 256 * (s >> 1) + 32 * warp + 16 * (s & 1) + 4 * tq);
        bb[s] = make_uint2(__byte_perm(w.x, w.y, 0x7632), __byte_perm(w.z, w.w, 0x7632));
        bad = or3(bad, lop_x3(w.x, w.y, par), lop_x3(w.z, w.w, par));
      }
      gbw = ldx8(scr->xm + 1536 + 64 * rn + posof(2 * lane));
      RETRY(or3(bad, lop_x3(cf.x, cf.y, par), lop_x3(gbw.x, gbw.y, par)))
    }
    float e[4][4] = {};
    unsigned v[8];
    auto item = [&](const int it) {
      mbar_wait(fulla + 8 * it, pha);
#pragma unroll
      for (int i = 0; i < 4; i++) ldsm_t(af[it][i], (ab + it * 16384 + (i >> 1) * 1024) ^ ((i & 1) << 5));
    };
    auto item_mma = [&](const int it) {
#pragma unroll
      for (int i = 0; i < 4; i++) mma16(e[2 * (it & 1) + (i & 1)], af[it][i], bb[(it & 2) + (i >> 1)].x, bb[(it & 2) + (i >> 1)].y);
    };
    unsigned t3 = sch.wt;
    PIN(t3);
    item(0); item_mma(0); item(1); item_mma(1);
    mbar_wait(bar0 + 8 * B_G);
#pragma unroll
    for (int i = 0; i < 8; i++) v[i] = ldx4(pa + i * 256);
    t3 += clock();
    uint32_t have2, have3 = 0;
    do have2 = mbar_test(fulla + 16, pha); while (!have2 && (int)((unsigned)clock() - t3) < 0);
    if (have2) {
      item(2); item_mma(2);
      do have3 = mbar_test(fulla + 24, pha); while (!have3 && (int)((unsigned)clock() - t3) < 0);
      if (have3) { item(3); item_mma(3); }
    }
    float y0, y1, df[4][4], st[2];
    uint32_t bz[4][2] = {};
    auto mm = [&](const int it, const int i) { mma16(df[2 * (it & 1) + (i & 1)], af[it][i], bz[(it & 2) + (i >> 1)][0], bz[(it & 2) + (i >> 1)][1]); };
    POLL {
      if (it_)
#pragma unroll
        for (int i = 0; i < 8; i++) v[i] = ldx4(pa + i * 256);
      y0 = ((bflo(v[0]) + bflo(v[1])) + (bflo(v[2]) + bflo(v[3]))) + ((bflo(v[4]) + bflo(v[5])) + (bflo(v[6]) + bflo(v[7])));
      y1 = ((bfhi(v[0]) + bfhi(v[1])) + (bfhi(v[2]) + bfhi(v[3]))) + ((bfhi(v[4]) + bfhi(v[5])) + (bfhi(v[6]) + bfhi(v[7])));
      const uint32_t zb = pack2(y0 * u2f(cf.x), y1 * u2f(cf.y));
#pragma unroll
      for (int s = 0; s < 4; s++) {
        const uint32_t w = __shfl_sync(~0u, zb, 8 * s + (lane & 7));
        bz[s][0] = (lane & 4) ? 0u : w; bz[s][1] = (lane & 4) ? w : 0u;
      }
      st[0] = y0 + y1; st[1] = y0 * y0 + y1 * y1;
      tred<1>(st, lane, 16);
#pragma unroll
      for (int i = 0; i < 4; i++) df[i][0] = df[i][1] = df[i][2] = df[i][3] = 0.f;
      mm(0, 0); mm(0, 1); mm(1, 0); mm(1, 1);
      st[0] += shx(st[0], 8);
      mm(0, 2); mm(0, 3); mm(1, 2); mm(1, 3);
      RETRY(or3(or3(lop_x3(v[0], v[1], par), lop_x3(v[2], v[3], par), lop_x3(v[4], v[5], par)), lop_x3(v[6], v[7], par), 0))
    }
    uint2 xq[8];
    if (warp == 0)
#pragma unroll
      for (int i = 0; i < 8; i++) xq[i] = ldx8(px + i * 512);
    if (have2) { mm(2, 0); mm(2, 1); mm(2, 2); mm(2, 3); }
    st[0] += shx(st[0], 4);
    st[0] += shx(st[0], 2);
    st[0] += shx(st[0], 1);
    sts4(a_st, st[0]);
    __syncwarp();
    arrive_n(bar0 + 8 * B_ST, lane == 0, 1);
    if (!have2) { item(2); item_mma(2); mm(2, 0); mm(2, 1); mm(2, 2); mm(2, 3); }
    if (!have3) { item(3); item_mma(3); }
    mm(3, 0); mm(3, 1); mm(3, 2); mm(3, 3);
    mbar_wait(bar0 + 8 * B_ST);
    float mean, rstd;
    {
      float4 u[4];
#pragma unroll
      for (int i = 0; i < 4; i++) u[i] = lds16(sb + O_SM + (352 + 4 * i) * 4);
      mean = (((u[0].x + u[0].y) + (u[0].z + u[0].w)) + ((u[1].x + u[1].y) + (u[1].z + u[1].w))) * (1.f / 512.f);
      const float sq = (((u[2].x + u[2].y) + (u[2].z + u[2].w)) + ((u[3].x + u[3].y) + (u[3].z + u[3].w))) * (1.f / 512.f);
      asm("rsqrt.approx.ftz.f32 %0, %1;" : "=f"(rstd) : "f"(fmaxf(sq - mean * mean, 0.f) + 1e-5f));
    }
    float A[4], r[4];
#pragma unroll
    for (int i = 0; i < 4; i++) {
      A[i] = (tq & 2) ? ((tq & 1) ? e[3][i] : e[2][i]) : ((tq & 1) ? e[1][i] : e[0][i]);
      r[i] = (tq & 2) ? ((tq & 1) ? df[3][i] : df[2][i]) : ((tq & 1) ? df[1][i] : df[0][i]);
    }
    sts4(a_rs, rstd * (r[0] + r[1]) + (A[1] - rstd * mean * A[0])); sts4(a_rs + 128, rstd * (r[2] + r[3]) + (A[3] - rstd * mean * A[2]));
    nbar(1, 256);
    if (wg) {
      const float4 g0 = lds16(a_rl), g1 = lds16(a_rl + 1024), u0 = lds16(a_rl + 512), u1 = lds16(a_rl + 1536);
      const float gg = bfr(((g0.x + g0.y) + (g0.z + g0.w)) + ((g1.x + g1.y) + (g1.z + g1.w)));
      const float uu = bfr(((u0.x + u0.y) + (u0.z + u0.w)) + ((u1.x + u1.y) + (u1.z + u1.w)));
      const float hh = bfr(gg * rcp(1.f + ex2(gg * (-2.302208198f - 0.1029432397f * gg * gg)))) * uu;
      send32(a_h, a_hb, hh, lane);
    } else spin_until(clock() + FDLY);
    uint32_t ad[8][4];
    mbar_wait(fullb + 8 * wg, phb);
#pragma unroll
    for (int i = 0; i < 8; i++) ldsm_t(ad[i], a_d + i * 2048);
    float x0, x1;
    if (warp == 0) {
      POLL {
        if (it_)
#pragma unroll
          for (int i = 0; i < 8; i++) xq[i] = ldx8(px + i * 512);
        unsigned bad = 0;
#pragma unroll
        for (int i = 0; i < 4; i++) bad = or3(bad, lop_x3(xq[i].x, xq[i].y, par), lop_x3(xq[i + 4].x, xq[i + 4].y, par));
        RETRY(bad)
      }
      x0 = x1 = 0.f;
#pragma unroll
      for (int i = 0; i < 8; i++) { x0 += u2f(xq[i].x); x1 += u2f(xq[i].y); }
      x0 *= 1.f / 7.f; x1 *= 1.f / 7.f;
    }
    mbar_wait(bar0 + 8 * B_HZ);
    float dd[4][4] = {};
#pragma unroll
    for (int i = 0; i < 4; i++) {
      const float4 hb = lds16(a_hl + i * 64);
      mma16(dd[(2 * i) & 3], ad[2 * i], __float_as_uint(hb.x), __float_as_uint(hb.y));
      mma16(dd[(2 * i + 1) & 3], ad[2 * i + 1], __float_as_uint(hb.z), __float_as_uint(hb.w));
    }
    sts4(a_t, (tq & 1) ? (dd[0][2] + dd[1][2]) + (dd[2][2] + dd[3][2]) : (dd[0][0] + dd[1][0]) + (dd[2][0] + dd[3][0]));
    if (warp) nbar_arrive(2, 256);
    else {
      nbar(2, 256);
      float t0, t1, t2, t3b;
      asm volatile("ld.shared.v2.f32 {%0, %1}, [%4]; ld.shared.v2.f32 {%2, %3}, [%4 + 256];"
                   : "=f"(t0), "=f"(t1), "=f"(t2), "=f"(t3b) : "r"(sb + O_SM + lane * 8) : "memory");
      t0 = bfhi(gbw.x) * (t0 + t2) + x0; t1 = bfhi(gbw.y) * (t1 + t3b) + x1;
      asm volatile("red.relaxed.gpu.global.add.noftz.bf16x2 [%0], %1;" ::"l"(po), "r"(pack2(t0, t1)) : "memory");
      if (f == 0 && tid == 0) stx4(&scr->cnt[0], epoch + 1);
    }
  }
}

static void make_sched(Sched& s) {
  const char* order = "FFAAbcFmmvog..d";
  const double dt = 4985 * 1e-3, dth = 4770 * 1e-3;
  const int nbig = NBIG;
  s.zero = 0; s.dth = (unsigned)(dth * 256 + 0.5);
  double t = 512 * dth + 0;
  int tile = 0, jm = 0;
  for (int i = 0; i < 3; i++) s.nr[i] = s.nt[i] = 0;
  auto add = [&](int c, int type, double step, int win, int b0, int tl) {
    s.r[c][s.nr[c]++] = make_uint2((unsigned)(t + 0.5) | (unsigned)(step + 0.5) << 16, type | win << 4 | (b0 + 64) << 8 | tl << 16);
    if (type == T_KV) s.nt[c]++;
  };
  const int w1 = 6, w2 = 4, wt = 6;
  for (const char* p = order; *p; p++) {
    const char c = *p;
    if (c == 'v' || c == 'o' || c == 'm') {
      const int ty = c == 'v' ? T_UV : c == 'o' ? T_WO : T_MOD;
      const double d = (c == 'm' ? 6200 : c == 'v' ? 5500 : 5600) * 1e-3;
      add(0, ty, 64 * d, wt, 0, c == 'm' ? jm : 0); add(1, ty, 64 * d, wt, 0, c == 'm' ? jm : 0);
      t += (c == 'm' ? 64 : 256) * d; jm += c == 'm';
    } else if (c == 'g' || c == 'd') {
      const double d = (c == 'g' ? 5500 : 5000) * 1e-3;
      add(2, c == 'g' ? T_GU : T_DN, 56 * d, wt, 64, 0);
      t += (c == 'g' ? 224 : 112) * d;
    } else if (c == '.') t += 100;
    else if (c == '-') t -= 100;
    else {
      const int na = c == 'F' ? 0 : c == 'C' || c == 'c' || c == 'a' ? nbig : 64, nf = c == 'A' || c == 'a' ? 0 : 56, n = na + nf;
      const int w = na && nf ? w2 : w1;
      const bool ff = c == 'b' || c == 'c';
      const int cf = c == 'c' ? 20 : 0, ca = cf * 7 / 5;
      t += 3 * ca;
      if (na) add(0, T_KV, n * dt - ca, w, ff ? -56 : 0, tile);
      t -= 3 * ca;
      if (na == 64) add(1, T_KV, n * dt, w, ff ? -56 : 0, tile);
      if (nf) add(2, T_KV, n * dt - cf, w, ff ? 64 : 64 - na, tile);
      tile += n; t += 4 * n * dt;
      s.t4 = (unsigned)t + 600;
    }
  }
  s.dt = (unsigned)(dt * 256 + 0.5); s.d4 = 1560 | 1200 << 16; s.d6 = 3190; s.wt = 250;
}

static void launch(void* const* d_in, void* d_out) {
  static TMaps tms;
  static Sched sch;
  static bool init = false;
  static void* scr = nullptr;
  if (!init) {
    void* fn = nullptr; cudaDriverEntryPointQueryResult qr;
    cudaGetDriverEntryPoint("cuTensorMapEncodeTiled", &fn, cudaEnableDefault, &qr);
    EncFn f = (EncFn)fn;
    const CUtensorMapSwizzle S64 = CU_TENSOR_MAP_SWIZZLE_64B, S128 = CU_TENSOR_MAP_SWIZZLE_128B;
    const CUtensorMapL2promotion P256 = CU_TENSOR_MAP_L2_PROMOTION_L2_256B;
    enc3d(f, &tms.m[0], d_in[2], 64, 512, 64, 8192, 128, 64, 128, 1, S128, CU_TENSOR_MAP_L2_PROMOTION_L2_128B);
    enc3d(f, &tms.m[1], d_in[3], 64, 512, 64, 8192, 128, 64, 64, 2, S128, P256);
    enc3d(f, &tms.m[2], d_in[1], 64, SK, 8, 1024, 128, 64, 64, 2, S128, P256);
    enc3d(f, &tms.m[3], d_in[11], 3072, 256, 2, 6144, 256 * 6144, 32, 256, 1, S64, CU_TENSOR_MAP_L2_PROMOTION_L2_128B);
    enc3d(f, &tms.m[4], d_in[4], 64, 512, 64, 8192, 128, 64, 128, 1, S128, CU_TENSOR_MAP_L2_PROMOTION_L2_128B);
    enc3d(f, &tms.m[5], d_in[5], 512, 128, 32, 1024, 128 * 1024, 64, 128, 1, S128, CU_TENSOR_MAP_L2_PROMOTION_L2_128B);
    enc3d(f, &tms.m[6], d_in[7], 1792, 256, 2, 3584, 256 * 3584, 32, 256, 1, S64, CU_TENSOR_MAP_L2_PROMOTION_L2_128B);
    enc3d(f, &tms.m[7], d_in[8], 1792, 256, 2, 3584, 256 * 3584, 32, 256, 1, S64, CU_TENSOR_MAP_L2_PROMOTION_L2_128B);
    enc3d(f, &tms.m[8], d_in[9], 512, 128, 14, 1024, 128 * 1024, 64, 128, 1, S128, CU_TENSOR_MAP_L2_PROMOTION_L2_128B);
    cudaFuncSetAttribute(fused_kernel, cudaFuncAttributeMaxDynamicSharedMemorySize, SMEM9);
    cudaGetSymbolAddress(&scr, g_scr);
    make_sched(sch);
    init = true;
  }
  fused_kernel<<<NCTA9, 384, SMEM9>>>((const bf16*)d_in[0], (const bf16*)d_in[10], (const bf16*)d_in[11], (bf16*)d_out, (Scratch*)scr, sch, tms);
}

static bool fits() {
  cudaFuncSetAttribute(fused_kernel, cudaFuncAttributeMaxDynamicSharedMemorySize, SMEM9);
  cudaLaunchConfig_t cfg = {};
  cfg.gridDim = dim3(NCTA9); cfg.blockDim = dim3(384); cfg.dynamicSmemBytes = SMEM9;
  cudaLaunchAttribute at[1];
  at[0].id = cudaLaunchAttributeClusterDimension; at[0].val.clusterDim.x = 8; at[0].val.clusterDim.y = 1; at[0].val.clusterDim.z = 1;
  cfg.attrs = at; cfg.numAttrs = 1;
  int n = 0;
  if (cudaOccupancyMaxActiveClusters(&n, fused_kernel, &cfg) != cudaSuccess) { (void)cudaGetLastError(); return false; }
  return n >= NCTA9 / 8;
}
}
#undef BAR_ARM
#undef BAR_ARRIVE
#undef BAR_INIT
#undef B_EMPTY
#undef B_FM
#undef B_FULL
#undef B_G
#undef B_G2
#undef B_H
#undef B_HZ
#undef B_LZ
#undef B_Q2
#undef B_QF
#undef B_ST
#undef B_TAB
#undef B_W
#undef B_WZ
#undef CNT_ADD
#undef DSC
#undef FDLY
#undef HI128
#undef HI64
#undef LANE0
#undef NBIG
#undef NCTA9
#undef NPE
#undef NPO
#undef NSL
#undef O_B
#undef O_BAR
#undef O_CTX
#undef O_DBG
#undef O_EP
#undef O_HW
#undef O_HZ
#undef O_LZ
#undef O_P
#undef O_Q
#undef O_R
#undef O_SILU
#undef O_SM
#undef O_X
#undef PIN
#undef PINL
#undef POLL
#undef QN
#undef RETRY
#undef SK
#undef SMEM9
#undef SMEM_BASE
#undef SPIN_MAX
#undef TAU
#undef VDLY
#undef VJ
#undef X16
#undef fbits

namespace v8 {
typedef __nv_bfloat16 bf16;
#define NCTA 128
#define SK 32768
#define SLOT 32768
#define NSLOT 6
#define OFF_WQ (2 * SLOT)
#define OFF_WUK (4 * SLOT)
#define OFF_Q 196608
#define OFF_P (OFF_Q + 16384)
#define OFF_B (OFF_P + 4096)
#define OFF_R4 (OFF_B + 2304)
#define OFF_SILU (OFF_R4 + 4096)
#define OFF_RA (OFF_SILU + 1024)
#define OFF_SM (OFF_RA + 1024)
#define OFF_BP (OFF_SM + 1792)
#define OFF_CO (OFF_BP + 1024)
#define OFF_BAR (OFF_CO + 1280)
#define OFF_MASK (OFF_BAR + 512)
#define OFF_DBG (OFF_MASK + 16)
#define SMEM_BYTES (OFF_DBG + 128)
#define OFF_MOD OFF_Q
#define OFF_UV (4 * SLOT)
#define OFF_O (5 * SLOT)
#define OFF_G 0
#define OFF_U 16384
#define OFF_D SLOT
#define OFF_XO (OFF_D + 16384)
#define FB_UK 4
#define FB_KV 6
#define FB_MOD 22
#define FB_UV 23
#define FB_O 25
#define FB_G 27
#define FB_D 29
#define EB 30
#define QB 50
#define XB 51
#define SPIN_MAX (1 << 20)
#define BACKOFF 40
#define RATE_NS 652
#define RATE_T0 200
#define RATE_TL 300
#define WINS 0x3222333
#define KVWIN 4
#define RATE_H 650
#define RATE_E 650
#define SMUL 9
#define NPRE0 1
#define NPRE1 3
#define HWIN 4
#define EWIN 3
#define WTEST 450
#define DLY5 650
#define DLY6 600
#define DLY7 600
#define P12(a, b, c, d, e, f, g, h, i, j, k, l) ((unsigned long long)(a) | (b) << 5 | (c) << 10 | (d) << 15 | (e) << 20 | (f) << 25 | \
  (unsigned long long)(g) << 30 | (unsigned long long)(h) << 35 | (unsigned long long)(i) << 40 | (unsigned long long)(j) << 45 | \
  (unsigned long long)(k) << 50 | (unsigned long long)(l) << 55)
#define ORDER0 P12(0, 1, 2, 3, 4, 5, 16, 6, 7, 8, 9, 10)
#define ORDER1 P12(11, 12, 13, 14, 15, 17, 18, 19, 20, 23, 21, 22)
#define TAIL_K 17
#define RS 16
template <int N> struct IC { static constexpr int value = N; };
struct TMaps { CUtensorMap m[9]; };

struct __align__(128) Scratch {
  uint4 xo[128 * 64 * RS];
  uint2 ml[32 * 64];
  unsigned h[8 * 256];
  unsigned qa[32 * 256];
  unsigned xc[128 * 64];
  unsigned xao[8 * 512];
  unsigned xf[112 * 512];
  unsigned xm[2048];
  unsigned cnt[5 * 32];
};
__device__ Scratch g_scr;
#define g_xo scr->xo
#define g_ml scr->ml
#define g_h scr->h
#define g_qa scr->qa
#define g_xc scr->xc
#define g_xao scr->xao
#define g_xf scr->xf
#define g_xm scr->xm
#define g_epoch scr->cnt[0]

__device__ __forceinline__ uint32_t s2u(const void* p) { return (uint32_t)__cvta_generic_to_shared(p); }
__device__ __forceinline__ float bflo(uint32_t u) { return __uint_as_float(u << 16); }
__device__ __forceinline__ float bfhi(uint32_t u) { return __uint_as_float(u & 0xffff0000u); }
__device__ __forceinline__ float u2f(uint32_t u) { return __uint_as_float(u); }
__device__ __forceinline__ void fma8(float* acc, uint4 v, float s) {
  acc[0] += s * bflo(v.x); acc[1] += s * bfhi(v.x); acc[2] += s * bflo(v.y); acc[3] += s * bfhi(v.y);
  acc[4] += s * bflo(v.z); acc[5] += s * bfhi(v.z); acc[6] += s * bflo(v.w); acc[7] += s * bfhi(v.w);
}
__device__ __forceinline__ uint32_t pack2(float a, float b) {
  __nv_bfloat162 p = __floats2bfloat162_rn(a, b); return *(uint32_t*)&p;
}
__device__ __forceinline__ float bfr(float v) { return bfhi(pack2(v, v)); }
__device__ __forceinline__ float silu_bf(float c) { return bfr(__fdividef(c, 1.f + __expf(-c))); }
#define fbits(v) ((__float_as_uint(v) & ~1u) | par)
__device__ __forceinline__ uint32_t pack2t(float a, float b, unsigned par) {
  const uint32_t ua = ((__float_as_uint(a) + ((par ^ 1) << 16)) & 0xFFFE0000u) | (par << 16);
  return __byte_perm(ua, pack2(b, b), 0x7632);
}
__device__ __forceinline__ void nbar(int id, int n) { asm volatile("bar.sync %0, %1;" ::"r"(id), "r"(n) : "memory"); }
__device__ __forceinline__ void nbar_arrive(int id, int n) { asm volatile("bar.arrive %0, %1;" ::"r"(id), "r"(n) : "memory"); }
__device__ __forceinline__ uint4 ldc16(const void* p) {
  uint4 v; asm volatile("ld.relaxed.cta.global.v4.u32 {%0,%1,%2,%3}, [%4];" : "=r"(v.x), "=r"(v.y), "=r"(v.z), "=r"(v.w) : "l"(p) : "memory"); return v;
}
__device__ __forceinline__ unsigned ldc4(const void* p) {
  unsigned v; asm volatile("ld.relaxed.cta.global.u32 %0, [%1];" : "=r"(v) : "l"(p) : "memory"); return v;
}
__device__ __forceinline__ uint4 ldx16(const void* p) {
  uint4 v; asm volatile("ld.relaxed.gpu.global.v4.u32 {%0,%1,%2,%3}, [%4];" : "=r"(v.x), "=r"(v.y), "=r"(v.z), "=r"(v.w) : "l"(p) : "memory"); return v;
}
__device__ __forceinline__ unsigned ldx4(const void* p) {
  unsigned v; asm volatile("ld.relaxed.gpu.global.u32 %0, [%1];" : "=r"(v) : "l"(p) : "memory"); return v;
}
__device__ __forceinline__ unsigned long long ldx64(const void* p) {
  unsigned long long v; asm volatile("ld.relaxed.gpu.global.u64 %0, [%1];" : "=l"(v) : "l"(p) : "memory"); return v;
}
__device__ __forceinline__ void stx16(void* p, uint4 v) {
  asm volatile("st.relaxed.gpu.global.v4.u32 [%0], {%1,%2,%3,%4};" ::"l"(p), "r"(v.x), "r"(v.y), "r"(v.z), "r"(v.w) : "memory");
}
__device__ __forceinline__ void stx8(void* p, uint2 v) { asm volatile("st.relaxed.gpu.global.v2.u32 [%0], {%1,%2};" ::"l"(p), "r"(v.x), "r"(v.y) : "memory"); }
__device__ __forceinline__ void stx4(void* p, unsigned v) { asm volatile("st.relaxed.gpu.global.u32 [%0], %1;" ::"l"(p), "r"(v) : "memory"); }
__device__ __forceinline__ unsigned lop_x3(unsigned a, unsigned b, unsigned c) {
  unsigned d; asm("lop3.b32 %0, %1, %2, %3, 0x7E;" : "=r"(d) : "r"(a), "r"(b), "r"(c)); return d; }
#define X16(v) (lop_x3(v.x, v.y, par) | lop_x3(v.z, v.w, par))
#define X8(v) lop_x3(v.x, v.y, par)
#define RETRY(bad) if (!__any_sync(~0u, (bad) & 1) || ++it_ >= SPIN_MAX) break; __nanosleep(BACKOFF);
#define POLL _Pragma("unroll 1") for (int it_ = 0;;)
__device__ __forceinline__ void mbar_wait(uint32_t bar) {
  uint32_t ok; int it = 0;
  do {
    asm volatile("{.reg .pred p; mbarrier.try_wait.parity.shared::cta.b64 p, [%1], 0; selp.u32 %0,1,0,p;}"
                 : "=r"(ok) : "r"(bar) : "memory");
  } while (!ok && ++it < SPIN_MAX);
}
__device__ __forceinline__ float ex2(float v) { float r; asm("ex2.approx.ftz.f32 %0, %1;" : "=f"(r) : "f"(v)); return r; }
__device__ __forceinline__ float rcp(float v) { float r; asm("rcp.approx.ftz.f32 %0, %1;" : "=f"(r) : "f"(v)); return r; }
__device__ __forceinline__ void mma16(float* d, const uint32_t* a, uint32_t b0, uint32_t b1) {
  asm volatile("mma.sync.aligned.m16n8k16.row.col.f32.bf16.bf16.f32 {%0,%1,%2,%3}, {%4,%5,%6,%7}, {%8,%9}, {%0,%1,%2,%3};"
               : "+f"(d[0]), "+f"(d[1]), "+f"(d[2]), "+f"(d[3]) : "r"(a[0]), "r"(a[1]), "r"(a[2]), "r"(a[3]), "r"(b0), "r"(b1));
}
__device__ __forceinline__ float4 lds16(uint32_t a) {
  float4 v; asm volatile("ld.shared.v4.f32 {%0,%1,%2,%3}, [%4];" : "=f"(v.x), "=f"(v.y), "=f"(v.z), "=f"(v.w) : "r"(a) : "memory"); return v;
}
__device__ __forceinline__ void ldsm_t(uint32_t* r, uint32_t a) {
  asm volatile("ldmatrix.sync.aligned.m8n8.x4.trans.shared.b16 {%0,%1,%2,%3}, [%4];" : "=r"(r[0]), "=r"(r[1]), "=r"(r[2]), "=r"(r[3]) : "r"(a) : "memory");
}
__device__ __forceinline__ void ldsm(uint32_t* r, uint32_t a) {
  asm volatile("ldmatrix.sync.aligned.m8n8.x4.shared.b16 {%0,%1,%2,%3}, [%4];" : "=r"(r[0]), "=r"(r[1]), "=r"(r[2]), "=r"(r[3]) : "r"(a) : "memory");
}
template <int N>
__device__ __forceinline__ void tred(float* a, int lane, int m) {
  const bool hi = lane & m;
#pragma unroll
  for (int i = 0; i < N; i++) {
    float send = hi ? a[i] : a[i + N], keep = hi ? a[i + N] : a[i];
    a[i] = keep + __shfl_xor_sync(~0u, send, m);
  }
}
template <int N>
__device__ __forceinline__ void tmax(float* a, int lane, int m) {
  const bool hi = lane & m;
#pragma unroll
  for (int i = 0; i < N; i++) {
    float send = hi ? a[i] : a[i + N], keep = hi ? a[i + N] : a[i];
    a[i] = fmaxf(keep, __shfl_xor_sync(~0u, send, m));
  }
}
__device__ __forceinline__ void arrive2(uint32_t bar, uint32_t rbar, bool local, bool remote) {
  asm volatile("{.reg .pred p, q; setp.ne.s32 p, %2, 0; setp.ne.s32 q, %3, 0; @p mbarrier.arrive.shared::cta.b64 _, [%0];\n"
               "@q mbarrier.arrive.relaxed.cluster.shared::cluster.b64 _, [%1];}" ::"r"(bar), "r"(rbar), "r"((int)local), "r"((int)remote) : "memory");
}
__device__ __forceinline__ unsigned long long stream_policy() {
  unsigned long long p;
  asm volatile("createpolicy.fractional.L2::evict_first.b64 %0, 1.0;" : "=l"(p));
  return p;
}
__device__ __forceinline__ void tma3d(uint32_t dst, const CUtensorMap* tm, uint32_t bar, int c0, int c1, int c2) {
  asm volatile("cp.async.bulk.tensor.3d.shared::cluster.global.mbarrier::complete_tx::bytes.L2::cache_hint [%0], [%1, {%3, %4, %5}], [%2], %6;"
               ::"r"(dst), "l"(tm), "r"(bar), "r"(c0), "r"(c1), "r"(c2), "l"(stream_policy()) : "memory");
}
__device__ __forceinline__ void st_async2(uint32_t dst, uint32_t bar, float v0, float v1) {
  asm volatile("st.async.shared::cluster.mbarrier::complete_tx::bytes.v2.f32 [%0], {%1, %2}, [%3];" ::"r"(dst), "f"(v0), "f"(v1), "r"(bar) : "memory");
}
__device__ __forceinline__ void st_pair(int mode, uint32_t dst, uint32_t bar, float v0, float v1) {
  asm volatile("{.reg .pred p, q; setp.eq.s32 p, %4, 1; setp.eq.s32 q, %4, 2; @p st.shared.v2.f32 [%0], {%1, %2};\n"
               "@q st.async.shared::cluster.mbarrier::complete_tx::bytes.v2.f32 [%0], {%1, %2}, [%3];}"
               ::"r"(dst), "f"(v0), "f"(v1), "r"(bar), "r"(mode) : "memory");
}
__device__ __forceinline__ void spin_until(unsigned t) { while ((int)((unsigned)clock() - t) < 0) {} }
__device__ __forceinline__ unsigned wait_until(unsigned t) {
  unsigned now;
  for (;;) {
    asm volatile("mov.u32 %0, %%globaltimer_lo;" : "=r"(now));
    if ((int)(now - t) >= 0) break;
  }
  return now;
}
#define PIN(x) asm volatile("" : "+r"(x))
#define PINL(x) asm volatile("" : "+l"(x))
#define BAR_ARRIVE(i) asm volatile("mbarrier.arrive.shared::cta.b64 _, [%0];" ::"r"(bar0 + 8 * (i)) : "memory")
#define CNT_ADD(c) asm volatile("red.relaxed.gpu.global.add.u32 [%0], 1;" ::"l"(scr->cnt + (c)) : "memory")
#define BAR_INIT(i, cnt) asm volatile("mbarrier.init.shared::cta.b64 [%0], %1;" ::"r"(bar0 + 8 * (i)), "r"(cnt) : "memory")
#define BAR_ARM(i, bytes) asm volatile("mbarrier.arrive.expect_tx.shared::cta.b64 _, [%0], %1;" ::"r"(bar0 + 8 * (i)), "r"(bytes) : "memory")

__device__ __forceinline__ void tail(unsigned char* smem, Scratch* __restrict__ scr, const bf16* __restrict__ x, bf16* __restrict__ out,
                                     const unsigned par, const unsigned epoch, const int warp) {
  int tid, b;
  asm volatile("mov.u32 %0, %%tid.x;" : "=r"(tid));
  asm volatile("mov.u32 %0, %%ctaid.x;" : "=r"(b));
  const int lane = tid & 31, g = lane >> 2, tq = lane & 3;
  const uint32_t sb = __shfl_sync(~0u, s2u(smem), 0), bar0 = sb + OFF_BAR;
  float* s_sm = (float*)(smem + OFF_SM);
  const int prow = 4 * (lane >> 4) + ((lane & 7) >> 1) + 8 * (lane & 1);
  const float* s_co = (const float*)(smem + OFF_CO);
  const int opos = (b & 15) * 32 + (lane & 16) + 2 * (lane & 6) + ((lane >> 2) & 2) + (lane & 1);
  const float xv = b < 16 ? __bfloat162float(x[(b & 15) * 32 + lane]) : 0.f;
  const int rk = b & 1, ob = 32 * rk + ((b >> 1) & 31);
  uint32_t psb;
  asm volatile("mapa.shared::cluster.u32 %0, %1, %2;" : "=r"(psb) : "r"(sb), "r"(rk ^ 1));
  {
    uint32_t a[8][4];
    {
      const int rg = tid >> 4;
      const uint4* src = g_xo + ((size_t)b * 64 + rg) * RS;
      const uint32_t dst = sb + OFF_XO + rg * 256 + (((tid & 15) ^ (rg & 7)) << 4);
      unsigned long long todo = 0x0001000100010001ull;
#pragma unroll 1
      for (int it = 0; it < SPIN_MAX * 16; it++) {
        unsigned long long mk = *(volatile unsigned long long*)(smem + OFF_MASK);
        const unsigned long long nw = (mk >> rg) & todo;
        todo ^= nw;
#pragma unroll
        for (int i = 0; i < 4; i++)
          if (nw >> (16 * i) & 1)
            asm volatile("cp.async.cg.shared.global [%0], [%1], 16;" ::"r"(dst + i * 4096), "l"(src + i * 16 * RS + (tid & 15)) : "memory");
        if (!__any_sync(~0u, todo != 0)) break;
      }
      asm volatile("cp.async.mbarrier.arrive.noinc.shared::cta.b64 [%0];" ::"r"(bar0 + 8 * (XB + 2)) : "memory");
    }
    mbar_wait(bar0 + 8 * FB_UV); mbar_wait(bar0 + 8 * (FB_UV + 1));
    const uint32_t ab = sb + OFF_UV + (warp >> 2) * 8192 + (8 * (lane >> 4) + (lane & 7)) * 128 + (((2 * (warp & 3) + ((lane >> 3) & 1)) ^ (lane & 7)) << 4);
#pragma unroll
    for (int s = 0; s < 8; s++) ldsm_t(a[s], ab + (s >> 2) * 16384 + (s & 3) * 2048);
    const int chn = 2 * warp + (tq & 1);
    uint32_t a_b = sb + OFF_B + (tq >> 1) * 272 + (32 * (chn >> 2) + 8 * (g >> 1) + 2 * (chn & 3) + (g & 1)) * 2;
    uint32_t a_bq = sb + OFF_B + (lane & 1) * 272 + (lane >> 3) * 16;
    unsigned* p_c = g_xc + (b >> 2) * 256 + warp * 32 + (b & 3) * 8 + (g & 3) * 2 + (g >> 2);
    PIN(a_b); PIN(a_bq); PINL(p_c);
    mbar_wait(bar0 + 8 * (XB + 6));
    uint32_t wb[8];
#pragma unroll
    for (int s = 0; s < 8; s++) wb[s] = *(const uint32_t*)(smem + OFF_RA + (4 * s + tq) * 4);
    const float invL = *(const float*)(smem + OFF_RA + 128);
    float ov;
    POLL {
      mbar_wait(bar0 + 8 * (XB + 2));
      uint32_t ao[4][4];
#pragma unroll
      for (int s = 0; s < 4; s++)
        ldsm_t(ao[s], sb + OFF_XO + (16 * s + 8 * (lane >> 4) + (lane & 7)) * 256 + (((2 * warp + ((lane >> 3) & 1)) ^ (lane & 7)) << 4));
      float d[4][4] = {};
#pragma unroll
      for (int s = 0; s < 4; s++) mma16(d[s], ao[s], wb[2 * s], wb[2 * s + 1]);
      const unsigned p2 = par * 0x10001u;
      unsigned bad = 0;
#pragma unroll
      for (int s = 0; s < 4; s++) bad |= lop_x3(ao[s][0], ao[s][1], p2) | lop_x3(ao[s][2], ao[s][3], p2);
      bad = g == 0 ? bad | (bad >> 16) : 0u;
      ov = (tq & 1) ? (d[0][2] + d[1][2]) + (d[2][2] + d[3][2]) : (d[0][0] + d[1][0]) + (d[2][0] + d[3][0]);
      if (__builtin_expect(!__any_sync(~0u, bad & 1) || ++it_ >= SPIN_MAX, 1)) break;
#pragma unroll
      for (int i = 0; i < 4; i++)
        asm volatile("cp.async.cg.shared.global [%0], [%1], 16;"
                     ::"r"(sb + OFF_XO + ((lane >> 1) + 16 * i) * 256 + (((2 * warp + (lane & 1)) ^ ((lane >> 1) & 7)) << 4)),
                       "l"(g_xo + ((size_t)b * 64 + (lane >> 1) + 16 * i) * RS + 2 * warp + (lane & 1)) : "memory");
      asm volatile("cp.async.wait_all;" ::: "memory");
      __syncwarp();
    }
    {
      const float lo = ov - bfhi(__float_as_uint(ov));
      asm volatile("st.shared.u16 [%0], %1;" ::"r"(a_b), "h"((unsigned short)((tq & 2) ? pack2(lo, lo) : __float_as_uint(ov) >> 16)) : "memory");
    }
    nbar(1, 256);
    float d[4][4] = {};
#pragma unroll
    for (int y = 0; y < 4; y++) {
      uint32_t bq[4];
      ldsm(bq, a_bq + 64 * y);
      mma16(d[(2 * y) & 3], a[2 * y], bq[0], bq[1]); mma16(d[(2 * y + 1) & 3], a[2 * y + 1], bq[2], bq[3]);
    }
    const float r0 = ((d[0][0] + d[0][1]) + (d[1][0] + d[1][1])) + ((d[2][0] + d[2][1]) + (d[3][0] + d[3][1]));
    const float r1 = ((d[0][2] + d[0][3]) + (d[1][2] + d[1][3])) + ((d[2][2] + d[2][3]) + (d[3][2] + d[3][3]));
    if (tq == 0) stx4(p_c, pack2t(r0 * invL, r1 * invL, par));
  }
  unsigned tpub = clock();
  mbar_wait(bar0 + 8 * (XB + 4));
  const float gav = s_co[256 + (opos & 31)];
  const float gbv = s_co[288 + (lane & 4) + 2 * (lane & 1) + ((lane >> 1) & 1)];
  float4 cf[2];
#pragma unroll
  for (int s = 0; s < 2; s++) cf[s] = *(const float4*)(s_co + 32 * warp + 16 * s + 4 * tq);
  {
    uint32_t a[2][4][4];
    mbar_wait(bar0 + 8 * (FB_O + (warp >> 2)));
    const uint32_t ab = sb + OFF_O + (32 * warp + prow) * 128 + ((((lane >> 3) & 1) ^ (prow & 7)) << 4);
#pragma unroll
    for (int i = 0; i < 8; i++) ldsm_t(a[i >> 2][i & 3], (ab + (i >> 2) * 2048) ^ ((i & 3) << 5));
    uint4 v;
    const unsigned* pc = g_xc + (4 * (b >> 4) + 2 * rk + (warp >> 2)) * 256 + 64 * (warp & 3) + 2 * lane;
    uint32_t ro = ((tq >> 1) == rk ? sb : psb) + OFF_P + (8 * (tq & 1) + g) * 144 + (8 * rk + warp) * 8;
    uint32_t a_q = sb + OFF_P + (8 * (lane >> 4) + (lane & 7)) * 144;
    unsigned* p_ao = g_xao + (b >> 5) * 1024 + (opos >> 4) * 32 + (b & 16) + (opos & 15);
    PIN(ro); PIN(a_q); PINL(p_ao); PINL(pc);
    spin_until(tpub + DLY5);
    POLL {
      const unsigned long long u0 = ldx64(pc);
      v.x = (unsigned)u0; v.y = u0 >> 32;
      RETRY(X8(v))
    }
    v.z = lane & 16 ? v.x : 0u; v.w = lane & 16 ? v.y : 0u;
    if (lane & 16) v.x = v.y = 0u;
    float d[4][4] = {};
#pragma unroll
    for (int mt = 0; mt < 4; mt++) mma16(d[mt], a[0][mt], v.x, v.y);
#pragma unroll
    for (int mt = 0; mt < 4; mt++) mma16(d[mt], a[1][mt], v.z, v.w);
    float r[8];
#pragma unroll
    for (int i = 0; i < 8; i++) r[i] = d[i >> 1][2 * (i & 1)] + d[i >> 1][2 * (i & 1) + 1];
    tred<4>(r, lane, 2); tred<2>(r, lane, 1);
    st_pair((tq >> 1) == rk ? 1 : 2, ro, psb + OFF_BAR + 8 * (XB + 3), r[0], r[1]);
    __syncwarp();
    if (lane == 0) BAR_ARRIVE(XB + 3);
    if (warp == 0) {
      mbar_wait(bar0 + 8 * (XB + 3));
      float p[8];
#pragma unroll
      for (int i = 0; i < 8; i++) {
        const float4 q = lds16(a_q + i * 16);
        p[i] = (lane & 8) ? q.y + q.w : q.x + q.z;
      }
      const float t = ((p[0] + p[1]) + (p[2] + p[3])) + ((p[4] + p[5]) + (p[6] + p[7]));
      stx4(p_ao, fbits(gav * t + xv));
    }
  }
  tpub = clock();
  if (b < 112) {
    uint32_t af[2][4][4], ad[4][4];
    const uint32_t ab = sb + (32 * warp + 8 * (lane >> 4) + (lane & 7)) * 64 + ((((lane >> 3) & 1) ^ ((lane >> 1) & 3)) << 4);
    uint32_t ro = ((tq & 1) == rk ? sb : psb) + OFF_R4 + (8 * (tq >> 1) + g) * 176 + (10 * rk + warp) * 8;
    uint32_t a_q = sb + OFF_R4 + (8 * (lane >> 4) + (lane & 7)) * 176 + (lane & 8) * 10;
    uint32_t a_d = sb + OFF_D + warp * 2048 + (8 * (lane >> 4) + (lane & 7)) * 128 + ((((lane >> 3) & 1) ^ (lane & 7)) << 4);
    unsigned* p_f = g_xf + b * 512 + 64 * warp + 16 * tq + 2 * g;
    const unsigned* pa = g_xao + (g >> 1) * 1024 + 512 * rk + 64 * warp + 4 * (lane & 7);
    PIN(ro); PIN(a_q); PIN(a_d); PINL(p_f); PINL(pa);
    spin_until(tpub + DLY6);
    uint4 v[2];
    {
      bool have = false;
      POLL {
        v[0] = ldx16(pa); v[1] = ldx16(pa + 32);
        const unsigned t1 = (unsigned)clock() + WTEST;
        while (!have && (int)((unsigned)clock() - t1) < 0) {
          uint32_t ok;
          asm volatile("{.reg .pred p, q; mbarrier.test_wait.parity.shared::cta.b64 p, [%1], 0; mbarrier.test_wait.parity.shared::cta.b64 q, [%1+8], 0;\n"
                       "and.pred p, p, q; vote.sync.all.pred p, p, 0xffffffff; selp.u32 %0, 1, 0, p;}" : "=r"(ok) : "r"(bar0 + 8 * FB_G) : "memory");
          if (ok) {
#pragma unroll
            for (int i = 0; i < 8; i++) ldsm_t(af[i >> 2][i & 3], (ab + ((i & 2) ? OFF_U : OFF_G) + (i >> 2) * 1024) ^ ((i & 1) << 5));
            have = true;
          }
        }
        if (!__any_sync(~0u, (X16(v[0]) | X16(v[1])) & 1) || ++it_ >= SPIN_MAX) break;
      }
      float df[4][4] = {}, dg[2][4] = {};
      uint32_t zb[4];
      const uint32_t one = g == 0 ? 0x3F803F80u : 0u;
#pragma unroll
      for (int s = 0; s < 2; s++) {
        const uint32_t y0 = pack2(u2f(v[s].x), u2f(v[s].y)), y1 = pack2(u2f(v[s].z), u2f(v[s].w));
        const uint32_t ya[4] = {y0, one, y1, one};
        mma16(dg[s], ya, y0, y1);
        zb[2 * s] = pack2(u2f(v[s].x) * cf[s].x, u2f(v[s].y) * cf[s].y); zb[2 * s + 1] = pack2(u2f(v[s].z) * cf[s].z, u2f(v[s].w) * cf[s].w);
      }
      float st[2] = {(dg[0][2] + dg[0][3]) + (dg[1][2] + dg[1][3]), (dg[0][0] + dg[0][1]) + (dg[1][0] + dg[1][1])};
      if (!have) {
        mbar_wait(bar0 + 8 * FB_G); mbar_wait(bar0 + 8 * (FB_G + 1));
#pragma unroll
        for (int i = 0; i < 8; i++) ldsm_t(af[i >> 2][i & 3], (ab + ((i & 2) ? OFF_U : OFF_G) + (i >> 2) * 1024) ^ ((i & 1) << 5));
      }
#pragma unroll
      for (int i = 0; i < 8; i++) mma16(df[i & 3], af[i >> 2][i & 3], zb[2 * (i >> 2)], zb[2 * (i >> 2) + 1]);
#pragma unroll
      for (int o2 = 1; o2 < 4; o2 <<= 1) { st[0] += __shfl_xor_sync(~0u, st[0], o2); st[1] += __shfl_xor_sync(~0u, st[1], o2); }
#pragma unroll
      for (int o2 = 4; o2 < 32; o2 <<= 1) st[1] += __shfl_xor_sync(~0u, st[1], o2);
      float r[8];
#pragma unroll
      for (int i = 0; i < 8; i++) r[i] = df[i >> 1][2 * (i & 1)] + df[i >> 1][2 * (i & 1) + 1];
      tred<4>(r, lane, 2); tred<2>(r, lane, 1);
      const int md = (tq & 1) == rk ? 1 : 2;
      st_pair(md, ro, psb + OFF_BAR + 8 * (XB + 5), r[0], r[1]);
      st_pair(lane < 2 ? md : 0, ro + 16 * 176, psb + OFF_BAR + 8 * (XB + 5), st[0], st[1]);
      __syncwarp();
      if (lane == 0) BAR_ARRIVE(XB + 5);
      mbar_wait(bar0 + 8 * FB_D);
#pragma unroll
      for (int mt = 0; mt < 4; mt++)
        ldsm_t(ad[mt], a_d ^ (mt << 5));
    }
    mbar_wait(bar0 + 8 * (XB + 5));
    {
      float4 q[5], u[8];
#pragma unroll
      for (int i = 0; i < 5; i++) q[i] = lds16(a_q + i * 16);
#pragma unroll
      for (int i = 0; i < 8; i++) u[i] = *(const float4*)(smem + OFF_R4 + 16 * 176 + (i >> 2) * 80 + (i & 3) * 16);
      float p[6] = {((q[0].x + q[0].z) + (q[1].x + q[1].z)) + ((q[2].x + q[2].z) + (q[3].x + q[3].z)), q[4].x, q[4].z,
                    ((q[0].y + q[0].w) + (q[1].y + q[1].w)) + ((q[2].y + q[2].w) + (q[3].y + q[3].w)), q[4].y, q[4].w};
      tred<3>(p, lane, 8);
      const float P = p[0], A1 = p[1], A2 = p[2];
      const float mean = (((u[0].x + u[0].z) + (u[1].x + u[1].z)) + ((u[2].x + u[2].z) + (u[3].x + u[3].z)) +
                          ((u[4].x + u[4].z) + (u[5].x + u[5].z)) + ((u[6].x + u[6].z) + (u[7].x + u[7].z))) * (1.f / 512.f);
      const float sq = (((u[0].y + u[0].w) + (u[1].y + u[1].w)) + ((u[2].y + u[2].w) + (u[3].y + u[3].w)) +
                         ((u[4].y + u[4].w) + (u[5].y + u[5].w)) + ((u[6].y + u[6].w) + (u[7].y + u[7].w))) * (1.f / 512.f);
      float rstd;
      asm("rsqrt.approx.ftz.f32 %0, %1;" : "=f"(rstd) : "f"(fmaxf(sq - mean * mean, 0.f) + 1e-5f));
      const float gg = bfr(rstd * (P - mean * A1) + A2);
      const float uu = __shfl_xor_sync(~0u, gg, 16);
      const float hh = bfr(gg * rcp(1.f + ex2(gg * (-2.302208198f - 0.1029432397f * gg * gg)))) * uu;
      const uint32_t hw = pack2(hh, __shfl_down_sync(~0u, hh, 1));
      const uint32_t b0 = __shfl_sync(~0u, hw, 2 * tq), b1 = __shfl_sync(~0u, hw, 2 * tq + 8);
      float f0 = 0, f1 = 0;
#pragma unroll
      for (int mt = 0; mt < 4; mt++) {
        float dd[4] = {0, 0, 0, 0};
        mma16(dd, ad[mt], b0, b1);
        if (tq == mt) { f0 = dd[0]; f1 = dd[2]; }
      }
      stx8(p_f, make_uint2(fbits(f0), fbits(f1)));
    }
    tpub = clock();
    if (b < 64 && warp == (b >> 3)) {
      const uint4 y = (b & 4) ? v[1] : v[0];
      float a4[4] = {u2f(y.x), u2f(y.y), u2f(y.z), u2f(y.w)};
      tred<2>(a4, lane, 16); tred<1>(a4, lane, 8);
      a4[0] += __shfl_xor_sync(~0u, a4[0], 4);
      if (!(lane & 4)) s_sm[416 + 8 * (lane >> 4) + 2 * tq + ((lane >> 3) & 1)] = a4[0];
      if (warp == 7) nbar_arrive(2, 256);
    } else if (b < 64 && warp == 7) nbar_arrive(2, 256);
    if (b < 64 && warp < 7) {
      uint4 v;
      const unsigned* pf = g_xf + (tid >> 1) * 512 + 8 * ob + 4 * (tid & 1);
      const int col = 16 * (ob >> 1) + 4 * (ob & 1) + ((tid >> 1) & 3) + 8 * (tid & 1);
      bf16* po = out + col;
      PINL(po); PINL(pf);
      spin_until(tpub + DLY7);
      POLL { v = ldx16(pf); RETRY(X16(v)) }
      float f[4] = {u2f(v.x), u2f(v.y), u2f(v.z), u2f(v.w)};
      tred<2>(f, lane, 16); tred<1>(f, lane, 8);
      f[0] += __shfl_xor_sync(~0u, f[0], 4); f[0] += __shfl_xor_sync(~0u, f[0], 2);
      if (!(lane & 6)) s_sm[352 + warp * 8 + 4 * (lane & 1) + (lane >> 3)] = f[0];
      nbar(2, 256);
      if (tid < 8) {
        const float* q = s_sm + 352 + tid;
        const float t = ((q[0] + q[8]) + (q[16] + q[24])) + ((q[32] + q[40]) + q[48]);
        *po = __float2bfloat16(s_sm[416 + (col & 15)] + bfr(gbv * bfr(t)));
        if (b == 0 && tid == 0) stx4(&g_epoch, epoch + 1);
      }
    }
  }
}

__global__ void __cluster_dims__(2, 1, 1) __launch_bounds__(384, 1)
fused_kernel(const bf16* __restrict__ x, const bf16* __restrict__ cvec, const bf16* __restrict__ w_mod, bf16* __restrict__ out,
             Scratch* __restrict__ scr, const __grid_constant__ TMaps tms) {
  extern __shared__ __align__(1024) unsigned char smem[];
  const int tid = threadIdx.x, warp = __shfl_sync(~0u, tid >> 5, 0), lane = tid & 31;
  const int b = blockIdx.x, rk = b & 1, pr = b >> 1, hd = b >> 2;
  uint32_t sb = s2u(smem), bar0 = sb + OFF_BAR;

  unsigned gt_start;
  asm volatile("mov.u32 %0, %%globaltimer_lo;" : "=r"(gt_start));
  const int g = lane >> 2, tq = lane & 3;
  const int arow = 64 * (b >> 4) + ((tid & 255) >> 3);
  uint4 wm0, wm1;
  uint32_t c0w, c1w;
  if (warp < 8) {
    const bf16* wa = w_mod + (size_t)arow * 3072 + (lane & 4) * 128 + 32 * (b & 15) + 8 * tq;
    wm0 = ldx16(wa); wm1 = ldx16(wa + 32 * 3072);
    c0w = ldc4(cvec + (arow & ~1)); c1w = ldc4(cvec + (arow & ~1) + 32);
  }
  const unsigned t_off = gt_start + RATE_T0;
  if (warp == 11) {
    if (lane == 0) {
#pragma unroll
      for (int i = 0; i < FB_KV; i++) { BAR_INIT(i, 1); BAR_ARM(i, 16384); }
    }
    __syncwarp();
    asm volatile("fence.mbarrier_init.release.cluster;" ::: "memory");
    asm volatile("barrier.cluster.arrive.relaxed.aligned;" ::: "memory");
#pragma unroll 1
    for (int i = 0; i < FB_KV; i++) {
      if (i >= HWIN) mbar_wait(bar0 + 8 * (i - HWIN));
      wait_until(t_off + (i < 4 ? 2 * i + ((b >> 1) & 1) : 4 * i - 8 + (b & 3)) * (RATE_H / 4));
      if (lane == 0) {
        if (i < 4) tma3d(sb + OFF_WQ + i * 16384, &tms.m[0], bar0 + 8 * i, 0, i * 128, 2 * hd + rk);
        else tma3d(sb + OFF_WQ + i * 16384, &tms.m[1], bar0 + 8 * i, 0, (b & 3) * 128 + (i - 4) * 64, 2 * hd);
      }
      __syncwarp();
    }
  }
  if (warp == 10) {
    const uint4 xa = ldc16(x + 16 * lane), xb = ldc16(x + 16 * lane + 8);
    const unsigned ep = ldc4(&g_epoch);
    float xv[16] = {bflo(xa.x), bfhi(xa.x), bflo(xa.y), bfhi(xa.y), bflo(xa.z), bfhi(xa.z), bflo(xa.w), bfhi(xa.w),
                    bflo(xb.x), bfhi(xb.x), bflo(xb.y), bfhi(xb.y), bflo(xb.z), bfhi(xb.z), bflo(xb.w), bfhi(xb.w)};
    float s = 0;
#pragma unroll
    for (int i = 0; i < 16; i++) s += xv[i];
#pragma unroll
    for (int o = 16; o; o >>= 1) s += __shfl_xor_sync(~0u, s, o);
    const float mean = s * (1.f / 512.f);
    s = 0;
#pragma unroll
    for (int i = 0; i < 16; i++) { xv[i] -= mean; s += xv[i] * xv[i]; }
#pragma unroll
    for (int o = 16; o; o >>= 1) s += __shfl_xor_sync(~0u, s, o);
    const float rstd = rsqrtf(s * (1.f / 512.f) + 1e-5f);
    if ((lane >> 1) == (b & 15))
#pragma unroll
      for (int i = 0; i < 4; i++)
        *(float4*)(smem + OFF_SM + (256 + (lane & 1) * 16 + 4 * i) * 4) = make_float4(xv[4 * i] * rstd, xv[4 * i + 1] * rstd, xv[4 * i + 2] * rstd, xv[4 * i + 3] * rstd);
    if (lane == 0) *(volatile unsigned*)(smem + OFF_MASK + 8) = ep;
    nbar_arrive(1, 288);
  }
  if (warp >= 8) {
    asm volatile("setmaxnreg.dec.sync.aligned.u32 72;");
    if (tid == 288) {
#pragma unroll
      for (int q = FB_KV; q < FB_KV + 16; q++) { BAR_INIT(q, 1); BAR_ARM(q, 32768); }
    }
    if (tid == 320) {
#pragma unroll
      for (int q = 0; q <= 13 + NSLOT; q++) BAR_INIT(EB + q, q == 0 ? 4 : q < 5 ? 16 : q < 16 ? 12 : 6);
    }
    if (tid == 256) {
#pragma unroll
      for (int q = FB_MOD; q <= FB_D; q++) { BAR_INIT(q, 1); BAR_ARM(q, 16384); }
      BAR_INIT(QB, 9); BAR_ARM(QB, 1024);
#pragma unroll
      for (int q = 0; q < 7; q++) BAR_INIT(XB + q, q == 2 ? 256 : q == 5 || q == 3 ? 9 : 1);
      BAR_ARM(XB + 3, 1024);
      BAR_ARM(XB + 5, 1024 + 64 + 512);
      *(volatile unsigned long long*)(smem + OFF_MASK) = 0;
    }
    if (warp != 11) {
      __syncwarp();
      asm volatile("fence.mbarrier_init.release.cluster;" ::: "memory");
      __threadfence_block();
      asm volatile("barrier.cluster.arrive.relaxed.aligned;" ::: "memory");
    }
    if (warp == 11) {
      asm volatile("barrier.cluster.wait.acquire.aligned;" ::: "memory");
      const unsigned epoch = *(volatile unsigned*)(smem + OFF_MASK + 8), par = (epoch + 1) & 1;
      mbar_wait(bar0 + 8 * (FB_KV + 15));
      for (int it = 0; ldx4(scr->cnt + 96 + 32 * (b >> 6)) != (epoch + 1) * 64 && it < SPIN_MAX; it++) {}
      uint4 hh;
      POLL { hh = ldx16(g_ml + (b >> 2) * 64 + 2 * lane); RETRY(X16(hh)) }
      int mi = __float_as_int(fmaxf(u2f(hh.x), u2f(hh.z)));
      mi ^= (mi >> 31) & 0x7fffffff;
      mi = __reduce_max_sync(~0u, mi);
      mi ^= (mi >> 31) & 0x7fffffff;
      const float M = __int_as_float(mi);
      const uint32_t wp = pack2(ex2(u2f(hh.x) - M), ex2(u2f(hh.z) - M));
      float L = bflo(wp) * u2f(hh.y) + bfhi(wp) * u2f(hh.w);
#pragma unroll
      for (int o2 = 16; o2; o2 >>= 1) L += __shfl_xor_sync(~0u, L, o2);
      *(uint32_t*)(smem + OFF_RA + lane * 4) = wp;
      if (lane == 0) *(float*)(smem + OFF_RA + 128) = rcp(L);
      __syncwarp();
      if (lane == 0) BAR_ARRIVE(XB + 6);
    }
    if (warp == 10) {
      if (lane < 8) asm volatile("prefetch.tensormap [%0];" ::"l"(&tms.m[lane + 1]) : "memory");
      asm volatile("barrier.cluster.wait.acquire.aligned;" ::: "memory");
      const unsigned epoch = *(volatile unsigned*)(smem + OFF_MASK + 8);
#pragma unroll 1
      for (int e = 0; e < 2; e++) {
        for (int it = 0; ldx4(scr->cnt + (e ? 2 + rk : 1)) != (epoch + 1) * (e ? 64 : 128) && it < SPIN_MAX; it++) {}
        if (lane == 0) BAR_ARRIVE(XB + e);
      }
      mbar_wait(bar0 + 8 * (FB_KV + 14));
      unsigned long long m = 0;
#pragma unroll 1
      for (int it = 0; ~m && it < SPIN_MAX; it++) {
        m = ldx64(scr->cnt + 32 + 32 * (b >> 6)) ^ ((epoch & 1) ? ~0ull : 0ull);
        if (lane == 0) *(volatile unsigned long long*)(smem + OFF_MASK) = m;
      }
    }
    if (warp == 9) {
      asm volatile("barrier.cluster.wait.acquire.aligned;" ::: "memory");
      const unsigned epoch = *(volatile unsigned*)(smem + OFF_MASK + 8);
      const unsigned par = (epoch + 1) & 1, inv = par ^ 1;
      const uint4 inv4 = make_uint4(inv, inv, inv, inv);
      mbar_wait(bar0 + 8 * FB_KV);
#pragma unroll 2
      for (int k = 0; k < 8; k++) {
        const uint32_t cp = ldc4(cvec + 2 * (lane + 32 * k));
        *(uint32_t*)(smem + OFF_SILU + (lane + 32 * k) * 4) = pack2(silu_bf(bflo(cp)), silu_bf(bfhi(cp)));
      }
      __syncwarp();
      mbar_wait(bar0 + 8 * FB_MOD);
      const uint32_t ab = sb + OFF_MOD + (8 * (lane >> 4) + (lane & 7)) * 32 + ((((lane >> 3) ^ (lane >> 2)) & 1) << 4);
      float d[4][4] = {};
#pragma unroll 2
      for (int s4 = 0; s4 < 8; s4++)
#pragma unroll
        for (int s = 0; s < 4; s++) {
          uint32_t a[4];
          const uint32_t* ps = (const uint32_t*)(smem + OFF_SILU) + 32 * s4 + 8 * s + tq;
          ldsm_t(a, ab + (4 * s4 + s) * 512); mma16(d[s], a, ps[0], ps[4]);
        }
      const float t = (tq & 1) ? (d[0][2] + d[1][2]) + (d[2][2] + d[3][2]) : (d[0][0] + d[1][0]) + (d[2][0] + d[3][0]);
      if (tq < 2) stx4(g_xm + b * 16 + 2 * (g & 6) + 2 * tq + (g & 1), fbits(bfr(t)));
      __syncwarp();
      if (lane == 0) CNT_ADD(6);
      mbar_wait(bar0 + 8 * (FB_KV + 8));
      if (lane < 16) stx16(g_xc + (b >> 2) * 256 + (lane >> 1) * 32 + (b & 3) * 8 + (lane & 1) * 4, inv4);
      if (lane < 8) stx16(g_xao + (b >> 5) * 1024 + (b & 15) * 64 + (lane & 4) * 8 + (b & 16) + (lane & 3) * 4, inv4);
      if (b < 112)
#pragma unroll 1
        for (int k = 0; k < 4; k++) stx16(g_xf + b * 512 + (lane + 32 * k) * 4, inv4);
      nbar_arrive(2, 288);
      for (int it = 0; ldx4(scr->cnt + 6) != (epoch + 1) * 128 && it < SPIN_MAX; it++) __nanosleep(100);
      {
        uint4 sv[2], cb[2];
        unsigned ga, gb;
        POLL {
#pragma unroll
          for (int k = 0; k < 2; k++) { sv[k] = ldx16(g_xm + 512 + 256 * rk + 4 * (lane + 32 * k)); cb[k] = ldx16(g_xm + 1024 + 256 * rk + 4 * (lane + 32 * k)); }
          ga = ldx4(g_xm + (b & 15) * 32 + lane); gb = ldx4(g_xm + 1536 + 256 * rk + 8 * (pr & 31) + (lane & 7));
          RETRY(X16(sv[0]) | X16(sv[1]) | X16(cb[0]) | X16(cb[1]) | lop_x3(ga, gb, par))
        }
#pragma unroll
        for (int k = 0; k < 2; k++) {
          const float c0 = bfr(1.f + bfhi(cb[k].x)), c1 = bfr(1.f + bfhi(cb[k].y)), c2 = bfr(1.f + bfhi(cb[k].z)), c3 = bfr(1.f + bfhi(cb[k].w));
          *(float4*)(smem + OFF_CO + (lane + 32 * k) * 16) = make_float4(c0, c1, c2, c3);
          uint2* pb = (uint2*)(smem + OFF_BP) + lane + 32 * k;
          pb[0] = make_uint2(pack2(c0, c1), pack2(c2, c3));
          pb[64] = make_uint2(__byte_perm(sv[k].x, sv[k].y, 0x7632), __byte_perm(sv[k].z, sv[k].w, 0x7632));
        }
        *(float*)(smem + OFF_CO + 1024 + lane * 4) = bfhi(ga);
        *(float*)(smem + OFF_CO + 1152 + lane * 4) = bfhi(gb);
      }
      __syncwarp();
      if (lane == 0) BAR_ARRIVE(XB + 4);
    }
    if (warp == 8) {
      const unsigned stag = ((pr * SMUL) & 63) * RATE_NS >> 6;
      unsigned tnext = t_off + 4 * RATE_H;
      asm volatile("barrier.cluster.wait.acquire.aligned;" ::: "memory");
#pragma unroll 1
      for (int k = 0; k < 24; k++) {
        const int code = (k < 12 ? ORDER0 >> (5 * k) : ORDER1 >> (5 * (k - 12))) & 31;
        const bool kv = code < 16;
        const int n = code, w = code - 16;
        if (!kv && w >= 5 && b >= 112) break;
        if (kv) mbar_wait(bar0 + 8 * (FB_KV + n - (n < 6 ? EWIN : KVWIN)));
        if (k >= TAIL_K) mbar_wait(bar0 + 8 * (FB_KV + (int)((ORDER1 >> (5 * (k - 12 - ((WINS >> (4 * (k - TAIL_K))) & 15)))) & 31)));
        const int e = kv ? (n == 3 ? 2 : n == 5 ? 1 : n) : w == 0 ? 0 : w < 5 ? 16 + ((w - 1) >> 1) : w == 7 ? 19 : 18;
        if (e != 1 && k) mbar_wait(bar0 + 8 * (EB + e));
        wait_until(tnext + stag);
        tnext += k > TAIL_K ? RATE_TL : k < 4 ? RATE_E : RATE_NS;
        if (lane == 0) {
          if (kv)
            asm volatile("cp.async.bulk.tensor.3d.shared::cluster.global.mbarrier::complete_tx::bytes.multicast::cluster.L2::cache_hint [%0], [%1, {%3, %4, %5}], [%2], %6, %7;"
                         ::"r"(sb + (n % NSLOT) * SLOT + rk * 16384), "l"(&tms.m[2]), "r"(bar0 + 8 * (FB_KV + n)), "r"(0), "r"(((n >> 1) * 64 + pr) * 64),
                           "r"(4 * (n & 1) + 2 * rk), "h"((unsigned short)3), "l"(stream_policy()) : "memory");
          else {
            tma3d(sb + (w == 0 ? OFF_MOD : w < 5 ? OFF_UV + (w - 1) * 16384 : w == 5 ? OFF_G : w == 6 ? OFF_U : OFF_D),
                  &tms.m[w == 0 ? 3 : w < 3 ? 4 : w < 5 ? 5 : w + 1], bar0 + 8 * (FB_MOD + w),
                  w == 0 ? 1024 + b * 16 : w < 3 || w == 7 ? 0 : w < 5 ? (pr & 7) * 64 : pr * 32, w == 7 ? b * 16 : w == 1 || w == 2 ? (b & 3) * 128 + (w - 1) * 64 : 0,
                  w == 1 || w == 2 ? 2 * hd : w == 3 || w == 4 ? (b >> 4) * 4 + 2 * rk + w - 3 : w == 5 || w == 6 ? rk : 0);
          }
        }
        __syncwarp();
      }
    }
    if (b < 112) {
      const int mt = warp & 1, dd = (warp >> 1) & 1;
      mbar_wait(bar0 + 8 * (XB + 4));
      const uint32_t ab = sb + (mt ? OFF_U : OFF_G) + (8 * (lane >> 4) + (lane & 7)) * 64 + (((2 * dd + ((lane >> 3) & 1)) ^ ((lane >> 1) & 3)) << 4);
      uint32_t base;
      asm volatile("mapa.shared::cluster.u32 %0, %1, %2;" : "=r"(base) : "r"(sb), "r"(dd));
      uint2 bb[16];
#pragma unroll
      for (int s = 0; s < 16; s++) bb[s] = *(const uint2*)(smem + OFF_BP + (g & 1) * 512 + (4 * s + tq) * 8);
      mbar_wait(bar0 + 8 * (FB_G + mt));
      float e[4][4] = {};
#pragma unroll
      for (int s = 0; s < 16; s++) { uint32_t a[4]; ldsm_t(a, ab + s * 1024); mma16(e[s & 3], a, bb[s].x, bb[s].y); }
      float r[4];
#pragma unroll
      for (int i = 0; i < 4; i++) r[i] = (e[0][i] + e[1][i]) + (e[2][i] + e[3][i]);
      if (tq < 2) st_async2(base + OFF_R4 + (8 * mt + g) * 176 + (10 * rk + 8 + tq) * 8, base + OFF_BAR + 8 * (XB + 5), tq ? r[1] : r[0], tq ? r[3] : r[2]);
    }
    return;
  }

  float* s_sm = (float*)(smem + OFF_SM);
  unsigned par, epoch;
  uint32_t rsb;
  {
    float* s_r4 = (float*)(smem + OFF_R4);
    asm volatile("barrier.cluster.arrive.relaxed.aligned;" ::: "memory");
    asm volatile("mapa.shared::cluster.u32 %0, %1, %2;" : "=r"(rsb) : "r"(sb), "r"(rk ^ 1));
    const float c0 = (arow & 1) ? bfhi(c0w) : bflo(c0w), c1 = (arow & 1) ? bfhi(c1w) : bflo(c1w);
    float acc[8] = {0, 0, 0, 0, 0, 0, 0, 0};
    fma8(acc, wm0, silu_bf(c0)); fma8(acc, wm1, silu_bf(c1));
    tred<4>(acc, lane, 8); tred<2>(acc, lane, 16);
    *(float2*)(s_r4 + warp * 64 + 8 * (lane & 7) + ((lane >> 1) & 4) + ((lane >> 3) & 2)) = make_float2(acc[0], acc[1]);
    nbar(1, 288);
    epoch = *(volatile unsigned*)(smem + OFF_MASK + 8);
    par = (epoch + 1) & 1;
    if (warp == 0) {
      float t = 0.f, ca = b < 16 ? 1.f : 0.f;
#pragma unroll
      for (int w = 0; w < 8; w++) { t += s_r4[w * 64 + lane]; ca += s_r4[w * 64 + 32 + lane]; }
      t += ca * s_sm[256 + lane];
      const float nb = __shfl_down_sync(~0u, t, 1);
      const uint32_t w0 = lane < 8 ? pack2t(t, nb, par) : pack2(t, nb);
      const uint32_t w1 = __shfl_down_sync(~0u, w0, 8), w2 = __shfl_down_sync(~0u, w0, 16), w3 = __shfl_down_sync(~0u, w0, 24);
      if (lane < 8 && !(lane & 1)) stx16(g_h + (b >> 5) * 512 + (b & 15) * 32 + (b & 16) + 2 * lane, make_uint4(w0, w1, w2, w3));
      __syncwarp();
      if (lane == 0) CNT_ADD(1);
    }
  }
  asm volatile("barrier.cluster.wait.acquire.aligned;" ::: "memory");
  {
    uint32_t a[4][4][4];
    mbar_wait(bar0 + 8 * (warp >> 1));
    const uint32_t ab = sb + OFF_WQ + (64 * warp + 8 * (lane >> 4) + (lane & 7)) * 128;
#pragma unroll
    for (int s = 0; s < 4; s++)
#pragma unroll
      for (int mt = 0; mt < 4; mt++) ldsm_t(a[s][mt], ab + s * 2048 + (((2 * mt + ((lane >> 3) & 1)) ^ (lane & 7)) << 4));
    uint4 v0, v1;
    const unsigned* ph = g_h + (g >> 1) * 512 + 64 * warp + 4 * (lane & 7);
    uint32_t off = OFF_B + warp * 272 + (32 * rk + 8 * tq + (lane & 4)) * 4;
    PIN(off); PINL(ph);
    mbar_wait(bar0 + 8 * XB);
    POLL { v0 = ldx16(ph); v1 = ldx16(ph + 32); RETRY(lop_x3(v0.x, v1.x, par)) }
    float d[4][4] = {};
#pragma unroll
    for (int mt = 0; mt < 4; mt++) {
      mma16(d[mt], a[0][mt], v0.x, v0.y); mma16(d[mt], a[1][mt], v0.z, v0.w);
      mma16(d[mt], a[2][mt], v1.x, v1.y); mma16(d[mt], a[3][mt], v1.z, v1.w);
    }
    float r[8];
#pragma unroll
    for (int mt = 0; mt < 4; mt++) { r[2 * mt] = d[mt][0] + d[mt][1]; r[2 * mt + 1] = d[mt][2] + d[mt][3]; }
    tred<4>(r, lane, 2); tred<2>(r, lane, 1);
    const float rc = __shfl_xor_sync(~0u, (lane & 4) ? r[0] : r[1], 4);
    const uint32_t wd = (lane & 4) ? pack2(rc, r[1]) : pack2(r[0], rc);
    const uint32_t w1 = __shfl_down_sync(~0u, wd, 8), w2 = __shfl_down_sync(~0u, wd, 16), w3 = __shfl_down_sync(~0u, wd, 24);
    asm volatile("{.reg .pred p; setp.lt.s32 p, %7, 8; @p st.shared.v4.b32 [%0], {%2,%3,%4,%5};\n"
                 "@p st.async.shared::cluster.mbarrier::complete_tx::bytes.v4.b32 [%1], {%2,%3,%4,%5}, [%6];}"
                 ::"r"(sb + off), "r"(rsb + off), "r"(wd), "r"(w1), "r"(w2), "r"(w3), "r"(rsb + OFF_BAR + 8 * QB), "r"(lane) : "memory");
    __syncwarp();
    arrive2(bar0 + 8 * QB, 0, lane == 0, false);
    arrive2(bar0 + 8 * (EB + 2), rsb + OFF_BAR + 8 * (EB + 2), lane == 0, lane == 0);
  }
  {
    uint32_t a[8][4];
    uint32_t a_bq = sb + OFF_B + (lane & 7) * 272 + (lane >> 3) * 16;
    unsigned* p_qa = g_qa + b * 64 + 8 * warp + 4 * lane;
    PIN(a_bq); PINL(p_qa);
    mbar_wait(bar0 + 8 * (FB_UK + (warp >> 2)));
    const uint32_t ab = sb + OFF_WUK + (warp >> 2) * 16384 + (16 * (warp & 3) + (lane & 15)) * 128;
#pragma unroll
    for (int s = 0; s < 8; s++) ldsm(a[s], ab + (s >> 2) * 8192 + (((2 * (s & 3) + (lane >> 4)) ^ (lane & 7)) << 4));
    mbar_wait(bar0 + 8 * QB);
    float d[4][4] = {};
#pragma unroll
    for (int y = 0; y < 4; y++) {
      uint32_t bq[4];
      ldsm(bq, a_bq + 64 * y);
      mma16(d[(2 * y) & 3], a[2 * y], bq[0], bq[1]); mma16(d[(2 * y + 1) & 3], a[2 * y + 1], bq[2], bq[3]);
    }
    float r[2] = {((d[0][0] + d[0][1]) + (d[1][0] + d[1][1])) + ((d[2][0] + d[2][1]) + (d[3][0] + d[3][1])),
                  ((d[0][2] + d[0][3]) + (d[1][2] + d[1][3])) + ((d[2][2] + d[2][3]) + (d[3][2] + d[3][3]))};
    tred<1>(r, lane, 1);
    r[0] += __shfl_xor_sync(~0u, r[0], 2);
    const float nb = __shfl_xor_sync(~0u, r[0], 4);
    const uint32_t w0 = lane < 8 ? pack2t(r[0], nb, par) : pack2(r[0], nb);
    const uint32_t w1 = __shfl_down_sync(~0u, w0, 8), w2 = __shfl_down_sync(~0u, w0, 16), w3 = __shfl_down_sync(~0u, w0, 24);
    if (lane < 2) stx16(p_qa, make_uint4(w0, w1, w2, w3));
    arrive2(bar0 + 8 * (EB + 4), rsb + OFF_BAR + 8 * (EB + 4), lane == 0, lane == 0);
  }
  {
    if (warp) nbar_arrive(3, 256); else { nbar(3, 256); if (lane == 0) CNT_ADD(2 + (b >> 6)); }
    asm volatile("setmaxnreg.inc.sync.aligned.u32 216;");
    const unsigned* pq = g_qa + rk * 4096 + tid * 4;
    uint32_t a_q = sb + OFF_Q + ((tid & 63) >> 3) * 2048 + (tid >> 6) * 128 + (((tid & 7) ^ (tid >> 6)) << 4);
    PINL(pq); PIN(a_q);
    mbar_wait(bar0 + 8 * (XB + 1));
    uint4 v[4];
    POLL {
#pragma unroll
      for (int k = 0; k < 4; k++) v[k] = ldx16(pq + 1024 * k);
      RETRY(lop_x3(v[0].x, v[1].x, par) | lop_x3(v[2].x, v[3].x, par))
    }
#pragma unroll
    for (int k = 0; k < 4; k++)
      asm volatile("st.shared.v4.b32 [%0], {%1,%2,%3,%4};" ::"r"((a_q + k * 512) ^ ((k & 1) << 6)), "r"(v[k].x), "r"(v[k].y), "r"(v[k].z), "r"(v[k].w) : "memory");
    if (warp >= 4) nbar_arrive(1, 256); else nbar(1, 256);
  }
  sb = __shfl_sync(~0u, sb, 0); bar0 = sb + OFF_BAR;
  if (warp < 4) {
    uint32_t qf[32][4];
#pragma unroll
    for (int s = 0; s < 32; s++) ldsm(qf[s], sb + OFF_Q + (s >> 2) * 2048 + (lane & 15) * 128 + (((2 * (s & 3) + (lane >> 4)) ^ (lane & 7)) << 4));
    float l0 = 0.f, l1 = 0.f, m0 = -1e30f, m1 = -1e30f;
    const float sc = 0.08838834764831845f * 1.4426950408889634f;
    const uint32_t kofs = (16 * warp + 8 * (lane >> 4) + (lane & 7)) * 128 + ((((lane >> 3) & 1) ^ (lane & 7)) << 4);
    uint32_t st = sb;
#pragma unroll 1
    for (int t = 0; t < 8; t++) {
      float sa[4][4] = {};
#pragma unroll
      for (int hf = 0; hf < 2; hf++) {
        const int n = 2 * t + hf;
        mbar_wait(bar0 + 8 * (FB_KV + n));
        uint32_t kf[16][4];
#pragma unroll
        for (int y = 0; y < 16; y++) ldsm(kf[y], st + (y >> 2) * 8192 + (kofs ^ ((y & 3) << 5)));
#pragma unroll
        for (int y = 0; y < 16; y++) {
          mma16(sa[(2 * y) & 3], qf[16 * hf + y], kf[y][0], kf[y][1]); mma16(sa[((2 * y) & 3) + 1], qf[16 * hf + y], kf[y][2], kf[y][3]);
        }
        __syncwarp();
        arrive2(bar0 + 8 * (EB + NSLOT + n), rsb + OFF_BAR + 8 * (EB + NSLOT + n), lane == 0 && n < 14, lane == 0 && n < 16 - NSLOT);
        if (hf == 0) arrive2(bar0 + 8 * EB, 0, lane == 0 && t == 0, false);
        st = st + SLOT == sb + NSLOT * SLOT ? sb : st + SLOT;
      }
#pragma unroll
      for (int i = 0; i < 4; i++) { sa[0][i] = (sa[0][i] + sa[2][i]) * sc; sa[1][i] = (sa[1][i] + sa[3][i]) * sc; }
      float cm[2] = {fmaxf(fmaxf(sa[0][0], sa[0][1]), fmaxf(sa[1][0], sa[1][1])), fmaxf(fmaxf(sa[0][2], sa[0][3]), fmaxf(sa[1][2], sa[1][3]))};
      tmax<1>(cm, lane, 1);
      cm[0] = fmaxf(cm[0], __shfl_xor_sync(~0u, cm[0], 2));
      float* pm = s_sm + (t & 1) * 64;
      if (tq < 2) pm[(g + 8 * tq) * 4 + warp] = cm[0];
      if (t >= 2) nbar(6 + (t & 1), 256); else nbar(3, 128);
      const float4 a0 = *(const float4*)(pm + g * 4), b0 = *(const float4*)(pm + g * 4 + 32);
      const float n0 = fmaxf(fmaxf(fmaxf(a0.x, a0.y), fmaxf(a0.z, a0.w)), m0), n1 = fmaxf(fmaxf(fmaxf(b0.x, b0.y), fmaxf(b0.z, b0.w)), m1);
      uint32_t pk[4];
#pragma unroll
      for (int i = 0; i < 2; i++) { pk[2 * i] = pack2(ex2(sa[i][0] - n0), ex2(sa[i][1] - n0)); pk[2 * i + 1] = pack2(ex2(sa[i][2] - n1), ex2(sa[i][3] - n1)); }
      *(uint4*)(smem + OFF_P + (t & 1) * 2048 + tid * 16) = make_uint4(pk[0], pk[1], pk[2], pk[3]);
      const float al0 = ex2(m0 - n0), al1 = ex2(m1 - n1);
      if (tid < 32 && tq == 0) *(float2*)(s_sm + 192 + (t & 1) * 16 + 2 * g) = make_float2(al0, al1);
      nbar_arrive(4 + (t & 1), 256);
      m0 = n0; m1 = n1;
      l0 = l0 * al0 + (bflo(pk[0]) + bfhi(pk[0])) + (bflo(pk[2]) + bfhi(pk[2]));
      l1 = l1 * al1 + (bflo(pk[1]) + bfhi(pk[1])) + (bflo(pk[3]) + bfhi(pk[3]));
    }
    float lr[2] = {l0, l1};
    tred<1>(lr, lane, 1);
    lr[0] += __shfl_xor_sync(~0u, lr[0], 2);
    if (tq < 2) s_sm[128 + (g + 8 * tq) * 4 + warp] = lr[0];
    nbar(3, 128);
    if (warp == 0 && tq < 2) {
      const float4 a0 = *(const float4*)(s_sm + 128 + (g + 8 * tq) * 4);
      stx8(g_ml + (16 * rk + g + 8 * tq) * 64 + pr, make_uint2(fbits(tq ? m1 : m0), fbits((a0.x + a0.y) + (a0.z + a0.w))));
    }
    if (warp == 0) { __syncwarp(); if (lane == 0) CNT_ADD(96 + 32 * rk); }
    nbar(2, 288);
    if (tid == 0) asm volatile("red.relaxed.gpu.global.xor.b64 [%0], %1;" ::"l"(scr->cnt + 32 + 32 * rk), "l"(1ull << pr) : "memory");
  } else {
    float o[16][4] = {};
    const uint32_t vofs = (warp & 1) * 16384 + (lane & 15) * 128 + (((lane >> 4) ^ (lane & 7)) << 4);
    const int hf = (warp >> 1) & 1;
    uint32_t st = sb + hf * SLOT;
    auto pv = [&](const int t, auto np) {
      constexpr int npre = decltype(np)::value;
      uint32_t vf[4][8][4];
      const int n = 2 * t + hf;
      mbar_wait(bar0 + 8 * (FB_KV + n));
#pragma unroll
      for (int s = 0; s < npre; s++)
#pragma unroll
        for (int y = 0; y < 8; y++) ldsm_t(vf[s][y], st + (y >> 2) * 8192 + s * 2048 + (vofs ^ ((y & 3) << 5)));
      nbar(4 + (t & 1), 256);
      const float2 al = *(const float2*)(s_sm + 192 + (t & 1) * 16 + 2 * g);
      uint4 pf[4];
#pragma unroll
      for (int s = 0; s < 4; s++) pf[s] = *(const uint4*)(smem + OFF_P + (t & 1) * 2048 + s * 512 + lane * 16);
      if (t < 6) nbar_arrive(6 + (t & 1), 256);
#pragma unroll
      for (int s = npre; s < 4; s++)
#pragma unroll
        for (int y = 0; y < 8; y++) ldsm_t(vf[s][y], st + (y >> 2) * 8192 + s * 2048 + (vofs ^ ((y & 3) << 5)));
#pragma unroll
      for (int nt = 0; nt < 16; nt++) { o[nt][0] *= al.x; o[nt][1] *= al.x; o[nt][2] *= al.y; o[nt][3] *= al.y; }
#pragma unroll
      for (int s = 0; s < 4; s++) {
        const uint32_t pa[4] = {pf[s].x, pf[s].y, pf[s].z, pf[s].w};
#pragma unroll
        for (int y = 0; y < 8; y++) { mma16(o[2 * y], pa, vf[s][y][0], vf[s][y][1]); mma16(o[2 * y + 1], pa, vf[s][y][2], vf[s][y][3]); }
      }
      __syncwarp();
      arrive2(bar0 + 8 * (EB + NSLOT + n), rsb + OFF_BAR + 8 * (EB + NSLOT + n), lane == 0 && n < 14, lane == 0 && n < 16 - NSLOT);
      st = st + 2 * SLOT >= sb + NSLOT * SLOT ? st - (NSLOT - 2) * SLOT : st + 2 * SLOT;
    };
#pragma unroll 1
    for (int t = 0; t < 7; t++) pv(t, IC<NPRE0>());
    pv(7, IC<NPRE1>());
    uint4* po = g_xo + ((size_t)((16 * rk + (g & 6)) * 4 + warp - 4) * 64 + pr) * RS + (lane & 7);
    const bool odd = lane & 4;
#pragma unroll
    for (int e = 0; e < 2; e++)
#pragma unroll
      for (int j2 = 0; j2 < 2; j2++) {
        uint32_t c0[4], c1[4];
#pragma unroll
        for (int i = 0; i < 4; i++) {
          c0[i] = i ? pack2(o[8 * j2 + i][2 * e], o[8 * j2 + i][2 * e + 1]) : pack2t(o[8 * j2][2 * e], o[8 * j2][2 * e + 1], par);
          c1[i] = i ? pack2(o[8 * j2 + 4 + i][2 * e], o[8 * j2 + 4 + i][2 * e + 1]) : pack2t(o[8 * j2 + 4][2 * e], o[8 * j2 + 4][2 * e + 1], par);
          const uint32_t r = __shfl_xor_sync(~0u, odd ? c0[i] : c1[i], 4);
          if (odd) c0[i] = r; else c1[i] = r;
        }
        stx16(po + e * 8 * 4 * 64 * RS + 8 * j2, make_uint4(c0[0], c0[1], c0[2], c0[3]));
        stx16(po + (e * 8 + 1) * 4 * 64 * RS + 8 * j2, make_uint4(c1[0], c1[1], c1[2], c1[3]));
      }
    nbar_arrive(2, 288);
  }
  tail(smem, scr, x, out, par, epoch, warp);
}

static void launch(void* const* d_in, void* d_out) {
  static TMaps tms;
  static bool init = false;
  static void* scr = nullptr;
  if (!init) {
    void* fn = nullptr; cudaDriverEntryPointQueryResult qr;
    cudaGetDriverEntryPoint("cuTensorMapEncodeTiled", &fn, cudaEnableDefault, &qr);
    EncFn f = (EncFn)fn;
    const CUtensorMapSwizzle S32 = CU_TENSOR_MAP_SWIZZLE_32B, S64 = CU_TENSOR_MAP_SWIZZLE_64B, S128 = CU_TENSOR_MAP_SWIZZLE_128B;
    const CUtensorMapL2promotion P128 = CU_TENSOR_MAP_L2_PROMOTION_L2_128B, P256 = CU_TENSOR_MAP_L2_PROMOTION_L2_256B;
    enc3d(f, &tms.m[0], d_in[2], 64, 512, 64, 8192, 128, 64, 128, 1, S128, P128);
    enc3d(f, &tms.m[1], d_in[3], 64, 512, 64, 8192, 128, 64, 64, 2, S128, P256);
    enc3d(f, &tms.m[2], d_in[1], 64, SK, 8, 1024, 128, 64, 64, 2, S128, P256);
    enc3d(f, &tms.m[3], d_in[11], 3072, 256, 2, 6144, 256 * 6144, 16, 256, 2, S32, P128);
    enc3d(f, &tms.m[4], d_in[4], 64, 512, 64, 8192, 128, 64, 64, 2, S128, P256);
    enc3d(f, &tms.m[5], d_in[5], 512, 128, 32, 1024, 128 * 1024, 64, 128, 1, S128, P128);
    enc3d(f, &tms.m[6], d_in[7], 1792, 256, 2, 3584, 256 * 3584, 32, 256, 1, S64, P128);
    enc3d(f, &tms.m[7], d_in[8], 1792, 256, 2, 3584, 256 * 3584, 32, 256, 1, S64, P128);
    enc3d(f, &tms.m[8], d_in[9], 64, 1792, 8, 1024, 128, 64, 16, 8, S128, P256);
    cudaFuncSetAttribute(fused_kernel, cudaFuncAttributeMaxDynamicSharedMemorySize, SMEM_BYTES);
    cudaGetSymbolAddress(&scr, g_scr);
    init = true;
  }
  fused_kernel<<<NCTA, 384, SMEM_BYTES>>>((const bf16*)d_in[0], (const bf16*)d_in[10], (const bf16*)d_in[11], (bf16*)d_out, (Scratch*)scr, tms);
}

}

extern "C" void kernel_launch(void* const* d_in, const int* in_sizes, int n_in, void* d_out, int out_size) {
  static int big = -1;
  if (big < 0) big = v9::fits();
  if (big) v9::launch(d_in, d_out); else v8::launch(d_in, d_out);
}
```

```cpp
#include <cuda_runtime.h>
#include <cuda_bf16.h>
#include <cuda.h>
#include <stdint.h>
#include <stdio.h>
#include <stdlib.h>

typedef CUresult (*EncFn)(CUtensorMap*, CUtensorMapDataType, cuuint32_t, void*, const cuuint64_t*, const cuuint64_t*,
                          const cuuint32_t*, const cuuint32_t*, CUtensorMapInterleave, CUtensorMapSwizzle,
                          CUtensorMapL2promotion, CUtensorMapFloatOOBfill);

static void enc3d(EncFn fn, CUtensorMap* tm, void* p, uint64_t d0, uint64_t d1, uint64_t d2, uint64_t s1, uint64_t s2, uint32_t b0,
                  uint32_t b1, uint32_t b2, CUtensorMapSwizzle sw, CUtensorMapL2promotion pr) {
  cuuint64_t gd[3] = {d0, d1, d2}, gs[2] = {s1, s2};
  cuuint32_t bx[3] = {b0, b1, b2}, es[3] = {1, 1, 1};
  fn(tm, CU_TENSOR_MAP_DATA_TYPE_BFLOAT16, 3, p, gd, gs, bx, es, CU_TENSOR_MAP_INTERLEAVE_NONE, sw, pr, CU_TENSOR_MAP_FLOAT_OOB_FILL_NONE);
}

namespace v9 {
typedef __nv_bfloat16 bf16;
#define SK 32768
#define SPIN_MAX (1 << 20)
template <int N> struct IC { static constexpr int value = N; };

__device__ __forceinline__ uint32_t s2u(const void* p) { return (uint32_t)__cvta_generic_to_shared(p); }
__device__ __forceinline__ float bflo(uint32_t u) { return __uint_as_float(u << 16); }
__device__ __forceinline__ float bfhi(uint32_t u) { return __uint_as_float(u & 0xffff0000u); }
__device__ __forceinline__ float u2f(uint32_t u) { return __uint_as_float(u); }
__device__ __forceinline__ void fma8(float* acc, uint4 v, float s) {
  acc[0] += s * bflo(v.x); acc[1] += s * bfhi(v.x); acc[2] += s * bflo(v.y); acc[3] += s * bfhi(v.y);
  acc[4] += s * bflo(v.z); acc[5] += s * bfhi(v.z); acc[6] += s * bflo(v.w); acc[7] += s * bfhi(v.w);
}
__device__ __forceinline__ uint32_t pack2(float a, float b) {
  __nv_bfloat162 p = __floats2bfloat162_rn(a, b); return *(uint32_t*)&p;
}
__device__ __forceinline__ float bfr(float v) { return bfhi(pack2(v, v)); }
__device__ __forceinline__ float silu_bf(float c) { return bfr(__fdividef(c, 1.f + __expf(-c))); }
#define fbits(v) ((__float_as_uint(v) & ~1u) | par)
__device__ __forceinline__ uint32_t pack2t(float a, float b, unsigned par) {
  const uint32_t ua = ((__float_as_uint(a) + ((par ^ 1) << 16)) & 0xFFFE0000u) | (par << 16);
  return __byte_perm(ua, pack2(b, b), 0x7632);
}
__device__ __forceinline__ void nbar(int id, int n) { asm volatile("bar.sync %0, %1;" ::"r"(id), "r"(n) : "memory"); }
__device__ __forceinline__ void nbar_arrive(int id, int n) { asm volatile("bar.arrive %0, %1;" ::"r"(id), "r"(n) : "memory"); }
__device__ __forceinline__ uint4 ldc16(const void* p) {
  uint4 v; asm volatile("ld.relaxed.cta.global.v4.u32 {%0,%1,%2,%3}, [%4];" : "=r"(v.x), "=r"(v.y), "=r"(v.z), "=r"(v.w) : "l"(p) : "memory"); return v;
}
__device__ __forceinline__ unsigned ldc4(const void* p) {
  unsigned v; asm volatile("ld.relaxed.cta.global.u32 %0, [%1];" : "=r"(v) : "l"(p) : "memory"); return v;
}
__device__ __forceinline__ uint4 ldx16(const void* p) {
  uint4 v; asm volatile("ld.relaxed.gpu.global.v4.u32 {%0,%1,%2,%3}, [%4];" : "=r"(v.x), "=r"(v.y), "=r"(v.z), "=r"(v.w) : "l"(p) : "memory"); return v;
}
__device__ __forceinline__ unsigned ldx4(const void* p) {
  unsigned v; asm volatile("ld.relaxed.gpu.global.u32 %0, [%1];" : "=r"(v) : "l"(p) : "memory"); return v;
}
__device__ __forceinline__ unsigned long long ldx64(const void* p) {
  unsigned long long v; asm volatile("ld.relaxed.gpu.global.u64 %0, [%1];" : "=l"(v) : "l"(p) : "memory"); return v;
}
__device__ __forceinline__ void stx16(void* p, uint4 v) {
  asm volatile("st.relaxed.gpu.global.v4.u32 [%0], {%1,%2,%3,%4};" ::"l"(p), "r"(v.x), "r"(v.y), "r"(v.z), "r"(v.w) : "memory");
}
__device__ __forceinline__ void stx8(void* p, uint2 v) { asm volatile("st.relaxed.gpu.global.v2.u32 [%0], {%1,%2};" ::"l"(p), "r"(v.x), "r"(v.y) : "memory"); }
__device__ __forceinline__ void stx4(void* p, unsigned v) { asm volatile("st.relaxed.gpu.global.u32 [%0], %1;" ::"l"(p), "r"(v) : "memory"); }
__device__ __forceinline__ void pub4(void* p, unsigned v) { asm volatile("red.relaxed.gpu.global.xor.b32 [%0], %1;" ::"l"(p), "r"(v) : "memory"); }
__device__ __forceinline__ void pub8(void* p, unsigned lo, unsigned hi) {
  asm volatile("{.reg .b64 t; mov.b64 t, {%1, %2}; red.relaxed.gpu.global.xor.b64 [%0], t;}" ::"l"(p), "r"(lo), "r"(hi) : "memory");
}
__device__ __forceinline__ unsigned lop_x3(unsigned a, unsigned b, unsigned c) {
  unsigned d; asm("lop3.b32 %0, %1, %2, %3, 0x7E;" : "=r"(d) : "r"(a), "r"(b), "r"(c)); return d; }
__device__ __forceinline__ unsigned or3(unsigned a, unsigned b, unsigned c) {
  unsigned d; asm("lop3.b32 %0, %1, %2, %3, 0xFE;" : "=r"(d) : "r"(a), "r"(b), "r"(c)); return d; }
__device__ __forceinline__ unsigned and3(unsigned a, unsigned b, unsigned c) {
  unsigned d; asm("lop3.b32 %0, %1, %2, %3, 0x80;" : "=r"(d) : "r"(a), "r"(b), "r"(c)); return d; }
__device__ __forceinline__ unsigned dep16(const uint32_t* f) {
  unsigned d = 0;
#pragma unroll
  for (int i = 0; i < 8; i++) d = or3(d, f[8 * i], f[8 * i + 4]);
  return d;
}
__device__ __forceinline__ uint2 ldx8(const void* p) {
  uint2 v; asm volatile("{.reg .b64 t; ld.relaxed.gpu.global.b64 t, [%2]; mov.b64 {%0, %1}, t;}" : "=r"(v.x), "=r"(v.y) : "l"(p) : "memory"); return v;
}
__device__ __forceinline__ float lds4(uint32_t a) { float v; asm volatile("ld.shared.f32 %0, [%1];" : "=f"(v) : "r"(a) : "memory"); return v; }
__device__ __forceinline__ float shx(float v, int m) {
  float r; asm volatile("shfl.sync.bfly.b32 %0, %1, %2, 0x1f, 0xffffffff;" : "=f"(r) : "f"(v), "r"(m)); return r;
}
__device__ __forceinline__ uint32_t mbar_test(uint32_t bar, uint32_t ph) {
  uint32_t ok;
  asm volatile("{.reg .pred p; mbarrier.test_wait.parity.shared::cta.b64 p, [%1], %2; vote.sync.all.pred p, p, 0xffffffff; selp.u32 %0, 1, 0, p;}"
               : "=r"(ok) : "r"(bar), "r"(ph) : "memory");
  return ok;
}
#define X16(v) (lop_x3(v.x, v.y, par) | lop_x3(v.z, v.w, par))
#define RETRY(bad) if (!__any_sync(~0u, (bad) & 1) || ++it_ >= SPIN_MAX) break;
#define POLL _Pragma("unroll 1") for (int it_ = 0;;)
__device__ __forceinline__ void mbar_wait(uint32_t bar, uint32_t ph = 0) {
  asm volatile("{.reg .pred p; .reg .u32 n; mov.u32 n, 0;\n"
               "W%=: mbarrier.try_wait.parity.shared::cta.b64 p, [%0], %1; add.u32 n, n, 1; setp.lt.and.u32 p, n, 0x100000, !p; @p bra W%=;}"
               ::"r"(bar), "r"(ph) : "memory");
}
__device__ __forceinline__ float ex2(float v) { float r; asm("ex2.approx.ftz.f32 %0, %1;" : "=f"(r) : "f"(v)); return r; }
__device__ __forceinline__ float rcp(float v) { float r; asm("rcp.approx.ftz.f32 %0, %1;" : "=f"(r) : "f"(v)); return r; }
__device__ __forceinline__ void mma16(float* d, const uint32_t* a, uint32_t b0, uint32_t b1) {
  asm volatile("mma.sync.aligned.m16n8k16.row.col.f32.bf16.bf16.f32 {%0,%1,%2,%3}, {%4,%5,%6,%7}, {%8,%9}, {%0,%1,%2,%3};"
               : "+f"(d[0]), "+f"(d[1]), "+f"(d[2]), "+f"(d[3]) : "r"(a[0]), "r"(a[1]), "r"(a[2]), "r"(a[3]), "r"(b0), "r"(b1));
}
__device__ __forceinline__ void mma16c(float* d, const uint32_t* a, uint32_t b0, uint32_t b1, const float* c) {
  asm volatile("mma.sync.aligned.m16n8k16.row.col.f32.bf16.bf16.f32 {%0,%1,%2,%3}, {%4,%5,%6,%7}, {%8,%9}, {%10,%11,%12,%13};"
               : "=f"(d[0]), "=f"(d[1]), "=f"(d[2]), "=f"(d[3])
               : "r"(a[0]), "r"(a[1]), "r"(a[2]), "r"(a[3]), "r"(b0), "r"(b1), "f"(c[0]), "f"(c[1]), "f"(c[2]), "f"(c[3]));
}
__device__ __forceinline__ float4 lds16(uint32_t a) {
  float4 v; asm volatile("ld.shared.v4.f32 {%0,%1,%2,%3}, [%4];" : "=f"(v.x), "=f"(v.y), "=f"(v.z), "=f"(v.w) : "r"(a) : "memory"); return v;
}
__device__ __forceinline__ void sts4(uint32_t a, float v) { asm volatile("st.shared.f32 [%0], %1;" ::"r"(a), "f"(v) : "memory"); }
__device__ __forceinline__ void sts16(uint32_t a, uint4 v) {
  asm volatile("st.shared.v4.b32 [%0], {%1,%2,%3,%4};" ::"r"(a), "r"(v.x), "r"(v.y), "r"(v.z), "r"(v.w) : "memory");
}
__device__ __forceinline__ void ldsm_t(uint32_t* r, uint32_t a) {
  asm volatile("ldmatrix.sync.aligned.m8n8.x4.trans.shared.b16 {%0,%1,%2,%3}, [%4];" : "=r"(r[0]), "=r"(r[1]), "=r"(r[2]), "=r"(r[3]) : "r"(a) : "memory");
}
__device__ __forceinline__ void ldsm(uint32_t* r, uint32_t a) {
  asm volatile("ldmatrix.sync.aligned.m8n8.x4.shared.b16 {%0,%1,%2,%3}, [%4];" : "=r"(r[0]), "=r"(r[1]), "=r"(r[2]), "=r"(r[3]) : "r"(a) : "memory");
}
__device__ __forceinline__ uint32_t mapa(uint32_t a, uint32_t r) {
  uint32_t v; asm volatile("mapa.shared::cluster.u32 %0, %1, %2;" : "=r"(v) : "r"(a), "r"(r)); return v;
}
__device__ __forceinline__ unsigned long long mapg(uint32_t a, uint32_t r) {
  unsigned long long v;
  asm volatile("{.reg .u32 t; .reg .u64 u; mapa.shared::cluster.u32 t, %1, %2; cvt.u64.u32 u, t; cvta.shared::cluster.u64 %0, u;}" : "=l"(v) : "r"(a), "r"(r));
  return v;
}
template <int N>
__device__ __forceinline__ void tred(float* a, int lane, int m) {
  const bool hi = lane & m;
#pragma unroll
  for (int i = 0; i < N; i++) {
    float send = hi ? a[i] : a[i + N], keep = hi ? a[i + N] : a[i];
    a[i] = keep + __shfl_xor_sync(~0u, send, m);
  }
}
template <int N>
__device__ __forceinline__ void tmax(float* a, int lane, int m) {
  const bool hi = lane & m;
#pragma unroll
  for (int i = 0; i < N; i++) {
    float send = hi ? a[i] : a[i + N], keep = hi ? a[i + N] : a[i];
    a[i] = fmaxf(keep, __shfl_xor_sync(~0u, send, m));
  }
}
__device__ __forceinline__ void arrive_n(uint32_t bar, bool on, int cnt) {
  asm volatile("{.reg .pred p; setp.ne.s32 p, %1, 0; @p mbarrier.arrive.shared::cta.b64 _, [%0], %2;}" ::"r"(bar), "r"((int)on), "r"(cnt) : "memory");
}
__device__ __forceinline__ unsigned long long stream_policy() {
  unsigned long long p;
  asm volatile("createpolicy.fractional.L2::evict_first.b64 %0, 1.0;" : "=l"(p));
  return p;
}
__device__ __forceinline__ void tma3d(uint32_t dst, const CUtensorMap* tm, uint32_t bar, int c0, int c1, int c2) {
  asm volatile("cp.async.bulk.tensor.3d.shared::cluster.global.mbarrier::complete_tx::bytes.L2::cache_hint [%0], [%1, {%3, %4, %5}], [%2], %6;"
               ::"r"(dst), "l"(tm), "r"(bar), "r"(c0), "r"(c1), "r"(c2), "l"(stream_policy()) : "memory");
}
__device__ __forceinline__ void spin_until(unsigned t) { while ((int)((unsigned)clock() - t) < 0) {} }
__device__ __forceinline__ void wait_until(unsigned t) {
  unsigned now;
  do { asm volatile("mov.u32 %0, %%globaltimer_lo;" : "=r"(now)); } while ((int)(now - t) < 0);
}
__device__ __forceinline__ void sleep_until(unsigned t) {
  unsigned now;
#pragma unroll 1
  do {
    __nanosleep(200);
    asm volatile("mov.u32 %0, %%globaltimer_lo;" : "=r"(now));
  } while ((int)(now - t) < 0);
}
#define PIN(x) asm volatile("" : "+r"(x))
#define PINL(x) asm volatile("" : "+l"(x))
#define BAR_ARRIVE(i) asm volatile("mbarrier.arrive.shared::cta.b64 _, [%0];" ::"r"(bar0 + 8 * (i)) : "memory")
#define LANE0(op, p, c, v) asm volatile("{.reg .pred q; setp.eq.s32 q, %2, 0; @q " op " [%0], %1;}" ::"l"((p) + lane), c(v), "r"(lane) : "memory")
#define CNT_ADD(c) LANE0("red.relaxed.gpu.global.add.u32", scr->cnt + (c), "r", 1)
#define BAR_INIT(i, cnt) asm volatile("mbarrier.init.shared::cta.b64 [%0], %1;" ::"r"(bar0 + 8 * (i)), "r"(cnt) : "memory")
#define BAR_ARM(i, bytes) asm volatile("mbarrier.arrive.expect_tx.shared::cta.b64 _, [%0], %1;" ::"r"(bar0 + 8 * (i)), "r"(bytes) : "memory")
struct TMaps { CUtensorMap m[9]; };

#define NCTA9 120
#define TAU 20
#define NSL 100
#define NPE 1
#define QN 4
#define FDLY 60
#define VJ 1
#define NPO 3
#define VDLY 150
#define O_Q 131072
#define O_LZ 163840
#define O_CTX 196608
#define O_HZ 198656
#define O_HW 200704
#define O_X 201728
#define O_P 218112
#define O_B 222208
#define O_R 224512
#define O_SILU 228608
#define O_SM 229632
#define O_BAR 231424
#define O_EP (O_BAR + 256)
#define O_DBG (O_EP + 16)
#define SMEM9 (O_DBG + 144)
#define B_FULL 0
#define B_FM 8
#define B_EMPTY 10
#define B_LZ 18
#define B_Q2 19
#define B_H 20
#define B_QF 21
#define B_TAB 22
#define B_W 23
#define B_ST 24
#define B_HZ 25
#define B_WZ 26
#define B_G 27
#define B_G2 28
enum { T_WQ, T_WUK, T_KV, T_MOD, T_UV, T_WO, T_GU, T_DN = 8 };
#define NBIG 40
struct Sched { unsigned zero, dth; uint2 r[3][8]; unsigned nr[3], nt[3], dt, t4, d4, d6, wt, pad; };

struct __align__(128) Scratch {
  unsigned cnt[8 * 32];
  uint2 rec[32 * 4 * 8 * 64];
  uint2 hdr[32 * 16];
  unsigned h[8 * 256];
  uint4 qa[2048];
  unsigned xao[8 * 512];
  unsigned xab[8 * 256];
  unsigned xm[2048];
};
__device__ Scratch g_scr;
#define SMEM_BASE 1024u
#define DSC ((SMEM_BASE >> 4) | (1u << 16))
#define HI128 (64u | (1u << 30))
#define HI64 (32u | (2u << 30))
template <int TA, int TB, unsigned HIA, unsigned HIB>
__device__ __forceinline__ void wgmma32(float* d, uint32_t da, uint32_t db, int acc) {
  asm volatile("{.reg .pred p; .reg .b64 da, db; setp.ne.b32 p, %18, 0; mov.b64 da, {%16, %21}; mov.b64 db, {%17, %22};\n"
               "wgmma.mma_async.sync.aligned.m64n32k16.f32.bf16.bf16 "
               "{%0,%1,%2,%3,%4,%5,%6,%7,%8,%9,%10,%11,%12,%13,%14,%15}, da, db, p, 1, 1, %19, %20;}"
               : "+f"(d[0]), "+f"(d[1]), "+f"(d[2]), "+f"(d[3]), "+f"(d[4]), "+f"(d[5]), "+f"(d[6]), "+f"(d[7]),
                 "+f"(d[8]), "+f"(d[9]), "+f"(d[10]), "+f"(d[11]), "+f"(d[12]), "+f"(d[13]), "+f"(d[14]), "+f"(d[15])
               : "r"(da), "r"(db), "r"(acc), "n"(TA), "n"(TB), "n"(HIA), "n"(HIB));
}
__device__ __forceinline__ void wgmma32r(float* d, const uint32_t* a, uint32_t db) {
  asm volatile("{.reg .b64 db; mov.b64 db, {%20, %21};\n"
               "wgmma.mma_async.sync.aligned.m64n32k16.f32.bf16.bf16 "
               "{%0,%1,%2,%3,%4,%5,%6,%7,%8,%9,%10,%11,%12,%13,%14,%15}, {%16,%17,%18,%19}, db, 1, 1, 1, 1;}"
               : "+f"(d[0]), "+f"(d[1]), "+f"(d[2]), "+f"(d[3]), "+f"(d[4]), "+f"(d[5]), "+f"(d[6]), "+f"(d[7]),
                 "+f"(d[8]), "+f"(d[9]), "+f"(d[10]), "+f"(d[11]), "+f"(d[12]), "+f"(d[13]), "+f"(d[14]), "+f"(d[15])
               : "r"(a[0]), "r"(a[1]), "r"(a[2]), "r"(a[3]), "r"(db), "n"(HI64));
}
template <int N> __device__ __forceinline__ void wg_wait(float* a) {
  asm volatile("wgmma.wait_group.sync.aligned %16;"
               : "+f"(a[0]), "+f"(a[1]), "+f"(a[2]), "+f"(a[3]), "+f"(a[4]), "+f"(a[5]), "+f"(a[6]), "+f"(a[7]), "+f"(a[8]), "+f"(a[9]), "+f"(a[10]),
                 "+f"(a[11]), "+f"(a[12]), "+f"(a[13]), "+f"(a[14]), "+f"(a[15]) : "n"(N) : "memory");
}
__device__ __forceinline__ void send32(uint32_t a, uint32_t bar, float v, int lane, int off) {
  const uint32_t w = pack2(v, __shfl_down_sync(~0u, v, 1));
  const int s = 2 * (lane & 3);
  asm volatile("{.reg .pred p; setp.eq.s32 p, %6, 0; @p st.async.shared::cluster.mbarrier::complete_tx::bytes.v4.b32 [%0], {%1,%2,%3,%4}, [%5];}"
               ::"r"(a), "r"(__shfl_sync(~0u, w, s)), "r"(__shfl_sync(~0u, w, s + 8)), "r"(__shfl_sync(~0u, w, s + 16)), "r"(__shfl_sync(~0u, w, s + 24)),
                 "r"(bar), "r"(off) : "memory");
}
__device__ __forceinline__ float sum8(uint32_t a) {
  const float4 p = lds16(a), q = lds16(a + 1024);
  return ((p.x + p.y) + (p.z + p.w)) + ((q.x + q.y) + (q.z + q.w));
}
__device__ __forceinline__ int posof(int c) { return (c & ~14) + 2 * (c & 6) + ((c >> 2) & 2); }

__global__ void __cluster_dims__(8, 1, 1) __launch_bounds__(384, 1)
fused_kernel(const bf16* __restrict__ x, const bf16* __restrict__ cvec, const bf16* __restrict__ w_mod, bf16* __restrict__ out,
             Scratch* __restrict__ scr, const __grid_constant__ Sched sch, const __grid_constant__ TMaps tms) {
  extern __shared__ __align__(1024) unsigned char smem[];
  const int tid = threadIdx.x, warp = __shfl_sync(~0u, tid >> 5, 0), lane = tid & 31;
  const int b = blockIdx.x, cl = b >> 3, rn = b & 7, rk = b & 1, hd = b >> 1, f = b - 64;
  const bool isA = b < 64;
  uint32_t sb = s2u(smem), bar0 = sb + O_BAR;
  unsigned gt_start;
  asm volatile("mov.u32 %0, %%globaltimer_lo;" : "=r"(gt_start));
  const int g = lane >> 2, tq = lane & 3;
  const int arow = 64 * rn + ((tid & 255) >> 4);
  uint4 wm[4];
  uint32_t cw, xw;
  if (warp < 8 && isA) {
    const bf16* wa = w_mod + (size_t)arow * 3072 + (lane & 8) * 64 + 64 * cl + 8 * (lane & 7);
#pragma unroll
    for (int i = 0; i < 4; i++) wm[i] = ldx16(wa + i * 16 * 3072);
    cw = ldc4(cvec + (arow & ~1) + 16 * tq);
    if (warp < 2) xw = ldc4(x + 64 * cl + (tid & 62));
  }
  if (warp == 11) {
    if (lane == 0) {
#pragma unroll
      for (int i = 0; i < B_EMPTY; i++) BAR_INIT(i, 1);
    }
    __syncwarp();
    asm volatile("fence.mbarrier_init.release.cluster;" ::: "memory");
    asm volatile("barrier.cluster.arrive.relaxed.aligned;" ::: "memory");
    if (isA) {
#pragma unroll 1
      for (int i = 0; i < 8; i++) {
        if (i >= 6) mbar_wait(bar0 + 8 * (i - 6));
        wait_until(gt_start + ((64 * i + b) * sch.dth >> 8));
        if (lane == 0) {
          BAR_ARM(i, 16384);
          tma3d(sb + i * 16384, &tms.m[i >> 2], bar0 + 8 * i, 0, i < 4 ? 128 * i : 256 * rk + 64 * (i - 4), i < 4 ? b : b & ~1);
        }
        __syncwarp();
      }
    }
  }
  if (warp == 10) {
    const unsigned ep = ldc4(&scr->cnt[0]);
    if (isA) {
      const uint4 xa = ldc16(x + 16 * lane), xb = ldc16(x + 16 * lane + 8);
      float xv[16] = {bflo(xa.x), bfhi(xa.x), bflo(xa.y), bfhi(xa.y), bflo(xa.z), bfhi(xa.z), bflo(xa.w), bfhi(xa.w),
                      bflo(xb.x), bfhi(xb.x), bflo(xb.y), bfhi(xb.y), bflo(xb.z), bfhi(xb.z), bflo(xb.w), bfhi(xb.w)};
      const float x0 = __shfl_sync(~0u, xv[0], 0);
      float s = 0, q = 0;
#pragma unroll
      for (int i = 0; i < 16; i++) { xv[i] -= x0; s += xv[i]; q += xv[i] * xv[i]; }
#pragma unroll
      for (int o = 16; o; o >>= 1) { s += __shfl_xor_sync(~0u, s, o); q += __shfl_xor_sync(~0u, q, o); }
      s *= 1.f / 512.f;
      float rstd;
      asm("rsqrt.approx.ftz.f32 %0, %1;" : "=f"(rstd) : "f"(fmaxf(q * (1.f / 512.f) - s * s, 0.f) + 1e-5f));
      *(float2*)(smem + O_SM + 1024) = make_float2(s + x0, rstd);
    }
    if (lane == 0) *(volatile unsigned*)(smem + O_EP) = ep;
    nbar_arrive(1, 288);
  }
  const int cls = isA ? (b >= NBIG) : 2, v0 = isA ? 2 : 0;
  if (warp >= 8) {
    asm volatile("setmaxnreg.dec.sync.aligned.u32 56;");
    if (warp == 8) {
      if (lane < 8) asm volatile("prefetch.tensormap [%0];" ::"l"(&tms.m[lane + 1]) : "memory");
      if ((sb & 0xFFFFFF) != SMEM_BASE) __trap();
    } else if (warp == 9) {
      if (lane == 0) {
#pragma unroll
        for (int i = B_EMPTY; i < B_LZ; i++) BAR_INIT(i, 8);
        BAR_INIT(B_LZ, 8); BAR_INIT(B_Q2, 9); BAR_ARM(B_Q2, 1024);
        BAR_INIT(B_H, 1); BAR_INIT(B_QF, 1); BAR_ARM(B_QF, 32768);
        BAR_INIT(B_TAB, 1); BAR_INIT(B_W, 1); BAR_INIT(B_ST, 8); BAR_INIT(B_WZ, 1); BAR_INIT(B_HZ, 1); BAR_ARM(B_HZ, isA ? 1024 : 512); BAR_INIT(B_G, 1); BAR_INIT(B_G2, 1);
      }

    }
    if (warp != 11) {
      __syncwarp();
      asm volatile("fence.mbarrier_init.release.cluster;" ::: "memory");
      __threadfence_block();
      asm volatile("barrier.cluster.arrive.relaxed.aligned;" ::: "memory");
    }
    asm volatile("barrier.cluster.wait.acquire.aligned;" ::: "memory");
    if (warp == 8) {
      const int nr = sch.nr[cls], vl = v0 + sch.nt[cls] - 1;
      unsigned long long hist = 0;
      int v = v0;
#pragma unroll 1
      for (int rd = 0; rd < nr; rd++) {
        const uint2 e = sch.r[cls][rd];
        const int type = e.y & 15, win = (e.y >> 4) & 15, pos = b + 64 - (int)((e.y >> 8) & 255), tile = e.y >> 16;
        const bool mod = type == T_MOD;
        const int ni = mod ? 1 : type == T_DN ? 2 : 4;
        unsigned t = gt_start + (e.x & 0xffff) + (pos * sch.dt >> 8);
        const int c0 = mod ? 1024 + 32 * b : type == T_WO || type == T_DN ? 64 * rn : type == T_GU ? 32 * f : 0;
        int c1 = type == T_KV ? 64 * (tile + pos) : 0;
        int c2 = mod ? tile : type == T_WO ? 4 * cl : type == T_DN ? 2 * cl - 16 : type == T_UV ? b : 0;
        const int i1 = type == T_UV ? 128 : 0;
#pragma unroll 1
        for (int j = 0; j < ni; j++) {
          const int slot = mod ? B_FM + tile : (v & 1) * 4 + j;
          if (mod ? tile : v >= 2) mbar_wait(bar0 + 8 * (B_EMPTY + (mod ? (vl & 1) * 4 : slot)), mod ? (vl >> 1) & 1 : ((v >> 1) - 1) & 1);
          const int hw = (int)(hist >> (6 * (win - 1))) & 63;
          if (hw) mbar_wait(bar0 + 8 * (hw & 15), (hw >> 4) & 1);
          wait_until(t);
          if (lane == 0) {
            BAR_ARM(slot, 16384);
            tma3d(sb + (mod ? (tile ? O_Q : O_X) : slot * 16384), &tms.m[type == T_GU ? type + (j & 1) : type], bar0 + 8 * slot, c0, c1, c2);
          }
          __syncwarp();
          hist = hist << 6 | (32 | (mod ? 0 : (v & 2) << 3) | slot);
          t += e.x >> 16; c1 += i1;
          c2 += type == T_KV ? 2 : type == T_WO || type == T_DN ? 1 : type == T_GU ? j & 1 : 0;
        }
        v += !mod;
      }
      return;
    }
    const unsigned epoch = *(volatile unsigned*)(smem + O_EP), par = (epoch + 1) & 1;
    if (warp == 10) {
      if (isA) {
        for (int it = 0; ldx4(scr->cnt + 1) != (epoch + 1) * 128 && it < SPIN_MAX; it++) {}
        if (lane == 0) BAR_ARRIVE(B_H);
      } else mbar_wait(bar0);
      if (!(rn & (QN - 1))) {
        for (int it = 0; ldx4(scr->cnt + 32 + 32 * (rn >> 2)) != (epoch + 1) * 32 && it < SPIN_MAX; it++) {}
        if (lane == 0)
          asm volatile("cp.async.bulk.shared::cluster.global.mbarrier::complete_tx::bytes.multicast::cluster [%0], [%1], %4, [%2], %3;"
                       ::"r"(sb + O_Q + rn * 4096), "l"(scr->qa + rn * 256), "r"(bar0 + 8 * B_QF), "h"((unsigned short)0xff), "n"(4096 * QN) : "memory");
      }
      const unsigned dl = isA ? sch.d4 : sch.d6;
      unsigned tw = gt_start + sch.t4;
      if (!isA) {
        const int nt = sch.nt[2];
#pragma unroll 1
        for (int t = 0; t < nt; t++) mbar_wait(bar0 + 8 * B_EMPTY + (t & 1) * 32, (t >> 1) & 1);
        unsigned long long now;
        asm volatile("mov.u64 %0, %%globaltimer;" : "=l"(now));
        LANE0("red.relaxed.gpu.global.max.u64", scr->cnt + 130, "l", now);
        CNT_ADD(128);
        tw = (unsigned)now + 1700;
      }
      sleep_until(tw);
      uint4 an;
      for (int it = 0; an = ldx16(scr->cnt + 128), an.x != (epoch + 1) * 56 && it < SPIN_MAX; it++) {}
      wait_until(an.z + (dl >> 16));
      if (lane == 0) BAR_ARRIVE(B_G2);
      wait_until(an.z + (dl & 0xffff));
      if (lane == 0) BAR_ARRIVE(B_G);
    } else if (warp == 11) {
      {
        uint2* ph = scr->hdr + ((lane & 24) + 2 * tq + (g & 1)) * 16 + cl;
        const bool own = (lane >> 4) * 4 + tq == rn;
        if (own) { stx8(ph, make_uint2(par ^ 1, 0)); if (cl == 14) stx8(ph + 1, make_uint2(0, 0)); }
        uint32_t a_w = sb + O_HW + ((lane >> 4) * 4 + tq) * 128 + (g & 1) * 64 + ((lane >> 1) & 4);
        PIN(a_w); PINL(ph);
        const int vt = v0 + sch.nt[cls];
#pragma unroll 1
        for (int t = 0; t < vt; t++) mbar_wait(bar0 + 8 * B_EMPTY + (t & 1) * 32, (t >> 1) & 1);
        float hz[8], M;
        uint32_t wp[4];
#pragma unroll 1
        for (int e = 0; e < 2; e++) {
          POLL {
            unsigned ok = 1;
#pragma unroll
            for (int u = 0; u < 8; u++)
              asm volatile("ld.relaxed.cluster.shared.f32 %0, [%1];" : "=f"(hz[u]) : "r"(sb + O_HZ + e * 1024 + u * 128 + lane * 4) : "memory");
#pragma unroll
            for (int u = 0; u < 4; u++) ok = and3(ok, __float_as_uint(hz[u]), __float_as_uint(hz[u + 4]));
            RETRY(~ok)
          }
          if (e) break;
          M = fmaxf(fmaxf(fmaxf(hz[0], hz[1]), fmaxf(hz[2], hz[3])), fmaxf(fmaxf(hz[4], hz[5]), fmaxf(hz[6], hz[7])));
          M = u2f(fbits(M));
#pragma unroll
          for (int u = 0; u < 4; u++) {
            wp[u] = pack2(ex2(hz[u] - M), ex2(hz[u + 4] - M));
            sts4(a_w + ((rn - u) & 3) * 8, u2f(wp[u])); sts4(a_w + ((rn - u) & 3) * 8 + 32, u2f(wp[u]));
          }
          __syncwarp();
          if (lane == 0) BAR_ARRIVE(B_WZ);
        }
        float L = 0.f;
#pragma unroll
        for (int u = 0; u < 4; u++) L += bflo(wp[u]) * hz[u] + bfhi(wp[u]) * hz[u + 4];
        if (own) pub8(ph, __float_as_uint(M) | 1u, __float_as_uint(L));
      }
      if (isA) {
        mbar_wait(bar0 + 8 * B_G2);
        unsigned long long hh;
        POLL { hh = ldx64(scr->hdr + hd * 16 + (lane & 15)); RETRY((lane & 15) == 15 ? 0u : (unsigned)hh ^ par) }
        const float m = (lane & 15) == 15 ? -1e30f : u2f((unsigned)hh);
        int mi = __float_as_int(m);
        mi ^= (mi >> 31) & 0x7fffffff;
        mi = __reduce_max_sync(~0u, mi);
        mi ^= (mi >> 31) & 0x7fffffff;
        const float w = ex2(m - __int_as_float(mi));
        float L = w * u2f(hh >> 32);
#pragma unroll
        for (int o2 = 8; o2; o2 >>= 1) L += __shfl_xor_sync(~0u, L, o2);
        sts4(sb + O_SM + (384 + 2 * (lane & 6) + ((lane >> 2) & 2) + (lane & 1)) * 4, w * rcp(L));
        __syncwarp();
        if (lane == 0) BAR_ARRIVE(B_W);
      }
    } else {
#pragma unroll 4
      for (int i = 0; i < 72; i++) sts16(sb + O_LZ + i * 512 + lane * 16, make_uint4(0, 0, 0, 0));
      __syncwarp();
      if (lane < 8) asm volatile("mbarrier.arrive.release.cluster.shared::cluster.b64 _, [%0];" ::"r"(mapa(bar0 + 8 * B_LZ, lane)) : "memory");
      if (isA) {
        mbar_wait(bar0 + 8 * B_QF);
#pragma unroll 2
        for (int k = 0; k < 8; k++) {
          const uint32_t cp = ldc4(cvec + 2 * (lane + 32 * k));
          *(uint32_t*)(smem + O_SILU + (lane + 32 * k) * 4) = pack2(silu_bf(bflo(cp)), silu_bf(bfhi(cp)));
        }
        __syncwarp();
        uint32_t ab = sb + O_X + (8 * (lane >> 4) + (lane & 7)) * 64 + ((((lane >> 3) & 1) ^ ((lane >> 1) & 3)) << 4);
        float d[4][4] = {};
#pragma unroll 1
        for (int jm = 0; jm < 2; jm++) {
          mbar_wait(bar0 + 8 * (B_FM + jm));
#pragma unroll 2
          for (int s2 = 0; s2 < 8; s2++)
#pragma unroll
            for (int s = 0; s < 2; s++) {
              uint32_t a0[4], a1[4];
              const uint32_t* ps = (const uint32_t*)(smem + O_SILU) + 128 * jm + 16 * s2 + 8 * s + tq;
              ldsm_t(a0, ab + (2 * s2 + s) * 1024); ldsm_t(a1, (ab + (2 * s2 + s) * 1024) ^ 32);
              mma16(d[s], a0, ps[0], ps[4]); mma16(d[2 + s], a1, ps[0], ps[4]);
            }
          ab -= O_X - O_Q;
        }
        const float t0 = (tq & 1) ? d[0][2] + d[1][2] : d[0][0] + d[1][0], t1 = (tq & 1) ? d[2][2] + d[3][2] : d[2][0] + d[3][0];
        stx4(scr->xm + b * 32 + posof(8 * tq + g), fbits(bfr(bfr((tq & 2) ? t1 : t0) + ((b >> 4) == 2 ? 1.f : 0.f))));
        __syncwarp();
        CNT_ADD(96);
      } else sleep_until(gt_start + sch.t4);
      for (int it = 0; ldx4(scr->cnt + 96) != (epoch + 1) * 64 && it < SPIN_MAX; it++) __nanosleep(NSL);
      if (isA) {
        unsigned long long ga;
        POLL { ga = ldx64(scr->xm + 64 * rn + 2 * lane); RETRY(lop_x3((unsigned)ga, ga >> 32, par)) }
        *(float2*)(smem + O_SM + (320 + 2 * lane) * 4) = make_float2(bfhi((unsigned)ga), bfhi(ga >> 32));
      }
      __syncwarp();
      if (lane == 0) BAR_ARRIVE(B_TAB);
    }
    return;
  }

  float* s_sm = (float*)(smem + O_SM);
  unsigned par, epoch;
  asm volatile("barrier.cluster.arrive.relaxed.aligned;" ::: "memory");
  if (isA) {
    float* s_r = (float*)(smem + O_R);
    float acc[8] = {0, 0, 0, 0, 0, 0, 0, 0};
    const float sl = silu_bf((arow & 1) ? bfhi(cw) : bflo(cw));
#pragma unroll
    for (int i = 0; i < 4; i++) fma8(acc, wm[i], __shfl_sync(~0u, sl, i, 4));
    tred<4>(acc, lane, 16);
    *(float4*)(s_r + warp * 128 + 8 * (lane & 15) + ((lane >> 2) & 4)) = make_float4(acc[0], acc[1], acc[2], acc[3]);
    nbar(1, 288);
    epoch = *(volatile unsigned*)(smem + O_EP);
    par = (epoch + 1) & 1;
    if (warp < 2) {
      float t = 0.f, ca = rn == 0 ? 1.f : 0.f;
#pragma unroll
      for (int w = 0; w < 8; w++) { t += s_r[w * 128 + tid]; ca += s_r[w * 128 + 64 + tid]; }
      t += ca * ((((tid & 1) ? bfhi(xw) : bflo(xw)) - s_sm[256]) * s_sm[257]);
      const float nb = __shfl_down_sync(~0u, t, 1);
      const uint32_t w0 = lane < 8 ? pack2t(t, nb, par) : pack2(t, nb);
      const uint32_t w1 = __shfl_down_sync(~0u, w0, 8), w2 = __shfl_down_sync(~0u, w0, 16), w3 = __shfl_down_sync(~0u, w0, 24);
      if (lane < 8 && !(lane & 1)) stx16(scr->h + (rn >> 1) * 512 + (2 * cl + warp) * 32 + rk * 16 + 2 * lane, make_uint4(w0, w1, w2, w3));
      __syncwarp();
      CNT_ADD(1);
    }
    asm volatile("barrier.cluster.wait.acquire.aligned;" ::: "memory");
    const uint32_t rsb = mapa(sb, rn ^ 1);
    {
      uint32_t a[4][4][4];
      mbar_wait(bar0 + 8 * (warp >> 1));
      const uint32_t ab = sb + (64 * warp + 8 * (lane >> 4) + (lane & 7)) * 128;
#pragma unroll
      for (int s = 0; s < 4; s++)
#pragma unroll
        for (int mt = 0; mt < 4; mt++) ldsm_t(a[s][mt], ab + s * 2048 + (((2 * mt + ((lane >> 3) & 1)) ^ (lane & 7)) << 4));
      arrive_n(bar0 + 8 * (B_EMPTY + (warp >> 1)), lane == 0, 4 + (dep16(&a[0][0][0]) & sch.zero));
      uint4 v0, v1;
      const unsigned* ph = scr->h + (g >> 1) * 512 + 64 * warp + 4 * (lane & 7);
      uint32_t off = O_B + warp * 272 + (32 * rk + 8 * tq + (lane & 4)) * 4;
      PIN(off); PINL(ph);
      mbar_wait(bar0 + 8 * B_H);
      POLL { v0 = ldx16(ph); v1 = ldx16(ph + 32); RETRY(lop_x3(v0.x, v1.x, par)) }
      float d[4][4] = {};
#pragma unroll
      for (int mt = 0; mt < 4; mt++) {
        mma16(d[mt], a[0][mt], v0.x, v0.y); mma16(d[mt], a[1][mt], v0.z, v0.w);
        mma16(d[mt], a[2][mt], v1.x, v1.y); mma16(d[mt], a[3][mt], v1.z, v1.w);
      }
      float r[8];
#pragma unroll
      for (int mt = 0; mt < 4; mt++) { r[2 * mt] = d[mt][0] + d[mt][1]; r[2 * mt + 1] = d[mt][2] + d[mt][3]; }
      tred<4>(r, lane, 2); tred<2>(r, lane, 1);
      const float rc = __shfl_xor_sync(~0u, (lane & 4) ? r[0] : r[1], 4);
      const uint32_t wd = (lane & 4) ? pack2(rc, r[1]) : pack2(r[0], rc);
      const uint32_t w1 = __shfl_down_sync(~0u, wd, 8), w2 = __shfl_down_sync(~0u, wd, 16), w3 = __shfl_down_sync(~0u, wd, 24);
      asm volatile("{.reg .pred p; setp.lt.s32 p, %7, 8; @p st.shared.v4.b32 [%0], {%2,%3,%4,%5};\n"
                   "@p st.async.shared::cluster.mbarrier::complete_tx::bytes.v4.b32 [%1], {%2,%3,%4,%5}, [%6];}"
                   ::"r"(sb + off), "r"(rsb + off), "r"(wd), "r"(w1), "r"(w2), "r"(w3), "r"(rsb + O_BAR + 8 * B_Q2), "r"(lane) : "memory");
      __syncwarp();
      arrive_n(bar0 + 8 * B_Q2, lane == 0, 1);
    }
    {
      uint32_t a[2][8][4];
      uint32_t a_bq = sb + O_B + (lane & 7) * 272 + (lane >> 3) * 16;
      uint4* p_qa = scr->qa + (4 * rk + (warp >> 1)) * 256 + hd * 8 + ((4 * (warp & 1) + tq) ^ (hd & 7));
      PIN(a_bq); PINL(p_qa);
      mbar_wait(bar0 + 8 * (4 + (warp >> 1)));
      const uint32_t ab = sb + 65536 + (warp >> 1) * 16384 + (32 * (warp & 1) + (lane & 15)) * 128;
#pragma unroll
      for (int i = 0; i < 16; i++) ldsm(a[i >> 3][i & 7], ab + (i >> 3) * 2048 + ((i >> 2) & 1) * 8192 + (((2 * (i & 3) + (lane >> 4)) ^ (lane & 7)) << 4));
      arrive_n(bar0 + 8 * (B_EMPTY + 4 + (warp >> 1)), lane == 0, 4 + (dep16(&a[0][0][0]) & sch.zero));
      mbar_wait(bar0 + 8 * B_Q2);
      float d[4][4] = {};
#pragma unroll
      for (int y = 0; y < 4; y++) {
        uint32_t bq[4];
        ldsm(bq, a_bq + 64 * y);
#pragma unroll
        for (int mt = 0; mt < 2; mt++) { mma16(d[2 * mt], a[mt][2 * y], bq[0], bq[1]); mma16(d[2 * mt + 1], a[mt][2 * y + 1], bq[2], bq[3]); }
      }
      float r[4];
#pragma unroll
      for (int i = 0; i < 4; i++) r[i] = (d[i & 2][2 * (i & 1)] + d[i & 2][2 * (i & 1) + 1]) + (d[(i & 2) + 1][2 * (i & 1)] + d[(i & 2) + 1][2 * (i & 1) + 1]);
      tred<2>(r, lane, 2); tred<1>(r, lane, 1);
      const float nb = __shfl_xor_sync(~0u, r[0], 4);
      const uint32_t w0 = (lane >> 3) == (hd & 3) ? pack2t(r[0], nb, par) : pack2(r[0], nb);
      const uint32_t w1 = __shfl_down_sync(~0u, w0, 8), w2 = __shfl_down_sync(~0u, w0, 16), w3 = __shfl_down_sync(~0u, w0, 24);
      if (lane < 4) stx16(p_qa, make_uint4(w0, w1, w2, w3));
      if (warp) nbar_arrive(3, 256); else { nbar(3, 256); CNT_ADD(32 + 32 * rk); }
    }
  } else {
    nbar(1, 288);
    epoch = *(volatile unsigned*)(smem + O_EP);
    par = (epoch + 1) & 1;
    asm volatile("barrier.cluster.wait.acquire.aligned;" ::: "memory");
    mbar_wait(bar0);
  }
  asm volatile("setmaxnreg.inc.sync.aligned.u32 224;");
  uint2* p_rec = scr->rec + ((16 * (warp >> 2) + 2 * (warp & 3) + (g & 1) + 4 * (tq & 2)) * 32 + 4 * rn + (tq & 1)) * 64 + cl * 4 + (g >> 1);
  PINL(p_rec);
  {
    const unsigned inv = par ^ 1;
#pragma unroll
    for (int q = 0; q < 2; q++) { stx8(p_rec + q * 128, make_uint2(inv, 0)); if (cl == 14) stx8(p_rec + q * 128 + 4, make_uint2(0, 0)); }
    if (isA) { if (warp < 2) { stx4(scr->xao + b * 64 + tid, inv); stx4(scr->xab + cl * 256 + (2 * (rn & 3) + warp) * 32 + (rn >> 2) * 16 + (lane >> 1), inv); } }
    else if (f == 0) { stx4(out + 2 * tid, 0); __threadfence(); }
  }
  sb = __shfl_sync(~0u, sb, 0); bar0 = sb + O_BAR;
  const int nt = sch.nt[cls], wg = warp >> 2;
  uint32_t a_z[4];
#pragma unroll
  for (int u = 0; u < 4; u++) {
    const int s3 = (rn - u - (lane >> 1 & 1)) & 3;
    a_z[u] = sb + O_LZ + (s3 + 4 * (lane & 1)) * 4096 + wg * 512 + g * 64 + (((warp & 3) ^ (s3 & 1) ^ (2 * (lane & 1))) << 4);
    PIN(a_z[u]);
  }
  uint32_t z[4][4], a_w = sb + O_HW + warp * 128 + (g & 1) * 64 + (tq & 1) * 8;
  PIN(a_w);
  {
    const float sc = 0.08838834764831845f * 1.4426950408889634f;
    float mrun = -1e30f;
    float o[4][16], sx[16], mref[8];
#pragma unroll
    for (int k = 0; k < 16; k++) { o[0][k] = o[1][k] = o[2][k] = o[3][k] = sx[k] = 0.f; mref[k >> 1] = -1e30f; }
    const int key = 16 * warp + (lane & 15);
    uint32_t a_p = sb + O_P + key * 64 + (((lane >> 4) ^ ((key >> 1) & 3)) << 4);
    uint32_t a_v = sb + wg * 32768 + (8 * (lane >> 4) + (lane & 7)) * 128 + (((2 * (warp & 3) + ((lane >> 3) & 1)) ^ (lane & 7)) << 4);
    const int rot = rn + warp;
    const int qown = wg == (rn >> 2) ? -warp & 3 : -1;
    uint32_t a_own = sb + O_LZ + rn * 4096 + (warp & 3) * 1024 + g * 64 + ((tq ^ (rn & 1) ^ ((rn >> 1) & 2)) << 4);
    PIN(a_own);
    unsigned long long dst[4];
#pragma unroll
    for (int q = 0; q < 4; q++) {
      dst[q] = mapg(a_own, 4 * wg + ((q + rot) & 3));
      PINL(dst[q]);
    }
    unsigned long long a_h = mapg(sb + O_HZ + wg * 1024 + rn * 128 + lane * 4, 2 * (warp & 3));
    unsigned long long a_h1 = mapg(sb + O_HZ + wg * 1024 + rn * 128 + lane * 4, 2 * (warp & 3) + 1);
    PIN(a_p); PIN(a_v); PINL(a_h); PINL(a_h1);
    uint32_t rel = lane < 4 && lane >= 2 * wg ? 2 - (tq >> 1) : 0;
    PIN(rel);
    uint32_t ones[4] = {0x3F803F80u, 0x3F803F80u, 0x3F803F80u, 0x3F803F80u};
    PIN(ones[0]); PIN(ones[1]); PIN(ones[2]); PIN(ones[3]);
    {
      asm volatile("{.reg .pred p; .reg .u32 n; mov.u32 n, 0;\n"
                   "W%=: mbarrier.try_wait.parity.acquire.cluster.shared::cta.b64 p, [%0], 0; add.u32 n, n, 1; setp.lt.and.u32 p, n, 0x100000, !p; @p bra W%=;}"
                   ::"r"(bar0 + 8 * B_LZ) : "memory");
      mbar_wait(bar0 + 8 * B_QF);
      unsigned bad = 0;
#pragma unroll
      for (int k = 0; k < 8; k++) bad |= __float_as_uint(lds4(sb + O_Q + k * 4096 + tid * 16 + (lane >> 3) * 4)) ^ par;
      if (__builtin_expect(__any_sync(~0u, bad & 1), 0)) {
#pragma unroll 1
        for (int k = 0; k < 8; k++) {
          uint4 v;
          POLL { v = ldx16(scr->qa + k * 256 + tid); RETRY(((lane & 16) ? ((lane & 8) ? v.w : v.z) : ((lane & 8) ? v.y : v.x)) ^ par) }
          sts16(sb + O_Q + k * 4096 + tid * 16, v);
        }
        asm volatile("fence.proxy.async.shared::cta;" ::: "memory");
      }
      if (warp >= 4) nbar_arrive(1, 256); else nbar(1, 256);
    }
#pragma unroll 1
    for (int t = 0; t < nt; t++) {
      const int v = v0 + t;
      const uint32_t fb = bar0 + (v & 1) * 32, ph = (v >> 1) & 1, av = a_v + (v & 1) * 65536;
      uint32_t vf[4][4][4], cnt;
      auto landed = [&]() {
        cnt = rel + (dep16(&vf[0][0][0]) & (nt >> 8));
        PIN(cnt);
      };
      if (wg == 0) {
        const uint32_t da = DSC + (v & 1) * 4096, db = DSC + O_Q / 16;
#pragma unroll 1
        for (int j = 0; j < 4; j++) {
          mbar_wait(fb + 8 * j, ph);
          asm volatile("wgmma.fence.sync.aligned;" ::: "memory");
#pragma unroll
          for (int k = 0; k < 8; k++)
            wgmma32<0, 0, HI128, HI128>(sx, da + j * 1024 + (k >> 2) * 512 + (k & 3) * 2, db + j * 512 + (k >> 2) * 256 + (k & 3) * 2, k ? 1 : j);
          asm volatile("wgmma.commit_group.sync.aligned;" ::: "memory");
          if (j == VJ) {
#pragma unroll
            for (int i = 0; i < 16; i++) ldsm_t(vf[i >> 2][i & 3], av + (((i >> 2) + rot) & 3) * 8192 + (i & 3) * 2048);
            nbar(5, 256);
            landed();
          }
        }
      } else {
        nbar_arrive(5, 256);
#pragma unroll 1
        for (int j = 0; j < 2; j++) {
          mbar_wait(fb + 16 + 8 * j, ph);
          if (j) spin_until(clock() + VDLY);
#pragma unroll
          for (int q = 0; q < 4; q++)
            if (((q + rot) & 2) == 2 * j)
#pragma unroll
              for (int k = 0; k < 4; k++) ldsm_t(vf[q][k], av + ((q + rot) & 3) * 8192 + k * 2048);
        }
        cnt = 0;
      }
      wg_wait<0>(sx);
      asm volatile("{.reg .pred p; setp.ne.s32 p, %1, 0; @p mbarrier.arrive.shared::cta.b64 _, [%0], %1;}" ::"r"(fb + 8 * B_EMPTY + 8 * tq), "r"(cnt) : "memory");
#pragma unroll 1
      for (int pass = 0;; pass++) {
        int ex = !(t | pass);
        if (wg == 0 && (t | pass)) {
          uint32_t pk[8];
#pragma unroll
          for (int i = 0; i < 8; i++) pk[i] = pack2(ex2(sx[2 * i] * sc - mref[i & 6]), ex2(sx[2 * i + 1] * sc - mref[(i & 6) + 1]));
          asm volatile("stmatrix.sync.aligned.m8n8.x4.shared.b16 [%0], {%2,%3,%4,%5};\n"
                       "stmatrix.sync.aligned.m8n8.x4.shared.b16 [%1], {%6,%7,%8,%9};"
                       ::"r"(a_p), "r"(a_p ^ 32), "r"(pk[0]), "r"(pk[1]), "r"(pk[2]), "r"(pk[3]), "r"(pk[4]), "r"(pk[5]), "r"(pk[6]), "r"(pk[7]) : "memory");
          const uint32_t mx = __vmaxu2(__vmaxu2(__vmaxu2(pk[0], pk[1]), __vmaxu2(pk[2], pk[3])), __vmaxu2(__vmaxu2(pk[4], pk[5]), __vmaxu2(pk[6], pk[7])));
          ex = max(mx, mx << 16) > (127u + TAU) << 23;
          asm volatile("fence.proxy.async.shared::cta;" ::: "memory");
        }
        asm volatile("{.reg .pred p, q; setp.ne.s32 q, %0, 0; bar.red.or.pred p, 4, 256, q; selp.s32 %0, 1, 0, p;}" : "+r"(ex)::"memory");
        if (!ex || pass) break;
        int ln;
        asm volatile("mov.u32 %0, %%laneid;" : "=r"(ln));
        const uint32_t a_pm = sb + O_SM + ln * 16;
        if (wg == 0) {
          float cm[8];
#pragma unroll
          for (int i = 0; i < 8; i++) cm[i] = fmaxf(sx[2 * (i & 6) + (i & 1)], sx[2 * (i & 6) + (i & 1) + 2]);
          tmax<4>(cm, lane, 16); tmax<2>(cm, lane, 8); tmax<1>(cm, lane, 4);
          sts4(a_pm + warp * 4, cm[0] * sc);
        }
        nbar(4, 256);
        const float4 pm = lds16(a_pm);
        const float mn = u2f(__float_as_uint(fmaxf(fmaxf(fmaxf(pm.x, pm.y), fmaxf(pm.z, pm.w)), mrun)) | 1u), al = ex2(mrun - mn);
        mrun = mn;
#pragma unroll
        for (int i = 0; i < 8; i++) {
          const float a = __shfl_sync(~0u, al, 4 * i + (ln & 3)), aw = wg ? a : 1.f;
          mref[i] = __shfl_sync(~0u, mn, 4 * i + (ln & 3));
#pragma unroll
          for (int e = 0; e < 2; e++) {
            const int k = 2 * (i & 6) + (i & 1) + 2 * e;
            o[0][k] *= a; o[1][k] *= a; o[2][k] *= a; o[3][k] *= a; sx[k] *= aw;
          }
        }
      }
      float hv = mrun;
      if (wg) {
        asm volatile("wgmma.fence.sync.aligned;" ::: "memory");
#pragma unroll
        for (int k = 0; k < 4; k++) wgmma32r(sx, ones, DSC + O_P / 16 + k * 64);
        asm volatile("wgmma.commit_group.sync.aligned;" ::: "memory");
        landed();
        asm volatile("{.reg .pred p; setp.ne.s32 p, %1, 0; @p mbarrier.arrive.shared::cta.b64 _, [%0], %1;}" ::"r"(fb + 8 * B_EMPTY + 8 * tq), "r"(cnt) : "memory");
        wg_wait<0>(sx);
        float lv[4];
#pragma unroll
        for (int j = 0; j < 4; j++) lv[j] = (lane & 4) ? sx[4 * j + 1] : sx[4 * j];
        hv = (lane & 16) ? ((lane & 8) ? lv[3] : lv[2]) : ((lane & 8) ? lv[1] : lv[0]);
      }
      asm volatile("{.reg .pred p; setp.eq.s32 p, %3, %4; @p st.relaxed.cluster.b32 [%0], %1; @p st.relaxed.cluster.b32 [%2], %1;}"
                   ::"l"(a_h), "r"(__float_as_uint(hv) | 1u), "l"(a_h1), "r"(t), "r"(nt - 1) : "memory");
#pragma unroll
      for (int q = 0; q < 4; q++) {
        if (q < 2) {
          asm volatile("wgmma.fence.sync.aligned;" ::: "memory");
#pragma unroll
          for (int u = q; u < (q ? 4 : 1); u++) {
#pragma unroll
            for (int k = 0; k < 4; k++) wgmma32r(o[u], vf[u][k], DSC + O_P / 16 + k * 64);
            asm volatile("wgmma.commit_group.sync.aligned;" ::: "memory");
          }
        }
        if (q == 3) {
#pragma unroll
          for (int u = 0; u < 4; u++)
            asm volatile("{.reg .pred p; setp.eq.s32 p, %5, %6; @p ldmatrix.sync.aligned.m8n8.x4.trans.shared.b16 {%0,%1,%2,%3}, [%4];}"
                         : "=r"(z[u][0]), "=r"(z[u][1]), "=r"(z[u][2]), "=r"(z[u][3]) : "r"(a_z[u] + u * 1024), "r"(t), "r"(nt - 1) : "memory");
        }
        if (q == 1) wg_wait<2>(o[q]); else if (q == 2) wg_wait<1>(o[q]); else wg_wait<0>(o[q]);
        if (q == 0 || t == nt - 1)
#pragma unroll
        for (int j = 0; j < 2; j++)
          asm volatile("{.reg .pred p, q, r; setp.eq.s32 p, %5, %6; setp.eq.and.s32 q|r, %7, %8, p; @r st.relaxed.cluster.v4.b32 [%0], {%1,%2,%3,%4};\n"
                       "@q st.shared.v4.b32 [%9], {%1,%2,%3,%4};}"
                       ::"l"(dst[q] + j * 512), "r"(pack2t(o[q][8 * j], o[q][8 * j + 1], 1)), "r"(pack2(o[q][8 * j + 2], o[q][8 * j + 3])),
                         "r"(pack2(o[q][8 * j + 4], o[q][8 * j + 5])), "r"(pack2(o[q][8 * j + 6], o[q][8 * j + 7])), "r"(t), "r"(nt - 1),
                         "r"(qown), "r"(q), "r"(a_own + j * 512) : "memory");
      }
    }
  }
  {
    uint32_t wx[4][4];
    mbar_wait(bar0 + 8 * B_WZ);
#pragma unroll
    for (int u = 0; u < 4; u++) {
      uint2 wp;
      asm volatile("ld.shared.v2.u32 {%0, %1}, [%2];" : "=r"(wp.x), "=r"(wp.y) : "r"(a_w + u * 8) : "memory");
      const bool lo = (g >> 1) == (tq >> 1), hi = (g >> 1) == 2 + (tq >> 1);
      wx[u][0] = lo ? wp.x : 0u; wx[u][1] = lo ? wp.y : 0u; wx[u][2] = hi ? wp.x : 0u; wx[u][3] = hi ? wp.y : 0u;
    }
    auto bad = [&]() {
      const unsigned ok = and3(and3(and3(z[0][0], z[0][1], z[0][2]), and3(z[0][3], z[1][0], z[1][1]), and3(z[1][2], z[1][3], z[2][0])),
                               and3(and3(z[2][1], z[2][2], z[2][3]), and3(z[3][0], z[3][1], z[3][2]), z[3][3]), 0x10001u);
      return __any_sync(~0u, g == 0 && ok != 0x10001u);
    };
    POLL {
      if (it_)
#pragma unroll
        for (int u = 0; u < 4; u++) ldsm_t(z[u], a_z[u] + u * 1024);
      if (!bad() || ++it_ >= SPIN_MAX) break;
    }
    float d0[8][4] = {}, d[8][4], r[8];
#pragma unroll
    for (int i = 0; i < 8; i++) mma16(d0[i], wx[i >> 1], z[i >> 1][2 * (i & 1)], z[i >> 1][2 * (i & 1) + 1]);
    POLL {
#pragma unroll
      for (int u = 0; u < 4; u++) ldsm_t(z[u], a_z[u ^ 2] + u * 1024);
#pragma unroll
      for (int i = 0; i < 8; i++) mma16c(d[i], wx[(i >> 1) ^ 2], z[i >> 1][2 * (i & 1)], z[i >> 1][2 * (i & 1) + 1], d0[i]);
      if (!bad() || ++it_ >= SPIN_MAX) break;
    }
#pragma unroll
    for (int i = 0; i < 8; i++) r[i] = (tq & 2) ? ((g & 1) ? d[i][3] : d[i][2]) : ((g & 1) ? d[i][1] : d[i][0]);
#pragma unroll
    for (int q = 0; q < 2; q++) pub8(p_rec + q * 128, pack2t(r[4 * q], r[4 * q + 1], par) | 1u, pack2(r[4 * q + 2], r[4 * q + 3]));
  }
  const int vt = v0 + nt;
  const uint32_t bufa = sb + (vt & 1) * 65536, fulla = bar0 + (vt & 1) * 32, pha = (vt >> 1) & 1, phb = ((vt + 1) >> 1) & 1;
  const uint32_t bufo = sb + ((vt + 1) & 1) * 65536, fullb = bar0 + ((vt + 1) & 1) * 32;
  uint32_t a_rs = sb + O_R + (warp >> 2) * 1024 + (16 * tq + g) * 16 + ((warp + tq) & 3) * 4;
  if (isA) {
    const int row = 16 * (warp & 6) + 8 * (warp & 1) + (lane & 16) + ((lane & 7) >> 1) + 4 * (lane & 1);
    uint32_t ab = bufa + row * 128 + ((((lane >> 3) & 1) ^ (row & 7)) << 4);
    const uint2* pr = scr->rec + (hd * 32 + warp) * 64 + lane;
    uint32_t a_cb = mapa(bar0 + 8 * B_HZ, (warp & 6) + (lane >> 4)), a_c = a_cb - (O_BAR + 8 * B_HZ - O_CTX) + (2 * rn + (warp & 1)) * 64 + tq * 16;
    uint32_t a_rl = sb + O_R + (32 * (warp & 1) + lane) * 16;
    uint32_t ao = bufo + (16 * warp + 8 * (lane >> 4) + (lane & 7)) * 128 + ((((lane >> 3) & 1) ^ (lane & 7)) << 4);
    uint32_t a_cx = sb + O_CTX + (warp >> 1) * 64 + tq * 16 + (warp & 1) * 8, a_ga = sb + O_SM + (320 + posof(tid & 63)) * 4;
    unsigned* p_ao = scr->xao + b * 64 + (tid & 63);
    unsigned* p_ab = scr->xab + cl * 256 + (2 * (rn & 3) + (warp & 1)) * 32 + (rn >> 2) * 16 + (lane >> 1);
    float xv = cl == 0 ? __bfloat162float(x[64 * rn + (tid & 63)]) : 0.f;
    unsigned p2 = lane >= 28 ? 0 : par;
    PIN(ab); PINL(pr); PIN(a_cb); PIN(a_c); PIN(a_rl); PIN(a_rs); PIN(ao); PIN(a_cx); PIN(a_ga); PINL(p_ao); PINL(p_ab); PIN(p2);
    asm volatile("" : "+f"(xv));
    uint32_t aw[4][4][4];
    auto wo = [&](const int j) {
      mbar_wait(fullb + 8 * j, phb);
#pragma unroll
      for (int mt = 0; mt < 4; mt++) ldsm_t(aw[j][mt], (ao + j * 16384) ^ (mt << 5));
    };
    {
      uint32_t a[4][4][4];
      uint2 z[4], y[4] = {};
      float d[4][4] = {}, r[8];
      mbar_wait(fulla, pha);
      POLL {
#pragma unroll
        for (int q = 0; q < 4; q++) z[q] = ldx8(pr + q * 512);
        RETRY(lop_x3(z[0].x, z[1].x, par) | lop_x3(z[2].x, z[3].x, par))
      }
#pragma unroll
      for (int q = 0; q < 4; q++) {
        if (q == 3) {
          mbar_wait(bar0 + 8 * B_G);
          if (lane < 28)
#pragma unroll
            for (int u = 0; u < 4; u++) y[u] = ldx8(pr + u * 512 + 32);
          __syncwarp();
        }
        mbar_wait(fulla + 8 * q, pha);
#pragma unroll
        for (int mt = 0; mt < 4; mt++) ldsm_t(a[q][mt], (ab + q * 16384) ^ (mt << 5));
#pragma unroll
        for (int mt = 0; mt < 4; mt++) mma16(d[mt], a[q][mt], z[q].x, z[q].y);
      }
      mbar_wait(bar0 + 8 * B_W);
      const float4 W = lds16(sb + O_SM + (384 + 4 * tq) * 4);
#pragma unroll
      for (int i = 0; i < 8; i++) { r[i] = W.x * d[i >> 1][2 * (i & 1)] + W.y * d[i >> 1][2 * (i & 1) + 1]; asm volatile("" : "+f"(r[i])); }
#pragma unroll
      for (int j = 0; j < NPE; j++) wo(j);
      POLL {
        if (it_)
#pragma unroll
          for (int u = 0; u < 4; u++) y[u] = ldx8(pr + u * 512 + 32);
#pragma unroll
        for (int mt = 0; mt < 4; mt++) d[mt][0] = d[mt][1] = d[mt][2] = d[mt][3] = 0.f;
#pragma unroll
        for (int q = 0; q < 4; q++)
#pragma unroll
          for (int mt = 0; mt < 4; mt++) mma16(d[mt], a[q][mt], y[q].x, y[q].y);
        RETRY(or3(lop_x3(y[0].x, y[1].x, p2), lop_x3(y[2].x, y[3].x, p2), 0))
      }
#pragma unroll
      for (int i = 0; i < 8; i++) r[i] = W.w * d[i >> 1][2 * (i & 1) + 1] + (W.z * d[i >> 1][2 * (i & 1)] + r[i]);
      tred<4>(r, lane, 2); tred<2>(r, lane, 1);
      sts4(a_rs, r[0]); sts4(a_rs + 128, r[1]);
      nbar(1, 256);
      send32(a_c, a_cb, sum8(a_rl), lane, lane & 12);
    }
    {
#pragma unroll
      for (int j = NPE; j < NPO; j++) wo(j);
      uint2 c[4];
      mbar_wait(bar0 + 8 * B_HZ);
#pragma unroll
      for (int j = 0; j < 4; j++) asm volatile("ld.shared.v2.u32 {%0, %1}, [%2];" : "=r"(c[j].x), "=r"(c[j].y) : "r"(a_cx + j * 256) : "memory");
      float d[4][4] = {};
#pragma unroll
      for (int j = 0; j < 4; j++) {
        if (j + 1 >= NPO && j < 3) wo(j + 1);
#pragma unroll
        for (int mt = 0; mt < 4; mt++) mma16(d[mt], aw[j][mt], c[j].x, c[j].y);
      }
      const float r0 = (tq & 2) ? ((tq & 1) ? d[3][0] : d[2][0]) : ((tq & 1) ? d[1][0] : d[0][0]);
      const float r1 = (tq & 2) ? ((tq & 1) ? d[3][2] : d[2][2]) : ((tq & 1) ? d[1][2] : d[0][2]);
      sts4(a_rs + 2048, r0); sts4(a_rs + 2048 + 128, r1);
      if (warp >= 2) nbar_arrive(2, 256);
      else {
        mbar_wait(bar0 + 8 * B_TAB);
        const float gav = lds4(a_ga);
        nbar(2, 256);
        const float t = gav * sum8(a_rl + 2048) + xv;
        asm volatile("{.reg .pred p; setp.eq.s32 p, %2, 0; @p red.relaxed.gpu.global.xor.b32 [%0], %1;}"
                     ::"l"(p_ab), "r"(pack2t(t, __shfl_down_sync(~0u, t, 1), par) | 1u), "r"(lane & 1) : "memory");
        pub4(p_ao, __float_as_uint(t) | 1u);
      }
    }
  } else {
    uint32_t af[4][4][4];
    uint32_t ab = bufa + (32 * warp + 8 * (lane >> 4) + (lane & 7)) * 64 + ((((lane >> 3) & 1) ^ ((lane >> 1) & 3)) << 4);
    uint32_t a_d = bufo + wg * 16384 + (8 * (lane >> 4) + (lane & 7)) * 128 + (((2 * (warp & 3) + ((lane >> 3) & 1)) ^ (lane & 7)) << 4);
    uint32_t a_rl = sb + O_R + lane * 16, a_st = sb + O_SM + (352 + 8 * (lane >> 4) + warp) * 4;
    const unsigned* pa = scr->xab + tid;
    uint32_t a_hb = mapa(bar0 + 8 * B_HZ, g), a_h = a_hb - (O_BAR + 8 * B_HZ - O_CTX) + rn * 64 + tq * 16;
    PIN(a_hb); PIN(a_h);
    uint32_t a_hl = sb + O_CTX + wg * 256 + tq * 16, a_t = sb + O_SM + (16 * warp + 8 * (tq & 1) + g) * 4;
    const unsigned* px = scr->xao + 64 * rn + 2 * lane;
    bf16* po = out + 64 * rn + 2 * lane;
    PIN(ab); PIN(a_d); PIN(a_rl); PINL(pa); PIN(a_rs); PIN(a_st); PINL(po); PIN(a_hl); PINL(px); PIN(a_t);
    mbar_wait(bar0 + 8 * B_TAB);
    uint2 cf;
    uint2 bb[4];
    uint2 gbw;
    POLL {
      unsigned bad = 0;
      cf = ldx8(scr->xm + 1024 + (lane & 16) * 16 + 32 * warp + posof(2 * (lane & 15)));
#pragma unroll
      for (int s = 0; s < 4; s++) {
        const uint4 w = ldx16(scr->xm + 1024 - (g & 1) * 512 + 256 * (s >> 1) + 32 * warp + 16 * (s & 1) + 4 * tq);
        bb[s] = make_uint2(__byte_perm(w.x, w.y, 0x7632), __byte_perm(w.z, w.w, 0x7632));
        bad = or3(bad, lop_x3(w.x, w.y, par), lop_x3(w.z, w.w, par));
      }
      gbw = ldx8(scr->xm + 1536 + 64 * rn + posof(2 * lane));
      RETRY(or3(bad, lop_x3(cf.x, cf.y, par), lop_x3(gbw.x, gbw.y, par)))
    }
    float e[4][4] = {};
    unsigned v[8];
    auto item = [&](const int it) {
      mbar_wait(fulla + 8 * it, pha);
#pragma unroll
      for (int i = 0; i < 4; i++) ldsm_t(af[it][i], (ab + it * 16384 + (i >> 1) * 1024) ^ ((i & 1) << 5));
    };
    auto item_mma = [&](const int it) {
#pragma unroll
      for (int i = 0; i < 4; i++) mma16(e[2 * (it & 1) + (i & 1)], af[it][i], bb[(it & 2) + (i >> 1)].x, bb[(it & 2) + (i >> 1)].y);
    };
    unsigned t3 = sch.wt;
    PIN(t3);
    item(0); item_mma(0); item(1); item_mma(1);
    mbar_wait(bar0 + 8 * B_G);
#pragma unroll
    for (int i = 0; i < 8; i++) v[i] = ldx4(pa + i * 256);
    t3 += clock();
    uint32_t have2, have3 = 0;
    do have2 = mbar_test(fulla + 16, pha); while (!have2 && (int)((unsigned)clock() - t3) < 0);
    if (have2) {
      item(2); item_mma(2);
      do have3 = mbar_test(fulla + 24, pha); while (!have3 && (int)((unsigned)clock() - t3) < 0);
      if (have3) { item(3); item_mma(3); }
    }
    float y0, y1, df[4][4], st[2];
    uint32_t bz[4][2] = {};
    auto mm = [&](const int it, const int i) { mma16(df[2 * (it & 1) + (i & 1)], af[it][i], bz[(it & 2) + (i >> 1)][0], bz[(it & 2) + (i >> 1)][1]); };
    POLL {
      if (it_)
#pragma unroll
        for (int i = 0; i < 8; i++) v[i] = ldx4(pa + i * 256);
      y0 = ((bflo(v[0]) + bflo(v[1])) + (bflo(v[2]) + bflo(v[3]))) + ((bflo(v[4]) + bflo(v[5])) + (bflo(v[6]) + bflo(v[7])));
      y1 = ((bfhi(v[0]) + bfhi(v[1])) + (bfhi(v[2]) + bfhi(v[3]))) + ((bfhi(v[4]) + bfhi(v[5])) + (bfhi(v[6]) + bfhi(v[7])));
      const uint32_t zb = pack2(y0 * u2f(cf.x), y1 * u2f(cf.y));
#pragma unroll
      for (int s = 0; s < 4; s++) {
        const uint32_t w = __shfl_sync(~0u, zb, 8 * s + (lane & 7));
        bz[s][0] = (lane & 4) ? 0u : w; bz[s][1] = (lane & 4) ? w : 0u;
      }
      st[0] = y0 + y1; st[1] = y0 * y0 + y1 * y1;
      tred<1>(st, lane, 16);
#pragma unroll
      for (int i = 0; i < 4; i++) df[i][0] = df[i][1] = df[i][2] = df[i][3] = 0.f;
      mm(0, 0); mm(0, 1); mm(1, 0); mm(1, 1);
      st[0] += shx(st[0], 8);
      mm(0, 2); mm(0, 3); mm(1, 2); mm(1, 3);
      RETRY(or3(or3(lop_x3(v[0], v[1], par), lop_x3(v[2], v[3], par), lop_x3(v[4], v[5], par)), lop_x3(v[6], v[7], par), 0))
    }
    uint2 xq[8];
    if (warp == 0)
#pragma unroll
      for (int i = 0; i < 8; i++) xq[i] = ldx8(px + i * 512);
    if (have2) { mm(2, 0); mm(2, 1); mm(2, 2); mm(2, 3); }
    st[0] += shx(st[0], 4);
    st[0] += shx(st[0], 2);
    st[0] += shx(st[0], 1);
    sts4(a_st, st[0]);
    __syncwarp();
    arrive_n(bar0 + 8 * B_ST, lane == 0, 1);
    if (!have2) { item(2); item_mma(2); mm(2, 0); mm(2, 1); mm(2, 2); mm(2, 3); }
    if (!have3) { item(3); item_mma(3); }
    mm(3, 0); mm(3, 1); mm(3, 2); mm(3, 3);
    mbar_wait(bar0 + 8 * B_ST);
    float mean, rstd;
    {
      float4 u[4];
#pragma unroll
      for (int i = 0; i < 4; i++) u[i] = lds16(sb + O_SM + (352 + 4 * i) * 4);
      mean = (((u[0].x + u[0].y) + (u[0].z + u[0].w)) + ((u[1].x + u[1].y) + (u[1].z + u[1].w))) * (1.f / 512.f);
      const float sq = (((u[2].x + u[2].y) + (u[2].z + u[2].w)) + ((u[3].x + u[3].y) + (u[3].z + u[3].w))) * (1.f / 512.f);
      asm("rsqrt.approx.ftz.f32 %0, %1;" : "=f"(rstd) : "f"(fmaxf(sq - mean * mean, 0.f) + 1e-5f));
    }
    float A[4], r[4];
#pragma unroll
    for (int i = 0; i < 4; i++) {
      A[i] = (tq & 2) ? ((tq & 1) ? e[3][i] : e[2][i]) : ((tq & 1) ? e[1][i] : e[0][i]);
      r[i] = (tq & 2) ? ((tq & 1) ? df[3][i] : df[2][i]) : ((tq & 1) ? df[1][i] : df[0][i]);
    }
    sts4(a_rs, rstd * (r[0] + r[1]) + (A[1] - rstd * mean * A[0])); sts4(a_rs + 128, rstd * (r[2] + r[3]) + (A[3] - rstd * mean * A[2]));
    nbar(1, 256);
    if (warp == 7) {
      const float4 g0 = lds16(a_rl), g1 = lds16(a_rl + 1024), u0 = lds16(a_rl + 512), u1 = lds16(a_rl + 1536);
      const float gg = ((g0.x + g0.y) + (g0.z + g0.w)) + ((g1.x + g1.y) + (g1.z + g1.w));
      const float uu = ((u0.x + u0.y) + (u0.z + u0.w)) + ((u1.x + u1.y) + (u1.z + u1.w));
      const float hh = (gg * uu) * rcp(1.f + ex2(gg * (-2.302208198f - 0.1029432397f * gg * gg)));
      send32(a_h, a_hb, hh, lane, 0);
    } else spin_until(clock() + FDLY);
    uint32_t ad[8][4];
    mbar_wait(fullb + 8 * wg, phb);
#pragma unroll
    for (int i = 0; i < 8; i++) ldsm_t(ad[i], a_d + i * 2048);
    float x0, x1;
    if (warp == 0) {
      POLL {
        if (it_)
#pragma unroll
          for (int i = 0; i < 8; i++) xq[i] = ldx8(px + i * 512);
        unsigned bad = 0;
#pragma unroll
        for (int i = 0; i < 4; i++) bad = or3(bad, lop_x3(xq[i].x, xq[i].y, par), lop_x3(xq[i + 4].x, xq[i + 4].y, par));
        RETRY(bad)
      }
      x0 = x1 = 0.f;
#pragma unroll
      for (int i = 0; i < 8; i++) { x0 += u2f(xq[i].x); x1 += u2f(xq[i].y); }
      x0 *= 1.f / 7.f; x1 *= 1.f / 7.f;
    }
    mbar_wait(bar0 + 8 * B_HZ);
    float dd[4][4] = {};
#pragma unroll
    for (int i = 0; i < 4; i++) {
      const float4 hb = lds16(a_hl + i * 64);
      mma16(dd[(2 * i) & 3], ad[2 * i], __float_as_uint(hb.x), __float_as_uint(hb.y));
      mma16(dd[(2 * i + 1) & 3], ad[2 * i + 1], __float_as_uint(hb.z), __float_as_uint(hb.w));
    }
    sts4(a_t, (tq & 1) ? (dd[0][2] + dd[1][2]) + (dd[2][2] + dd[3][2]) : (dd[0][0] + dd[1][0]) + (dd[2][0] + dd[3][0]));
    if (warp) nbar_arrive(2, 256);
    else {
      nbar(2, 256);
      float t0, t1, t2, t3b;
      asm volatile("ld.shared.v2.f32 {%0, %1}, [%4]; ld.shared.v2.f32 {%2, %3}, [%4 + 256];"
                   : "=f"(t0), "=f"(t1), "=f"(t2), "=f"(t3b) : "r"(sb + O_SM + lane * 8) : "memory");
      t0 = bfhi(gbw.x) * (t0 + t2) + x0; t1 = bfhi(gbw.y) * (t1 + t3b) + x1;
      asm volatile("red.relaxed.gpu.global.add.noftz.bf16x2 [%0], %1;" ::"l"(po), "r"(pack2(t0, t1)) : "memory");
      if (f == 0 && tid == 0) stx4(&scr->cnt[0], epoch + 1);
    }
  }
}

static void make_sched(Sched& s) {
  const char* order = "FFAAbcFmmvog..d";
  const double dt = 4985 * 1e-3, dth = 4730 * 1e-3;
  const int nbig = NBIG;
  s.zero = 0; s.dth = (unsigned)(dth * 256 + 0.5);
  double t = 512 * dth + 0;
  int tile = 0, jm = 0;
  for (int i = 0; i < 3; i++) s.nr[i] = s.nt[i] = 0;
  auto add = [&](int c, int type, double step, int win, int b0, int tl) {
    s.r[c][s.nr[c]++] = make_uint2((unsigned)(t + 0.5) | (unsigned)(step + 0.5) << 16, type | win << 4 | (b0 + 64) << 8 | tl << 16);
    if (type == T_KV) s.nt[c]++;
  };
  const int w1 = 6, w2 = 4, wt = 6;
  for (const char* p = order; *p; p++) {
    const char c = *p;
    if (c == 'v' || c == 'o' || c == 'm') {
      const int ty = c == 'v' ? T_UV : c == 'o' ? T_WO : T_MOD;
      const double d = (c == 'm' ? 6000 : c == 'v' ? 5500 : 5500) * 1e-3;
      add(0, ty, 64 * d, wt, 0, c == 'm' ? jm : 0); add(1, ty, 64 * d, wt, 0, c == 'm' ? jm : 0);
      t += (c == 'm' ? 64 : 256) * d; jm += c == 'm';
    } else if (c == 'g' || c == 'd') {
      const double d = (c == 'g' ? 5500 : 5000) * 1e-3;
      add(2, c == 'g' ? T_GU : T_DN, 56 * d, wt, 64, 0);
      t += (c == 'g' ? 224 : 112) * d;
    } else if (c == '.') t += 100;
    else if (c == '-') t -= 100;
    else {
      const int na = c == 'F' ? 0 : c == 'C' || c == 'c' || c == 'a' ? nbig : 64, nf = c == 'A' || c == 'a' ? 0 : 56, n = na + nf;
      const int w = na && nf ? w2 : w1;
      const bool ff = c == 'b' || c == 'c';
      const int cf = c == 'c' ? 20 : 0, ca = cf * 7 / 5;
      t += 3 * ca;
      if (na) add(0, T_KV, n * dt - ca, w, ff ? -56 : 0, tile);
      t -= 3 * ca;
      if (na == 64) add(1, T_KV, n * dt, w, ff ? -56 : 0, tile);
      if (nf) add(2, T_KV, n * dt - cf, w, ff ? 64 : 64 - na, tile);
      tile += n; t += 4 * n * dt;
      s.t4 = (unsigned)t + 600;
    }
  }
  s.dt = (unsigned)(dt * 256 + 0.5); s.d4 = 1560 | 1200 << 16; s.d6 = 3160; s.wt = 250;
}

static void launch(void* const* d_in, void* d_out) {
  static TMaps tms;
  static Sched sch;
  static bool init = false;
  static void* scr = nullptr;
  if (!init) {
    void* fn = nullptr; cudaDriverEntryPointQueryResult qr;
    cudaGetDriverEntryPoint("cuTensorMapEncodeTiled", &fn, cudaEnableDefault, &qr);
    EncFn f = (EncFn)fn;
    const CUtensorMapSwizzle S64 = CU_TENSOR_MAP_SWIZZLE_64B, S128 = CU_TENSOR_MAP_SWIZZLE_128B;
    const CUtensorMapL2promotion P256 = CU_TENSOR_MAP_L2_PROMOTION_L2_256B;
    enc3d(f, &tms.m[0], d_in[2], 64, 512, 64, 8192, 128, 64, 128, 1, S128, CU_TENSOR_MAP_L2_PROMOTION_L2_128B);
    enc3d(f, &tms.m[1], d_in[3], 64, 512, 64, 8192, 128, 64, 64, 2, S128, P256);
    enc3d(f, &tms.m[2], d_in[1], 64, SK, 8, 1024, 128, 64, 64, 2, S128, P256);
    enc3d(f, &tms.m[3], d_in[11], 3072, 256, 2, 6144, 256 * 6144, 32, 256, 1, S64, CU_TENSOR_MAP_L2_PROMOTION_L2_128B);
    enc3d(f, &tms.m[4], d_in[4], 64, 512, 64, 8192, 128, 64, 128, 1, S128, CU_TENSOR_MAP_L2_PROMOTION_L2_128B);
    enc3d(f, &tms.m[5], d_in[5], 512, 128, 32, 1024, 128 * 1024, 64, 128, 1, S128, CU_TENSOR_MAP_L2_PROMOTION_L2_128B);
    enc3d(f, &tms.m[6], d_in[7], 1792, 256, 2, 3584, 256 * 3584, 32, 256, 1, S64, CU_TENSOR_MAP_L2_PROMOTION_L2_128B);
    enc3d(f, &tms.m[7], d_in[8], 1792, 256, 2, 3584, 256 * 3584, 32, 256, 1, S64, CU_TENSOR_MAP_L2_PROMOTION_L2_128B);
    enc3d(f, &tms.m[8], d_in[9], 512, 128, 14, 1024, 128 * 1024, 64, 128, 1, S128, CU_TENSOR_MAP_L2_PROMOTION_L2_128B);
    cudaFuncSetAttribute(fused_kernel, cudaFuncAttributeMaxDynamicSharedMemorySize, SMEM9);
    cudaGetSymbolAddress(&scr, g_scr);
    make_sched(sch);
    init = true;
  }
  fused_kernel<<<NCTA9, 384, SMEM9>>>((const bf16*)d_in[0], (const bf16*)d_in[10], (const bf16*)d_in[11], (bf16*)d_out, (Scratch*)scr, sch, tms);
}

static bool fits() {
  cudaFuncSetAttribute(fused_kernel, cudaFuncAttributeMaxDynamicSharedMemorySize, SMEM9);
  cudaLaunchConfig_t cfg = {};
  cfg.gridDim = dim3(NCTA9); cfg.blockDim = dim3(384); cfg.dynamicSmemBytes = SMEM9;
  cudaLaunchAttribute at[1];
  at[0].id = cudaLaunchAttributeClusterDimension; at[0].val.clusterDim.x = 8; at[0].val.clusterDim.y = 1; at[0].val.clusterDim.z = 1;
  cfg.attrs = at; cfg.numAttrs = 1;
  int n = 0;
  if (cudaOccupancyMaxActiveClusters(&n, fused_kernel, &cfg) != cudaSuccess) { (void)cudaGetLastError(); return false; }
  return n >= NCTA9 / 8;
}
}
#undef BAR_ARM
#undef BAR_ARRIVE
#undef BAR_INIT
#undef B_EMPTY
#undef B_FM
#undef B_FULL
#undef B_G
#undef B_G2
#undef B_H
#undef B_HZ
#undef B_LZ
#undef B_Q2
#undef B_QF
#undef B_ST
#undef B_TAB
#undef B_W
#undef B_WZ
#undef CNT_ADD
#undef DSC
#undef FDLY
#undef HI128
#undef HI64
#undef LANE0
#undef NBIG
#undef NCTA9
#undef NPE
#undef NPO
#undef NSL
#undef O_B
#undef O_BAR
#undef O_CTX
#undef O_DBG
#undef O_EP
#undef O_HW
#undef O_HZ
#undef O_LZ
#undef O_P
#undef O_Q
#undef O_R
#undef O_SILU
#undef O_SM
#undef O_X
#undef PIN
#undef PINL
#undef POLL
#undef QN
#undef RETRY
#undef SK
#undef SMEM9
#undef SMEM_BASE
#undef SPIN_MAX
#undef TAU
#undef VDLY
#undef VJ
#undef X16
#undef fbits

namespace v8 {
typedef __nv_bfloat16 bf16;
#define NCTA 128
#define SK 32768
#define SLOT 32768
#define NSLOT 6
#define OFF_WQ (2 * SLOT)
#define OFF_WUK (4 * SLOT)
#define OFF_Q 196608
#define OFF_P (OFF_Q + 16384)
#define OFF_B (OFF_P + 4096)
#define OFF_R4 (OFF_B + 2304)
#define OFF_SILU (OFF_R4 + 4096)
#define OFF_RA (OFF_SILU + 1024)
#define OFF_SM (OFF_RA + 1024)
#define OFF_BP (OFF_SM + 1792)
#define OFF_CO (OFF_BP + 1024)
#define OFF_BAR (OFF_CO + 1280)
#define OFF_MASK (OFF_BAR + 512)
#define OFF_DBG (OFF_MASK + 16)
#define SMEM_BYTES (OFF_DBG + 128)
#define OFF_MOD OFF_Q
#define OFF_UV (4 * SLOT)
#define OFF_O (5 * SLOT)
#define OFF_G 0
#define OFF_U 16384
#define OFF_D SLOT
#define OFF_XO (OFF_D + 16384)
#define FB_UK 4
#define FB_KV 6
#define FB_MOD 22
#define FB_UV 23
#define FB_O 25
#define FB_G 27
#define FB_D 29
#define EB 30
#define QB 50
#define XB 51
#define SPIN_MAX (1 << 20)
#define BACKOFF 40
#define RATE_NS 652
#define RATE_T0 200
#define RATE_TL 300
#define WINS 0x3222333
#define KVWIN 4
#define RATE_H 650
#define RATE_E 650
#define SMUL 9
#define NPRE0 1
#define NPRE1 3
#define HWIN 4
#define EWIN 3
#define WTEST 450
#define DLY5 650
#define DLY6 600
#define DLY7 600
#define P12(a, b, c, d, e, f, g, h, i, j, k, l) ((unsigned long long)(a) | (b) << 5 | (c) << 10 | (d) << 15 | (e) << 20 | (f) << 25 | \
  (unsigned long long)(g) << 30 | (unsigned long long)(h) << 35 | (unsigned long long)(i) << 40 | (unsigned long long)(j) << 45 | \
  (unsigned long long)(k) << 50 | (unsigned long long)(l) << 55)
#define ORDER0 P12(0, 1, 2, 3, 4, 5, 16, 6, 7, 8, 9, 10)
#define ORDER1 P12(11, 12, 13, 14, 15, 17, 18, 19, 20, 23, 21, 22)
#define TAIL_K 17
#define RS 16
template <int N> struct IC { static constexpr int value = N; };
struct TMaps { CUtensorMap m[9]; };

struct __align__(128) Scratch {
  uint4 xo[128 * 64 * RS];
  uint2 ml[32 * 64];
  unsigned h[8 * 256];
  unsigned qa[32 * 256];
  unsigned xc[128 * 64];
  unsigned xao[8 * 512];
  unsigned xf[112 * 512];
  unsigned xm[2048];
  unsigned cnt[5 * 32];
};
__device__ Scratch g_scr;
#define g_xo scr->xo
#define g_ml scr->ml
#define g_h scr->h
#define g_qa scr->qa
#define g_xc scr->xc
#define g_xao scr->xao
#define g_xf scr->xf
#define g_xm scr->xm
#define g_epoch scr->cnt[0]

__device__ __forceinline__ uint32_t s2u(const void* p) { return (uint32_t)__cvta_generic_to_shared(p); }
__device__ __forceinline__ float bflo(uint32_t u) { return __uint_as_float(u << 16); }
__device__ __forceinline__ float bfhi(uint32_t u) { return __uint_as_float(u & 0xffff0000u); }
__device__ __forceinline__ float u2f(uint32_t u) { return __uint_as_float(u); }
__device__ __forceinline__ void fma8(float* acc, uint4 v, float s) {
  acc[0] += s * bflo(v.x); acc[1] += s * bfhi(v.x); acc[2] += s * bflo(v.y); acc[3] += s * bfhi(v.y);
  acc[4] += s * bflo(v.z); acc[5] += s * bfhi(v.z); acc[6] += s * bflo(v.w); acc[7] += s * bfhi(v.w);
}
__device__ __forceinline__ uint32_t pack2(float a, float b) {
  __nv_bfloat162 p = __floats2bfloat162_rn(a, b); return *(uint32_t*)&p;
}
__device__ __forceinline__ float bfr(float v) { return bfhi(pack2(v, v)); }
__device__ __forceinline__ float silu_bf(float c) { return bfr(__fdividef(c, 1.f + __expf(-c))); }
#define fbits(v) ((__float_as_uint(v) & ~1u) | par)
__device__ __forceinline__ uint32_t pack2t(float a, float b, unsigned par) {
  const uint32_t ua = ((__float_as_uint(a) + ((par ^ 1) << 16)) & 0xFFFE0000u) | (par << 16);
  return __byte_perm(ua, pack2(b, b), 0x7632);
}
__device__ __forceinline__ void nbar(int id, int n) { asm volatile("bar.sync %0, %1;" ::"r"(id), "r"(n) : "memory"); }
__device__ __forceinline__ void nbar_arrive(int id, int n) { asm volatile("bar.arrive %0, %1;" ::"r"(id), "r"(n) : "memory"); }
__device__ __forceinline__ uint4 ldc16(const void* p) {
  uint4 v; asm volatile("ld.relaxed.cta.global.v4.u32 {%0,%1,%2,%3}, [%4];" : "=r"(v.x), "=r"(v.y), "=r"(v.z), "=r"(v.w) : "l"(p) : "memory"); return v;
}
__device__ __forceinline__ unsigned ldc4(const void* p) {
  unsigned v; asm volatile("ld.relaxed.cta.global.u32 %0, [%1];" : "=r"(v) : "l"(p) : "memory"); return v;
}
__device__ __forceinline__ uint4 ldx16(const void* p) {
  uint4 v; asm volatile("ld.relaxed.gpu.global.v4.u32 {%0,%1,%2,%3}, [%4];" : "=r"(v.x), "=r"(v.y), "=r"(v.z), "=r"(v.w) : "l"(p) : "memory"); return v;
}
__device__ __forceinline__ unsigned ldx4(const void* p) {
  unsigned v; asm volatile("ld.relaxed.gpu.global.u32 %0, [%1];" : "=r"(v) : "l"(p) : "memory"); return v;
}
__device__ __forceinline__ unsigned long long ldx64(const void* p) {
  unsigned long long v; asm volatile("ld.relaxed.gpu.global.u64 %0, [%1];" : "=l"(v) : "l"(p) : "memory"); return v;
}
__device__ __forceinline__ void stx16(void* p, uint4 v) {
  asm volatile("st.relaxed.gpu.global.v4.u32 [%0], {%1,%2,%3,%4};" ::"l"(p), "r"(v.x), "r"(v.y), "r"(v.z), "r"(v.w) : "memory");
}
__device__ __forceinline__ void stx8(void* p, uint2 v) { asm volatile("st.relaxed.gpu.global.v2.u32 [%0], {%1,%2};" ::"l"(p), "r"(v.x), "r"(v.y) : "memory"); }
__device__ __forceinline__ void stx4(void* p, unsigned v) { asm volatile("st.relaxed.gpu.global.u32 [%0], %1;" ::"l"(p), "r"(v) : "memory"); }
__device__ __forceinline__ unsigned lop_x3(unsigned a, unsigned b, unsigned c) {
  unsigned d; asm("lop3.b32 %0, %1, %2, %3, 0x7E;" : "=r"(d) : "r"(a), "r"(b), "r"(c)); return d; }
#define X16(v) (lop_x3(v.x, v.y, par) | lop_x3(v.z, v.w, par))
#define X8(v) lop_x3(v.x, v.y, par)
#define RETRY(bad) if (!__any_sync(~0u, (bad) & 1) || ++it_ >= SPIN_MAX) break; __nanosleep(BACKOFF);
#define POLL _Pragma("unroll 1") for (int it_ = 0;;)
__device__ __forceinline__ void mbar_wait(uint32_t bar) {
  uint32_t ok; int it = 0;
  do {
    asm volatile("{.reg .pred p; mbarrier.try_wait.parity.shared::cta.b64 p, [%1], 0; selp.u32 %0,1,0,p;}"
                 : "=r"(ok) : "r"(bar) : "memory");
  } while (!ok && ++it < SPIN_MAX);
}
__device__ __forceinline__ float ex2(float v) { float r; asm("ex2.approx.ftz.f32 %0, %1;" : "=f"(r) : "f"(v)); return r; }
__device__ __forceinline__ float rcp(float v) { float r; asm("rcp.approx.ftz.f32 %0, %1;" : "=f"(r) : "f"(v)); return r; }
__device__ __forceinline__ void mma16(float* d, const uint32_t* a, uint32_t b0, uint32_t b1) {
  asm volatile("mma.sync.aligned.m16n8k16.row.col.f32.bf16.bf16.f32 {%0,%1,%2,%3}, {%4,%5,%6,%7}, {%8,%9}, {%0,%1,%2,%3};"
               : "+f"(d[0]), "+f"(d[1]), "+f"(d[2]), "+f"(d[3]) : "r"(a[0]), "r"(a[1]), "r"(a[2]), "r"(a[3]), "r"(b0), "r"(b1));
}
__device__ __forceinline__ float4 lds16(uint32_t a) {
  float4 v; asm volatile("ld.shared.v4.f32 {%0,%1,%2,%3}, [%4];" : "=f"(v.x), "=f"(v.y), "=f"(v.z), "=f"(v.w) : "r"(a) : "memory"); return v;
}
__device__ __forceinline__ void ldsm_t(uint32_t* r, uint32_t a) {
  asm volatile("ldmatrix.sync.aligned.m8n8.x4.trans.shared.b16 {%0,%1,%2,%3}, [%4];" : "=r"(r[0]), "=r"(r[1]), "=r"(r[2]), "=r"(r[3]) : "r"(a) : "memory");
}
__device__ __forceinline__ void ldsm(uint32_t* r, uint32_t a) {
  asm volatile("ldmatrix.sync.aligned.m8n8.x4.shared.b16 {%0,%1,%2,%3}, [%4];" : "=r"(r[0]), "=r"(r[1]), "=r"(r[2]), "=r"(r[3]) : "r"(a) : "memory");
}
template <int N>
__device__ __forceinline__ void tred(float* a, int lane, int m) {
  const bool hi = lane & m;
#pragma unroll
  for (int i = 0; i < N; i++) {
    float send = hi ? a[i] : a[i + N], keep = hi ? a[i + N] : a[i];
    a[i] = keep + __shfl_xor_sync(~0u, send, m);
  }
}
template <int N>
__device__ __forceinline__ void tmax(float* a, int lane, int m) {
  const bool hi = lane & m;
#pragma unroll
  for (int i = 0; i < N; i++) {
    float send = hi ? a[i] : a[i + N], keep = hi ? a[i + N] : a[i];
    a[i] = fmaxf(keep, __shfl_xor_sync(~0u, send, m));
  }
}
__device__ __forceinline__ void arrive2(uint32_t bar, uint32_t rbar, bool local, bool remote) {
  asm volatile("{.reg .pred p, q; setp.ne.s32 p, %2, 0; setp.ne.s32 q, %3, 0; @p mbarrier.arrive.shared::cta.b64 _, [%0];\n"
               "@q mbarrier.arrive.relaxed.cluster.shared::cluster.b64 _, [%1];}" ::"r"(bar), "r"(rbar), "r"((int)local), "r"((int)remote) : "memory");
}
__device__ __forceinline__ unsigned long long stream_policy() {
  unsigned long long p;
  asm volatile("createpolicy.fractional.L2::evict_first.b64 %0, 1.0;" : "=l"(p));
  return p;
}
__device__ __forceinline__ void tma3d(uint32_t dst, const CUtensorMap* tm, uint32_t bar, int c0, int c1, int c2) {
  asm volatile("cp.async.bulk.tensor.3d.shared::cluster.global.mbarrier::complete_tx::bytes.L2::cache_hint [%0], [%1, {%3, %4, %5}], [%2], %6;"
               ::"r"(dst), "l"(tm), "r"(bar), "r"(c0), "r"(c1), "r"(c2), "l"(stream_policy()) : "memory");
}
__device__ __forceinline__ void st_async2(uint32_t dst, uint32_t bar, float v0, float v1) {
  asm volatile("st.async.shared::cluster.mbarrier::complete_tx::bytes.v2.f32 [%0], {%1, %2}, [%3];" ::"r"(dst), "f"(v0), "f"(v1), "r"(bar) : "memory");
}
__device__ __forceinline__ void st_pair(int mode, uint32_t dst, uint32_t bar, float v0, float v1) {
  asm volatile("{.reg .pred p, q; setp.eq.s32 p, %4, 1; setp.eq.s32 q, %4, 2; @p st.shared.v2.f32 [%0], {%1, %2};\n"
               "@q st.async.shared::cluster.mbarrier::complete_tx::bytes.v2.f32 [%0], {%1, %2}, [%3];}"
               ::"r"(dst), "f"(v0), "f"(v1), "r"(bar), "r"(mode) : "memory");
}
__device__ __forceinline__ void spin_until(unsigned t) { while ((int)((unsigned)clock() - t) < 0) {} }
__device__ __forceinline__ unsigned wait_until(unsigned t) {
  unsigned now;
  for (;;) {
    asm volatile("mov.u32 %0, %%globaltimer_lo;" : "=r"(now));
    if ((int)(now - t) >= 0) break;
  }
  return now;
}
#define PIN(x) asm volatile("" : "+r"(x))
#define PINL(x) asm volatile("" : "+l"(x))
#define BAR_ARRIVE(i) asm volatile("mbarrier.arrive.shared::cta.b64 _, [%0];" ::"r"(bar0 + 8 * (i)) : "memory")
#define CNT_ADD(c) asm volatile("red.relaxed.gpu.global.add.u32 [%0], 1;" ::"l"(scr->cnt + (c)) : "memory")
#define BAR_INIT(i, cnt) asm volatile("mbarrier.init.shared::cta.b64 [%0], %1;" ::"r"(bar0 + 8 * (i)), "r"(cnt) : "memory")
#define BAR_ARM(i, bytes) asm volatile("mbarrier.arrive.expect_tx.shared::cta.b64 _, [%0], %1;" ::"r"(bar0 + 8 * (i)), "r"(bytes) : "memory")

__device__ __forceinline__ void tail(unsigned char* smem, Scratch* __restrict__ scr, const bf16* __restrict__ x, bf16* __restrict__ out,
                                     const unsigned par, const unsigned epoch, const int warp) {
  int tid, b;
  asm volatile("mov.u32 %0, %%tid.x;" : "=r"(tid));
  asm volatile("mov.u32 %0, %%ctaid.x;" : "=r"(b));
  const int lane = tid & 31, g = lane >> 2, tq = lane & 3;
  const uint32_t sb = __shfl_sync(~0u, s2u(smem), 0), bar0 = sb + OFF_BAR;
  float* s_sm = (float*)(smem + OFF_SM);
  const int prow = 4 * (lane >> 4) + ((lane & 7) >> 1) + 8 * (lane & 1);
  const float* s_co = (const float*)(smem + OFF_CO);
  const int opos = (b & 15) * 32 + (lane & 16) + 2 * (lane & 6) + ((lane >> 2) & 2) + (lane & 1);
  const float xv = b < 16 ? __bfloat162float(x[(b & 15) * 32 + lane]) : 0.f;
  const int rk = b & 1, ob = 32 * rk + ((b >> 1) & 31);
  uint32_t psb;
  asm volatile("mapa.shared::cluster.u32 %0, %1, %2;" : "=r"(psb) : "r"(sb), "r"(rk ^ 1));
  {
    uint32_t a[8][4];
    {
      const int rg = tid >> 4;
      const uint4* src = g_xo + ((size_t)b * 64 + rg) * RS;
      const uint32_t dst = sb + OFF_XO + rg * 256 + (((tid & 15) ^ (rg & 7)) << 4);
      unsigned long long todo = 0x0001000100010001ull;
#pragma unroll 1
      for (int it = 0; it < SPIN_MAX * 16; it++) {
        unsigned long long mk = *(volatile unsigned long long*)(smem + OFF_MASK);
        const unsigned long long nw = (mk >> rg) & todo;
        todo ^= nw;
#pragma unroll
        for (int i = 0; i < 4; i++)
          if (nw >> (16 * i) & 1)
            asm volatile("cp.async.cg.shared.global [%0], [%1], 16;" ::"r"(dst + i * 4096), "l"(src + i * 16 * RS + (tid & 15)) : "memory");
        if (!__any_sync(~0u, todo != 0)) break;
      }
      asm volatile("cp.async.mbarrier.arrive.noinc.shared::cta.b64 [%0];" ::"r"(bar0 + 8 * (XB + 2)) : "memory");
    }
    mbar_wait(bar0 + 8 * FB_UV); mbar_wait(bar0 + 8 * (FB_UV + 1));
    const uint32_t ab = sb + OFF_UV + (warp >> 2) * 8192 + (8 * (lane >> 4) + (lane & 7)) * 128 + (((2 * (warp & 3) + ((lane >> 3) & 1)) ^ (lane & 7)) << 4);
#pragma unroll
    for (int s = 0; s < 8; s++) ldsm_t(a[s], ab + (s >> 2) * 16384 + (s & 3) * 2048);
    const int chn = 2 * warp + (tq & 1);
    uint32_t a_b = sb + OFF_B + (tq >> 1) * 272 + (32 * (chn >> 2) + 8 * (g >> 1) + 2 * (chn & 3) + (g & 1)) * 2;
    uint32_t a_bq = sb + OFF_B + (lane & 1) * 272 + (lane >> 3) * 16;
    unsigned* p_c = g_xc + (b >> 2) * 256 + warp * 32 + (b & 3) * 8 + (g & 3) * 2 + (g >> 2);
    PIN(a_b); PIN(a_bq); PINL(p_c);
    mbar_wait(bar0 + 8 * (XB + 6));
    uint32_t wb[8];
#pragma unroll
    for (int s = 0; s < 8; s++) wb[s] = *(const uint32_t*)(smem + OFF_RA + (4 * s + tq) * 4);
    const float invL = *(const float*)(smem + OFF_RA + 128);
    float ov;
    POLL {
      mbar_wait(bar0 + 8 * (XB + 2));
      uint32_t ao[4][4];
#pragma unroll
      for (int s = 0; s < 4; s++)
        ldsm_t(ao[s], sb + OFF_XO + (16 * s + 8 * (lane >> 4) + (lane & 7)) * 256 + (((2 * warp + ((lane >> 3) & 1)) ^ (lane & 7)) << 4));
      float d[4][4] = {};
#pragma unroll
      for (int s = 0; s < 4; s++) mma16(d[s], ao[s], wb[2 * s], wb[2 * s + 1]);
      const unsigned p2 = par * 0x10001u;
      unsigned bad = 0;
#pragma unroll
      for (int s = 0; s < 4; s++) bad |= lop_x3(ao[s][0], ao[s][1], p2) | lop_x3(ao[s][2], ao[s][3], p2);
      bad = g == 0 ? bad | (bad >> 16) : 0u;
      ov = (tq & 1) ? (d[0][2] + d[1][2]) + (d[2][2] + d[3][2]) : (d[0][0] + d[1][0]) + (d[2][0] + d[3][0]);
      if (__builtin_expect(!__any_sync(~0u, bad & 1) || ++it_ >= SPIN_MAX, 1)) break;
#pragma unroll
      for (int i = 0; i < 4; i++)
        asm volatile("cp.async.cg.shared.global [%0], [%1], 16;"
                     ::"r"(sb + OFF_XO + ((lane >> 1) + 16 * i) * 256 + (((2 * warp + (lane & 1)) ^ ((lane >> 1) & 7)) << 4)),
                       "l"(g_xo + ((size_t)b * 64 + (lane >> 1) + 16 * i) * RS + 2 * warp + (lane & 1)) : "memory");
      asm volatile("cp.async.wait_all;" ::: "memory");
      __syncwarp();
    }
    {
      const float lo = ov - bfhi(__float_as_uint(ov));
      asm volatile("st.shared.u16 [%0], %1;" ::"r"(a_b), "h"((unsigned short)((tq & 2) ? pack2(lo, lo) : __float_as_uint(ov) >> 16)) : "memory");
    }
    nbar(1, 256);
    float d[4][4] = {};
#pragma unroll
    for (int y = 0; y < 4; y++) {
      uint32_t bq[4];
      ldsm(bq, a_bq + 64 * y);
      mma16(d[(2 * y) & 3], a[2 * y], bq[0], bq[1]); mma16(d[(2 * y + 1) & 3], a[2 * y + 1], bq[2], bq[3]);
    }
    const float r0 = ((d[0][0] + d[0][1]) + (d[1][0] + d[1][1])) + ((d[2][0] + d[2][1]) + (d[3][0] + d[3][1]));
    const float r1 = ((d[0][2] + d[0][3]) + (d[1][2] + d[1][3])) + ((d[2][2] + d[2][3]) + (d[3][2] + d[3][3]));
    if (tq == 0) stx4(p_c, pack2t(r0 * invL, r1 * invL, par));
  }
  unsigned tpub = clock();
  mbar_wait(bar0 + 8 * (XB + 4));
  const float gav = s_co[256 + (opos & 31)];
  const float gbv = s_co[288 + (lane & 4) + 2 * (lane & 1) + ((lane >> 1) & 1)];
  float4 cf[2];
#pragma unroll
  for (int s = 0; s < 2; s++) cf[s] = *(const float4*)(s_co + 32 * warp + 16 * s + 4 * tq);
  {
    uint32_t a[2][4][4];
    mbar_wait(bar0 + 8 * (FB_O + (warp >> 2)));
    const uint32_t ab = sb + OFF_O + (32 * warp + prow) * 128 + ((((lane >> 3) & 1) ^ (prow & 7)) << 4);
#pragma unroll
    for (int i = 0; i < 8; i++) ldsm_t(a[i >> 2][i & 3], (ab + (i >> 2) * 2048) ^ ((i & 3) << 5));
    uint4 v;
    const unsigned* pc = g_xc + (4 * (b >> 4) + 2 * rk + (warp >> 2)) * 256 + 64 * (warp & 3) + 2 * lane;
    uint32_t ro = ((tq >> 1) == rk ? sb : psb) + OFF_P + (8 * (tq & 1) + g) * 144 + (8 * rk + warp) * 8;
    uint32_t a_q = sb + OFF_P + (8 * (lane >> 4) + (lane & 7)) * 144;
    unsigned* p_ao = g_xao + (b >> 5) * 1024 + (opos >> 4) * 32 + (b & 16) + (opos & 15);
    PIN(ro); PIN(a_q); PINL(p_ao); PINL(pc);
    spin_until(tpub + DLY5);
    POLL {
      const unsigned long long u0 = ldx64(pc);
      v.x = (unsigned)u0; v.y = u0 >> 32;
      RETRY(X8(v))
    }
    v.z = lane & 16 ? v.x : 0u; v.w = lane & 16 ? v.y : 0u;
    if (lane & 16) v.x = v.y = 0u;
    float d[4][4] = {};
#pragma unroll
    for (int mt = 0; mt < 4; mt++) mma16(d[mt], a[0][mt], v.x, v.y);
#pragma unroll
    for (int mt = 0; mt < 4; mt++) mma16(d[mt], a[1][mt], v.z, v.w);
    float r[8];
#pragma unroll
    for (int i = 0; i < 8; i++) r[i] = d[i >> 1][2 * (i & 1)] + d[i >> 1][2 * (i & 1) + 1];
    tred<4>(r, lane, 2); tred<2>(r, lane, 1);
    st_pair((tq >> 1) == rk ? 1 : 2, ro, psb + OFF_BAR + 8 * (XB + 3), r[0], r[1]);
    __syncwarp();
    if (lane == 0) BAR_ARRIVE(XB + 3);
    if (warp == 0) {
      mbar_wait(bar0 + 8 * (XB + 3));
      float p[8];
#pragma unroll
      for (int i = 0; i < 8; i++) {
        const float4 q = lds16(a_q + i * 16);
        p[i] = (lane & 8) ? q.y + q.w : q.x + q.z;
      }
      const float t = ((p[0] + p[1]) + (p[2] + p[3])) + ((p[4] + p[5]) + (p[6] + p[7]));
      stx4(p_ao, fbits(gav * t + xv));
    }
  }
  tpub = clock();
  if (b < 112) {
    uint32_t af[2][4][4], ad[4][4];
    const uint32_t ab = sb + (32 * warp + 8 * (lane >> 4) + (lane & 7)) * 64 + ((((lane >> 3) & 1) ^ ((lane >> 1) & 3)) << 4);
    uint32_t ro = ((tq & 1) == rk ? sb : psb) + OFF_R4 + (8 * (tq >> 1) + g) * 176 + (10 * rk + warp) * 8;
    uint32_t a_q = sb + OFF_R4 + (8 * (lane >> 4) + (lane & 7)) * 176 + (lane & 8) * 10;
    uint32_t a_d = sb + OFF_D + warp * 2048 + (8 * (lane >> 4) + (lane & 7)) * 128 + ((((lane >> 3) & 1) ^ (lane & 7)) << 4);
    unsigned* p_f = g_xf + b * 512 + 64 * warp + 16 * tq + 2 * g;
    const unsigned* pa = g_xao + (g >> 1) * 1024 + 512 * rk + 64 * warp + 4 * (lane & 7);
    PIN(ro); PIN(a_q); PIN(a_d); PINL(p_f); PINL(pa);
    spin_until(tpub + DLY6);
    uint4 v[2];
    {
      bool have = false;
      POLL {
        v[0] = ldx16(pa); v[1] = ldx16(pa + 32);
        const unsigned t1 = (unsigned)clock() + WTEST;
        while (!have && (int)((unsigned)clock() - t1) < 0) {
          uint32_t ok;
          asm volatile("{.reg .pred p, q; mbarrier.test_wait.parity.shared::cta.b64 p, [%1], 0; mbarrier.test_wait.parity.shared::cta.b64 q, [%1+8], 0;\n"
                       "and.pred p, p, q; vote.sync.all.pred p, p, 0xffffffff; selp.u32 %0, 1, 0, p;}" : "=r"(ok) : "r"(bar0 + 8 * FB_G) : "memory");
          if (ok) {
#pragma unroll
            for (int i = 0; i < 8; i++) ldsm_t(af[i >> 2][i & 3], (ab + ((i & 2) ? OFF_U : OFF_G) + (i >> 2) * 1024) ^ ((i & 1) << 5));
            have = true;
          }
        }
        if (!__any_sync(~0u, (X16(v[0]) | X16(v[1])) & 1) || ++it_ >= SPIN_MAX) break;
      }
      float df[4][4] = {}, dg[2][4] = {};
      uint32_t zb[4];
      const uint32_t one = g == 0 ? 0x3F803F80u : 0u;
#pragma unroll
      for (int s = 0; s < 2; s++) {
        const uint32_t y0 = pack2(u2f(v[s].x), u2f(v[s].y)), y1 = pack2(u2f(v[s].z), u2f(v[s].w));
        const uint32_t ya[4] = {y0, one, y1, one};
        mma16(dg[s], ya, y0, y1);
        zb[2 * s] = pack2(u2f(v[s].x) * cf[s].x, u2f(v[s].y) * cf[s].y); zb[2 * s + 1] = pack2(u2f(v[s].z) * cf[s].z, u2f(v[s].w) * cf[s].w);
      }
      float st[2] = {(dg[0][2] + dg[0][3]) + (dg[1][2] + dg[1][3]), (dg[0][0] + dg[0][1]) + (dg[1][0] + dg[1][1])};
      if (!have) {
        mbar_wait(bar0 + 8 * FB_G); mbar_wait(bar0 + 8 * (FB_G + 1));
#pragma unroll
        for (int i = 0; i < 8; i++) ldsm_t(af[i >> 2][i & 3], (ab + ((i & 2) ? OFF_U : OFF_G) + (i >> 2) * 1024) ^ ((i & 1) << 5));
      }
#pragma unroll
      for (int i = 0; i < 8; i++) mma16(df[i & 3], af[i >> 2][i & 3], zb[2 * (i >> 2)], zb[2 * (i >> 2) + 1]);
#pragma unroll
      for (int o2 = 1; o2 < 4; o2 <<= 1) { st[0] += __shfl_xor_sync(~0u, st[0], o2); st[1] += __shfl_xor_sync(~0u, st[1], o2); }
#pragma unroll
      for (int o2 = 4; o2 < 32; o2 <<= 1) st[1] += __shfl_xor_sync(~0u, st[1], o2);
      float r[8];
#pragma unroll
      for (int i = 0; i < 8; i++) r[i] = df[i >> 1][2 * (i & 1)] + df[i >> 1][2 * (i & 1) + 1];
      tred<4>(r, lane, 2); tred<2>(r, lane, 1);
      const int md = (tq & 1) == rk ? 1 : 2;
      st_pair(md, ro, psb + OFF_BAR + 8 * (XB + 5), r[0], r[1]);
      st_pair(lane < 2 ? md : 0, ro + 16 * 176, psb + OFF_BAR + 8 * (XB + 5), st[0], st[1]);
      __syncwarp();
      if (lane == 0) BAR_ARRIVE(XB + 5);
      mbar_wait(bar0 + 8 * FB_D);
#pragma unroll
      for (int mt = 0; mt < 4; mt++)
        ldsm_t(ad[mt], a_d ^ (mt << 5));
    }
    mbar_wait(bar0 + 8 * (XB + 5));
    {
      float4 q[5], u[8];
#pragma unroll
      for (int i = 0; i < 5; i++) q[i] = lds16(a_q + i * 16);
#pragma unroll
      for (int i = 0; i < 8; i++) u[i] = *(const float4*)(smem + OFF_R4 + 16 * 176 + (i >> 2) * 80 + (i & 3) * 16);
      float p[6] = {((q[0].x + q[0].z) + (q[1].x + q[1].z)) + ((q[2].x + q[2].z) + (q[3].x + q[3].z)), q[4].x, q[4].z,
                    ((q[0].y + q[0].w) + (q[1].y + q[1].w)) + ((q[2].y + q[2].w) + (q[3].y + q[3].w)), q[4].y, q[4].w};
      tred<3>(p, lane, 8);
      const float P = p[0], A1 = p[1], A2 = p[2];
      const float mean = (((u[0].x + u[0].z) + (u[1].x + u[1].z)) + ((u[2].x + u[2].z) + (u[3].x + u[3].z)) +
                          ((u[4].x + u[4].z) + (u[5].x + u[5].z)) + ((u[6].x + u[6].z) + (u[7].x + u[7].z))) * (1.f / 512.f);
      const float sq = (((u[0].y + u[0].w) + (u[1].y + u[1].w)) + ((u[2].y + u[2].w) + (u[3].y + u[3].w)) +
                         ((u[4].y + u[4].w) + (u[5].y + u[5].w)) + ((u[6].y + u[6].w) + (u[7].y + u[7].w))) * (1.f / 512.f);
      float rstd;
      asm("rsqrt.approx.ftz.f32 %0, %1;" : "=f"(rstd) : "f"(fmaxf(sq - mean * mean, 0.f) + 1e-5f));
      const float gg = bfr(rstd * (P - mean * A1) + A2);
      const float uu = __shfl_xor_sync(~0u, gg, 16);
      const float hh = bfr(gg * rcp(1.f + ex2(gg * (-2.302208198f - 0.1029432397f * gg * gg)))) * uu;
      const uint32_t hw = pack2(hh, __shfl_down_sync(~0u, hh, 1));
      const uint32_t b0 = __shfl_sync(~0u, hw, 2 * tq), b1 = __shfl_sync(~0u, hw, 2 * tq + 8);
      float f0 = 0, f1 = 0;
#pragma unroll
      for (int mt = 0; mt < 4; mt++) {
        float dd[4] = {0, 0, 0, 0};
        mma16(dd, ad[mt], b0, b1);
        if (tq == mt) { f0 = dd[0]; f1 = dd[2]; }
      }
      stx8(p_f, make_uint2(fbits(f0), fbits(f1)));
    }
    tpub = clock();
    if (b < 64 && warp == (b >> 3)) {
      const uint4 y = (b & 4) ? v[1] : v[0];
      float a4[4] = {u2f(y.x), u2f(y.y), u2f(y.z), u2f(y.w)};
      tred<2>(a4, lane, 16); tred<1>(a4, lane, 8);
      a4[0] += __shfl_xor_sync(~0u, a4[0], 4);
      if (!(lane & 4)) s_sm[416 + 8 * (lane >> 4) + 2 * tq + ((lane >> 3) & 1)] = a4[0];
      if (warp == 7) nbar_arrive(2, 256);
    } else if (b < 64 && warp == 7) nbar_arrive(2, 256);
    if (b < 64 && warp < 7) {
      uint4 v;
      const unsigned* pf = g_xf + (tid >> 1) * 512 + 8 * ob + 4 * (tid & 1);
      const int col = 16 * (ob >> 1) + 4 * (ob & 1) + ((tid >> 1) & 3) + 8 * (tid & 1);
      bf16* po = out + col;
      PINL(po); PINL(pf);
      spin_until(tpub + DLY7);
      POLL { v = ldx16(pf); RETRY(X16(v)) }
      float f[4] = {u2f(v.x), u2f(v.y), u2f(v.z), u2f(v.w)};
      tred<2>(f, lane, 16); tred<1>(f, lane, 8);
      f[0] += __shfl_xor_sync(~0u, f[0], 4); f[0] += __shfl_xor_sync(~0u, f[0], 2);
      if (!(lane & 6)) s_sm[352 + warp * 8 + 4 * (lane & 1) + (lane >> 3)] = f[0];
      nbar(2, 256);
      if (tid < 8) {
        const float* q = s_sm + 352 + tid;
        const float t = ((q[0] + q[8]) + (q[16] + q[24])) + ((q[32] + q[40]) + q[48]);
        *po = __float2bfloat16(s_sm[416 + (col & 15)] + bfr(gbv * bfr(t)));
        if (b == 0 && tid == 0) stx4(&g_epoch, epoch + 1);
      }
    }
  }
}

__global__ void __cluster_dims__(2, 1, 1) __launch_bounds__(384, 1)
fused_kernel(const bf16* __restrict__ x, const bf16* __restrict__ cvec, const bf16* __restrict__ w_mod, bf16* __restrict__ out,
             Scratch* __restrict__ scr, const __grid_constant__ TMaps tms) {
  extern __shared__ __align__(1024) unsigned char smem[];
  const int tid = threadIdx.x, warp = __shfl_sync(~0u, tid >> 5, 0), lane = tid & 31;
  const int b = blockIdx.x, rk = b & 1, pr = b >> 1, hd = b >> 2;
  uint32_t sb = s2u(smem), bar0 = sb + OFF_BAR;

  unsigned gt_start;
  asm volatile("mov.u32 %0, %%globaltimer_lo;" : "=r"(gt_start));
  const int g = lane >> 2, tq = lane & 3;
  const int arow = 64 * (b >> 4) + ((tid & 255) >> 3);
  uint4 wm0, wm1;
  uint32_t c0w, c1w;
  if (warp < 8) {
    const bf16* wa = w_mod + (size_t)arow * 3072 + (lane & 4) * 128 + 32 * (b & 15) + 8 * tq;
    wm0 = ldx16(wa); wm1 = ldx16(wa + 32 * 3072);
    c0w = ldc4(cvec + (arow & ~1)); c1w = ldc4(cvec + (arow & ~1) + 32);
  }
  const unsigned t_off = gt_start + RATE_T0;
  if (warp == 11) {
    if (lane == 0) {
#pragma unroll
      for (int i = 0; i < FB_KV; i++) { BAR_INIT(i, 1); BAR_ARM(i, 16384); }
    }
    __syncwarp();
    asm volatile("fence.mbarrier_init.release.cluster;" ::: "memory");
    asm volatile("barrier.cluster.arrive.relaxed.aligned;" ::: "memory");
#pragma unroll 1
    for (int i = 0; i < FB_KV; i++) {
      if (i >= HWIN) mbar_wait(bar0 + 8 * (i - HWIN));
      wait_until(t_off + (i < 4 ? 2 * i + ((b >> 1) & 1) : 4 * i - 8 + (b & 3)) * (RATE_H / 4));
      if (lane == 0) {
        if (i < 4) tma3d(sb + OFF_WQ + i * 16384, &tms.m[0], bar0 + 8 * i, 0, i * 128, 2 * hd + rk);
        else tma3d(sb + OFF_WQ + i * 16384, &tms.m[1], bar0 + 8 * i, 0, (b & 3) * 128 + (i - 4) * 64, 2 * hd);
      }
      __syncwarp();
    }
  }
  if (warp == 10) {
    const uint4 xa = ldc16(x + 16 * lane), xb = ldc16(x + 16 * lane + 8);
    const unsigned ep = ldc4(&g_epoch);
    float xv[16] = {bflo(xa.x), bfhi(xa.x), bflo(xa.y), bfhi(xa.y), bflo(xa.z), bfhi(xa.z), bflo(xa.w), bfhi(xa.w),
                    bflo(xb.x), bfhi(xb.x), bflo(xb.y), bfhi(xb.y), bflo(xb.z), bfhi(xb.z), bflo(xb.w), bfhi(xb.w)};
    float s = 0;
#pragma unroll
    for (int i = 0; i < 16; i++) s += xv[i];
#pragma unroll
    for (int o = 16; o; o >>= 1) s += __shfl_xor_sync(~0u, s, o);
    const float mean = s * (1.f / 512.f);
    s = 0;
#pragma unroll
    for (int i = 0; i < 16; i++) { xv[i] -= mean; s += xv[i] * xv[i]; }
#pragma unroll
    for (int o = 16; o; o >>= 1) s += __shfl_xor_sync(~0u, s, o);
    const float rstd = rsqrtf(s * (1.f / 512.f) + 1e-5f);
    if ((lane >> 1) == (b & 15))
#pragma unroll
      for (int i = 0; i < 4; i++)
        *(float4*)(smem + OFF_SM + (256 + (lane & 1) * 16 + 4 * i) * 4) = make_float4(xv[4 * i] * rstd, xv[4 * i + 1] * rstd, xv[4 * i + 2] * rstd, xv[4 * i + 3] * rstd);
    if (lane == 0) *(volatile unsigned*)(smem + OFF_MASK + 8) = ep;
    nbar_arrive(1, 288);
  }
  if (warp >= 8) {
    asm volatile("setmaxnreg.dec.sync.aligned.u32 72;");
    if (tid == 288) {
#pragma unroll
      for (int q = FB_KV; q < FB_KV + 16; q++) { BAR_INIT(q, 1); BAR_ARM(q, 32768); }
    }
    if (tid == 320) {
#pragma unroll
      for (int q = 0; q <= 13 + NSLOT; q++) BAR_INIT(EB + q, q == 0 ? 4 : q < 5 ? 16 : q < 16 ? 12 : 6);
    }
    if (tid == 256) {
#pragma unroll
      for (int q = FB_MOD; q <= FB_D; q++) { BAR_INIT(q, 1); BAR_ARM(q, 16384); }
      BAR_INIT(QB, 9); BAR_ARM(QB, 1024);
#pragma unroll
      for (int q = 0; q < 7; q++) BAR_INIT(XB + q, q == 2 ? 256 : q == 5 || q == 3 ? 9 : 1);
      BAR_ARM(XB + 3, 1024);
      BAR_ARM(XB + 5, 1024 + 64 + 512);
      *(volatile unsigned long long*)(smem + OFF_MASK) = 0;
    }
    if (warp != 11) {
      __syncwarp();
      asm volatile("fence.mbarrier_init.release.cluster;" ::: "memory");
      __threadfence_block();
      asm volatile("barrier.cluster.arrive.relaxed.aligned;" ::: "memory");
    }
    if (warp == 11) {
      asm volatile("barrier.cluster.wait.acquire.aligned;" ::: "memory");
      const unsigned epoch = *(volatile unsigned*)(smem + OFF_MASK + 8), par = (epoch + 1) & 1;
      mbar_wait(bar0 + 8 * (FB_KV + 15));
      for (int it = 0; ldx4(scr->cnt + 96 + 32 * (b >> 6)) != (epoch + 1) * 64 && it < SPIN_MAX; it++) {}
      uint4 hh;
      POLL { hh = ldx16(g_ml + (b >> 2) * 64 + 2 * lane); RETRY(X16(hh)) }
      int mi = __float_as_int(fmaxf(u2f(hh.x), u2f(hh.z)));
      mi ^= (mi >> 31) & 0x7fffffff;
      mi = __reduce_max_sync(~0u, mi);
      mi ^= (mi >> 31) & 0x7fffffff;
      const float M = __int_as_float(mi);
      const uint32_t wp = pack2(ex2(u2f(hh.x) - M), ex2(u2f(hh.z) - M));
      float L = bflo(wp) * u2f(hh.y) + bfhi(wp) * u2f(hh.w);
#pragma unroll
      for (int o2 = 16; o2; o2 >>= 1) L += __shfl_xor_sync(~0u, L, o2);
      *(uint32_t*)(smem + OFF_RA + lane * 4) = wp;
      if (lane == 0) *(float*)(smem + OFF_RA + 128) = rcp(L);
      __syncwarp();
      if (lane == 0) BAR_ARRIVE(XB + 6);
    }
    if (warp == 10) {
      if (lane < 8) asm volatile("prefetch.tensormap [%0];" ::"l"(&tms.m[lane + 1]) : "memory");
      asm volatile("barrier.cluster.wait.acquire.aligned;" ::: "memory");
      const unsigned epoch = *(volatile unsigned*)(smem + OFF_MASK + 8);
#pragma unroll 1
      for (int e = 0; e < 2; e++) {
        for (int it = 0; ldx4(scr->cnt + (e ? 2 + rk : 1)) != (epoch + 1) * (e ? 64 : 128) && it < SPIN_MAX; it++) {}
        if (lane == 0) BAR_ARRIVE(XB + e);
      }
      mbar_wait(bar0 + 8 * (FB_KV + 14));
      unsigned long long m = 0;
#pragma unroll 1
      for (int it = 0; ~m && it < SPIN_MAX; it++) {
        m = ldx64(scr->cnt + 32 + 32 * (b >> 6)) ^ ((epoch & 1) ? ~0ull : 0ull);
        if (lane == 0) *(volatile unsigned long long*)(smem + OFF_MASK) = m;
      }
    }
    if (warp == 9) {
      asm volatile("barrier.cluster.wait.acquire.aligned;" ::: "memory");
      const unsigned epoch = *(volatile unsigned*)(smem + OFF_MASK + 8);
      const unsigned par = (epoch + 1) & 1, inv = par ^ 1;
      const uint4 inv4 = make_uint4(inv, inv, inv, inv);
      mbar_wait(bar0 + 8 * FB_KV);
#pragma unroll 2
      for (int k = 0; k < 8; k++) {
        const uint32_t cp = ldc4(cvec + 2 * (lane + 32 * k));
        *(uint32_t*)(smem + OFF_SILU + (lane + 32 * k) * 4) = pack2(silu_bf(bflo(cp)), silu_bf(bfhi(cp)));
      }
      __syncwarp();
      mbar_wait(bar0 + 8 * FB_MOD);
      const uint32_t ab = sb + OFF_MOD + (8 * (lane >> 4) + (lane & 7)) * 32 + ((((lane >> 3) ^ (lane >> 2)) & 1) << 4);
      float d[4][4] = {};
#pragma unroll 2
      for (int s4 = 0; s4 < 8; s4++)
#pragma unroll
        for (int s = 0; s < 4; s++) {
          uint32_t a[4];
          const uint32_t* ps = (const uint32_t*)(smem + OFF_SILU) + 32 * s4 + 8 * s + tq;
          ldsm_t(a, ab + (4 * s4 + s) * 512); mma16(d[s], a, ps[0], ps[4]);
        }
      const float t = (tq & 1) ? (d[0][2] + d[1][2]) + (d[2][2] + d[3][2]) : (d[0][0] + d[1][0]) + (d[2][0] + d[3][0]);
      if (tq < 2) stx4(g_xm + b * 16 + 2 * (g & 6) + 2 * tq + (g & 1), fbits(bfr(t)));
      __syncwarp();
      if (lane == 0) CNT_ADD(6);
      mbar_wait(bar0 + 8 * (FB_KV + 8));
      if (lane < 16) stx16(g_xc + (b >> 2) * 256 + (lane >> 1) * 32 + (b & 3) * 8 + (lane & 1) * 4, inv4);
      if (lane < 8) stx16(g_xao + (b >> 5) * 1024 + (b & 15) * 64 + (lane & 4) * 8 + (b & 16) + (lane & 3) * 4, inv4);
      if (b < 112)
#pragma unroll 1
        for (int k = 0; k < 4; k++) stx16(g_xf + b * 512 + (lane + 32 * k) * 4, inv4);
      nbar_arrive(2, 288);
      for (int it = 0; ldx4(scr->cnt + 6) != (epoch + 1) * 128 && it < SPIN_MAX; it++) __nanosleep(100);
      {
        uint4 sv[2], cb[2];
        unsigned ga, gb;
        POLL {
#pragma unroll
          for (int k = 0; k < 2; k++) { sv[k] = ldx16(g_xm + 512 + 256 * rk + 4 * (lane + 32 * k)); cb[k] = ldx16(g_xm + 1024 + 256 * rk + 4 * (lane + 32 * k)); }
          ga = ldx4(g_xm + (b & 15) * 32 + lane); gb = ldx4(g_xm + 1536 + 256 * rk + 8 * (pr & 31) + (lane & 7));
          RETRY(X16(sv[0]) | X16(sv[1]) | X16(cb[0]) | X16(cb[1]) | lop_x3(ga, gb, par))
        }
#pragma unroll
        for (int k = 0; k < 2; k++) {
          const float c0 = bfr(1.f + bfhi(cb[k].x)), c1 = bfr(1.f + bfhi(cb[k].y)), c2 = bfr(1.f + bfhi(cb[k].z)), c3 = bfr(1.f + bfhi(cb[k].w));
          *(float4*)(smem + OFF_CO + (lane + 32 * k) * 16) = make_float4(c0, c1, c2, c3);
          uint2* pb = (uint2*)(smem + OFF_BP) + lane + 32 * k;
          pb[0] = make_uint2(pack2(c0, c1), pack2(c2, c3));
          pb[64] = make_uint2(__byte_perm(sv[k].x, sv[k].y, 0x7632), __byte_perm(sv[k].z, sv[k].w, 0x7632));
        }
        *(float*)(smem + OFF_CO + 1024 + lane * 4) = bfhi(ga);
        *(float*)(smem + OFF_CO + 1152 + lane * 4) = bfhi(gb);
      }
      __syncwarp();
      if (lane == 0) BAR_ARRIVE(XB + 4);
    }
    if (warp == 8) {
      const unsigned stag = ((pr * SMUL) & 63) * RATE_NS >> 6;
      unsigned tnext = t_off + 4 * RATE_H;
      asm volatile("barrier.cluster.wait.acquire.aligned;" ::: "memory");
#pragma unroll 1
      for (int k = 0; k < 24; k++) {
        const int code = (k < 12 ? ORDER0 >> (5 * k) : ORDER1 >> (5 * (k - 12))) & 31;
        const bool kv = code < 16;
        const int n = code, w = code - 16;
        if (!kv && w >= 5 && b >= 112) break;
        if (kv) mbar_wait(bar0 + 8 * (FB_KV + n - (n < 6 ? EWIN : KVWIN)));
        if (k >= TAIL_K) mbar_wait(bar0 + 8 * (FB_KV + (int)((ORDER1 >> (5 * (k - 12 - ((WINS >> (4 * (k - TAIL_K))) & 15)))) & 31)));
        const int e = kv ? (n == 3 ? 2 : n == 5 ? 1 : n) : w == 0 ? 0 : w < 5 ? 16 + ((w - 1) >> 1) : w == 7 ? 19 : 18;
        if (e != 1 && k) mbar_wait(bar0 + 8 * (EB + e));
        wait_until(tnext + stag);
        tnext += k > TAIL_K ? RATE_TL : k < 4 ? RATE_E : RATE_NS;
        if (lane == 0) {
          if (kv)
            asm volatile("cp.async.bulk.tensor.3d.shared::cluster.global.mbarrier::complete_tx::bytes.multicast::cluster.L2::cache_hint [%0], [%1, {%3, %4, %5}], [%2], %6, %7;"
                         ::"r"(sb + (n % NSLOT) * SLOT + rk * 16384), "l"(&tms.m[2]), "r"(bar0 + 8 * (FB_KV + n)), "r"(0), "r"(((n >> 1) * 64 + pr) * 64),
                           "r"(4 * (n & 1) + 2 * rk), "h"((unsigned short)3), "l"(stream_policy()) : "memory");
          else {
            tma3d(sb + (w == 0 ? OFF_MOD : w < 5 ? OFF_UV + (w - 1) * 16384 : w == 5 ? OFF_G : w == 6 ? OFF_U : OFF_D),
                  &tms.m[w == 0 ? 3 : w < 3 ? 4 : w < 5 ? 5 : w + 1], bar0 + 8 * (FB_MOD + w),
                  w == 0 ? 1024 + b * 16 : w < 3 || w == 7 ? 0 : w < 5 ? (pr & 7) * 64 : pr * 32, w == 7 ? b * 16 : w == 1 || w == 2 ? (b & 3) * 128 + (w - 1) * 64 : 0,
                  w == 1 || w == 2 ? 2 * hd : w == 3 || w == 4 ? (b >> 4) * 4 + 2 * rk + w - 3 : w == 5 || w == 6 ? rk : 0);
          }
        }
        __syncwarp();
      }
    }
    if (b < 112) {
      const int mt = warp & 1, dd = (warp >> 1) & 1;
      mbar_wait(bar0 + 8 * (XB + 4));
      const uint32_t ab = sb + (mt ? OFF_U : OFF_G) + (8 * (lane >> 4) + (lane & 7)) * 64 + (((2 * dd + ((lane >> 3) & 1)) ^ ((lane >> 1) & 3)) << 4);
      uint32_t base;
      asm volatile("mapa.shared::cluster.u32 %0, %1, %2;" : "=r"(base) : "r"(sb), "r"(dd));
      uint2 bb[16];
#pragma unroll
      for (int s = 0; s < 16; s++) bb[s] = *(const uint2*)(smem + OFF_BP + (g & 1) * 512 + (4 * s + tq) * 8);
      mbar_wait(bar0 + 8 * (FB_G + mt));
      float e[4][4] = {};
#pragma unroll
      for (int s = 0; s < 16; s++) { uint32_t a[4]; ldsm_t(a, ab + s * 1024); mma16(e[s & 3], a, bb[s].x, bb[s].y); }
      float r[4];
#pragma unroll
      for (int i = 0; i < 4; i++) r[i] = (e[0][i] + e[1][i]) + (e[2][i] + e[3][i]);
      if (tq < 2) st_async2(base + OFF_R4 + (8 * mt + g) * 176 + (10 * rk + 8 + tq) * 8, base + OFF_BAR + 8 * (XB + 5), tq ? r[1] : r[0], tq ? r[3] : r[2]);
    }
    return;
  }

  float* s_sm = (float*)(smem + OFF_SM);
  unsigned par, epoch;
  uint32_t rsb;
  {
    float* s_r4 = (float*)(smem + OFF_R4);
    asm volatile("barrier.cluster.arrive.relaxed.aligned;" ::: "memory");
    asm volatile("mapa.shared::cluster.u32 %0, %1, %2;" : "=r"(rsb) : "r"(sb), "r"(rk ^ 1));
    const float c0 = (arow & 1) ? bfhi(c0w) : bflo(c0w), c1 = (arow & 1) ? bfhi(c1w) : bflo(c1w);
    float acc[8] = {0, 0, 0, 0, 0, 0, 0, 0};
    fma8(acc, wm0, silu_bf(c0)); fma8(acc, wm1, silu_bf(c1));
    tred<4>(acc, lane, 8); tred<2>(acc, lane, 16);
    *(float2*)(s_r4 + warp * 64 + 8 * (lane & 7) + ((lane >> 1) & 4) + ((lane >> 3) & 2)) = make_float2(acc[0], acc[1]);
    nbar(1, 288);
    epoch = *(volatile unsigned*)(smem + OFF_MASK + 8);
    par = (epoch + 1) & 1;
    if (warp == 0) {
      float t = 0.f, ca = b < 16 ? 1.f : 0.f;
#pragma unroll
      for (int w = 0; w < 8; w++) { t += s_r4[w * 64 + lane]; ca += s_r4[w * 64 + 32 + lane]; }
      t += ca * s_sm[256 + lane];
      const float nb = __shfl_down_sync(~0u, t, 1);
      const uint32_t w0 = lane < 8 ? pack2t(t, nb, par) : pack2(t, nb);
      const uint32_t w1 = __shfl_down_sync(~0u, w0, 8), w2 = __shfl_down_sync(~0u, w0, 16), w3 = __shfl_down_sync(~0u, w0, 24);
      if (lane < 8 && !(lane & 1)) stx16(g_h + (b >> 5) * 512 + (b & 15) * 32 + (b & 16) + 2 * lane, make_uint4(w0, w1, w2, w3));
      __syncwarp();
      if (lane == 0) CNT_ADD(1);
    }
  }
  asm volatile("barrier.cluster.wait.acquire.aligned;" ::: "memory");
  {
    uint32_t a[4][4][4];
    mbar_wait(bar0 + 8 * (warp >> 1));
    const uint32_t ab = sb + OFF_WQ + (64 * warp + 8 * (lane >> 4) + (lane & 7)) * 128;
#pragma unroll
    for (int s = 0; s < 4; s++)
#pragma unroll
      for (int mt = 0; mt < 4; mt++) ldsm_t(a[s][mt], ab + s * 2048 + (((2 * mt + ((lane >> 3) & 1)) ^ (lane & 7)) << 4));
    uint4 v0, v1;
    const unsigned* ph = g_h + (g >> 1) * 512 + 64 * warp + 4 * (lane & 7);
    uint32_t off = OFF_B + warp * 272 + (32 * rk + 8 * tq + (lane & 4)) * 4;
    PIN(off); PINL(ph);
    mbar_wait(bar0 + 8 * XB);
    POLL { v0 = ldx16(ph); v1 = ldx16(ph + 32); RETRY(lop_x3(v0.x, v1.x, par)) }
    float d[4][4] = {};
#pragma unroll
    for (int mt = 0; mt < 4; mt++) {
      mma16(d[mt], a[0][mt], v0.x, v0.y); mma16(d[mt], a[1][mt], v0.z, v0.w);
      mma16(d[mt], a[2][mt], v1.x, v1.y); mma16(d[mt], a[3][mt], v1.z, v1.w);
    }
    float r[8];
#pragma unroll
    for (int mt = 0; mt < 4; mt++) { r[2 * mt] = d[mt][0] + d[mt][1]; r[2 * mt + 1] = d[mt][2] + d[mt][3]; }
    tred<4>(r, lane, 2); tred<2>(r, lane, 1);
    const float rc = __shfl_xor_sync(~0u, (lane & 4) ? r[0] : r[1], 4);
    const uint32_t wd = (lane & 4) ? pack2(rc, r[1]) : pack2(r[0], rc);
    const uint32_t w1 = __shfl_down_sync(~0u, wd, 8), w2 = __shfl_down_sync(~0u, wd, 16), w3 = __shfl_down_sync(~0u, wd, 24);
    asm volatile("{.reg .pred p; setp.lt.s32 p, %7, 8; @p st.shared.v4.b32 [%0], {%2,%3,%4,%5};\n"
                 "@p st.async.shared::cluster.mbarrier::complete_tx::bytes.v4.b32 [%1], {%2,%3,%4,%5}, [%6];}"
                 ::"r"(sb + off), "r"(rsb + off), "r"(wd), "r"(w1), "r"(w2), "r"(w3), "r"(rsb + OFF_BAR + 8 * QB), "r"(lane) : "memory");
    __syncwarp();
    arrive2(bar0 + 8 * QB, 0, lane == 0, false);
    arrive2(bar0 + 8 * (EB + 2), rsb + OFF_BAR + 8 * (EB + 2), lane == 0, lane == 0);
  }
  {
    uint32_t a[8][4];
    uint32_t a_bq = sb + OFF_B + (lane & 7) * 272 + (lane >> 3) * 16;
    unsigned* p_qa = g_qa + b * 64 + 8 * warp + 4 * lane;
    PIN(a_bq); PINL(p_qa);
    mbar_wait(bar0 + 8 * (FB_UK + (warp >> 2)));
    const uint32_t ab = sb + OFF_WUK + (warp >> 2) * 16384 + (16 * (warp & 3) + (lane & 15)) * 128;
#pragma unroll
    for (int s = 0; s < 8; s++) ldsm(a[s], ab + (s >> 2) * 8192 + (((2 * (s & 3) + (lane >> 4)) ^ (lane & 7)) << 4));
    mbar_wait(bar0 + 8 * QB);
    float d[4][4] = {};
#pragma unroll
    for (int y = 0; y < 4; y++) {
      uint32_t bq[4];
      ldsm(bq, a_bq + 64 * y);
      mma16(d[(2 * y) & 3], a[2 * y], bq[0], bq[1]); mma16(d[(2 * y + 1) & 3], a[2 * y + 1], bq[2], bq[3]);
    }
    float r[2] = {((d[0][0] + d[0][1]) + (d[1][0] + d[1][1])) + ((d[2][0] + d[2][1]) + (d[3][0] + d[3][1])),
                  ((d[0][2] + d[0][3]) + (d[1][2] + d[1][3])) + ((d[2][2] + d[2][3]) + (d[3][2] + d[3][3]))};
    tred<1>(r, lane, 1);
    r[0] += __shfl_xor_sync(~0u, r[0], 2);
    const float nb = __shfl_xor_sync(~0u, r[0], 4);
    const uint32_t w0 = lane < 8 ? pack2t(r[0], nb, par) : pack2(r[0], nb);
    const uint32_t w1 = __shfl_down_sync(~0u, w0, 8), w2 = __shfl_down_sync(~0u, w0, 16), w3 = __shfl_down_sync(~0u, w0, 24);
    if (lane < 2) stx16(p_qa, make_uint4(w0, w1, w2, w3));
    arrive2(bar0 + 8 * (EB + 4), rsb + OFF_BAR + 8 * (EB + 4), lane == 0, lane == 0);
  }
  {
    if (warp) nbar_arrive(3, 256); else { nbar(3, 256); if (lane == 0) CNT_ADD(2 + (b >> 6)); }
    asm volatile("setmaxnreg.inc.sync.aligned.u32 216;");
    const unsigned* pq = g_qa + rk * 4096 + tid * 4;
    uint32_t a_q = sb + OFF_Q + ((tid & 63) >> 3) * 2048 + (tid >> 6) * 128 + (((tid & 7) ^ (tid >> 6)) << 4);
    PINL(pq); PIN(a_q);
    mbar_wait(bar0 + 8 * (XB + 1));
    uint4 v[4];
    POLL {
#pragma unroll
      for (int k = 0; k < 4; k++) v[k] = ldx16(pq + 1024 * k);
      RETRY(lop_x3(v[0].x, v[1].x, par) | lop_x3(v[2].x, v[3].x, par))
    }
#pragma unroll
    for (int k = 0; k < 4; k++)
      asm volatile("st.shared.v4.b32 [%0], {%1,%2,%3,%4};" ::"r"((a_q + k * 512) ^ ((k & 1) << 6)), "r"(v[k].x), "r"(v[k].y), "r"(v[k].z), "r"(v[k].w) : "memory");
    if (warp >= 4) nbar_arrive(1, 256); else nbar(1, 256);
  }
  sb = __shfl_sync(~0u, sb, 0); bar0 = sb + OFF_BAR;
  if (warp < 4) {
    uint32_t qf[32][4];
#pragma unroll
    for (int s = 0; s < 32; s++) ldsm(qf[s], sb + OFF_Q + (s >> 2) * 2048 + (lane & 15) * 128 + (((2 * (s & 3) + (lane >> 4)) ^ (lane & 7)) << 4));
    float l0 = 0.f, l1 = 0.f, m0 = -1e30f, m1 = -1e30f;
    const float sc = 0.08838834764831845f * 1.4426950408889634f;
    const uint32_t kofs = (16 * warp + 8 * (lane >> 4) + (lane & 7)) * 128 + ((((lane >> 3) & 1) ^ (lane & 7)) << 4);
    uint32_t st = sb;
#pragma unroll 1
    for (int t = 0; t < 8; t++) {
      float sa[4][4] = {};
#pragma unroll
      for (int hf = 0; hf < 2; hf++) {
        const int n = 2 * t + hf;
        mbar_wait(bar0 + 8 * (FB_KV + n));
        uint32_t kf[16][4];
#pragma unroll
        for (int y = 0; y < 16; y++) ldsm(kf[y], st + (y >> 2) * 8192 + (kofs ^ ((y & 3) << 5)));
#pragma unroll
        for (int y = 0; y < 16; y++) {
          mma16(sa[(2 * y) & 3], qf[16 * hf + y], kf[y][0], kf[y][1]); mma16(sa[((2 * y) & 3) + 1], qf[16 * hf + y], kf[y][2], kf[y][3]);
        }
        __syncwarp();
        arrive2(bar0 + 8 * (EB + NSLOT + n), rsb + OFF_BAR + 8 * (EB + NSLOT + n), lane == 0 && n < 14, lane == 0 && n < 16 - NSLOT);
        if (hf == 0) arrive2(bar0 + 8 * EB, 0, lane == 0 && t == 0, false);
        st = st + SLOT == sb + NSLOT * SLOT ? sb : st + SLOT;
      }
#pragma unroll
      for (int i = 0; i < 4; i++) { sa[0][i] = (sa[0][i] + sa[2][i]) * sc; sa[1][i] = (sa[1][i] + sa[3][i]) * sc; }
      float cm[2] = {fmaxf(fmaxf(sa[0][0], sa[0][1]), fmaxf(sa[1][0], sa[1][1])), fmaxf(fmaxf(sa[0][2], sa[0][3]), fmaxf(sa[1][2], sa[1][3]))};
      tmax<1>(cm, lane, 1);
      cm[0] = fmaxf(cm[0], __shfl_xor_sync(~0u, cm[0], 2));
      float* pm = s_sm + (t & 1) * 64;
      if (tq < 2) pm[(g + 8 * tq) * 4 + warp] = cm[0];
      if (t >= 2) nbar(6 + (t & 1), 256); else nbar(3, 128);
      const float4 a0 = *(const float4*)(pm + g * 4), b0 = *(const float4*)(pm + g * 4 + 32);
      const float n0 = fmaxf(fmaxf(fmaxf(a0.x, a0.y), fmaxf(a0.z, a0.w)), m0), n1 = fmaxf(fmaxf(fmaxf(b0.x, b0.y), fmaxf(b0.z, b0.w)), m1);
      uint32_t pk[4];
#pragma unroll
      for (int i = 0; i < 2; i++) { pk[2 * i] = pack2(ex2(sa[i][0] - n0), ex2(sa[i][1] - n0)); pk[2 * i + 1] = pack2(ex2(sa[i][2] - n1), ex2(sa[i][3] - n1)); }
      *(uint4*)(smem + OFF_P + (t & 1) * 2048 + tid * 16) = make_uint4(pk[0], pk[1], pk[2], pk[3]);
      const float al0 = ex2(m0 - n0), al1 = ex2(m1 - n1);
      if (tid < 32 && tq == 0) *(float2*)(s_sm + 192 + (t & 1) * 16 + 2 * g) = make_float2(al0, al1);
      nbar_arrive(4 + (t & 1), 256);
      m0 = n0; m1 = n1;
      l0 = l0 * al0 + (bflo(pk[0]) + bfhi(pk[0])) + (bflo(pk[2]) + bfhi(pk[2]));
      l1 = l1 * al1 + (bflo(pk[1]) + bfhi(pk[1])) + (bflo(pk[3]) + bfhi(pk[3]));
    }
    float lr[2] = {l0, l1};
    tred<1>(lr, lane, 1);
    lr[0] += __shfl_xor_sync(~0u, lr[0], 2);
    if (tq < 2) s_sm[128 + (g + 8 * tq) * 4 + warp] = lr[0];
    nbar(3, 128);
    if (warp == 0 && tq < 2) {
      const float4 a0 = *(const float4*)(s_sm + 128 + (g + 8 * tq) * 4);
      stx8(g_ml + (16 * rk + g + 8 * tq) * 64 + pr, make_uint2(fbits(tq ? m1 : m0), fbits((a0.x + a0.y) + (a0.z + a0.w))));
    }
    if (warp == 0) { __syncwarp(); if (lane == 0) CNT_ADD(96 + 32 * rk); }
    nbar(2, 288);
    if (tid == 0) asm volatile("red.relaxed.gpu.global.xor.b64 [%0], %1;" ::"l"(scr->cnt + 32 + 32 * rk), "l"(1ull << pr) : "memory");
  } else {
    float o[16][4] = {};
    const uint32_t vofs = (warp & 1) * 16384 + (lane & 15) * 128 + (((lane >> 4) ^ (lane & 7)) << 4);
    const int hf = (warp >> 1) & 1;
    uint32_t st = sb + hf * SLOT;
    auto pv = [&](const int t, auto np) {
      constexpr int npre = decltype(np)::value;
      uint32_t vf[4][8][4];
      const int n = 2 * t + hf;
      mbar_wait(bar0 + 8 * (FB_KV + n));
#pragma unroll
      for (int s = 0; s < npre; s++)
#pragma unroll
        for (int y = 0; y < 8; y++) ldsm_t(vf[s][y], st + (y >> 2) * 8192 + s * 2048 + (vofs ^ ((y & 3) << 5)));
      nbar(4 + (t & 1), 256);
      const float2 al = *(const float2*)(s_sm + 192 + (t & 1) * 16 + 2 * g);
      uint4 pf[4];
#pragma unroll
      for (int s = 0; s < 4; s++) pf[s] = *(const uint4*)(smem + OFF_P + (t & 1) * 2048 + s * 512 + lane * 16);
      if (t < 6) nbar_arrive(6 + (t & 1), 256);
#pragma unroll
      for (int s = npre; s < 4; s++)
#pragma unroll
        for (int y = 0; y < 8; y++) ldsm_t(vf[s][y], st + (y >> 2) * 8192 + s * 2048 + (vofs ^ ((y & 3) << 5)));
#pragma unroll
      for (int nt = 0; nt < 16; nt++) { o[nt][0] *= al.x; o[nt][1] *= al.x; o[nt][2] *= al.y; o[nt][3] *= al.y; }
#pragma unroll
      for (int s = 0; s < 4; s++) {
        const uint32_t pa[4] = {pf[s].x, pf[s].y, pf[s].z, pf[s].w};
#pragma unroll
        for (int y = 0; y < 8; y++) { mma16(o[2 * y], pa, vf[s][y][0], vf[s][y][1]); mma16(o[2 * y + 1], pa, vf[s][y][2], vf[s][y][3]); }
      }
      __syncwarp();
      arrive2(bar0 + 8 * (EB + NSLOT + n), rsb + OFF_BAR + 8 * (EB + NSLOT + n), lane == 0 && n < 14, lane == 0 && n < 16 - NSLOT);
      st = st + 2 * SLOT >= sb + NSLOT * SLOT ? st - (NSLOT - 2) * SLOT : st + 2 * SLOT;
    };
#pragma unroll 1
    for (int t = 0; t < 7; t++) pv(t, IC<NPRE0>());
    pv(7, IC<NPRE1>());
    uint4* po = g_xo + ((size_t)((16 * rk + (g & 6)) * 4 + warp - 4) * 64 + pr) * RS + (lane & 7);
    const bool odd = lane & 4;
#pragma unroll
    for (int e = 0; e < 2; e++)
#pragma unroll
      for (int j2 = 0; j2 < 2; j2++) {
        uint32_t c0[4], c1[4];
#pragma unroll
        for (int i = 0; i < 4; i++) {
          c0[i] = i ? pack2(o[8 * j2 + i][2 * e], o[8 * j2 + i][2 * e + 1]) : pack2t(o[8 * j2][2 * e], o[8 * j2][2 * e + 1], par);
          c1[i] = i ? pack2(o[8 * j2 + 4 + i][2 * e], o[8 * j2 + 4 + i][2 * e + 1]) : pack2t(o[8 * j2 + 4][2 * e], o[8 * j2 + 4][2 * e + 1], par);
          const uint32_t r = __shfl_xor_sync(~0u, odd ? c0[i] : c1[i], 4);
          if (odd) c0[i] = r; else c1[i] = r;
        }
        stx16(po + e * 8 * 4 * 64 * RS + 8 * j2, make_uint4(c0[0], c0[1], c0[2], c0[3]));
        stx16(po + (e * 8 + 1) * 4 * 64 * RS + 8 * j2, make_uint4(c1[0], c1[1], c1[2], c1[3]));
      }
    nbar_arrive(2, 288);
  }
  tail(smem, scr, x, out, par, epoch, warp);
}

static void launch(void* const* d_in, void* d_out) {
  static TMaps tms;
  static bool init = false;
  static void* scr = nullptr;
  if (!init) {
    void* fn = nullptr; cudaDriverEntryPointQueryResult qr;
    cudaGetDriverEntryPoint("cuTensorMapEncodeTiled", &fn, cudaEnableDefault, &qr);
    EncFn f = (EncFn)fn;
    const CUtensorMapSwizzle S32 = CU_TENSOR_MAP_SWIZZLE_32B, S64 = CU_TENSOR_MAP_SWIZZLE_64B, S128 = CU_TENSOR_MAP_SWIZZLE_128B;
    const CUtensorMapL2promotion P128 = CU_TENSOR_MAP_L2_PROMOTION_L2_128B, P256 = CU_TENSOR_MAP_L2_PROMOTION_L2_256B;
    enc3d(f, &tms.m[0], d_in[2], 64, 512, 64, 8192, 128, 64, 128, 1, S128, P128);
    enc3d(f, &tms.m[1], d_in[3], 64, 512, 64, 8192, 128, 64, 64, 2, S128, P256);
    enc3d(f, &tms.m[2], d_in[1], 64, SK, 8, 1024, 128, 64, 64, 2, S128, P256);
    enc3d(f, &tms.m[3], d_in[11], 3072, 256, 2, 6144, 256 * 6144, 16, 256, 2, S32, P128);
    enc3d(f, &tms.m[4], d_in[4], 64, 512, 64, 8192, 128, 64, 64, 2, S128, P256);
    enc3d(f, &tms.m[5], d_in[5], 512, 128, 32, 1024, 128 * 1024, 64, 128, 1, S128, P128);
    enc3d(f, &tms.m[6], d_in[7], 1792, 256, 2, 3584, 256 * 3584, 32, 256, 1, S64, P128);
    enc3d(f, &tms.m[7], d_in[8], 1792, 256, 2, 3584, 256 * 3584, 32, 256, 1, S64, P128);
    enc3d(f, &tms.m[8], d_in[9], 64, 1792, 8, 1024, 128, 64, 16, 8, S128, P256);
    cudaFuncSetAttribute(fused_kernel, cudaFuncAttributeMaxDynamicSharedMemorySize, SMEM_BYTES);
    cudaGetSymbolAddress(&scr, g_scr);
    init = true;
  }
  fused_kernel<<<NCTA, 384, SMEM_BYTES>>>((const bf16*)d_in[0], (const bf16*)d_in[10], (const bf16*)d_in[11], (bf16*)d_out, (Scratch*)scr, tms);
}

}

extern "C" void kernel_launch(void* const* d_in, const int* in_sizes, int n_in, void* d_out, int out_size) {
  static int big = -1;
  if (big < 0) big = v9::fits();
  if (big) v9::launch(d_in, d_out); else v8::launch(d_in, d_out);
}
```

```cpp
#include <cuda_runtime.h>
#include <cuda_bf16.h>
#include <cuda.h>
#include <stdint.h>
#include <stdio.h>
#include <stdlib.h>

typedef CUresult (*EncFn)(CUtensorMap*, CUtensorMapDataType, cuuint32_t, void*, const cuuint64_t*, const cuuint64_t*,
                          const cuuint32_t*, const cuuint32_t*, CUtensorMapInterleave, CUtensorMapSwizzle,
                          CUtensorMapL2promotion, CUtensorMapFloatOOBfill);

static void enc3d(EncFn fn, CUtensorMap* tm, void* p, uint64_t d0, uint64_t d1, uint64_t d2, uint64_t s1, uint64_t s2, uint32_t b0,
                  uint32_t b1, uint32_t b2, CUtensorMapSwizzle sw, CUtensorMapL2promotion pr) {
  cuuint64_t gd[3] = {d0, d1, d2}, gs[2] = {s1, s2};
  cuuint32_t bx[3] = {b0, b1, b2}, es[3] = {1, 1, 1};
  fn(tm, CU_TENSOR_MAP_DATA_TYPE_BFLOAT16, 3, p, gd, gs, bx, es, CU_TENSOR_MAP_INTERLEAVE_NONE, sw, pr, CU_TENSOR_MAP_FLOAT_OOB_FILL_NONE);
}

namespace v9 {
typedef __nv_bfloat16 bf16;
#define SK 32768
#define SPIN_MAX (1 << 20)
template <int N> struct IC { static constexpr int value = N; };

__device__ __forceinline__ uint32_t s2u(const void* p) { return (uint32_t)__cvta_generic_to_shared(p); }
__device__ __forceinline__ float bflo(uint32_t u) { return __uint_as_float(u << 16); }
__device__ __forceinline__ float bfhi(uint32_t u) { return __uint_as_float(u & 0xffff0000u); }
__device__ __forceinline__ float u2f(uint32_t u) { return __uint_as_float(u); }
__device__ __forceinline__ void fma8(float* acc, uint4 v, float s) {
  acc[0] += s * bflo(v.x); acc[1] += s * bfhi(v.x); acc[2] += s * bflo(v.y); acc[3] += s * bfhi(v.y);
  acc[4] += s * bflo(v.z); acc[5] += s * bfhi(v.z); acc[6] += s * bflo(v.w); acc[7] += s * bfhi(v.w);
}
__device__ __forceinline__ uint32_t pack2(float a, float b) {
  __nv_bfloat162 p = __floats2bfloat162_rn(a, b); return *(uint32_t*)&p;
}
__device__ __forceinline__ float bfr(float v) { return bfhi(pack2(v, v)); }
__device__ __forceinline__ float silu_bf(float c) { return bfr(__fdividef(c, 1.f + __expf(-c))); }
#define fbits(v) ((__float_as_uint(v) & ~1u) | par)
__device__ __forceinline__ uint32_t pack2t(float a, float b, unsigned par) {
  const uint32_t ua = ((__float_as_uint(a) + ((par ^ 1) << 16)) & 0xFFFE0000u) | (par << 16);
  return __byte_perm(ua, pack2(b, b), 0x7632);
}
__device__ __forceinline__ void nbar(int id, int n) { asm volatile("bar.sync %0, %1;" ::"r"(id), "r"(n) : "memory"); }
__device__ __forceinline__ void nbar_arrive(int id, int n) { asm volatile("bar.arrive %0, %1;" ::"r"(id), "r"(n) : "memory"); }
__device__ __forceinline__ uint4 ldc16(const void* p) {
  uint4 v; asm volatile("ld.relaxed.cta.global.v4.u32 {%0,%1,%2,%3}, [%4];" : "=r"(v.x), "=r"(v.y), "=r"(v.z), "=r"(v.w) : "l"(p) : "memory"); return v;
}
__device__ __forceinline__ unsigned ldc4(const void* p) {
  unsigned v; asm volatile("ld.relaxed.cta.global.u32 %0, [%1];" : "=r"(v) : "l"(p) : "memory"); return v;
}
__device__ __forceinline__ uint4 ldx16(const void* p) {
  uint4 v; asm volatile("ld.relaxed.gpu.global.v4.u32 {%0,%1,%2,%3}, [%4];" : "=r"(v.x), "=r"(v.y), "=r"(v.z), "=r"(v.w) : "l"(p) : "memory"); return v;
}
__device__ __forceinline__ unsigned ldx4(const void* p) {
  unsigned v; asm volatile("ld.relaxed.gpu.global.u32 %0, [%1];" : "=r"(v) : "l"(p) : "memory"); return v;
}
__device__ __forceinline__ unsigned long long ldx64(const void* p) {
  unsigned long long v; asm volatile("ld.relaxed.gpu.global.u64 %0, [%1];" : "=l"(v) : "l"(p) : "memory"); return v;
}
__device__ __forceinline__ void stx16(void* p, uint4 v) {
  asm volatile("st.relaxed.gpu.global.v4.u32 [%0], {%1,%2,%3,%4};" ::"l"(p), "r"(v.x), "r"(v.y), "r"(v.z), "r"(v.w) : "memory");
}
__device__ __forceinline__ void stx8(void* p, uint2 v) { asm volatile("st.relaxed.gpu.global.v2.u32 [%0], {%1,%2};" ::"l"(p), "r"(v.x), "r"(v.y) : "memory"); }
__device__ __forceinline__ void stx4(void* p, unsigned v) { asm volatile("st.relaxed.gpu.global.u32 [%0], %1;" ::"l"(p), "r"(v) : "memory"); }
__device__ __forceinline__ void pub4(void* p, unsigned v) { asm volatile("red.relaxed.gpu.global.xor.b32 [%0], %1;" ::"l"(p), "r"(v) : "memory"); }
__device__ __forceinline__ void pub8(void* p, unsigned lo, unsigned hi) {
  asm volatile("{.reg .b64 t; mov.b64 t, {%1, %2}; red.relaxed.gpu.global.xor.b64 [%0], t;}" ::"l"(p), "r"(lo), "r"(hi) : "memory");
}
__device__ __forceinline__ unsigned lop_x3(unsigned a, unsigned b, unsigned c) {
  unsigned d; asm("lop3.b32 %0, %1, %2, %3, 0x7E;" : "=r"(d) : "r"(a), "r"(b), "r"(c)); return d; }
__device__ __forceinline__ unsigned or3(unsigned a, unsigned b, unsigned c) {
  unsigned d; asm("lop3.b32 %0, %1, %2, %3, 0xFE;" : "=r"(d) : "r"(a), "r"(b), "r"(c)); return d; }
__device__ __forceinline__ unsigned and3(unsigned a, unsigned b, unsigned c) {
  unsigned d; asm("lop3.b32 %0, %1, %2, %3, 0x80;" : "=r"(d) : "r"(a), "r"(b), "r"(c)); return d; }
__device__ __forceinline__ unsigned dep16(const uint32_t* f) {
  unsigned d = 0;
#pragma unroll
  for (int i = 0; i < 8; i++) d = or3(d, f[8 * i], f[8 * i + 4]);
  return d;
}
__device__ __forceinline__ uint2 ldx8(const void* p) {
  uint2 v; asm volatile("{.reg .b64 t; ld.relaxed.gpu.global.b64 t, [%2]; mov.b64 {%0, %1}, t;}" : "=r"(v.x), "=r"(v.y) : "l"(p) : "memory"); return v;
}
__device__ __forceinline__ float lds4(uint32_t a) { float v; asm volatile("ld.shared.f32 %0, [%1];" : "=f"(v) : "r"(a) : "memory"); return v; }
__device__ __forceinline__ float shx(float v, int m) {
  float r; asm volatile("shfl.sync.bfly.b32 %0, %1, %2, 0x1f, 0xffffffff;" : "=f"(r) : "f"(v), "r"(m)); return r;
}
__device__ __forceinline__ uint32_t mbar_test(uint32_t bar, uint32_t ph) {
  uint32_t ok;
  asm volatile("{.reg .pred p; mbarrier.test_wait.parity.shared::cta.b64 p, [%1], %2; vote.sync.all.pred p, p, 0xffffffff; selp.u32 %0, 1, 0, p;}"
               : "=r"(ok) : "r"(bar), "r"(ph) : "memory");
  return ok;
}
#define X16(v) (lop_x3(v.x, v.y, par) | lop_x3(v.z, v.w, par))
#define RETRY(bad) if (!__any_sync(~0u, (bad) & 1) || ++it_ >= SPIN_MAX) break;
#define POLL _Pragma("unroll 1") for (int it_ = 0;;)
__device__ __forceinline__ void mbar_wait(uint32_t bar, uint32_t ph = 0) {
  asm volatile("{.reg .pred p; .reg .u32 n; mov.u32 n, 0;\n"
               "W%=: mbarrier.try_wait.parity.shared::cta.b64 p, [%0], %1; add.u32 n, n, 1; setp.lt.and.u32 p, n, 0x100000, !p; @p bra W%=;}"
               ::"r"(bar), "r"(ph) : "memory");
}
__device__ __forceinline__ float ex2(float v) { float r; asm("ex2.approx.ftz.f32 %0, %1;" : "=f"(r) : "f"(v)); return r; }
__device__ __forceinline__ float rcp(float v) { float r; asm("rcp.approx.ftz.f32 %0, %1;" : "=f"(r) : "f"(v)); return r; }
__device__ __forceinline__ void mma16(float* d, const uint32_t* a, uint32_t b0, uint32_t b1) {
  asm volatile("mma.sync.aligned.m16n8k16.row.col.f32.bf16.bf16.f32 {%0,%1,%2,%3}, {%4,%5,%6,%7}, {%8,%9}, {%0,%1,%2,%3};"
               : "+f"(d[0]), "+f"(d[1]), "+f"(d[2]), "+f"(d[3]) : "r"(a[0]), "r"(a[1]), "r"(a[2]), "r"(a[3]), "r"(b0), "r"(b1));
}
__device__ __forceinline__ void mma16c(float* d, const uint32_t* a, uint32_t b0, uint32_t b1, const float* c) {
  asm volatile("mma.sync.aligned.m16n8k16.row.col.f32.bf16.bf16.f32 {%0,%1,%2,%3}, {%4,%5,%6,%7}, {%8,%9}, {%10,%11,%12,%13};"
               : "=f"(d[0]), "=f"(d[1]), "=f"(d[2]), "=f"(d[3])
               : "r"(a[0]), "r"(a[1]), "r"(a[2]), "r"(a[3]), "r"(b0), "r"(b1), "f"(c[0]), "f"(c[1]), "f"(c[2]), "f"(c[3]));
}
__device__ __forceinline__ float4 lds16(uint32_t a) {
  float4 v; asm volatile("ld.shared.v4.f32 {%0,%1,%2,%3}, [%4];" : "=f"(v.x), "=f"(v.y), "=f"(v.z), "=f"(v.w) : "r"(a) : "memory"); return v;
}
__device__ __forceinline__ void sts4(uint32_t a, float v) { asm volatile("st.shared.f32 [%0], %1;" ::"r"(a), "f"(v) : "memory"); }
__device__ __forceinline__ void sts16(uint32_t a, uint4 v) {
  asm volatile("st.shared.v4.b32 [%0], {%1,%2,%3,%4};" ::"r"(a), "r"(v.x), "r"(v.y), "r"(v.z), "r"(v.w) : "memory");
}
__device__ __forceinline__ void ldsm_t(uint32_t* r, uint32_t a) {
  asm volatile("ldmatrix.sync.aligned.m8n8.x4.trans.shared.b16 {%0,%1,%2,%3}, [%4];" : "=r"(r[0]), "=r"(r[1]), "=r"(r[2]), "=r"(r[3]) : "r"(a) : "memory");
}
__device__ __forceinline__ void ldsm(uint32_t* r, uint32_t a) {
  asm volatile("ldmatrix.sync.aligned.m8n8.x4.shared.b16 {%0,%1,%2,%3}, [%4];" : "=r"(r[0]), "=r"(r[1]), "=r"(r[2]), "=r"(r[3]) : "r"(a) : "memory");
}
__device__ __forceinline__ uint32_t mapa(uint32_t a, uint32_t r) {
  uint32_t v; asm volatile("mapa.shared::cluster.u32 %0, %1, %2;" : "=r"(v) : "r"(a), "r"(r)); return v;
}
__device__ __forceinline__ unsigned long long mapg(uint32_t a, uint32_t r) {
  unsigned long long v;
  asm volatile("{.reg .u32 t; .reg .u64 u; mapa.shared::cluster.u32 t, %1, %2; cvt.u64.u32 u, t; cvta.shared::cluster.u64 %0, u;}" : "=l"(v) : "r"(a), "r"(r));
  return v;
}
template <int N>
__device__ __forceinline__ void tred(float* a, int lane, int m) {
  const bool hi = lane & m;
#pragma unroll
  for (int i = 0; i < N; i++) {
    float send = hi ? a[i] : a[i + N], keep = hi ? a[i + N] : a[i];
    a[i] = keep + __shfl_xor_sync(~0u, send, m);
  }
}
template <int N>
__device__ __forceinline__ void tmax(float* a, int lane, int m) {
  const bool hi = lane & m;
#pragma unroll
  for (int i = 0; i < N; i++) {
    float send = hi ? a[i] : a[i + N], keep = hi ? a[i + N] : a[i];
    a[i] = fmaxf(keep, __shfl_xor_sync(~0u, send, m));
  }
}
__device__ __forceinline__ void arrive_n(uint32_t bar, bool on, int cnt) {
  asm volatile("{.reg .pred p; setp.ne.s32 p, %1, 0; @p mbarrier.arrive.shared::cta.b64 _, [%0], %2;}" ::"r"(bar), "r"((int)on), "r"(cnt) : "memory");
}
__device__ __forceinline__ unsigned long long stream_policy() {
  unsigned long long p;
  asm volatile("createpolicy.fractional.L2::evict_first.b64 %0, 1.0;" : "=l"(p));
  return p;
}
__device__ __forceinline__ void tma3d(uint32_t dst, const CUtensorMap* tm, uint32_t bar, int c0, int c1, int c2) {
  asm volatile("cp.async.bulk.tensor.3d.shared::cluster.global.mbarrier::complete_tx::bytes.L2::cache_hint [%0], [%1, {%3, %4, %5}], [%2], %6;"
               ::"r"(dst), "l"(tm), "r"(bar), "r"(c0), "r"(c1), "r"(c2), "l"(stream_policy()) : "memory");
}
__device__ __forceinline__ void spin_until(unsigned t) { while ((int)((unsigned)clock() - t) < 0) {} }
__device__ __forceinline__ void wait_until(unsigned t) {
  unsigned now;
  do { asm volatile("mov.u32 %0, %%globaltimer_lo;" : "=r"(now)); } while ((int)(now - t) < 0);
}
__device__ __forceinline__ void sleep_until(unsigned t) {
  unsigned now;
#pragma unroll 1
  do {
    __nanosleep(200);
    asm volatile("mov.u32 %0, %%globaltimer_lo;" : "=r"(now));
  } while ((int)(now - t) < 0);
}
#define PIN(x) asm volatile("" : "+r"(x))
#define PINL(x) asm volatile("" : "+l"(x))
#define BAR_ARRIVE(i) asm volatile("mbarrier.arrive.shared::cta.b64 _, [%0];" ::"r"(bar0 + 8 * (i)) : "memory")
#define LANE0(op, p, c, v) asm volatile("{.reg .pred q; setp.eq.s32 q, %2, 0; @q " op " [%0], %1;}" ::"l"((p) + lane), c(v), "r"(lane) : "memory")
#define CNT_ADD(c) LANE0("red.relaxed.gpu.global.add.u32", scr->cnt + (c), "r", 1)
#define BAR_INIT(i, cnt) asm volatile("mbarrier.init.shared::cta.b64 [%0], %1;" ::"r"(bar0 + 8 * (i)), "r"(cnt) : "memory")
#define BAR_ARM(i, bytes) asm volatile("mbarrier.arrive.expect_tx.shared::cta.b64 _, [%0], %1;" ::"r"(bar0 + 8 * (i)), "r"(bytes) : "memory")
struct TMaps { CUtensorMap m[9]; };

#define NCTA9 120
#define TAU 20
#define NSL 100
#define NPE 1
#define QN 4
#define FDLY 60
#define VJ 1
#define NPO 3
#define VDLY 150
#define O_Q 131072
#define O_LZ 163840
#define O_CTX 196608
#define O_HZ 198656
#define O_HW 200704
#define O_X 201728
#define O_P 218112
#define O_B 222208
#define O_R 224512
#define O_SILU 228608
#define O_SM 229632
#define O_BAR 231424
#define O_EP (O_BAR + 256)
#define O_DBG (O_EP + 16)
#define SMEM9 (O_DBG + 144)
#define B_FULL 0
#define B_FM 8
#define B_EMPTY 10
#define B_LZ 18
#define B_Q2 19
#define B_H 20
#define B_QF 21
#define B_TAB 22
#define B_W 23
#define B_ST 24
#define B_HZ 25
#define B_WZ 26
#define B_G 27
#define B_G2 28
enum { T_WQ, T_WUK, T_KV, T_MOD, T_UV, T_WO, T_GU, T_DN = 8 };
#define NBIG 40
struct Sched { unsigned zero, dth; uint2 r[3][8]; unsigned nr[3], nt[3], dt, t4, d4, d6, wt, pad; };

struct __align__(128) Scratch {
  unsigned cnt[8 * 32];
  uint2 rec[32 * 4 * 8 * 64];
  uint2 hdr[32 * 16];
  unsigned h[8 * 256];
  uint4 qa[2048];
  unsigned xao[8 * 512];
  unsigned xab[8 * 256];
  unsigned xm[2048];
};
__device__ Scratch g_scr;
#define SMEM_BASE 1024u
#define DSC ((SMEM_BASE >> 4) | (1u << 16))
#define HI128 (64u | (1u << 30))
#define HI64 (32u | (2u << 30))
template <int TA, int TB, unsigned HIA, unsigned HIB>
__device__ __forceinline__ void wgmma32(float* d, uint32_t da, uint32_t db, int acc) {
  asm volatile("{.reg .pred p; .reg .b64 da, db; setp.ne.b32 p, %18, 0; mov.b64 da, {%16, %21}; mov.b64 db, {%17, %22};\n"
               "wgmma.mma_async.sync.aligned.m64n32k16.f32.bf16.bf16 "
               "{%0,%1,%2,%3,%4,%5,%6,%7,%8,%9,%10,%11,%12,%13,%14,%15}, da, db, p, 1, 1, %19, %20;}"
               : "+f"(d[0]), "+f"(d[1]), "+f"(d[2]), "+f"(d[3]), "+f"(d[4]), "+f"(d[5]), "+f"(d[6]), "+f"(d[7]),
                 "+f"(d[8]), "+f"(d[9]), "+f"(d[10]), "+f"(d[11]), "+f"(d[12]), "+f"(d[13]), "+f"(d[14]), "+f"(d[15])
               : "r"(da), "r"(db), "r"(acc), "n"(TA), "n"(TB), "n"(HIA), "n"(HIB));
}
__device__ __forceinline__ void wgmma32r(float* d, const uint32_t* a, uint32_t db) {
  asm volatile("{.reg .b64 db; mov.b64 db, {%20, %21};\n"
               "wgmma.mma_async.sync.aligned.m64n32k16.f32.bf16.bf16 "
               "{%0,%1,%2,%3,%4,%5,%6,%7,%8,%9,%10,%11,%12,%13,%14,%15}, {%16,%17,%18,%19}, db, 1, 1, 1, 1;}"
               : "+f"(d[0]), "+f"(d[1]), "+f"(d[2]), "+f"(d[3]), "+f"(d[4]), "+f"(d[5]), "+f"(d[6]), "+f"(d[7]),
                 "+f"(d[8]), "+f"(d[9]), "+f"(d[10]), "+f"(d[11]), "+f"(d[12]), "+f"(d[13]), "+f"(d[14]), "+f"(d[15])
               : "r"(a[0]), "r"(a[1]), "r"(a[2]), "r"(a[3]), "r"(db), "n"(HI64));
}
template <int N> __device__ __forceinline__ void wg_wait(float* a) {
  asm volatile("wgmma.wait_group.sync.aligned %16;"
               : "+f"(a[0]), "+f"(a[1]), "+f"(a[2]), "+f"(a[3]), "+f"(a[4]), "+f"(a[5]), "+f"(a[6]), "+f"(a[7]), "+f"(a[8]), "+f"(a[9]), "+f"(a[10]),
                 "+f"(a[11]), "+f"(a[12]), "+f"(a[13]), "+f"(a[14]), "+f"(a[15]) : "n"(N) : "memory");
}
__device__ __forceinline__ void send32(uint32_t a, uint32_t bar, float v, int lane, int off) {
  const uint32_t w = pack2(v, __shfl_down_sync(~0u, v, 1));
  const int s = 2 * (lane & 3);
  asm volatile("{.reg .pred p; setp.eq.s32 p, %6, 0; @p st.async.shared::cluster.mbarrier::complete_tx::bytes.v4.b32 [%0], {%1,%2,%3,%4}, [%5];}"
               ::"r"(a), "r"(__shfl_sync(~0u, w, s)), "r"(__shfl_sync(~0u, w, s + 8)), "r"(__shfl_sync(~0u, w, s + 16)), "r"(__shfl_sync(~0u, w, s + 24)),
                 "r"(bar), "r"(off) : "memory");
}
__device__ __forceinline__ float sum8(uint32_t a) {
  const float4 p = lds16(a), q = lds16(a + 1024);
  return ((p.x + p.y) + (p.z + p.w)) + ((q.x + q.y) + (q.z + q.w));
}
__device__ __forceinline__ int posof(int c) { return (c & ~14) + 2 * (c & 6) + ((c >> 2) & 2); }

__global__ void __cluster_dims__(8, 1, 1) __launch_bounds__(384, 1)
fused_kernel(const bf16* __restrict__ x, const bf16* __restrict__ cvec, const bf16* __restrict__ w_mod, bf16* __restrict__ out,
             Scratch* __restrict__ scr, const __grid_constant__ Sched sch, const __grid_constant__ TMaps tms) {
  extern __shared__ __align__(1024) unsigned char smem[];
  const int tid = threadIdx.x, lane = tid & 31;
  const int b = blockIdx.x, cl = b >> 3, rn = b & 7, rk = b & 1, hd = b >> 1, f = b - 64;
  const bool isA = b < 64;
  uint32_t sb = s2u(smem), bar0 = sb + O_BAR;
  const int g = lane >> 2, tq = lane & 3;
  const int arow = 64 * rn + ((tid & 255) >> 4);
  uint4 wm[4];
  uint32_t cw, xw;
  if (tid < 256 && isA) {
    const bf16* wa = w_mod + (size_t)arow * 3072 + (lane & 8) * 64 + 64 * cl + 8 * (lane & 7);
#pragma unroll
    for (int i = 0; i < 4; i++) wm[i] = ldx16(wa + i * 16 * 3072);
    cw = ldc4(cvec + (arow & ~1) + 16 * tq);
    if (tid < 64) xw = ldc4(x + 64 * cl + (tid & 62));
  }
  unsigned gt_start;
  asm volatile("mov.u32 %0, %%globaltimer_lo;" : "=r"(gt_start));
  const int warp = __shfl_sync(~0u, tid >> 5, 0);
  if (warp == 11) {
    if (lane == 0) {
#pragma unroll
      for (int i = 0; i < B_EMPTY; i++) BAR_INIT(i, 1);
    }
    __syncwarp();
    asm volatile("fence.mbarrier_init.release.cluster;" ::: "memory");
    asm volatile("barrier.cluster.arrive.relaxed.aligned;" ::: "memory");
    if (isA) {
#pragma unroll 1
      for (int i = 0; i < 8; i++) {
        if (i >= 6) mbar_wait(bar0 + 8 * (i - 6));
        wait_until(gt_start + ((64 * i + b) * sch.dth >> 8));
        if (lane == 0) {
          BAR_ARM(i, 16384);
          tma3d(sb + i * 16384, &tms.m[i >> 2], bar0 + 8 * i, 0, i < 4 ? 128 * i : 256 * rk + 64 * (i - 4), i < 4 ? b : b & ~1);
        }
        __syncwarp();
      }
    }
  }
  if (warp == 10) {
    const unsigned ep = ldc4(&scr->cnt[0]);
    if (isA) {
      const uint4 xa = ldc16(x + 16 * lane), xb = ldc16(x + 16 * lane + 8);
      float xv[16] = {bflo(xa.x), bfhi(xa.x), bflo(xa.y), bfhi(xa.y), bflo(xa.z), bfhi(xa.z), bflo(xa.w), bfhi(xa.w),
                      bflo(xb.x), bfhi(xb.x), bflo(xb.y), bfhi(xb.y), bflo(xb.z), bfhi(xb.z), bflo(xb.w), bfhi(xb.w)};
      const float x0 = __shfl_sync(~0u, xv[0], 0);
      float s = 0, q = 0;
#pragma unroll
      for (int i = 0; i < 16; i++) { xv[i] -= x0; s += xv[i]; q += xv[i] * xv[i]; }
#pragma unroll
      for (int o = 16; o; o >>= 1) { s += __shfl_xor_sync(~0u, s, o); q += __shfl_xor_sync(~0u, q, o); }
      s *= 1.f / 512.f;
      float rstd;
      asm("rsqrt.approx.ftz.f32 %0, %1;" : "=f"(rstd) : "f"(fmaxf(q * (1.f / 512.f) - s * s, 0.f) + 1e-5f));
      *(float2*)(smem + O_SM + 1024) = make_float2(s + x0, rstd);
    }
    if (lane == 0) *(volatile unsigned*)(smem + O_EP) = ep;
    nbar_arrive(1, 288);
  }
  const int cls = isA ? (b >= NBIG) : 2, v0 = isA ? 2 : 0;
  if (warp >= 8) {
    asm volatile("setmaxnreg.dec.sync.aligned.u32 56;");
    if (warp == 8) {
      if (lane < 8) asm volatile("prefetch.tensormap [%0];" ::"l"(&tms.m[lane + 1]) : "memory");
      if ((sb & 0xFFFFFF) != SMEM_BASE) __trap();
    } else if (warp == 9) {
      if (lane == 0) {
#pragma unroll
        for (int i = B_EMPTY; i < B_LZ; i++) BAR_INIT(i, 8);
        BAR_INIT(B_LZ, 8); BAR_INIT(B_Q2, 9); BAR_ARM(B_Q2, 1024);
        BAR_INIT(B_H, 1); BAR_INIT(B_QF, 1); BAR_ARM(B_QF, 32768);
        BAR_INIT(B_TAB, 1); BAR_INIT(B_W, 1); BAR_INIT(B_ST, 8); BAR_INIT(B_WZ, 1); BAR_INIT(B_HZ, 1); BAR_ARM(B_HZ, isA ? 1024 : 512); BAR_INIT(B_G, 1); BAR_INIT(B_G2, 1);
      }

    }
    if (warp != 11) {
      __syncwarp();
      asm volatile("fence.mbarrier_init.release.cluster;" ::: "memory");
      __threadfence_block();
      asm volatile("barrier.cluster.arrive.relaxed.aligned;" ::: "memory");
    }
    asm volatile("barrier.cluster.wait.acquire.aligned;" ::: "memory");
    if (warp == 8) {
      const int nr = sch.nr[cls], vl = v0 + sch.nt[cls] - 1;
      unsigned long long hist = 0;
      int v = v0;
#pragma unroll 1
      for (int rd = 0; rd < nr; rd++) {
        const uint2 e = sch.r[cls][rd];
        const int type = e.y & 15, win = (e.y >> 4) & 15, pos = b + 64 - (int)((e.y >> 8) & 255), tile = e.y >> 16;
        const bool mod = type == T_MOD;
        const int ni = mod ? 1 : type == T_DN ? 2 : 4;
        unsigned t = gt_start + (e.x & 0xffff) + (pos * sch.dt >> 8);
        const int c0 = mod ? 1024 + 32 * b : type == T_WO || type == T_DN ? 64 * rn : type == T_GU ? 32 * f : 0;
        int c1 = type == T_KV ? 64 * (tile + pos) : 0;
        int c2 = mod ? tile : type == T_WO ? 4 * cl : type == T_DN ? 2 * cl - 16 : type == T_UV ? b : 0;
        const int i1 = type == T_UV ? 128 : 0;
#pragma unroll 1
        for (int j = 0; j < ni; j++) {
          const int slot = mod ? B_FM + tile : (v & 1) * 4 + j;
          if (mod ? tile : v >= 2) mbar_wait(bar0 + 8 * (B_EMPTY + (mod ? (vl & 1) * 4 : slot)), mod ? (vl >> 1) & 1 : ((v >> 1) - 1) & 1);
          const int hw = (int)(hist >> (6 * (win - 1))) & 63;
          if (hw) mbar_wait(bar0 + 8 * (hw & 15), (hw >> 4) & 1);
          wait_until(t);
          if (lane == 0) {
            BAR_ARM(slot, 16384);
            tma3d(sb + (mod ? (tile ? O_Q : O_X) : slot * 16384), &tms.m[type == T_GU ? type + (j & 1) : type], bar0 + 8 * slot, c0, c1, c2);
          }
          __syncwarp();
          hist = hist << 6 | (32 | (mod ? 0 : (v & 2) << 3) | slot);
          t += e.x >> 16; c1 += i1;
          c2 += type == T_KV ? 2 : type == T_WO || type == T_DN ? 1 : type == T_GU ? j & 1 : 0;
        }
        v += !mod;
      }
      return;
    }
    const unsigned epoch = *(volatile unsigned*)(smem + O_EP), par = (epoch + 1) & 1;
    if (warp == 10) {
      if (isA) {
        for (int it = 0; ldx4(scr->cnt + 1) != (epoch + 1) * 128 && it < SPIN_MAX; it++) {}
        if (lane == 0) BAR_ARRIVE(B_H);
      } else mbar_wait(bar0);
      if (!(rn & (QN - 1))) {
        for (int it = 0; ldx4(scr->cnt + 32 + 32 * (rn >> 2)) != (epoch + 1) * 32 && it < SPIN_MAX; it++) {}
        if (lane == 0)
          asm volatile("cp.async.bulk.shared::cluster.global.mbarrier::complete_tx::bytes.multicast::cluster [%0], [%1], %4, [%2], %3;"
                       ::"r"(sb + O_Q + rn * 4096), "l"(scr->qa + rn * 256), "r"(bar0 + 8 * B_QF), "h"((unsigned short)0xff), "n"(4096 * QN) : "memory");
      }
      const unsigned dl = isA ? sch.d4 : sch.d6;
      unsigned tw = gt_start + sch.t4;
      if (!isA) {
        const int nt = sch.nt[2];
#pragma unroll 1
        for (int t = 0; t < nt; t++) mbar_wait(bar0 + 8 * B_EMPTY + (t & 1) * 32, (t >> 1) & 1);
        unsigned long long now;
        asm volatile("mov.u64 %0, %%globaltimer;" : "=l"(now));
        LANE0("red.relaxed.gpu.global.max.u64", scr->cnt + 130, "l", now);
        CNT_ADD(128);
        tw = (unsigned)now + 1700;
      }
      sleep_until(tw);
      uint4 an;
      for (int it = 0; an = ldx16(scr->cnt + 128), an.x != (epoch + 1) * 56 && it < SPIN_MAX; it++) {}
      wait_until(an.z + (dl >> 16));
      if (lane == 0) BAR_ARRIVE(B_G2);
      wait_until(an.z + (dl & 0xffff));
      if (lane == 0) BAR_ARRIVE(B_G);
    } else if (warp == 11) {
      {
        uint2* ph = scr->hdr + ((lane & 24) + 2 * tq + (g & 1)) * 16 + cl;
        const bool own = (lane >> 4) * 4 + tq == rn;
        if (own) { stx8(ph, make_uint2(par ^ 1, 0)); if (cl == 14) stx8(ph + 1, make_uint2(0, 0)); }
        uint32_t a_w = sb + O_HW + ((lane >> 4) * 4 + tq) * 128 + (g & 1) * 64 + ((lane >> 1) & 4);
        PIN(a_w); PINL(ph);
        const int vt = v0 + sch.nt[cls];
#pragma unroll 1
        for (int t = 0; t < vt; t++) mbar_wait(bar0 + 8 * B_EMPTY + (t & 1) * 32, (t >> 1) & 1);
        float hz[8], M;
        uint32_t wp[4];
#pragma unroll 1
        for (int e = 0; e < 2; e++) {
          POLL {
            unsigned ok = 1;
#pragma unroll
            for (int u = 0; u < 8; u++)
              asm volatile("ld.relaxed.cluster.shared.f32 %0, [%1];" : "=f"(hz[u]) : "r"(sb + O_HZ + e * 1024 + u * 128 + lane * 4) : "memory");
#pragma unroll
            for (int u = 0; u < 4; u++) ok = and3(ok, __float_as_uint(hz[u]), __float_as_uint(hz[u + 4]));
            RETRY(~ok)
          }
          if (e) break;
          M = fmaxf(fmaxf(fmaxf(hz[0], hz[1]), fmaxf(hz[2], hz[3])), fmaxf(fmaxf(hz[4], hz[5]), fmaxf(hz[6], hz[7])));
          M = u2f(fbits(M));
#pragma unroll
          for (int u = 0; u < 4; u++) {
            wp[u] = pack2(ex2(hz[u] - M), ex2(hz[u + 4] - M));
            sts4(a_w + ((rn - u) & 3) * 8, u2f(wp[u])); sts4(a_w + ((rn - u) & 3) * 8 + 32, u2f(wp[u]));
          }
          __syncwarp();
          if (lane == 0) BAR_ARRIVE(B_WZ);
        }
        float L = 0.f;
#pragma unroll
        for (int u = 0; u < 4; u++) L += bflo(wp[u]) * hz[u] + bfhi(wp[u]) * hz[u + 4];
        if (own) pub8(ph, __float_as_uint(M) | 1u, __float_as_uint(L));
      }
      if (isA) {
        mbar_wait(bar0 + 8 * B_G2);
        unsigned long long hh;
        POLL { hh = ldx64(scr->hdr + hd * 16 + (lane & 15)); RETRY((lane & 15) == 15 ? 0u : (unsigned)hh ^ par) }
        const float m = (lane & 15) == 15 ? -1e30f : u2f((unsigned)hh);
        int mi = __float_as_int(m);
        mi ^= (mi >> 31) & 0x7fffffff;
        mi = __reduce_max_sync(~0u, mi);
        mi ^= (mi >> 31) & 0x7fffffff;
        const float w = ex2(m - __int_as_float(mi));
        float L = w * u2f(hh >> 32);
#pragma unroll
        for (int o2 = 8; o2; o2 >>= 1) L += __shfl_xor_sync(~0u, L, o2);
        sts4(sb + O_SM + (384 + 2 * (lane & 6) + ((lane >> 2) & 2) + (lane & 1)) * 4, w * rcp(L));
        __syncwarp();
        if (lane == 0) BAR_ARRIVE(B_W);
      }
    } else {
#pragma unroll 4
      for (int i = 0; i < 72; i++) sts16(sb + O_LZ + i * 512 + lane * 16, make_uint4(0, 0, 0, 0));
      __syncwarp();
      if (lane < 8) asm volatile("mbarrier.arrive.release.cluster.shared::cluster.b64 _, [%0];" ::"r"(mapa(bar0 + 8 * B_LZ, lane)) : "memory");
      if (isA) {
        mbar_wait(bar0 + 8 * B_QF);
#pragma unroll 2
        for (int k = 0; k < 8; k++) {
          const uint32_t cp = ldc4(cvec + 2 * (lane + 32 * k));
          *(uint32_t*)(smem + O_SILU + (lane + 32 * k) * 4) = pack2(silu_bf(bflo(cp)), silu_bf(bfhi(cp)));
        }
        __syncwarp();
        uint32_t ab = sb + O_X + (8 * (lane >> 4) + (lane & 7)) * 64 + ((((lane >> 3) & 1) ^ ((lane >> 1) & 3)) << 4);
        float d[4][4] = {};
#pragma unroll 1
        for (int jm = 0; jm < 2; jm++) {
          mbar_wait(bar0 + 8 * (B_FM + jm));
#pragma unroll 2
          for (int s2 = 0; s2 < 8; s2++)
#pragma unroll
            for (int s = 0; s < 2; s++) {
              uint32_t a0[4], a1[4];
              const uint32_t* ps = (const uint32_t*)(smem + O_SILU) + 128 * jm + 16 * s2 + 8 * s + tq;
              ldsm_t(a0, ab + (2 * s2 + s) * 1024); ldsm_t(a1, (ab + (2 * s2 + s) * 1024) ^ 32);
              mma16(d[s], a0, ps[0], ps[4]); mma16(d[2 + s], a1, ps[0], ps[4]);
            }
          ab -= O_X - O_Q;
        }
        const float t0 = (tq & 1) ? d[0][2] + d[1][2] : d[0][0] + d[1][0], t1 = (tq & 1) ? d[2][2] + d[3][2] : d[2][0] + d[3][0];
        stx4(scr->xm + b * 32 + posof(8 * tq + g), fbits(bfr(bfr((tq & 2) ? t1 : t0) + ((b >> 4) == 2 ? 1.f : 0.f))));
        __syncwarp();
        CNT_ADD(96);
      } else sleep_until(gt_start + sch.t4);
      for (int it = 0; ldx4(scr->cnt + 96) != (epoch + 1) * 64 && it < SPIN_MAX; it++) __nanosleep(NSL);
      if (isA) {
        unsigned long long ga;
        POLL { ga = ldx64(scr->xm + 64 * rn + 2 * lane); RETRY(lop_x3((unsigned)ga, ga >> 32, par)) }
        *(float2*)(smem + O_SM + (320 + 2 * lane) * 4) = make_float2(bfhi((unsigned)ga), bfhi(ga >> 32));
      }
      __syncwarp();
      if (lane == 0) BAR_ARRIVE(B_TAB);
    }
    return;
  }

  float* s_sm = (float*)(smem + O_SM);
  unsigned par, epoch;
  asm volatile("barrier.cluster.arrive.relaxed.aligned;" ::: "memory");
  if (isA) {
    float* s_r = (float*)(smem + O_R);
    float acc[8] = {0, 0, 0, 0, 0, 0, 0, 0};
    const float sl = silu_bf((arow & 1) ? bfhi(cw) : bflo(cw));
#pragma unroll
    for (int i = 0; i < 4; i++) fma8(acc, wm[i], __shfl_sync(~0u, sl, i, 4));
    tred<4>(acc, lane, 16);
    *(float4*)(s_r + warp * 128 + 8 * (lane & 15) + ((lane >> 2) & 4)) = make_float4(acc[0], acc[1], acc[2], acc[3]);
    nbar(1, 288);
    epoch = *(volatile unsigned*)(smem + O_EP);
    par = (epoch + 1) & 1;
    if (warp < 2) {
      float t = 0.f, ca = rn == 0 ? 1.f : 0.f;
#pragma unroll
      for (int w = 0; w < 8; w++) { t += s_r[w * 128 + tid]; ca += s_r[w * 128 + 64 + tid]; }
      t += ca * ((((tid & 1) ? bfhi(xw) : bflo(xw)) - s_sm[256]) * s_sm[257]);
      const float nb = __shfl_down_sync(~0u, t, 1);
      const uint32_t w0 = lane < 8 ? pack2t(t, nb, par) : pack2(t, nb);
      const uint32_t w1 = __shfl_down_sync(~0u, w0, 8), w2 = __shfl_down_sync(~0u, w0, 16), w3 = __shfl_down_sync(~0u, w0, 24);
      if (lane < 8 && !(lane & 1)) stx16(scr->h + (rn >> 1) * 512 + (2 * cl + warp) * 32 + rk * 16 + 2 * lane, make_uint4(w0, w1, w2, w3));
      __syncwarp();
      CNT_ADD(1);
    }
    asm volatile("barrier.cluster.wait.acquire.aligned;" ::: "memory");
    const uint32_t rsb = mapa(sb, rn ^ 1);
    {
      uint32_t a[4][4][4];
      mbar_wait(bar0 + 8 * (warp >> 1));
      const uint32_t ab = sb + (64 * warp + 8 * (lane >> 4) + (lane & 7)) * 128;
#pragma unroll
      for (int s = 0; s < 4; s++)
#pragma unroll
        for (int mt = 0; mt < 4; mt++) ldsm_t(a[s][mt], ab + s * 2048 + (((2 * mt + ((lane >> 3) & 1)) ^ (lane & 7)) << 4));
      arrive_n(bar0 + 8 * (B_EMPTY + (warp >> 1)), lane == 0, 4 + (dep16(&a[0][0][0]) & sch.zero));
      uint4 v0, v1;
      const unsigned* ph = scr->h + (g >> 1) * 512 + 64 * warp + 4 * (lane & 7);
      uint32_t off = O_B + warp * 272 + (32 * rk + 8 * tq + (lane & 4)) * 4;
      PIN(off); PINL(ph);
      mbar_wait(bar0 + 8 * B_H);
      POLL { v0 = ldx16(ph); v1 = ldx16(ph + 32); RETRY(lop_x3(v0.x, v1.x, par)) }
      float d[4][4] = {};
#pragma unroll
      for (int mt = 0; mt < 4; mt++) {
        mma16(d[mt], a[0][mt], v0.x, v0.y); mma16(d[mt], a[1][mt], v0.z, v0.w);
        mma16(d[mt], a[2][mt], v1.x, v1.y); mma16(d[mt], a[3][mt], v1.z, v1.w);
      }
      float r[8];
#pragma unroll
      for (int mt = 0; mt < 4; mt++) { r[2 * mt] = d[mt][0] + d[mt][1]; r[2 * mt + 1] = d[mt][2] + d[mt][3]; }
      tred<4>(r, lane, 2); tred<2>(r, lane, 1);
      const float rc = __shfl_xor_sync(~0u, (lane & 4) ? r[0] : r[1], 4);
      const uint32_t wd = (lane & 4) ? pack2(rc, r[1]) : pack2(r[0], rc);
      const uint32_t w1 = __shfl_down_sync(~0u, wd, 8), w2 = __shfl_down_sync(~0u, wd, 16), w3 = __shfl_down_sync(~0u, wd, 24);
      asm volatile("{.reg .pred p; setp.lt.s32 p, %7, 8; @p st.shared.v4.b32 [%0], {%2,%3,%4,%5};\n"
                   "@p st.async.shared::cluster.mbarrier::complete_tx::bytes.v4.b32 [%1], {%2,%3,%4,%5}, [%6];}"
                   ::"r"(sb + off), "r"(rsb + off), "r"(wd), "r"(w1), "r"(w2), "r"(w3), "r"(rsb + O_BAR + 8 * B_Q2), "r"(lane) : "memory");
      __syncwarp();
      arrive_n(bar0 + 8 * B_Q2, lane == 0, 1);
    }
    {
      uint32_t a[2][8][4];
      uint32_t a_bq = sb + O_B + (lane & 7) * 272 + (lane >> 3) * 16;
      uint4* p_qa = scr->qa + (4 * rk + (warp >> 1)) * 256 + hd * 8 + ((4 * (warp & 1) + tq) ^ (hd & 7));
      PIN(a_bq); PINL(p_qa);
      mbar_wait(bar0 + 8 * (4 + (warp >> 1)));
      const uint32_t ab = sb + 65536 + (warp >> 1) * 16384 + (32 * (warp & 1) + (lane & 15)) * 128;
#pragma unroll
      for (int i = 0; i < 16; i++) ldsm(a[i >> 3][i & 7], ab + (i >> 3) * 2048 + ((i >> 2) & 1) * 8192 + (((2 * (i & 3) + (lane >> 4)) ^ (lane & 7)) << 4));
      arrive_n(bar0 + 8 * (B_EMPTY + 4 + (warp >> 1)), lane == 0, 4 + (dep16(&a[0][0][0]) & sch.zero));
      mbar_wait(bar0 + 8 * B_Q2);
      float d[4][4] = {};
#pragma unroll
      for (int y = 0; y < 4; y++) {
        uint32_t bq[4];
        ldsm(bq, a_bq + 64 * y);
#pragma unroll
        for (int mt = 0; mt < 2; mt++) { mma16(d[2 * mt], a[mt][2 * y], bq[0], bq[1]); mma16(d[2 * mt + 1], a[mt][2 * y + 1], bq[2], bq[3]); }
      }
      float r[4];
#pragma unroll
      for (int i = 0; i < 4; i++) r[i] = (d[i & 2][2 * (i & 1)] + d[i & 2][2 * (i & 1) + 1]) + (d[(i & 2) + 1][2 * (i & 1)] + d[(i & 2) + 1][2 * (i & 1) + 1]);
      tred<2>(r, lane, 2); tred<1>(r, lane, 1);
      const float nb = __shfl_xor_sync(~0u, r[0], 4);
      const uint32_t w0 = (lane >> 3) == (hd & 3) ? pack2t(r[0], nb, par) : pack2(r[0], nb);
      const uint32_t w1 = __shfl_down_sync(~0u, w0, 8), w2 = __shfl_down_sync(~0u, w0, 16), w3 = __shfl_down_sync(~0u, w0, 24);
      if (lane < 4) stx16(p_qa, make_uint4(w0, w1, w2, w3));
      if (warp) nbar_arrive(3, 256); else { nbar(3, 256); CNT_ADD(32 + 32 * rk); }
    }
  } else {
    nbar(1, 288);
    epoch = *(volatile unsigned*)(smem + O_EP);
    par = (epoch + 1) & 1;
    asm volatile("barrier.cluster.wait.acquire.aligned;" ::: "memory");
    mbar_wait(bar0);
  }
  asm volatile("setmaxnreg.inc.sync.aligned.u32 224;");
  uint2* p_rec = scr->rec + ((16 * (warp >> 2) + 2 * (warp & 3) + (g & 1) + 4 * (tq & 2)) * 32 + 4 * rn + (tq & 1)) * 64 + cl * 4 + (g >> 1);
  PINL(p_rec);
  {
    const unsigned inv = par ^ 1;
#pragma unroll
    for (int q = 0; q < 2; q++) { stx8(p_rec + q * 128, make_uint2(inv, 0)); if (cl == 14) stx8(p_rec + q * 128 + 4, make_uint2(0, 0)); }
    if (isA) { if (warp < 2) { stx4(scr->xao + b * 64 + tid, inv); stx4(scr->xab + cl * 256 + (2 * (rn & 3) + warp) * 32 + (rn >> 2) * 16 + (lane >> 1), inv); } }
    else if (f == 0) { stx4(out + 2 * tid, 0); __threadfence(); }
  }
  sb = __shfl_sync(~0u, sb, 0); bar0 = sb + O_BAR;
  const int nt = sch.nt[cls], wg = warp >> 2;
  uint32_t a_z[4];
#pragma unroll
  for (int u = 0; u < 4; u++) {
    const int s3 = (rn - u - (lane >> 1 & 1)) & 3;
    a_z[u] = sb + O_LZ + (s3 + 4 * (lane & 1)) * 4096 + wg * 512 + g * 64 + (((warp & 3) ^ (s3 & 1) ^ (2 * (lane & 1))) << 4);
    PIN(a_z[u]);
  }
  uint32_t z[4][4], a_w = sb + O_HW + warp * 128 + (g & 1) * 64 + (tq & 1) * 8;
  PIN(a_w);
  {
    const float sc = 0.08838834764831845f * 1.4426950408889634f;
    float mrun = -1e30f;
    float o[4][16], sx[16], mref[8];
#pragma unroll
    for (int k = 0; k < 16; k++) { o[0][k] = o[1][k] = o[2][k] = o[3][k] = sx[k] = 0.f; mref[k >> 1] = -1e30f; }
    const int key = 16 * warp + (lane & 15);
    uint32_t a_p = sb + O_P + key * 64 + (((lane >> 4) ^ ((key >> 1) & 3)) << 4);
    uint32_t a_v = sb + wg * 32768 + (8 * (lane >> 4) + (lane & 7)) * 128 + (((2 * (warp & 3) + ((lane >> 3) & 1)) ^ (lane & 7)) << 4);
    const int rot = rn + warp;
    const int qown = wg == (rn >> 2) ? -warp & 3 : -1;
    uint32_t a_own = sb + O_LZ + rn * 4096 + (warp & 3) * 1024 + g * 64 + ((tq ^ (rn & 1) ^ ((rn >> 1) & 2)) << 4);
    PIN(a_own);
    unsigned long long dst[4];
#pragma unroll
    for (int q = 0; q < 4; q++) {
      dst[q] = mapg(a_own, 4 * wg + ((q + rot) & 3));
      PINL(dst[q]);
    }
    unsigned long long a_h = mapg(sb + O_HZ + wg * 1024 + rn * 128 + lane * 4, 2 * (warp & 3));
    unsigned long long a_h1 = mapg(sb + O_HZ + wg * 1024 + rn * 128 + lane * 4, 2 * (warp & 3) + 1);
    PIN(a_p); PIN(a_v); PINL(a_h); PINL(a_h1);
    uint32_t rel = lane < 4 && lane >= 2 * wg ? 2 - (tq >> 1) : 0;
    PIN(rel);
    uint32_t ones[4] = {0x3F803F80u, 0x3F803F80u, 0x3F803F80u, 0x3F803F80u};
    PIN(ones[0]); PIN(ones[1]); PIN(ones[2]); PIN(ones[3]);
    {
      asm volatile("{.reg .pred p; .reg .u32 n; mov.u32 n, 0;\n"
                   "W%=: mbarrier.try_wait.parity.acquire.cluster.shared::cta.b64 p, [%0], 0; add.u32 n, n, 1; setp.lt.and.u32 p, n, 0x100000, !p; @p bra W%=;}"
                   ::"r"(bar0 + 8 * B_LZ) : "memory");
      mbar_wait(bar0 + 8 * B_QF);
      unsigned bad = 0;
#pragma unroll
      for (int k = 0; k < 8; k++) bad |= __float_as_uint(lds4(sb + O_Q + k * 4096 + tid * 16 + (lane >> 3) * 4)) ^ par;
      if (__builtin_expect(__any_sync(~0u, bad & 1), 0)) {
#pragma unroll 1
        for (int k = 0; k < 8; k++) {
          uint4 v;
          POLL { v = ldx16(scr->qa + k * 256 + tid); RETRY(((lane & 16) ? ((lane & 8) ? v.w : v.z) : ((lane & 8) ? v.y : v.x)) ^ par) }
          sts16(sb + O_Q + k * 4096 + tid * 16, v);
        }
        asm volatile("fence.proxy.async.shared::cta;" ::: "memory");
      }
      if (warp >= 4) nbar_arrive(1, 256); else nbar(1, 256);
    }
#pragma unroll 1
    for (int t = 0; t < nt; t++) {
      const int v = v0 + t;
      const uint32_t fb = bar0 + (v & 1) * 32, ph = (v >> 1) & 1, av = a_v + (v & 1) * 65536;
      uint32_t vf[4][4][4], cnt;
      auto landed = [&]() {
        cnt = rel + (dep16(&vf[0][0][0]) & (nt >> 8));
        PIN(cnt);
      };
      if (wg == 0) {
        const uint32_t da = DSC + (v & 1) * 4096, db = DSC + O_Q / 16;
#pragma unroll 1
        for (int j = 0; j < 4; j++) {
          mbar_wait(fb + 8 * j, ph);
          asm volatile("wgmma.fence.sync.aligned;" ::: "memory");
#pragma unroll
          for (int k = 0; k < 8; k++)
            wgmma32<0, 0, HI128, HI128>(sx, da + j * 1024 + (k >> 2) * 512 + (k & 3) * 2, db + j * 512 + (k >> 2) * 256 + (k & 3) * 2, k ? 1 : j);
          asm volatile("wgmma.commit_group.sync.aligned;" ::: "memory");
          if (j == VJ) {
#pragma unroll
            for (int i = 0; i < 16; i++) ldsm_t(vf[i >> 2][i & 3], av + (((i >> 2) + rot) & 3) * 8192 + (i & 3) * 2048);
            nbar(5, 256);
            landed();
          }
        }
      } else {
        nbar_arrive(5, 256);
#pragma unroll 1
        for (int j = 0; j < 2; j++) {
          mbar_wait(fb + 16 + 8 * j, ph);
          if (j) spin_until(clock() + VDLY);
#pragma unroll
          for (int q = 0; q < 4; q++)
            if (((q + rot) & 2) == 2 * j)
#pragma unroll
              for (int k = 0; k < 4; k++) ldsm_t(vf[q][k], av + ((q + rot) & 3) * 8192 + k * 2048);
        }
        cnt = 0;
      }
      wg_wait<0>(sx);
      asm volatile("{.reg .pred p; setp.ne.s32 p, %1, 0; @p mbarrier.arrive.shared::cta.b64 _, [%0], %1;}" ::"r"(fb + 8 * B_EMPTY + 8 * tq), "r"(cnt) : "memory");
#pragma unroll 1
      for (int pass = 0;; pass++) {
        int ex = !(t | pass);
        if (wg == 0 && (t | pass)) {
          uint32_t pk[8];
#pragma unroll
          for (int i = 0; i < 8; i++) pk[i] = pack2(ex2(sx[2 * i] * sc - mref[i & 6]), ex2(sx[2 * i + 1] * sc - mref[(i & 6) + 1]));
          asm volatile("stmatrix.sync.aligned.m8n8.x4.shared.b16 [%0], {%2,%3,%4,%5};\n"
                       "stmatrix.sync.aligned.m8n8.x4.shared.b16 [%1], {%6,%7,%8,%9};"
                       ::"r"(a_p), "r"(a_p ^ 32), "r"(pk[0]), "r"(pk[1]), "r"(pk[2]), "r"(pk[3]), "r"(pk[4]), "r"(pk[5]), "r"(pk[6]), "r"(pk[7]) : "memory");
          const uint32_t mx = __vmaxu2(__vmaxu2(__vmaxu2(pk[0], pk[1]), __vmaxu2(pk[2], pk[3])), __vmaxu2(__vmaxu2(pk[4], pk[5]), __vmaxu2(pk[6], pk[7])));
          ex = max(mx, mx << 16) > (127u + TAU) << 23;
          asm volatile("fence.proxy.async.shared::cta;" ::: "memory");
        }
        asm volatile("{.reg .pred p, q; setp.ne.s32 q, %0, 0; bar.red.or.pred p, 4, 256, q; selp.s32 %0, 1, 0, p;}" : "+r"(ex)::"memory");
        if (!ex || pass) break;
        int ln;
        asm volatile("mov.u32 %0, %%laneid;" : "=r"(ln));
        const uint32_t a_pm = sb + O_SM + ln * 16;
        if (wg == 0) {
          float cm[8];
#pragma unroll
          for (int i = 0; i < 8; i++) cm[i] = fmaxf(sx[2 * (i & 6) + (i & 1)], sx[2 * (i & 6) + (i & 1) + 2]);
          tmax<4>(cm, lane, 16); tmax<2>(cm, lane, 8); tmax<1>(cm, lane, 4);
          sts4(a_pm + warp * 4, cm[0] * sc);
        }
        nbar(4, 256);
        const float4 pm = lds16(a_pm);
        const float mn = u2f(__float_as_uint(fmaxf(fmaxf(fmaxf(pm.x, pm.y), fmaxf(pm.z, pm.w)), mrun)) | 1u), al = ex2(mrun - mn);
        mrun = mn;
#pragma unroll
        for (int i = 0; i < 8; i++) {
          const float a = __shfl_sync(~0u, al, 4 * i + (ln & 3)), aw = wg ? a : 1.f;
          mref[i] = __shfl_sync(~0u, mn, 4 * i + (ln & 3));
#pragma unroll
          for (int e = 0; e < 2; e++) {
            const int k = 2 * (i & 6) + (i & 1) + 2 * e;
            o[0][k] *= a; o[1][k] *= a; o[2][k] *= a; o[3][k] *= a; sx[k] *= aw;
          }
        }
      }
      float hv = mrun;
      if (wg) {
        asm volatile("wgmma.fence.sync.aligned;" ::: "memory");
#pragma unroll
        for (int k = 0; k < 4; k++) wgmma32r(sx, ones, DSC + O_P / 16 + k * 64);
        asm volatile("wgmma.commit_group.sync.aligned;" ::: "memory");
        landed();
        asm volatile("{.reg .pred p; setp.ne.s32 p, %1, 0; @p mbarrier.arrive.shared::cta.b64 _, [%0], %1;}" ::"r"(fb + 8 * B_EMPTY + 8 * tq), "r"(cnt) : "memory");
        wg_wait<0>(sx);
        float lv[4];
#pragma unroll
        for (int j = 0; j < 4; j++) lv[j] = (lane & 4) ? sx[4 * j + 1] : sx[4 * j];
        hv = (lane & 16) ? ((lane & 8) ? lv[3] : lv[2]) : ((lane & 8) ? lv[1] : lv[0]);
      }
      asm volatile("{.reg .pred p; setp.eq.s32 p, %3, %4; @p st.relaxed.cluster.b32 [%0], %1; @p st.relaxed.cluster.b32 [%2], %1;}"
                   ::"l"(a_h), "r"(__float_as_uint(hv) | 1u), "l"(a_h1), "r"(t), "r"(nt - 1) : "memory");
#pragma unroll
      for (int q = 0; q < 4; q++) {
        if (q < 2) {
          asm volatile("wgmma.fence.sync.aligned;" ::: "memory");
#pragma unroll
          for (int u = q; u < (q ? 4 : 1); u++) {
#pragma unroll
            for (int k = 0; k < 4; k++) wgmma32r(o[u], vf[u][k], DSC + O_P / 16 + k * 64);
            asm volatile("wgmma.commit_group.sync.aligned;" ::: "memory");
          }
        }
        if (q == 3) {
#pragma unroll
          for (int u = 0; u < 4; u++)
            asm volatile("{.reg .pred p; setp.eq.s32 p, %5, %6; @p ldmatrix.sync.aligned.m8n8.x4.trans.shared.b16 {%0,%1,%2,%3}, [%4];}"
                         : "=r"(z[u][0]), "=r"(z[u][1]), "=r"(z[u][2]), "=r"(z[u][3]) : "r"(a_z[u] + u * 1024), "r"(t), "r"(nt - 1) : "memory");
        }
        if (q == 1) wg_wait<2>(o[q]); else if (q == 2) wg_wait<1>(o[q]); else wg_wait<0>(o[q]);
        if (q == 0 || t == nt - 1)
#pragma unroll
        for (int j = 0; j < 2; j++)
          asm volatile("{.reg .pred p, q, r; setp.eq.s32 p, %5, %6; setp.eq.and.s32 q|r, %7, %8, p; @r st.relaxed.cluster.v4.b32 [%0], {%1,%2,%3,%4};\n"
                       "@q st.shared.v4.b32 [%9], {%1,%2,%3,%4};}"
                       ::"l"(dst[q] + j * 512), "r"(pack2t(o[q][8 * j], o[q][8 * j + 1], 1)), "r"(pack2(o[q][8 * j + 2], o[q][8 * j + 3])),
                         "r"(pack2(o[q][8 * j + 4], o[q][8 * j + 5])), "r"(pack2(o[q][8 * j + 6], o[q][8 * j + 7])), "r"(t), "r"(nt - 1),
                         "r"(qown), "r"(q), "r"(a_own + j * 512) : "memory");
      }
    }
  }
  {
    uint32_t wx[4][4];
    mbar_wait(bar0 + 8 * B_WZ);
#pragma unroll
    for (int u = 0; u < 4; u++) {
      uint2 wp;
      asm volatile("ld.shared.v2.u32 {%0, %1}, [%2];" : "=r"(wp.x), "=r"(wp.y) : "r"(a_w + u * 8) : "memory");
      const bool lo = (g >> 1) == (tq >> 1), hi = (g >> 1) == 2 + (tq >> 1);
      wx[u][0] = lo ? wp.x : 0u; wx[u][1] = lo ? wp.y : 0u; wx[u][2] = hi ? wp.x : 0u; wx[u][3] = hi ? wp.y : 0u;
    }
    auto bad = [&]() {
      const unsigned ok = and3(and3(and3(z[0][0], z[0][1], z[0][2]), and3(z[0][3], z[1][0], z[1][1]), and3(z[1][2], z[1][3], z[2][0])),
                               and3(and3(z[2][1], z[2][2], z[2][3]), and3(z[3][0], z[3][1], z[3][2]), z[3][3]), 0x10001u);
      return __any_sync(~0u, g == 0 && ok != 0x10001u);
    };
    POLL {
      if (it_)
#pragma unroll
        for (int u = 0; u < 4; u++) ldsm_t(z[u], a_z[u] + u * 1024);
      if (!bad() || ++it_ >= SPIN_MAX) break;
    }
    float d0[8][4] = {}, d[8][4], r[8];
#pragma unroll
    for (int i = 0; i < 8; i++) mma16(d0[i], wx[i >> 1], z[i >> 1][2 * (i & 1)], z[i >> 1][2 * (i & 1) + 1]);
    POLL {
#pragma unroll
      for (int u = 0; u < 4; u++) ldsm_t(z[u], a_z[u ^ 2] + u * 1024);
#pragma unroll
      for (int i = 0; i < 8; i++) mma16c(d[i], wx[(i >> 1) ^ 2], z[i >> 1][2 * (i & 1)], z[i >> 1][2 * (i & 1) + 1], d0[i]);
      if (!bad() || ++it_ >= SPIN_MAX) break;
    }
#pragma unroll
    for (int i = 0; i < 8; i++) r[i] = (tq & 2) ? ((g & 1) ? d[i][3] : d[i][2]) : ((g & 1) ? d[i][1] : d[i][0]);
#pragma unroll
    for (int q = 0; q < 2; q++) pub8(p_rec + q * 128, pack2t(r[4 * q], r[4 * q + 1], par) | 1u, pack2(r[4 * q + 2], r[4 * q + 3]));
  }
  const int vt = v0 + nt;
  const uint32_t bufa = sb + (vt & 1) * 65536, fulla = bar0 + (vt & 1) * 32, pha = (vt >> 1) & 1, phb = ((vt + 1) >> 1) & 1;
  const uint32_t bufo = sb + ((vt + 1) & 1) * 65536, fullb = bar0 + ((vt + 1) & 1) * 32;
  uint32_t a_rs = sb + O_R + (warp >> 2) * 1024 + (16 * tq + g) * 16 + ((warp + tq) & 3) * 4;
  if (isA) {
    const int row = 16 * (warp & 6) + 8 * (warp & 1) + (lane & 16) + ((lane & 7) >> 1) + 4 * (lane & 1);
    uint32_t ab = bufa + row * 128 + ((((lane >> 3) & 1) ^ (row & 7)) << 4);
    const uint2* pr = scr->rec + (hd * 32 + warp) * 64 + lane;
    uint32_t a_cb = mapa(bar0 + 8 * B_HZ, (warp & 6) + (lane >> 4)), a_c = a_cb - (O_BAR + 8 * B_HZ - O_CTX) + (2 * rn + (warp & 1)) * 64 + tq * 16;
    uint32_t a_rl = sb + O_R + (32 * (warp & 1) + lane) * 16;
    uint32_t ao = bufo + (16 * warp + 8 * (lane >> 4) + (lane & 7)) * 128 + ((((lane >> 3) & 1) ^ (lane & 7)) << 4);
    uint32_t a_cx = sb + O_CTX + (warp >> 1) * 64 + tq * 16 + (warp & 1) * 8, a_ga = sb + O_SM + (320 + posof(tid & 63)) * 4;
    unsigned* p_ao = scr->xao + b * 64 + (tid & 63);
    unsigned* p_ab = scr->xab + cl * 256 + (2 * (rn & 3) + (warp & 1)) * 32 + (rn >> 2) * 16 + (lane >> 1);
    float xv = cl == 0 ? __bfloat162float(x[64 * rn + (tid & 63)]) : 0.f;
    unsigned p2 = lane >= 28 ? 0 : par;
    PIN(ab); PINL(pr); PIN(a_cb); PIN(a_c); PIN(a_rl); PIN(a_rs); PIN(ao); PIN(a_cx); PIN(a_ga); PINL(p_ao); PINL(p_ab); PIN(p2);
    asm volatile("" : "+f"(xv));
    uint32_t aw[4][4][4];
    auto wo = [&](const int j) {
      mbar_wait(fullb + 8 * j, phb);
#pragma unroll
      for (int mt = 0; mt < 4; mt++) ldsm_t(aw[j][mt], (ao + j * 16384) ^ (mt << 5));
    };
    {
      uint32_t a[4][4][4];
      uint2 z[4], y[4] = {};
      float d[4][4] = {}, r[8];
      mbar_wait(fulla, pha);
      POLL {
#pragma unroll
        for (int q = 0; q < 4; q++) z[q] = ldx8(pr + q * 512);
        RETRY(lop_x3(z[0].x, z[1].x, par) | lop_x3(z[2].x, z[3].x, par))
      }
#pragma unroll
      for (int q = 0; q < 4; q++) {
        if (q == 3) {
          mbar_wait(bar0 + 8 * B_G);
          if (lane < 28)
#pragma unroll
            for (int u = 0; u < 4; u++) y[u] = ldx8(pr + u * 512 + 32);
          __syncwarp();
        }
        mbar_wait(fulla + 8 * q, pha);
#pragma unroll
        for (int mt = 0; mt < 4; mt++) ldsm_t(a[q][mt], (ab + q * 16384) ^ (mt << 5));
#pragma unroll
        for (int mt = 0; mt < 4; mt++) mma16(d[mt], a[q][mt], z[q].x, z[q].y);
      }
      mbar_wait(bar0 + 8 * B_W);
      const float4 W = lds16(sb + O_SM + (384 + 4 * tq) * 4);
#pragma unroll
      for (int i = 0; i < 8; i++) { r[i] = W.x * d[i >> 1][2 * (i & 1)] + W.y * d[i >> 1][2 * (i & 1) + 1]; asm volatile("" : "+f"(r[i])); }
#pragma unroll
      for (int j = 0; j < NPE; j++) wo(j);
      POLL {
        if (it_)
#pragma unroll
          for (int u = 0; u < 4; u++) y[u] = ldx8(pr + u * 512 + 32);
#pragma unroll
        for (int mt = 0; mt < 4; mt++) d[mt][0] = d[mt][1] = d[mt][2] = d[mt][3] = 0.f;
#pragma unroll
        for (int q = 0; q < 4; q++)
#pragma unroll
          for (int mt = 0; mt < 4; mt++) mma16(d[mt], a[q][mt], y[q].x, y[q].y);
        RETRY(or3(lop_x3(y[0].x, y[1].x, p2), lop_x3(y[2].x, y[3].x, p2), 0))
      }
#pragma unroll
      for (int i = 0; i < 8; i++) r[i] = W.w * d[i >> 1][2 * (i & 1) + 1] + (W.z * d[i >> 1][2 * (i & 1)] + r[i]);
      tred<4>(r, lane, 2); tred<2>(r, lane, 1);
      sts4(a_rs, r[0]); sts4(a_rs + 128, r[1]);
      nbar(1, 256);
      send32(a_c, a_cb, sum8(a_rl), lane, lane & 12);
    }
    {
#pragma unroll
      for (int j = NPE; j < NPO; j++) wo(j);
      uint2 c[4];
      mbar_wait(bar0 + 8 * B_HZ);
#pragma unroll
      for (int j = 0; j < 4; j++) asm volatile("ld.shared.v2.u32 {%0, %1}, [%2];" : "=r"(c[j].x), "=r"(c[j].y) : "r"(a_cx + j * 256) : "memory");
      float d[4][4] = {};
#pragma unroll
      for (int j = 0; j < 4; j++) {
        if (j + 1 >= NPO && j < 3) wo(j + 1);
#pragma unroll
        for (int mt = 0; mt < 4; mt++) mma16(d[mt], aw[j][mt], c[j].x, c[j].y);
      }
      const float r0 = (tq & 2) ? ((tq & 1) ? d[3][0] : d[2][0]) : ((tq & 1) ? d[1][0] : d[0][0]);
      const float r1 = (tq & 2) ? ((tq & 1) ? d[3][2] : d[2][2]) : ((tq & 1) ? d[1][2] : d[0][2]);
      sts4(a_rs + 2048, r0); sts4(a_rs + 2048 + 128, r1);
      if (warp >= 2) nbar_arrive(2, 256);
      else {
        mbar_wait(bar0 + 8 * B_TAB);
        const float gav = lds4(a_ga);
        nbar(2, 256);
        const float t = gav * sum8(a_rl + 2048) + xv;
        asm volatile("{.reg .pred p; setp.eq.s32 p, %2, 0; @p red.relaxed.gpu.global.xor.b32 [%0], %1;}"
                     ::"l"(p_ab), "r"(pack2t(t, __shfl_down_sync(~0u, t, 1), par) | 1u), "r"(lane & 1) : "memory");
        pub4(p_ao, __float_as_uint(t) | 1u);
      }
    }
  } else {
    uint32_t af[4][4][4];
    uint32_t ab = bufa + (32 * warp + 8 * (lane >> 4) + (lane & 7)) * 64 + ((((lane >> 3) & 1) ^ ((lane >> 1) & 3)) << 4);
    uint32_t a_d = bufo + wg * 16384 + (8 * (lane >> 4) + (lane & 7)) * 128 + (((2 * (warp & 3) + ((lane >> 3) & 1)) ^ (lane & 7)) << 4);
    uint32_t a_rl = sb + O_R + lane * 16, a_st = sb + O_SM + (352 + 8 * (lane >> 4) + warp) * 4;
    const unsigned* pa = scr->xab + tid;
    uint32_t a_hb = mapa(bar0 + 8 * B_HZ, g), a_h = a_hb - (O_BAR + 8 * B_HZ - O_CTX) + rn * 64 + tq * 16;
    PIN(a_hb); PIN(a_h);
    uint32_t a_hl = sb + O_CTX + wg * 256 + tq * 16, a_t = sb + O_SM + (16 * warp + 8 * (tq & 1) + g) * 4;
    const unsigned* px = scr->xao + 64 * rn + 2 * lane;
    bf16* po = out + 64 * rn + 2 * lane;
    PIN(ab); PIN(a_d); PIN(a_rl); PINL(pa); PIN(a_rs); PIN(a_st); PINL(po); PIN(a_hl); PINL(px); PIN(a_t);
    mbar_wait(bar0 + 8 * B_TAB);
    uint2 cf;
    uint2 bb[4];
    uint2 gbw;
    POLL {
      unsigned bad = 0;
      cf = ldx8(scr->xm + 1024 + (lane & 16) * 16 + 32 * warp + posof(2 * (lane & 15)));
#pragma unroll
      for (int s = 0; s < 4; s++) {
        const uint4 w = ldx16(scr->xm + 1024 - (g & 1) * 512 + 256 * (s >> 1) + 32 * warp + 16 * (s & 1) + 4 * tq);
        bb[s] = make_uint2(__byte_perm(w.x, w.y, 0x7632), __byte_perm(w.z, w.w, 0x7632));
        bad = or3(bad, lop_x3(w.x, w.y, par), lop_x3(w.z, w.w, par));
      }
      gbw = ldx8(scr->xm + 1536 + 64 * rn + posof(2 * lane));
      RETRY(or3(bad, lop_x3(cf.x, cf.y, par), lop_x3(gbw.x, gbw.y, par)))
    }
    float e[4][4] = {};
    unsigned v[8];
    auto item = [&](const int it) {
      mbar_wait(fulla + 8 * it, pha);
#pragma unroll
      for (int i = 0; i < 4; i++) ldsm_t(af[it][i], (ab + it * 16384 + (i >> 1) * 1024) ^ ((i & 1) << 5));
    };
    auto item_mma = [&](const int it) {
#pragma unroll
      for (int i = 0; i < 4; i++) mma16(e[2 * (it & 1) + (i & 1)], af[it][i], bb[(it & 2) + (i >> 1)].x, bb[(it & 2) + (i >> 1)].y);
    };
    unsigned t3 = sch.wt;
    PIN(t3);
    item(0); item_mma(0); item(1); item_mma(1);
    mbar_wait(bar0 + 8 * B_G);
#pragma unroll
    for (int i = 0; i < 8; i++) v[i] = ldx4(pa + i * 256);
    t3 += clock();
    uint32_t have2, have3 = 0;
    do have2 = mbar_test(fulla + 16, pha); while (!have2 && (int)((unsigned)clock() - t3) < 0);
    if (have2) {
      item(2); item_mma(2);
      do have3 = mbar_test(fulla + 24, pha); while (!have3 && (int)((unsigned)clock() - t3) < 0);
      if (have3) { item(3); item_mma(3); }
    }
    float y0, y1, df[4][4], st[2];
    uint32_t bz[4][2] = {};
    auto mm = [&](const int it, const int i) { mma16(df[2 * (it & 1) + (i & 1)], af[it][i], bz[(it & 2) + (i >> 1)][0], bz[(it & 2) + (i >> 1)][1]); };
    POLL {
      if (it_)
#pragma unroll
        for (int i = 0; i < 8; i++) v[i] = ldx4(pa + i * 256);
      y0 = ((bflo(v[0]) + bflo(v[1])) + (bflo(v[2]) + bflo(v[3]))) + ((bflo(v[4]) + bflo(v[5])) + (bflo(v[6]) + bflo(v[7])));
      y1 = ((bfhi(v[0]) + bfhi(v[1])) + (bfhi(v[2]) + bfhi(v[3]))) + ((bfhi(v[4]) + bfhi(v[5])) + (bfhi(v[6]) + bfhi(v[7])));
      const uint32_t zb = pack2(y0 * u2f(cf.x), y1 * u2f(cf.y));
#pragma unroll
      for (int s = 0; s < 4; s++) {
        const uint32_t w = __shfl_sync(~0u, zb, 8 * s + (lane & 7));
        bz[s][0] = (lane & 4) ? 0u : w; bz[s][1] = (lane & 4) ? w : 0u;
      }
      st[0] = y0 + y1; st[1] = y0 * y0 + y1 * y1;
      tred<1>(st, lane, 16);
#pragma unroll
      for (int i = 0; i < 4; i++) df[i][0] = df[i][1] = df[i][2] = df[i][3] = 0.f;
      mm(0, 0); mm(0, 1); mm(1, 0); mm(1, 1);
      st[0] += shx(st[0], 8);
      mm(0, 2); mm(0, 3); mm(1, 2); mm(1, 3);
      RETRY(or3(or3(lop_x3(v[0], v[1], par), lop_x3(v[2], v[3], par), lop_x3(v[4], v[5], par)), lop_x3(v[6], v[7], par), 0))
    }
    uint2 xq[8];
    if (warp == 0)
#pragma unroll
      for (int i = 0; i < 8; i++) xq[i] = ldx8(px + i * 512);
    if (have2) { mm(2, 0); mm(2, 1); mm(2, 2); mm(2, 3); }
    st[0] += shx(st[0], 4);
    st[0] += shx(st[0], 2);
    st[0] += shx(st[0], 1);
    sts4(a_st, st[0]);
    __syncwarp();
    arrive_n(bar0 + 8 * B_ST, lane == 0, 1);
    if (!have2) { item(2); item_mma(2); mm(2, 0); mm(2, 1); mm(2, 2); mm(2, 3); }
    if (!have3) { item(3); item_mma(3); }
    mm(3, 0); mm(3, 1); mm(3, 2); mm(3, 3);
    mbar_wait(bar0 + 8 * B_ST);
    float mean, rstd;
    {
      float4 u[4];
#pragma unroll
      for (int i = 0; i < 4; i++) u[i] = lds16(sb + O_SM + (352 + 4 * i) * 4);
      mean = (((u[0].x + u[0].y) + (u[0].z + u[0].w)) + ((u[1].x + u[1].y) + (u[1].z + u[1].w))) * (1.f / 512.f);
      const float sq = (((u[2].x + u[2].y) + (u[2].z + u[2].w)) + ((u[3].x + u[3].y) + (u[3].z + u[3].w))) * (1.f / 512.f);
      asm("rsqrt.approx.ftz.f32 %0, %1;" : "=f"(rstd) : "f"(fmaxf(sq - mean * mean, 0.f) + 1e-5f));
    }
    float A[4], r[4];
#pragma unroll
    for (int i = 0; i < 4; i++) {
      A[i] = (tq & 2) ? ((tq & 1) ? e[3][i] : e[2][i]) : ((tq & 1) ? e[1][i] : e[0][i]);
      r[i] = (tq & 2) ? ((tq & 1) ? df[3][i] : df[2][i]) : ((tq & 1) ? df[1][i] : df[0][i]);
    }
    sts4(a_rs, rstd * (r[0] + r[1]) + (A[1] - rstd * mean * A[0])); sts4(a_rs + 128, rstd * (r[2] + r[3]) + (A[3] - rstd * mean * A[2]));
    nbar(1, 256);
    if (warp == 7) {
      const float4 g0 = lds16(a_rl), g1 = lds16(a_rl + 1024), u0 = lds16(a_rl + 512), u1 = lds16(a_rl + 1536);
      const float gg = ((g0.x + g0.y) + (g0.z + g0.w)) + ((g1.x + g1.y) + (g1.z + g1.w));
      const float uu = ((u0.x + u0.y) + (u0.z + u0.w)) + ((u1.x + u1.y) + (u1.z + u1.w));
      const float hh = (gg * uu) * rcp(1.f + ex2(gg * (-2.302208198f - 0.1029432397f * gg * gg)));
      send32(a_h, a_hb, hh, lane, 0);
    } else spin_until(clock() + FDLY);
    uint32_t ad[8][4];
    mbar_wait(fullb + 8 * wg, phb);
#pragma unroll
    for (int i = 0; i < 8; i++) ldsm_t(ad[i], a_d + i * 2048);
    float x0, x1;
    if (warp == 0) {
      POLL {
        if (it_)
#pragma unroll
          for (int i = 0; i < 8; i++) xq[i] = ldx8(px + i * 512);
        unsigned bad = 0;
#pragma unroll
        for (int i = 0; i < 4; i++) bad = or3(bad, lop_x3(xq[i].x, xq[i].y, par), lop_x3(xq[i + 4].x, xq[i + 4].y, par));
        RETRY(bad)
      }
      x0 = x1 = 0.f;
#pragma unroll
      for (int i = 0; i < 8; i++) { x0 += u2f(xq[i].x); x1 += u2f(xq[i].y); }
      x0 *= 1.f / 7.f; x1 *= 1.f / 7.f;
    }
    mbar_wait(bar0 + 8 * B_HZ);
    float dd[4][4] = {};
#pragma unroll
    for (int i = 0; i < 4; i++) {
      const float4 hb = lds16(a_hl + i * 64);
      mma16(dd[(2 * i) & 3], ad[2 * i], __float_as_uint(hb.x), __float_as_uint(hb.y));
      mma16(dd[(2 * i + 1) & 3], ad[2 * i + 1], __float_as_uint(hb.z), __float_as_uint(hb.w));
    }
    sts4(a_t, (tq & 1) ? (dd[0][2] + dd[1][2]) + (dd[2][2] + dd[3][2]) : (dd[0][0] + dd[1][0]) + (dd[2][0] + dd[3][0]));
    if (warp) nbar_arrive(2, 256);
    else {
      nbar(2, 256);
      float t0, t1, t2, t3b;
      asm volatile("ld.shared.v2.f32 {%0, %1}, [%4]; ld.shared.v2.f32 {%2, %3}, [%4 + 256];"
                   : "=f"(t0), "=f"(t1), "=f"(t2), "=f"(t3b) : "r"(sb + O_SM + lane * 8) : "memory");
      t0 = bfhi(gbw.x) * (t0 + t2) + x0; t1 = bfhi(gbw.y) * (t1 + t3b) + x1;
      asm volatile("red.relaxed.gpu.global.add.noftz.bf16x2 [%0], %1;" ::"l"(po), "r"(pack2(t0, t1)) : "memory");
      if (f == 0 && tid == 0) stx4(&scr->cnt[0], epoch + 1);
    }
  }
}

static void make_sched(Sched& s) {
  const char* order = "FFAAbcFmmvog..d";
  const double dt = 4985 * 1e-3, dth = 4660 * 1e-3;
  const int nbig = NBIG;
  s.zero = 0; s.dth = (unsigned)(dth * 256 + 0.5);
  double t = 512 * dth + 0;
  int tile = 0, jm = 0;
  for (int i = 0; i < 3; i++) s.nr[i] = s.nt[i] = 0;
  auto add = [&](int c, int type, double step, int win, int b0, int tl) {
    s.r[c][s.nr[c]++] = make_uint2((unsigned)(t + 0.5) | (unsigned)(step + 0.5) << 16, type | win << 4 | (b0 + 64) << 8 | tl << 16);
    if (type == T_KV) s.nt[c]++;
  };
  const int w1 = 6, w2 = 4, wt = 6;
  for (const char* p = order; *p; p++) {
    const char c = *p;
    if (c == 'v' || c == 'o' || c == 'm') {
      const int ty = c == 'v' ? T_UV : c == 'o' ? T_WO : T_MOD;
      const double d = (c == 'm' ? 6000 : c == 'v' ? 5500 : 5500) * 1e-3;
      add(0, ty, 64 * d, wt, 0, c == 'm' ? jm : 0); add(1, ty, 64 * d, wt, 0, c == 'm' ? jm : 0);
      t += (c == 'm' ? 64 : 256) * d; jm += c == 'm';
    } else if (c == 'g' || c == 'd') {
      const double d = (c == 'g' ? 5500 : 5000) * 1e-3;
      add(2, c == 'g' ? T_GU : T_DN, 56 * d, wt, 64, 0);
      t += (c == 'g' ? 224 : 112) * d;
    } else if (c == '.') t += 100;
    else if (c == '-') t -= 100;
    else {
      const int na = c == 'F' ? 0 : c == 'C' || c == 'c' || c == 'a' ? nbig : 64, nf = c == 'A' || c == 'a' ? 0 : 56, n = na + nf;
      const int w = na && nf ? w2 : w1;
      const bool ff = c == 'b' || c == 'c';
      const int cf = c == 'c' ? 20 : 0, ca = cf * 7 / 5;
      t += 3 * ca;
      if (na) add(0, T_KV, n * dt - ca, w, ff ? -56 : 0, tile);
      t -= 3 * ca;
      if (na == 64) add(1, T_KV, n * dt, w, ff ? -56 : 0, tile);
      if (nf) add(2, T_KV, n * dt - cf, w, ff ? 64 : 64 - na, tile);
      tile += n; t += 4 * n * dt;
      s.t4 = (unsigned)t + 600;
    }
  }
  s.dt = (unsigned)(dt * 256 + 0.5); s.d4 = 1560 | 1200 << 16; s.d6 = 3160; s.wt = 250;
}

static void launch(void* const* d_in, void* d_out) {
  static TMaps tms;
  static Sched sch;
  static bool init = false;
  static void* scr = nullptr;
  if (!init) {
    void* fn = nullptr; cudaDriverEntryPointQueryResult qr;
    cudaGetDriverEntryPoint("cuTensorMapEncodeTiled", &fn, cudaEnableDefault, &qr);
    EncFn f = (EncFn)fn;
    const CUtensorMapSwizzle S64 = CU_TENSOR_MAP_SWIZZLE_64B, S128 = CU_TENSOR_MAP_SWIZZLE_128B;
    const CUtensorMapL2promotion P256 = CU_TENSOR_MAP_L2_PROMOTION_L2_256B;
    enc3d(f, &tms.m[0], d_in[2], 64, 512, 64, 8192, 128, 64, 128, 1, S128, CU_TENSOR_MAP_L2_PROMOTION_L2_128B);
    enc3d(f, &tms.m[1], d_in[3], 64, 512, 64, 8192, 128, 64, 64, 2, S128, P256);
    enc3d(f, &tms.m[2], d_in[1], 64, SK, 8, 1024, 128, 64, 64, 2, S128, P256);
    enc3d(f, &tms.m[3], d_in[11], 3072, 256, 2, 6144, 256 * 6144, 32, 256, 1, S64, CU_TENSOR_MAP_L2_PROMOTION_L2_128B);
    enc3d(f, &tms.m[4], d_in[4], 64, 512, 64, 8192, 128, 64, 128, 1, S128, CU_TENSOR_MAP_L2_PROMOTION_L2_128B);
    enc3d(f, &tms.m[5], d_in[5], 512, 128, 32, 1024, 128 * 1024, 64, 128, 1, S128, CU_TENSOR_MAP_L2_PROMOTION_L2_128B);
    enc3d(f, &tms.m[6], d_in[7], 1792, 256, 2, 3584, 256 * 3584, 32, 256, 1, S64, CU_TENSOR_MAP_L2_PROMOTION_L2_128B);
    enc3d(f, &tms.m[7], d_in[8], 1792, 256, 2, 3584, 256 * 3584, 32, 256, 1, S64, CU_TENSOR_MAP_L2_PROMOTION_L2_128B);
    enc3d(f, &tms.m[8], d_in[9], 512, 128, 14, 1024, 128 * 1024, 64, 128, 1, S128, CU_TENSOR_MAP_L2_PROMOTION_L2_128B);
    cudaFuncSetAttribute(fused_kernel, cudaFuncAttributeMaxDynamicSharedMemorySize, SMEM9);
    cudaGetSymbolAddress(&scr, g_scr);
    make_sched(sch);
    init = true;
  }
  fused_kernel<<<NCTA9, 384, SMEM9>>>((const bf16*)d_in[0], (const bf16*)d_in[10], (const bf16*)d_in[11], (bf16*)d_out, (Scratch*)scr, sch, tms);
}

static bool fits() {
  cudaFuncSetAttribute(fused_kernel, cudaFuncAttributeMaxDynamicSharedMemorySize, SMEM9);
  cudaLaunchConfig_t cfg = {};
  cfg.gridDim = dim3(NCTA9); cfg.blockDim = dim3(384); cfg.dynamicSmemBytes = SMEM9;
  cudaLaunchAttribute at[1];
  at[0].id = cudaLaunchAttributeClusterDimension; at[0].val.clusterDim.x = 8; at[0].val.clusterDim.y = 1; at[0].val.clusterDim.z = 1;
  cfg.attrs = at; cfg.numAttrs = 1;
  int n = 0;
  if (cudaOccupancyMaxActiveClusters(&n, fused_kernel, &cfg) != cudaSuccess) { (void)cudaGetLastError(); return false; }
  return n >= NCTA9 / 8;
}
}
#undef BAR_ARM
#undef BAR_ARRIVE
#undef BAR_INIT
#undef B_EMPTY
#undef B_FM
#undef B_FULL
#undef B_G
#undef B_G2
#undef B_H
#undef B_HZ
#undef B_LZ
#undef B_Q2
#undef B_QF
#undef B_ST
#undef B_TAB
#undef B_W
#undef B_WZ
#undef CNT_ADD
#undef DSC
#undef FDLY
#undef HI128
#undef HI64
#undef LANE0
#undef NBIG
#undef NCTA9
#undef NPE
#undef NPO
#undef NSL
#undef O_B
#undef O_BAR
#undef O_CTX
#undef O_DBG
#undef O_EP
#undef O_HW
#undef O_HZ
#undef O_LZ
#undef O_P
#undef O_Q
#undef O_R
#undef O_SILU
#undef O_SM
#undef O_X
#undef PIN
#undef PINL
#undef POLL
#undef QN
#undef RETRY
#undef SK
#undef SMEM9
#undef SMEM_BASE
#undef SPIN_MAX
#undef TAU
#undef VDLY
#undef VJ
#undef X16
#undef fbits

namespace v8 {
typedef __nv_bfloat16 bf16;
#define NCTA 128
#define SK 32768
#define SLOT 32768
#define NSLOT 6
#define OFF_WQ (2 * SLOT)
#define OFF_WUK (4 * SLOT)
#define OFF_Q 196608
#define OFF_P (OFF_Q + 16384)
#define OFF_B (OFF_P + 4096)
#define OFF_R4 (OFF_B + 2304)
#define OFF_SILU (OFF_R4 + 4096)
#define OFF_RA (OFF_SILU + 1024)
#define OFF_SM (OFF_RA + 1024)
#define OFF_BP (OFF_SM + 1792)
#define OFF_CO (OFF_BP + 1024)
#define OFF_BAR (OFF_CO + 1280)
#define OFF_MASK (OFF_BAR + 512)
#define OFF_DBG (OFF_MASK + 16)
#define SMEM_BYTES (OFF_DBG + 128)
#define OFF_MOD OFF_Q
#define OFF_UV (4 * SLOT)
#define OFF_O (5 * SLOT)
#define OFF_G 0
#define OFF_U 16384
#define OFF_D SLOT
#define OFF_XO (OFF_D + 16384)
#define FB_UK 4
#define FB_KV 6
#define FB_MOD 22
#define FB_UV 23
#define FB_O 25
#define FB_G 27
#define FB_D 29
#define EB 30
#define QB 50
#define XB 51
#define SPIN_MAX (1 << 20)
#define BACKOFF 40
#define RATE_NS 652
#define RATE_T0 200
#define RATE_TL 300
#define WINS 0x3222333
#define KVWIN 4
#define RATE_H 650
#define RATE_E 650
#define SMUL 9
#define NPRE0 1
#define NPRE1 3
#define HWIN 4
#define EWIN 3
#define WTEST 450
#define DLY5 650
#define DLY6 600
#define DLY7 600
#define P12(a, b, c, d, e, f, g, h, i, j, k, l) ((unsigned long long)(a) | (b) << 5 | (c) << 10 | (d) << 15 | (e) << 20 | (f) << 25 | \
  (unsigned long long)(g) << 30 | (unsigned long long)(h) << 35 | (unsigned long long)(i) << 40 | (unsigned long long)(j) << 45 | \
  (unsigned long long)(k) << 50 | (unsigned long long)(l) << 55)
#define ORDER0 P12(0, 1, 2, 3, 4, 5, 16, 6, 7, 8, 9, 10)
#define ORDER1 P12(11, 12, 13, 14, 15, 17, 18, 19, 20, 23, 21, 22)
#define TAIL_K 17
#define RS 16
template <int N> struct IC { static constexpr int value = N; };
struct TMaps { CUtensorMap m[9]; };

struct __align__(128) Scratch {
  uint4 xo[128 * 64 * RS];
  uint2 ml[32 * 64];
  unsigned h[8 * 256];
  unsigned qa[32 * 256];
  unsigned xc[128 * 64];
  unsigned xao[8 * 512];
  unsigned xf[112 * 512];
  unsigned xm[2048];
  unsigned cnt[5 * 32];
};
__device__ Scratch g_scr;
#define g_xo scr->xo
#define g_ml scr->ml
#define g_h scr->h
#define g_qa scr->qa
#define g_xc scr->xc
#define g_xao scr->xao
#define g_xf scr->xf
#define g_xm scr->xm
#define g_epoch scr->cnt[0]

__device__ __forceinline__ uint32_t s2u(const void* p) { return (uint32_t)__cvta_generic_to_shared(p); }
__device__ __forceinline__ float bflo(uint32_t u) { return __uint_as_float(u << 16); }
__device__ __forceinline__ float bfhi(uint32_t u) { return __uint_as_float(u & 0xffff0000u); }
__device__ __forceinline__ float u2f(uint32_t u) { return __uint_as_float(u); }
__device__ __forceinline__ void fma8(float* acc, uint4 v, float s) {
  acc[0] += s * bflo(v.x); acc[1] += s * bfhi(v.x); acc[2] += s * bflo(v.y); acc[3] += s * bfhi(v.y);
  acc[4] += s * bflo(v.z); acc[5] += s * bfhi(v.z); acc[6] += s * bflo(v.w); acc[7] += s * bfhi(v.w);
}
__device__ __forceinline__ uint32_t pack2(float a, float b) {
  __nv_bfloat162 p = __floats2bfloat162_rn(a, b); return *(uint32_t*)&p;
}
__device__ __forceinline__ float bfr(float v) { return bfhi(pack2(v, v)); }
__device__ __forceinline__ float silu_bf(float c) { return bfr(__fdividef(c, 1.f + __expf(-c))); }
#define fbits(v) ((__float_as_uint(v) & ~1u) | par)
__device__ __forceinline__ uint32_t pack2t(float a, float b, unsigned par) {
  const uint32_t ua = ((__float_as_uint(a) + ((par ^ 1) << 16)) & 0xFFFE0000u) | (par << 16);
  return __byte_perm(ua, pack2(b, b), 0x7632);
}
__device__ __forceinline__ void nbar(int id, int n) { asm volatile("bar.sync %0, %1;" ::"r"(id), "r"(n) : "memory"); }
__device__ __forceinline__ void nbar_arrive(int id, int n) { asm volatile("bar.arrive %0, %1;" ::"r"(id), "r"(n) : "memory"); }
__device__ __forceinline__ uint4 ldc16(const void* p) {
  uint4 v; asm volatile("ld.relaxed.cta.global.v4.u32 {%0,%1,%2,%3}, [%4];" : "=r"(v.x), "=r"(v.y), "=r"(v.z), "=r"(v.w) : "l"(p) : "memory"); return v;
}
__device__ __forceinline__ unsigned ldc4(const void* p) {
  unsigned v; asm volatile("ld.relaxed.cta.global.u32 %0, [%1];" : "=r"(v) : "l"(p) : "memory"); return v;
}
__device__ __forceinline__ uint4 ldx16(const void* p) {
  uint4 v; asm volatile("ld.relaxed.gpu.global.v4.u32 {%0,%1,%2,%3}, [%4];" : "=r"(v.x), "=r"(v.y), "=r"(v.z), "=r"(v.w) : "l"(p) : "memory"); return v;
}
__device__ __forceinline__ unsigned ldx4(const void* p) {
  unsigned v; asm volatile("ld.relaxed.gpu.global.u32 %0, [%1];" : "=r"(v) : "l"(p) : "memory"); return v;
}
__device__ __forceinline__ unsigned long long ldx64(const void* p) {
  unsigned long long v; asm volatile("ld.relaxed.gpu.global.u64 %0, [%1];" : "=l"(v) : "l"(p) : "memory"); return v;
}
__device__ __forceinline__ void stx16(void* p, uint4 v) {
  asm volatile("st.relaxed.gpu.global.v4.u32 [%0], {%1,%2,%3,%4};" ::"l"(p), "r"(v.x), "r"(v.y), "r"(v.z), "r"(v.w) : "memory");
}
__device__ __forceinline__ void stx8(void* p, uint2 v) { asm volatile("st.relaxed.gpu.global.v2.u32 [%0], {%1,%2};" ::"l"(p), "r"(v.x), "r"(v.y) : "memory"); }
__device__ __forceinline__ void stx4(void* p, unsigned v) { asm volatile("st.relaxed.gpu.global.u32 [%0], %1;" ::"l"(p), "r"(v) : "memory"); }
__device__ __forceinline__ unsigned lop_x3(unsigned a, unsigned b, unsigned c) {
  unsigned d; asm("lop3.b32 %0, %1, %2, %3, 0x7E;" : "=r"(d) : "r"(a), "r"(b), "r"(c)); return d; }
#define X16(v) (lop_x3(v.x, v.y, par) | lop_x3(v.z, v.w, par))
#define X8(v) lop_x3(v.x, v.y, par)
#define RETRY(bad) if (!__any_sync(~0u, (bad) & 1) || ++it_ >= SPIN_MAX) break; __nanosleep(BACKOFF);
#define POLL _Pragma("unroll 1") for (int it_ = 0;;)
__device__ __forceinline__ void mbar_wait(uint32_t bar) {
  uint32_t ok; int it = 0;
  do {
    asm volatile("{.reg .pred p; mbarrier.try_wait.parity.shared::cta.b64 p, [%1], 0; selp.u32 %0,1,0,p;}"
                 : "=r"(ok) : "r"(bar) : "memory");
  } while (!ok && ++it < SPIN_MAX);
}
__device__ __forceinline__ float ex2(float v) { float r; asm("ex2.approx.ftz.f32 %0, %1;" : "=f"(r) : "f"(v)); return r; }
__device__ __forceinline__ float rcp(float v) { float r; asm("rcp.approx.ftz.f32 %0, %1;" : "=f"(r) : "f"(v)); return r; }
__device__ __forceinline__ void mma16(float* d, const uint32_t* a, uint32_t b0, uint32_t b1) {
  asm volatile("mma.sync.aligned.m16n8k16.row.col.f32.bf16.bf16.f32 {%0,%1,%2,%3}, {%4,%5,%6,%7}, {%8,%9}, {%0,%1,%2,%3};"
               : "+f"(d[0]), "+f"(d[1]), "+f"(d[2]), "+f"(d[3]) : "r"(a[0]), "r"(a[1]), "r"(a[2]), "r"(a[3]), "r"(b0), "r"(b1));
}
__device__ __forceinline__ float4 lds16(uint32_t a) {
  float4 v; asm volatile("ld.shared.v4.f32 {%0,%1,%2,%3}, [%4];" : "=f"(v.x), "=f"(v.y), "=f"(v.z), "=f"(v.w) : "r"(a) : "memory"); return v;
}
__device__ __forceinline__ void ldsm_t(uint32_t* r, uint32_t a) {
  asm volatile("ldmatrix.sync.aligned.m8n8.x4.trans.shared.b16 {%0,%1,%2,%3}, [%4];" : "=r"(r[0]), "=r"(r[1]), "=r"(r[2]), "=r"(r[3]) : "r"(a) : "memory");
}
__device__ __forceinline__ void ldsm(uint32_t* r, uint32_t a) {
  asm volatile("ldmatrix.sync.aligned.m8n8.x4.shared.b16 {%0,%1,%2,%3}, [%4];" : "=r"(r[0]), "=r"(r[1]), "=r"(r[2]), "=r"(r[3]) : "r"(a) : "memory");
}
template <int N>
__device__ __forceinline__ void tred(float* a, int lane, int m) {
  const bool hi = lane & m;
#pragma unroll
  for (int i = 0; i < N; i++) {
    float send = hi ? a[i] : a[i + N], keep = hi ? a[i + N] : a[i];
    a[i] = keep + __shfl_xor_sync(~0u, send, m);
  }
}
template <int N>
__device__ __forceinline__ void tmax(float* a, int lane, int m) {
  const bool hi = lane & m;
#pragma unroll
  for (int i = 0; i < N; i++) {
    float send = hi ? a[i] : a[i + N], keep = hi ? a[i + N] : a[i];
    a[i] = fmaxf(keep, __shfl_xor_sync(~0u, send, m));
  }
}
__device__ __forceinline__ void arrive2(uint32_t bar, uint32_t rbar, bool local, bool remote) {
  asm volatile("{.reg .pred p, q; setp.ne.s32 p, %2, 0; setp.ne.s32 q, %3, 0; @p mbarrier.arrive.shared::cta.b64 _, [%0];\n"
               "@q mbarrier.arrive.relaxed.cluster.shared::cluster.b64 _, [%1];}" ::"r"(bar), "r"(rbar), "r"((int)local), "r"((int)remote) : "memory");
}
__device__ __forceinline__ unsigned long long stream_policy() {
  unsigned long long p;
  asm volatile("createpolicy.fractional.L2::evict_first.b64 %0, 1.0;" : "=l"(p));
  return p;
}
__device__ __forceinline__ void tma3d(uint32_t dst, const CUtensorMap* tm, uint32_t bar, int c0, int c1, int c2) {
  asm volatile("cp.async.bulk.tensor.3d.shared::cluster.global.mbarrier::complete_tx::bytes.L2::cache_hint [%0], [%1, {%3, %4, %5}], [%2], %6;"
               ::"r"(dst), "l"(tm), "r"(bar), "r"(c0), "r"(c1), "r"(c2), "l"(stream_policy()) : "memory");
}
__device__ __forceinline__ void st_async2(uint32_t dst, uint32_t bar, float v0, float v1) {
  asm volatile("st.async.shared::cluster.mbarrier::complete_tx::bytes.v2.f32 [%0], {%1, %2}, [%3];" ::"r"(dst), "f"(v0), "f"(v1), "r"(bar) : "memory");
}
__device__ __forceinline__ void st_pair(int mode, uint32_t dst, uint32_t bar, float v0, float v1) {
  asm volatile("{.reg .pred p, q; setp.eq.s32 p, %4, 1; setp.eq.s32 q, %4, 2; @p st.shared.v2.f32 [%0], {%1, %2};\n"
               "@q st.async.shared::cluster.mbarrier::complete_tx::bytes.v2.f32 [%0], {%1, %2}, [%3];}"
               ::"r"(dst), "f"(v0), "f"(v1), "r"(bar), "r"(mode) : "memory");
}
__device__ __forceinline__ void spin_until(unsigned t) { while ((int)((unsigned)clock() - t) < 0) {} }
__device__ __forceinline__ unsigned wait_until(unsigned t) {
  unsigned now;
  for (;;) {
    asm volatile("mov.u32 %0, %%globaltimer_lo;" : "=r"(now));
    if ((int)(now - t) >= 0) break;
  }
  return now;
}
#define PIN(x) asm volatile("" : "+r"(x))
#define PINL(x) asm volatile("" : "+l"(x))
#define BAR_ARRIVE(i) asm volatile("mbarrier.arrive.shared::cta.b64 _, [%0];" ::"r"(bar0 + 8 * (i)) : "memory")
#define CNT_ADD(c) asm volatile("red.relaxed.gpu.global.add.u32 [%0], 1;" ::"l"(scr->cnt + (c)) : "memory")
#define BAR_INIT(i, cnt) asm volatile("mbarrier.init.shared::cta.b64 [%0], %1;" ::"r"(bar0 + 8 * (i)), "r"(cnt) : "memory")
#define BAR_ARM(i, bytes) asm volatile("mbarrier.arrive.expect_tx.shared::cta.b64 _, [%0], %1;" ::"r"(bar0 + 8 * (i)), "r"(bytes) : "memory")

__device__ __forceinline__ void tail(unsigned char* smem, Scratch* __restrict__ scr, const bf16* __restrict__ x, bf16* __restrict__ out,
                                     const unsigned par, const unsigned epoch, const int warp) {
  int tid, b;
  asm volatile("mov.u32 %0, %%tid.x;" : "=r"(tid));
  asm volatile("mov.u32 %0, %%ctaid.x;" : "=r"(b));
  const int lane = tid & 31, g = lane >> 2, tq = lane & 3;
  const uint32_t sb = __shfl_sync(~0u, s2u(smem), 0), bar0 = sb + OFF_BAR;
  float* s_sm = (float*)(smem + OFF_SM);
  const int prow = 4 * (lane >> 4) + ((lane & 7) >> 1) + 8 * (lane & 1);
  const float* s_co = (const float*)(smem + OFF_CO);
  const int opos = (b & 15) * 32 + (lane & 16) + 2 * (lane & 6) + ((lane >> 2) & 2) + (lane & 1);
  const float xv = b < 16 ? __bfloat162float(x[(b & 15) * 32 + lane]) : 0.f;
  const int rk = b & 1, ob = 32 * rk + ((b >> 1) & 31);
  uint32_t psb;
  asm volatile("mapa.shared::cluster.u32 %0, %1, %2;" : "=r"(psb) : "r"(sb), "r"(rk ^ 1));
  {
    uint32_t a[8][4];
    {
      const int rg = tid >> 4;
      const uint4* src = g_xo + ((size_t)b * 64 + rg) * RS;
      const uint32_t dst = sb + OFF_XO + rg * 256 + (((tid & 15) ^ (rg & 7)) << 4);
      unsigned long long todo = 0x0001000100010001ull;
#pragma unroll 1
      for (int it = 0; it < SPIN_MAX * 16; it++) {
        unsigned long long mk = *(volatile unsigned long long*)(smem + OFF_MASK);
        const unsigned long long nw = (mk >> rg) & todo;
        todo ^= nw;
#pragma unroll
        for (int i = 0; i < 4; i++)
          if (nw >> (16 * i) & 1)
            asm volatile("cp.async.cg.shared.global [%0], [%1], 16;" ::"r"(dst + i * 4096), "l"(src + i * 16 * RS + (tid & 15)) : "memory");
        if (!__any_sync(~0u, todo != 0)) break;
      }
      asm volatile("cp.async.mbarrier.arrive.noinc.shared::cta.b64 [%0];" ::"r"(bar0 + 8 * (XB + 2)) : "memory");
    }
    mbar_wait(bar0 + 8 * FB_UV); mbar_wait(bar0 + 8 * (FB_UV + 1));
    const uint32_t ab = sb + OFF_UV + (warp >> 2) * 8192 + (8 * (lane >> 4) + (lane & 7)) * 128 + (((2 * (warp & 3) + ((lane >> 3) & 1)) ^ (lane & 7)) << 4);
#pragma unroll
    for (int s = 0; s < 8; s++) ldsm_t(a[s], ab + (s >> 2) * 16384 + (s & 3) * 2048);
    const int chn = 2 * warp + (tq & 1);
    uint32_t a_b = sb + OFF_B + (tq >> 1) * 272 + (32 * (chn >> 2) + 8 * (g >> 1) + 2 * (chn & 3) + (g & 1)) * 2;
    uint32_t a_bq = sb + OFF_B + (lane & 1) * 272 + (lane >> 3) * 16;
    unsigned* p_c = g_xc + (b >> 2) * 256 + warp * 32 + (b & 3) * 8 + (g & 3) * 2 + (g >> 2);
    PIN(a_b); PIN(a_bq); PINL(p_c);
    mbar_wait(bar0 + 8 * (XB + 6));
    uint32_t wb[8];
#pragma unroll
    for (int s = 0; s < 8; s++) wb[s] = *(const uint32_t*)(smem + OFF_RA + (4 * s + tq) * 4);
    const float invL = *(const float*)(smem + OFF_RA + 128);
    float ov;
    POLL {
      mbar_wait(bar0 + 8 * (XB + 2));
      uint32_t ao[4][4];
#pragma unroll
      for (int s = 0; s < 4; s++)
        ldsm_t(ao[s], sb + OFF_XO + (16 * s + 8 * (lane >> 4) + (lane & 7)) * 256 + (((2 * warp + ((lane >> 3) & 1)) ^ (lane & 7)) << 4));
      float d[4][4] = {};
#pragma unroll
      for (int s = 0; s < 4; s++) mma16(d[s], ao[s], wb[2 * s], wb[2 * s + 1]);
      const unsigned p2 = par * 0x10001u;
      unsigned bad = 0;
#pragma unroll
      for (int s = 0; s < 4; s++) bad |= lop_x3(ao[s][0], ao[s][1], p2) | lop_x3(ao[s][2], ao[s][3], p2);
      bad = g == 0 ? bad | (bad >> 16) : 0u;
      ov = (tq & 1) ? (d[0][2] + d[1][2]) + (d[2][2] + d[3][2]) : (d[0][0] + d[1][0]) + (d[2][0] + d[3][0]);
      if (__builtin_expect(!__any_sync(~0u, bad & 1) || ++it_ >= SPIN_MAX, 1)) break;
#pragma unroll
      for (int i = 0; i < 4; i++)
        asm volatile("cp.async.cg.shared.global [%0], [%1], 16;"
                     ::"r"(sb + OFF_XO + ((lane >> 1) + 16 * i) * 256 + (((2 * warp + (lane & 1)) ^ ((lane >> 1) & 7)) << 4)),
                       "l"(g_xo + ((size_t)b * 64 + (lane >> 1) + 16 * i) * RS + 2 * warp + (lane & 1)) : "memory");
      asm volatile("cp.async.wait_all;" ::: "memory");
      __syncwarp();
    }
    {
      const float lo = ov - bfhi(__float_as_uint(ov));
      asm volatile("st.shared.u16 [%0], %1;" ::"r"(a_b), "h"((unsigned short)((tq & 2) ? pack2(lo, lo) : __float_as_uint(ov) >> 16)) : "memory");
    }
    nbar(1, 256);
    float d[4][4] = {};
#pragma unroll
    for (int y = 0; y < 4; y++) {
      uint32_t bq[4];
      ldsm(bq, a_bq + 64 * y);
      mma16(d[(2 * y) & 3], a[2 * y], bq[0], bq[1]); mma16(d[(2 * y + 1) & 3], a[2 * y + 1], bq[2], bq[3]);
    }
    const float r0 = ((d[0][0] + d[0][1]) + (d[1][0] + d[1][1])) + ((d[2][0] + d[2][1]) + (d[3][0] + d[3][1]));
    const float r1 = ((d[0][2] + d[0][3]) + (d[1][2] + d[1][3])) + ((d[2][2] + d[2][3]) + (d[3][2] + d[3][3]));
    if (tq == 0) stx4(p_c, pack2t(r0 * invL, r1 * invL, par));
  }
  unsigned tpub = clock();
  mbar_wait(bar0 + 8 * (XB + 4));
  const float gav = s_co[256 + (opos & 31)];
  const float gbv = s_co[288 + (lane & 4) + 2 * (lane & 1) + ((lane >> 1) & 1)];
  float4 cf[2];
#pragma unroll
  for (int s = 0; s < 2; s++) cf[s] = *(const float4*)(s_co + 32 * warp + 16 * s + 4 * tq);
  {
    uint32_t a[2][4][4];
    mbar_wait(bar0 + 8 * (FB_O + (warp >> 2)));
    const uint32_t ab = sb + OFF_O + (32 * warp + prow) * 128 + ((((lane >> 3) & 1) ^ (prow & 7)) << 4);
#pragma unroll
    for (int i = 0; i < 8; i++) ldsm_t(a[i >> 2][i & 3], (ab + (i >> 2) * 2048) ^ ((i & 3) << 5));
    uint4 v;
    const unsigned* pc = g_xc + (4 * (b >> 4) + 2 * rk + (warp >> 2)) * 256 + 64 * (warp & 3) + 2 * lane;
    uint32_t ro = ((tq >> 1) == rk ? sb : psb) + OFF_P + (8 * (tq & 1) + g) * 144 + (8 * rk + warp) * 8;
    uint32_t a_q = sb + OFF_P + (8 * (lane >> 4) + (lane & 7)) * 144;
    unsigned* p_ao = g_xao + (b >> 5) * 1024 + (opos >> 4) * 32 + (b & 16) + (opos & 15);
    PIN(ro); PIN(a_q); PINL(p_ao); PINL(pc);
    spin_until(tpub + DLY5);
    POLL {
      const unsigned long long u0 = ldx64(pc);
      v.x = (unsigned)u0; v.y = u0 >> 32;
      RETRY(X8(v))
    }
    v.z = lane & 16 ? v.x : 0u; v.w = lane & 16 ? v.y : 0u;
    if (lane & 16) v.x = v.y = 0u;
    float d[4][4] = {};
#pragma unroll
    for (int mt = 0; mt < 4; mt++) mma16(d[mt], a[0][mt], v.x, v.y);
#pragma unroll
    for (int mt = 0; mt < 4; mt++) mma16(d[mt], a[1][mt], v.z, v.w);
    float r[8];
#pragma unroll
    for (int i = 0; i < 8; i++) r[i] = d[i >> 1][2 * (i & 1)] + d[i >> 1][2 * (i & 1) + 1];
    tred<4>(r, lane, 2); tred<2>(r, lane, 1);
    st_pair((tq >> 1) == rk ? 1 : 2, ro, psb + OFF_BAR + 8 * (XB + 3), r[0], r[1]);
    __syncwarp();
    if (lane == 0) BAR_ARRIVE(XB + 3);
    if (warp == 0) {
      mbar_wait(bar0 + 8 * (XB + 3));
      float p[8];
#pragma unroll
      for (int i = 0; i < 8; i++) {
        const float4 q = lds16(a_q + i * 16);
        p[i] = (lane & 8) ? q.y + q.w : q.x + q.z;
      }
      const float t = ((p[0] + p[1]) + (p[2] + p[3])) + ((p[4] + p[5]) + (p[6] + p[7]));
      stx4(p_ao, fbits(gav * t + xv));
    }
  }
  tpub = clock();
  if (b < 112) {
    uint32_t af[2][4][4], ad[4][4];
    const uint32_t ab = sb + (32 * warp + 8 * (lane >> 4) + (lane & 7)) * 64 + ((((lane >> 3) & 1) ^ ((lane >> 1) & 3)) << 4);
    uint32_t ro = ((tq & 1) == rk ? sb : psb) + OFF_R4 + (8 * (tq >> 1) + g) * 176 + (10 * rk + warp) * 8;
    uint32_t a_q = sb + OFF_R4 + (8 * (lane >> 4) + (lane & 7)) * 176 + (lane & 8) * 10;
    uint32_t a_d = sb + OFF_D + warp * 2048 + (8 * (lane >> 4) + (lane & 7)) * 128 + ((((lane >> 3) & 1) ^ (lane & 7)) << 4);
    unsigned* p_f = g_xf + b * 512 + 64 * warp + 16 * tq + 2 * g;
    const unsigned* pa = g_xao + (g >> 1) * 1024 + 512 * rk + 64 * warp + 4 * (lane & 7);
    PIN(ro); PIN(a_q); PIN(a_d); PINL(p_f); PINL(pa);
    spin_until(tpub + DLY6);
    uint4 v[2];
    {
      bool have = false;
      POLL {
        v[0] = ldx16(pa); v[1] = ldx16(pa + 32);
        const unsigned t1 = (unsigned)clock() + WTEST;
        while (!have && (int)((unsigned)clock() - t1) < 0) {
          uint32_t ok;
          asm volatile("{.reg .pred p, q; mbarrier.test_wait.parity.shared::cta.b64 p, [%1], 0; mbarrier.test_wait.parity.shared::cta.b64 q, [%1+8], 0;\n"
                       "and.pred p, p, q; vote.sync.all.pred p, p, 0xffffffff; selp.u32 %0, 1, 0, p;}" : "=r"(ok) : "r"(bar0 + 8 * FB_G) : "memory");
          if (ok) {
#pragma unroll
            for (int i = 0; i < 8; i++) ldsm_t(af[i >> 2][i & 3], (ab + ((i & 2) ? OFF_U : OFF_G) + (i >> 2) * 1024) ^ ((i & 1) << 5));
            have = true;
          }
        }
        if (!__any_sync(~0u, (X16(v[0]) | X16(v[1])) & 1) || ++it_ >= SPIN_MAX) break;
      }
      float df[4][4] = {}, dg[2][4] = {};
      uint32_t zb[4];
      const uint32_t one = g == 0 ? 0x3F803F80u : 0u;
#pragma unroll
      for (int s = 0; s < 2; s++) {
        const uint32_t y0 = pack2(u2f(v[s].x), u2f(v[s].y)), y1 = pack2(u2f(v[s].z), u2f(v[s].w));
        const uint32_t ya[4] = {y0, one, y1, one};
        mma16(dg[s], ya, y0, y1);
        zb[2 * s] = pack2(u2f(v[s].x) * cf[s].x, u2f(v[s].y) * cf[s].y); zb[2 * s + 1] = pack2(u2f(v[s].z) * cf[s].z, u2f(v[s].w) * cf[s].w);
      }
      float st[2] = {(dg[0][2] + dg[0][3]) + (dg[1][2] + dg[1][3]), (dg[0][0] + dg[0][1]) + (dg[1][0] + dg[1][1])};
      if (!have) {
        mbar_wait(bar0 + 8 * FB_G); mbar_wait(bar0 + 8 * (FB_G + 1));
#pragma unroll
        for (int i = 0; i < 8; i++) ldsm_t(af[i >> 2][i & 3], (ab + ((i & 2) ? OFF_U : OFF_G) + (i >> 2) * 1024) ^ ((i & 1) << 5));
      }
#pragma unroll
      for (int i = 0; i < 8; i++) mma16(df[i & 3], af[i >> 2][i & 3], zb[2 * (i >> 2)], zb[2 * (i >> 2) + 1]);
#pragma unroll
      for (int o2 = 1; o2 < 4; o2 <<= 1) { st[0] += __shfl_xor_sync(~0u, st[0], o2); st[1] += __shfl_xor_sync(~0u, st[1], o2); }
#pragma unroll
      for (int o2 = 4; o2 < 32; o2 <<= 1) st[1] += __shfl_xor_sync(~0u, st[1], o2);
      float r[8];
#pragma unroll
      for (int i = 0; i < 8; i++) r[i] = df[i >> 1][2 * (i & 1)] + df[i >> 1][2 * (i & 1) + 1];
      tred<4>(r, lane, 2); tred<2>(r, lane, 1);
      const int md = (tq & 1) == rk ? 1 : 2;
      st_pair(md, ro, psb + OFF_BAR + 8 * (XB + 5), r[0], r[1]);
      st_pair(lane < 2 ? md : 0, ro + 16 * 176, psb + OFF_BAR + 8 * (XB + 5), st[0], st[1]);
      __syncwarp();
      if (lane == 0) BAR_ARRIVE(XB + 5);
      mbar_wait(bar0 + 8 * FB_D);
#pragma unroll
      for (int mt = 0; mt < 4; mt++)
        ldsm_t(ad[mt], a_d ^ (mt << 5));
    }
    mbar_wait(bar0 + 8 * (XB + 5));
    {
      float4 q[5], u[8];
#pragma unroll
      for (int i = 0; i < 5; i++) q[i] = lds16(a_q + i * 16);
#pragma unroll
      for (int i = 0; i < 8; i++) u[i] = *(const float4*)(smem + OFF_R4 + 16 * 176 + (i >> 2) * 80 + (i & 3) * 16);
      float p[6] = {((q[0].x + q[0].z) + (q[1].x + q[1].z)) + ((q[2].x + q[2].z) + (q[3].x + q[3].z)), q[4].x, q[4].z,
                    ((q[0].y + q[0].w) + (q[1].y + q[1].w)) + ((q[2].y + q[2].w) + (q[3].y + q[3].w)), q[4].y, q[4].w};
      tred<3>(p, lane, 8);
      const float P = p[0], A1 = p[1], A2 = p[2];
      const float mean = (((u[0].x + u[0].z) + (u[1].x + u[1].z)) + ((u[2].x + u[2].z) + (u[3].x + u[3].z)) +
                          ((u[4].x + u[4].z) + (u[5].x + u[5].z)) + ((u[6].x + u[6].z) + (u[7].x + u[7].z))) * (1.f / 512.f);
      const float sq = (((u[0].y + u[0].w) + (u[1].y + u[1].w)) + ((u[2].y + u[2].w) + (u[3].y + u[3].w)) +
                         ((u[4].y + u[4].w) + (u[5].y + u[5].w)) + ((u[6].y + u[6].w) + (u[7].y + u[7].w))) * (1.f / 512.f);
      float rstd;
      asm("rsqrt.approx.ftz.f32 %0, %1;" : "=f"(rstd) : "f"(fmaxf(sq - mean * mean, 0.f) + 1e-5f));
      const float gg = bfr(rstd * (P - mean * A1) + A2);
      const float uu = __shfl_xor_sync(~0u, gg, 16);
      const float hh = bfr(gg * rcp(1.f + ex2(gg * (-2.302208198f - 0.1029432397f * gg * gg)))) * uu;
      const uint32_t hw = pack2(hh, __shfl_down_sync(~0u, hh, 1));
      const uint32_t b0 = __shfl_sync(~0u, hw, 2 * tq), b1 = __shfl_sync(~0u, hw, 2 * tq + 8);
      float f0 = 0, f1 = 0;
#pragma unroll
      for (int mt = 0; mt < 4; mt++) {
        float dd[4] = {0, 0, 0, 0};
        mma16(dd, ad[mt], b0, b1);
        if (tq == mt) { f0 = dd[0]; f1 = dd[2]; }
      }
      stx8(p_f, make_uint2(fbits(f0), fbits(f1)));
    }
    tpub = clock();
    if (b < 64 && warp == (b >> 3)) {
      const uint4 y = (b & 4) ? v[1] : v[0];
      float a4[4] = {u2f(y.x), u2f(y.y), u2f(y.z), u2f(y.w)};
      tred<2>(a4, lane, 16); tred<1>(a4, lane, 8);
      a4[0] += __shfl_xor_sync(~0u, a4[0], 4);
      if (!(lane & 4)) s_sm[416 + 8 * (lane >> 4) + 2 * tq + ((lane >> 3) & 1)] = a4[0];
      if (warp == 7) nbar_arrive(2, 256);
    } else if (b < 64 && warp == 7) nbar_arrive(2, 256);
    if (b < 64 && warp < 7) {
      uint4 v;
      const unsigned* pf = g_xf + (tid >> 1) * 512 + 8 * ob + 4 * (tid & 1);
      const int col = 16 * (ob >> 1) + 4 * (ob & 1) + ((tid >> 1) & 3) + 8 * (tid & 1);
      bf16* po = out + col;
      PINL(po); PINL(pf);
      spin_until(tpub + DLY7);
      POLL { v = ldx16(pf); RETRY(X16(v)) }
      float f[4] = {u2f(v.x), u2f(v.y), u2f(v.z), u2f(v.w)};
      tred<2>(f, lane, 16); tred<1>(f, lane, 8);
      f[0] += __shfl_xor_sync(~0u, f[0], 4); f[0] += __shfl_xor_sync(~0u, f[0], 2);
      if (!(lane & 6)) s_sm[352 + warp * 8 + 4 * (lane & 1) + (lane >> 3)] = f[0];
      nbar(2, 256);
      if (tid < 8) {
        const float* q = s_sm + 352 + tid;
        const float t = ((q[0] + q[8]) + (q[16] + q[24])) + ((q[32] + q[40]) + q[48]);
        *po = __float2bfloat16(s_sm[416 + (col & 15)] + bfr(gbv * bfr(t)));
        if (b == 0 && tid == 0) stx4(&g_epoch, epoch + 1);
      }
    }
  }
}

__global__ void __cluster_dims__(2, 1, 1) __launch_bounds__(384, 1)
fused_kernel(const bf16* __restrict__ x, const bf16* __restrict__ cvec, const bf16* __restrict__ w_mod, bf16* __restrict__ out,
             Scratch* __restrict__ scr, const __grid_constant__ TMaps tms) {
  extern __shared__ __align__(1024) unsigned char smem[];
  const int tid = threadIdx.x, warp = __shfl_sync(~0u, tid >> 5, 0), lane = tid & 31;
  const int b = blockIdx.x, rk = b & 1, pr = b >> 1, hd = b >> 2;
  uint32_t sb = s2u(smem), bar0 = sb + OFF_BAR;

  unsigned gt_start;
  asm volatile("mov.u32 %0, %%globaltimer_lo;" : "=r"(gt_start));
  const int g = lane >> 2, tq = lane & 3;
  const int arow = 64 * (b >> 4) + ((tid & 255) >> 3);
  uint4 wm0, wm1;
  uint32_t c0w, c1w;
  if (warp < 8) {
    const bf16* wa = w_mod + (size_t)arow * 3072 + (lane & 4) * 128 + 32 * (b & 15) + 8 * tq;
    wm0 = ldx16(wa); wm1 = ldx16(wa + 32 * 3072);
    c0w = ldc4(cvec + (arow & ~1)); c1w = ldc4(cvec + (arow & ~1) + 32);
  }
  const unsigned t_off = gt_start + RATE_T0;
  if (warp == 11) {
    if (lane == 0) {
#pragma unroll
      for (int i = 0; i < FB_KV; i++) { BAR_INIT(i, 1); BAR_ARM(i, 16384); }
    }
    __syncwarp();
    asm volatile("fence.mbarrier_init.release.cluster;" ::: "memory");
    asm volatile("barrier.cluster.arrive.relaxed.aligned;" ::: "memory");
#pragma unroll 1
    for (int i = 0; i < FB_KV; i++) {
      if (i >= HWIN) mbar_wait(bar0 + 8 * (i - HWIN));
      wait_until(t_off + (i < 4 ? 2 * i + ((b >> 1) & 1) : 4 * i - 8 + (b & 3)) * (RATE_H / 4));
      if (lane == 0) {
        if (i < 4) tma3d(sb + OFF_WQ + i * 16384, &tms.m[0], bar0 + 8 * i, 0, i * 128, 2 * hd + rk);
        else tma3d(sb + OFF_WQ + i * 16384, &tms.m[1], bar0 + 8 * i, 0, (b & 3) * 128 + (i - 4) * 64, 2 * hd);
      }
      __syncwarp();
    }
  }
  if (warp == 10) {
    const uint4 xa = ldc16(x + 16 * lane), xb = ldc16(x + 16 * lane + 8);
    const unsigned ep = ldc4(&g_epoch);
    float xv[16] = {bflo(xa.x), bfhi(xa.x), bflo(xa.y), bfhi(xa.y), bflo(xa.z), bfhi(xa.z), bflo(xa.w), bfhi(xa.w),
                    bflo(xb.x), bfhi(xb.x), bflo(xb.y), bfhi(xb.y), bflo(xb.z), bfhi(xb.z), bflo(xb.w), bfhi(xb.w)};
    float s = 0;
#pragma unroll
    for (int i = 0; i < 16; i++) s += xv[i];
#pragma unroll
    for (int o = 16; o; o >>= 1) s += __shfl_xor_sync(~0u, s, o);
    const float mean = s * (1.f / 512.f);
    s = 0;
#pragma unroll
    for (int i = 0; i < 16; i++) { xv[i] -= mean; s += xv[i] * xv[i]; }
#pragma unroll
    for (int o = 16; o; o >>= 1) s += __shfl_xor_sync(~0u, s, o);
    const float rstd = rsqrtf(s * (1.f / 512.f) + 1e-5f);
    if ((lane >> 1) == (b & 15))
#pragma unroll
      for (int i = 0; i < 4; i++)
        *(float4*)(smem + OFF_SM + (256 + (lane & 1) * 16 + 4 * i) * 4) = make_float4(xv[4 * i] * rstd, xv[4 * i + 1] * rstd, xv[4 * i + 2] * rstd, xv[4 * i + 3] * rstd);
    if (lane == 0) *(volatile unsigned*)(smem + OFF_MASK + 8) = ep;
    nbar_arrive(1, 288);
  }
  if (warp >= 8) {
    asm volatile("setmaxnreg.dec.sync.aligned.u32 72;");
    if (tid == 288) {
#pragma unroll
      for (int q = FB_KV; q < FB_KV + 16; q++) { BAR_INIT(q, 1); BAR_ARM(q, 32768); }
    }
    if (tid == 320) {
#pragma unroll
      for (int q = 0; q <= 13 + NSLOT; q++) BAR_INIT(EB + q, q == 0 ? 4 : q < 5 ? 16 : q < 16 ? 12 : 6);
    }
    if (tid == 256) {
#pragma unroll
      for (int q = FB_MOD; q <= FB_D; q++) { BAR_INIT(q, 1); BAR_ARM(q, 16384); }
      BAR_INIT(QB, 9); BAR_ARM(QB, 1024);
#pragma unroll
      for (int q = 0; q < 7; q++) BAR_INIT(XB + q, q == 2 ? 256 : q == 5 || q == 3 ? 9 : 1);
      BAR_ARM(XB + 3, 1024);
      BAR_ARM(XB + 5, 1024 + 64 + 512);
      *(volatile unsigned long long*)(smem + OFF_MASK) = 0;
    }
    if (warp != 11) {
      __syncwarp();
      asm volatile("fence.mbarrier_init.release.cluster;" ::: "memory");
      __threadfence_block();
      asm volatile("barrier.cluster.arrive.relaxed.aligned;" ::: "memory");
    }
    if (warp == 11) {
      asm volatile("barrier.cluster.wait.acquire.aligned;" ::: "memory");
      const unsigned epoch = *(volatile unsigned*)(smem + OFF_MASK + 8), par = (epoch + 1) & 1;
      mbar_wait(bar0 + 8 * (FB_KV + 15));
      for (int it = 0; ldx4(scr->cnt + 96 + 32 * (b >> 6)) != (epoch + 1) * 64 && it < SPIN_MAX; it++) {}
      uint4 hh;
      POLL { hh = ldx16(g_ml + (b >> 2) * 64 + 2 * lane); RETRY(X16(hh)) }
      int mi = __float_as_int(fmaxf(u2f(hh.x), u2f(hh.z)));
      mi ^= (mi >> 31) & 0x7fffffff;
      mi = __reduce_max_sync(~0u, mi);
      mi ^= (mi >> 31) & 0x7fffffff;
      const float M = __int_as_float(mi);
      const uint32_t wp = pack2(ex2(u2f(hh.x) - M), ex2(u2f(hh.z) - M));
      float L = bflo(wp) * u2f(hh.y) + bfhi(wp) * u2f(hh.w);
#pragma unroll
      for (int o2 = 16; o2; o2 >>= 1) L += __shfl_xor_sync(~0u, L, o2);
      *(uint32_t*)(smem + OFF_RA + lane * 4) = wp;
      if (lane == 0) *(float*)(smem + OFF_RA + 128) = rcp(L);
      __syncwarp();
      if (lane == 0) BAR_ARRIVE(XB + 6);
    }
    if (warp == 10) {
      if (lane < 8) asm volatile("prefetch.tensormap [%0];" ::"l"(&tms.m[lane + 1]) : "memory");
      asm volatile("barrier.cluster.wait.acquire.aligned;" ::: "memory");
      const unsigned epoch = *(volatile unsigned*)(smem + OFF_MASK + 8);
#pragma unroll 1
      for (int e = 0; e < 2; e++) {
        for (int it = 0; ldx4(scr->cnt + (e ? 2 + rk : 1)) != (epoch + 1) * (e ? 64 : 128) && it < SPIN_MAX; it++) {}
        if (lane == 0) BAR_ARRIVE(XB + e);
      }
      mbar_wait(bar0 + 8 * (FB_KV + 14));
      unsigned long long m = 0;
#pragma unroll 1
      for (int it = 0; ~m && it < SPIN_MAX; it++) {
        m = ldx64(scr->cnt + 32 + 32 * (b >> 6)) ^ ((epoch & 1) ? ~0ull : 0ull);
        if (lane == 0) *(volatile unsigned long long*)(smem + OFF_MASK) = m;
      }
    }
    if (warp == 9) {
      asm volatile("barrier.cluster.wait.acquire.aligned;" ::: "memory");
      const unsigned epoch = *(volatile unsigned*)(smem + OFF_MASK + 8);
      const unsigned par = (epoch + 1) & 1, inv = par ^ 1;
      const uint4 inv4 = make_uint4(inv, inv, inv, inv);
      mbar_wait(bar0 + 8 * FB_KV);
#pragma unroll 2
      for (int k = 0; k < 8; k++) {
        const uint32_t cp = ldc4(cvec + 2 * (lane + 32 * k));
        *(uint32_t*)(smem + OFF_SILU + (lane + 32 * k) * 4) = pack2(silu_bf(bflo(cp)), silu_bf(bfhi(cp)));
      }
      __syncwarp();
      mbar_wait(bar0 + 8 * FB_MOD);
      const uint32_t ab = sb + OFF_MOD + (8 * (lane >> 4) + (lane & 7)) * 32 + ((((lane >> 3) ^ (lane >> 2)) & 1) << 4);
      float d[4][4] = {};
#pragma unroll 2
      for (int s4 = 0; s4 < 8; s4++)
#pragma unroll
        for (int s = 0; s < 4; s++) {
          uint32_t a[4];
          const uint32_t* ps = (const uint32_t*)(smem + OFF_SILU) + 32 * s4 + 8 * s + tq;
          ldsm_t(a, ab + (4 * s4 + s) * 512); mma16(d[s], a, ps[0], ps[4]);
        }
      const float t = (tq & 1) ? (d[0][2] + d[1][2]) + (d[2][2] + d[3][2]) : (d[0][0] + d[1][0]) + (d[2][0] + d[3][0]);
      if (tq < 2) stx4(g_xm + b * 16 + 2 * (g & 6) + 2 * tq + (g & 1), fbits(bfr(t)));
      __syncwarp();
      if (lane == 0) CNT_ADD(6);
      mbar_wait(bar0 + 8 * (FB_KV + 8));
      if (lane < 16) stx16(g_xc + (b >> 2) * 256 + (lane >> 1) * 32 + (b & 3) * 8 + (lane & 1) * 4, inv4);
      if (lane < 8) stx16(g_xao + (b >> 5) * 1024 + (b & 15) * 64 + (lane & 4) * 8 + (b & 16) + (lane & 3) * 4, inv4);
      if (b < 112)
#pragma unroll 1
        for (int k = 0; k < 4; k++) stx16(g_xf + b * 512 + (lane + 32 * k) * 4, inv4);
      nbar_arrive(2, 288);
      for (int it = 0; ldx4(scr->cnt + 6) != (epoch + 1) * 128 && it < SPIN_MAX; it++) __nanosleep(100);
      {
        uint4 sv[2], cb[2];
        unsigned ga, gb;
        POLL {
#pragma unroll
          for (int k = 0; k < 2; k++) { sv[k] = ldx16(g_xm + 512 + 256 * rk + 4 * (lane + 32 * k)); cb[k] = ldx16(g_xm + 1024 + 256 * rk + 4 * (lane + 32 * k)); }
          ga = ldx4(g_xm + (b & 15) * 32 + lane); gb = ldx4(g_xm + 1536 + 256 * rk + 8 * (pr & 31) + (lane & 7));
          RETRY(X16(sv[0]) | X16(sv[1]) | X16(cb[0]) | X16(cb[1]) | lop_x3(ga, gb, par))
        }
#pragma unroll
        for (int k = 0; k < 2; k++) {
          const float c0 = bfr(1.f + bfhi(cb[k].x)), c1 = bfr(1.f + bfhi(cb[k].y)), c2 = bfr(1.f + bfhi(cb[k].z)), c3 = bfr(1.f + bfhi(cb[k].w));
          *(float4*)(smem + OFF_CO + (lane + 32 * k) * 16) = make_float4(c0, c1, c2, c3);
          uint2* pb = (uint2*)(smem + OFF_BP) + lane + 32 * k;
          pb[0] = make_uint2(pack2(c0, c1), pack2(c2, c3));
          pb[64] = make_uint2(__byte_perm(sv[k].x, sv[k].y, 0x7632), __byte_perm(sv[k].z, sv[k].w, 0x7632));
        }
        *(float*)(smem + OFF_CO + 1024 + lane * 4) = bfhi(ga);
        *(float*)(smem + OFF_CO + 1152 + lane * 4) = bfhi(gb);
      }
      __syncwarp();
      if (lane == 0) BAR_ARRIVE(XB + 4);
    }
    if (warp == 8) {
      const unsigned stag = ((pr * SMUL) & 63) * RATE_NS >> 6;
      unsigned tnext = t_off + 4 * RATE_H;
      asm volatile("barrier.cluster.wait.acquire.aligned;" ::: "memory");
#pragma unroll 1
      for (int k = 0; k < 24; k++) {
        const int code = (k < 12 ? ORDER0 >> (5 * k) : ORDER1 >> (5 * (k - 12))) & 31;
        const bool kv = code < 16;
        const int n = code, w = code - 16;
        if (!kv && w >= 5 && b >= 112) break;
        if (kv) mbar_wait(bar0 + 8 * (FB_KV + n - (n < 6 ? EWIN : KVWIN)));
        if (k >= TAIL_K) mbar_wait(bar0 + 8 * (FB_KV + (int)((ORDER1 >> (5 * (k - 12 - ((WINS >> (4 * (k - TAIL_K))) & 15)))) & 31)));
        const int e = kv ? (n == 3 ? 2 : n == 5 ? 1 : n) : w == 0 ? 0 : w < 5 ? 16 + ((w - 1) >> 1) : w == 7 ? 19 : 18;
        if (e != 1 && k) mbar_wait(bar0 + 8 * (EB + e));
        wait_until(tnext + stag);
        tnext += k > TAIL_K ? RATE_TL : k < 4 ? RATE_E : RATE_NS;
        if (lane == 0) {
          if (kv)
            asm volatile("cp.async.bulk.tensor.3d.shared::cluster.global.mbarrier::complete_tx::bytes.multicast::cluster.L2::cache_hint [%0], [%1, {%3, %4, %5}], [%2], %6, %7;"
                         ::"r"(sb + (n % NSLOT) * SLOT + rk * 16384), "l"(&tms.m[2]), "r"(bar0 + 8 * (FB_KV + n)), "r"(0), "r"(((n >> 1) * 64 + pr) * 64),
                           "r"(4 * (n & 1) + 2 * rk), "h"((unsigned short)3), "l"(stream_policy()) : "memory");
          else {
            tma3d(sb + (w == 0 ? OFF_MOD : w < 5 ? OFF_UV + (w - 1) * 16384 : w == 5 ? OFF_G : w == 6 ? OFF_U : OFF_D),
                  &tms.m[w == 0 ? 3 : w < 3 ? 4 : w < 5 ? 5 : w + 1], bar0 + 8 * (FB_MOD + w),
                  w == 0 ? 1024 + b * 16 : w < 3 || w == 7 ? 0 : w < 5 ? (pr & 7) * 64 : pr * 32, w == 7 ? b * 16 : w == 1 || w == 2 ? (b & 3) * 128 + (w - 1) * 64 : 0,
                  w == 1 || w == 2 ? 2 * hd : w == 3 || w == 4 ? (b >> 4) * 4 + 2 * rk + w - 3 : w == 5 || w == 6 ? rk : 0);
          }
        }
        __syncwarp();
      }
    }
    if (b < 112) {
      const int mt = warp & 1, dd = (warp >> 1) & 1;
      mbar_wait(bar0 + 8 * (XB + 4));
      const uint32_t ab = sb + (mt ? OFF_U : OFF_G) + (8 * (lane >> 4) + (lane & 7)) * 64 + (((2 * dd + ((lane >> 3) & 1)) ^ ((lane >> 1) & 3)) << 4);
      uint32_t base;
      asm volatile("mapa.shared::cluster.u32 %0, %1, %2;" : "=r"(base) : "r"(sb), "r"(dd));
      uint2 bb[16];
#pragma unroll
      for (int s = 0; s < 16; s++) bb[s] = *(const uint2*)(smem + OFF_BP + (g & 1) * 512 + (4 * s + tq) * 8);
      mbar_wait(bar0 + 8 * (FB_G + mt));
      float e[4][4] = {};
#pragma unroll
      for (int s = 0; s < 16; s++) { uint32_t a[4]; ldsm_t(a, ab + s * 1024); mma16(e[s & 3], a, bb[s].x, bb[s].y); }
      float r[4];
#pragma unroll
      for (int i = 0; i < 4; i++) r[i] = (e[0][i] + e[1][i]) + (e[2][i] + e[3][i]);
      if (tq < 2) st_async2(base + OFF_R4 + (8 * mt + g) * 176 + (10 * rk + 8 + tq) * 8, base + OFF_BAR + 8 * (XB + 5), tq ? r[1] : r[0], tq ? r[3] : r[2]);
    }
    return;
  }

  float* s_sm = (float*)(smem + OFF_SM);
  unsigned par, epoch;
  uint32_t rsb;
  {
    float* s_r4 = (float*)(smem + OFF_R4);
    asm volatile("barrier.cluster.arrive.relaxed.aligned;" ::: "memory");
    asm volatile("mapa.shared::cluster.u32 %0, %1, %2;" : "=r"(rsb) : "r"(sb), "r"(rk ^ 1));
    const float c0 = (arow & 1) ? bfhi(c0w) : bflo(c0w), c1 = (arow & 1) ? bfhi(c1w) : bflo(c1w);
    float acc[8] = {0, 0, 0, 0, 0, 0, 0, 0};
    fma8(acc, wm0, silu_bf(c0)); fma8(acc, wm1, silu_bf(c1));
    tred<4>(acc, lane, 8); tred<2>(acc, lane, 16);
    *(float2*)(s_r4 + warp * 64 + 8 * (lane & 7) + ((lane >> 1) & 4) + ((lane >> 3) & 2)) = make_float2(acc[0], acc[1]);
    nbar(1, 288);
    epoch = *(volatile unsigned*)(smem + OFF_MASK + 8);
    par = (epoch + 1) & 1;
    if (warp == 0) {
      float t = 0.f, ca = b < 16 ? 1.f : 0.f;
#pragma unroll
      for (int w = 0; w < 8; w++) { t += s_r4[w * 64 + lane]; ca += s_r4[w * 64 + 32 + lane]; }
      t += ca * s_sm[256 + lane];
      const float nb = __shfl_down_sync(~0u, t, 1);
      const uint32_t w0 = lane < 8 ? pack2t(t, nb, par) : pack2(t, nb);
      const uint32_t w1 = __shfl_down_sync(~0u, w0, 8), w2 = __shfl_down_sync(~0u, w0, 16), w3 = __shfl_down_sync(~0u, w0, 24);
      if (lane < 8 && !(lane & 1)) stx16(g_h + (b >> 5) * 512 + (b & 15) * 32 + (b & 16) + 2 * lane, make_uint4(w0, w1, w2, w3));
      __syncwarp();
      if (lane == 0) CNT_ADD(1);
    }
  }
  asm volatile("barrier.cluster.wait.acquire.aligned;" ::: "memory");
  {
    uint32_t a[4][4][4];
    mbar_wait(bar0 + 8 * (warp >> 1));
    const uint32_t ab = sb + OFF_WQ + (64 * warp + 8 * (lane >> 4) + (lane & 7)) * 128;
#pragma unroll
    for (int s = 0; s < 4; s++)
#pragma unroll
      for (int mt = 0; mt < 4; mt++) ldsm_t(a[s][mt], ab + s * 2048 + (((2 * mt + ((lane >> 3) & 1)) ^ (lane & 7)) << 4));
    uint4 v0, v1;
    const unsigned* ph = g_h + (g >> 1) * 512 + 64 * warp + 4 * (lane & 7);
    uint32_t off = OFF_B + warp * 272 + (32 * rk + 8 * tq + (lane & 4)) * 4;
    PIN(off); PINL(ph);
    mbar_wait(bar0 + 8 * XB);
    POLL { v0 = ldx16(ph); v1 = ldx16(ph + 32); RETRY(lop_x3(v0.x, v1.x, par)) }
    float d[4][4] = {};
#pragma unroll
    for (int mt = 0; mt < 4; mt++) {
      mma16(d[mt], a[0][mt], v0.x, v0.y); mma16(d[mt], a[1][mt], v0.z, v0.w);
      mma16(d[mt], a[2][mt], v1.x, v1.y); mma16(d[mt], a[3][mt], v1.z, v1.w);
    }
    float r[8];
#pragma unroll
    for (int mt = 0; mt < 4; mt++) { r[2 * mt] = d[mt][0] + d[mt][1]; r[2 * mt + 1] = d[mt][2] + d[mt][3]; }
    tred<4>(r, lane, 2); tred<2>(r, lane, 1);
    const float rc = __shfl_xor_sync(~0u, (lane & 4) ? r[0] : r[1], 4);
    const uint32_t wd = (lane & 4) ? pack2(rc, r[1]) : pack2(r[0], rc);
    const uint32_t w1 = __shfl_down_sync(~0u, wd, 8), w2 = __shfl_down_sync(~0u, wd, 16), w3 = __shfl_down_sync(~0u, wd, 24);
    asm volatile("{.reg .pred p; setp.lt.s32 p, %7, 8; @p st.shared.v4.b32 [%0], {%2,%3,%4,%5};\n"
                 "@p st.async.shared::cluster.mbarrier::complete_tx::bytes.v4.b32 [%1], {%2,%3,%4,%5}, [%6];}"
                 ::"r"(sb + off), "r"(rsb + off), "r"(wd), "r"(w1), "r"(w2), "r"(w3), "r"(rsb + OFF_BAR + 8 * QB), "r"(lane) : "memory");
    __syncwarp();
    arrive2(bar0 + 8 * QB, 0, lane == 0, false);
    arrive2(bar0 + 8 * (EB + 2), rsb + OFF_BAR + 8 * (EB + 2), lane == 0, lane == 0);
  }
  {
    uint32_t a[8][4];
    uint32_t a_bq = sb + OFF_B + (lane & 7) * 272 + (lane >> 3) * 16;
    unsigned* p_qa = g_qa + b * 64 + 8 * warp + 4 * lane;
    PIN(a_bq); PINL(p_qa);
    mbar_wait(bar0 + 8 * (FB_UK + (warp >> 2)));
    const uint32_t ab = sb + OFF_WUK + (warp >> 2) * 16384 + (16 * (warp & 3) + (lane & 15)) * 128;
#pragma unroll
    for (int s = 0; s < 8; s++) ldsm(a[s], ab + (s >> 2) * 8192 + (((2 * (s & 3) + (lane >> 4)) ^ (lane & 7)) << 4));
    mbar_wait(bar0 + 8 * QB);
    float d[4][4] = {};
#pragma unroll
    for (int y = 0; y < 4; y++) {
      uint32_t bq[4];
      ldsm(bq, a_bq + 64 * y);
      mma16(d[(2 * y) & 3], a[2 * y], bq[0], bq[1]); mma16(d[(2 * y + 1) & 3], a[2 * y + 1], bq[2], bq[3]);
    }
    float r[2] = {((d[0][0] + d[0][1]) + (d[1][0] + d[1][1])) + ((d[2][0] + d[2][1]) + (d[3][0] + d[3][1])),
                  ((d[0][2] + d[0][3]) + (d[1][2] + d[1][3])) + ((d[2][2] + d[2][3]) + (d[3][2] + d[3][3]))};
    tred<1>(r, lane, 1);
    r[0] += __shfl_xor_sync(~0u, r[0], 2);
    const float nb = __shfl_xor_sync(~0u, r[0], 4);
    const uint32_t w0 = lane < 8 ? pack2t(r[0], nb, par) : pack2(r[0], nb);
    const uint32_t w1 = __shfl_down_sync(~0u, w0, 8), w2 = __shfl_down_sync(~0u, w0, 16), w3 = __shfl_down_sync(~0u, w0, 24);
    if (lane < 2) stx16(p_qa, make_uint4(w0, w1, w2, w3));
    arrive2(bar0 + 8 * (EB + 4), rsb + OFF_BAR + 8 * (EB + 4), lane == 0, lane == 0);
  }
  {
    if (warp) nbar_arrive(3, 256); else { nbar(3, 256); if (lane == 0) CNT_ADD(2 + (b >> 6)); }
    asm volatile("setmaxnreg.inc.sync.aligned.u32 216;");
    const unsigned* pq = g_qa + rk * 4096 + tid * 4;
    uint32_t a_q = sb + OFF_Q + ((tid & 63) >> 3) * 2048 + (tid >> 6) * 128 + (((tid & 7) ^ (tid >> 6)) << 4);
    PINL(pq); PIN(a_q);
    mbar_wait(bar0 + 8 * (XB + 1));
    uint4 v[4];
    POLL {
#pragma unroll
      for (int k = 0; k < 4; k++) v[k] = ldx16(pq + 1024 * k);
      RETRY(lop_x3(v[0].x, v[1].x, par) | lop_x3(v[2].x, v[3].x, par))
    }
#pragma unroll
    for (int k = 0; k < 4; k++)
      asm volatile("st.shared.v4.b32 [%0], {%1,%2,%3,%4};" ::"r"((a_q + k * 512) ^ ((k & 1) << 6)), "r"(v[k].x), "r"(v[k].y), "r"(v[k].z), "r"(v[k].w) : "memory");
    if (warp >= 4) nbar_arrive(1, 256); else nbar(1, 256);
  }
  sb = __shfl_sync(~0u, sb, 0); bar0 = sb + OFF_BAR;
  if (warp < 4) {
    uint32_t qf[32][4];
#pragma unroll
    for (int s = 0; s < 32; s++) ldsm(qf[s], sb + OFF_Q + (s >> 2) * 2048 + (lane & 15) * 128 + (((2 * (s & 3) + (lane >> 4)) ^ (lane & 7)) << 4));
    float l0 = 0.f, l1 = 0.f, m0 = -1e30f, m1 = -1e30f;
    const float sc = 0.08838834764831845f * 1.4426950408889634f;
    const uint32_t kofs = (16 * warp + 8 * (lane >> 4) + (lane & 7)) * 128 + ((((lane >> 3) & 1) ^ (lane & 7)) << 4);
    uint32_t st = sb;
#pragma unroll 1
    for (int t = 0; t < 8; t++) {
      float sa[4][4] = {};
#pragma unroll
      for (int hf = 0; hf < 2; hf++) {
        const int n = 2 * t + hf;
        mbar_wait(bar0 + 8 * (FB_KV + n));
        uint32_t kf[16][4];
#pragma unroll
        for (int y = 0; y < 16; y++) ldsm(kf[y], st + (y >> 2) * 8192 + (kofs ^ ((y & 3) << 5)));
#pragma unroll
        for (int y = 0; y < 16; y++) {
          mma16(sa[(2 * y) & 3], qf[16 * hf + y], kf[y][0], kf[y][1]); mma16(sa[((2 * y) & 3) + 1], qf[16 * hf + y], kf[y][2], kf[y][3]);
        }
        __syncwarp();
        arrive2(bar0 + 8 * (EB + NSLOT + n), rsb + OFF_BAR + 8 * (EB + NSLOT + n), lane == 0 && n < 14, lane == 0 && n < 16 - NSLOT);
        if (hf == 0) arrive2(bar0 + 8 * EB, 0, lane == 0 && t == 0, false);
        st = st + SLOT == sb + NSLOT * SLOT ? sb : st + SLOT;
      }
#pragma unroll
      for (int i = 0; i < 4; i++) { sa[0][i] = (sa[0][i] + sa[2][i]) * sc; sa[1][i] = (sa[1][i] + sa[3][i]) * sc; }
      float cm[2] = {fmaxf(fmaxf(sa[0][0], sa[0][1]), fmaxf(sa[1][0], sa[1][1])), fmaxf(fmaxf(sa[0][2], sa[0][3]), fmaxf(sa[1][2], sa[1][3]))};
      tmax<1>(cm, lane, 1);
      cm[0] = fmaxf(cm[0], __shfl_xor_sync(~0u, cm[0], 2));
      float* pm = s_sm + (t & 1) * 64;
      if (tq < 2) pm[(g + 8 * tq) * 4 + warp] = cm[0];
      if (t >= 2) nbar(6 + (t & 1), 256); else nbar(3, 128);
      const float4 a0 = *(const float4*)(pm + g * 4), b0 = *(const float4*)(pm + g * 4 + 32);
      const float n0 = fmaxf(fmaxf(fmaxf(a0.x, a0.y), fmaxf(a0.z, a0.w)), m0), n1 = fmaxf(fmaxf(fmaxf(b0.x, b0.y), fmaxf(b0.z, b0.w)), m1);
      uint32_t pk[4];
#pragma unroll
      for (int i = 0; i < 2; i++) { pk[2 * i] = pack2(ex2(sa[i][0] - n0), ex2(sa[i][1] - n0)); pk[2 * i + 1] = pack2(ex2(sa[i][2] - n1), ex2(sa[i][3] - n1)); }
      *(uint4*)(smem + OFF_P + (t & 1) * 2048 + tid * 16) = make_uint4(pk[0], pk[1], pk[2], pk[3]);
      const float al0 = ex2(m0 - n0), al1 = ex2(m1 - n1);
      if (tid < 32 && tq == 0) *(float2*)(s_sm + 192 + (t & 1) * 16 + 2 * g) = make_float2(al0, al1);
      nbar_arrive(4 + (t & 1), 256);
      m0 = n0; m1 = n1;
      l0 = l0 * al0 + (bflo(pk[0]) + bfhi(pk[0])) + (bflo(pk[2]) + bfhi(pk[2]));
      l1 = l1 * al1 + (bflo(pk[1]) + bfhi(pk[1])) + (bflo(pk[3]) + bfhi(pk[3]));
    }
    float lr[2] = {l0, l1};
    tred<1>(lr, lane, 1);
    lr[0] += __shfl_xor_sync(~0u, lr[0], 2);
    if (tq < 2) s_sm[128 + (g + 8 * tq) * 4 + warp] = lr[0];
    nbar(3, 128);
    if (warp == 0 && tq < 2) {
      const float4 a0 = *(const float4*)(s_sm + 128 + (g + 8 * tq) * 4);
      stx8(g_ml + (16 * rk + g + 8 * tq) * 64 + pr, make_uint2(fbits(tq ? m1 : m0), fbits((a0.x + a0.y) + (a0.z + a0.w))));
    }
    if (warp == 0) { __syncwarp(); if (lane == 0) CNT_ADD(96 + 32 * rk); }
    nbar(2, 288);
    if (tid == 0) asm volatile("red.relaxed.gpu.global.xor.b64 [%0], %1;" ::"l"(scr->cnt + 32 + 32 * rk), "l"(1ull << pr) : "memory");
  } else {
    float o[16][4] = {};
    const uint32_t vofs = (warp & 1) * 16384 + (lane & 15) * 128 + (((lane >> 4) ^ (lane & 7)) << 4);
    const int hf = (warp >> 1) & 1;
    uint32_t st = sb + hf * SLOT;
    auto pv = [&](const int t, auto np) {
      constexpr int npre = decltype(np)::value;
      uint32_t vf[4][8][4];
      const int n = 2 * t + hf;
      mbar_wait(bar0 + 8 * (FB_KV + n));
#pragma unroll
      for (int s = 0; s < npre; s++)
#pragma unroll
        for (int y = 0; y < 8; y++) ldsm_t(vf[s][y], st + (y >> 2) * 8192 + s * 2048 + (vofs ^ ((y & 3) << 5)));
      nbar(4 + (t & 1), 256);
      const float2 al = *(const float2*)(s_sm + 192 + (t & 1) * 16 + 2 * g);
      uint4 pf[4];
#pragma unroll
      for (int s = 0; s < 4; s++) pf[s] = *(const uint4*)(smem + OFF_P + (t & 1) * 2048 + s * 512 + lane * 16);
      if (t < 6) nbar_arrive(6 + (t & 1), 256);
#pragma unroll
      for (int s = npre; s < 4; s++)
#pragma unroll
        for (int y = 0; y < 8; y++) ldsm_t(vf[s][y], st + (y >> 2) * 8192 + s * 2048 + (vofs ^ ((y & 3) << 5)));
#pragma unroll
      for (int nt = 0; nt < 16; nt++) { o[nt][0] *= al.x; o[nt][1] *= al.x; o[nt][2] *= al.y; o[nt][3] *= al.y; }
#pragma unroll
      for (int s = 0; s < 4; s++) {
        const uint32_t pa[4] = {pf[s].x, pf[s].y, pf[s].z, pf[s].w};
#pragma unroll
        for (int y = 0; y < 8; y++) { mma16(o[2 * y], pa, vf[s][y][0], vf[s][y][1]); mma16(o[2 * y + 1], pa, vf[s][y][2], vf[s][y][3]); }
      }
      __syncwarp();
      arrive2(bar0 + 8 * (EB + NSLOT + n), rsb + OFF_BAR + 8 * (EB + NSLOT + n), lane == 0 && n < 14, lane == 0 && n < 16 - NSLOT);
      st = st + 2 * SLOT >= sb + NSLOT * SLOT ? st - (NSLOT - 2) * SLOT : st + 2 * SLOT;
    };
#pragma unroll 1
    for (int t = 0; t < 7; t++) pv(t, IC<NPRE0>());
    pv(7, IC<NPRE1>());
    uint4* po = g_xo + ((size_t)((16 * rk + (g & 6)) * 4 + warp - 4) * 64 + pr) * RS + (lane & 7);
    const bool odd = lane & 4;
#pragma unroll
    for (int e = 0; e < 2; e++)
#pragma unroll
      for (int j2 = 0; j2 < 2; j2++) {
        uint32_t c0[4], c1[4];
#pragma unroll
        for (int i = 0; i < 4; i++) {
          c0[i] = i ? pack2(o[8 * j2 + i][2 * e], o[8 * j2 + i][2 * e + 1]) : pack2t(o[8 * j2][2 * e], o[8 * j2][2 * e + 1], par);
          c1[i] = i ? pack2(o[8 * j2 + 4 + i][2 * e], o[8 * j2 + 4 + i][2 * e + 1]) : pack2t(o[8 * j2 + 4][2 * e], o[8 * j2 + 4][2 * e + 1], par);
          const uint32_t r = __shfl_xor_sync(~0u, odd ? c0[i] : c1[i], 4);
          if (odd) c0[i] = r; else c1[i] = r;
        }
        stx16(po + e * 8 * 4 * 64 * RS + 8 * j2, make_uint4(c0[0], c0[1], c0[2], c0[3]));
        stx16(po + (e * 8 + 1) * 4 * 64 * RS + 8 * j2, make_uint4(c1[0], c1[1], c1[2], c1[3]));
      }
    nbar_arrive(2, 288);
  }
  tail(smem, scr, x, out, par, epoch, warp);
}

static void launch(void* const* d_in, void* d_out) {
  static TMaps tms;
  static bool init = false;
  static void* scr = nullptr;
  if (!init) {
    void* fn = nullptr; cudaDriverEntryPointQueryResult qr;
    cudaGetDriverEntryPoint("cuTensorMapEncodeTiled", &fn, cudaEnableDefault, &qr);
    EncFn f = (EncFn)fn;
    const CUtensorMapSwizzle S32 = CU_TENSOR_MAP_SWIZZLE_32B, S64 = CU_TENSOR_MAP_SWIZZLE_64B, S128 = CU_TENSOR_MAP_SWIZZLE_128B;
    const CUtensorMapL2promotion P128 = CU_TENSOR_MAP_L2_PROMOTION_L2_128B, P256 = CU_TENSOR_MAP_L2_PROMOTION_L2_256B;
    enc3d(f, &tms.m[0], d_in[2], 64, 512, 64, 8192, 128, 64, 128, 1, S128, P128);
    enc3d(f, &tms.m[1], d_in[3], 64, 512, 64, 8192, 128, 64, 64, 2, S128, P256);
    enc3d(f, &tms.m[2], d_in[1], 64, SK, 8, 1024, 128, 64, 64, 2, S128, P256);
    enc3d(f, &tms.m[3], d_in[11], 3072, 256, 2, 6144, 256 * 6144, 16, 256, 2, S32, P128);
    enc3d(f, &tms.m[4], d_in[4], 64, 512, 64, 8192, 128, 64, 64, 2, S128, P256);
    enc3d(f, &tms.m[5], d_in[5], 512, 128, 32, 1024, 128 * 1024, 64, 128, 1, S128, P128);
    enc3d(f, &tms.m[6], d_in[7], 1792, 256, 2, 3584, 256 * 3584, 32, 256, 1, S64, P128);
    enc3d(f, &tms.m[7], d_in[8], 1792, 256, 2, 3584, 256 * 3584, 32, 256, 1, S64, P128);
    enc3d(f, &tms.m[8], d_in[9], 64, 1792, 8, 1024, 128, 64, 16, 8, S128, P256);
    cudaFuncSetAttribute(fused_kernel, cudaFuncAttributeMaxDynamicSharedMemorySize, SMEM_BYTES);
    cudaGetSymbolAddress(&scr, g_scr);
    init = true;
  }
  fused_kernel<<<NCTA, 384, SMEM_BYTES>>>((const bf16*)d_in[0], (const bf16*)d_in[10], (const bf16*)d_in[11], (bf16*)d_out, (Scratch*)scr, tms);
}

}

extern "C" void kernel_launch(void* const* d_in, const int* in_sizes, int n_in, void* d_out, int out_size) {
  static int big = -1;
  if (big < 0) big = v9::fits();
  if (big) v9::launch(d_in, d_out); else v8::launch(d_in, d_out);
}
```

```cpp
#include <cuda_runtime.h>
#include <cuda_bf16.h>
#include <cuda.h>
#include <stdint.h>
#include <stdio.h>
#include <stdlib.h>

typedef CUresult (*EncFn)(CUtensorMap*, CUtensorMapDataType, cuuint32_t, void*, const cuuint64_t*, const cuuint64_t*,
                          const cuuint32_t*, const cuuint32_t*, CUtensorMapInterleave, CUtensorMapSwizzle,
                          CUtensorMapL2promotion, CUtensorMapFloatOOBfill);

static void enc3d(EncFn fn, CUtensorMap* tm, void* p, uint64_t d0, uint64_t d1, uint64_t d2, uint64_t s1, uint64_t s2, uint32_t b0,
                  uint32_t b1, uint32_t b2, CUtensorMapSwizzle sw, CUtensorMapL2promotion pr) {
  cuuint64_t gd[3] = {d0, d1, d2}, gs[2] = {s1, s2};
  cuuint32_t bx[3] = {b0, b1, b2}, es[3] = {1, 1, 1};
  fn(tm, CU_TENSOR_MAP_DATA_TYPE_BFLOAT16, 3, p, gd, gs, bx, es, CU_TENSOR_MAP_INTERLEAVE_NONE, sw, pr, CU_TENSOR_MAP_FLOAT_OOB_FILL_NONE);
}

namespace v9 {
typedef __nv_bfloat16 bf16;
#define SK 32768
#define SPIN_MAX (1 << 20)
template <int N> struct IC { static constexpr int value = N; };

__device__ __forceinline__ uint32_t s2u(const void* p) { return (uint32_t)__cvta_generic_to_shared(p); }
__device__ __forceinline__ float bflo(uint32_t u) { return __uint_as_float(u << 16); }
__device__ __forceinline__ float bfhi(uint32_t u) { return __uint_as_float(u & 0xffff0000u); }
__device__ __forceinline__ float u2f(uint32_t u) { return __uint_as_float(u); }
__device__ __forceinline__ void fma8(float* acc, uint4 v, float s) {
  acc[0] += s * bflo(v.x); acc[1] += s * bfhi(v.x); acc[2] += s * bflo(v.y); acc[3] += s * bfhi(v.y);
  acc[4] += s * bflo(v.z); acc[5] += s * bfhi(v.z); acc[6] += s * bflo(v.w); acc[7] += s * bfhi(v.w);
}
__device__ __forceinline__ uint32_t pack2(float a, float b) {
  __nv_bfloat162 p = __floats2bfloat162_rn(a, b); return *(uint32_t*)&p;
}
__device__ __forceinline__ float bfr(float v) { return bfhi(pack2(v, v)); }
__device__ __forceinline__ float silu_bf(float c) { return bfr(__fdividef(c, 1.f + __expf(-c))); }
#define fbits(v) ((__float_as_uint(v) & ~1u) | par)
__device__ __forceinline__ uint32_t pack2t(float a, float b, unsigned par) {
  const uint32_t ua = ((__float_as_uint(a) + ((par ^ 1) << 16)) & 0xFFFE0000u) | (par << 16);
  return __byte_perm(ua, pack2(b, b), 0x7632);
}
__device__ __forceinline__ void nbar(int id, int n) { asm volatile("bar.sync %0, %1;" ::"r"(id), "r"(n) : "memory"); }
__device__ __forceinline__ void nbar_arrive(int id, int n) { asm volatile("bar.arrive %0, %1;" ::"r"(id), "r"(n) : "memory"); }
__device__ __forceinline__ uint4 ldc16(const void* p) {
  uint4 v; asm volatile("ld.relaxed.cta.global.v4.u32 {%0,%1,%2,%3}, [%4];" : "=r"(v.x), "=r"(v.y), "=r"(v.z), "=r"(v.w) : "l"(p) : "memory"); return v;
}
__device__ __forceinline__ unsigned ldc4(const void* p) {
  unsigned v; asm volatile("ld.relaxed.cta.global.u32 %0, [%1];" : "=r"(v) : "l"(p) : "memory"); return v;
}
__device__ __forceinline__ uint4 ldx16(const void* p) {
  uint4 v; asm volatile("ld.relaxed.gpu.global.v4.u32 {%0,%1,%2,%3}, [%4];" : "=r"(v.x), "=r"(v.y), "=r"(v.z), "=r"(v.w) : "l"(p) : "memory"); return v;
}
__device__ __forceinline__ unsigned ldx4(const void* p) {
  unsigned v; asm volatile("ld.relaxed.gpu.global.u32 %0, [%1];" : "=r"(v) : "l"(p) : "memory"); return v;
}
__device__ __forceinline__ unsigned long long ldx64(const void* p) {
  unsigned long long v; asm volatile("ld.relaxed.gpu.global.u64 %0, [%1];" : "=l"(v) : "l"(p) : "memory"); return v;
}
__device__ __forceinline__ void stx16(void* p, uint4 v) {
  asm volatile("st.relaxed.gpu.global.v4.u32 [%0], {%1,%2,%3,%4};" ::"l"(p), "r"(v.x), "r"(v.y), "r"(v.z), "r"(v.w) : "memory");
}
__device__ __forceinline__ void stx8(void* p, uint2 v) { asm volatile("st.relaxed.gpu.global.v2.u32 [%0], {%1,%2};" ::"l"(p), "r"(v.x), "r"(v.y) : "memory"); }
__device__ __forceinline__ void stx4(void* p, unsigned v) { asm volatile("st.relaxed.gpu.global.u32 [%0], %1;" ::"l"(p), "r"(v) : "memory"); }
__device__ __forceinline__ void pub4(void* p, unsigned v) { asm volatile("red.relaxed.gpu.global.xor.b32 [%0], %1;" ::"l"(p), "r"(v) : "memory"); }
__device__ __forceinline__ void pub8(void* p, unsigned lo, unsigned hi) {
  asm volatile("{.reg .b64 t; mov.b64 t, {%1, %2}; red.relaxed.gpu.global.xor.b64 [%0], t;}" ::"l"(p), "r"(lo), "r"(hi) : "memory");
}
__device__ __forceinline__ unsigned lop_x3(unsigned a, unsigned b, unsigned c) {
  unsigned d; asm("lop3.b32 %0, %1, %2, %3, 0x7E;" : "=r"(d) : "r"(a), "r"(b), "r"(c)); return d; }
__device__ __forceinline__ unsigned or3(unsigned a, unsigned b, unsigned c) {
  unsigned d; asm("lop3.b32 %0, %1, %2, %3, 0xFE;" : "=r"(d) : "r"(a), "r"(b), "r"(c)); return d; }
__device__ __forceinline__ unsigned and3(unsigned a, unsigned b, unsigned c) {
  unsigned d; asm("lop3.b32 %0, %1, %2, %3, 0x80;" : "=r"(d) : "r"(a), "r"(b), "r"(c)); return d; }
__device__ __forceinline__ unsigned dep16(const uint32_t* f) {
  unsigned d = 0;
#pragma unroll
  for (int i = 0; i < 8; i++) d = or3(d, f[8 * i], f[8 * i + 4]);
  return d;
}
__device__ __forceinline__ uint2 ldx8(const void* p) {
  uint2 v; asm volatile("{.reg .b64 t; ld.relaxed.gpu.global.b64 t, [%2]; mov.b64 {%0, %1}, t;}" : "=r"(v.x), "=r"(v.y) : "l"(p) : "memory"); return v;
}
__device__ __forceinline__ float lds4(uint32_t a) { float v; asm volatile("ld.shared.f32 %0, [%1];" : "=f"(v) : "r"(a) : "memory"); return v; }
__device__ __forceinline__ float shx(float v, int m) {
  float r; asm volatile("shfl.sync.bfly.b32 %0, %1, %2, 0x1f, 0xffffffff;" : "=f"(r) : "f"(v), "r"(m)); return r;
}
__device__ __forceinline__ uint32_t mbar_test(uint32_t bar, uint32_t ph) {
  uint32_t ok;
  asm volatile("{.reg .pred p; mbarrier.test_wait.parity.shared::cta.b64 p, [%1], %2; vote.sync.all.pred p, p, 0xffffffff; selp.u32 %0, 1, 0, p;}"
               : "=r"(ok) : "r"(bar), "r"(ph) : "memory");
  return ok;
}
#define X16(v) (lop_x3(v.x, v.y, par) | lop_x3(v.z, v.w, par))
#define RETRY(bad) if (!__any_sync(~0u, (bad) & 1) || ++it_ >= SPIN_MAX) break;
#define POLL _Pragma("unroll 1") for (int it_ = 0;;)
__device__ __forceinline__ void mbar_wait(uint32_t bar, uint32_t ph = 0) {
  asm volatile("{.reg .pred p; .reg .u32 n; mov.u32 n, 0;\n"
               "W%=: mbarrier.try_wait.parity.shared::cta.b64 p, [%0], %1; add.u32 n, n, 1; setp.lt.and.u32 p, n, 0x100000, !p; @p bra W%=;}"
               ::"r"(bar), "r"(ph) : "memory");
}
__device__ __forceinline__ float ex2(float v) { float r; asm("ex2.approx.ftz.f32 %0, %1;" : "=f"(r) : "f"(v)); return r; }
__device__ __forceinline__ float rcp(float v) { float r; asm("rcp.approx.ftz.f32 %0, %1;" : "=f"(r) : "f"(v)); return r; }
__device__ __forceinline__ void mma16(float* d, const uint32_t* a, uint32_t b0, uint32_t b1) {
  asm volatile("mma.sync.aligned.m16n8k16.row.col.f32.bf16.bf16.f32 {%0,%1,%2,%3}, {%4,%5,%6,%7}, {%8,%9}, {%0,%1,%2,%3};"
               : "+f"(d[0]), "+f"(d[1]), "+f"(d[2]), "+f"(d[3]) : "r"(a[0]), "r"(a[1]), "r"(a[2]), "r"(a[3]), "r"(b0), "r"(b1));
}
__device__ __forceinline__ void mma16c(float* d, const uint32_t* a, uint32_t b0, uint32_t b1, const float* c) {
  asm volatile("mma.sync.aligned.m16n8k16.row.col.f32.bf16.bf16.f32 {%0,%1,%2,%3}, {%4,%5,%6,%7}, {%8,%9}, {%10,%11,%12,%13};"
               : "=f"(d[0]), "=f"(d[1]), "=f"(d[2]), "=f"(d[3])
               : "r"(a[0]), "r"(a[1]), "r"(a[2]), "r"(a[3]), "r"(b0), "r"(b1), "f"(c[0]), "f"(c[1]), "f"(c[2]), "f"(c[3]));
}
__device__ __forceinline__ float4 lds16(uint32_t a) {
  float4 v; asm volatile("ld.shared.v4.f32 {%0,%1,%2,%3}, [%4];" : "=f"(v.x), "=f"(v.y), "=f"(v.z), "=f"(v.w) : "r"(a) : "memory"); return v;
}
__device__ __forceinline__ void sts4(uint32_t a, float v) { asm volatile("st.shared.f32 [%0], %1;" ::"r"(a), "f"(v) : "memory"); }
__device__ __forceinline__ void sts16(uint32_t a, uint4 v) {
  asm volatile("st.shared.v4.b32 [%0], {%1,%2,%3,%4};" ::"r"(a), "r"(v.x), "r"(v.y), "r"(v.z), "r"(v.w) : "memory");
}
__device__ __forceinline__ void ldsm_t(uint32_t* r, uint32_t a) {
  asm volatile("ldmatrix.sync.aligned.m8n8.x4.trans.shared.b16 {%0,%1,%2,%3}, [%4];" : "=r"(r[0]), "=r"(r[1]), "=r"(r[2]), "=r"(r[3]) : "r"(a) : "memory");
}
__device__ __forceinline__ void ldsm(uint32_t* r, uint32_t a) {
  asm volatile("ldmatrix.sync.aligned.m8n8.x4.shared.b16 {%0,%1,%2,%3}, [%4];" : "=r"(r[0]), "=r"(r[1]), "=r"(r[2]), "=r"(r[3]) : "r"(a) : "memory");
}
__device__ __forceinline__ uint32_t mapa(uint32_t a, uint32_t r) {
  uint32_t v; asm volatile("mapa.shared::cluster.u32 %0, %1, %2;" : "=r"(v) : "r"(a), "r"(r)); return v;
}
__device__ __forceinline__ unsigned long long mapg(uint32_t a, uint32_t r) {
  unsigned long long v;
  asm volatile("{.reg .u32 t; .reg .u64 u; mapa.shared::cluster.u32 t, %1, %2; cvt.u64.u32 u, t; cvta.shared::cluster.u64 %0, u;}" : "=l"(v) : "r"(a), "r"(r));
  return v;
}
template <int N>
__device__ __forceinline__ void tred(float* a, int lane, int m) {
  const bool hi = lane & m;
#pragma unroll
  for (int i = 0; i < N; i++) {
    float send = hi ? a[i] : a[i + N], keep = hi ? a[i + N] : a[i];
    a[i] = keep + __shfl_xor_sync(~0u, send, m);
  }
}
template <int N>
__device__ __forceinline__ void tmax(float* a, int lane, int m) {
  const bool hi = lane & m;
#pragma unroll
  for (int i = 0; i < N; i++) {
    float send = hi ? a[i] : a[i + N], keep = hi ? a[i + N] : a[i];
    a[i] = fmaxf(keep, __shfl_xor_sync(~0u, send, m));
  }
}
__device__ __forceinline__ void arrive_n(uint32_t bar, bool on, int cnt) {
  asm volatile("{.reg .pred p; setp.ne.s32 p, %1, 0; @p mbarrier.arrive.shared::cta.b64 _, [%0], %2;}" ::"r"(bar), "r"((int)on), "r"(cnt) : "memory");
}
__device__ __forceinline__ unsigned long long stream_policy() {
  unsigned long long p;
  asm volatile("createpolicy.fractional.L2::evict_first.b64 %0, 1.0;" : "=l"(p));
  return p;
}
__device__ __forceinline__ void tma3d(uint32_t dst, const CUtensorMap* tm, uint32_t bar, int c0, int c1, int c2) {
  asm volatile("cp.async.bulk.tensor.3d.shared::cluster.global.mbarrier::complete_tx::bytes.L2::cache_hint [%0], [%1, {%3, %4, %5}], [%2], %6;"
               ::"r"(dst), "l"(tm), "r"(bar), "r"(c0), "r"(c1), "r"(c2), "l"(stream_policy()) : "memory");
}
__device__ __forceinline__ void spin_until(unsigned t) { while ((int)((unsigned)clock() - t) < 0) {} }
__device__ __forceinline__ void wait_until(unsigned t) {
  unsigned now;
  do { asm volatile("mov.u32 %0, %%globaltimer_lo;" : "=r"(now)); } while ((int)(now - t) < 0);
}
__device__ __forceinline__ void sleep_until(unsigned t) {
  unsigned now;
#pragma unroll 1
  do {
    __nanosleep(200);
    asm volatile("mov.u32 %0, %%globaltimer_lo;" : "=r"(now));
  } while ((int)(now - t) < 0);
}
#define PIN(x) asm volatile("" : "+r"(x))
#define PINL(x) asm volatile("" : "+l"(x))
#define BAR_ARRIVE(i) asm volatile("mbarrier.arrive.shared::cta.b64 _, [%0];" ::"r"(bar0 + 8 * (i)) : "memory")
#define LANE0(op, p, c, v) asm volatile("{.reg .pred q; setp.eq.s32 q, %2, 0; @q " op " [%0], %1;}" ::"l"((p) + lane), c(v), "r"(lane) : "memory")
#define CNT_ADD(c) LANE0("red.relaxed.gpu.global.add.u32", scr->cnt + (c), "r", 1)
#define BAR_INIT(i, cnt) asm volatile("mbarrier.init.shared::cta.b64 [%0], %1;" ::"r"(bar0 + 8 * (i)), "r"(cnt) : "memory")
#define BAR_ARM(i, bytes) asm volatile("mbarrier.arrive.expect_tx.shared::cta.b64 _, [%0], %1;" ::"r"(bar0 + 8 * (i)), "r"(bytes) : "memory")
struct TMaps { CUtensorMap m[9]; };

#define NCTA9 120
#define TAU 20
#define NSL 100
#define NPE 1
#define QN 4
#define FDLY 60
#define VJ 1
#define NPO 3
#define VDLY 150
#define O_Q 131072
#define O_LZ 163840
#define O_CTX 196608
#define O_HZ 198656
#define O_HW 200704
#define O_X 201728
#define O_P 218112
#define O_B 222208
#define O_R 224512
#define O_SILU 228608
#define O_SM 229632
#define O_BAR 231424
#define O_EP (O_BAR + 256)
#define O_DBG (O_EP + 16)
#define SMEM9 (O_DBG + 144)
#define B_FULL 0
#define B_FM 8
#define B_EMPTY 10
#define B_LZ 18
#define B_Q2 19
#define B_H 20
#define B_QF 21
#define B_TAB 22
#define B_W 23
#define B_ST 24
#define B_HZ 25
#define B_WZ 26
#define B_G 27
#define B_G2 28
enum { T_WQ, T_WUK, T_KV, T_MOD, T_UV, T_WO, T_GU, T_DN = 8 };
#define NBIG 40
struct Sched { unsigned zero, dth; uint2 r[3][8]; unsigned nr[3], nt[3], dt, t4, d4, d6, wt, pad; };

struct __align__(128) Scratch {
  unsigned cnt[8 * 32];
  uint2 rec[32 * 4 * 8 * 64];
  uint2 hdr[32 * 16];
  unsigned h[8 * 256];
  uint4 qa[2048];
  unsigned xao[8 * 512];
  unsigned xab[8 * 256];
  unsigned xm[2048];
};
__device__ Scratch g_scr;
#define SMEM_BASE 1024u
#define DSC ((SMEM_BASE >> 4) | (1u << 16))
#define HI128 (64u | (1u << 30))
#define HI64 (32u | (2u << 30))
template <int TA, int TB, unsigned HIA, unsigned HIB>
__device__ __forceinline__ void wgmma32(float* d, uint32_t da, uint32_t db, int acc) {
  asm volatile("{.reg .pred p; .reg .b64 da, db; setp.ne.b32 p, %18, 0; mov.b64 da, {%16, %21}; mov.b64 db, {%17, %22};\n"
               "wgmma.mma_async.sync.aligned.m64n32k16.f32.bf16.bf16 "
               "{%0,%1,%2,%3,%4,%5,%6,%7,%8,%9,%10,%11,%12,%13,%14,%15}, da, db, p, 1, 1, %19, %20;}"
               : "+f"(d[0]), "+f"(d[1]), "+f"(d[2]), "+f"(d[3]), "+f"(d[4]), "+f"(d[5]), "+f"(d[6]), "+f"(d[7]),
                 "+f"(d[8]), "+f"(d[9]), "+f"(d[10]), "+f"(d[11]), "+f"(d[12]), "+f"(d[13]), "+f"(d[14]), "+f"(d[15])
               : "r"(da), "r"(db), "r"(acc), "n"(TA), "n"(TB), "n"(HIA), "n"(HIB));
}
__device__ __forceinline__ void wgmma32r(float* d, const uint32_t* a, uint32_t db) {
  asm volatile("{.reg .b64 db; mov.b64 db, {%20, %21};\n"
               "wgmma.mma_async.sync.aligned.m64n32k16.f32.bf16.bf16 "
               "{%0,%1,%2,%3,%4,%5,%6,%7,%8,%9,%10,%11,%12,%13,%14,%15}, {%16,%17,%18,%19}, db, 1, 1, 1, 1;}"
               : "+f"(d[0]), "+f"(d[1]), "+f"(d[2]), "+f"(d[3]), "+f"(d[4]), "+f"(d[5]), "+f"(d[6]), "+f"(d[7]),
                 "+f"(d[8]), "+f"(d[9]), "+f"(d[10]), "+f"(d[11]), "+f"(d[12]), "+f"(d[13]), "+f"(d[14]), "+f"(d[15])
               : "r"(a[0]), "r"(a[1]), "r"(a[2]), "r"(a[3]), "r"(db), "n"(HI64));
}
template <int N> __device__ __forceinline__ void wg_wait(float* a) {
  asm volatile("wgmma.wait_group.sync.aligned %16;"
               : "+f"(a[0]), "+f"(a[1]), "+f"(a[2]), "+f"(a[3]), "+f"(a[4]), "+f"(a[5]), "+f"(a[6]), "+f"(a[7]), "+f"(a[8]), "+f"(a[9]), "+f"(a[10]),
                 "+f"(a[11]), "+f"(a[12]), "+f"(a[13]), "+f"(a[14]), "+f"(a[15]) : "n"(N) : "memory");
}
__device__ __forceinline__ void send32(uint32_t a, uint32_t bar, float v, int lane, int off) {
  const uint32_t w = pack2(v, __shfl_down_sync(~0u, v, 1));
  const int s = 2 * (lane & 3);
  asm volatile("{.reg .pred p; setp.eq.s32 p, %6, 0; @p st.async.shared::cluster.mbarrier::complete_tx::bytes.v4.b32 [%0], {%1,%2,%3,%4}, [%5];}"
               ::"r"(a), "r"(__shfl_sync(~0u, w, s)), "r"(__shfl_sync(~0u, w, s + 8)), "r"(__shfl_sync(~0u, w, s + 16)), "r"(__shfl_sync(~0u, w, s + 24)),
                 "r"(bar), "r"(off) : "memory");
}
__device__ __forceinline__ float sum8(uint32_t a) {
  const float4 p = lds16(a), q = lds16(a + 1024);
  return ((p.x + p.y) + (p.z + p.w)) + ((q.x + q.y) + (q.z + q.w));
}
__device__ __forceinline__ int posof(int c) { return (c & ~14) + 2 * (c & 6) + ((c >> 2) & 2); }

__global__ void __cluster_dims__(8, 1, 1) __launch_bounds__(384, 1)
fused_kernel(const bf16* __restrict__ x, const bf16* __restrict__ cvec, const bf16* __restrict__ w_mod, bf16* __restrict__ out,
             Scratch* __restrict__ scr, const __grid_constant__ Sched sch, const __grid_constant__ TMaps tms) {
  extern __shared__ __align__(1024) unsigned char smem[];
  const int tid = threadIdx.x, lane = tid & 31;
  const int b = blockIdx.x, cl = b >> 3, rn = b & 7, rk = b & 1, hd = b >> 1, f = b - 64;
  const bool isA = b < 64;
  uint32_t sb = s2u(smem), bar0 = sb + O_BAR;
  const int g = lane >> 2, tq = lane & 3;
  const int arow = 64 * rn + ((tid & 255) >> 4);
  uint4 wm[4];
  uint32_t cw, xw;
  if (tid < 256 && isA) {
    const bf16* wa = w_mod + (size_t)arow * 3072 + (lane & 8) * 64 + 64 * cl + 8 * (lane & 7);
#pragma unroll
    for (int i = 0; i < 4; i++) wm[i] = ldx16(wa + i * 16 * 3072);
    cw = ldc4(cvec + (arow & ~1) + 16 * tq);
    if (tid < 64) xw = ldc4(x + 64 * cl + (tid & 62));
  }
  unsigned gt_start;
  asm volatile("mov.u32 %0, %%globaltimer_lo;" : "=r"(gt_start));
  const int warp = __shfl_sync(~0u, tid >> 5, 0);
  if (warp == 11) {
    if (lane == 0) {
#pragma unroll
      for (int i = 0; i < B_EMPTY; i++) BAR_INIT(i, 1);
    }
    __syncwarp();
    asm volatile("fence.mbarrier_init.release.cluster;" ::: "memory");
    asm volatile("barrier.cluster.arrive.relaxed.aligned;" ::: "memory");
    if (isA) {
#pragma unroll 1
      for (int i = 0; i < 8; i++) {
        if (i >= 6) mbar_wait(bar0 + 8 * (i - 6));
        wait_until(gt_start + ((64 * i + b) * sch.dth >> 8));
        if (lane == 0) {
          BAR_ARM(i, 16384);
          tma3d(sb + i * 16384, &tms.m[i >> 2], bar0 + 8 * i, 0, i < 4 ? 128 * i : 256 * rk + 64 * (i - 4), i < 4 ? b : b & ~1);
        }
        __syncwarp();
      }
    }
  }
  if (warp == 10) {
    const unsigned ep = ldc4(&scr->cnt[0]);
    if (isA) {
      const uint4 xa = ldc16(x + 16 * lane), xb = ldc16(x + 16 * lane + 8);
      float xv[16] = {bflo(xa.x), bfhi(xa.x), bflo(xa.y), bfhi(xa.y), bflo(xa.z), bfhi(xa.z), bflo(xa.w), bfhi(xa.w),
                      bflo(xb.x), bfhi(xb.x), bflo(xb.y), bfhi(xb.y), bflo(xb.z), bfhi(xb.z), bflo(xb.w), bfhi(xb.w)};
      const float x0 = __shfl_sync(~0u, xv[0], 0);
      float s = 0, q = 0;
#pragma unroll
      for (int i = 0; i < 16; i++) { xv[i] -= x0; s += xv[i]; q += xv[i] * xv[i]; }
#pragma unroll
      for (int o = 16; o; o >>= 1) { s += __shfl_xor_sync(~0u, s, o); q += __shfl_xor_sync(~0u, q, o); }
      s *= 1.f / 512.f;
      float rstd;
      asm("rsqrt.approx.ftz.f32 %0, %1;" : "=f"(rstd) : "f"(fmaxf(q * (1.f / 512.f) - s * s, 0.f) + 1e-5f));
      *(float2*)(smem + O_SM + 1024) = make_float2(s + x0, rstd);
    }
    if (lane == 0) *(volatile unsigned*)(smem + O_EP) = ep;
    nbar_arrive(1, 288);
  }
  const int cls = isA ? (b >= NBIG) : 2, v0 = isA ? 2 : 0;
  if (warp >= 8) {
    asm volatile("setmaxnreg.dec.sync.aligned.u32 56;");
    if (warp == 8) {
      if (lane < 8) asm volatile("prefetch.tensormap [%0];" ::"l"(&tms.m[lane + 1]) : "memory");
      if ((sb & 0xFFFFFF) != SMEM_BASE) __trap();
    } else if (warp == 9) {
      if (lane == 0) {
#pragma unroll
        for (int i = B_EMPTY; i < B_LZ; i++) BAR_INIT(i, 8);
        BAR_INIT(B_LZ, 8); BAR_INIT(B_Q2, 9); BAR_ARM(B_Q2, 1024);
        BAR_INIT(B_H, 1); BAR_INIT(B_QF, 1); BAR_ARM(B_QF, 32768);
        BAR_INIT(B_TAB, 1); BAR_INIT(B_W, 1); BAR_INIT(B_ST, 8); BAR_INIT(B_WZ, 1); BAR_INIT(B_HZ, 1); BAR_ARM(B_HZ, isA ? 1024 : 512); BAR_INIT(B_G, 1); BAR_INIT(B_G2, 1);
      }

    }
    if (warp != 11) {
      __syncwarp();
      asm volatile("fence.mbarrier_init.release.cluster;" ::: "memory");
      __threadfence_block();
      asm volatile("barrier.cluster.arrive.relaxed.aligned;" ::: "memory");
    }
    asm volatile("barrier.cluster.wait.acquire.aligned;" ::: "memory");
    if (warp == 8) {
      const int nr = sch.nr[cls], vl = v0 + sch.nt[cls] - 1;
      unsigned long long hist = 0;
      int v = v0;
#pragma unroll 1
      for (int rd = 0; rd < nr; rd++) {
        const uint2 e = sch.r[cls][rd];
        const int type = e.y & 15, win = (e.y >> 4) & 15, pos = b + 64 - (int)((e.y >> 8) & 255), tile = e.y >> 16;
        const bool mod = type == T_MOD;
        const int ni = mod ? 1 : type == T_DN ? 2 : 4;
        unsigned t = gt_start + (e.x & 0xffff) + (pos * sch.dt >> 8);
        const int c0 = mod ? 1024 + 32 * b : type == T_WO || type == T_DN ? 64 * rn : type == T_GU ? 32 * f : 0;
        int c1 = type == T_KV ? 64 * (tile + pos) : 0;
        int c2 = mod ? tile : type == T_WO ? 4 * cl : type == T_DN ? 2 * cl - 16 : type == T_UV ? b : 0;
        const int i1 = type == T_UV ? 128 : 0;
#pragma unroll 1
        for (int j = 0; j < ni; j++) {
          const int slot = mod ? B_FM + tile : (v & 1) * 4 + j;
          if (mod ? tile : v >= 2) mbar_wait(bar0 + 8 * (B_EMPTY + (mod ? (vl & 1) * 4 : slot)), mod ? (vl >> 1) & 1 : ((v >> 1) - 1) & 1);
          const int hw = (int)(hist >> (6 * (win - 1))) & 63;
          if (hw) mbar_wait(bar0 + 8 * (hw & 15), (hw >> 4) & 1);
          wait_until(t);
          if (lane == 0) {
            BAR_ARM(slot, 16384);
            tma3d(sb + (mod ? (tile ? O_Q : O_X) : slot * 16384), &tms.m[type == T_GU ? type + (j & 1) : type], bar0 + 8 * slot, c0, c1, c2);
          }
          __syncwarp();
          hist = hist << 6 | (32 | (mod ? 0 : (v & 2) << 3) | slot);
          t += e.x >> 16; c1 += i1;
          c2 += type == T_KV ? 2 : type == T_WO || type == T_DN ? 1 : type == T_GU ? j & 1 : 0;
        }
        v += !mod;
      }
      return;
    }
    const unsigned epoch = *(volatile unsigned*)(smem + O_EP), par = (epoch + 1) & 1;
    if (warp == 10) {
      if (isA) {
        for (int it = 0; ldx4(scr->cnt + 1) != (epoch + 1) * 128 && it < SPIN_MAX; it++) {}
        if (lane == 0) BAR_ARRIVE(B_H);
      } else mbar_wait(bar0);
      if (!(rn & (QN - 1))) {
        for (int it = 0; ldx4(scr->cnt + 32 + 32 * (rn >> 2)) != (epoch + 1) * 32 && it < SPIN_MAX; it++) {}
        if (lane == 0)
          asm volatile("cp.async.bulk.shared::cluster.global.mbarrier::complete_tx::bytes.multicast::cluster [%0], [%1], %4, [%2], %3;"
                       ::"r"(sb + O_Q + rn * 4096), "l"(scr->qa + rn * 256), "r"(bar0 + 8 * B_QF), "h"((unsigned short)0xff), "n"(4096 * QN) : "memory");
      }
      const unsigned dl = isA ? sch.d4 : sch.d6;
      unsigned tw = gt_start + sch.t4;
      if (!isA) {
        const int nt = sch.nt[2];
#pragma unroll 1
        for (int t = 0; t < nt; t++) mbar_wait(bar0 + 8 * B_EMPTY + (t & 1) * 32, (t >> 1) & 1);
        unsigned long long now;
        asm volatile("mov.u64 %0, %%globaltimer;" : "=l"(now));
        LANE0("red.relaxed.gpu.global.max.u64", scr->cnt + 130, "l", now);
        CNT_ADD(128);
        tw = (unsigned)now + 1700;
      }
      sleep_until(tw);
      uint4 an;
      for (int it = 0; an = ldx16(scr->cnt + 128), an.x != (epoch + 1) * 56 && it < SPIN_MAX; it++) {}
      wait_until(an.z + (dl >> 16));
      if (lane == 0) BAR_ARRIVE(B_G2);
      wait_until(an.z + (dl & 0xffff));
      if (lane == 0) BAR_ARRIVE(B_G);
    } else if (warp == 11) {
      {
        uint2* ph = scr->hdr + ((lane & 24) + 2 * tq + (g & 1)) * 16 + cl;
        const bool own = (lane >> 4) * 4 + tq == rn;
        if (own) { stx8(ph, make_uint2(par ^ 1, 0)); if (cl == 14) stx8(ph + 1, make_uint2(0, 0)); }
        uint32_t a_w = sb + O_HW + ((lane >> 4) * 4 + tq) * 128 + (g & 1) * 64 + ((lane >> 1) & 4);
        PIN(a_w); PINL(ph);
        const int vt = v0 + sch.nt[cls];
#pragma unroll 1
        for (int t = 0; t < vt; t++) mbar_wait(bar0 + 8 * B_EMPTY + (t & 1) * 32, (t >> 1) & 1);
        float hz[8], M;
        uint32_t wp[4];
#pragma unroll 1
        for (int e = 0; e < 2; e++) {
          POLL {
            unsigned ok = 1;
#pragma unroll
            for (int u = 0; u < 8; u++)
              asm volatile("ld.relaxed.cluster.shared.f32 %0, [%1];" : "=f"(hz[u]) : "r"(sb + O_HZ + e * 1024 + u * 128 + lane * 4) : "memory");
#pragma unroll
            for (int u = 0; u < 4; u++) ok = and3(ok, __float_as_uint(hz[u]), __float_as_uint(hz[u + 4]));
            RETRY(~ok)
          }
          if (e) break;
          M = fmaxf(fmaxf(fmaxf(hz[0], hz[1]), fmaxf(hz[2], hz[3])), fmaxf(fmaxf(hz[4], hz[5]), fmaxf(hz[6], hz[7])));
          M = u2f(fbits(M));
#pragma unroll
          for (int u = 0; u < 4; u++) {
            wp[u] = pack2(ex2(hz[u] - M), ex2(hz[u + 4] - M));
            sts4(a_w + ((rn - u) & 3) * 8, u2f(wp[u])); sts4(a_w + ((rn - u) & 3) * 8 + 32, u2f(wp[u]));
          }
          __syncwarp();
          if (lane == 0) BAR_ARRIVE(B_WZ);
        }
        float L = 0.f;
#pragma unroll
        for (int u = 0; u < 4; u++) L += bflo(wp[u]) * hz[u] + bfhi(wp[u]) * hz[u + 4];
        if (own) pub8(ph, __float_as_uint(M) | 1u, __float_as_uint(L));
      }
      if (isA) {
        mbar_wait(bar0 + 8 * B_G2);
        unsigned long long hh;
        POLL { hh = ldx64(scr->hdr + hd * 16 + (lane & 15)); RETRY((lane & 15) == 15 ? 0u : (unsigned)hh ^ par) }
        const float m = (lane & 15) == 15 ? -1e30f : u2f((unsigned)hh);
        int mi = __float_as_int(m);
        mi ^= (mi >> 31) & 0x7fffffff;
        mi = __reduce_max_sync(~0u, mi);
        mi ^= (mi >> 31) & 0x7fffffff;
        const float w = ex2(m - __int_as_float(mi));
        float L = w * u2f(hh >> 32);
#pragma unroll
        for (int o2 = 8; o2; o2 >>= 1) L += __shfl_xor_sync(~0u, L, o2);
        sts4(sb + O_SM + (384 + 2 * (lane & 6) + ((lane >> 2) & 2) + (lane & 1)) * 4, w * rcp(L));
        __syncwarp();
        if (lane == 0) BAR_ARRIVE(B_W);
      }
    } else {
#pragma unroll 4
      for (int i = 0; i < 72; i++) sts16(sb + O_LZ + i * 512 + lane * 16, make_uint4(0, 0, 0, 0));
      __syncwarp();
      if (lane < 8) asm volatile("mbarrier.arrive.release.cluster.shared::cluster.b64 _, [%0];" ::"r"(mapa(bar0 + 8 * B_LZ, lane)) : "memory");
      if (isA) {
        mbar_wait(bar0 + 8 * B_QF);
#pragma unroll 2
        for (int k = 0; k < 8; k++) {
          const uint32_t cp = ldc4(cvec + 2 * (lane + 32 * k));
          *(uint32_t*)(smem + O_SILU + (lane + 32 * k) * 4) = pack2(silu_bf(bflo(cp)), silu_bf(bfhi(cp)));
        }
        __syncwarp();
        uint32_t ab = sb + O_X + (8 * (lane >> 4) + (lane & 7)) * 64 + ((((lane >> 3) & 1) ^ ((lane >> 1) & 3)) << 4);
        float d[4][4] = {};
#pragma unroll 1
        for (int jm = 0; jm < 2; jm++) {
          mbar_wait(bar0 + 8 * (B_FM + jm));
#pragma unroll 2
          for (int s2 = 0; s2 < 8; s2++)
#pragma unroll
            for (int s = 0; s < 2; s++) {
              uint32_t a0[4], a1[4];
              const uint32_t* ps = (const uint32_t*)(smem + O_SILU) + 128 * jm + 16 * s2 + 8 * s + tq;
              ldsm_t(a0, ab + (2 * s2 + s) * 1024); ldsm_t(a1, (ab + (2 * s2 + s) * 1024) ^ 32);
              mma16(d[s], a0, ps[0], ps[4]); mma16(d[2 + s], a1, ps[0], ps[4]);
            }
          ab -= O_X - O_Q;
        }
        const float t0 = (tq & 1) ? d[0][2] + d[1][2] : d[0][0] + d[1][0], t1 = (tq & 1) ? d[2][2] + d[3][2] : d[2][0] + d[3][0];
        stx4(scr->xm + b * 32 + posof(8 * tq + g), fbits(bfr(bfr((tq & 2) ? t1 : t0) + ((b >> 4) == 2 ? 1.f : 0.f))));
        __syncwarp();
        CNT_ADD(96);
      } else sleep_until(gt_start + sch.t4);
      for (int it = 0; ldx4(scr->cnt + 96) != (epoch + 1) * 64 && it < SPIN_MAX; it++) __nanosleep(NSL);
      if (isA) {
        unsigned long long ga;
        POLL { ga = ldx64(scr->xm + 64 * rn + 2 * lane); RETRY(lop_x3((unsigned)ga, ga >> 32, par)) }
        *(float2*)(smem + O_SM + (320 + 2 * lane) * 4) = make_float2(bfhi((unsigned)ga), bfhi(ga >> 32));
      }
      __syncwarp();
      if (lane == 0) BAR_ARRIVE(B_TAB);
    }
    return;
  }

  float* s_sm = (float*)(smem + O_SM);
  unsigned par, epoch;
  asm volatile("barrier.cluster.arrive.relaxed.aligned;" ::: "memory");
  if (isA) {
    float* s_r = (float*)(smem + O_R);
    float acc[8] = {0, 0, 0, 0, 0, 0, 0, 0};
    const float sl = silu_bf((arow & 1) ? bfhi(cw) : bflo(cw));
#pragma unroll
    for (int i = 0; i < 4; i++) fma8(acc, wm[i], __shfl_sync(~0u, sl, i, 4));
    tred<4>(acc, lane, 16);
    *(float4*)(s_r + warp * 128 + 8 * (lane & 15) + ((lane >> 2) & 4)) = make_float4(acc[0], acc[1], acc[2], acc[3]);
    nbar(1, 288);
    epoch = *(volatile unsigned*)(smem + O_EP);
    par = (epoch + 1) & 1;
    if (warp < 2) {
      float t = 0.f, ca = rn == 0 ? 1.f : 0.f;
#pragma unroll
      for (int w = 0; w < 8; w++) { t += s_r[w * 128 + tid]; ca += s_r[w * 128 + 64 + tid]; }
      t += ca * ((((tid & 1) ? bfhi(xw) : bflo(xw)) - s_sm[256]) * s_sm[257]);
      const float nb = __shfl_down_sync(~0u, t, 1);
      const uint32_t w0 = lane < 8 ? pack2t(t, nb, par) : pack2(t, nb);
      const uint32_t w1 = __shfl_down_sync(~0u, w0, 8), w2 = __shfl_down_sync(~0u, w0, 16), w3 = __shfl_down_sync(~0u, w0, 24);
      if (lane < 8 && !(lane & 1)) stx16(scr->h + (rn >> 1) * 512 + (2 * cl + warp) * 32 + rk * 16 + 2 * lane, make_uint4(w0, w1, w2, w3));
      __syncwarp();
      CNT_ADD(1);
    }
    asm volatile("barrier.cluster.wait.acquire.aligned;" ::: "memory");
    const uint32_t rsb = mapa(sb, rn ^ 1);
    {
      uint32_t a[4][4][4];
      mbar_wait(bar0 + 8 * (warp >> 1));
      const uint32_t ab = sb + (64 * warp + 8 * (lane >> 4) + (lane & 7)) * 128;
#pragma unroll
      for (int s = 0; s < 4; s++)
#pragma unroll
        for (int mt = 0; mt < 4; mt++) ldsm_t(a[s][mt], ab + s * 2048 + (((2 * mt + ((lane >> 3) & 1)) ^ (lane & 7)) << 4));
      arrive_n(bar0 + 8 * (B_EMPTY + (warp >> 1)), lane == 0, 4 + (dep16(&a[0][0][0]) & sch.zero));
      uint4 v0, v1;
      const unsigned* ph = scr->h + (g >> 1) * 512 + 64 * warp + 4 * (lane & 7);
      uint32_t off = O_B + warp * 272 + (32 * rk + 8 * tq + (lane & 4)) * 4;
      PIN(off); PINL(ph);
      mbar_wait(bar0 + 8 * B_H);
      POLL { v0 = ldx16(ph); v1 = ldx16(ph + 32); RETRY(lop_x3(v0.x, v1.x, par)) }
      float d[4][4] = {};
#pragma unroll
      for (int mt = 0; mt < 4; mt++) {
        mma16(d[mt], a[0][mt], v0.x, v0.y); mma16(d[mt], a[1][mt], v0.z, v0.w);
        mma16(d[mt], a[2][mt], v1.x, v1.y); mma16(d[mt], a[3][mt], v1.z, v1.w);
      }
      float r[8];
#pragma unroll
      for (int mt = 0; mt < 4; mt++) { r[2 * mt] = d[mt][0] + d[mt][1]; r[2 * mt + 1] = d[mt][2] + d[mt][3]; }
      tred<4>(r, lane, 2); tred<2>(r, lane, 1);
      const float rc = __shfl_xor_sync(~0u, (lane & 4) ? r[0] : r[1], 4);
      const uint32_t wd = (lane & 4) ? pack2(rc, r[1]) : pack2(r[0], rc);
      const uint32_t w1 = __shfl_down_sync(~0u, wd, 8), w2 = __shfl_down_sync(~0u, wd, 16), w3 = __shfl_down_sync(~0u, wd, 24);
      asm volatile("{.reg .pred p; setp.lt.s32 p, %7, 8; @p st.shared.v4.b32 [%0], {%2,%3,%4,%5};\n"
                   "@p st.async.shared::cluster.mbarrier::complete_tx::bytes.v4.b32 [%1], {%2,%3,%4,%5}, [%6];}"
                   ::"r"(sb + off), "r"(rsb + off), "r"(wd), "r"(w1), "r"(w2), "r"(w3), "r"(rsb + O_BAR + 8 * B_Q2), "r"(lane) : "memory");
      __syncwarp();
      arrive_n(bar0 + 8 * B_Q2, lane == 0, 1);
    }
    {
      uint32_t a[2][8][4];
      uint32_t a_bq = sb + O_B + (lane & 7) * 272 + (lane >> 3) * 16;
      uint4* p_qa = scr->qa + (4 * rk + (warp >> 1)) * 256 + hd * 8 + ((4 * (warp & 1) + tq) ^ (hd & 7));
      PIN(a_bq); PINL(p_qa);
      mbar_wait(bar0 + 8 * (4 + (warp >> 1)));
      const uint32_t ab = sb + 65536 + (warp >> 1) * 16384 + (32 * (warp & 1) + (lane & 15)) * 128;
#pragma unroll
      for (int i = 0; i < 16; i++) ldsm(a[i >> 3][i & 7], ab + (i >> 3) * 2048 + ((i >> 2) & 1) * 8192 + (((2 * (i & 3) + (lane >> 4)) ^ (lane & 7)) << 4));
      arrive_n(bar0 + 8 * (B_EMPTY + 4 + (warp >> 1)), lane == 0, 4 + (dep16(&a[0][0][0]) & sch.zero));
      mbar_wait(bar0 + 8 * B_Q2);
      float d[4][4] = {};
#pragma unroll
      for (int y = 0; y < 4; y++) {
        uint32_t bq[4];
        ldsm(bq, a_bq + 64 * y);
#pragma unroll
        for (int mt = 0; mt < 2; mt++) { mma16(d[2 * mt], a[mt][2 * y], bq[0], bq[1]); mma16(d[2 * mt + 1], a[mt][2 * y + 1], bq[2], bq[3]); }
      }
      float r[4];
#pragma unroll
      for (int i = 0; i < 4; i++) r[i] = (d[i & 2][2 * (i & 1)] + d[i & 2][2 * (i & 1) + 1]) + (d[(i & 2) + 1][2 * (i & 1)] + d[(i & 2) + 1][2 * (i & 1) + 1]);
      tred<2>(r, lane, 2); tred<1>(r, lane, 1);
      const float nb = __shfl_xor_sync(~0u, r[0], 4);
      const uint32_t w0 = (lane >> 3) == (hd & 3) ? pack2t(r[0], nb, par) : pack2(r[0], nb);
      const uint32_t w1 = __shfl_down_sync(~0u, w0, 8), w2 = __shfl_down_sync(~0u, w0, 16), w3 = __shfl_down_sync(~0u, w0, 24);
      if (lane < 4) stx16(p_qa, make_uint4(w0, w1, w2, w3));
      if (warp) nbar_arrive(3, 256); else { nbar(3, 256); CNT_ADD(32 + 32 * rk); }
    }
  } else {
    nbar(1, 288);
    epoch = *(volatile unsigned*)(smem + O_EP);
    par = (epoch + 1) & 1;
    asm volatile("barrier.cluster.wait.acquire.aligned;" ::: "memory");
    mbar_wait(bar0);
  }
  asm volatile("setmaxnreg.inc.sync.aligned.u32 224;");
  uint2* p_rec = scr->rec + ((16 * (warp >> 2) + 2 * (warp & 3) + (g & 1) + 4 * (tq & 2)) * 32 + 4 * rn + (tq & 1)) * 64 + cl * 4 + (g >> 1);
  PINL(p_rec);
  {
    const unsigned inv = par ^ 1;
#pragma unroll
    for (int q = 0; q < 2; q++) { stx8(p_rec + q * 128, make_uint2(inv, 0)); if (cl == 14) stx8(p_rec + q * 128 + 4, make_uint2(0, 0)); }
    if (isA) { if (warp < 2) { stx4(scr->xao + b * 64 + tid, inv); stx4(scr->xab + cl * 256 + (2 * (rn & 3) + warp) * 32 + (rn >> 2) * 16 + (lane >> 1), inv); } }
    else if (f == 0) { stx4(out + 2 * tid, 0); __threadfence(); }
  }
  sb = __shfl_sync(~0u, sb, 0); bar0 = sb + O_BAR;
  const int nt = sch.nt[cls], wg = warp >> 2;
  uint32_t a_z[4];
#pragma unroll
  for (int u = 0; u < 4; u++) {
    const int s3 = (rn - u - (lane >> 1 & 1)) & 3;
    a_z[u] = sb + O_LZ + (s3 + 4 * (lane & 1)) * 4096 + wg * 512 + g * 64 + (((warp & 3) ^ (s3 & 1) ^ (2 * (lane & 1))) << 4);
    PIN(a_z[u]);
  }
  uint32_t z[4][4], a_w = sb + O_HW + warp * 128 + (g & 1) * 64 + (tq & 1) * 8;
  PIN(a_w);
  {
    const float sc = 0.08838834764831845f * 1.4426950408889634f;
    float mrun = -1e30f;
    float o[4][16], sx[16], mref[8];
#pragma unroll
    for (int k = 0; k < 16; k++) { o[0][k] = o[1][k] = o[2][k] = o[3][k] = sx[k] = 0.f; mref[k >> 1] = -1e30f; }
    const int key = 16 * warp + (lane & 15);
    uint32_t a_p = sb + O_P + key * 64 + (((lane >> 4) ^ ((key >> 1) & 3)) << 4);
    uint32_t a_v = sb + wg * 32768 + (8 * (lane >> 4) + (lane & 7)) * 128 + (((2 * (warp & 3) + ((lane >> 3) & 1)) ^ (lane & 7)) << 4);
    const int rot = rn + warp;
    const int qown = wg == (rn >> 2) ? -warp & 3 : -1;
    uint32_t a_own = sb + O_LZ + rn * 4096 + (warp & 3) * 1024 + g * 64 + ((tq ^ (rn & 1) ^ ((rn >> 1) & 2)) << 4);
    PIN(a_own);
    unsigned long long dst[4];
#pragma unroll
    for (int q = 0; q < 4; q++) {
      dst[q] = mapg(a_own, 4 * wg + ((q + rot) & 3));
      PINL(dst[q]);
    }
    unsigned long long a_h = mapg(sb + O_HZ + wg * 1024 + rn * 128 + lane * 4, 2 * (warp & 3));
    unsigned long long a_h1 = mapg(sb + O_HZ + wg * 1024 + rn * 128 + lane * 4, 2 * (warp & 3) + 1);
    PIN(a_p); PIN(a_v); PINL(a_h); PINL(a_h1);
    uint32_t rel = lane < 4 && lane >= 2 * wg ? 2 - (tq >> 1) : 0;
    PIN(rel);
    uint32_t ones[4] = {0x3F803F80u, 0x3F803F80u, 0x3F803F80u, 0x3F803F80u};
    PIN(ones[0]); PIN(ones[1]); PIN(ones[2]); PIN(ones[3]);
    {
      asm volatile("{.reg .pred p; .reg .u32 n; mov.u32 n, 0;\n"
                   "W%=: mbarrier.try_wait.parity.acquire.cluster.shared::cta.b64 p, [%0], 0; add.u32 n, n, 1; setp.lt.and.u32 p, n, 0x100000, !p; @p bra W%=;}"
                   ::"r"(bar0 + 8 * B_LZ) : "memory");
      mbar_wait(bar0 + 8 * B_QF);
      unsigned bad = 0;
#pragma unroll
      for (int k = 0; k < 8; k++) bad |= __float_as_uint(lds4(sb + O_Q + k * 4096 + tid * 16 + (lane >> 3) * 4)) ^ par;
      if (__builtin_expect(__any_sync(~0u, bad & 1), 0)) {
#pragma unroll 1
        for (int k = 0; k < 8; k++) {
          uint4 v;
          POLL { v = ldx16(scr->qa + k * 256 + tid); RETRY(((lane & 16) ? ((lane & 8) ? v.w : v.z) : ((lane & 8) ? v.y : v.x)) ^ par) }
          sts16(sb + O_Q + k * 4096 + tid * 16, v);
        }
        asm volatile("fence.proxy.async.shared::cta;" ::: "memory");
      }
      if (warp >= 4) nbar_arrive(1, 256); else nbar(1, 256);
    }
#pragma unroll 1
    for (int t = 0; t < nt; t++) {
      const int v = v0 + t;
      const uint32_t fb = bar0 + (v & 1) * 32, ph = (v >> 1) & 1, av = a_v + (v & 1) * 65536;
      uint32_t vf[4][4][4], cnt;
      auto landed = [&]() {
        cnt = rel + (dep16(&vf[0][0][0]) & (nt >> 8));
        PIN(cnt);
      };
      if (wg == 0) {
        const uint32_t da = DSC + (v & 1) * 4096, db = DSC + O_Q / 16;
#pragma unroll 1
        for (int j = 0; j < 4; j++) {
          mbar_wait(fb + 8 * j, ph);
          asm volatile("wgmma.fence.sync.aligned;" ::: "memory");
#pragma unroll
          for (int k = 0; k < 8; k++)
            wgmma32<0, 0, HI128, HI128>(sx, da + j * 1024 + (k >> 2) * 512 + (k & 3) * 2, db + j * 512 + (k >> 2) * 256 + (k & 3) * 2, k ? 1 : j);
          asm volatile("wgmma.commit_group.sync.aligned;" ::: "memory");
          if (j == VJ) {
#pragma unroll
            for (int i = 0; i < 16; i++) ldsm_t(vf[i >> 2][i & 3], av + (((i >> 2) + rot) & 3) * 8192 + (i & 3) * 2048);
            nbar(5, 256);
            landed();
          }
        }
      } else {
        nbar_arrive(5, 256);
#pragma unroll 1
        for (int j = 0; j < 2; j++) {
          mbar_wait(fb + 16 + 8 * j, ph);
          if (j) spin_until(clock() + VDLY);
#pragma unroll
          for (int q = 0; q < 4; q++)
            if (((q + rot) & 2) == 2 * j)
#pragma unroll
              for (int k = 0; k < 4; k++) ldsm_t(vf[q][k], av + ((q + rot) & 3) * 8192 + k * 2048);
        }
        cnt = 0;
      }
      auto scores = [&]() {
        wg_wait<0>(sx);
        asm volatile("{.reg .pred p; setp.ne.s32 p, %1, 0; @p mbarrier.arrive.shared::cta.b64 _, [%0], %1;}" ::"r"(fb + 8 * B_EMPTY + 8 * tq), "r"(cnt) : "memory");
        cnt = 0;
      };
      int ex = t == 0;
#pragma unroll 1
      for (int pass = 0;; pass++) {
        if (ex) {
          scores();
          int ln;
          asm volatile("mov.u32 %0, %%laneid;" : "=r"(ln));
          const uint32_t a_pm = sb + O_SM + ln * 16;
          if (wg == 0) {
            float cm[8];
#pragma unroll
            for (int i = 0; i < 8; i++) cm[i] = fmaxf(sx[2 * (i & 6) + (i & 1)], sx[2 * (i & 6) + (i & 1) + 2]);
            tmax<4>(cm, lane, 16); tmax<2>(cm, lane, 8); tmax<1>(cm, lane, 4);
            sts4(a_pm + warp * 4, cm[0] * sc);
          }
          nbar(4, 256);
          const float4 pm = lds16(a_pm);
          const float mn = u2f(__float_as_uint(fmaxf(fmaxf(fmaxf(pm.x, pm.y), fmaxf(pm.z, pm.w)), mrun)) | 1u), al = ex2(mrun - mn);
          mrun = mn;
#pragma unroll
          for (int i = 0; i < 8; i++) {
            const float a = __shfl_sync(~0u, al, 4 * i + (ln & 3)), aw = wg ? a : 1.f;
            mref[i] = __shfl_sync(~0u, mn, 4 * i + (ln & 3));
#pragma unroll
            for (int e = 0; e < 2; e++) {
              const int k = 2 * (i & 6) + (i & 1) + 2 * e;
              o[0][k] *= a; o[1][k] *= a; o[2][k] *= a; o[3][k] *= a; sx[k] *= aw;
            }
          }
          pass = 1;
        }
        scores();
        ex = 0;
        if (wg == 0) {
          uint32_t pk[8];
#pragma unroll
          for (int i = 0; i < 8; i++) pk[i] = pack2(ex2(sx[2 * i] * sc - mref[i & 6]), ex2(sx[2 * i + 1] * sc - mref[(i & 6) + 1]));
          asm volatile("stmatrix.sync.aligned.m8n8.x4.shared.b16 [%0], {%2,%3,%4,%5};\n"
                       "stmatrix.sync.aligned.m8n8.x4.shared.b16 [%1], {%6,%7,%8,%9};"
                       ::"r"(a_p), "r"(a_p ^ 32), "r"(pk[0]), "r"(pk[1]), "r"(pk[2]), "r"(pk[3]), "r"(pk[4]), "r"(pk[5]), "r"(pk[6]), "r"(pk[7]) : "memory");
          const uint32_t mx = __vmaxu2(__vmaxu2(__vmaxu2(pk[0], pk[1]), __vmaxu2(pk[2], pk[3])), __vmaxu2(__vmaxu2(pk[4], pk[5]), __vmaxu2(pk[6], pk[7])));
          ex = max(mx, mx << 16) > (127u + TAU) << 23;
          asm volatile("fence.proxy.async.shared::cta;" ::: "memory");
        }
        asm volatile("{.reg .pred p, q; setp.ne.s32 q, %0, 0; bar.red.or.pred p, 4, 256, q; selp.s32 %0, 1, 0, p;}" : "+r"(ex)::"memory");
        if (!ex || pass) break;
      }
      float hv = mrun;
      if (wg) {
        asm volatile("wgmma.fence.sync.aligned;" ::: "memory");
#pragma unroll
        for (int k = 0; k < 4; k++) wgmma32r(sx, ones, DSC + O_P / 16 + k * 64);
        asm volatile("wgmma.commit_group.sync.aligned;" ::: "memory");
        landed();
        asm volatile("{.reg .pred p; setp.ne.s32 p, %1, 0; @p mbarrier.arrive.shared::cta.b64 _, [%0], %1;}" ::"r"(fb + 8 * B_EMPTY + 8 * tq), "r"(cnt) : "memory");
        wg_wait<0>(sx);
        float lv[4];
#pragma unroll
        for (int j = 0; j < 4; j++) lv[j] = (lane & 4) ? sx[4 * j + 1] : sx[4 * j];
        hv = (lane & 16) ? ((lane & 8) ? lv[3] : lv[2]) : ((lane & 8) ? lv[1] : lv[0]);
      }
      asm volatile("{.reg .pred p; setp.eq.s32 p, %3, %4; @p st.relaxed.cluster.b32 [%0], %1; @p st.relaxed.cluster.b32 [%2], %1;}"
                   ::"l"(a_h), "r"(__float_as_uint(hv) | 1u), "l"(a_h1), "r"(t), "r"(nt - 1) : "memory");
#pragma unroll
      for (int q = 0; q < 4; q++) {
        if (q < 2) {
          asm volatile("wgmma.fence.sync.aligned;" ::: "memory");
#pragma unroll
          for (int u = q; u < (q ? 4 : 1); u++) {
#pragma unroll
            for (int k = 0; k < 4; k++) wgmma32r(o[u], vf[u][k], DSC + O_P / 16 + k * 64);
            asm volatile("wgmma.commit_group.sync.aligned;" ::: "memory");
          }
        }
        if (q == 3) {
#pragma unroll
          for (int u = 0; u < 4; u++)
            asm volatile("{.reg .pred p; setp.eq.s32 p, %5, %6; @p ldmatrix.sync.aligned.m8n8.x4.trans.shared.b16 {%0,%1,%2,%3}, [%4];}"
                         : "=r"(z[u][0]), "=r"(z[u][1]), "=r"(z[u][2]), "=r"(z[u][3]) : "r"(a_z[u] + u * 1024), "r"(t), "r"(nt - 1) : "memory");
        }
        if (q == 1) wg_wait<2>(o[q]); else if (q == 2) wg_wait<1>(o[q]); else wg_wait<0>(o[q]);
        if (q == 0 || t == nt - 1)
#pragma unroll
        for (int j = 0; j < 2; j++)
          asm volatile("{.reg .pred p, q, r; setp.eq.s32 p, %5, %6; setp.eq.and.s32 q|r, %7, %8, p; @r st.relaxed.cluster.v4.b32 [%0], {%1,%2,%3,%4};\n"
                       "@q st.shared.v4.b32 [%9], {%1,%2,%3,%4};}"
                       ::"l"(dst[q] + j * 512), "r"(pack2t(o[q][8 * j], o[q][8 * j + 1], 1)), "r"(pack2(o[q][8 * j + 2], o[q][8 * j + 3])),
                         "r"(pack2(o[q][8 * j + 4], o[q][8 * j + 5])), "r"(pack2(o[q][8 * j + 6], o[q][8 * j + 7])), "r"(t), "r"(nt - 1),
                         "r"(qown), "r"(q), "r"(a_own + j * 512) : "memory");
      }
    }
  }
  {
    uint32_t wx[4][4];
    mbar_wait(bar0 + 8 * B_WZ);
#pragma unroll
    for (int u = 0; u < 4; u++) {
      uint2 wp;
      asm volatile("ld.shared.v2.u32 {%0, %1}, [%2];" : "=r"(wp.x), "=r"(wp.y) : "r"(a_w + u * 8) : "memory");
      const bool lo = (g >> 1) == (tq >> 1), hi = (g >> 1) == 2 + (tq >> 1);
      wx[u][0] = lo ? wp.x : 0u; wx[u][1] = lo ? wp.y : 0u; wx[u][2] = hi ? wp.x : 0u; wx[u][3] = hi ? wp.y : 0u;
    }
    auto bad = [&]() {
      const unsigned ok = and3(and3(and3(z[0][0], z[0][1], z[0][2]), and3(z[0][3], z[1][0], z[1][1]), and3(z[1][2], z[1][3], z[2][0])),
                               and3(and3(z[2][1], z[2][2], z[2][3]), and3(z[3][0], z[3][1], z[3][2]), z[3][3]), 0x10001u);
      return __any_sync(~0u, g == 0 && ok != 0x10001u);
    };
    POLL {
      if (it_)
#pragma unroll
        for (int u = 0; u < 4; u++) ldsm_t(z[u], a_z[u] + u * 1024);
      if (!bad() || ++it_ >= SPIN_MAX) break;
    }
    float d0[8][4] = {}, d[8][4], r[8];
#pragma unroll
    for (int i = 0; i < 8; i++) mma16(d0[i], wx[i >> 1], z[i >> 1][2 * (i & 1)], z[i >> 1][2 * (i & 1) + 1]);
    POLL {
#pragma unroll
      for (int u = 0; u < 4; u++) ldsm_t(z[u], a_z[u ^ 2] + u * 1024);
#pragma unroll
      for (int i = 0; i < 8; i++) mma16c(d[i], wx[(i >> 1) ^ 2], z[i >> 1][2 * (i & 1)], z[i >> 1][2 * (i & 1) + 1], d0[i]);
      if (!bad() || ++it_ >= SPIN_MAX) break;
    }
#pragma unroll
    for (int i = 0; i < 8; i++) r[i] = (tq & 2) ? ((g & 1) ? d[i][3] : d[i][2]) : ((g & 1) ? d[i][1] : d[i][0]);
#pragma unroll
    for (int q = 0; q < 2; q++) pub8(p_rec + q * 128, pack2t(r[4 * q], r[4 * q + 1], par) | 1u, pack2(r[4 * q + 2], r[4 * q + 3]));
  }
  const int vt = v0 + nt;
  const uint32_t bufa = sb + (vt & 1) * 65536, fulla = bar0 + (vt & 1) * 32, pha = (vt >> 1) & 1, phb = ((vt + 1) >> 1) & 1;
  const uint32_t bufo = sb + ((vt + 1) & 1) * 65536, fullb = bar0 + ((vt + 1) & 1) * 32;
  uint32_t a_rs = sb + O_R + (warp >> 2) * 1024 + (16 * tq + g) * 16 + ((warp + tq) & 3) * 4;
  if (isA) {
    const int row = 16 * (warp & 6) + 8 * (warp & 1) + (lane & 16) + ((lane & 7) >> 1) + 4 * (lane & 1);
    uint32_t ab = bufa + row * 128 + ((((lane >> 3) & 1) ^ (row & 7)) << 4);
    const uint2* pr = scr->rec + (hd * 32 + warp) * 64 + lane;
    uint32_t a_cb = mapa(bar0 + 8 * B_HZ, (warp & 6) + (lane >> 4)), a_c = a_cb - (O_BAR + 8 * B_HZ - O_CTX) + (2 * rn + (warp & 1)) * 64 + tq * 16;
    uint32_t a_rl = sb + O_R + (32 * (warp & 1) + lane) * 16;
    uint32_t ao = bufo + (16 * warp + 8 * (lane >> 4) + (lane & 7)) * 128 + ((((lane >> 3) & 1) ^ (lane & 7)) << 4);
    uint32_t a_cx = sb + O_CTX + (warp >> 1) * 64 + tq * 16 + (warp & 1) * 8, a_ga = sb + O_SM + (320 + posof(tid & 63)) * 4;
    unsigned* p_ao = scr->xao + b * 64 + (tid & 63);
    unsigned* p_ab = scr->xab + cl * 256 + (2 * (rn & 3) + (warp & 1)) * 32 + (rn >> 2) * 16 + (lane >> 1);
    float xv = cl == 0 ? __bfloat162float(x[64 * rn + (tid & 63)]) : 0.f;
    unsigned p2 = lane >= 28 ? 0 : par;
    PIN(ab); PINL(pr); PIN(a_cb); PIN(a_c); PIN(a_rl); PIN(a_rs); PIN(ao); PIN(a_cx); PIN(a_ga); PINL(p_ao); PINL(p_ab); PIN(p2);
    asm volatile("" : "+f"(xv));
    uint32_t aw[4][4][4];
    auto wo = [&](const int j) {
      mbar_wait(fullb + 8 * j, phb);
#pragma unroll
      for (int mt = 0; mt < 4; mt++) ldsm_t(aw[j][mt], (ao + j * 16384) ^ (mt << 5));
    };
    {
      uint32_t a[4][4][4];
      uint2 z[4], y[4] = {};
      float d[4][4] = {}, r[8];
      mbar_wait(fulla, pha);
      POLL {
#pragma unroll
        for (int q = 0; q < 4; q++) z[q] = ldx8(pr + q * 512);
        RETRY(lop_x3(z[0].x, z[1].x, par) | lop_x3(z[2].x, z[3].x, par))
      }
#pragma unroll
      for (int q = 0; q < 4; q++) {
        if (q == 3) {
          mbar_wait(bar0 + 8 * B_G);
          if (lane < 28)
#pragma unroll
            for (int u = 0; u < 4; u++) y[u] = ldx8(pr + u * 512 + 32);
          __syncwarp();
        }
        mbar_wait(fulla + 8 * q, pha);
#pragma unroll
        for (int mt = 0; mt < 4; mt++) ldsm_t(a[q][mt], (ab + q * 16384) ^ (mt << 5));
#pragma unroll
        for (int mt = 0; mt < 4; mt++) mma16(d[mt], a[q][mt], z[q].x, z[q].y);
      }
      mbar_wait(bar0 + 8 * B_W);
      const float4 W = lds16(sb + O_SM + (384 + 4 * tq) * 4);
#pragma unroll
      for (int i = 0; i < 8; i++) { r[i] = W.x * d[i >> 1][2 * (i & 1)] + W.y * d[i >> 1][2 * (i & 1) + 1]; asm volatile("" : "+f"(r[i])); }
#pragma unroll
      for (int j = 0; j < NPE; j++) wo(j);
      POLL {
        if (it_)
#pragma unroll
          for (int u = 0; u < 4; u++) y[u] = ldx8(pr + u * 512 + 32);
#pragma unroll
        for (int mt = 0; mt < 4; mt++) d[mt][0] = d[mt][1] = d[mt][2] = d[mt][3] = 0.f;
#pragma unroll
        for (int q = 0; q < 4; q++)
#pragma unroll
          for (int mt = 0; mt < 4; mt++) mma16(d[mt], a[q][mt], y[q].x, y[q].y);
        RETRY(or3(lop_x3(y[0].x, y[1].x, p2), lop_x3(y[2].x, y[3].x, p2), 0))
      }
#pragma unroll
      for (int i = 0; i < 8; i++) r[i] = W.w * d[i >> 1][2 * (i & 1) + 1] + (W.z * d[i >> 1][2 * (i & 1)] + r[i]);
      tred<4>(r, lane, 2); tred<2>(r, lane, 1);
      sts4(a_rs, r[0]); sts4(a_rs + 128, r[1]);
      nbar(1, 256);
      send32(a_c, a_cb, sum8(a_rl), lane, lane & 12);
    }
    {
#pragma unroll
      for (int j = NPE; j < NPO; j++) wo(j);
      uint2 c[4];
      mbar_wait(bar0 + 8 * B_HZ);
#pragma unroll
      for (int j = 0; j < 4; j++) asm volatile("ld.shared.v2.u32 {%0, %1}, [%2];" : "=r"(c[j].x), "=r"(c[j].y) : "r"(a_cx + j * 256) : "memory");
      float d[4][4] = {};
#pragma unroll
      for (int j = 0; j < 4; j++) {
        if (j + 1 >= NPO && j < 3) wo(j + 1);
#pragma unroll
        for (int mt = 0; mt < 4; mt++) mma16(d[mt], aw[j][mt], c[j].x, c[j].y);
      }
      const float r0 = (tq & 2) ? ((tq & 1) ? d[3][0] : d[2][0]) : ((tq & 1) ? d[1][0] : d[0][0]);
      const float r1 = (tq & 2) ? ((tq & 1) ? d[3][2] : d[2][2]) : ((tq & 1) ? d[1][2] : d[0][2]);
      sts4(a_rs + 2048, r0); sts4(a_rs + 2048 + 128, r1);
      if (warp >= 2) nbar_arrive(2, 256);
      else {
        mbar_wait(bar0 + 8 * B_TAB);
        const float gav = lds4(a_ga);
        nbar(2, 256);
        const float t = gav * sum8(a_rl + 2048) + xv;
        asm volatile("{.reg .pred p; setp.eq.s32 p, %2, 0; @p red.relaxed.gpu.global.xor.b32 [%0], %1;}"
                     ::"l"(p_ab), "r"(pack2t(t, __shfl_down_sync(~0u, t, 1), par) | 1u), "r"(lane & 1) : "memory");
        pub4(p_ao, __float_as_uint(t) | 1u);
      }
    }
  } else {
    uint32_t af[4][4][4];
    uint32_t ab = bufa + (32 * warp + 8 * (lane >> 4) + (lane & 7)) * 64 + ((((lane >> 3) & 1) ^ ((lane >> 1) & 3)) << 4);
    uint32_t a_d = bufo + wg * 16384 + (8 * (lane >> 4) + (lane & 7)) * 128 + (((2 * (warp & 3) + ((lane >> 3) & 1)) ^ (lane & 7)) << 4);
    uint32_t a_rl = sb + O_R + lane * 16, a_st = sb + O_SM + (352 + 8 * (lane >> 4) + warp) * 4;
    const unsigned* pa = scr->xab + tid;
    uint32_t a_hb = mapa(bar0 + 8 * B_HZ, g), a_h = a_hb - (O_BAR + 8 * B_HZ - O_CTX) + rn * 64 + tq * 16;
    PIN(a_hb); PIN(a_h);
    uint32_t a_hl = sb + O_CTX + wg * 256 + tq * 16, a_t = sb + O_SM + (16 * warp + 8 * (tq & 1) + g) * 4;
    const unsigned* px = scr->xao + 64 * rn + 2 * lane;
    bf16* po = out + 64 * rn + 2 * lane;
    PIN(ab); PIN(a_d); PIN(a_rl); PINL(pa); PIN(a_rs); PIN(a_st); PINL(po); PIN(a_hl); PINL(px); PIN(a_t);
    mbar_wait(bar0 + 8 * B_TAB);
    uint2 cf;
    uint2 bb[4];
    uint2 gbw;
    POLL {
      unsigned bad = 0;
      cf = ldx8(scr->xm + 1024 + (lane & 16) * 16 + 32 * warp + posof(2 * (lane & 15)));
#pragma unroll
      for (int s = 0; s < 4; s++) {
        const uint4 w = ldx16(scr->xm + 1024 - (g & 1) * 512 + 256 * (s >> 1) + 32 * warp + 16 * (s & 1) + 4 * tq);
        bb[s] = make_uint2(__byte_perm(w.x, w.y, 0x7632), __byte_perm(w.z, w.w, 0x7632));
        bad = or3(bad, lop_x3(w.x, w.y, par), lop_x3(w.z, w.w, par));
      }
      gbw = ldx8(scr->xm + 1536 + 64 * rn + posof(2 * lane));
      RETRY(or3(bad, lop_x3(cf.x, cf.y, par), lop_x3(gbw.x, gbw.y, par)))
    }
    float e[4][4] = {};
    unsigned v[8];
    auto item = [&](const int it) {
      mbar_wait(fulla + 8 * it, pha);
#pragma unroll
      for (int i = 0; i < 4; i++) ldsm_t(af[it][i], (ab + it * 16384 + (i >> 1) * 1024) ^ ((i & 1) << 5));
    };
    auto item_mma = [&](const int it) {
#pragma unroll
      for (int i = 0; i < 4; i++) mma16(e[2 * (it & 1) + (i & 1)], af[it][i], bb[(it & 2) + (i >> 1)].x, bb[(it & 2) + (i >> 1)].y);
    };
    unsigned t3 = sch.wt;
    PIN(t3);
    item(0); item_mma(0); item(1); item_mma(1);
    mbar_wait(bar0 + 8 * B_G);
#pragma unroll
    for (int i = 0; i < 8; i++) v[i] = ldx4(pa + i * 256);
    t3 += clock();
    uint32_t have2, have3 = 0;
    do have2 = mbar_test(fulla + 16, pha); while (!have2 && (int)((unsigned)clock() - t3) < 0);
    if (have2) {
      item(2); item_mma(2);
      do have3 = mbar_test(fulla + 24, pha); while (!have3 && (int)((unsigned)clock() - t3) < 0);
      if (have3) { item(3); item_mma(3); }
    }
    float y0, y1, df[4][4], st[2];
    uint32_t bz[4][2] = {};
    auto mm = [&](const int it, const int i) { mma16(df[2 * (it & 1) + (i & 1)], af[it][i], bz[(it & 2) + (i >> 1)][0], bz[(it & 2) + (i >> 1)][1]); };
    POLL {
      if (it_)
#pragma unroll
        for (int i = 0; i < 8; i++) v[i] = ldx4(pa + i * 256);
      y0 = ((bflo(v[0]) + bflo(v[1])) + (bflo(v[2]) + bflo(v[3]))) + ((bflo(v[4]) + bflo(v[5])) + (bflo(v[6]) + bflo(v[7])));
      y1 = ((bfhi(v[0]) + bfhi(v[1])) + (bfhi(v[2]) + bfhi(v[3]))) + ((bfhi(v[4]) + bfhi(v[5])) + (bfhi(v[6]) + bfhi(v[7])));
      const uint32_t zb = pack2(y0 * u2f(cf.x), y1 * u2f(cf.y));
#pragma unroll
      for (int s = 0; s < 4; s++) {
        const uint32_t w = __shfl_sync(~0u, zb, 8 * s + (lane & 7));
        bz[s][0] = (lane & 4) ? 0u : w; bz[s][1] = (lane & 4) ? w : 0u;
      }
      st[0] = y0 + y1; st[1] = y0 * y0 + y1 * y1;
      tred<1>(st, lane, 16);
#pragma unroll
      for (int i = 0; i < 4; i++) df[i][0] = df[i][1] = df[i][2] = df[i][3] = 0.f;
      mm(0, 0); mm(0, 1); mm(1, 0); mm(1, 1);
      st[0] += shx(st[0], 8);
      mm(0, 2); mm(0, 3); mm(1, 2); mm(1, 3);
      RETRY(or3(or3(lop_x3(v[0], v[1], par), lop_x3(v[2], v[3], par), lop_x3(v[4], v[5], par)), lop_x3(v[6], v[7], par), 0))
    }
    uint2 xq[8];
    if (warp == 0)
#pragma unroll
      for (int i = 0; i < 8; i++) xq[i] = ldx8(px + i * 512);
    if (have2) { mm(2, 0); mm(2, 1); mm(2, 2); mm(2, 3); }
    st[0] += shx(st[0], 4);
    st[0] += shx(st[0], 2);
    st[0] += shx(st[0], 1);
    sts4(a_st, st[0]);
    __syncwarp();
    arrive_n(bar0 + 8 * B_ST, lane == 0, 1);
    if (!have2) { item(2); item_mma(2); mm(2, 0); mm(2, 1); mm(2, 2); mm(2, 3); }
    if (!have3) { item(3); item_mma(3); }
    mm(3, 0); mm(3, 1); mm(3, 2); mm(3, 3);
    mbar_wait(bar0 + 8 * B_ST);
    float mean, rstd;
    {
      float4 u[4];
#pragma unroll
      for (int i = 0; i < 4; i++) u[i] = lds16(sb + O_SM + (352 + 4 * i) * 4);
      mean = (((u[0].x + u[0].y) + (u[0].z + u[0].w)) + ((u[1].x + u[1].y) + (u[1].z + u[1].w))) * (1.f / 512.f);
      const float sq = (((u[2].x + u[2].y) + (u[2].z + u[2].w)) + ((u[3].x + u[3].y) + (u[3].z + u[3].w))) * (1.f / 512.f);
      asm("rsqrt.approx.ftz.f32 %0, %1;" : "=f"(rstd) : "f"(fmaxf(sq - mean * mean, 0.f) + 1e-5f));
    }
    float A[4], r[4];
#pragma unroll
    for (int i = 0; i < 4; i++) {
      A[i] = (tq & 2) ? ((tq & 1) ? e[3][i] : e[2][i]) : ((tq & 1) ? e[1][i] : e[0][i]);
      r[i] = (tq & 2) ? ((tq & 1) ? df[3][i] : df[2][i]) : ((tq & 1) ? df[1][i] : df[0][i]);
    }
    sts4(a_rs, rstd * (r[0] + r[1]) + (A[1] - rstd * mean * A[0])); sts4(a_rs + 128, rstd * (r[2] + r[3]) + (A[3] - rstd * mean * A[2]));
    nbar(1, 256);
    if (warp == 7) {
      const float4 g0 = lds16(a_rl), g1 = lds16(a_rl + 1024), u0 = lds16(a_rl + 512), u1 = lds16(a_rl + 1536);
      const float gg = ((g0.x + g0.y) + (g0.z + g0.w)) + ((g1.x + g1.y) + (g1.z + g1.w));
      const float uu = ((u0.x + u0.y) + (u0.z + u0.w)) + ((u1.x + u1.y) + (u1.z + u1.w));
      const float hh = (gg * uu) * rcp(1.f + ex2(gg * (-2.302208198f - 0.1029432397f * gg * gg)));
      send32(a_h, a_hb, hh, lane, 0);
    } else spin_until(clock() + FDLY);
    uint32_t ad[8][4];
    mbar_wait(fullb + 8 * wg, phb);
#pragma unroll
    for (int i = 0; i < 8; i++) ldsm_t(ad[i], a_d + i * 2048);
    float x0, x1;
    if (warp == 0) {
      POLL {
        if (it_)
#pragma unroll
          for (int i = 0; i < 8; i++) xq[i] = ldx8(px + i * 512);
        unsigned bad = 0;
#pragma unroll
        for (int i = 0; i < 4; i++) bad = or3(bad, lop_x3(xq[i].x, xq[i].y, par), lop_x3(xq[i + 4].x, xq[i + 4].y, par));
        RETRY(bad)
      }
      x0 = x1 = 0.f;
#pragma unroll
      for (int i = 0; i < 8; i++) { x0 += u2f(xq[i].x); x1 += u2f(xq[i].y); }
      x0 *= 1.f / 7.f; x1 *= 1.f / 7.f;
    }
    mbar_wait(bar0 + 8 * B_HZ);
    float dd[4][4] = {};
#pragma unroll
    for (int i = 0; i < 4; i++) {
      const float4 hb = lds16(a_hl + i * 64);
      mma16(dd[(2 * i) & 3], ad[2 * i], __float_as_uint(hb.x), __float_as_uint(hb.y));
      mma16(dd[(2 * i + 1) & 3], ad[2 * i + 1], __float_as_uint(hb.z), __float_as_uint(hb.w));
    }
    sts4(a_t, (tq & 1) ? (dd[0][2] + dd[1][2]) + (dd[2][2] + dd[3][2]) : (dd[0][0] + dd[1][0]) + (dd[2][0] + dd[3][0]));
    if (warp) nbar_arrive(2, 256);
    else {
      nbar(2, 256);
      float t0, t1, t2, t3b;
      asm volatile("ld.shared.v2.f32 {%0, %1}, [%4]; ld.shared.v2.f32 {%2, %3}, [%4 + 256];"
                   : "=f"(t0), "=f"(t1), "=f"(t2), "=f"(t3b) : "r"(sb + O_SM + lane * 8) : "memory");
      t0 = bfhi(gbw.x) * (t0 + t2) + x0; t1 = bfhi(gbw.y) * (t1 + t3b) + x1;
      asm volatile("red.relaxed.gpu.global.add.noftz.bf16x2 [%0], %1;" ::"l"(po), "r"(pack2(t0, t1)) : "memory");
      if (f == 0 && tid == 0) stx4(&scr->cnt[0], epoch + 1);
    }
  }
}

static void make_sched(Sched& s) {
  const char* order = "FFAAbcFmmvog..d";
  const double dt = 4985 * 1e-3, dth = 4660 * 1e-3;
  const int nbig = NBIG;
  s.zero = 0; s.dth = (unsigned)(dth * 256 + 0.5);
  double t = 512 * dth + 0;
  int tile = 0, jm = 0;
  for (int i = 0; i < 3; i++) s.nr[i] = s.nt[i] = 0;
  auto add = [&](int c, int type, double step, int win, int b0, int tl) {
    s.r[c][s.nr[c]++] = make_uint2((unsigned)(t + 0.5) | (unsigned)(step + 0.5) << 16, type | win << 4 | (b0 + 64) << 8 | tl << 16);
    if (type == T_KV) s.nt[c]++;
  };
  const int w1 = 6, w2 = 4, wt = 6;
  for (const char* p = order; *p; p++) {
    const char c = *p;
    if (c == 'v' || c == 'o' || c == 'm') {
      const int ty = c == 'v' ? T_UV : c == 'o' ? T_WO : T_MOD;
      const double d = (c == 'm' ? 6000 : c == 'v' ? 5500 : 5500) * 1e-3;
      add(0, ty, 64 * d, wt, 0, c == 'm' ? jm : 0); add(1, ty, 64 * d, wt, 0, c == 'm' ? jm : 0);
      t += (c == 'm' ? 64 : 256) * d; jm += c == 'm';
    } else if (c == 'g' || c == 'd') {
      const double d = (c == 'g' ? 5500 : 5000) * 1e-3;
      add(2, c == 'g' ? T_GU : T_DN, 56 * d, wt, 64, 0);
      t += (c == 'g' ? 224 : 112) * d;
    } else if (c == '.') t += 100;
    else if (c == '-') t -= 100;
    else {
      const int na = c == 'F' ? 0 : c == 'C' || c == 'c' || c == 'a' ? nbig : 64, nf = c == 'A' || c == 'a' ? 0 : 56, n = na + nf;
      const int w = na && nf ? w2 : w1;
      const bool ff = c == 'b' || c == 'c';
      const int cf = c == 'c' ? 20 : 0, ca = cf * 7 / 5;
      t += 3 * ca;
      if (na) add(0, T_KV, n * dt - ca, w, ff ? -56 : 0, tile);
      t -= 3 * ca;
      if (na == 64) add(1, T_KV, n * dt, w, ff ? -56 : 0, tile);
      if (nf) add(2, T_KV, n * dt - cf, w, ff ? 64 : 64 - na, tile);
      tile += n; t += 4 * n * dt;
      s.t4 = (unsigned)t + 600;
    }
  }
  s.dt = (unsigned)(dt * 256 + 0.5); s.d4 = 1540 | 1200 << 16; s.d6 = 3140; s.wt = 250;
}

static void launch(void* const* d_in, void* d_out) {
  static TMaps tms;
  static Sched sch;
  static bool init = false;
  static void* scr = nullptr;
  if (!init) {
    void* fn = nullptr; cudaDriverEntryPointQueryResult qr;
    cudaGetDriverEntryPoint("cuTensorMapEncodeTiled", &fn, cudaEnableDefault, &qr);
    EncFn f = (EncFn)fn;
    const CUtensorMapSwizzle S64 = CU_TENSOR_MAP_SWIZZLE_64B, S128 = CU_TENSOR_MAP_SWIZZLE_128B;
    const CUtensorMapL2promotion P256 = CU_TENSOR_MAP_L2_PROMOTION_L2_256B;
    enc3d(f, &tms.m[0], d_in[2], 64, 512, 64, 8192, 128, 64, 128, 1, S128, CU_TENSOR_MAP_L2_PROMOTION_L2_128B);
    enc3d(f, &tms.m[1], d_in[3], 64, 512, 64, 8192, 128, 64, 64, 2, S128, P256);
    enc3d(f, &tms.m[2], d_in[1], 64, SK, 8, 1024, 128, 64, 64, 2, S128, P256);
    enc3d(f, &tms.m[3], d_in[11], 3072, 256, 2, 6144, 256 * 6144, 32, 256, 1, S64, CU_TENSOR_MAP_L2_PROMOTION_L2_128B);
    enc3d(f, &tms.m[4], d_in[4], 64, 512, 64, 8192, 128, 64, 128, 1, S128, CU_TENSOR_MAP_L2_PROMOTION_L2_128B);
    enc3d(f, &tms.m[5], d_in[5], 512, 128, 32, 1024, 128 * 1024, 64, 128, 1, S128, CU_TENSOR_MAP_L2_PROMOTION_L2_128B);
    enc3d(f, &tms.m[6], d_in[7], 1792, 256, 2, 3584, 256 * 3584, 32, 256, 1, S64, CU_TENSOR_MAP_L2_PROMOTION_L2_128B);
    enc3d(f, &tms.m[7], d_in[8], 1792, 256, 2, 3584, 256 * 3584, 32, 256, 1, S64, CU_TENSOR_MAP_L2_PROMOTION_L2_128B);
    enc3d(f, &tms.m[8], d_in[9], 512, 128, 14, 1024, 128 * 1024, 64, 128, 1, S128, CU_TENSOR_MAP_L2_PROMOTION_L2_128B);
    cudaFuncSetAttribute(fused_kernel, cudaFuncAttributeMaxDynamicSharedMemorySize, SMEM9);
    cudaGetSymbolAddress(&scr, g_scr);
    make_sched(sch);
    init = true;
  }
  fused_kernel<<<NCTA9, 384, SMEM9>>>((const bf16*)d_in[0], (const bf16*)d_in[10], (const bf16*)d_in[11], (bf16*)d_out, (Scratch*)scr, sch, tms);
}

static bool fits() {
  cudaFuncSetAttribute(fused_kernel, cudaFuncAttributeMaxDynamicSharedMemorySize, SMEM9);
  cudaLaunchConfig_t cfg = {};
  cfg.gridDim = dim3(NCTA9); cfg.blockDim = dim3(384); cfg.dynamicSmemBytes = SMEM9;
  cudaLaunchAttribute at[1];
  at[0].id = cudaLaunchAttributeClusterDimension; at[0].val.clusterDim.x = 8; at[0].val.clusterDim.y = 1; at[0].val.clusterDim.z = 1;
  cfg.attrs = at; cfg.numAttrs = 1;
  int n = 0;
  if (cudaOccupancyMaxActiveClusters(&n, fused_kernel, &cfg) != cudaSuccess) { (void)cudaGetLastError(); return false; }
  return n >= NCTA9 / 8;
}
}
#undef BAR_ARM
#undef BAR_ARRIVE
#undef BAR_INIT
#undef B_EMPTY
#undef B_FM
#undef B_FULL
#undef B_G
#undef B_G2
#undef B_H
#undef B_HZ
#undef B_LZ
#undef B_Q2
#undef B_QF
#undef B_ST
#undef B_TAB
#undef B_W
#undef B_WZ
#undef CNT_ADD
#undef DSC
#undef FDLY
#undef HI128
#undef HI64
#undef LANE0
#undef NBIG
#undef NCTA9
#undef NPE
#undef NPO
#undef NSL
#undef O_B
#undef O_BAR
#undef O_CTX
#undef O_DBG
#undef O_EP
#undef O_HW
#undef O_HZ
#undef O_LZ
#undef O_P
#undef O_Q
#undef O_R
#undef O_SILU
#undef O_SM
#undef O_X
#undef PIN
#undef PINL
#undef POLL
#undef QN
#undef RETRY
#undef SK
#undef SMEM9
#undef SMEM_BASE
#undef SPIN_MAX
#undef TAU
#undef VDLY
#undef VJ
#undef X16
#undef fbits

namespace v8 {
typedef __nv_bfloat16 bf16;
#define NCTA 128
#define SK 32768
#define SLOT 32768
#define NSLOT 6
#define OFF_WQ (2 * SLOT)
#define OFF_WUK (4 * SLOT)
#define OFF_Q 196608
#define OFF_P (OFF_Q + 16384)
#define OFF_B (OFF_P + 4096)
#define OFF_R4 (OFF_B + 2304)
#define OFF_SILU (OFF_R4 + 4096)
#define OFF_RA (OFF_SILU + 1024)
#define OFF_SM (OFF_RA + 1024)
#define OFF_BP (OFF_SM + 1792)
#define OFF_CO (OFF_BP + 1024)
#define OFF_BAR (OFF_CO + 1280)
#define OFF_MASK (OFF_BAR + 512)
#define OFF_DBG (OFF_MASK + 16)
#define SMEM_BYTES (OFF_DBG + 128)
#define OFF_MOD OFF_Q
#define OFF_UV (4 * SLOT)
#define OFF_O (5 * SLOT)
#define OFF_G 0
#define OFF_U 16384
#define OFF_D SLOT
#define OFF_XO (OFF_D + 16384)
#define FB_UK 4
#define FB_KV 6
#define FB_MOD 22
#define FB_UV 23
#define FB_O 25
#define FB_G 27
#define FB_D 29
#define EB 30
#define QB 50
#define XB 51
#define SPIN_MAX (1 << 20)
#define BACKOFF 40
#define RATE_NS 652
#define RATE_T0 200
#define RATE_TL 300
#define WINS 0x3222333
#define KVWIN 4
#define RATE_H 650
#define RATE_E 650
#define SMUL 9
#define NPRE0 1
#define NPRE1 3
#define HWIN 4
#define EWIN 3
#define WTEST 450
#define DLY5 650
#define DLY6 600
#define DLY7 600
#define P12(a, b, c, d, e, f, g, h, i, j, k, l) ((unsigned long long)(a) | (b) << 5 | (c) << 10 | (d) << 15 | (e) << 20 | (f) << 25 | \
  (unsigned long long)(g) << 30 | (unsigned long long)(h) << 35 | (unsigned long long)(i) << 40 | (unsigned long long)(j) << 45 | \
  (unsigned long long)(k) << 50 | (unsigned long long)(l) << 55)
#define ORDER0 P12(0, 1, 2, 3, 4, 5, 16, 6, 7, 8, 9, 10)
#define ORDER1 P12(11, 12, 13, 14, 15, 17, 18, 19, 20, 23, 21, 22)
#define TAIL_K 17
#define RS 16
template <int N> struct IC { static constexpr int value = N; };
struct TMaps { CUtensorMap m[9]; };

struct __align__(128) Scratch {
  uint4 xo[128 * 64 * RS];
  uint2 ml[32 * 64];
  unsigned h[8 * 256];
  unsigned qa[32 * 256];
  unsigned xc[128 * 64];
  unsigned xao[8 * 512];
  unsigned xf[112 * 512];
  unsigned xm[2048];
  unsigned cnt[5 * 32];
};
__device__ Scratch g_scr;
#define g_xo scr->xo
#define g_ml scr->ml
#define g_h scr->h
#define g_qa scr->qa
#define g_xc scr->xc
#define g_xao scr->xao
#define g_xf scr->xf
#define g_xm scr->xm
#define g_epoch scr->cnt[0]

__device__ __forceinline__ uint32_t s2u(const void* p) { return (uint32_t)__cvta_generic_to_shared(p); }
__device__ __forceinline__ float bflo(uint32_t u) { return __uint_as_float(u << 16); }
__device__ __forceinline__ float bfhi(uint32_t u) { return __uint_as_float(u & 0xffff0000u); }
__device__ __forceinline__ float u2f(uint32_t u) { return __uint_as_float(u); }
__device__ __forceinline__ void fma8(float* acc, uint4 v, float s) {
  acc[0] += s * bflo(v.x); acc[1] += s * bfhi(v.x); acc[2] += s * bflo(v.y); acc[3] += s * bfhi(v.y);
  acc[4] += s * bflo(v.z); acc[5] += s * bfhi(v.z); acc[6] += s * bflo(v.w); acc[7] += s * bfhi(v.w);
}
__device__ __forceinline__ uint32_t pack2(float a, float b) {
  __nv_bfloat162 p = __floats2bfloat162_rn(a, b); return *(uint32_t*)&p;
}
__device__ __forceinline__ float bfr(float v) { return bfhi(pack2(v, v)); }
__device__ __forceinline__ float silu_bf(float c) { return bfr(__fdividef(c, 1.f + __expf(-c))); }
#define fbits(v) ((__float_as_uint(v) & ~1u) | par)
__device__ __forceinline__ uint32_t pack2t(float a, float b, unsigned par) {
  const uint32_t ua = ((__float_as_uint(a) + ((par ^ 1) << 16)) & 0xFFFE0000u) | (par << 16);
  return __byte_perm(ua, pack2(b, b), 0x7632);
}
__device__ __forceinline__ void nbar(int id, int n) { asm volatile("bar.sync %0, %1;" ::"r"(id), "r"(n) : "memory"); }
__device__ __forceinline__ void nbar_arrive(int id, int n) { asm volatile("bar.arrive %0, %1;" ::"r"(id), "r"(n) : "memory"); }
__device__ __forceinline__ uint4 ldc16(const void* p) {
  uint4 v; asm volatile("ld.relaxed.cta.global.v4.u32 {%0,%1,%2,%3}, [%4];" : "=r"(v.x), "=r"(v.y), "=r"(v.z), "=r"(v.w) : "l"(p) : "memory"); return v;
}
__device__ __forceinline__ unsigned ldc4(const void* p) {
  unsigned v; asm volatile("ld.relaxed.cta.global.u32 %0, [%1];" : "=r"(v) : "l"(p) : "memory"); return v;
}
__device__ __forceinline__ uint4 ldx16(const void* p) {
  uint4 v; asm volatile("ld.relaxed.gpu.global.v4.u32 {%0,%1,%2,%3}, [%4];" : "=r"(v.x), "=r"(v.y), "=r"(v.z), "=r"(v.w) : "l"(p) : "memory"); return v;
}
__device__ __forceinline__ unsigned ldx4(const void* p) {
  unsigned v; asm volatile("ld.relaxed.gpu.global.u32 %0, [%1];" : "=r"(v) : "l"(p) : "memory"); return v;
}
__device__ __forceinline__ unsigned long long ldx64(const void* p) {
  unsigned long long v; asm volatile("ld.relaxed.gpu.global.u64 %0, [%1];" : "=l"(v) : "l"(p) : "memory"); return v;
}
__device__ __forceinline__ void stx16(void* p, uint4 v) {
  asm volatile("st.relaxed.gpu.global.v4.u32 [%0], {%1,%2,%3,%4};" ::"l"(p), "r"(v.x), "r"(v.y), "r"(v.z), "r"(v.w) : "memory");
}
__device__ __forceinline__ void stx8(void* p, uint2 v) { asm volatile("st.relaxed.gpu.global.v2.u32 [%0], {%1,%2};" ::"l"(p), "r"(v.x), "r"(v.y) : "memory"); }
__device__ __forceinline__ void stx4(void* p, unsigned v) { asm volatile("st.relaxed.gpu.global.u32 [%0], %1;" ::"l"(p), "r"(v) : "memory"); }
__device__ __forceinline__ unsigned lop_x3(unsigned a, unsigned b, unsigned c) {
  unsigned d; asm("lop3.b32 %0, %1, %2, %3, 0x7E;" : "=r"(d) : "r"(a), "r"(b), "r"(c)); return d; }
#define X16(v) (lop_x3(v.x, v.y, par) | lop_x3(v.z, v.w, par))
#define X8(v) lop_x3(v.x, v.y, par)
#define RETRY(bad) if (!__any_sync(~0u, (bad) & 1) || ++it_ >= SPIN_MAX) break; __nanosleep(BACKOFF);
#define POLL _Pragma("unroll 1") for (int it_ = 0;;)
__device__ __forceinline__ void mbar_wait(uint32_t bar) {
  uint32_t ok; int it = 0;
  do {
    asm volatile("{.reg .pred p; mbarrier.try_wait.parity.shared::cta.b64 p, [%1], 0; selp.u32 %0,1,0,p;}"
                 : "=r"(ok) : "r"(bar) : "memory");
  } while (!ok && ++it < SPIN_MAX);
}
__device__ __forceinline__ float ex2(float v) { float r; asm("ex2.approx.ftz.f32 %0, %1;" : "=f"(r) : "f"(v)); return r; }
__device__ __forceinline__ float rcp(float v) { float r; asm("rcp.approx.ftz.f32 %0, %1;" : "=f"(r) : "f"(v)); return r; }
__device__ __forceinline__ void mma16(float* d, const uint32_t* a, uint32_t b0, uint32_t b1) {
  asm volatile("mma.sync.aligned.m16n8k16.row.col.f32.bf16.bf16.f32 {%0,%1,%2,%3}, {%4,%5,%6,%7}, {%8,%9}, {%0,%1,%2,%3};"
               : "+f"(d[0]), "+f"(d[1]), "+f"(d[2]), "+f"(d[3]) : "r"(a[0]), "r"(a[1]), "r"(a[2]), "r"(a[3]), "r"(b0), "r"(b1));
}
__device__ __forceinline__ float4 lds16(uint32_t a) {
  float4 v; asm volatile("ld.shared.v4.f32 {%0,%1,%2,%3}, [%4];" : "=f"(v.x), "=f"(v.y), "=f"(v.z), "=f"(v.w) : "r"(a) : "memory"); return v;
}
__device__ __forceinline__ void ldsm_t(uint32_t* r, uint32_t a) {
  asm volatile("ldmatrix.sync.aligned.m8n8.x4.trans.shared.b16 {%0,%1,%2,%3}, [%4];" : "=r"(r[0]), "=r"(r[1]), "=r"(r[2]), "=r"(r[3]) : "r"(a) : "memory");
}
__device__ __forceinline__ void ldsm(uint32_t* r, uint32_t a) {
  asm volatile("ldmatrix.sync.aligned.m8n8.x4.shared.b16 {%0,%1,%2,%3}, [%4];" : "=r"(r[0]), "=r"(r[1]), "=r"(r[2]), "=r"(r[3]) : "r"(a) : "memory");
}
template <int N>
__device__ __forceinline__ void tred(float* a, int lane, int m) {
  const bool hi = lane & m;
#pragma unroll
  for (int i = 0; i < N; i++) {
    float send = hi ? a[i] : a[i + N], keep = hi ? a[i + N] : a[i];
    a[i] = keep + __shfl_xor_sync(~0u, send, m);
  }
}
template <int N>
__device__ __forceinline__ void tmax(float* a, int lane, int m) {
  const bool hi = lane & m;
#pragma unroll
  for (int i = 0; i < N; i++) {
    float send = hi ? a[i] : a[i + N], keep = hi ? a[i + N] : a[i];
    a[i] = fmaxf(keep, __shfl_xor_sync(~0u, send, m));
  }
}
__device__ __forceinline__ void arrive2(uint32_t bar, uint32_t rbar, bool local, bool remote) {
  asm volatile("{.reg .pred p, q; setp.ne.s32 p, %2, 0; setp.ne.s32 q, %3, 0; @p mbarrier.arrive.shared::cta.b64 _, [%0];\n"
               "@q mbarrier.arrive.relaxed.cluster.shared::cluster.b64 _, [%1];}" ::"r"(bar), "r"(rbar), "r"((int)local), "r"((int)remote) : "memory");
}
__device__ __forceinline__ unsigned long long stream_policy() {
  unsigned long long p;
  asm volatile("createpolicy.fractional.L2::evict_first.b64 %0, 1.0;" : "=l"(p));
  return p;
}
__device__ __forceinline__ void tma3d(uint32_t dst, const CUtensorMap* tm, uint32_t bar, int c0, int c1, int c2) {
  asm volatile("cp.async.bulk.tensor.3d.shared::cluster.global.mbarrier::complete_tx::bytes.L2::cache_hint [%0], [%1, {%3, %4, %5}], [%2], %6;"
               ::"r"(dst), "l"(tm), "r"(bar), "r"(c0), "r"(c1), "r"(c2), "l"(stream_policy()) : "memory");
}
__device__ __forceinline__ void st_async2(uint32_t dst, uint32_t bar, float v0, float v1) {
  asm volatile("st.async.shared::cluster.mbarrier::complete_tx::bytes.v2.f32 [%0], {%1, %2}, [%3];" ::"r"(dst), "f"(v0), "f"(v1), "r"(bar) : "memory");
}
__device__ __forceinline__ void st_pair(int mode, uint32_t dst, uint32_t bar, float v0, float v1) {
  asm volatile("{.reg .pred p, q; setp.eq.s32 p, %4, 1; setp.eq.s32 q, %4, 2; @p st.shared.v2.f32 [%0], {%1, %2};\n"
               "@q st.async.shared::cluster.mbarrier::complete_tx::bytes.v2.f32 [%0], {%1, %2}, [%3];}"
               ::"r"(dst), "f"(v0), "f"(v1), "r"(bar), "r"(mode) : "memory");
}
__device__ __forceinline__ void spin_until(unsigned t) { while ((int)((unsigned)clock() - t) < 0) {} }
__device__ __forceinline__ unsigned wait_until(unsigned t) {
  unsigned now;
  for (;;) {
    asm volatile("mov.u32 %0, %%globaltimer_lo;" : "=r"(now));
    if ((int)(now - t) >= 0) break;
  }
  return now;
}
#define PIN(x) asm volatile("" : "+r"(x))
#define PINL(x) asm volatile("" : "+l"(x))
#define BAR_ARRIVE(i) asm volatile("mbarrier.arrive.shared::cta.b64 _, [%0];" ::"r"(bar0 + 8 * (i)) : "memory")
#define CNT_ADD(c) asm volatile("red.relaxed.gpu.global.add.u32 [%0], 1;" ::"l"(scr->cnt + (c)) : "memory")
#define BAR_INIT(i, cnt) asm volatile("mbarrier.init.shared::cta.b64 [%0], %1;" ::"r"(bar0 + 8 * (i)), "r"(cnt) : "memory")
#define BAR_ARM(i, bytes) asm volatile("mbarrier.arrive.expect_tx.shared::cta.b64 _, [%0], %1;" ::"r"(bar0 + 8 * (i)), "r"(bytes) : "memory")

__device__ __forceinline__ void tail(unsigned char* smem, Scratch* __restrict__ scr, const bf16* __restrict__ x, bf16* __restrict__ out,
                                     const unsigned par, const unsigned epoch, const int warp) {
  int tid, b;
  asm volatile("mov.u32 %0, %%tid.x;" : "=r"(tid));
  asm volatile("mov.u32 %0, %%ctaid.x;" : "=r"(b));
  const int lane = tid & 31, g = lane >> 2, tq = lane & 3;
  const uint32_t sb = __shfl_sync(~0u, s2u(smem), 0), bar0 = sb + OFF_BAR;
  float* s_sm = (float*)(smem + OFF_SM);
  const int prow = 4 * (lane >> 4) + ((lane & 7) >> 1) + 8 * (lane & 1);
  const float* s_co = (const float*)(smem + OFF_CO);
  const int opos = (b & 15) * 32 + (lane & 16) + 2 * (lane & 6) + ((lane >> 2) & 2) + (lane & 1);
  const float xv = b < 16 ? __bfloat162float(x[(b & 15) * 32 + lane]) : 0.f;
  const int rk = b & 1, ob = 32 * rk + ((b >> 1) & 31);
  uint32_t psb;
  asm volatile("mapa.shared::cluster.u32 %0, %1, %2;" : "=r"(psb) : "r"(sb), "r"(rk ^ 1));
  {
    uint32_t a[8][4];
    {
      const int rg = tid >> 4;
      const uint4* src = g_xo + ((size_t)b * 64 + rg) * RS;
      const uint32_t dst = sb + OFF_XO + rg * 256 + (((tid & 15) ^ (rg & 7)) << 4);
      unsigned long long todo = 0x0001000100010001ull;
#pragma unroll 1
      for (int it = 0; it < SPIN_MAX * 16; it++) {
        unsigned long long mk = *(volatile unsigned long long*)(smem + OFF_MASK);
        const unsigned long long nw = (mk >> rg) & todo;
        todo ^= nw;
#pragma unroll
        for (int i = 0; i < 4; i++)
          if (nw >> (16 * i) & 1)
            asm volatile("cp.async.cg.shared.global [%0], [%1], 16;" ::"r"(dst + i * 4096), "l"(src + i * 16 * RS + (tid & 15)) : "memory");
        if (!__any_sync(~0u, todo != 0)) break;
      }
      asm volatile("cp.async.mbarrier.arrive.noinc.shared::cta.b64 [%0];" ::"r"(bar0 + 8 * (XB + 2)) : "memory");
    }
    mbar_wait(bar0 + 8 * FB_UV); mbar_wait(bar0 + 8 * (FB_UV + 1));
    const uint32_t ab = sb + OFF_UV + (warp >> 2) * 8192 + (8 * (lane >> 4) + (lane & 7)) * 128 + (((2 * (warp & 3) + ((lane >> 3) & 1)) ^ (lane & 7)) << 4);
#pragma unroll
    for (int s = 0; s < 8; s++) ldsm_t(a[s], ab + (s >> 2) * 16384 + (s & 3) * 2048);
    const int chn = 2 * warp + (tq & 1);
    uint32_t a_b = sb + OFF_B + (tq >> 1) * 272 + (32 * (chn >> 2) + 8 * (g >> 1) + 2 * (chn & 3) + (g & 1)) * 2;
    uint32_t a_bq = sb + OFF_B + (lane & 1) * 272 + (lane >> 3) * 16;
    unsigned* p_c = g_xc + (b >> 2) * 256 + warp * 32 + (b & 3) * 8 + (g & 3) * 2 + (g >> 2);
    PIN(a_b); PIN(a_bq); PINL(p_c);
    mbar_wait(bar0 + 8 * (XB + 6));
    uint32_t wb[8];
#pragma unroll
    for (int s = 0; s < 8; s++) wb[s] = *(const uint32_t*)(smem + OFF_RA + (4 * s + tq) * 4);
    const float invL = *(const float*)(smem + OFF_RA + 128);
    float ov;
    POLL {
      mbar_wait(bar0 + 8 * (XB + 2));
      uint32_t ao[4][4];
#pragma unroll
      for (int s = 0; s < 4; s++)
        ldsm_t(ao[s], sb + OFF_XO + (16 * s + 8 * (lane >> 4) + (lane & 7)) * 256 + (((2 * warp + ((lane >> 3) & 1)) ^ (lane & 7)) << 4));
      float d[4][4] = {};
#pragma unroll
      for (int s = 0; s < 4; s++) mma16(d[s], ao[s], wb[2 * s], wb[2 * s + 1]);
      const unsigned p2 = par * 0x10001u;
      unsigned bad = 0;
#pragma unroll
      for (int s = 0; s < 4; s++) bad |= lop_x3(ao[s][0], ao[s][1], p2) | lop_x3(ao[s][2], ao[s][3], p2);
      bad = g == 0 ? bad | (bad >> 16) : 0u;
      ov = (tq & 1) ? (d[0][2] + d[1][2]) + (d[2][2] + d[3][2]) : (d[0][0] + d[1][0]) + (d[2][0] + d[3][0]);
      if (__builtin_expect(!__any_sync(~0u, bad & 1) || ++it_ >= SPIN_MAX, 1)) break;
#pragma unroll
      for (int i = 0; i < 4; i++)
        asm volatile("cp.async.cg.shared.global [%0], [%1], 16;"
                     ::"r"(sb + OFF_XO + ((lane >> 1) + 16 * i) * 256 + (((2 * warp + (lane & 1)) ^ ((lane >> 1) & 7)) << 4)),
                       "l"(g_xo + ((size_t)b * 64 + (lane >> 1) + 16 * i) * RS + 2 * warp + (lane & 1)) : "memory");
      asm volatile("cp.async.wait_all;" ::: "memory");
      __syncwarp();
    }
    {
      const float lo = ov - bfhi(__float_as_uint(ov));
      asm volatile("st.shared.u16 [%0], %1;" ::"r"(a_b), "h"((unsigned short)((tq & 2) ? pack2(lo, lo) : __float_as_uint(ov) >> 16)) : "memory");
    }
    nbar(1, 256);
    float d[4][4] = {};
#pragma unroll
    for (int y = 0; y < 4; y++) {
      uint32_t bq[4];
      ldsm(bq, a_bq + 64 * y);
      mma16(d[(2 * y) & 3], a[2 * y], bq[0], bq[1]); mma16(d[(2 * y + 1) & 3], a[2 * y + 1], bq[2], bq[3]);
    }
    const float r0 = ((d[0][0] + d[0][1]) + (d[1][0] + d[1][1])) + ((d[2][0] + d[2][1]) + (d[3][0] + d[3][1]));
    const float r1 = ((d[0][2] + d[0][3]) + (d[1][2] + d[1][3])) + ((d[2][2] + d[2][3]) + (d[3][2] + d[3][3]));
    if (tq == 0) stx4(p_c, pack2t(r0 * invL, r1 * invL, par));
  }
  unsigned tpub = clock();
  mbar_wait(bar0 + 8 * (XB + 4));
  const float gav = s_co[256 + (opos & 31)];
  const float gbv = s_co[288 + (lane & 4) + 2 * (lane & 1) + ((lane >> 1) & 1)];
  float4 cf[2];
#pragma unroll
  for (int s = 0; s < 2; s++) cf[s] = *(const float4*)(s_co + 32 * warp + 16 * s + 4 * tq);
  {
    uint32_t a[2][4][4];
    mbar_wait(bar0 + 8 * (FB_O + (warp >> 2)));
    const uint32_t ab = sb + OFF_O + (32 * warp + prow) * 128 + ((((lane >> 3) & 1) ^ (prow & 7)) << 4);
#pragma unroll
    for (int i = 0; i < 8; i++) ldsm_t(a[i >> 2][i & 3], (ab + (i >> 2) * 2048) ^ ((i & 3) << 5));
    uint4 v;
    const unsigned* pc = g_xc + (4 * (b >> 4) + 2 * rk + (warp >> 2)) * 256 + 64 * (warp & 3) + 2 * lane;
    uint32_t ro = ((tq >> 1) == rk ? sb : psb) + OFF_P + (8 * (tq & 1) + g) * 144 + (8 * rk + warp) * 8;
    uint32_t a_q = sb + OFF_P + (8 * (lane >> 4) + (lane & 7)) * 144;
    unsigned* p_ao = g_xao + (b >> 5) * 1024 + (opos >> 4) * 32 + (b & 16) + (opos & 15);
    PIN(ro); PIN(a_q); PINL(p_ao); PINL(pc);
    spin_until(tpub + DLY5);
    POLL {
      const unsigned long long u0 = ldx64(pc);
      v.x = (unsigned)u0; v.y = u0 >> 32;
      RETRY(X8(v))
    }
    v.z = lane & 16 ? v.x : 0u; v.w = lane & 16 ? v.y : 0u;
    if (lane & 16) v.x = v.y = 0u;
    float d[4][4] = {};
#pragma unroll
    for (int mt = 0; mt < 4; mt++) mma16(d[mt], a[0][mt], v.x, v.y);
#pragma unroll
    for (int mt = 0; mt < 4; mt++) mma16(d[mt], a[1][mt], v.z, v.w);
    float r[8];
#pragma unroll
    for (int i = 0; i < 8; i++) r[i] = d[i >> 1][2 * (i & 1)] + d[i >> 1][2 * (i & 1) + 1];
    tred<4>(r, lane, 2); tred<2>(r, lane, 1);
    st_pair((tq >> 1) == rk ? 1 : 2, ro, psb + OFF_BAR + 8 * (XB + 3), r[0], r[1]);
    __syncwarp();
    if (lane == 0) BAR_ARRIVE(XB + 3);
    if (warp == 0) {
      mbar_wait(bar0 + 8 * (XB + 3));
      float p[8];
#pragma unroll
      for (int i = 0; i < 8; i++) {
        const float4 q = lds16(a_q + i * 16);
        p[i] = (lane & 8) ? q.y + q.w : q.x + q.z;
      }
      const float t = ((p[0] + p[1]) + (p[2] + p[3])) + ((p[4] + p[5]) + (p[6] + p[7]));
      stx4(p_ao, fbits(gav * t + xv));
    }
  }
  tpub = clock();
  if (b < 112) {
    uint32_t af[2][4][4], ad[4][4];
    const uint32_t ab = sb + (32 * warp + 8 * (lane >> 4) + (lane & 7)) * 64 + ((((lane >> 3) & 1) ^ ((lane >> 1) & 3)) << 4);
    uint32_t ro = ((tq & 1) == rk ? sb : psb) + OFF_R4 + (8 * (tq >> 1) + g) * 176 + (10 * rk + warp) * 8;
    uint32_t a_q = sb + OFF_R4 + (8 * (lane >> 4) + (lane & 7)) * 176 + (lane & 8) * 10;
    uint32_t a_d = sb + OFF_D + warp * 2048 + (8 * (lane >> 4) + (lane & 7)) * 128 + ((((lane >> 3) & 1) ^ (lane & 7)) << 4);
    unsigned* p_f = g_xf + b * 512 + 64 * warp + 16 * tq + 2 * g;
    const unsigned* pa = g_xao + (g >> 1) * 1024 + 512 * rk + 64 * warp + 4 * (lane & 7);
    PIN(ro); PIN(a_q); PIN(a_d); PINL(p_f); PINL(pa);
    spin_until(tpub + DLY6);
    uint4 v[2];
    {
      bool have = false;
      POLL {
        v[0] = ldx16(pa); v[1] = ldx16(pa + 32);
        const unsigned t1 = (unsigned)clock() + WTEST;
        while (!have && (int)((unsigned)clock() - t1) < 0) {
          uint32_t ok;
          asm volatile("{.reg .pred p, q; mbarrier.test_wait.parity.shared::cta.b64 p, [%1], 0; mbarrier.test_wait.parity.shared::cta.b64 q, [%1+8], 0;\n"
                       "and.pred p, p, q; vote.sync.all.pred p, p, 0xffffffff; selp.u32 %0, 1, 0, p;}" : "=r"(ok) : "r"(bar0 + 8 * FB_G) : "memory");
          if (ok) {
#pragma unroll
            for (int i = 0; i < 8; i++) ldsm_t(af[i >> 2][i & 3], (ab + ((i & 2) ? OFF_U : OFF_G) + (i >> 2) * 1024) ^ ((i & 1) << 5));
            have = true;
          }
        }
        if (!__any_sync(~0u, (X16(v[0]) | X16(v[1])) & 1) || ++it_ >= SPIN_MAX) break;
      }
      float df[4][4] = {}, dg[2][4] = {};
      uint32_t zb[4];
      const uint32_t one = g == 0 ? 0x3F803F80u : 0u;
#pragma unroll
      for (int s = 0; s < 2; s++) {
        const uint32_t y0 = pack2(u2f(v[s].x), u2f(v[s].y)), y1 = pack2(u2f(v[s].z), u2f(v[s].w));
        const uint32_t ya[4] = {y0, one, y1, one};
        mma16(dg[s], ya, y0, y1);
        zb[2 * s] = pack2(u2f(v[s].x) * cf[s].x, u2f(v[s].y) * cf[s].y); zb[2 * s + 1] = pack2(u2f(v[s].z) * cf[s].z, u2f(v[s].w) * cf[s].w);
      }
      float st[2] = {(dg[0][2] + dg[0][3]) + (dg[1][2] + dg[1][3]), (dg[0][0] + dg[0][1]) + (dg[1][0] + dg[1][1])};
      if (!have) {
        mbar_wait(bar0 + 8 * FB_G); mbar_wait(bar0 + 8 * (FB_G + 1));
#pragma unroll
        for (int i = 0; i < 8; i++) ldsm_t(af[i >> 2][i & 3], (ab + ((i & 2) ? OFF_U : OFF_G) + (i >> 2) * 1024) ^ ((i & 1) << 5));
      }
#pragma unroll
      for (int i = 0; i < 8; i++) mma16(df[i & 3], af[i >> 2][i & 3], zb[2 * (i >> 2)], zb[2 * (i >> 2) + 1]);
#pragma unroll
      for (int o2 = 1; o2 < 4; o2 <<= 1) { st[0] += __shfl_xor_sync(~0u, st[0], o2); st[1] += __shfl_xor_sync(~0u, st[1], o2); }
#pragma unroll
      for (int o2 = 4; o2 < 32; o2 <<= 1) st[1] += __shfl_xor_sync(~0u, st[1], o2);
      float r[8];
#pragma unroll
      for (int i = 0; i < 8; i++) r[i] = df[i >> 1][2 * (i & 1)] + df[i >> 1][2 * (i & 1) + 1];
      tred<4>(r, lane, 2); tred<2>(r, lane, 1);
      const int md = (tq & 1) == rk ? 1 : 2;
      st_pair(md, ro, psb + OFF_BAR + 8 * (XB + 5), r[0], r[1]);
      st_pair(lane < 2 ? md : 0, ro + 16 * 176, psb + OFF_BAR + 8 * (XB + 5), st[0], st[1]);
      __syncwarp();
      if (lane == 0) BAR_ARRIVE(XB + 5);
      mbar_wait(bar0 + 8 * FB_D);
#pragma unroll
      for (int mt = 0; mt < 4; mt++)
        ldsm_t(ad[mt], a_d ^ (mt << 5));
    }
    mbar_wait(bar0 + 8 * (XB + 5));
    {
      float4 q[5], u[8];
#pragma unroll
      for (int i = 0; i < 5; i++) q[i] = lds16(a_q + i * 16);
#pragma unroll
      for (int i = 0; i < 8; i++) u[i] = *(const float4*)(smem + OFF_R4 + 16 * 176 + (i >> 2) * 80 + (i & 3) * 16);
      float p[6] = {((q[0].x + q[0].z) + (q[1].x + q[1].z)) + ((q[2].x + q[2].z) + (q[3].x + q[3].z)), q[4].x, q[4].z,
                    ((q[0].y + q[0].w) + (q[1].y + q[1].w)) + ((q[2].y + q[2].w) + (q[3].y + q[3].w)), q[4].y, q[4].w};
      tred<3>(p, lane, 8);
      const float P = p[0], A1 = p[1], A2 = p[2];
      const float mean = (((u[0].x + u[0].z) + (u[1].x + u[1].z)) + ((u[2].x + u[2].z) + (u[3].x + u[3].z)) +
                          ((u[4].x + u[4].z) + (u[5].x + u[5].z)) + ((u[6].x + u[6].z) + (u[7].x + u[7].z))) * (1.f / 512.f);
      const float sq = (((u[0].y + u[0].w) + (u[1].y + u[1].w)) + ((u[2].y + u[2].w) + (u[3].y + u[3].w)) +
                         ((u[4].y + u[4].w) + (u[5].y + u[5].w)) + ((u[6].y + u[6].w) + (u[7].y + u[7].w))) * (1.f / 512.f);
      float rstd;
      asm("rsqrt.approx.ftz.f32 %0, %1;" : "=f"(rstd) : "f"(fmaxf(sq - mean * mean, 0.f) + 1e-5f));
      const float gg = bfr(rstd * (P - mean * A1) + A2);
      const float uu = __shfl_xor_sync(~0u, gg, 16);
      const float hh = bfr(gg * rcp(1.f + ex2(gg * (-2.302208198f - 0.1029432397f * gg * gg)))) * uu;
      const uint32_t hw = pack2(hh, __shfl_down_sync(~0u, hh, 1));
      const uint32_t b0 = __shfl_sync(~0u, hw, 2 * tq), b1 = __shfl_sync(~0u, hw, 2 * tq + 8);
      float f0 = 0, f1 = 0;
#pragma unroll
      for (int mt = 0; mt < 4; mt++) {
        float dd[4] = {0, 0, 0, 0};
        mma16(dd, ad[mt], b0, b1);
        if (tq == mt) { f0 = dd[0]; f1 = dd[2]; }
      }
      stx8(p_f, make_uint2(fbits(f0), fbits(f1)));
    }
    tpub = clock();
    if (b < 64 && warp == (b >> 3)) {
      const uint4 y = (b & 4) ? v[1] : v[0];
      float a4[4] = {u2f(y.x), u2f(y.y), u2f(y.z), u2f(y.w)};
      tred<2>(a4, lane, 16); tred<1>(a4, lane, 8);
      a4[0] += __shfl_xor_sync(~0u, a4[0], 4);
      if (!(lane & 4)) s_sm[416 + 8 * (lane >> 4) + 2 * tq + ((lane >> 3) & 1)] = a4[0];
      if (warp == 7) nbar_arrive(2, 256);
    } else if (b < 64 && warp == 7) nbar_arrive(2, 256);
    if (b < 64 && warp < 7) {
      uint4 v;
      const unsigned* pf = g_xf + (tid >> 1) * 512 + 8 * ob + 4 * (tid & 1);
      const int col = 16 * (ob >> 1) + 4 * (ob & 1) + ((tid >> 1) & 3) + 8 * (tid & 1);
      bf16* po = out + col;
      PINL(po); PINL(pf);
      spin_until(tpub + DLY7);
      POLL { v = ldx16(pf); RETRY(X16(v)) }
      float f[4] = {u2f(v.x), u2f(v.y), u2f(v.z), u2f(v.w)};
      tred<2>(f, lane, 16); tred<1>(f, lane, 8);
      f[0] += __shfl_xor_sync(~0u, f[0], 4); f[0] += __shfl_xor_sync(~0u, f[0], 2);
      if (!(lane & 6)) s_sm[352 + warp * 8 + 4 * (lane & 1) + (lane >> 3)] = f[0];
      nbar(2, 256);
      if (tid < 8) {
        const float* q = s_sm + 352 + tid;
        const float t = ((q[0] + q[8]) + (q[16] + q[24])) + ((q[32] + q[40]) + q[48]);
        *po = __float2bfloat16(s_sm[416 + (col & 15)] + bfr(gbv * bfr(t)));
        if (b == 0 && tid == 0) stx4(&g_epoch, epoch + 1);
      }
    }
  }
}

__global__ void __cluster_dims__(2, 1, 1) __launch_bounds__(384, 1)
fused_kernel(const bf16* __restrict__ x, const bf16* __restrict__ cvec, const bf16* __restrict__ w_mod, bf16* __restrict__ out,
             Scratch* __restrict__ scr, const __grid_constant__ TMaps tms) {
  extern __shared__ __align__(1024) unsigned char smem[];
  const int tid = threadIdx.x, warp = __shfl_sync(~0u, tid >> 5, 0), lane = tid & 31;
  const int b = blockIdx.x, rk = b & 1, pr = b >> 1, hd = b >> 2;
  uint32_t sb = s2u(smem), bar0 = sb + OFF_BAR;

  unsigned gt_start;
  asm volatile("mov.u32 %0, %%globaltimer_lo;" : "=r"(gt_start));
  const int g = lane >> 2, tq = lane & 3;
  const int arow = 64 * (b >> 4) + ((tid & 255) >> 3);
  uint4 wm0, wm1;
  uint32_t c0w, c1w;
  if (warp < 8) {
    const bf16* wa = w_mod + (size_t)arow * 3072 + (lane & 4) * 128 + 32 * (b & 15) + 8 * tq;
    wm0 = ldx16(wa); wm1 = ldx16(wa + 32 * 3072);
    c0w = ldc4(cvec + (arow & ~1)); c1w = ldc4(cvec + (arow & ~1) + 32);
  }
  const unsigned t_off = gt_start + RATE_T0;
  if (warp == 11) {
    if (lane == 0) {
#pragma unroll
      for (int i = 0; i < FB_KV; i++) { BAR_INIT(i, 1); BAR_ARM(i, 16384); }
    }
    __syncwarp();
    asm volatile("fence.mbarrier_init.release.cluster;" ::: "memory");
    asm volatile("barrier.cluster.arrive.relaxed.aligned;" ::: "memory");
#pragma unroll 1
    for (int i = 0; i < FB_KV; i++) {
      if (i >= HWIN) mbar_wait(bar0 + 8 * (i - HWIN));
      wait_until(t_off + (i < 4 ? 2 * i + ((b >> 1) & 1) : 4 * i - 8 + (b & 3)) * (RATE_H / 4));
      if (lane == 0) {
        if (i < 4) tma3d(sb + OFF_WQ + i * 16384, &tms.m[0], bar0 + 8 * i, 0, i * 128, 2 * hd + rk);
        else tma3d(sb + OFF_WQ + i * 16384, &tms.m[1], bar0 + 8 * i, 0, (b & 3) * 128 + (i - 4) * 64, 2 * hd);
      }
      __syncwarp();
    }
  }
  if (warp == 10) {
    const uint4 xa = ldc16(x + 16 * lane), xb = ldc16(x + 16 * lane + 8);
    const unsigned ep = ldc4(&g_epoch);
    float xv[16] = {bflo(xa.x), bfhi(xa.x), bflo(xa.y), bfhi(xa.y), bflo(xa.z), bfhi(xa.z), bflo(xa.w), bfhi(xa.w),
                    bflo(xb.x), bfhi(xb.x), bflo(xb.y), bfhi(xb.y), bflo(xb.z), bfhi(xb.z), bflo(xb.w), bfhi(xb.w)};
    float s = 0;
#pragma unroll
    for (int i = 0; i < 16; i++) s += xv[i];
#pragma unroll
    for (int o = 16; o; o >>= 1) s += __shfl_xor_sync(~0u, s, o);
    const float mean = s * (1.f / 512.f);
    s = 0;
#pragma unroll
    for (int i = 0; i < 16; i++) { xv[i] -= mean; s += xv[i] * xv[i]; }
#pragma unroll
    for (int o = 16; o; o >>= 1) s += __shfl_xor_sync(~0u, s, o);
    const float rstd = rsqrtf(s * (1.f / 512.f) + 1e-5f);
    if ((lane >> 1) == (b & 15))
#pragma unroll
      for (int i = 0; i < 4; i++)
        *(float4*)(smem + OFF_SM + (256 + (lane & 1) * 16 + 4 * i) * 4) = make_float4(xv[4 * i] * rstd, xv[4 * i + 1] * rstd, xv[4 * i + 2] * rstd, xv[4 * i + 3] * rstd);
    if (lane == 0) *(volatile unsigned*)(smem + OFF_MASK + 8) = ep;
    nbar_arrive(1, 288);
  }
  if (warp >= 8) {
    asm volatile("setmaxnreg.dec.sync.aligned.u32 72;");
    if (tid == 288) {
#pragma unroll
      for (int q = FB_KV; q < FB_KV + 16; q++) { BAR_INIT(q, 1); BAR_ARM(q, 32768); }
    }
    if (tid == 320) {
#pragma unroll
      for (int q = 0; q <= 13 + NSLOT; q++) BAR_INIT(EB + q, q == 0 ? 4 : q < 5 ? 16 : q < 16 ? 12 : 6);
    }
    if (tid == 256) {
#pragma unroll
      for (int q = FB_MOD; q <= FB_D; q++) { BAR_INIT(q, 1); BAR_ARM(q, 16384); }
      BAR_INIT(QB, 9); BAR_ARM(QB, 1024);
#pragma unroll
      for (int q = 0; q < 7; q++) BAR_INIT(XB + q, q == 2 ? 256 : q == 5 || q == 3 ? 9 : 1);
      BAR_ARM(XB + 3, 1024);
      BAR_ARM(XB + 5, 1024 + 64 + 512);
      *(volatile unsigned long long*)(smem + OFF_MASK) = 0;
    }
    if (warp != 11) {
      __syncwarp();
      asm volatile("fence.mbarrier_init.release.cluster;" ::: "memory");
      __threadfence_block();
      asm volatile("barrier.cluster.arrive.relaxed.aligned;" ::: "memory");
    }
    if (warp == 11) {
      asm volatile("barrier.cluster.wait.acquire.aligned;" ::: "memory");
      const unsigned epoch = *(volatile unsigned*)(smem + OFF_MASK + 8), par = (epoch + 1) & 1;
      mbar_wait(bar0 + 8 * (FB_KV + 15));
      for (int it = 0; ldx4(scr->cnt + 96 + 32 * (b >> 6)) != (epoch + 1) * 64 && it < SPIN_MAX; it++) {}
      uint4 hh;
      POLL { hh = ldx16(g_ml + (b >> 2) * 64 + 2 * lane); RETRY(X16(hh)) }
      int mi = __float_as_int(fmaxf(u2f(hh.x), u2f(hh.z)));
      mi ^= (mi >> 31) & 0x7fffffff;
      mi = __reduce_max_sync(~0u, mi);
      mi ^= (mi >> 31) & 0x7fffffff;
      const float M = __int_as_float(mi);
      const uint32_t wp = pack2(ex2(u2f(hh.x) - M), ex2(u2f(hh.z) - M));
      float L = bflo(wp) * u2f(hh.y) + bfhi(wp) * u2f(hh.w);
#pragma unroll
      for (int o2 = 16; o2; o2 >>= 1) L += __shfl_xor_sync(~0u, L, o2);
      *(uint32_t*)(smem + OFF_RA + lane * 4) = wp;
      if (lane == 0) *(float*)(smem + OFF_RA + 128) = rcp(L);
      __syncwarp();
      if (lane == 0) BAR_ARRIVE(XB + 6);
    }
    if (warp == 10) {
      if (lane < 8) asm volatile("prefetch.tensormap [%0];" ::"l"(&tms.m[lane + 1]) : "memory");
      asm volatile("barrier.cluster.wait.acquire.aligned;" ::: "memory");
      const unsigned epoch = *(volatile unsigned*)(smem + OFF_MASK + 8);
#pragma unroll 1
      for (int e = 0; e < 2; e++) {
        for (int it = 0; ldx4(scr->cnt + (e ? 2 + rk : 1)) != (epoch + 1) * (e ? 64 : 128) && it < SPIN_MAX; it++) {}
        if (lane == 0) BAR_ARRIVE(XB + e);
      }
      mbar_wait(bar0 + 8 * (FB_KV + 14));
      unsigned long long m = 0;
#pragma unroll 1
      for (int it = 0; ~m && it < SPIN_MAX; it++) {
        m = ldx64(scr->cnt + 32 + 32 * (b >> 6)) ^ ((epoch & 1) ? ~0ull : 0ull);
        if (lane == 0) *(volatile unsigned long long*)(smem + OFF_MASK) = m;
      }
    }
    if (warp == 9) {
      asm volatile("barrier.cluster.wait.acquire.aligned;" ::: "memory");
      const unsigned epoch = *(volatile unsigned*)(smem + OFF_MASK + 8);
      const unsigned par = (epoch + 1) & 1, inv = par ^ 1;
      const uint4 inv4 = make_uint4(inv, inv, inv, inv);
      mbar_wait(bar0 + 8 * FB_KV);
#pragma unroll 2
      for (int k = 0; k < 8; k++) {
        const uint32_t cp = ldc4(cvec + 2 * (lane + 32 * k));
        *(uint32_t*)(smem + OFF_SILU + (lane + 32 * k) * 4) = pack2(silu_bf(bflo(cp)), silu_bf(bfhi(cp)));
      }
      __syncwarp();
      mbar_wait(bar0 + 8 * FB_MOD);
      const uint32_t ab = sb + OFF_MOD + (8 * (lane >> 4) + (lane & 7)) * 32 + ((((lane >> 3) ^ (lane >> 2)) & 1) << 4);
      float d[4][4] = {};
#pragma unroll 2
      for (int s4 = 0; s4 < 8; s4++)
#pragma unroll
        for (int s = 0; s < 4; s++) {
          uint32_t a[4];
          const uint32_t* ps = (const uint32_t*)(smem + OFF_SILU) + 32 * s4 + 8 * s + tq;
          ldsm_t(a, ab + (4 * s4 + s) * 512); mma16(d[s], a, ps[0], ps[4]);
        }
      const float t = (tq & 1) ? (d[0][2] + d[1][2]) + (d[2][2] + d[3][2]) : (d[0][0] + d[1][0]) + (d[2][0] + d[3][0]);
      if (tq < 2) stx4(g_xm + b * 16 + 2 * (g & 6) + 2 * tq + (g & 1), fbits(bfr(t)));
      __syncwarp();
      if (lane == 0) CNT_ADD(6);
      mbar_wait(bar0 + 8 * (FB_KV + 8));
      if (lane < 16) stx16(g_xc + (b >> 2) * 256 + (lane >> 1) * 32 + (b & 3) * 8 + (lane & 1) * 4, inv4);
      if (lane < 8) stx16(g_xao + (b >> 5) * 1024 + (b & 15) * 64 + (lane & 4) * 8 + (b & 16) + (lane & 3) * 4, inv4);
      if (b < 112)
#pragma unroll 1
        for (int k = 0; k < 4; k++) stx16(g_xf + b * 512 + (lane + 32 * k) * 4, inv4);
      nbar_arrive(2, 288);
      for (int it = 0; ldx4(scr->cnt + 6) != (epoch + 1) * 128 && it < SPIN_MAX; it++) __nanosleep(100);
      {
        uint4 sv[2], cb[2];
        unsigned ga, gb;
        POLL {
#pragma unroll
          for (int k = 0; k < 2; k++) { sv[k] = ldx16(g_xm + 512 + 256 * rk + 4 * (lane + 32 * k)); cb[k] = ldx16(g_xm + 1024 + 256 * rk + 4 * (lane + 32 * k)); }
          ga = ldx4(g_xm + (b & 15) * 32 + lane); gb = ldx4(g_xm + 1536 + 256 * rk + 8 * (pr & 31) + (lane & 7));
          RETRY(X16(sv[0]) | X16(sv[1]) | X16(cb[0]) | X16(cb[1]) | lop_x3(ga, gb, par))
        }
#pragma unroll
        for (int k = 0; k < 2; k++) {
          const float c0 = bfr(1.f + bfhi(cb[k].x)), c1 = bfr(1.f + bfhi(cb[k].y)), c2 = bfr(1.f + bfhi(cb[k].z)), c3 = bfr(1.f + bfhi(cb[k].w));
          *(float4*)(smem + OFF_CO + (lane + 32 * k) * 16) = make_float4(c0, c1, c2, c3);
          uint2* pb = (uint2*)(smem + OFF_BP) + lane + 32 * k;
          pb[0] = make_uint2(pack2(c0, c1), pack2(c2, c3));
          pb[64] = make_uint2(__byte_perm(sv[k].x, sv[k].y, 0x7632), __byte_perm(sv[k].z, sv[k].w, 0x7632));
        }
        *(float*)(smem + OFF_CO + 1024 + lane * 4) = bfhi(ga);
        *(float*)(smem + OFF_CO + 1152 + lane * 4) = bfhi(gb);
      }
      __syncwarp();
      if (lane == 0) BAR_ARRIVE(XB + 4);
    }
    if (warp == 8) {
      const unsigned stag = ((pr * SMUL) & 63) * RATE_NS >> 6;
      unsigned tnext = t_off + 4 * RATE_H;
      asm volatile("barrier.cluster.wait.acquire.aligned;" ::: "memory");
#pragma unroll 1
      for (int k = 0; k < 24; k++) {
        const int code = (k < 12 ? ORDER0 >> (5 * k) : ORDER1 >> (5 * (k - 12))) & 31;
        const bool kv = code < 16;
        const int n = code, w = code - 16;
        if (!kv && w >= 5 && b >= 112) break;
        if (kv) mbar_wait(bar0 + 8 * (FB_KV + n - (n < 6 ? EWIN : KVWIN)));
        if (k >= TAIL_K) mbar_wait(bar0 + 8 * (FB_KV + (int)((ORDER1 >> (5 * (k - 12 - ((WINS >> (4 * (k - TAIL_K))) & 15)))) & 31)));
        const int e = kv ? (n == 3 ? 2 : n == 5 ? 1 : n) : w == 0 ? 0 : w < 5 ? 16 + ((w - 1) >> 1) : w == 7 ? 19 : 18;
        if (e != 1 && k) mbar_wait(bar0 + 8 * (EB + e));
        wait_until(tnext + stag);
        tnext += k > TAIL_K ? RATE_TL : k < 4 ? RATE_E : RATE_NS;
        if (lane == 0) {
          if (kv)
            asm volatile("cp.async.bulk.tensor.3d.shared::cluster.global.mbarrier::complete_tx::bytes.multicast::cluster.L2::cache_hint [%0], [%1, {%3, %4, %5}], [%2], %6, %7;"
                         ::"r"(sb + (n % NSLOT) * SLOT + rk * 16384), "l"(&tms.m[2]), "r"(bar0 + 8 * (FB_KV + n)), "r"(0), "r"(((n >> 1) * 64 + pr) * 64),
                           "r"(4 * (n & 1) + 2 * rk), "h"((unsigned short)3), "l"(stream_policy()) : "memory");
          else {
            tma3d(sb + (w == 0 ? OFF_MOD : w < 5 ? OFF_UV + (w - 1) * 16384 : w == 5 ? OFF_G : w == 6 ? OFF_U : OFF_D),
                  &tms.m[w == 0 ? 3 : w < 3 ? 4 : w < 5 ? 5 : w + 1], bar0 + 8 * (FB_MOD + w),
                  w == 0 ? 1024 + b * 16 : w < 3 || w == 7 ? 0 : w < 5 ? (pr & 7) * 64 : pr * 32, w == 7 ? b * 16 : w == 1 || w == 2 ? (b & 3) * 128 + (w - 1) * 64 : 0,
                  w == 1 || w == 2 ? 2 * hd : w == 3 || w == 4 ? (b >> 4) * 4 + 2 * rk + w - 3 : w == 5 || w == 6 ? rk : 0);
          }
        }
        __syncwarp();
      }
    }
    if (b < 112) {
      const int mt = warp & 1, dd = (warp >> 1) & 1;
      mbar_wait(bar0 + 8 * (XB + 4));
      const uint32_t ab = sb + (mt ? OFF_U : OFF_G) + (8 * (lane >> 4) + (lane & 7)) * 64 + (((2 * dd + ((lane >> 3) & 1)) ^ ((lane >> 1) & 3)) << 4);
      uint32_t base;
      asm volatile("mapa.shared::cluster.u32 %0, %1, %2;" : "=r"(base) : "r"(sb), "r"(dd));
      uint2 bb[16];
#pragma unroll
      for (int s = 0; s < 16; s++) bb[s] = *(const uint2*)(smem + OFF_BP + (g & 1) * 512 + (4 * s + tq) * 8);
      mbar_wait(bar0 + 8 * (FB_G + mt));
      float e[4][4] = {};
#pragma unroll
      for (int s = 0; s < 16; s++) { uint32_t a[4]; ldsm_t(a, ab + s * 1024); mma16(e[s & 3], a, bb[s].x, bb[s].y); }
      float r[4];
#pragma unroll
      for (int i = 0; i < 4; i++) r[i] = (e[0][i] + e[1][i]) + (e[2][i] + e[3][i]);
      if (tq < 2) st_async2(base + OFF_R4 + (8 * mt + g) * 176 + (10 * rk + 8 + tq) * 8, base + OFF_BAR + 8 * (XB + 5), tq ? r[1] : r[0], tq ? r[3] : r[2]);
    }
    return;
  }

  float* s_sm = (float*)(smem + OFF_SM);
  unsigned par, epoch;
  uint32_t rsb;
  {
    float* s_r4 = (float*)(smem + OFF_R4);
    asm volatile("barrier.cluster.arrive.relaxed.aligned;" ::: "memory");
    asm volatile("mapa.shared::cluster.u32 %0, %1, %2;" : "=r"(rsb) : "r"(sb), "r"(rk ^ 1));
    const float c0 = (arow & 1) ? bfhi(c0w) : bflo(c0w), c1 = (arow & 1) ? bfhi(c1w) : bflo(c1w);
    float acc[8] = {0, 0, 0, 0, 0, 0, 0, 0};
    fma8(acc, wm0, silu_bf(c0)); fma8(acc, wm1, silu_bf(c1));
    tred<4>(acc, lane, 8); tred<2>(acc, lane, 16);
    *(float2*)(s_r4 + warp * 64 + 8 * (lane & 7) + ((lane >> 1) & 4) + ((lane >> 3) & 2)) = make_float2(acc[0], acc[1]);
    nbar(1, 288);
    epoch = *(volatile unsigned*)(smem + OFF_MASK + 8);
    par = (epoch + 1) & 1;
    if (warp == 0) {
      float t = 0.f, ca = b < 16 ? 1.f : 0.f;
#pragma unroll
      for (int w = 0; w < 8; w++) { t += s_r4[w * 64 + lane]; ca += s_r4[w * 64 + 32 + lane]; }
      t += ca * s_sm[256 + lane];
      const float nb = __shfl_down_sync(~0u, t, 1);
      const uint32_t w0 = lane < 8 ? pack2t(t, nb, par) : pack2(t, nb);
      const uint32_t w1 = __shfl_down_sync(~0u, w0, 8), w2 = __shfl_down_sync(~0u, w0, 16), w3 = __shfl_down_sync(~0u, w0, 24);
      if (lane < 8 && !(lane & 1)) stx16(g_h + (b >> 5) * 512 + (b & 15) * 32 + (b & 16) + 2 * lane, make_uint4(w0, w1, w2, w3));
      __syncwarp();
      if (lane == 0) CNT_ADD(1);
    }
  }
  asm volatile("barrier.cluster.wait.acquire.aligned;" ::: "memory");
  {
    uint32_t a[4][4][4];
    mbar_wait(bar0 + 8 * (warp >> 1));
    const uint32_t ab = sb + OFF_WQ + (64 * warp + 8 * (lane >> 4) + (lane & 7)) * 128;
#pragma unroll
    for (int s = 0; s < 4; s++)
#pragma unroll
      for (int mt = 0; mt < 4; mt++) ldsm_t(a[s][mt], ab + s * 2048 + (((2 * mt + ((lane >> 3) & 1)) ^ (lane & 7)) << 4));
    uint4 v0, v1;
    const unsigned* ph = g_h + (g >> 1) * 512 + 64 * warp + 4 * (lane & 7);
    uint32_t off = OFF_B + warp * 272 + (32 * rk + 8 * tq + (lane & 4)) * 4;
    PIN(off); PINL(ph);
    mbar_wait(bar0 + 8 * XB);
    POLL { v0 = ldx16(ph); v1 = ldx16(ph + 32); RETRY(lop_x3(v0.x, v1.x, par)) }
    float d[4][4] = {};
#pragma unroll
    for (int mt = 0; mt < 4; mt++) {
      mma16(d[mt], a[0][mt], v0.x, v0.y); mma16(d[mt], a[1][mt], v0.z, v0.w);
      mma16(d[mt], a[2][mt], v1.x, v1.y); mma16(d[mt], a[3][mt], v1.z, v1.w);
    }
    float r[8];
#pragma unroll
    for (int mt = 0; mt < 4; mt++) { r[2 * mt] = d[mt][0] + d[mt][1]; r[2 * mt + 1] = d[mt][2] + d[mt][3]; }
    tred<4>(r, lane, 2); tred<2>(r, lane, 1);
    const float rc = __shfl_xor_sync(~0u, (lane & 4) ? r[0] : r[1], 4);
    const uint32_t wd = (lane & 4) ? pack2(rc, r[1]) : pack2(r[0], rc);
    const uint32_t w1 = __shfl_down_sync(~0u, wd, 8), w2 = __shfl_down_sync(~0u, wd, 16), w3 = __shfl_down_sync(~0u, wd, 24);
    asm volatile("{.reg .pred p; setp.lt.s32 p, %7, 8; @p st.shared.v4.b32 [%0], {%2,%3,%4,%5};\n"
                 "@p st.async.shared::cluster.mbarrier::complete_tx::bytes.v4.b32 [%1], {%2,%3,%4,%5}, [%6];}"
                 ::"r"(sb + off), "r"(rsb + off), "r"(wd), "r"(w1), "r"(w2), "r"(w3), "r"(rsb + OFF_BAR + 8 * QB), "r"(lane) : "memory");
    __syncwarp();
    arrive2(bar0 + 8 * QB, 0, lane == 0, false);
    arrive2(bar0 + 8 * (EB + 2), rsb + OFF_BAR + 8 * (EB + 2), lane == 0, lane == 0);
  }
  {
    uint32_t a[8][4];
    uint32_t a_bq = sb + OFF_B + (lane & 7) * 272 + (lane >> 3) * 16;
    unsigned* p_qa = g_qa + b * 64 + 8 * warp + 4 * lane;
    PIN(a_bq); PINL(p_qa);
    mbar_wait(bar0 + 8 * (FB_UK + (warp >> 2)));
    const uint32_t ab = sb + OFF_WUK + (warp >> 2) * 16384 + (16 * (warp & 3) + (lane & 15)) * 128;
#pragma unroll
    for (int s = 0; s < 8; s++) ldsm(a[s], ab + (s >> 2) * 8192 + (((2 * (s & 3) + (lane >> 4)) ^ (lane & 7)) << 4));
    mbar_wait(bar0 + 8 * QB);
    float d[4][4] = {};
#pragma unroll
    for (int y = 0; y < 4; y++) {
      uint32_t bq[4];
      ldsm(bq, a_bq + 64 * y);
      mma16(d[(2 * y) & 3], a[2 * y], bq[0], bq[1]); mma16(d[(2 * y + 1) & 3], a[2 * y + 1], bq[2], bq[3]);
    }
    float r[2] = {((d[0][0] + d[0][1]) + (d[1][0] + d[1][1])) + ((d[2][0] + d[2][1]) + (d[3][0] + d[3][1])),
                  ((d[0][2] + d[0][3]) + (d[1][2] + d[1][3])) + ((d[2][2] + d[2][3]) + (d[3][2] + d[3][3]))};
    tred<1>(r, lane, 1);
    r[0] += __shfl_xor_sync(~0u, r[0], 2);
    const float nb = __shfl_xor_sync(~0u, r[0], 4);
    const uint32_t w0 = lane < 8 ? pack2t(r[0], nb, par) : pack2(r[0], nb);
    const uint32_t w1 = __shfl_down_sync(~0u, w0, 8), w2 = __shfl_down_sync(~0u, w0, 16), w3 = __shfl_down_sync(~0u, w0, 24);
    if (lane < 2) stx16(p_qa, make_uint4(w0, w1, w2, w3));
    arrive2(bar0 + 8 * (EB + 4), rsb + OFF_BAR + 8 * (EB + 4), lane == 0, lane == 0);
  }
  {
    if (warp) nbar_arrive(3, 256); else { nbar(3, 256); if (lane == 0) CNT_ADD(2 + (b >> 6)); }
    asm volatile("setmaxnreg.inc.sync.aligned.u32 216;");
    const unsigned* pq = g_qa + rk * 4096 + tid * 4;
    uint32_t a_q = sb + OFF_Q + ((tid & 63) >> 3) * 2048 + (tid >> 6) * 128 + (((tid & 7) ^ (tid >> 6)) << 4);
    PINL(pq); PIN(a_q);
    mbar_wait(bar0 + 8 * (XB + 1));
    uint4 v[4];
    POLL {
#pragma unroll
      for (int k = 0; k < 4; k++) v[k] = ldx16(pq + 1024 * k);
      RETRY(lop_x3(v[0].x, v[1].x, par) | lop_x3(v[2].x, v[3].x, par))
    }
#pragma unroll
    for (int k = 0; k < 4; k++)
      asm volatile("st.shared.v4.b32 [%0], {%1,%2,%3,%4};" ::"r"((a_q + k * 512) ^ ((k & 1) << 6)), "r"(v[k].x), "r"(v[k].y), "r"(v[k].z), "r"(v[k].w) : "memory");
    if (warp >= 4) nbar_arrive(1, 256); else nbar(1, 256);
  }
  sb = __shfl_sync(~0u, sb, 0); bar0 = sb + OFF_BAR;
  if (warp < 4) {
    uint32_t qf[32][4];
#pragma unroll
    for (int s = 0; s < 32; s++) ldsm(qf[s], sb + OFF_Q + (s >> 2) * 2048 + (lane & 15) * 128 + (((2 * (s & 3) + (lane >> 4)) ^ (lane & 7)) << 4));
    float l0 = 0.f, l1 = 0.f, m0 = -1e30f, m1 = -1e30f;
    const float sc = 0.08838834764831845f * 1.4426950408889634f;
    const uint32_t kofs = (16 * warp + 8 * (lane >> 4) + (lane & 7)) * 128 + ((((lane >> 3) & 1) ^ (lane & 7)) << 4);
    uint32_t st = sb;
#pragma unroll 1
    for (int t = 0; t < 8; t++) {
      float sa[4][4] = {};
#pragma unroll
      for (int hf = 0; hf < 2; hf++) {
        const int n = 2 * t + hf;
        mbar_wait(bar0 + 8 * (FB_KV + n));
        uint32_t kf[16][4];
#pragma unroll
        for (int y = 0; y < 16; y++) ldsm(kf[y], st + (y >> 2) * 8192 + (kofs ^ ((y & 3) << 5)));
#pragma unroll
        for (int y = 0; y < 16; y++) {
          mma16(sa[(2 * y) & 3], qf[16 * hf + y], kf[y][0], kf[y][1]); mma16(sa[((2 * y) & 3) + 1], qf[16 * hf + y], kf[y][2], kf[y][3]);
        }
        __syncwarp();
        arrive2(bar0 + 8 * (EB + NSLOT + n), rsb + OFF_BAR + 8 * (EB + NSLOT + n), lane == 0 && n < 14, lane == 0 && n < 16 - NSLOT);
        if (hf == 0) arrive2(bar0 + 8 * EB, 0, lane == 0 && t == 0, false);
        st = st + SLOT == sb + NSLOT * SLOT ? sb : st + SLOT;
      }
#pragma unroll
      for (int i = 0; i < 4; i++) { sa[0][i] = (sa[0][i] + sa[2][i]) * sc; sa[1][i] = (sa[1][i] + sa[3][i]) * sc; }
      float cm[2] = {fmaxf(fmaxf(sa[0][0], sa[0][1]), fmaxf(sa[1][0], sa[1][1])), fmaxf(fmaxf(sa[0][2], sa[0][3]), fmaxf(sa[1][2], sa[1][3]))};
      tmax<1>(cm, lane, 1);
      cm[0] = fmaxf(cm[0], __shfl_xor_sync(~0u, cm[0], 2));
      float* pm = s_sm + (t & 1) * 64;
      if (tq < 2) pm[(g + 8 * tq) * 4 + warp] = cm[0];
      if (t >= 2) nbar(6 + (t & 1), 256); else nbar(3, 128);
      const float4 a0 = *(const float4*)(pm + g * 4), b0 = *(const float4*)(pm + g * 4 + 32);
      const float n0 = fmaxf(fmaxf(fmaxf(a0.x, a0.y), fmaxf(a0.z, a0.w)), m0), n1 = fmaxf(fmaxf(fmaxf(b0.x, b0.y), fmaxf(b0.z, b0.w)), m1);
      uint32_t pk[4];
#pragma unroll
      for (int i = 0; i < 2; i++) { pk[2 * i] = pack2(ex2(sa[i][0] - n0), ex2(sa[i][1] - n0)); pk[2 * i + 1] = pack2(ex2(sa[i][2] - n1), ex2(sa[i][3] - n1)); }
      *(uint4*)(smem + OFF_P + (t & 1) * 2048 + tid * 16) = make_uint4(pk[0], pk[1], pk[2], pk[3]);
      const float al0 = ex2(m0 - n0), al1 = ex2(m1 - n1);
      if (tid < 32 && tq == 0) *(float2*)(s_sm + 192 + (t & 1) * 16 + 2 * g) = make_float2(al0, al1);
      nbar_arrive(4 + (t & 1), 256);
      m0 = n0; m1 = n1;
      l0 = l0 * al0 + (bflo(pk[0]) + bfhi(pk[0])) + (bflo(pk[2]) + bfhi(pk[2]));
      l1 = l1 * al1 + (bflo(pk[1]) + bfhi(pk[1])) + (bflo(pk[3]) + bfhi(pk[3]));
    }
    float lr[2] = {l0, l1};
    tred<1>(lr, lane, 1);
    lr[0] += __shfl_xor_sync(~0u, lr[0], 2);
    if (tq < 2) s_sm[128 + (g + 8 * tq) * 4 + warp] = lr[0];
    nbar(3, 128);
    if (warp == 0 && tq < 2) {
      const float4 a0 = *(const float4*)(s_sm + 128 + (g + 8 * tq) * 4);
      stx8(g_ml + (16 * rk + g + 8 * tq) * 64 + pr, make_uint2(fbits(tq ? m1 : m0), fbits((a0.x + a0.y) + (a0.z + a0.w))));
    }
    if (warp == 0) { __syncwarp(); if (lane == 0) CNT_ADD(96 + 32 * rk); }
    nbar(2, 288);
    if (tid == 0) asm volatile("red.relaxed.gpu.global.xor.b64 [%0], %1;" ::"l"(scr->cnt + 32 + 32 * rk), "l"(1ull << pr) : "memory");
  } else {
    float o[16][4] = {};
    const uint32_t vofs = (warp & 1) * 16384 + (lane & 15) * 128 + (((lane >> 4) ^ (lane & 7)) << 4);
    const int hf = (warp >> 1) & 1;
    uint32_t st = sb + hf * SLOT;
    auto pv = [&](const int t, auto np) {
      constexpr int npre = decltype(np)::value;
      uint32_t vf[4][8][4];
      const int n = 2 * t + hf;
      mbar_wait(bar0 + 8 * (FB_KV + n));
#pragma unroll
      for (int s = 0; s < npre; s++)
#pragma unroll
        for (int y = 0; y < 8; y++) ldsm_t(vf[s][y], st + (y >> 2) * 8192 + s * 2048 + (vofs ^ ((y & 3) << 5)));
      nbar(4 + (t & 1), 256);
      const float2 al = *(const float2*)(s_sm + 192 + (t & 1) * 16 + 2 * g);
      uint4 pf[4];
#pragma unroll
      for (int s = 0; s < 4; s++) pf[s] = *(const uint4*)(smem + OFF_P + (t & 1) * 2048 + s * 512 + lane * 16);
      if (t < 6) nbar_arrive(6 + (t & 1), 256);
#pragma unroll
      for (int s = npre; s < 4; s++)
#pragma unroll
        for (int y = 0; y < 8; y++) ldsm_t(vf[s][y], st + (y >> 2) * 8192 + s * 2048 + (vofs ^ ((y & 3) << 5)));
#pragma unroll
      for (int nt = 0; nt < 16; nt++) { o[nt][0] *= al.x; o[nt][1] *= al.x; o[nt][2] *= al.y; o[nt][3] *= al.y; }
#pragma unroll
      for (int s = 0; s < 4; s++) {
        const uint32_t pa[4] = {pf[s].x, pf[s].y, pf[s].z, pf[s].w};
#pragma unroll
        for (int y = 0; y < 8; y++) { mma16(o[2 * y], pa, vf[s][y][0], vf[s][y][1]); mma16(o[2 * y + 1], pa, vf[s][y][2], vf[s][y][3]); }
      }
      __syncwarp();
      arrive2(bar0 + 8 * (EB + NSLOT + n), rsb + OFF_BAR + 8 * (EB + NSLOT + n), lane == 0 && n < 14, lane == 0 && n < 16 - NSLOT);
      st = st + 2 * SLOT >= sb + NSLOT * SLOT ? st - (NSLOT - 2) * SLOT : st + 2 * SLOT;
    };
#pragma unroll 1
    for (int t = 0; t < 7; t++) pv(t, IC<NPRE0>());
    pv(7, IC<NPRE1>());
    uint4* po = g_xo + ((size_t)((16 * rk + (g & 6)) * 4 + warp - 4) * 64 + pr) * RS + (lane & 7);
    const bool odd = lane & 4;
#pragma unroll
    for (int e = 0; e < 2; e++)
#pragma unroll
      for (int j2 = 0; j2 < 2; j2++) {
        uint32_t c0[4], c1[4];
#pragma unroll
        for (int i = 0; i < 4; i++) {
          c0[i] = i ? pack2(o[8 * j2 + i][2 * e], o[8 * j2 + i][2 * e + 1]) : pack2t(o[8 * j2][2 * e], o[8 * j2][2 * e + 1], par);
          c1[i] = i ? pack2(o[8 * j2 + 4 + i][2 * e], o[8 * j2 + 4 + i][2 * e + 1]) : pack2t(o[8 * j2 + 4][2 * e], o[8 * j2 + 4][2 * e + 1], par);
          const uint32_t r = __shfl_xor_sync(~0u, odd ? c0[i] : c1[i], 4);
          if (odd) c0[i] = r; else c1[i] = r;
        }
        stx16(po + e * 8 * 4 * 64 * RS + 8 * j2, make_uint4(c0[0], c0[1], c0[2], c0[3]));
        stx16(po + (e * 8 + 1) * 4 * 64 * RS + 8 * j2, make_uint4(c1[0], c1[1], c1[2], c1[3]));
      }
    nbar_arrive(2, 288);
  }
  tail(smem, scr, x, out, par, epoch, warp);
}

static void launch(void* const* d_in, void* d_out) {
  static TMaps tms;
  static bool init = false;
  static void* scr = nullptr;
  if (!init) {
    void* fn = nullptr; cudaDriverEntryPointQueryResult qr;
    cudaGetDriverEntryPoint("cuTensorMapEncodeTiled", &fn, cudaEnableDefault, &qr);
    EncFn f = (EncFn)fn;
    const CUtensorMapSwizzle S32 = CU_TENSOR_MAP_SWIZZLE_32B, S64 = CU_TENSOR_MAP_SWIZZLE_64B, S128 = CU_TENSOR_MAP_SWIZZLE_128B;
    const CUtensorMapL2promotion P128 = CU_TENSOR_MAP_L2_PROMOTION_L2_128B, P256 = CU_TENSOR_MAP_L2_PROMOTION_L2_256B;
    enc3d(f, &tms.m[0], d_in[2], 64, 512, 64, 8192, 128, 64, 128, 1, S128, P128);
    enc3d(f, &tms.m[1], d_in[3], 64, 512, 64, 8192, 128, 64, 64, 2, S128, P256);
    enc3d(f, &tms.m[2], d_in[1], 64, SK, 8, 1024, 128, 64, 64, 2, S128, P256);
    enc3d(f, &tms.m[3], d_in[11], 3072, 256, 2, 6144, 256 * 6144, 16, 256, 2, S32, P128);
    enc3d(f, &tms.m[4], d_in[4], 64, 512, 64, 8192, 128, 64, 64, 2, S128, P256);
    enc3d(f, &tms.m[5], d_in[5], 512, 128, 32, 1024, 128 * 1024, 64, 128, 1, S128, P128);
    enc3d(f, &tms.m[6], d_in[7], 1792, 256, 2, 3584, 256 * 3584, 32, 256, 1, S64, P128);
    enc3d(f, &tms.m[7], d_in[8], 1792, 256, 2, 3584, 256 * 3584, 32, 256, 1, S64, P128);
    enc3d(f, &tms.m[8], d_in[9], 64, 1792, 8, 1024, 128, 64, 16, 8, S128, P256);
    cudaFuncSetAttribute(fused_kernel, cudaFuncAttributeMaxDynamicSharedMemorySize, SMEM_BYTES);
    cudaGetSymbolAddress(&scr, g_scr);
    init = true;
  }
  fused_kernel<<<NCTA, 384, SMEM_BYTES>>>((const bf16*)d_in[0], (const bf16*)d_in[10], (const bf16*)d_in[11], (bf16*)d_out, (Scratch*)scr, tms);
}

}

extern "C" void kernel_launch(void* const* d_in, const int* in_sizes, int n_in, void* d_out, int out_size) {
  static int big = -1;
  if (big < 0) big = v9::fits();
  if (big) v9::launch(d_in, d_out); else v8::launch(d_in, d_out);
}
```

```cpp
#include <cuda_runtime.h>
#include <cuda_bf16.h>
#include <cuda.h>
#include <stdint.h>
#include <stdio.h>
#include <stdlib.h>

typedef CUresult (*EncFn)(CUtensorMap*, CUtensorMapDataType, cuuint32_t, void*, const cuuint64_t*, const cuuint64_t*,
                          const cuuint32_t*, const cuuint32_t*, CUtensorMapInterleave, CUtensorMapSwizzle,
                          CUtensorMapL2promotion, CUtensorMapFloatOOBfill);

static void enc3d(EncFn fn, CUtensorMap* tm, void* p, uint64_t d0, uint64_t d1, uint64_t d2, uint64_t s1, uint64_t s2, uint32_t b0,
                  uint32_t b1, uint32_t b2, CUtensorMapSwizzle sw, CUtensorMapL2promotion pr) {
  cuuint64_t gd[3] = {d0, d1, d2}, gs[2] = {s1, s2};
  cuuint32_t bx[3] = {b0, b1, b2}, es[3] = {1, 1, 1};
  fn(tm, CU_TENSOR_MAP_DATA_TYPE_BFLOAT16, 3, p, gd, gs, bx, es, CU_TENSOR_MAP_INTERLEAVE_NONE, sw, pr, CU_TENSOR_MAP_FLOAT_OOB_FILL_NONE);
}

namespace v9 {
typedef __nv_bfloat16 bf16;
#define SK 32768
#define SPIN_MAX (1 << 20)
template <int N> struct IC { static constexpr int value = N; };

__device__ __forceinline__ uint32_t s2u(const void* p) { return (uint32_t)__cvta_generic_to_shared(p); }
__device__ __forceinline__ float bflo(uint32_t u) { return __uint_as_float(u << 16); }
__device__ __forceinline__ float bfhi(uint32_t u) { return __uint_as_float(u & 0xffff0000u); }
__device__ __forceinline__ float u2f(uint32_t u) { return __uint_as_float(u); }
__device__ __forceinline__ void fma8(float* acc, uint4 v, float s) {
  acc[0] += s * bflo(v.x); acc[1] += s * bfhi(v.x); acc[2] += s * bflo(v.y); acc[3] += s * bfhi(v.y);
  acc[4] += s * bflo(v.z); acc[5] += s * bfhi(v.z); acc[6] += s * bflo(v.w); acc[7] += s * bfhi(v.w);
}
__device__ __forceinline__ uint32_t pack2(float a, float b) {
  __nv_bfloat162 p = __floats2bfloat162_rn(a, b); return *(uint32_t*)&p;
}
__device__ __forceinline__ float bfr(float v) { return bfhi(pack2(v, v)); }
__device__ __forceinline__ float silu_bf(float c) { return bfr(__fdividef(c, 1.f + __expf(-c))); }
#define fbits(v) ((__float_as_uint(v) & ~1u) | par)
__device__ __forceinline__ uint32_t pack2t(float a, float b, unsigned par) {
  const uint32_t ua = ((__float_as_uint(a) + ((par ^ 1) << 16)) & 0xFFFE0000u) | (par << 16);
  return __byte_perm(ua, pack2(b, b), 0x7632);
}
__device__ __forceinline__ void nbar(int id, int n) { asm volatile("bar.sync %0, %1;" ::"r"(id), "r"(n) : "memory"); }
__device__ __forceinline__ void nbar_arrive(int id, int n) { asm volatile("bar.arrive %0, %1;" ::"r"(id), "r"(n) : "memory"); }
__device__ __forceinline__ uint4 ldc16(const void* p) {
  uint4 v; asm volatile("ld.relaxed.cta.global.v4.u32 {%0,%1,%2,%3}, [%4];" : "=r"(v.x), "=r"(v.y), "=r"(v.z), "=r"(v.w) : "l"(p) : "memory"); return v;
}
__device__ __forceinline__ unsigned ldc4(const void* p) {
  unsigned v; asm volatile("ld.relaxed.cta.global.u32 %0, [%1];" : "=r"(v) : "l"(p) : "memory"); return v;
}
__device__ __forceinline__ uint4 ldx16(const void* p) {
  uint4 v; asm volatile("ld.relaxed.gpu.global.v4.u32 {%0,%1,%2,%3}, [%4];" : "=r"(v.x), "=r"(v.y), "=r"(v.z), "=r"(v.w) : "l"(p) : "memory"); return v;
}
__device__ __forceinline__ unsigned ldx4(const void* p) {
  unsigned v; asm volatile("ld.relaxed.gpu.global.u32 %0, [%1];" : "=r"(v) : "l"(p) : "memory"); return v;
}
__device__ __forceinline__ unsigned long long ldx64(const void* p) {
  unsigned long long v; asm volatile("ld.relaxed.gpu.global.u64 %0, [%1];" : "=l"(v) : "l"(p) : "memory"); return v;
}
__device__ __forceinline__ void stx16(void* p, uint4 v) {
  asm volatile("st.relaxed.gpu.global.v4.u32 [%0], {%1,%2,%3,%4};" ::"l"(p), "r"(v.x), "r"(v.y), "r"(v.z), "r"(v.w) : "memory");
}
__device__ __forceinline__ void stx8(void* p, uint2 v) { asm volatile("st.relaxed.gpu.global.v2.u32 [%0], {%1,%2};" ::"l"(p), "r"(v.x), "r"(v.y) : "memory"); }
__device__ __forceinline__ void stx4(void* p, unsigned v) { asm volatile("st.relaxed.gpu.global.u32 [%0], %1;" ::"l"(p), "r"(v) : "memory"); }
__device__ __forceinline__ void pub4(void* p, unsigned v) { asm volatile("red.relaxed.gpu.global.xor.b32 [%0], %1;" ::"l"(p), "r"(v) : "memory"); }
__device__ __forceinline__ void pub8(void* p, unsigned lo, unsigned hi) {
  asm volatile("{.reg .b64 t; mov.b64 t, {%1, %2}; red.relaxed.gpu.global.xor.b64 [%0], t;}" ::"l"(p), "r"(lo), "r"(hi) : "memory");
}
__device__ __forceinline__ unsigned lop_x3(unsigned a, unsigned b, unsigned c) {
  unsigned d; asm("lop3.b32 %0, %1, %2, %3, 0x7E;" : "=r"(d) : "r"(a), "r"(b), "r"(c)); return d; }
__device__ __forceinline__ unsigned or3(unsigned a, unsigned b, unsigned c) {
  unsigned d; asm("lop3.b32 %0, %1, %2, %3, 0xFE;" : "=r"(d) : "r"(a), "r"(b), "r"(c)); return d; }
__device__ __forceinline__ unsigned and3(unsigned a, unsigned b, unsigned c) {
  unsigned d; asm("lop3.b32 %0, %1, %2, %3, 0x80;" : "=r"(d) : "r"(a), "r"(b), "r"(c)); return d; }
__device__ __forceinline__ unsigned dep16(const uint32_t* f) {
  unsigned d = 0;
#pragma unroll
  for (int i = 0; i < 8; i++) d = or3(d, f[8 * i], f[8 * i + 4]);
  return d;
}
__device__ __forceinline__ unsigned dep12(const uint32_t* f) {
  unsigned d = 0;
#pragma unroll
  for (int i = 0; i < 6; i++) d = or3(d, f[8 * i], f[8 * i + 4]);
  return d;
}
__device__ __forceinline__ uint2 ldx8(const void* p) {
  uint2 v; asm volatile("{.reg .b64 t; ld.relaxed.gpu.global.b64 t, [%2]; mov.b64 {%0, %1}, t;}" : "=r"(v.x), "=r"(v.y) : "l"(p) : "memory"); return v;
}
__device__ __forceinline__ float lds4(uint32_t a) { float v; asm volatile("ld.shared.f32 %0, [%1];" : "=f"(v) : "r"(a) : "memory"); return v; }
__device__ __forceinline__ float shx(float v, int m) {
  float r; asm volatile("shfl.sync.bfly.b32 %0, %1, %2, 0x1f, 0xffffffff;" : "=f"(r) : "f"(v), "r"(m)); return r;
}
__device__ __forceinline__ uint32_t mbar_test(uint32_t bar, uint32_t ph) {
  uint32_t ok;
  asm volatile("{.reg .pred p; mbarrier.test_wait.parity.shared::cta.b64 p, [%1], %2; vote.sync.all.pred p, p, 0xffffffff; selp.u32 %0, 1, 0, p;}"
               : "=r"(ok) : "r"(bar), "r"(ph) : "memory");
  return ok;
}
#define X16(v) (lop_x3(v.x, v.y, par) | lop_x3(v.z, v.w, par))
#define RETRY(bad) if (!__any_sync(~0u, (bad) & 1) || ++it_ >= SPIN_MAX) break;
#define POLL _Pragma("unroll 1") for (int it_ = 0;;)
__device__ __forceinline__ void mbar_wait(uint32_t bar, uint32_t ph = 0) {
  asm volatile("{.reg .pred p; .reg .u32 n; mov.u32 n, 0;\n"
               "W%=: mbarrier.try_wait.parity.shared::cta.b64 p, [%0], %1; add.u32 n, n, 1; setp.lt.and.u32 p, n, 0x100000, !p; @p bra W%=;}"
               ::"r"(bar), "r"(ph) : "memory");
}
__device__ __forceinline__ float ex2(float v) { float r; asm("ex2.approx.ftz.f32 %0, %1;" : "=f"(r) : "f"(v)); return r; }
__device__ __forceinline__ float rcp(float v) { float r; asm("rcp.approx.ftz.f32 %0, %1;" : "=f"(r) : "f"(v)); return r; }
__device__ __forceinline__ void mma16(float* d, const uint32_t* a, uint32_t b0, uint32_t b1) {
  asm volatile("mma.sync.aligned.m16n8k16.row.col.f32.bf16.bf16.f32 {%0,%1,%2,%3}, {%4,%5,%6,%7}, {%8,%9}, {%0,%1,%2,%3};"
               : "+f"(d[0]), "+f"(d[1]), "+f"(d[2]), "+f"(d[3]) : "r"(a[0]), "r"(a[1]), "r"(a[2]), "r"(a[3]), "r"(b0), "r"(b1));
}
__device__ __forceinline__ void mma16c(float* d, const uint32_t* a, uint32_t b0, uint32_t b1, const float* c) {
  asm volatile("mma.sync.aligned.m16n8k16.row.col.f32.bf16.bf16.f32 {%0,%1,%2,%3}, {%4,%5,%6,%7}, {%8,%9}, {%10,%11,%12,%13};"
               : "=f"(d[0]), "=f"(d[1]), "=f"(d[2]), "=f"(d[3])
               : "r"(a[0]), "r"(a[1]), "r"(a[2]), "r"(a[3]), "r"(b0), "r"(b1), "f"(c[0]), "f"(c[1]), "f"(c[2]), "f"(c[3]));
}
__device__ __forceinline__ float4 lds16(uint32_t a) {
  float4 v; asm volatile("ld.shared.v4.f32 {%0,%1,%2,%3}, [%4];" : "=f"(v.x), "=f"(v.y), "=f"(v.z), "=f"(v.w) : "r"(a) : "memory"); return v;
}
__device__ __forceinline__ void sts4(uint32_t a, float v) { asm volatile("st.shared.f32 [%0], %1;" ::"r"(a), "f"(v) : "memory"); }
__device__ __forceinline__ void sts16(uint32_t a, uint4 v) {
  asm volatile("st.shared.v4.b32 [%0], {%1,%2,%3,%4};" ::"r"(a), "r"(v.x), "r"(v.y), "r"(v.z), "r"(v.w) : "memory");
}
__device__ __forceinline__ void ldsm_t(uint32_t* r, uint32_t a) {
  asm volatile("ldmatrix.sync.aligned.m8n8.x4.trans.shared.b16 {%0,%1,%2,%3}, [%4];" : "=r"(r[0]), "=r"(r[1]), "=r"(r[2]), "=r"(r[3]) : "r"(a) : "memory");
}
__device__ __forceinline__ void ldsm(uint32_t* r, uint32_t a) {
  asm volatile("ldmatrix.sync.aligned.m8n8.x4.shared.b16 {%0,%1,%2,%3}, [%4];" : "=r"(r[0]), "=r"(r[1]), "=r"(r[2]), "=r"(r[3]) : "r"(a) : "memory");
}
__device__ __forceinline__ uint32_t mapa(uint32_t a, uint32_t r) {
  uint32_t v; asm volatile("mapa.shared::cluster.u32 %0, %1, %2;" : "=r"(v) : "r"(a), "r"(r)); return v;
}
__device__ __forceinline__ unsigned long long mapg(uint32_t a, uint32_t r) {
  unsigned long long v;
  asm volatile("{.reg .u32 t; .reg .u64 u; mapa.shared::cluster.u32 t, %1, %2; cvt.u64.u32 u, t; cvta.shared::cluster.u64 %0, u;}" : "=l"(v) : "r"(a), "r"(r));
  return v;
}
template <int N>
__device__ __forceinline__ void tred(float* a, int lane, int m) {
  const bool hi = lane & m;
#pragma unroll
  for (int i = 0; i < N; i++) {
    float send = hi ? a[i] : a[i + N], keep = hi ? a[i + N] : a[i];
    a[i] = keep + __shfl_xor_sync(~0u, send, m);
  }
}
template <int N>
__device__ __forceinline__ void tmax(float* a, int lane, int m) {
  const bool hi = lane & m;
#pragma unroll
  for (int i = 0; i < N; i++) {
    float send = hi ? a[i] : a[i + N], keep = hi ? a[i + N] : a[i];
    a[i] = fmaxf(keep, __shfl_xor_sync(~0u, send, m));
  }
}
__device__ __forceinline__ void arrive_n(uint32_t bar, bool on, int cnt) {
  asm volatile("{.reg .pred p; setp.ne.s32 p, %1, 0; @p mbarrier.arrive.shared::cta.b64 _, [%0], %2;}" ::"r"(bar), "r"((int)on), "r"(cnt) : "memory");
}
__device__ __forceinline__ unsigned long long stream_policy() {
  unsigned long long p;
  asm volatile("createpolicy.fractional.L2::evict_first.b64 %0, 1.0;" : "=l"(p));
  return p;
}
__device__ __forceinline__ void tma3d(uint32_t dst, const CUtensorMap* tm, uint32_t bar, int c0, int c1, int c2) {
  asm volatile("cp.async.bulk.tensor.3d.shared::cluster.global.mbarrier::complete_tx::bytes.L2::cache_hint [%0], [%1, {%3, %4, %5}], [%2], %6;"
               ::"r"(dst), "l"(tm), "r"(bar), "r"(c0), "r"(c1), "r"(c2), "l"(stream_policy()) : "memory");
}
__device__ __forceinline__ void spin_until(unsigned t) { while ((int)((unsigned)clock() - t) < 0) {} }
__device__ __forceinline__ void wait_until(unsigned t) {
  unsigned now;
  do { asm volatile("mov.u32 %0, %%globaltimer_lo;" : "=r"(now)); } while ((int)(now - t) < 0);
}
__device__ __forceinline__ void sleep_until(unsigned t) {
  unsigned now;
#pragma unroll 1
  do {
    __nanosleep(200);
    asm volatile("mov.u32 %0, %%globaltimer_lo;" : "=r"(now));
  } while ((int)(now - t) < 0);
}
#define PIN(x) asm volatile("" : "+r"(x))
#define PINL(x) asm volatile("" : "+l"(x))
#define BAR_ARRIVE(i) asm volatile("mbarrier.arrive.shared::cta.b64 _, [%0];" ::"r"(bar0 + 8 * (i)) : "memory")
#define LANE0(op, p, c, v) asm volatile("{.reg .pred q; setp.eq.s32 q, %2, 0; @q " op " [%0], %1;}" ::"l"((p) + lane), c(v), "r"(lane) : "memory")
#define CNT_ADD(c) LANE0("red.relaxed.gpu.global.add.u32", scr->cnt + (c), "r", 1)
#define BAR_INIT(i, cnt) asm volatile("mbarrier.init.shared::cta.b64 [%0], %1;" ::"r"(bar0 + 8 * (i)), "r"(cnt) : "memory")
#define BAR_ARM(i, bytes) asm volatile("mbarrier.arrive.expect_tx.shared::cta.b64 _, [%0], %1;" ::"r"(bar0 + 8 * (i)), "r"(bytes) : "memory")
struct TMaps { CUtensorMap m[9]; };

#define NCTA9 120
#define TAU 20
#define NSL 100
#define NPE 1
#define QN 4
#define FDLY 60
#define VJ 1
#define LDLY 35
#define NSP 4
#define NPO 3
#define O_Q 131072
#define O_LZ 163840
#define O_CTX 196608
#define O_HZ 198656
#define O_HW 200704
#define O_X 201728
#define O_P 218112
#define O_B 222208
#define O_R 224512
#define O_SILU 228608
#define O_SM 229632
#define O_BAR 231424
#define O_EP (O_BAR + 256)
#define O_DBG (O_EP + 16)
#define SMEM9 (O_DBG + 144)
#define B_FULL 0
#define B_FM 8
#define B_EMPTY 10
#define B_LZ 18
#define B_Q2 19
#define B_H 20
#define B_QF 21
#define B_TAB 22
#define B_W 23
#define B_ST 24
#define B_HZ 25
#define B_WZ 26
#define B_G 27
#define B_G2 28
enum { T_WQ, T_WUK, T_KV, T_MOD, T_UV, T_WO, T_GU, T_DN = 8 };
#define NBIG 40
struct Sched { unsigned zero, dth; uint2 r[3][8]; unsigned nr[3], nt[3], dt, t4, d4, d6, wt, pad; };

struct __align__(128) Scratch {
  unsigned cnt[8 * 32];
  uint2 rec[32 * 4 * 8 * 64];
  uint2 hdr[32 * 16];
  unsigned h[8 * 256];
  uint4 qa[2048];
  unsigned xao[8 * 512];
  unsigned xab[8 * 256];
  unsigned xm[2048];
};
__device__ Scratch g_scr;
#define SMEM_BASE 1024u
#define DSC ((SMEM_BASE >> 4) | (1u << 16))
#define HI128 (64u | (1u << 30))
#define HI64 (32u | (2u << 30))
template <int TA, int TB, unsigned HIA, unsigned HIB>
__device__ __forceinline__ void wgmma32(float* d, uint32_t da, uint32_t db, int acc) {
  asm volatile("{.reg .pred p; .reg .b64 da, db; setp.ne.b32 p, %18, 0; mov.b64 da, {%16, %21}; mov.b64 db, {%17, %22};\n"
               "wgmma.mma_async.sync.aligned.m64n32k16.f32.bf16.bf16 "
               "{%0,%1,%2,%3,%4,%5,%6,%7,%8,%9,%10,%11,%12,%13,%14,%15}, da, db, p, 1, 1, %19, %20;}"
               : "+f"(d[0]), "+f"(d[1]), "+f"(d[2]), "+f"(d[3]), "+f"(d[4]), "+f"(d[5]), "+f"(d[6]), "+f"(d[7]),
                 "+f"(d[8]), "+f"(d[9]), "+f"(d[10]), "+f"(d[11]), "+f"(d[12]), "+f"(d[13]), "+f"(d[14]), "+f"(d[15])
               : "r"(da), "r"(db), "r"(acc), "n"(TA), "n"(TB), "n"(HIA), "n"(HIB));
}
__device__ __forceinline__ void wgmma32r(float* d, const uint32_t* a, uint32_t db) {
  asm volatile("{.reg .b64 db; mov.b64 db, {%20, %21};\n"
               "wgmma.mma_async.sync.aligned.m64n32k16.f32.bf16.bf16 "
               "{%0,%1,%2,%3,%4,%5,%6,%7,%8,%9,%10,%11,%12,%13,%14,%15}, {%16,%17,%18,%19}, db, 1, 1, 1, 1;}"
               : "+f"(d[0]), "+f"(d[1]), "+f"(d[2]), "+f"(d[3]), "+f"(d[4]), "+f"(d[5]), "+f"(d[6]), "+f"(d[7]),
                 "+f"(d[8]), "+f"(d[9]), "+f"(d[10]), "+f"(d[11]), "+f"(d[12]), "+f"(d[13]), "+f"(d[14]), "+f"(d[15])
               : "r"(a[0]), "r"(a[1]), "r"(a[2]), "r"(a[3]), "r"(db), "n"(HI64));
}
template <int N> __device__ __forceinline__ void wg_wait(float* a) {
  asm volatile("wgmma.wait_group.sync.aligned %16;"
               : "+f"(a[0]), "+f"(a[1]), "+f"(a[2]), "+f"(a[3]), "+f"(a[4]), "+f"(a[5]), "+f"(a[6]), "+f"(a[7]), "+f"(a[8]), "+f"(a[9]), "+f"(a[10]),
                 "+f"(a[11]), "+f"(a[12]), "+f"(a[13]), "+f"(a[14]), "+f"(a[15]) : "n"(N) : "memory");
}
__device__ __forceinline__ void send32(uint32_t a, uint32_t bar, float v, int lane, int off) {
  const uint32_t w = pack2(v, __shfl_down_sync(~0u, v, 1));
  const int s = 2 * (lane & 3);
  asm volatile("{.reg .pred p; setp.eq.s32 p, %6, 0; @p st.async.shared::cluster.mbarrier::complete_tx::bytes.v4.b32 [%0], {%1,%2,%3,%4}, [%5];}"
               ::"r"(a), "r"(__shfl_sync(~0u, w, s)), "r"(__shfl_sync(~0u, w, s + 8)), "r"(__shfl_sync(~0u, w, s + 16)), "r"(__shfl_sync(~0u, w, s + 24)),
                 "r"(bar), "r"(off) : "memory");
}
__device__ __forceinline__ float sum8(uint32_t a) {
  const float4 p = lds16(a), q = lds16(a + 1024);
  return ((p.x + p.y) + (p.z + p.w)) + ((q.x + q.y) + (q.z + q.w));
}
__device__ __forceinline__ int posof(int c) { return (c & ~14) + 2 * (c & 6) + ((c >> 2) & 2); }

__global__ void __cluster_dims__(8, 1, 1) __launch_bounds__(384, 1)
fused_kernel(const bf16* __restrict__ x, const bf16* __restrict__ cvec, const bf16* __restrict__ w_mod, bf16* __restrict__ out,
             Scratch* __restrict__ scr, const __grid_constant__ Sched sch, const __grid_constant__ TMaps tms) {
  extern __shared__ __align__(1024) unsigned char smem[];
  const int tid = threadIdx.x, lane = tid & 31;
  const int b = blockIdx.x, cl = b >> 3, rn = b & 7, rk = b & 1, hd = b >> 1, f = b - 64;
  const bool isA = b < 64;
  uint32_t sb = s2u(smem), bar0 = sb + O_BAR;
  const int g = lane >> 2, tq = lane & 3;
  const int arow = 64 * rn + ((tid & 255) >> 4);
  uint4 wm[4];
  uint32_t cw, xw;
  if (tid < 256 && isA) {
    const bf16* wa = w_mod + (size_t)arow * 3072 + (lane & 8) * 64 + 64 * cl + 8 * (lane & 7);
#pragma unroll
    for (int i = 0; i < 4; i++) wm[i] = ldx16(wa + i * 16 * 3072);
    cw = ldc4(cvec + (arow & ~1) + 16 * tq);
    if (tid < 64) xw = ldc4(x + 64 * cl + (tid & 62));
  }
  unsigned gt_start;
  asm volatile("mov.u32 %0, %%globaltimer_lo;" : "=r"(gt_start));
  const int warp = __shfl_sync(~0u, tid >> 5, 0);
  if (warp == 11) {
    if (lane == 0) {
#pragma unroll
      for (int i = 0; i < B_EMPTY; i++) BAR_INIT(i, 1);
    }
    __syncwarp();
    asm volatile("fence.mbarrier_init.release.cluster;" ::: "memory");
    asm volatile("barrier.cluster.arrive.relaxed.aligned;" ::: "memory");
    if (isA) {
#pragma unroll 1
      for (int i = 0; i < 8; i++) {
        if (i >= 6) mbar_wait(bar0 + 8 * (i - 6));
        wait_until(gt_start + ((64 * i + b) * sch.dth >> 8));
        if (lane == 0) {
          BAR_ARM(i, 16384);
          tma3d(sb + i * 16384, &tms.m[i >> 2], bar0 + 8 * i, 0, i < 4 ? 128 * i : 256 * rk + 64 * (i - 4), i < 4 ? b : b & ~1);
        }
        __syncwarp();
      }
    }
  }
  if (warp == 10) {
    const unsigned ep = ldc4(&scr->cnt[0]);
    if (isA) {
      const uint4 xa = ldc16(x + 16 * lane), xb = ldc16(x + 16 * lane + 8);
      float xv[16] = {bflo(xa.x), bfhi(xa.x), bflo(xa.y), bfhi(xa.y), bflo(xa.z), bfhi(xa.z), bflo(xa.w), bfhi(xa.w),
                      bflo(xb.x), bfhi(xb.x), bflo(xb.y), bfhi(xb.y), bflo(xb.z), bfhi(xb.z), bflo(xb.w), bfhi(xb.w)};
      const float x0 = __shfl_sync(~0u, xv[0], 0);
      float s = 0, q = 0;
#pragma unroll
      for (int i = 0; i < 16; i++) { xv[i] -= x0; s += xv[i]; q += xv[i] * xv[i]; }
#pragma unroll
      for (int o = 16; o; o >>= 1) { s += __shfl_xor_sync(~0u, s, o); q += __shfl_xor_sync(~0u, q, o); }
      s *= 1.f / 512.f;
      float rstd;
      asm("rsqrt.approx.ftz.f32 %0, %1;" : "=f"(rstd) : "f"(fmaxf(q * (1.f / 512.f) - s * s, 0.f) + 1e-5f));
      *(float2*)(smem + O_SM + 1024) = make_float2(s + x0, rstd);
    }
    if (lane == 0) *(volatile unsigned*)(smem + O_EP) = ep;
    nbar_arrive(1, 288);
  }
  const int cls = isA ? (b >= NBIG) : 2, v0 = isA ? 2 : 0;
  if (warp >= 8) {
    asm volatile("setmaxnreg.dec.sync.aligned.u32 56;");
    if (warp == 8) {
      if (lane < 8) asm volatile("prefetch.tensormap [%0];" ::"l"(&tms.m[lane + 1]) : "memory");
      if ((sb & 0xFFFFFF) != SMEM_BASE) __trap();
    } else if (warp == 9) {
      if (lane == 0) {
#pragma unroll
        for (int i = B_EMPTY; i < B_LZ; i++) BAR_INIT(i, 8);
        BAR_INIT(B_LZ, 8); BAR_INIT(B_Q2, 9); BAR_ARM(B_Q2, 1024);
        BAR_INIT(B_H, 1); BAR_INIT(B_QF, 1); BAR_ARM(B_QF, 32768);
        BAR_INIT(B_TAB, 1); BAR_INIT(B_W, 1); BAR_INIT(B_ST, 8); BAR_INIT(B_WZ, 1); BAR_INIT(B_HZ, 1); BAR_ARM(B_HZ, isA ? 1024 : 512); BAR_INIT(B_G, 1); BAR_INIT(B_G2, 1);
      }

    }
    if (warp != 11) {
      __syncwarp();
      asm volatile("fence.mbarrier_init.release.cluster;" ::: "memory");
      __threadfence_block();
      asm volatile("barrier.cluster.arrive.relaxed.aligned;" ::: "memory");
    }
    asm volatile("barrier.cluster.wait.acquire.aligned;" ::: "memory");
    if (warp == 8) {
      const int nr = sch.nr[cls], vl = v0 + sch.nt[cls] - 1;
      unsigned long long hist = 0;
      int v = v0;
#pragma unroll 1
      for (int rd = 0; rd < nr; rd++) {
        const uint2 e = sch.r[cls][rd];
        const int type = e.y & 15, win = (e.y >> 4) & 15, pos = b + 64 - (int)((e.y >> 8) & 255), tile = e.y >> 16;
        const bool mod = type == T_MOD;
        const int ni = mod ? 1 : type == T_DN ? 2 : 4;
        unsigned t = gt_start + (e.x & 0xffff) + (pos * sch.dt >> 8);
        const int c0 = mod ? 1024 + 32 * b : type == T_WO || type == T_DN ? 64 * rn : type == T_GU ? 32 * f : 0;
        int c1 = type == T_KV ? 64 * (tile + pos) : 0;
        int c2 = mod ? tile : type == T_WO ? 4 * cl : type == T_DN ? 2 * cl - 16 : type == T_UV ? b : 0;
        const int i1 = type == T_UV ? 128 : 0;
#pragma unroll 1
        for (int j = 0; j < ni; j++) {
          const int slot = mod ? B_FM + tile : (v & 1) * 4 + j;
          if (mod ? tile : v >= 2) mbar_wait(bar0 + 8 * (B_EMPTY + (mod ? (vl & 1) * 4 : slot)), mod ? (vl >> 1) & 1 : ((v >> 1) - 1) & 1);
          const int hw = (int)(hist >> (6 * (win - 1))) & 63;
          if (hw) mbar_wait(bar0 + 8 * (hw & 15), (hw >> 4) & 1);
          wait_until(t);
          if (lane == 0) {
            BAR_ARM(slot, 16384);
            tma3d(sb + (mod ? (tile ? O_Q : O_X) : slot * 16384), &tms.m[type == T_GU ? type + (j & 1) : type], bar0 + 8 * slot, c0, c1, c2);
          }
          __syncwarp();
          hist = hist << 6 | (32 | (mod ? 0 : (v & 2) << 3) | slot);
          t += e.x >> 16; c1 += i1;
          c2 += type == T_KV ? 2 : type == T_WO || type == T_DN ? 1 : type == T_GU ? j & 1 : 0;
        }
        v += !mod;
      }
      return;
    }
    const unsigned epoch = *(volatile unsigned*)(smem + O_EP), par = (epoch + 1) & 1;
    if (warp == 10) {
      if (isA) {
        for (int it = 0; ldx4(scr->cnt + 1) != (epoch + 1) * 128 && it < SPIN_MAX; it++) {}
        if (lane == 0) BAR_ARRIVE(B_H);
      } else mbar_wait(bar0);
      if (!(rn & (QN - 1))) {
        for (int it = 0; ldx4(scr->cnt + 32 + 32 * (rn >> 2)) != (epoch + 1) * 32 && it < SPIN_MAX; it++) {}
        if (lane == 0)
          asm volatile("cp.async.bulk.shared::cluster.global.mbarrier::complete_tx::bytes.multicast::cluster [%0], [%1], %4, [%2], %3;"
                       ::"r"(sb + O_Q + rn * 4096), "l"(scr->qa + rn * 256), "r"(bar0 + 8 * B_QF), "h"((unsigned short)0xff), "n"(4096 * QN) : "memory");
      }
      const unsigned dl = isA ? sch.d4 : sch.d6;
      unsigned tw = gt_start + sch.t4;
      if (!isA) {
        const int nt = sch.nt[2];
#pragma unroll 1
        for (int t = 0; t < nt; t++) mbar_wait(bar0 + 8 * B_EMPTY + (t & 1) * 32, (t >> 1) & 1);
        unsigned long long now;
        asm volatile("mov.u64 %0, %%globaltimer;" : "=l"(now));
        LANE0("red.relaxed.gpu.global.max.u64", scr->cnt + 130, "l", now);
        CNT_ADD(128);
        tw = (unsigned)now + 1700;
      }
      sleep_until(tw);
      uint4 an;
      for (int it = 0; an = ldx16(scr->cnt + 128), an.x != (epoch + 1) * 56 && it < SPIN_MAX; it++) {}
      wait_until(an.z + (dl >> 16));
      if (lane == 0) BAR_ARRIVE(B_G2);
      wait_until(an.z + (dl & 0xffff));
      if (lane == 0) BAR_ARRIVE(B_G);
    } else if (warp == 11) {
      {
        uint2* ph = scr->hdr + ((lane & 24) + 2 * tq + (g & 1)) * 16 + cl;
        const bool own = (lane >> 4) * 4 + tq == rn;
        if (own) { stx8(ph, make_uint2(par ^ 1, 0)); if (cl == 14) stx8(ph + 1, make_uint2(0, 0)); }
        uint32_t a_w = sb + O_HW + ((lane >> 4) * 4 + tq) * 128 + (g & 1) * 64 + ((lane >> 1) & 4);
        PIN(a_w); PINL(ph);
        const int vt = v0 + sch.nt[cls];
#pragma unroll 1
        for (int t = 0; t < vt; t++) mbar_wait(bar0 + 8 * B_EMPTY + (t & 1) * 32, (t >> 1) & 1);
        float hz[8], M;
        uint32_t wp[4];
#pragma unroll 1
        for (int e = 0; e < 2; e++) {
          POLL {
            unsigned ok = 1;
#pragma unroll
            for (int u = 0; u < 8; u++)
              asm volatile("ld.relaxed.cluster.shared.f32 %0, [%1];" : "=f"(hz[u]) : "r"(sb + O_HZ + e * 1024 + u * 128 + lane * 4) : "memory");
#pragma unroll
            for (int u = 0; u < 4; u++) ok = and3(ok, __float_as_uint(hz[u]), __float_as_uint(hz[u + 4]));
            RETRY(~ok)
          }
          if (e) break;
          M = fmaxf(fmaxf(fmaxf(hz[0], hz[1]), fmaxf(hz[2], hz[3])), fmaxf(fmaxf(hz[4], hz[5]), fmaxf(hz[6], hz[7])));
          M = u2f(fbits(M));
#pragma unroll
          for (int u = 0; u < 4; u++) {
            wp[u] = pack2(ex2(hz[u] - M), ex2(hz[u + 4] - M));
            sts4(a_w + ((rn - u) & 3) * 8, u2f(wp[u])); sts4(a_w + ((rn - u) & 3) * 8 + 32, u2f(wp[u]));
          }
          __syncwarp();
          if (lane == 0) BAR_ARRIVE(B_WZ);
        }
        float L = 0.f;
#pragma unroll
        for (int u = 0; u < 4; u++) L += bflo(wp[u]) * hz[u] + bfhi(wp[u]) * hz[u + 4];
        if (own) pub8(ph, __float_as_uint(M) | 1u, __float_as_uint(L));
      }
      if (isA) {
        mbar_wait(bar0 + 8 * B_G2);
        unsigned long long hh;
        POLL { hh = ldx64(scr->hdr + hd * 16 + (lane & 15)); RETRY((lane & 15) == 15 ? 0u : (unsigned)hh ^ par) }
        const float m = (lane & 15) == 15 ? -1e30f : u2f((unsigned)hh);
        int mi = __float_as_int(m);
        mi ^= (mi >> 31) & 0x7fffffff;
        mi = __reduce_max_sync(~0u, mi);
        mi ^= (mi >> 31) & 0x7fffffff;
        const float w = ex2(m - __int_as_float(mi));
        float L = w * u2f(hh >> 32);
#pragma unroll
        for (int o2 = 8; o2; o2 >>= 1) L += __shfl_xor_sync(~0u, L, o2);
        sts4(sb + O_SM + (384 + 2 * (lane & 6) + ((lane >> 2) & 2) + (lane & 1)) * 4, w * rcp(L));
        __syncwarp();
        if (lane == 0) BAR_ARRIVE(B_W);
      }
    } else {
#pragma unroll 4
      for (int i = 0; i < 72; i++) sts16(sb + O_LZ + i * 512 + lane * 16, make_uint4(0, 0, 0, 0));
      __syncwarp();
      if (lane < 8) asm volatile("mbarrier.arrive.release.cluster.shared::cluster.b64 _, [%0];" ::"r"(mapa(bar0 + 8 * B_LZ, lane)) : "memory");
      if (isA) {
        mbar_wait(bar0 + 8 * B_QF);
#pragma unroll 2
        for (int k = 0; k < 8; k++) {
          const uint32_t cp = ldc4(cvec + 2 * (lane + 32 * k));
          *(uint32_t*)(smem + O_SILU + (lane + 32 * k) * 4) = pack2(silu_bf(bflo(cp)), silu_bf(bfhi(cp)));
        }
        __syncwarp();
        uint32_t ab = sb + O_X + (8 * (lane >> 4) + (lane & 7)) * 64 + ((((lane >> 3) & 1) ^ ((lane >> 1) & 3)) << 4);
        float d[4][4] = {};
#pragma unroll 1
        for (int jm = 0; jm < 2; jm++) {
          mbar_wait(bar0 + 8 * (B_FM + jm));
#pragma unroll 2
          for (int s2 = 0; s2 < 8; s2++)
#pragma unroll
            for (int s = 0; s < 2; s++) {
              uint32_t a0[4], a1[4];
              const uint32_t* ps = (const uint32_t*)(smem + O_SILU) + 128 * jm + 16 * s2 + 8 * s + tq;
              ldsm_t(a0, ab + (2 * s2 + s) * 1024); ldsm_t(a1, (ab + (2 * s2 + s) * 1024) ^ 32);
              mma16(d[s], a0, ps[0], ps[4]); mma16(d[2 + s], a1, ps[0], ps[4]);
            }
          ab -= O_X - O_Q;
        }
        const float t0 = (tq & 1) ? d[0][2] + d[1][2] : d[0][0] + d[1][0], t1 = (tq & 1) ? d[2][2] + d[3][2] : d[2][0] + d[3][0];
        stx4(scr->xm + b * 32 + posof(8 * tq + g), fbits(bfr(bfr((tq & 2) ? t1 : t0) + ((b >> 4) == 2 ? 1.f : 0.f))));
        __syncwarp();
        CNT_ADD(96);
      } else sleep_until(gt_start + sch.t4);
      for (int it = 0; ldx4(scr->cnt + 96) != (epoch + 1) * 64 && it < SPIN_MAX; it++) __nanosleep(NSL);
      if (isA) {
        unsigned long long ga;
        POLL { ga = ldx64(scr->xm + 64 * rn + 2 * lane); RETRY(lop_x3((unsigned)ga, ga >> 32, par)) }
        *(float2*)(smem + O_SM + (320 + 2 * lane) * 4) = make_float2(bfhi((unsigned)ga), bfhi(ga >> 32));
      }
      __syncwarp();
      if (lane == 0) BAR_ARRIVE(B_TAB);
    }
    return;
  }

  float* s_sm = (float*)(smem + O_SM);
  unsigned par, epoch;
  asm volatile("barrier.cluster.arrive.relaxed.aligned;" ::: "memory");
  if (isA) {
    float* s_r = (float*)(smem + O_R);
    float acc[8] = {0, 0, 0, 0, 0, 0, 0, 0};
    const float sl = silu_bf((arow & 1) ? bfhi(cw) : bflo(cw));
#pragma unroll
    for (int i = 0; i < 4; i++) fma8(acc, wm[i], __shfl_sync(~0u, sl, i, 4));
    tred<4>(acc, lane, 16);
    *(float4*)(s_r + warp * 128 + 8 * (lane & 15) + ((lane >> 2) & 4)) = make_float4(acc[0], acc[1], acc[2], acc[3]);
    nbar(1, 288);
    epoch = *(volatile unsigned*)(smem + O_EP);
    par = (epoch + 1) & 1;
    if (warp < 2) {
      float t = 0.f, ca = rn == 0 ? 1.f : 0.f;
#pragma unroll
      for (int w = 0; w < 8; w++) { t += s_r[w * 128 + tid]; ca += s_r[w * 128 + 64 + tid]; }
      t += ca * ((((tid & 1) ? bfhi(xw) : bflo(xw)) - s_sm[256]) * s_sm[257]);
      const float nb = __shfl_down_sync(~0u, t, 1);
      const uint32_t w0 = lane < 8 ? pack2t(t, nb, par) : pack2(t, nb);
      const uint32_t w1 = __shfl_down_sync(~0u, w0, 8), w2 = __shfl_down_sync(~0u, w0, 16), w3 = __shfl_down_sync(~0u, w0, 24);
      if (lane < 8 && !(lane & 1)) stx16(scr->h + (rn >> 1) * 512 + (2 * cl + warp) * 32 + rk * 16 + 2 * lane, make_uint4(w0, w1, w2, w3));
      __syncwarp();
      CNT_ADD(1);
    }
    asm volatile("barrier.cluster.wait.acquire.aligned;" ::: "memory");
    const uint32_t rsb = mapa(sb, rn ^ 1);
    {
      uint32_t a[4][4][4];
      mbar_wait(bar0 + 8 * (warp >> 1));
      const uint32_t ab = sb + (64 * warp + 8 * (lane >> 4) + (lane & 7)) * 128;
#pragma unroll
      for (int s = 0; s < 4; s++)
#pragma unroll
        for (int mt = 0; mt < 4; mt++) ldsm_t(a[s][mt], ab + s * 2048 + (((2 * mt + ((lane >> 3) & 1)) ^ (lane & 7)) << 4));
      arrive_n(bar0 + 8 * (B_EMPTY + (warp >> 1)), lane == 0, 4 + (dep16(&a[0][0][0]) & sch.zero));
      uint4 v0, v1;
      const unsigned* ph = scr->h + (g >> 1) * 512 + 64 * warp + 4 * (lane & 7);
      uint32_t off = O_B + warp * 272 + (32 * rk + 8 * tq + (lane & 4)) * 4;
      PIN(off); PINL(ph);
      mbar_wait(bar0 + 8 * B_H);
      POLL { v0 = ldx16(ph); v1 = ldx16(ph + 32); RETRY(lop_x3(v0.x, v1.x, par)) }
      float d[4][4] = {};
#pragma unroll
      for (int mt = 0; mt < 4; mt++) {
        mma16(d[mt], a[0][mt], v0.x, v0.y); mma16(d[mt], a[1][mt], v0.z, v0.w);
        mma16(d[mt], a[2][mt], v1.x, v1.y); mma16(d[mt], a[3][mt], v1.z, v1.w);
      }
      float r[8];
#pragma unroll
      for (int mt = 0; mt < 4; mt++) { r[2 * mt] = d[mt][0] + d[mt][1]; r[2 * mt + 1] = d[mt][2] + d[mt][3]; }
      tred<4>(r, lane, 2); tred<2>(r, lane, 1);
      const float rc = __shfl_xor_sync(~0u, (lane & 4) ? r[0] : r[1], 4);
      const uint32_t wd = (lane & 4) ? pack2(rc, r[1]) : pack2(r[0], rc);
      const uint32_t w1 = __shfl_down_sync(~0u, wd, 8), w2 = __shfl_down_sync(~0u, wd, 16), w3 = __shfl_down_sync(~0u, wd, 24);
      asm volatile("{.reg .pred p; setp.lt.s32 p, %7, 8; @p st.shared.v4.b32 [%0], {%2,%3,%4,%5};\n"
                   "@p st.async.shared::cluster.mbarrier::complete_tx::bytes.v4.b32 [%1], {%2,%3,%4,%5}, [%6];}"
                   ::"r"(sb + off), "r"(rsb + off), "r"(wd), "r"(w1), "r"(w2), "r"(w3), "r"(rsb + O_BAR + 8 * B_Q2), "r"(lane) : "memory");
      __syncwarp();
      arrive_n(bar0 + 8 * B_Q2, lane == 0, 1);
    }
    {
      uint32_t a[2][8][4];
      uint32_t a_bq = sb + O_B + (lane & 7) * 272 + (lane >> 3) * 16;
      uint4* p_qa = scr->qa + (4 * rk + (warp >> 1)) * 256 + hd * 8 + ((4 * (warp & 1) + tq) ^ (hd & 7));
      PIN(a_bq); PINL(p_qa);
      mbar_wait(bar0 + 8 * (4 + (warp >> 1)));
      const uint32_t ab = sb + 65536 + (warp >> 1) * 16384 + (32 * (warp & 1) + (lane & 15)) * 128;
#pragma unroll
      for (int i = 0; i < 16; i++) ldsm(a[i >> 3][i & 7], ab + (i >> 3) * 2048 + ((i >> 2) & 1) * 8192 + (((2 * (i & 3) + (lane >> 4)) ^ (lane & 7)) << 4));
      arrive_n(bar0 + 8 * (B_EMPTY + 4 + (warp >> 1)), lane == 0, 4 + (dep16(&a[0][0][0]) & sch.zero));
      mbar_wait(bar0 + 8 * B_Q2);
      float d[4][4] = {};
#pragma unroll
      for (int y = 0; y < 4; y++) {
        uint32_t bq[4];
        ldsm(bq, a_bq + 64 * y);
#pragma unroll
        for (int mt = 0; mt < 2; mt++) { mma16(d[2 * mt], a[mt][2 * y], bq[0], bq[1]); mma16(d[2 * mt + 1], a[mt][2 * y + 1], bq[2], bq[3]); }
      }
      float r[4];
#pragma unroll
      for (int i = 0; i < 4; i++) r[i] = (d[i & 2][2 * (i & 1)] + d[i & 2][2 * (i & 1) + 1]) + (d[(i & 2) + 1][2 * (i & 1)] + d[(i & 2) + 1][2 * (i & 1) + 1]);
      tred<2>(r, lane, 2); tred<1>(r, lane, 1);
      const float nb = __shfl_xor_sync(~0u, r[0], 4);
      const uint32_t w0 = (lane >> 3) == (hd & 3) ? pack2t(r[0], nb, par) : pack2(r[0], nb);
      const uint32_t w1 = __shfl_down_sync(~0u, w0, 8), w2 = __shfl_down_sync(~0u, w0, 16), w3 = __shfl_down_sync(~0u, w0, 24);
      if (lane < 4) stx16(p_qa, make_uint4(w0, w1, w2, w3));
      if (warp) nbar_arrive(3, 256); else { nbar(3, 256); CNT_ADD(32 + 32 * rk); }
    }
  } else {
    nbar(1, 288);
    epoch = *(volatile unsigned*)(smem + O_EP);
    par = (epoch + 1) & 1;
    asm volatile("barrier.cluster.wait.acquire.aligned;" ::: "memory");
    mbar_wait(bar0);
  }
  asm volatile("setmaxnreg.inc.sync.aligned.u32 224;");
  uint2* p_rec = scr->rec + ((16 * (warp >> 2) + 2 * (warp & 3) + (g & 1) + 4 * (tq & 2)) * 32 + 4 * rn + (tq & 1)) * 64 + cl * 4 + (g >> 1);
  PINL(p_rec);
  {
    const unsigned inv = par ^ 1;
#pragma unroll
    for (int q = 0; q < 2; q++) { stx8(p_rec + q * 128, make_uint2(inv, 0)); if (cl == 14) stx8(p_rec + q * 128 + 4, make_uint2(0, 0)); }
    if (isA) { if (warp < 2) { stx4(scr->xao + b * 64 + tid, inv); stx4(scr->xab + cl * 256 + (2 * (rn & 3) + warp) * 32 + (rn >> 2) * 16 + (lane >> 1), inv); } }
    else if (f == 0) { stx4(out + 2 * tid, 0); __threadfence(); }
  }
  sb = __shfl_sync(~0u, sb, 0); bar0 = sb + O_BAR;
  const int nt = sch.nt[cls], wg = warp >> 2;
  uint32_t a_z[4];
#pragma unroll
  for (int u = 0; u < 4; u++) {
    const int s3 = (rn - u - (lane >> 1 & 1)) & 3;
    a_z[u] = sb + O_LZ + (s3 + 4 * (lane & 1)) * 4096 + wg * 512 + g * 64 + (((warp & 3) ^ (s3 & 1) ^ (2 * (lane & 1))) << 4);
    PIN(a_z[u]);
  }
  uint32_t z[4][4], a_w = sb + O_HW + warp * 128 + (g & 1) * 64 + (tq & 1) * 8;
  PIN(a_w);
  {
    const float sc = 0.08838834764831845f * 1.4426950408889634f;
    float mrun = -1e30f;
    float o[4][16], sx[16], mref[8];
#pragma unroll
    for (int k = 0; k < 16; k++) { o[0][k] = o[1][k] = o[2][k] = o[3][k] = sx[k] = 0.f; mref[k >> 1] = -1e30f; }
    const int key = 16 * warp + (lane & 15);
    uint32_t a_p = sb + O_P + key * 64 + (((lane >> 4) ^ ((key >> 1) & 3)) << 4);
    uint32_t a_v = sb + wg * 32768 + (8 * (lane >> 4) + (lane & 7)) * 128 + (((2 * (warp & 3) + ((lane >> 3) & 1)) ^ (lane & 7)) << 4);
    const int rot = rn + warp;
    const int qown = wg == (rn >> 2) ? -warp & 3 : -1;
    uint32_t a_own = sb + O_LZ + rn * 4096 + (warp & 3) * 1024 + g * 64 + ((tq ^ (rn & 1) ^ ((rn >> 1) & 2)) << 4);
    PIN(a_own);
    unsigned long long dst[4];
#pragma unroll
    for (int q = 0; q < 4; q++) {
      dst[q] = mapg(a_own, 4 * wg + ((q + rot) & 3));
      PINL(dst[q]);
    }
    unsigned long long a_h = mapg(sb + O_HZ + wg * 1024 + rn * 128 + lane * 4, 2 * (warp & 3));
    unsigned long long a_h1 = mapg(sb + O_HZ + wg * 1024 + rn * 128 + lane * 4, 2 * (warp & 3) + 1);
    PIN(a_p); PIN(a_v); PINL(a_h); PINL(a_h1);
    uint32_t rel = lane < 4 && lane >= 2 * wg ? 2 - (tq >> 1) : 0;
    PIN(rel);
    uint32_t ones[4] = {0x3F803F80u, 0x3F803F80u, 0x3F803F80u, 0x3F803F80u};
    PIN(ones[0]); PIN(ones[1]); PIN(ones[2]); PIN(ones[3]);
    {
      asm volatile("{.reg .pred p; .reg .u32 n; mov.u32 n, 0;\n"
                   "W%=: mbarrier.try_wait.parity.acquire.cluster.shared::cta.b64 p, [%0], 0; add.u32 n, n, 1; setp.lt.and.u32 p, n, 0x100000, !p; @p bra W%=;}"
                   ::"r"(bar0 + 8 * B_LZ) : "memory");
      mbar_wait(bar0 + 8 * B_QF);
      unsigned bad = 0;
#pragma unroll
      for (int k = 0; k < 8; k++) bad |= __float_as_uint(lds4(sb + O_Q + k * 4096 + tid * 16 + (lane >> 3) * 4)) ^ par;
      if (__builtin_expect(__any_sync(~0u, bad & 1), 0)) {
#pragma unroll 1
        for (int k = 0; k < 8; k++) {
          uint4 v;
          POLL { v = ldx16(scr->qa + k * 256 + tid); RETRY(((lane & 16) ? ((lane & 8) ? v.w : v.z) : ((lane & 8) ? v.y : v.x)) ^ par) }
          sts16(sb + O_Q + k * 4096 + tid * 16, v);
        }
        asm volatile("fence.proxy.async.shared::cta;" ::: "memory");
      }
      if (warp >= 4) nbar_arrive(1, 256); else nbar(1, 256);
    }
#pragma unroll 1
    for (int t = 0; t < nt; t++) {
      const int v = v0 + t;
      const uint32_t fb = bar0 + (v & 1) * 32, ph = (v >> 1) & 1, av = a_v + (v & 1) * 65536;
      uint32_t vf[4][4][4], cnt;
      auto landed = [&]() {
        cnt = rel + (dep16(&vf[0][0][0]) & (nt >> 8));
        PIN(cnt);
      };
      if (wg == 0) {
        const uint32_t da = DSC + (v & 1) * 4096, db = DSC + O_Q / 16;
#pragma unroll 1
        for (int j = 0; j < 4; j++) {
          mbar_wait(fb + 8 * j, ph);
          asm volatile("wgmma.fence.sync.aligned;" ::: "memory");
#pragma unroll
          for (int k = 0; k < 8; k++)
            wgmma32<0, 0, HI128, HI128>(sx, da + j * 1024 + (k >> 2) * 512 + (k & 3) * 2, db + j * 512 + (k >> 2) * 256 + (k & 3) * 2, k ? 1 : j);
          asm volatile("wgmma.commit_group.sync.aligned;" ::: "memory");
          if (j == VJ) {
#pragma unroll
            for (int i = 0; i < 16; i++) ldsm_t(vf[i >> 2][i & 3], av + (((i >> 2) + rot) & 3) * 8192 + (i & 3) * 2048);
            nbar(5, 256);
            landed();
          }
        }
      } else {
        nbar_arrive(5, 256);
#pragma unroll 1
        for (int j = 0; j < 2; j++) {
          mbar_wait(fb + 16 + 8 * j, ph);
#pragma unroll
          for (int q = 0; q < 4; q++)
            if (((q + rot) & 2) == 2 * j)
#pragma unroll
              for (int k = 0; k < 4; k++) ldsm_t(vf[q][k], av + ((q + rot) & 3) * 8192 + k * 2048);
        }
        cnt = 0;
      }
      auto scores = [&]() {
        wg_wait<0>(sx);
        asm volatile("{.reg .pred p; setp.ne.s32 p, %1, 0; @p mbarrier.arrive.shared::cta.b64 _, [%0], %1;}" ::"r"(fb + 8 * B_EMPTY + 8 * tq), "r"(cnt) : "memory");
        cnt = 0;
      };
      int ex = t == 0;
#pragma unroll 1
      for (int pass = 0;; pass++) {
        if (ex) {
          scores();
          int ln;
          asm volatile("mov.u32 %0, %%laneid;" : "=r"(ln));
          const uint32_t a_pm = sb + O_SM + ln * 16;
          if (wg == 0) {
            float cm[8];
#pragma unroll
            for (int i = 0; i < 8; i++) cm[i] = fmaxf(sx[2 * (i & 6) + (i & 1)], sx[2 * (i & 6) + (i & 1) + 2]);
            tmax<4>(cm, lane, 16); tmax<2>(cm, lane, 8); tmax<1>(cm, lane, 4);
            sts4(a_pm + warp * 4, cm[0] * sc);
          }
          nbar(4, 256);
          const float4 pm = lds16(a_pm);
          const float mn = u2f(__float_as_uint(fmaxf(fmaxf(fmaxf(pm.x, pm.y), fmaxf(pm.z, pm.w)), mrun)) | 1u), al = ex2(mrun - mn);
          mrun = mn;
#pragma unroll
          for (int i = 0; i < 8; i++) {
            const float a = __shfl_sync(~0u, al, 4 * i + (ln & 3)), aw = wg ? a : 1.f;
            mref[i] = __shfl_sync(~0u, mn, 4 * i + (ln & 3));
#pragma unroll
            for (int e = 0; e < 2; e++) {
              const int k = 2 * (i & 6) + (i & 1) + 2 * e;
              o[0][k] *= a; o[1][k] *= a; o[2][k] *= a; o[3][k] *= a; sx[k] *= aw;
            }
          }
          pass = 1;
        }
        scores();
        ex = 0;
        if (wg == 0) {
          uint32_t pk[8];
#pragma unroll
          for (int i = 0; i < 8; i++) pk[i] = pack2(ex2(sx[2 * i] * sc - mref[i & 6]), ex2(sx[2 * i + 1] * sc - mref[(i & 6) + 1]));
          asm volatile("stmatrix.sync.aligned.m8n8.x4.shared.b16 [%0], {%2,%3,%4,%5};\n"
                       "stmatrix.sync.aligned.m8n8.x4.shared.b16 [%1], {%6,%7,%8,%9};"
                       ::"r"(a_p), "r"(a_p ^ 32), "r"(pk[0]), "r"(pk[1]), "r"(pk[2]), "r"(pk[3]), "r"(pk[4]), "r"(pk[5]), "r"(pk[6]), "r"(pk[7]) : "memory");
          const uint32_t mx = __vmaxu2(__vmaxu2(__vmaxu2(pk[0], pk[1]), __vmaxu2(pk[2], pk[3])), __vmaxu2(__vmaxu2(pk[4], pk[5]), __vmaxu2(pk[6], pk[7])));
          ex = max(mx, mx << 16) > (127u + TAU) << 23;
          asm volatile("fence.proxy.async.shared::cta;" ::: "memory");
        }
        asm volatile("{.reg .pred p, q; setp.ne.s32 q, %0, 0; bar.red.or.pred p, 4, 256, q; selp.s32 %0, 1, 0, p;}" : "+r"(ex)::"memory");
        if (!ex || pass) break;
      }
      auto head = [&](float hv, int off) {
        asm volatile("{.reg .pred p; setp.eq.s32 p, %3, 0; @p st.relaxed.cluster.b32 [%0], %1; @p st.relaxed.cluster.b32 [%2], %1;}"
                     ::"l"(a_h), "r"(__float_as_uint(hv) | 1u), "l"(a_h1), "r"(off | (t ^ (nt - 1))) : "memory");
      };
      auto sums = [&]() {
        asm volatile("wgmma.fence.sync.aligned;" ::: "memory");
#pragma unroll
        for (int k = 0; k < 4; k++) wgmma32r(sx, ones, DSC + O_P / 16 + k * 64);
        asm volatile("wgmma.commit_group.sync.aligned;" ::: "memory");
        cnt = rel + (dep12(&vf[1][0][0]) & (nt >> 8));
        scores();
        float lv[4];
#pragma unroll
        for (int j = 0; j < 4; j++) lv[j] = (lane & 4) ? sx[4 * j + 1] : sx[4 * j];
        return (lane & 16) ? ((lane & 8) ? lv[3] : lv[2]) : ((lane & 8) ? lv[1] : lv[0]);
      };
      if (wg) spin_until(clock() + LDLY);
#pragma unroll
      for (int q = 0; q < 4; q++) {
        if (q < 2) {
          asm volatile("wgmma.fence.sync.aligned;" ::: "memory");
#pragma unroll
          for (int u = q; u < (q ? 4 : 1); u++) {
#pragma unroll
            for (int k = 0; k < 4; k++) wgmma32r(o[u], vf[u][k], DSC + O_P / 16 + k * 64);
            asm volatile("wgmma.commit_group.sync.aligned;" ::: "memory");
          }
        }
        if (q == 0) head(mrun, wg);
        if (q == 3) {
#pragma unroll
          for (int u = 0; u < 4; u++)
            asm volatile("{.reg .pred p; setp.eq.s32 p, %5, %6; @p ldmatrix.sync.aligned.m8n8.x4.trans.shared.b16 {%0,%1,%2,%3}, [%4];}"
                         : "=r"(z[u][0]), "=r"(z[u][1]), "=r"(z[u][2]), "=r"(z[u][3]) : "r"(a_z[u] + u * 1024), "r"(t), "r"(nt - 1) : "memory");
        }
        if (q == 1) wg_wait<2>(o[q]); else if (q == 2) wg_wait<1>(o[q]); else wg_wait<0>(o[q]);
        if (q == 0 || t == nt - 1)
#pragma unroll
        for (int j = 0; j < 2; j++)
          asm volatile("{.reg .pred p, q, r; setp.eq.s32 p, %5, %6; setp.eq.and.s32 q|r, %7, %8, p; @r st.relaxed.cluster.v4.b32 [%0], {%1,%2,%3,%4};\n"
                       "@q st.shared.v4.b32 [%9], {%1,%2,%3,%4};}"
                       ::"l"(dst[q] + j * 512), "r"(pack2t(o[q][8 * j], o[q][8 * j + 1], 1)), "r"(pack2(o[q][8 * j + 2], o[q][8 * j + 3])),
                         "r"(pack2(o[q][8 * j + 4], o[q][8 * j + 5])), "r"(pack2(o[q][8 * j + 6], o[q][8 * j + 7])), "r"(t), "r"(nt - 1),
                         "r"(qown), "r"(q), "r"(a_own + j * 512) : "memory");
        if (q == 0 && wg) head(sums(), 0);
      }
    }
  }
  {
    uint32_t wx[4][4];
    mbar_wait(bar0 + 8 * B_WZ);
#pragma unroll
    for (int u = 0; u < 4; u++) {
      uint2 wp;
      asm volatile("ld.shared.v2.u32 {%0, %1}, [%2];" : "=r"(wp.x), "=r"(wp.y) : "r"(a_w + u * 8) : "memory");
      const bool lo = (g >> 1) == (tq >> 1), hi = (g >> 1) == 2 + (tq >> 1);
      wx[u][0] = lo ? wp.x : 0u; wx[u][1] = lo ? wp.y : 0u; wx[u][2] = hi ? wp.x : 0u; wx[u][3] = hi ? wp.y : 0u;
    }
    auto bad = [&]() {
      const unsigned ok = and3(and3(and3(z[0][0], z[0][1], z[0][2]), and3(z[0][3], z[1][0], z[1][1]), and3(z[1][2], z[1][3], z[2][0])),
                               and3(and3(z[2][1], z[2][2], z[2][3]), and3(z[3][0], z[3][1], z[3][2]), z[3][3]), 0x10001u);
      return __any_sync(~0u, g == 0 && ok != 0x10001u);
    };
    POLL {
      if (it_)
#pragma unroll
        for (int u = 0; u < 4; u++) ldsm_t(z[u], a_z[u] + u * 1024);
      if (!bad() || ++it_ >= SPIN_MAX) break;
    }
    float d0[8][4] = {}, d[8][4], r[8];
#pragma unroll
    for (int i = 0; i < 8; i++) mma16(d0[i], wx[i >> 1], z[i >> 1][2 * (i & 1)], z[i >> 1][2 * (i & 1) + 1]);
    POLL {
#pragma unroll
      for (int u = 0; u < 4; u++) ldsm_t(z[u], a_z[u ^ 2] + u * 1024);
#pragma unroll
      for (int i = 0; i < NSP; i++) mma16c(d[i], wx[(i >> 1) ^ 2], z[i >> 1][2 * (i & 1)], z[i >> 1][2 * (i & 1) + 1], d0[i]);
      if (!bad() || ++it_ >= SPIN_MAX) break;
    }
#pragma unroll
    for (int i = NSP; i < 8; i++) mma16c(d[i], wx[(i >> 1) ^ 2], z[i >> 1][2 * (i & 1)], z[i >> 1][2 * (i & 1) + 1], d0[i]);
#pragma unroll
    for (int i = 0; i < 8; i++) r[i] = (tq & 2) ? ((g & 1) ? d[i][3] : d[i][2]) : ((g & 1) ? d[i][1] : d[i][0]);
#pragma unroll
    for (int q = 0; q < 2; q++) pub8(p_rec + q * 128, pack2t(r[4 * q], r[4 * q + 1], par) | 1u, pack2(r[4 * q + 2], r[4 * q + 3]));
  }
  const int vt = v0 + nt;
  const uint32_t bufa = sb + (vt & 1) * 65536, fulla = bar0 + (vt & 1) * 32, pha = (vt >> 1) & 1, phb = ((vt + 1) >> 1) & 1;
  const uint32_t bufo = sb + ((vt + 1) & 1) * 65536, fullb = bar0 + ((vt + 1) & 1) * 32;
  uint32_t a_rs = sb + O_R + (warp >> 2) * 1024 + (16 * tq + g) * 16 + ((warp + tq) & 3) * 4;
  if (isA) {
    const int row = 16 * (warp & 6) + 8 * (warp & 1) + (lane & 16) + ((lane & 7) >> 1) + 4 * (lane & 1);
    uint32_t ab = bufa + row * 128 + ((((lane >> 3) & 1) ^ (row & 7)) << 4);
    const uint2* pr = scr->rec + (hd * 32 + warp) * 64 + lane;
    uint32_t a_cb = mapa(bar0 + 8 * B_HZ, (warp & 6) + (lane >> 4)), a_c = a_cb - (O_BAR + 8 * B_HZ - O_CTX) + (2 * rn + (warp & 1)) * 64 + tq * 16;
    uint32_t a_rl = sb + O_R + (32 * (warp & 1) + lane) * 16;
    uint32_t ao = bufo + (16 * warp + 8 * (lane >> 4) + (lane & 7)) * 128 + ((((lane >> 3) & 1) ^ (lane & 7)) << 4);
    uint32_t a_cx = sb + O_CTX + (warp >> 1) * 64 + tq * 16 + (warp & 1) * 8, a_ga = sb + O_SM + (320 + posof(tid & 63)) * 4;
    unsigned* p_ao = scr->xao + b * 64 + (tid & 63);
    unsigned* p_ab = scr->xab + cl * 256 + (2 * (rn & 3) + (warp & 1)) * 32 + (rn >> 2) * 16 + (lane >> 1);
    float xv = cl == 0 ? __bfloat162float(x[64 * rn + (tid & 63)]) : 0.f;
    unsigned p2 = lane >= 28 ? 0 : par;
    PIN(ab); PINL(pr); PIN(a_cb); PIN(a_c); PIN(a_rl); PIN(a_rs); PIN(ao); PIN(a_cx); PIN(a_ga); PINL(p_ao); PINL(p_ab); PIN(p2);
    asm volatile("" : "+f"(xv));
    uint32_t aw[4][4][4];
    auto wo = [&](const int j) {
      mbar_wait(fullb + 8 * j, phb);
#pragma unroll
      for (int mt = 0; mt < 4; mt++) ldsm_t(aw[j][mt], (ao + j * 16384) ^ (mt << 5));
    };
    {
      uint32_t a[4][4][4];
      uint2 z[4], y[4] = {};
      float d[4][4] = {}, r[8];
      mbar_wait(fulla, pha);
      POLL {
#pragma unroll
        for (int q = 0; q < 4; q++) z[q] = ldx8(pr + q * 512);
        RETRY(lop_x3(z[0].x, z[1].x, par) | lop_x3(z[2].x, z[3].x, par))
      }
#pragma unroll
      for (int q = 0; q < 4; q++) {
        if (q == 3) {
          mbar_wait(bar0 + 8 * B_G);
          if (lane < 28)
#pragma unroll
            for (int u = 0; u < 4; u++) y[u] = ldx8(pr + u * 512 + 32);
          __syncwarp();
        }
        mbar_wait(fulla + 8 * q, pha);
#pragma unroll
        for (int mt = 0; mt < 4; mt++) ldsm_t(a[q][mt], (ab + q * 16384) ^ (mt << 5));
#pragma unroll
        for (int mt = 0; mt < 4; mt++) mma16(d[mt], a[q][mt], z[q].x, z[q].y);
      }
      mbar_wait(bar0 + 8 * B_W);
      const float4 W = lds16(sb + O_SM + (384 + 4 * tq) * 4);
#pragma unroll
      for (int i = 0; i < 8; i++) { r[i] = W.x * d[i >> 1][2 * (i & 1)] + W.y * d[i >> 1][2 * (i & 1) + 1]; asm volatile("" : "+f"(r[i])); }
#pragma unroll
      for (int j = 0; j < NPE; j++) wo(j);
      POLL {
        if (it_)
#pragma unroll
          for (int u = 0; u < 4; u++) y[u] = ldx8(pr + u * 512 + 32);
#pragma unroll
        for (int mt = 0; mt < 4; mt++) d[mt][0] = d[mt][1] = d[mt][2] = d[mt][3] = 0.f;
#pragma unroll
        for (int q = 0; q < 4; q++)
#pragma unroll
          for (int mt = 0; mt < 4; mt++) mma16(d[mt], a[q][mt], y[q].x, y[q].y);
        RETRY(or3(lop_x3(y[0].x, y[1].x, p2), lop_x3(y[2].x, y[3].x, p2), 0))
      }
#pragma unroll
      for (int i = 0; i < 8; i++) r[i] = W.w * d[i >> 1][2 * (i & 1) + 1] + (W.z * d[i >> 1][2 * (i & 1)] + r[i]);
      tred<4>(r, lane, 2); tred<2>(r, lane, 1);
      sts4(a_rs, r[0]); sts4(a_rs + 128, r[1]);
      nbar(1, 256);
      send32(a_c, a_cb, sum8(a_rl), lane, lane & 12);
    }
    {
#pragma unroll
      for (int j = NPE; j < NPO; j++) wo(j);
      uint2 c[4];
      mbar_wait(bar0 + 8 * B_HZ);
#pragma unroll
      for (int j = 0; j < 4; j++) asm volatile("ld.shared.v2.u32 {%0, %1}, [%2];" : "=r"(c[j].x), "=r"(c[j].y) : "r"(a_cx + j * 256) : "memory");
      float d[4][4] = {};
#pragma unroll
      for (int j = 0; j < 4; j++) {
        if (j + 1 >= NPO && j < 3) wo(j + 1);
#pragma unroll
        for (int mt = 0; mt < 4; mt++) mma16(d[mt], aw[j][mt], c[j].x, c[j].y);
      }
      const float r0 = (tq & 2) ? ((tq & 1) ? d[3][0] : d[2][0]) : ((tq & 1) ? d[1][0] : d[0][0]);
      const float r1 = (tq & 2) ? ((tq & 1) ? d[3][2] : d[2][2]) : ((tq & 1) ? d[1][2] : d[0][2]);
      sts4(a_rs + 2048, r0); sts4(a_rs + 2048 + 128, r1);
      if (warp >= 2) nbar_arrive(2, 256);
      else {
        mbar_wait(bar0 + 8 * B_TAB);
        const float gav = lds4(a_ga);
        nbar(2, 256);
        const float t = gav * sum8(a_rl + 2048) + xv;
        asm volatile("{.reg .pred p; setp.eq.s32 p, %2, 0; @p red.relaxed.gpu.global.xor.b32 [%0], %1;}"
                     ::"l"(p_ab), "r"(pack2t(t, __shfl_down_sync(~0u, t, 1), par) | 1u), "r"(lane & 1) : "memory");
        pub4(p_ao, __float_as_uint(t) | 1u);
      }
    }
  } else {
    uint32_t af[4][4][4];
    uint32_t ab = bufa + (32 * warp + 8 * (lane >> 4) + (lane & 7)) * 64 + ((((lane >> 3) & 1) ^ ((lane >> 1) & 3)) << 4);
    uint32_t a_d = bufo + wg * 16384 + (8 * (lane >> 4) + (lane & 7)) * 128 + (((2 * (warp & 3) + ((lane >> 3) & 1)) ^ (lane & 7)) << 4);
    uint32_t a_rl = sb + O_R + lane * 16, a_st = sb + O_SM + (352 + 8 * (lane >> 4) + warp) * 4;
    const unsigned* pa = scr->xab + tid;
    uint32_t a_hb = mapa(bar0 + 8 * B_HZ, g), a_h = a_hb - (O_BAR + 8 * B_HZ - O_CTX) + rn * 64 + tq * 16;
    PIN(a_hb); PIN(a_h);
    uint32_t a_hl = sb + O_CTX + wg * 256 + tq * 16, a_t = sb + O_SM + (16 * warp + 8 * (tq & 1) + g) * 4;
    const unsigned* px = scr->xao + 64 * rn + 2 * lane;
    bf16* po = out + 64 * rn + 2 * lane;
    PIN(ab); PIN(a_d); PIN(a_rl); PINL(pa); PIN(a_rs); PIN(a_st); PINL(po); PIN(a_hl); PINL(px); PIN(a_t);
    mbar_wait(bar0 + 8 * B_TAB);
    uint2 cf;
    uint2 bb[4];
    uint2 gbw;
    POLL {
      unsigned bad = 0;
      cf = ldx8(scr->xm + 1024 + (lane & 16) * 16 + 32 * warp + posof(2 * (lane & 15)));
#pragma unroll
      for (int s = 0; s < 4; s++) {
        const uint4 w = ldx16(scr->xm + 1024 - (g & 1) * 512 + 256 * (s >> 1) + 32 * warp + 16 * (s & 1) + 4 * tq);
        bb[s] = make_uint2(__byte_perm(w.x, w.y, 0x7632), __byte_perm(w.z, w.w, 0x7632));
        bad = or3(bad, lop_x3(w.x, w.y, par), lop_x3(w.z, w.w, par));
      }
      gbw = ldx8(scr->xm + 1536 + 64 * rn + posof(2 * lane));
      RETRY(or3(bad, lop_x3(cf.x, cf.y, par), lop_x3(gbw.x, gbw.y, par)))
    }
    float e[4][4] = {};
    unsigned v[8];
    auto item = [&](const int it) {
      mbar_wait(fulla + 8 * it, pha);
#pragma unroll
      for (int i = 0; i < 4; i++) ldsm_t(af[it][i], (ab + it * 16384 + (i >> 1) * 1024) ^ ((i & 1) << 5));
    };
    auto item_mma = [&](const int it) {
#pragma unroll
      for (int i = 0; i < 4; i++) mma16(e[2 * (it & 1) + (i & 1)], af[it][i], bb[(it & 2) + (i >> 1)].x, bb[(it & 2) + (i >> 1)].y);
    };
    unsigned t3 = sch.wt;
    PIN(t3);
    item(0); item_mma(0); item(1); item_mma(1);
    mbar_wait(bar0 + 8 * B_G);
#pragma unroll
    for (int i = 0; i < 8; i++) v[i] = ldx4(pa + i * 256);
    t3 += clock();
    uint32_t have2, have3 = 0;
    do have2 = mbar_test(fulla + 16, pha); while (!have2 && (int)((unsigned)clock() - t3) < 0);
    if (have2) {
      item(2); item_mma(2);
      do have3 = mbar_test(fulla + 24, pha); while (!have3 && (int)((unsigned)clock() - t3) < 0);
      if (have3) { item(3); item_mma(3); }
    }
    float y0, y1, df[4][4], st[2];
    uint32_t bz[4][2] = {};
    auto mm = [&](const int it, const int i) { mma16(df[2 * (it & 1) + (i & 1)], af[it][i], bz[(it & 2) + (i >> 1)][0], bz[(it & 2) + (i >> 1)][1]); };
    POLL {
      if (it_)
#pragma unroll
        for (int i = 0; i < 8; i++) v[i] = ldx4(pa + i * 256);
      y0 = ((bflo(v[0]) + bflo(v[1])) + (bflo(v[2]) + bflo(v[3]))) + ((bflo(v[4]) + bflo(v[5])) + (bflo(v[6]) + bflo(v[7])));
      y1 = ((bfhi(v[0]) + bfhi(v[1])) + (bfhi(v[2]) + bfhi(v[3]))) + ((bfhi(v[4]) + bfhi(v[5])) + (bfhi(v[6]) + bfhi(v[7])));
      const uint32_t zb = pack2(y0 * u2f(cf.x), y1 * u2f(cf.y));
#pragma unroll
      for (int s = 0; s < 4; s++) {
        const uint32_t w = __shfl_sync(~0u, zb, 8 * s + (lane & 7));
        bz[s][0] = (lane & 4) ? 0u : w; bz[s][1] = (lane & 4) ? w : 0u;
      }
      st[0] = y0 + y1; st[1] = y0 * y0 + y1 * y1;
      tred<1>(st, lane, 16);
#pragma unroll
      for (int i = 0; i < 4; i++) df[i][0] = df[i][1] = df[i][2] = df[i][3] = 0.f;
      mm(0, 0); mm(0, 1); mm(1, 0); mm(1, 1);
      st[0] += shx(st[0], 8);
      mm(0, 2); mm(0, 3); mm(1, 2); mm(1, 3);
      RETRY(or3(or3(lop_x3(v[0], v[1], par), lop_x3(v[2], v[3], par), lop_x3(v[4], v[5], par)), lop_x3(v[6], v[7], par), 0))
    }
    uint2 xq[8];
    if (warp == 0)
#pragma unroll
      for (int i = 0; i < 8; i++) xq[i] = ldx8(px + i * 512);
    if (have2) { mm(2, 0); mm(2, 1); mm(2, 2); mm(2, 3); }
    st[0] += shx(st[0], 4);
    st[0] += shx(st[0], 2);
    st[0] += shx(st[0], 1);
    sts4(a_st, st[0]);
    __syncwarp();
    arrive_n(bar0 + 8 * B_ST, lane == 0, 1);
    if (!have2) { item(2); item_mma(2); mm(2, 0); mm(2, 1); mm(2, 2); mm(2, 3); }
    if (!have3) { item(3); item_mma(3); }
    mm(3, 0); mm(3, 1); mm(3, 2); mm(3, 3);
    mbar_wait(bar0 + 8 * B_ST);
    float mean, rstd;
    {
      float4 u[4];
#pragma unroll
      for (int i = 0; i < 4; i++) u[i] = lds16(sb + O_SM + (352 + 4 * i) * 4);
      mean = (((u[0].x + u[0].y) + (u[0].z + u[0].w)) + ((u[1].x + u[1].y) + (u[1].z + u[1].w))) * (1.f / 512.f);
      const float sq = (((u[2].x + u[2].y) + (u[2].z + u[2].w)) + ((u[3].x + u[3].y) + (u[3].z + u[3].w))) * (1.f / 512.f);
      asm("rsqrt.approx.ftz.f32 %0, %1;" : "=f"(rstd) : "f"(fmaxf(sq - mean * mean, 0.f) + 1e-5f));
    }
    float A[4], r[4];
#pragma unroll
    for (int i = 0; i < 4; i++) {
      A[i] = (tq & 2) ? ((tq & 1) ? e[3][i] : e[2][i]) : ((tq & 1) ? e[1][i] : e[0][i]);
      r[i] = (tq & 2) ? ((tq & 1) ? df[3][i] : df[2][i]) : ((tq & 1) ? df[1][i] : df[0][i]);
    }
    sts4(a_rs, rstd * (r[0] + r[1]) + (A[1] - rstd * mean * A[0])); sts4(a_rs + 128, rstd * (r[2] + r[3]) + (A[3] - rstd * mean * A[2]));
    nbar(1, 256);
    if (warp == 7) {
      const float4 g0 = lds16(a_rl), g1 = lds16(a_rl + 1024), u0 = lds16(a_rl + 512), u1 = lds16(a_rl + 1536);
      const float gg = ((g0.x + g0.y) + (g0.z + g0.w)) + ((g1.x + g1.y) + (g1.z + g1.w));
      const float uu = ((u0.x + u0.y) + (u0.z + u0.w)) + ((u1.x + u1.y) + (u1.z + u1.w));
      const float hh = (gg * uu) * rcp(1.f + ex2(gg * (-2.302208198f - 0.1029432397f * gg * gg)));
      send32(a_h, a_hb, hh, lane, 0);
    } else spin_until(clock() + FDLY);
    uint32_t ad[8][4];
    mbar_wait(fullb + 8 * wg, phb);
#pragma unroll
    for (int i = 0; i < 8; i++) ldsm_t(ad[i], a_d + i * 2048);
    float x0, x1;
    if (warp == 0) {
      POLL {
        if (it_)
#pragma unroll
          for (int i = 0; i < 8; i++) xq[i] = ldx8(px + i * 512);
        unsigned bad = 0;
#pragma unroll
        for (int i = 0; i < 4; i++) bad = or3(bad, lop_x3(xq[i].x, xq[i].y, par), lop_x3(xq[i + 4].x, xq[i + 4].y, par));
        RETRY(bad)
      }
      x0 = x1 = 0.f;
#pragma unroll
      for (int i = 0; i < 8; i++) { x0 += u2f(xq[i].x); x1 += u2f(xq[i].y); }
      x0 *= 1.f / 7.f; x1 *= 1.f / 7.f;
    }
    mbar_wait(bar0 + 8 * B_HZ);
    float dd[4][4] = {};
#pragma unroll
    for (int i = 0; i < 4; i++) {
      const float4 hb = lds16(a_hl + i * 64);
      mma16(dd[(2 * i) & 3], ad[2 * i], __float_as_uint(hb.x), __float_as_uint(hb.y));
      mma16(dd[(2 * i + 1) & 3], ad[2 * i + 1], __float_as_uint(hb.z), __float_as_uint(hb.w));
    }
    sts4(a_t, (tq & 1) ? (dd[0][2] + dd[1][2]) + (dd[2][2] + dd[3][2]) : (dd[0][0] + dd[1][0]) + (dd[2][0] + dd[3][0]));
    if (warp) nbar_arrive(2, 256);
    else {
      nbar(2, 256);
      float t0, t1, t2, t3b;
      asm volatile("ld.shared.v2.f32 {%0, %1}, [%4]; ld.shared.v2.f32 {%2, %3}, [%4 + 256];"
                   : "=f"(t0), "=f"(t1), "=f"(t2), "=f"(t3b) : "r"(sb + O_SM + lane * 8) : "memory");
      t0 = bfhi(gbw.x) * (t0 + t2) + x0; t1 = bfhi(gbw.y) * (t1 + t3b) + x1;
      asm volatile("red.relaxed.gpu.global.add.noftz.bf16x2 [%0], %1;" ::"l"(po), "r"(pack2(t0, t1)) : "memory");
      if (f == 0 && tid == 0) stx4(&scr->cnt[0], epoch + 1);
    }
  }
}

static void make_sched(Sched& s) {
  const char* order = "FFAAbcFmmvog..d";
  const double dt = 4985 * 1e-3, dth = 4660 * 1e-3;
  const int nbig = NBIG;
  s.zero = 0; s.dth = (unsigned)(dth * 256 + 0.5);
  double t = 512 * dth + 0;
  int tile = 0, jm = 0;
  for (int i = 0; i < 3; i++) s.nr[i] = s.nt[i] = 0;
  auto add = [&](int c, int type, double step, int win, int b0, int tl) {
    s.r[c][s.nr[c]++] = make_uint2((unsigned)(t + 0.5) | (unsigned)(step + 0.5) << 16, type | win << 4 | (b0 + 64) << 8 | tl << 16);
    if (type == T_KV) s.nt[c]++;
  };
  const int w1 = 6, w2 = 4, wt = 6;
  for (const char* p = order; *p; p++) {
    const char c = *p;
    if (c == 'v' || c == 'o' || c == 'm') {
      const int ty = c == 'v' ? T_UV : c == 'o' ? T_WO : T_MOD;
      const double d = (c == 'm' ? 6000 : c == 'v' ? 5500 : 5500) * 1e-3;
      add(0, ty, 64 * d, wt, 0, c == 'm' ? jm : 0); add(1, ty, 64 * d, wt, 0, c == 'm' ? jm : 0);
      t += (c == 'm' ? 64 : 256) * d; jm += c == 'm';
    } else if (c == 'g' || c == 'd') {
      const double d = (c == 'g' ? 5500 : 5000) * 1e-3;
      add(2, c == 'g' ? T_GU : T_DN, 56 * d, wt, 64, 0);
      t += (c == 'g' ? 224 : 112) * d;
    } else if (c == '.') t += 100;
    else if (c == '-') t -= 100;
    else {
      const int na = c == 'F' ? 0 : c == 'C' || c == 'c' || c == 'a' ? nbig : 64, nf = c == 'A' || c == 'a' ? 0 : 56, n = na + nf;
      const int w = na && nf ? w2 : w1;
      const bool ff = c == 'b' || c == 'c';
      const int cf = c == 'c' ? 20 : 0, ca = cf * 7 / 5;
      t += 3 * ca;
      if (na) add(0, T_KV, n * dt - ca, w, ff ? -56 : 0, tile);
      t -= 3 * ca;
      if (na == 64) add(1, T_KV, n * dt, w, ff ? -56 : 0, tile);
      if (nf) add(2, T_KV, n * dt - cf, w, ff ? 64 : 64 - na, tile);
      tile += n; t += 4 * n * dt;
      s.t4 = (unsigned)t + 600;
    }
  }
  s.dt = (unsigned)(dt * 256 + 0.5); s.d4 = 1520 | 1400 << 16; s.d6 = 3140; s.wt = 250;
}

static void launch(void* const* d_in, void* d_out) {
  static TMaps tms;
  static Sched sch;
  static bool init = false;
  static void* scr = nullptr;
  if (!init) {
    void* fn = nullptr; cudaDriverEntryPointQueryResult qr;
    cudaGetDriverEntryPoint("cuTensorMapEncodeTiled", &fn, cudaEnableDefault, &qr);
    EncFn f = (EncFn)fn;
    const CUtensorMapSwizzle S64 = CU_TENSOR_MAP_SWIZZLE_64B, S128 = CU_TENSOR_MAP_SWIZZLE_128B;
    const CUtensorMapL2promotion P256 = CU_TENSOR_MAP_L2_PROMOTION_L2_256B;
    enc3d(f, &tms.m[0], d_in[2], 64, 512, 64, 8192, 128, 64, 128, 1, S128, CU_TENSOR_MAP_L2_PROMOTION_L2_128B);
    enc3d(f, &tms.m[1], d_in[3], 64, 512, 64, 8192, 128, 64, 64, 2, S128, P256);
    enc3d(f, &tms.m[2], d_in[1], 64, SK, 8, 1024, 128, 64, 64, 2, S128, P256);
    enc3d(f, &tms.m[3], d_in[11], 3072, 256, 2, 6144, 256 * 6144, 32, 256, 1, S64, CU_TENSOR_MAP_L2_PROMOTION_L2_128B);
    enc3d(f, &tms.m[4], d_in[4], 64, 512, 64, 8192, 128, 64, 128, 1, S128, CU_TENSOR_MAP_L2_PROMOTION_L2_128B);
    enc3d(f, &tms.m[5], d_in[5], 512, 128, 32, 1024, 128 * 1024, 64, 128, 1, S128, CU_TENSOR_MAP_L2_PROMOTION_L2_128B);
    enc3d(f, &tms.m[6], d_in[7], 1792, 256, 2, 3584, 256 * 3584, 32, 256, 1, S64, CU_TENSOR_MAP_L2_PROMOTION_L2_128B);
    enc3d(f, &tms.m[7], d_in[8], 1792, 256, 2, 3584, 256 * 3584, 32, 256, 1, S64, CU_TENSOR_MAP_L2_PROMOTION_L2_128B);
    enc3d(f, &tms.m[8], d_in[9], 512, 128, 14, 1024, 128 * 1024, 64, 128, 1, S128, CU_TENSOR_MAP_L2_PROMOTION_L2_128B);
    cudaFuncSetAttribute(fused_kernel, cudaFuncAttributeMaxDynamicSharedMemorySize, SMEM9);
    cudaGetSymbolAddress(&scr, g_scr);
    make_sched(sch);
    init = true;
  }
  fused_kernel<<<NCTA9, 384, SMEM9>>>((const bf16*)d_in[0], (const bf16*)d_in[10], (const bf16*)d_in[11], (bf16*)d_out, (Scratch*)scr, sch, tms);
}

static bool fits() {
  cudaFuncSetAttribute(fused_kernel, cudaFuncAttributeMaxDynamicSharedMemorySize, SMEM9);
  cudaLaunchConfig_t cfg = {};
  cfg.gridDim = dim3(NCTA9); cfg.blockDim = dim3(384); cfg.dynamicSmemBytes = SMEM9;
  cudaLaunchAttribute at[1];
  at[0].id = cudaLaunchAttributeClusterDimension; at[0].val.clusterDim.x = 8; at[0].val.clusterDim.y = 1; at[0].val.clusterDim.z = 1;
  cfg.attrs = at; cfg.numAttrs = 1;
  int n = 0;
  if (cudaOccupancyMaxActiveClusters(&n, fused_kernel, &cfg) != cudaSuccess) { (void)cudaGetLastError(); return false; }
  return n >= NCTA9 / 8;
}
}
#undef BAR_ARM
#undef BAR_ARRIVE
#undef BAR_INIT
#undef B_EMPTY
#undef B_FM
#undef B_FULL
#undef B_G
#undef B_G2
#undef B_H
#undef B_HZ
#undef B_LZ
#undef B_Q2
#undef B_QF
#undef B_ST
#undef B_TAB
#undef B_W
#undef B_WZ
#undef CNT_ADD
#undef DSC
#undef FDLY
#undef HI128
#undef HI64
#undef LANE0
#undef LDLY
#undef NBIG
#undef NCTA9
#undef NPE
#undef NPO
#undef NSL
#undef NSP
#undef O_B
#undef O_BAR
#undef O_CTX
#undef O_DBG
#undef O_EP
#undef O_HW
#undef O_HZ
#undef O_LZ
#undef O_P
#undef O_Q
#undef O_R
#undef O_SILU
#undef O_SM
#undef O_X
#undef PIN
#undef PINL
#undef POLL
#undef QN
#undef RETRY
#undef SK
#undef SMEM9
#undef SMEM_BASE
#undef SPIN_MAX
#undef TAU
#undef VJ
#undef X16
#undef fbits

namespace v8 {
typedef __nv_bfloat16 bf16;
#define NCTA 128
#define SK 32768
#define SLOT 32768
#define NSLOT 6
#define OFF_WQ (2 * SLOT)
#define OFF_WUK (4 * SLOT)
#define OFF_Q 196608
#define OFF_P (OFF_Q + 16384)
#define OFF_B (OFF_P + 4096)
#define OFF_R4 (OFF_B + 2304)
#define OFF_SILU (OFF_R4 + 4096)
#define OFF_RA (OFF_SILU + 1024)
#define OFF_SM (OFF_RA + 1024)
#define OFF_BP (OFF_SM + 1792)
#define OFF_CO (OFF_BP + 1024)
#define OFF_BAR (OFF_CO + 1280)
#define OFF_MASK (OFF_BAR + 512)
#define OFF_DBG (OFF_MASK + 16)
#define SMEM_BYTES (OFF_DBG + 128)
#define OFF_MOD OFF_Q
#define OFF_UV (4 * SLOT)
#define OFF_O (5 * SLOT)
#define OFF_G 0
#define OFF_U 16384
#define OFF_D SLOT
#define OFF_XO (OFF_D + 16384)
#define FB_UK 4
#define FB_KV 6
#define FB_MOD 22
#define FB_UV 23
#define FB_O 25
#define FB_G 27
#define FB_D 29
#define EB 30
#define QB 50
#define XB 51
#define SPIN_MAX (1 << 20)
#define BACKOFF 40
#define RATE_NS 652
#define RATE_T0 200
#define RATE_TL 300
#define WINS 0x3222333
#define KVWIN 4
#define RATE_H 650
#define RATE_E 650
#define SMUL 9
#define NPRE0 1
#define NPRE1 3
#define HWIN 4
#define EWIN 3
#define WTEST 450
#define DLY5 650
#define DLY6 600
#define DLY7 600
#define P12(a, b, c, d, e, f, g, h, i, j, k, l) ((unsigned long long)(a) | (b) << 5 | (c) << 10 | (d) << 15 | (e) << 20 | (f) << 25 | \
  (unsigned long long)(g) << 30 | (unsigned long long)(h) << 35 | (unsigned long long)(i) << 40 | (unsigned long long)(j) << 45 | \
  (unsigned long long)(k) << 50 | (unsigned long long)(l) << 55)
#define ORDER0 P12(0, 1, 2, 3, 4, 5, 16, 6, 7, 8, 9, 10)
#define ORDER1 P12(11, 12, 13, 14, 15, 17, 18, 19, 20, 23, 21, 22)
#define TAIL_K 17
#define RS 16
template <int N> struct IC { static constexpr int value = N; };
struct TMaps { CUtensorMap m[9]; };

struct __align__(128) Scratch {
  uint4 xo[128 * 64 * RS];
  uint2 ml[32 * 64];
  unsigned h[8 * 256];
  unsigned qa[32 * 256];
  unsigned xc[128 * 64];
  unsigned xao[8 * 512];
  unsigned xf[112 * 512];
  unsigned xm[2048];
  unsigned cnt[5 * 32];
};
__device__ Scratch g_scr;
#define g_xo scr->xo
#define g_ml scr->ml
#define g_h scr->h
#define g_qa scr->qa
#define g_xc scr->xc
#define g_xao scr->xao
#define g_xf scr->xf
#define g_xm scr->xm
#define g_epoch scr->cnt[0]

__device__ __forceinline__ uint32_t s2u(const void* p) { return (uint32_t)__cvta_generic_to_shared(p); }
__device__ __forceinline__ float bflo(uint32_t u) { return __uint_as_float(u << 16); }
__device__ __forceinline__ float bfhi(uint32_t u) { return __uint_as_float(u & 0xffff0000u); }
__device__ __forceinline__ float u2f(uint32_t u) { return __uint_as_float(u); }
__device__ __forceinline__ void fma8(float* acc, uint4 v, float s) {
  acc[0] += s * bflo(v.x); acc[1] += s * bfhi(v.x); acc[2] += s * bflo(v.y); acc[3] += s * bfhi(v.y);
  acc[4] += s * bflo(v.z); acc[5] += s * bfhi(v.z); acc[6] += s * bflo(v.w); acc[7] += s * bfhi(v.w);
}
__device__ __forceinline__ uint32_t pack2(float a, float b) {
  __nv_bfloat162 p = __floats2bfloat162_rn(a, b); return *(uint32_t*)&p;
}
__device__ __forceinline__ float bfr(float v) { return bfhi(pack2(v, v)); }
__device__ __forceinline__ float silu_bf(float c) { return bfr(__fdividef(c, 1.f + __expf(-c))); }
#define fbits(v) ((__float_as_uint(v) & ~1u) | par)
__device__ __forceinline__ uint32_t pack2t(float a, float b, unsigned par) {
  const uint32_t ua = ((__float_as_uint(a) + ((par ^ 1) << 16)) & 0xFFFE0000u) | (par << 16);
  return __byte_perm(ua, pack2(b, b), 0x7632);
}
__device__ __forceinline__ void nbar(int id, int n) { asm volatile("bar.sync %0, %1;" ::"r"(id), "r"(n) : "memory"); }
__device__ __forceinline__ void nbar_arrive(int id, int n) { asm volatile("bar.arrive %0, %1;" ::"r"(id), "r"(n) : "memory"); }
__device__ __forceinline__ uint4 ldc16(const void* p) {
  uint4 v; asm volatile("ld.relaxed.cta.global.v4.u32 {%0,%1,%2,%3}, [%4];" : "=r"(v.x), "=r"(v.y), "=r"(v.z), "=r"(v.w) : "l"(p) : "memory"); return v;
}
__device__ __forceinline__ unsigned ldc4(const void* p) {
  unsigned v; asm volatile("ld.relaxed.cta.global.u32 %0, [%1];" : "=r"(v) : "l"(p) : "memory"); return v;
}
__device__ __forceinline__ uint4 ldx16(const void* p) {
  uint4 v; asm volatile("ld.relaxed.gpu.global.v4.u32 {%0,%1,%2,%3}, [%4];" : "=r"(v.x), "=r"(v.y), "=r"(v.z), "=r"(v.w) : "l"(p) : "memory"); return v;
}
__device__ __forceinline__ unsigned ldx4(const void* p) {
  unsigned v; asm volatile("ld.relaxed.gpu.global.u32 %0, [%1];" : "=r"(v) : "l"(p) : "memory"); return v;
}
__device__ __forceinline__ unsigned long long ldx64(const void* p) {
  unsigned long long v; asm volatile("ld.relaxed.gpu.global.u64 %0, [%1];" : "=l"(v) : "l"(p) : "memory"); return v;
}
__device__ __forceinline__ void stx16(void* p, uint4 v) {
  asm volatile("st.relaxed.gpu.global.v4.u32 [%0], {%1,%2,%3,%4};" ::"l"(p), "r"(v.x), "r"(v.y), "r"(v.z), "r"(v.w) : "memory");
}
__device__ __forceinline__ void stx8(void* p, uint2 v) { asm volatile("st.relaxed.gpu.global.v2.u32 [%0], {%1,%2};" ::"l"(p), "r"(v.x), "r"(v.y) : "memory"); }
__device__ __forceinline__ void stx4(void* p, unsigned v) { asm volatile("st.relaxed.gpu.global.u32 [%0], %1;" ::"l"(p), "r"(v) : "memory"); }
__device__ __forceinline__ unsigned lop_x3(unsigned a, unsigned b, unsigned c) {
  unsigned d; asm("lop3.b32 %0, %1, %2, %3, 0x7E;" : "=r"(d) : "r"(a), "r"(b), "r"(c)); return d; }
#define X16(v) (lop_x3(v.x, v.y, par) | lop_x3(v.z, v.w, par))
#define X8(v) lop_x3(v.x, v.y, par)
#define RETRY(bad) if (!__any_sync(~0u, (bad) & 1) || ++it_ >= SPIN_MAX) break; __nanosleep(BACKOFF);
#define POLL _Pragma("unroll 1") for (int it_ = 0;;)
__device__ __forceinline__ void mbar_wait(uint32_t bar) {
  uint32_t ok; int it = 0;
  do {
    asm volatile("{.reg .pred p; mbarrier.try_wait.parity.shared::cta.b64 p, [%1], 0; selp.u32 %0,1,0,p;}"
                 : "=r"(ok) : "r"(bar) : "memory");
  } while (!ok && ++it < SPIN_MAX);
}
__device__ __forceinline__ float ex2(float v) { float r; asm("ex2.approx.ftz.f32 %0, %1;" : "=f"(r) : "f"(v)); return r; }
__device__ __forceinline__ float rcp(float v) { float r; asm("rcp.approx.ftz.f32 %0, %1;" : "=f"(r) : "f"(v)); return r; }
__device__ __forceinline__ void mma16(float* d, const uint32_t* a, uint32_t b0, uint32_t b1) {
  asm volatile("mma.sync.aligned.m16n8k16.row.col.f32.bf16.bf16.f32 {%0,%1,%2,%3}, {%4,%5,%6,%7}, {%8,%9}, {%0,%1,%2,%3};"
               : "+f"(d[0]), "+f"(d[1]), "+f"(d[2]), "+f"(d[3]) : "r"(a[0]), "r"(a[1]), "r"(a[2]), "r"(a[3]), "r"(b0), "r"(b1));
}
__device__ __forceinline__ float4 lds16(uint32_t a) {
  float4 v; asm volatile("ld.shared.v4.f32 {%0,%1,%2,%3}, [%4];" : "=f"(v.x), "=f"(v.y), "=f"(v.z), "=f"(v.w) : "r"(a) : "memory"); return v;
}
__device__ __forceinline__ void ldsm_t(uint32_t* r, uint32_t a) {
  asm volatile("ldmatrix.sync.aligned.m8n8.x4.trans.shared.b16 {%0,%1,%2,%3}, [%4];" : "=r"(r[0]), "=r"(r[1]), "=r"(r[2]), "=r"(r[3]) : "r"(a) : "memory");
}
__device__ __forceinline__ void ldsm(uint32_t* r, uint32_t a) {
  asm volatile("ldmatrix.sync.aligned.m8n8.x4.shared.b16 {%0,%1,%2,%3}, [%4];" : "=r"(r[0]), "=r"(r[1]), "=r"(r[2]), "=r"(r[3]) : "r"(a) : "memory");
}
template <int N>
__device__ __forceinline__ void tred(float* a, int lane, int m) {
  const bool hi = lane & m;
#pragma unroll
  for (int i = 0; i < N; i++) {
    float send = hi ? a[i] : a[i + N], keep = hi ? a[i + N] : a[i];
    a[i] = keep + __shfl_xor_sync(~0u, send, m);
  }
}
template <int N>
__device__ __forceinline__ void tmax(float* a, int lane, int m) {
  const bool hi = lane & m;
#pragma unroll
  for (int i = 0; i < N; i++) {
    float send = hi ? a[i] : a[i + N], keep = hi ? a[i + N] : a[i];
    a[i] = fmaxf(keep, __shfl_xor_sync(~0u, send, m));
  }
}
__device__ __forceinline__ void arrive2(uint32_t bar, uint32_t rbar, bool local, bool remote) {
  asm volatile("{.reg .pred p, q; setp.ne.s32 p, %2, 0; setp.ne.s32 q, %3, 0; @p mbarrier.arrive.shared::cta.b64 _, [%0];\n"
               "@q mbarrier.arrive.relaxed.cluster.shared::cluster.b64 _, [%1];}" ::"r"(bar), "r"(rbar), "r"((int)local), "r"((int)remote) : "memory");
}
__device__ __forceinline__ unsigned long long stream_policy() {
  unsigned long long p;
  asm volatile("createpolicy.fractional.L2::evict_first.b64 %0, 1.0;" : "=l"(p));
  return p;
}
__device__ __forceinline__ void tma3d(uint32_t dst, const CUtensorMap* tm, uint32_t bar, int c0, int c1, int c2) {
  asm volatile("cp.async.bulk.tensor.3d.shared::cluster.global.mbarrier::complete_tx::bytes.L2::cache_hint [%0], [%1, {%3, %4, %5}], [%2], %6;"
               ::"r"(dst), "l"(tm), "r"(bar), "r"(c0), "r"(c1), "r"(c2), "l"(stream_policy()) : "memory");
}
__device__ __forceinline__ void st_async2(uint32_t dst, uint32_t bar, float v0, float v1) {
  asm volatile("st.async.shared::cluster.mbarrier::complete_tx::bytes.v2.f32 [%0], {%1, %2}, [%3];" ::"r"(dst), "f"(v0), "f"(v1), "r"(bar) : "memory");
}
__device__ __forceinline__ void st_pair(int mode, uint32_t dst, uint32_t bar, float v0, float v1) {
  asm volatile("{.reg .pred p, q; setp.eq.s32 p, %4, 1; setp.eq.s32 q, %4, 2; @p st.shared.v2.f32 [%0], {%1, %2};\n"
               "@q st.async.shared::cluster.mbarrier::complete_tx::bytes.v2.f32 [%0], {%1, %2}, [%3];}"
               ::"r"(dst), "f"(v0), "f"(v1), "r"(bar), "r"(mode) : "memory");
}
__device__ __forceinline__ void spin_until(unsigned t) { while ((int)((unsigned)clock() - t) < 0) {} }
__device__ __forceinline__ unsigned wait_until(unsigned t) {
  unsigned now;
  for (;;) {
    asm volatile("mov.u32 %0, %%globaltimer_lo;" : "=r"(now));
    if ((int)(now - t) >= 0) break;
  }
  return now;
}
#define PIN(x) asm volatile("" : "+r"(x))
#define PINL(x) asm volatile("" : "+l"(x))
#define BAR_ARRIVE(i) asm volatile("mbarrier.arrive.shared::cta.b64 _, [%0];" ::"r"(bar0 + 8 * (i)) : "memory")
#define CNT_ADD(c) asm volatile("red.relaxed.gpu.global.add.u32 [%0], 1;" ::"l"(scr->cnt + (c)) : "memory")
#define BAR_INIT(i, cnt) asm volatile("mbarrier.init.shared::cta.b64 [%0], %1;" ::"r"(bar0 + 8 * (i)), "r"(cnt) : "memory")
#define BAR_ARM(i, bytes) asm volatile("mbarrier.arrive.expect_tx.shared::cta.b64 _, [%0], %1;" ::"r"(bar0 + 8 * (i)), "r"(bytes) : "memory")

__device__ __forceinline__ void tail(unsigned char* smem, Scratch* __restrict__ scr, const bf16* __restrict__ x, bf16* __restrict__ out,
                                     const unsigned par, const unsigned epoch, const int warp) {
  int tid, b;
  asm volatile("mov.u32 %0, %%tid.x;" : "=r"(tid));
  asm volatile("mov.u32 %0, %%ctaid.x;" : "=r"(b));
  const int lane = tid & 31, g = lane >> 2, tq = lane & 3;
  const uint32_t sb = __shfl_sync(~0u, s2u(smem), 0), bar0 = sb + OFF_BAR;
  float* s_sm = (float*)(smem + OFF_SM);
  const int prow = 4 * (lane >> 4) + ((lane & 7) >> 1) + 8 * (lane & 1);
  const float* s_co = (const float*)(smem + OFF_CO);
  const int opos = (b & 15) * 32 + (lane & 16) + 2 * (lane & 6) + ((lane >> 2) & 2) + (lane & 1);
  const float xv = b < 16 ? __bfloat162float(x[(b & 15) * 32 + lane]) : 0.f;
  const int rk = b & 1, ob = 32 * rk + ((b >> 1) & 31);
  uint32_t psb;
  asm volatile("mapa.shared::cluster.u32 %0, %1, %2;" : "=r"(psb) : "r"(sb), "r"(rk ^ 1));
  {
    uint32_t a[8][4];
    {
      const int rg = tid >> 4;
      const uint4* src = g_xo + ((size_t)b * 64 + rg) * RS;
      const uint32_t dst = sb + OFF_XO + rg * 256 + (((tid & 15) ^ (rg & 7)) << 4);
      unsigned long long todo = 0x0001000100010001ull;
#pragma unroll 1
      for (int it = 0; it < SPIN_MAX * 16; it++) {
        unsigned long long mk = *(volatile unsigned long long*)(smem + OFF_MASK);
        const unsigned long long nw = (mk >> rg) & todo;
        todo ^= nw;
#pragma unroll
        for (int i = 0; i < 4; i++)
          if (nw >> (16 * i) & 1)
            asm volatile("cp.async.cg.shared.global [%0], [%1], 16;" ::"r"(dst + i * 4096), "l"(src + i * 16 * RS + (tid & 15)) : "memory");
        if (!__any_sync(~0u, todo != 0)) break;
      }
      asm volatile("cp.async.mbarrier.arrive.noinc.shared::cta.b64 [%0];" ::"r"(bar0 + 8 * (XB + 2)) : "memory");
    }
    mbar_wait(bar0 + 8 * FB_UV); mbar_wait(bar0 + 8 * (FB_UV + 1));
    const uint32_t ab = sb + OFF_UV + (warp >> 2) * 8192 + (8 * (lane >> 4) + (lane & 7)) * 128 + (((2 * (warp & 3) + ((lane >> 3) & 1)) ^ (lane & 7)) << 4);
#pragma unroll
    for (int s = 0; s < 8; s++) ldsm_t(a[s], ab + (s >> 2) * 16384 + (s & 3) * 2048);
    const int chn = 2 * warp + (tq & 1);
    uint32_t a_b = sb + OFF_B + (tq >> 1) * 272 + (32 * (chn >> 2) + 8 * (g >> 1) + 2 * (chn & 3) + (g & 1)) * 2;
    uint32_t a_bq = sb + OFF_B + (lane & 1) * 272 + (lane >> 3) * 16;
    unsigned* p_c = g_xc + (b >> 2) * 256 + warp * 32 + (b & 3) * 8 + (g & 3) * 2 + (g >> 2);
    PIN(a_b); PIN(a_bq); PINL(p_c);
    mbar_wait(bar0 + 8 * (XB + 6));
    uint32_t wb[8];
#pragma unroll
    for (int s = 0; s < 8; s++) wb[s] = *(const uint32_t*)(smem + OFF_RA + (4 * s + tq) * 4);
    const float invL = *(const float*)(smem + OFF_RA + 128);
    float ov;
    POLL {
      mbar_wait(bar0 + 8 * (XB + 2));
      uint32_t ao[4][4];
#pragma unroll
      for (int s = 0; s < 4; s++)
        ldsm_t(ao[s], sb + OFF_XO + (16 * s + 8 * (lane >> 4) + (lane & 7)) * 256 + (((2 * warp + ((lane >> 3) & 1)) ^ (lane & 7)) << 4));
      float d[4][4] = {};
#pragma unroll
      for (int s = 0; s < 4; s++) mma16(d[s], ao[s], wb[2 * s], wb[2 * s + 1]);
      const unsigned p2 = par * 0x10001u;
      unsigned bad = 0;
#pragma unroll
      for (int s = 0; s < 4; s++) bad |= lop_x3(ao[s][0], ao[s][1], p2) | lop_x3(ao[s][2], ao[s][3], p2);
      bad = g == 0 ? bad | (bad >> 16) : 0u;
      ov = (tq & 1) ? (d[0][2] + d[1][2]) + (d[2][2] + d[3][2]) : (d[0][0] + d[1][0]) + (d[2][0] + d[3][0]);
      if (__builtin_expect(!__any_sync(~0u, bad & 1) || ++it_ >= SPIN_MAX, 1)) break;
#pragma unroll
      for (int i = 0; i < 4; i++)
        asm volatile("cp.async.cg.shared.global [%0], [%1], 16;"
                     ::"r"(sb + OFF_XO + ((lane >> 1) + 16 * i) * 256 + (((2 * warp + (lane & 1)) ^ ((lane >> 1) & 7)) << 4)),
                       "l"(g_xo + ((size_t)b * 64 + (lane >> 1) + 16 * i) * RS + 2 * warp + (lane & 1)) : "memory");
      asm volatile("cp.async.wait_all;" ::: "memory");
      __syncwarp();
    }
    {
      const float lo = ov - bfhi(__float_as_uint(ov));
      asm volatile("st.shared.u16 [%0], %1;" ::"r"(a_b), "h"((unsigned short)((tq & 2) ? pack2(lo, lo) : __float_as_uint(ov) >> 16)) : "memory");
    }
    nbar(1, 256);
    float d[4][4] = {};
#pragma unroll
    for (int y = 0; y < 4; y++) {
      uint32_t bq[4];
      ldsm(bq, a_bq + 64 * y);
      mma16(d[(2 * y) & 3], a[2 * y], bq[0], bq[1]); mma16(d[(2 * y + 1) & 3], a[2 * y + 1], bq[2], bq[3]);
    }
    const float r0 = ((d[0][0] + d[0][1]) + (d[1][0] + d[1][1])) + ((d[2][0] + d[2][1]) + (d[3][0] + d[3][1]));
    const float r1 = ((d[0][2] + d[0][3]) + (d[1][2] + d[1][3])) + ((d[2][2] + d[2][3]) + (d[3][2] + d[3][3]));
    if (tq == 0) stx4(p_c, pack2t(r0 * invL, r1 * invL, par));
  }
  unsigned tpub = clock();
  mbar_wait(bar0 + 8 * (XB + 4));
  const float gav = s_co[256 + (opos & 31)];
  const float gbv = s_co[288 + (lane & 4) + 2 * (lane & 1) + ((lane >> 1) & 1)];
  float4 cf[2];
#pragma unroll
  for (int s = 0; s < 2; s++) cf[s] = *(const float4*)(s_co + 32 * warp + 16 * s + 4 * tq);
  {
    uint32_t a[2][4][4];
    mbar_wait(bar0 + 8 * (FB_O + (warp >> 2)));
    const uint32_t ab = sb + OFF_O + (32 * warp + prow) * 128 + ((((lane >> 3) & 1) ^ (prow & 7)) << 4);
#pragma unroll
    for (int i = 0; i < 8; i++) ldsm_t(a[i >> 2][i & 3], (ab + (i >> 2) * 2048) ^ ((i & 3) << 5));
    uint4 v;
    const unsigned* pc = g_xc + (4 * (b >> 4) + 2 * rk + (warp >> 2)) * 256 + 64 * (warp & 3) + 2 * lane;
    uint32_t ro = ((tq >> 1) == rk ? sb : psb) + OFF_P + (8 * (tq & 1) + g) * 144 + (8 * rk + warp) * 8;
    uint32_t a_q = sb + OFF_P + (8 * (lane >> 4) + (lane & 7)) * 144;
    unsigned* p_ao = g_xao + (b >> 5) * 1024 + (opos >> 4) * 32 + (b & 16) + (opos & 15);
    PIN(ro); PIN(a_q); PINL(p_ao); PINL(pc);
    spin_until(tpub + DLY5);
    POLL {
      const unsigned long long u0 = ldx64(pc);
      v.x = (unsigned)u0; v.y = u0 >> 32;
      RETRY(X8(v))
    }
    v.z = lane & 16 ? v.x : 0u; v.w = lane & 16 ? v.y : 0u;
    if (lane & 16) v.x = v.y = 0u;
    float d[4][4] = {};
#pragma unroll
    for (int mt = 0; mt < 4; mt++) mma16(d[mt], a[0][mt], v.x, v.y);
#pragma unroll
    for (int mt = 0; mt < 4; mt++) mma16(d[mt], a[1][mt], v.z, v.w);
    float r[8];
#pragma unroll
    for (int i = 0; i < 8; i++) r[i] = d[i >> 1][2 * (i & 1)] + d[i >> 1][2 * (i & 1) + 1];
    tred<4>(r, lane, 2); tred<2>(r, lane, 1);
    st_pair((tq >> 1) == rk ? 1 : 2, ro, psb + OFF_BAR + 8 * (XB + 3), r[0], r[1]);
    __syncwarp();
    if (lane == 0) BAR_ARRIVE(XB + 3);
    if (warp == 0) {
      mbar_wait(bar0 + 8 * (XB + 3));
      float p[8];
#pragma unroll
      for (int i = 0; i < 8; i++) {
        const float4 q = lds16(a_q + i * 16);
        p[i] = (lane & 8) ? q.y + q.w : q.x + q.z;
      }
      const float t = ((p[0] + p[1]) + (p[2] + p[3])) + ((p[4] + p[5]) + (p[6] + p[7]));
      stx4(p_ao, fbits(gav * t + xv));
    }
  }
  tpub = clock();
  if (b < 112) {
    uint32_t af[2][4][4], ad[4][4];
    const uint32_t ab = sb + (32 * warp + 8 * (lane >> 4) + (lane & 7)) * 64 + ((((lane >> 3) & 1) ^ ((lane >> 1) & 3)) << 4);
    uint32_t ro = ((tq & 1) == rk ? sb : psb) + OFF_R4 + (8 * (tq >> 1) + g) * 176 + (10 * rk + warp) * 8;
    uint32_t a_q = sb + OFF_R4 + (8 * (lane >> 4) + (lane & 7)) * 176 + (lane & 8) * 10;
    uint32_t a_d = sb + OFF_D + warp * 2048 + (8 * (lane >> 4) + (lane & 7)) * 128 + ((((lane >> 3) & 1) ^ (lane & 7)) << 4);
    unsigned* p_f = g_xf + b * 512 + 64 * warp + 16 * tq + 2 * g;
    const unsigned* pa = g_xao + (g >> 1) * 1024 + 512 * rk + 64 * warp + 4 * (lane & 7);
    PIN(ro); PIN(a_q); PIN(a_d); PINL(p_f); PINL(pa);
    spin_until(tpub + DLY6);
    uint4 v[2];
    {
      bool have = false;
      POLL {
        v[0] = ldx16(pa); v[1] = ldx16(pa + 32);
        const unsigned t1 = (unsigned)clock() + WTEST;
        while (!have && (int)((unsigned)clock() - t1) < 0) {
          uint32_t ok;
          asm volatile("{.reg .pred p, q; mbarrier.test_wait.parity.shared::cta.b64 p, [%1], 0; mbarrier.test_wait.parity.shared::cta.b64 q, [%1+8], 0;\n"
                       "and.pred p, p, q; vote.sync.all.pred p, p, 0xffffffff; selp.u32 %0, 1, 0, p;}" : "=r"(ok) : "r"(bar0 + 8 * FB_G) : "memory");
          if (ok) {
#pragma unroll
            for (int i = 0; i < 8; i++) ldsm_t(af[i >> 2][i & 3], (ab + ((i & 2) ? OFF_U : OFF_G) + (i >> 2) * 1024) ^ ((i & 1) << 5));
            have = true;
          }
        }
        if (!__any_sync(~0u, (X16(v[0]) | X16(v[1])) & 1) || ++it_ >= SPIN_MAX) break;
      }
      float df[4][4] = {}, dg[2][4] = {};
      uint32_t zb[4];
      const uint32_t one = g == 0 ? 0x3F803F80u : 0u;
#pragma unroll
      for (int s = 0; s < 2; s++) {
        const uint32_t y0 = pack2(u2f(v[s].x), u2f(v[s].y)), y1 = pack2(u2f(v[s].z), u2f(v[s].w));
        const uint32_t ya[4] = {y0, one, y1, one};
        mma16(dg[s], ya, y0, y1);
        zb[2 * s] = pack2(u2f(v[s].x) * cf[s].x, u2f(v[s].y) * cf[s].y); zb[2 * s + 1] = pack2(u2f(v[s].z) * cf[s].z, u2f(v[s].w) * cf[s].w);
      }
      float st[2] = {(dg[0][2] + dg[0][3]) + (dg[1][2] + dg[1][3]), (dg[0][0] + dg[0][1]) + (dg[1][0] + dg[1][1])};
      if (!have) {
        mbar_wait(bar0 + 8 * FB_G); mbar_wait(bar0 + 8 * (FB_G + 1));
#pragma unroll
        for (int i = 0; i < 8; i++) ldsm_t(af[i >> 2][i & 3], (ab + ((i & 2) ? OFF_U : OFF_G) + (i >> 2) * 1024) ^ ((i & 1) << 5));
      }
#pragma unroll
      for (int i = 0; i < 8; i++) mma16(df[i & 3], af[i >> 2][i & 3], zb[2 * (i >> 2)], zb[2 * (i >> 2) + 1]);
#pragma unroll
      for (int o2 = 1; o2 < 4; o2 <<= 1) { st[0] += __shfl_xor_sync(~0u, st[0], o2); st[1] += __shfl_xor_sync(~0u, st[1], o2); }
#pragma unroll
      for (int o2 = 4; o2 < 32; o2 <<= 1) st[1] += __shfl_xor_sync(~0u, st[1], o2);
      float r[8];
#pragma unroll
      for (int i = 0; i < 8; i++) r[i] = df[i >> 1][2 * (i & 1)] + df[i >> 1][2 * (i & 1) + 1];
      tred<4>(r, lane, 2); tred<2>(r, lane, 1);
      const int md = (tq & 1) == rk ? 1 : 2;
      st_pair(md, ro, psb + OFF_BAR + 8 * (XB + 5), r[0], r[1]);
      st_pair(lane < 2 ? md : 0, ro + 16 * 176, psb + OFF_BAR + 8 * (XB + 5), st[0], st[1]);
      __syncwarp();
      if (lane == 0) BAR_ARRIVE(XB + 5);
      mbar_wait(bar0 + 8 * FB_D);
#pragma unroll
      for (int mt = 0; mt < 4; mt++)
        ldsm_t(ad[mt], a_d ^ (mt << 5));
    }
    mbar_wait(bar0 + 8 * (XB + 5));
    {
      float4 q[5], u[8];
#pragma unroll
      for (int i = 0; i < 5; i++) q[i] = lds16(a_q + i * 16);
#pragma unroll
      for (int i = 0; i < 8; i++) u[i] = *(const float4*)(smem + OFF_R4 + 16 * 176 + (i >> 2) * 80 + (i & 3) * 16);
      float p[6] = {((q[0].x + q[0].z) + (q[1].x + q[1].z)) + ((q[2].x + q[2].z) + (q[3].x + q[3].z)), q[4].x, q[4].z,
                    ((q[0].y + q[0].w) + (q[1].y + q[1].w)) + ((q[2].y + q[2].w) + (q[3].y + q[3].w)), q[4].y, q[4].w};
      tred<3>(p, lane, 8);
      const float P = p[0], A1 = p[1], A2 = p[2];
      const float mean = (((u[0].x + u[0].z) + (u[1].x + u[1].z)) + ((u[2].x + u[2].z) + (u[3].x + u[3].z)) +
                          ((u[4].x + u[4].z) + (u[5].x + u[5].z)) + ((u[6].x + u[6].z) + (u[7].x + u[7].z))) * (1.f / 512.f);
      const float sq = (((u[0].y + u[0].w) + (u[1].y + u[1].w)) + ((u[2].y + u[2].w) + (u[3].y + u[3].w)) +
                         ((u[4].y + u[4].w) + (u[5].y + u[5].w)) + ((u[6].y + u[6].w) + (u[7].y + u[7].w))) * (1.f / 512.f);
      float rstd;
      asm("rsqrt.approx.ftz.f32 %0, %1;" : "=f"(rstd) : "f"(fmaxf(sq - mean * mean, 0.f) + 1e-5f));
      const float gg = bfr(rstd * (P - mean * A1) + A2);
      const float uu = __shfl_xor_sync(~0u, gg, 16);
      const float hh = bfr(gg * rcp(1.f + ex2(gg * (-2.302208198f - 0.1029432397f * gg * gg)))) * uu;
      const uint32_t hw = pack2(hh, __shfl_down_sync(~0u, hh, 1));
      const uint32_t b0 = __shfl_sync(~0u, hw, 2 * tq), b1 = __shfl_sync(~0u, hw, 2 * tq + 8);
      float f0 = 0, f1 = 0;
#pragma unroll
      for (int mt = 0; mt < 4; mt++) {
        float dd[4] = {0, 0, 0, 0};
        mma16(dd, ad[mt], b0, b1);
        if (tq == mt) { f0 = dd[0]; f1 = dd[2]; }
      }
      stx8(p_f, make_uint2(fbits(f0), fbits(f1)));
    }
    tpub = clock();
    if (b < 64 && warp == (b >> 3)) {
      const uint4 y = (b & 4) ? v[1] : v[0];
      float a4[4] = {u2f(y.x), u2f(y.y), u2f(y.z), u2f(y.w)};
      tred<2>(a4, lane, 16); tred<1>(a4, lane, 8);
      a4[0] += __shfl_xor_sync(~0u, a4[0], 4);
      if (!(lane & 4)) s_sm[416 + 8 * (lane >> 4) + 2 * tq + ((lane >> 3) & 1)] = a4[0];
      if (warp == 7) nbar_arrive(2, 256);
    } else if (b < 64 && warp == 7) nbar_arrive(2, 256);
    if (b < 64 && warp < 7) {
      uint4 v;
      const unsigned* pf = g_xf + (tid >> 1) * 512 + 8 * ob + 4 * (tid & 1);
      const int col = 16 * (ob >> 1) + 4 * (ob & 1) + ((tid >> 1) & 3) + 8 * (tid & 1);
      bf16* po = out + col;
      PINL(po); PINL(pf);
      spin_until(tpub + DLY7);
      POLL { v = ldx16(pf); RETRY(X16(v)) }
      float f[4] = {u2f(v.x), u2f(v.y), u2f(v.z), u2f(v.w)};
      tred<2>(f, lane, 16); tred<1>(f, lane, 8);
      f[0] += __shfl_xor_sync(~0u, f[0], 4); f[0] += __shfl_xor_sync(~0u, f[0], 2);
      if (!(lane & 6)) s_sm[352 + warp * 8 + 4 * (lane & 1) + (lane >> 3)] = f[0];
      nbar(2, 256);
      if (tid < 8) {
        const float* q = s_sm + 352 + tid;
        const float t = ((q[0] + q[8]) + (q[16] + q[24])) + ((q[32] + q[40]) + q[48]);
        *po = __float2bfloat16(s_sm[416 + (col & 15)] + bfr(gbv * bfr(t)));
        if (b == 0 && tid == 0) stx4(&g_epoch, epoch + 1);
      }
    }
  }
}

__global__ void __cluster_dims__(2, 1, 1) __launch_bounds__(384, 1)
fused_kernel(const bf16* __restrict__ x, const bf16* __restrict__ cvec, const bf16* __restrict__ w_mod, bf16* __restrict__ out,
             Scratch* __restrict__ scr, const __grid_constant__ TMaps tms) {
  extern __shared__ __align__(1024) unsigned char smem[];
  const int tid = threadIdx.x, warp = __shfl_sync(~0u, tid >> 5, 0), lane = tid & 31;
  const int b = blockIdx.x, rk = b & 1, pr = b >> 1, hd = b >> 2;
  uint32_t sb = s2u(smem), bar0 = sb + OFF_BAR;

  unsigned gt_start;
  asm volatile("mov.u32 %0, %%globaltimer_lo;" : "=r"(gt_start));
  const int g = lane >> 2, tq = lane & 3;
  const int arow = 64 * (b >> 4) + ((tid & 255) >> 3);
  uint4 wm0, wm1;
  uint32_t c0w, c1w;
  if (warp < 8) {
    const bf16* wa = w_mod + (size_t)arow * 3072 + (lane & 4) * 128 + 32 * (b & 15) + 8 * tq;
    wm0 = ldx16(wa); wm1 = ldx16(wa + 32 * 3072);
    c0w = ldc4(cvec + (arow & ~1)); c1w = ldc4(cvec + (arow & ~1) + 32);
  }
  const unsigned t_off = gt_start + RATE_T0;
  if (warp == 11) {
    if (lane == 0) {
#pragma unroll
      for (int i = 0; i < FB_KV; i++) { BAR_INIT(i, 1); BAR_ARM(i, 16384); }
    }
    __syncwarp();
    asm volatile("fence.mbarrier_init.release.cluster;" ::: "memory");
    asm volatile("barrier.cluster.arrive.relaxed.aligned;" ::: "memory");
#pragma unroll 1
    for (int i = 0; i < FB_KV; i++) {
      if (i >= HWIN) mbar_wait(bar0 + 8 * (i - HWIN));
      wait_until(t_off + (i < 4 ? 2 * i + ((b >> 1) & 1) : 4 * i - 8 + (b & 3)) * (RATE_H / 4));
      if (lane == 0) {
        if (i < 4) tma3d(sb + OFF_WQ + i * 16384, &tms.m[0], bar0 + 8 * i, 0, i * 128, 2 * hd + rk);
        else tma3d(sb + OFF_WQ + i * 16384, &tms.m[1], bar0 + 8 * i, 0, (b & 3) * 128 + (i - 4) * 64, 2 * hd);
      }
      __syncwarp();
    }
  }
  if (warp == 10) {
    const uint4 xa = ldc16(x + 16 * lane), xb = ldc16(x + 16 * lane + 8);
    const unsigned ep = ldc4(&g_epoch);
    float xv[16] = {bflo(xa.x), bfhi(xa.x), bflo(xa.y), bfhi(xa.y), bflo(xa.z), bfhi(xa.z), bflo(xa.w), bfhi(xa.w),
                    bflo(xb.x), bfhi(xb.x), bflo(xb.y), bfhi(xb.y), bflo(xb.z), bfhi(xb.z), bflo(xb.w), bfhi(xb.w)};
    float s = 0;
#pragma unroll
    for (int i = 0; i < 16; i++) s += xv[i];
#pragma unroll
    for (int o = 16; o; o >>= 1) s += __shfl_xor_sync(~0u, s, o);
    const float mean = s * (1.f / 512.f);
    s = 0;
#pragma unroll
    for (int i = 0; i < 16; i++) { xv[i] -= mean; s += xv[i] * xv[i]; }
#pragma unroll
    for (int o = 16; o; o >>= 1) s += __shfl_xor_sync(~0u, s, o);
    const float rstd = rsqrtf(s * (1.f / 512.f) + 1e-5f);
    if ((lane >> 1) == (b & 15))
#pragma unroll
      for (int i = 0; i < 4; i++)
        *(float4*)(smem + OFF_SM + (256 + (lane & 1) * 16 + 4 * i) * 4) = make_float4(xv[4 * i] * rstd, xv[4 * i + 1] * rstd, xv[4 * i + 2] * rstd, xv[4 * i + 3] * rstd);
    if (lane == 0) *(volatile unsigned*)(smem + OFF_MASK + 8) = ep;
    nbar_arrive(1, 288);
  }
  if (warp >= 8) {
    asm volatile("setmaxnreg.dec.sync.aligned.u32 72;");
    if (tid == 288) {
#pragma unroll
      for (int q = FB_KV; q < FB_KV + 16; q++) { BAR_INIT(q, 1); BAR_ARM(q, 32768); }
    }
    if (tid == 320) {
#pragma unroll
      for (int q = 0; q <= 13 + NSLOT; q++) BAR_INIT(EB + q, q == 0 ? 4 : q < 5 ? 16 : q < 16 ? 12 : 6);
    }
    if (tid == 256) {
#pragma unroll
      for (int q = FB_MOD; q <= FB_D; q++) { BAR_INIT(q, 1); BAR_ARM(q, 16384); }
      BAR_INIT(QB, 9); BAR_ARM(QB, 1024);
#pragma unroll
      for (int q = 0; q < 7; q++) BAR_INIT(XB + q, q == 2 ? 256 : q == 5 || q == 3 ? 9 : 1);
      BAR_ARM(XB + 3, 1024);
      BAR_ARM(XB + 5, 1024 + 64 + 512);
      *(volatile unsigned long long*)(smem + OFF_MASK) = 0;
    }
    if (warp != 11) {
      __syncwarp();
      asm volatile("fence.mbarrier_init.release.cluster;" ::: "memory");
      __threadfence_block();
      asm volatile("barrier.cluster.arrive.relaxed.aligned;" ::: "memory");
    }
    if (warp == 11) {
      asm volatile("barrier.cluster.wait.acquire.aligned;" ::: "memory");
      const unsigned epoch = *(volatile unsigned*)(smem + OFF_MASK + 8), par = (epoch + 1) & 1;
      mbar_wait(bar0 + 8 * (FB_KV + 15));
      for (int it = 0; ldx4(scr->cnt + 96 + 32 * (b >> 6)) != (epoch + 1) * 64 && it < SPIN_MAX; it++) {}
      uint4 hh;
      POLL { hh = ldx16(g_ml + (b >> 2) * 64 + 2 * lane); RETRY(X16(hh)) }
      int mi = __float_as_int(fmaxf(u2f(hh.x), u2f(hh.z)));
      mi ^= (mi >> 31) & 0x7fffffff;
      mi = __reduce_max_sync(~0u, mi);
      mi ^= (mi >> 31) & 0x7fffffff;
      const float M = __int_as_float(mi);
      const uint32_t wp = pack2(ex2(u2f(hh.x) - M), ex2(u2f(hh.z) - M));
      float L = bflo(wp) * u2f(hh.y) + bfhi(wp) * u2f(hh.w);
#pragma unroll
      for (int o2 = 16; o2; o2 >>= 1) L += __shfl_xor_sync(~0u, L, o2);
      *(uint32_t*)(smem + OFF_RA + lane * 4) = wp;
      if (lane == 0) *(float*)(smem + OFF_RA + 128) = rcp(L);
      __syncwarp();
      if (lane == 0) BAR_ARRIVE(XB + 6);
    }
    if (warp == 10) {
      if (lane < 8) asm volatile("prefetch.tensormap [%0];" ::"l"(&tms.m[lane + 1]) : "memory");
      asm volatile("barrier.cluster.wait.acquire.aligned;" ::: "memory");
      const unsigned epoch = *(volatile unsigned*)(smem + OFF_MASK + 8);
#pragma unroll 1
      for (int e = 0; e < 2; e++) {
        for (int it = 0; ldx4(scr->cnt + (e ? 2 + rk : 1)) != (epoch + 1) * (e ? 64 : 128) && it < SPIN_MAX; it++) {}
        if (lane == 0) BAR_ARRIVE(XB + e);
      }
      mbar_wait(bar0 + 8 * (FB_KV + 14));
      unsigned long long m = 0;
#pragma unroll 1
      for (int it = 0; ~m && it < SPIN_MAX; it++) {
        m = ldx64(scr->cnt + 32 + 32 * (b >> 6)) ^ ((epoch & 1) ? ~0ull : 0ull);
        if (lane == 0) *(volatile unsigned long long*)(smem + OFF_MASK) = m;
      }
    }
    if (warp == 9) {
      asm volatile("barrier.cluster.wait.acquire.aligned;" ::: "memory");
      const unsigned epoch = *(volatile unsigned*)(smem + OFF_MASK + 8);
      const unsigned par = (epoch + 1) & 1, inv = par ^ 1;
      const uint4 inv4 = make_uint4(inv, inv, inv, inv);
      mbar_wait(bar0 + 8 * FB_KV);
#pragma unroll 2
      for (int k = 0; k < 8; k++) {
        const uint32_t cp = ldc4(cvec + 2 * (lane + 32 * k));
        *(uint32_t*)(smem + OFF_SILU + (lane + 32 * k) * 4) = pack2(silu_bf(bflo(cp)), silu_bf(bfhi(cp)));
      }
      __syncwarp();
      mbar_wait(bar0 + 8 * FB_MOD);
      const uint32_t ab = sb + OFF_MOD + (8 * (lane >> 4) + (lane & 7)) * 32 + ((((lane >> 3) ^ (lane >> 2)) & 1) << 4);
      float d[4][4] = {};
#pragma unroll 2
      for (int s4 = 0; s4 < 8; s4++)
#pragma unroll
        for (int s = 0; s < 4; s++) {
          uint32_t a[4];
          const uint32_t* ps = (const uint32_t*)(smem + OFF_SILU) + 32 * s4 + 8 * s + tq;
          ldsm_t(a, ab + (4 * s4 + s) * 512); mma16(d[s], a, ps[0], ps[4]);
        }
      const float t = (tq & 1) ? (d[0][2] + d[1][2]) + (d[2][2] + d[3][2]) : (d[0][0] + d[1][0]) + (d[2][0] + d[3][0]);
      if (tq < 2) stx4(g_xm + b * 16 + 2 * (g & 6) + 2 * tq + (g & 1), fbits(bfr(t)));
      __syncwarp();
      if (lane == 0) CNT_ADD(6);
      mbar_wait(bar0 + 8 * (FB_KV + 8));
      if (lane < 16) stx16(g_xc + (b >> 2) * 256 + (lane >> 1) * 32 + (b & 3) * 8 + (lane & 1) * 4, inv4);
      if (lane < 8) stx16(g_xao + (b >> 5) * 1024 + (b & 15) * 64 + (lane & 4) * 8 + (b & 16) + (lane & 3) * 4, inv4);
      if (b < 112)
#pragma unroll 1
        for (int k = 0; k < 4; k++) stx16(g_xf + b * 512 + (lane + 32 * k) * 4, inv4);
      nbar_arrive(2, 288);
      for (int it = 0; ldx4(scr->cnt + 6) != (epoch + 1) * 128 && it < SPIN_MAX; it++) __nanosleep(100);
      {
        uint4 sv[2], cb[2];
        unsigned ga, gb;
        POLL {
#pragma unroll
          for (int k = 0; k < 2; k++) { sv[k] = ldx16(g_xm + 512 + 256 * rk + 4 * (lane + 32 * k)); cb[k] = ldx16(g_xm + 1024 + 256 * rk + 4 * (lane + 32 * k)); }
          ga = ldx4(g_xm + (b & 15) * 32 + lane); gb = ldx4(g_xm + 1536 + 256 * rk + 8 * (pr & 31) + (lane & 7));
          RETRY(X16(sv[0]) | X16(sv[1]) | X16(cb[0]) | X16(cb[1]) | lop_x3(ga, gb, par))
        }
#pragma unroll
        for (int k = 0; k < 2; k++) {
          const float c0 = bfr(1.f + bfhi(cb[k].x)), c1 = bfr(1.f + bfhi(cb[k].y)), c2 = bfr(1.f + bfhi(cb[k].z)), c3 = bfr(1.f + bfhi(cb[k].w));
          *(float4*)(smem + OFF_CO + (lane + 32 * k) * 16) = make_float4(c0, c1, c2, c3);
          uint2* pb = (uint2*)(smem + OFF_BP) + lane + 32 * k;
          pb[0] = make_uint2(pack2(c0, c1), pack2(c2, c3));
          pb[64] = make_uint2(__byte_perm(sv[k].x, sv[k].y, 0x7632), __byte_perm(sv[k].z, sv[k].w, 0x7632));
        }
        *(float*)(smem + OFF_CO + 1024 + lane * 4) = bfhi(ga);
        *(float*)(smem + OFF_CO + 1152 + lane * 4) = bfhi(gb);
      }
      __syncwarp();
      if (lane == 0) BAR_ARRIVE(XB + 4);
    }
    if (warp == 8) {
      const unsigned stag = ((pr * SMUL) & 63) * RATE_NS >> 6;
      unsigned tnext = t_off + 4 * RATE_H;
      asm volatile("barrier.cluster.wait.acquire.aligned;" ::: "memory");
#pragma unroll 1
      for (int k = 0; k < 24; k++) {
        const int code = (k < 12 ? ORDER0 >> (5 * k) : ORDER1 >> (5 * (k - 12))) & 31;
        const bool kv = code < 16;
        const int n = code, w = code - 16;
        if (!kv && w >= 5 && b >= 112) break;
        if (kv) mbar_wait(bar0 + 8 * (FB_KV + n - (n < 6 ? EWIN : KVWIN)));
        if (k >= TAIL_K) mbar_wait(bar0 + 8 * (FB_KV + (int)((ORDER1 >> (5 * (k - 12 - ((WINS >> (4 * (k - TAIL_K))) & 15)))) & 31)));
        const int e = kv ? (n == 3 ? 2 : n == 5 ? 1 : n) : w == 0 ? 0 : w < 5 ? 16 + ((w - 1) >> 1) : w == 7 ? 19 : 18;
        if (e != 1 && k) mbar_wait(bar0 + 8 * (EB + e));
        wait_until(tnext + stag);
        tnext += k > TAIL_K ? RATE_TL : k < 4 ? RATE_E : RATE_NS;
        if (lane == 0) {
          if (kv)
            asm volatile("cp.async.bulk.tensor.3d.shared::cluster.global.mbarrier::complete_tx::bytes.multicast::cluster.L2::cache_hint [%0], [%1, {%3, %4, %5}], [%2], %6, %7;"
                         ::"r"(sb + (n % NSLOT) * SLOT + rk * 16384), "l"(&tms.m[2]), "r"(bar0 + 8 * (FB_KV + n)), "r"(0), "r"(((n >> 1) * 64 + pr) * 64),
                           "r"(4 * (n & 1) + 2 * rk), "h"((unsigned short)3), "l"(stream_policy()) : "memory");
          else {
            tma3d(sb + (w == 0 ? OFF_MOD : w < 5 ? OFF_UV + (w - 1) * 16384 : w == 5 ? OFF_G : w == 6 ? OFF_U : OFF_D),
                  &tms.m[w == 0 ? 3 : w < 3 ? 4 : w < 5 ? 5 : w + 1], bar0 + 8 * (FB_MOD + w),
                  w == 0 ? 1024 + b * 16 : w < 3 || w == 7 ? 0 : w < 5 ? (pr & 7) * 64 : pr * 32, w == 7 ? b * 16 : w == 1 || w == 2 ? (b & 3) * 128 + (w - 1) * 64 : 0,
                  w == 1 || w == 2 ? 2 * hd : w == 3 || w == 4 ? (b >> 4) * 4 + 2 * rk + w - 3 : w == 5 || w == 6 ? rk : 0);
          }
        }
        __syncwarp();
      }
    }
    if (b < 112) {
      const int mt = warp & 1, dd = (warp >> 1) & 1;
      mbar_wait(bar0 + 8 * (XB + 4));
      const uint32_t ab = sb + (mt ? OFF_U : OFF_G) + (8 * (lane >> 4) + (lane & 7)) * 64 + (((2 * dd + ((lane >> 3) & 1)) ^ ((lane >> 1) & 3)) << 4);
      uint32_t base;
      asm volatile("mapa.shared::cluster.u32 %0, %1, %2;" : "=r"(base) : "r"(sb), "r"(dd));
      uint2 bb[16];
#pragma unroll
      for (int s = 0; s < 16; s++) bb[s] = *(const uint2*)(smem + OFF_BP + (g & 1) * 512 + (4 * s + tq) * 8);
      mbar_wait(bar0 + 8 * (FB_G + mt));
      float e[4][4] = {};
#pragma unroll
      for (int s = 0; s < 16; s++) { uint32_t a[4]; ldsm_t(a, ab + s * 1024); mma16(e[s & 3], a, bb[s].x, bb[s].y); }
      float r[4];
#pragma unroll
      for (int i = 0; i < 4; i++) r[i] = (e[0][i] + e[1][i]) + (e[2][i] + e[3][i]);
      if (tq < 2) st_async2(base + OFF_R4 + (8 * mt + g) * 176 + (10 * rk + 8 + tq) * 8, base + OFF_BAR + 8 * (XB + 5), tq ? r[1] : r[0], tq ? r[3] : r[2]);
    }
    return;
  }

  float* s_sm = (float*)(smem + OFF_SM);
  unsigned par, epoch;
  uint32_t rsb;
  {
    float* s_r4 = (float*)(smem + OFF_R4);
    asm volatile("barrier.cluster.arrive.relaxed.aligned;" ::: "memory");
    asm volatile("mapa.shared::cluster.u32 %0, %1, %2;" : "=r"(rsb) : "r"(sb), "r"(rk ^ 1));
    const float c0 = (arow & 1) ? bfhi(c0w) : bflo(c0w), c1 = (arow & 1) ? bfhi(c1w) : bflo(c1w);
    float acc[8] = {0, 0, 0, 0, 0, 0, 0, 0};
    fma8(acc, wm0, silu_bf(c0)); fma8(acc, wm1, silu_bf(c1));
    tred<4>(acc, lane, 8); tred<2>(acc, lane, 16);
    *(float2*)(s_r4 + warp * 64 + 8 * (lane & 7) + ((lane >> 1) & 4) + ((lane >> 3) & 2)) = make_float2(acc[0], acc[1]);
    nbar(1, 288);
    epoch = *(volatile unsigned*)(smem + OFF_MASK + 8);
    par = (epoch + 1) & 1;
    if (warp == 0) {
      float t = 0.f, ca = b < 16 ? 1.f : 0.f;
#pragma unroll
      for (int w = 0; w < 8; w++) { t += s_r4[w * 64 + lane]; ca += s_r4[w * 64 + 32 + lane]; }
      t += ca * s_sm[256 + lane];
      const float nb = __shfl_down_sync(~0u, t, 1);
      const uint32_t w0 = lane < 8 ? pack2t(t, nb, par) : pack2(t, nb);
      const uint32_t w1 = __shfl_down_sync(~0u, w0, 8), w2 = __shfl_down_sync(~0u, w0, 16), w3 = __shfl_down_sync(~0u, w0, 24);
      if (lane < 8 && !(lane & 1)) stx16(g_h + (b >> 5) * 512 + (b & 15) * 32 + (b & 16) + 2 * lane, make_uint4(w0, w1, w2, w3));
      __syncwarp();
      if (lane == 0) CNT_ADD(1);
    }
  }
  asm volatile("barrier.cluster.wait.acquire.aligned;" ::: "memory");
  {
    uint32_t a[4][4][4];
    mbar_wait(bar0 + 8 * (warp >> 1));
    const uint32_t ab = sb + OFF_WQ + (64 * warp + 8 * (lane >> 4) + (lane & 7)) * 128;
#pragma unroll
    for (int s = 0; s < 4; s++)
#pragma unroll
      for (int mt = 0; mt < 4; mt++) ldsm_t(a[s][mt], ab + s * 2048 + (((2 * mt + ((lane >> 3) & 1)) ^ (lane & 7)) << 4));
    uint4 v0, v1;
    const unsigned* ph = g_h + (g >> 1) * 512 + 64 * warp + 4 * (lane & 7);
    uint32_t off = OFF_B + warp * 272 + (32 * rk + 8 * tq + (lane & 4)) * 4;
    PIN(off); PINL(ph);
    mbar_wait(bar0 + 8 * XB);
    POLL { v0 = ldx16(ph); v1 = ldx16(ph + 32); RETRY(lop_x3(v0.x, v1.x, par)) }
    float d[4][4] = {};
#pragma unroll
    for (int mt = 0; mt < 4; mt++) {
      mma16(d[mt], a[0][mt], v0.x, v0.y); mma16(d[mt], a[1][mt], v0.z, v0.w);
      mma16(d[mt], a[2][mt], v1.x, v1.y); mma16(d[mt], a[3][mt], v1.z, v1.w);
    }
    float r[8];
#pragma unroll
    for (int mt = 0; mt < 4; mt++) { r[2 * mt] = d[mt][0] + d[mt][1]; r[2 * mt + 1] = d[mt][2] + d[mt][3]; }
    tred<4>(r, lane, 2); tred<2>(r, lane, 1);
    const float rc = __shfl_xor_sync(~0u, (lane & 4) ? r[0] : r[1], 4);
    const uint32_t wd = (lane & 4) ? pack2(rc, r[1]) : pack2(r[0], rc);
    const uint32_t w1 = __shfl_down_sync(~0u, wd, 8), w2 = __shfl_down_sync(~0u, wd, 16), w3 = __shfl_down_sync(~0u, wd, 24);
    asm volatile("{.reg .pred p; setp.lt.s32 p, %7, 8; @p st.shared.v4.b32 [%0], {%2,%3,%4,%5};\n"
                 "@p st.async.shared::cluster.mbarrier::complete_tx::bytes.v4.b32 [%1], {%2,%3,%4,%5}, [%6];}"
                 ::"r"(sb + off), "r"(rsb + off), "r"(wd), "r"(w1), "r"(w2), "r"(w3), "r"(rsb + OFF_BAR + 8 * QB), "r"(lane) : "memory");
    __syncwarp();
    arrive2(bar0 + 8 * QB, 0, lane == 0, false);
    arrive2(bar0 + 8 * (EB + 2), rsb + OFF_BAR + 8 * (EB + 2), lane == 0, lane == 0);
  }
  {
    uint32_t a[8][4];
    uint32_t a_bq = sb + OFF_B + (lane & 7) * 272 + (lane >> 3) * 16;
    unsigned* p_qa = g_qa + b * 64 + 8 * warp + 4 * lane;
    PIN(a_bq); PINL(p_qa);
    mbar_wait(bar0 + 8 * (FB_UK + (warp >> 2)));
    const uint32_t ab = sb + OFF_WUK + (warp >> 2) * 16384 + (16 * (warp & 3) + (lane & 15)) * 128;
#pragma unroll
    for (int s = 0; s < 8; s++) ldsm(a[s], ab + (s >> 2) * 8192 + (((2 * (s & 3) + (lane >> 4)) ^ (lane & 7)) << 4));
    mbar_wait(bar0 + 8 * QB);
    float d[4][4] = {};
#pragma unroll
    for (int y = 0; y < 4; y++) {
      uint32_t bq[4];
      ldsm(bq, a_bq + 64 * y);
      mma16(d[(2 * y) & 3], a[2 * y], bq[0], bq[1]); mma16(d[(2 * y + 1) & 3], a[2 * y + 1], bq[2], bq[3]);
    }
    float r[2] = {((d[0][0] + d[0][1]) + (d[1][0] + d[1][1])) + ((d[2][0] + d[2][1]) + (d[3][0] + d[3][1])),
                  ((d[0][2] + d[0][3]) + (d[1][2] + d[1][3])) + ((d[2][2] + d[2][3]) + (d[3][2] + d[3][3]))};
    tred<1>(r, lane, 1);
    r[0] += __shfl_xor_sync(~0u, r[0], 2);
    const float nb = __shfl_xor_sync(~0u, r[0], 4);
    const uint32_t w0 = lane < 8 ? pack2t(r[0], nb, par) : pack2(r[0], nb);
    const uint32_t w1 = __shfl_down_sync(~0u, w0, 8), w2 = __shfl_down_sync(~0u, w0, 16), w3 = __shfl_down_sync(~0u, w0, 24);
    if (lane < 2) stx16(p_qa, make_uint4(w0, w1, w2, w3));
    arrive2(bar0 + 8 * (EB + 4), rsb + OFF_BAR + 8 * (EB + 4), lane == 0, lane == 0);
  }
  {
    if (warp) nbar_arrive(3, 256); else { nbar(3, 256); if (lane == 0) CNT_ADD(2 + (b >> 6)); }
    asm volatile("setmaxnreg.inc.sync.aligned.u32 216;");
    const unsigned* pq = g_qa + rk * 4096 + tid * 4;
    uint32_t a_q = sb + OFF_Q + ((tid & 63) >> 3) * 2048 + (tid >> 6) * 128 + (((tid & 7) ^ (tid >> 6)) << 4);
    PINL(pq); PIN(a_q);
    mbar_wait(bar0 + 8 * (XB + 1));
    uint4 v[4];
    POLL {
#pragma unroll
      for (int k = 0; k < 4; k++) v[k] = ldx16(pq + 1024 * k);
      RETRY(lop_x3(v[0].x, v[1].x, par) | lop_x3(v[2].x, v[3].x, par))
    }
#pragma unroll
    for (int k = 0; k < 4; k++)
      asm volatile("st.shared.v4.b32 [%0], {%1,%2,%3,%4};" ::"r"((a_q + k * 512) ^ ((k & 1) << 6)), "r"(v[k].x), "r"(v[k].y), "r"(v[k].z), "r"(v[k].w) : "memory");
    if (warp >= 4) nbar_arrive(1, 256); else nbar(1, 256);
  }
  sb = __shfl_sync(~0u, sb, 0); bar0 = sb + OFF_BAR;
  if (warp < 4) {
    uint32_t qf[32][4];
#pragma unroll
    for (int s = 0; s < 32; s++) ldsm(qf[s], sb + OFF_Q + (s >> 2) * 2048 + (lane & 15) * 128 + (((2 * (s & 3) + (lane >> 4)) ^ (lane & 7)) << 4));
    float l0 = 0.f, l1 = 0.f, m0 = -1e30f, m1 = -1e30f;
    const float sc = 0.08838834764831845f * 1.4426950408889634f;
    const uint32_t kofs = (16 * warp + 8 * (lane >> 4) + (lane & 7)) * 128 + ((((lane >> 3) & 1) ^ (lane & 7)) << 4);
    uint32_t st = sb;
#pragma unroll 1
    for (int t = 0; t < 8; t++) {
      float sa[4][4] = {};
#pragma unroll
      for (int hf = 0; hf < 2; hf++) {
        const int n = 2 * t + hf;
        mbar_wait(bar0 + 8 * (FB_KV + n));
        uint32_t kf[16][4];
#pragma unroll
        for (int y = 0; y < 16; y++) ldsm(kf[y], st + (y >> 2) * 8192 + (kofs ^ ((y & 3) << 5)));
#pragma unroll
        for (int y = 0; y < 16; y++) {
          mma16(sa[(2 * y) & 3], qf[16 * hf + y], kf[y][0], kf[y][1]); mma16(sa[((2 * y) & 3) + 1], qf[16 * hf + y], kf[y][2], kf[y][3]);
        }
        __syncwarp();
        arrive2(bar0 + 8 * (EB + NSLOT + n), rsb + OFF_BAR + 8 * (EB + NSLOT + n), lane == 0 && n < 14, lane == 0 && n < 16 - NSLOT);
        if (hf == 0) arrive2(bar0 + 8 * EB, 0, lane == 0 && t == 0, false);
        st = st + SLOT == sb + NSLOT * SLOT ? sb : st + SLOT;
      }
#pragma unroll
      for (int i = 0; i < 4; i++) { sa[0][i] = (sa[0][i] + sa[2][i]) * sc; sa[1][i] = (sa[1][i] + sa[3][i]) * sc; }
      float cm[2] = {fmaxf(fmaxf(sa[0][0], sa[0][1]), fmaxf(sa[1][0], sa[1][1])), fmaxf(fmaxf(sa[0][2], sa[0][3]), fmaxf(sa[1][2], sa[1][3]))};
      tmax<1>(cm, lane, 1);
      cm[0] = fmaxf(cm[0], __shfl_xor_sync(~0u, cm[0], 2));
      float* pm = s_sm + (t & 1) * 64;
      if (tq < 2) pm[(g + 8 * tq) * 4 + warp] = cm[0];
      if (t >= 2) nbar(6 + (t & 1), 256); else nbar(3, 128);
      const float4 a0 = *(const float4*)(pm + g * 4), b0 = *(const float4*)(pm + g * 4 + 32);
      const float n0 = fmaxf(fmaxf(fmaxf(a0.x, a0.y), fmaxf(a0.z, a0.w)), m0), n1 = fmaxf(fmaxf(fmaxf(b0.x, b0.y), fmaxf(b0.z, b0.w)), m1);
      uint32_t pk[4];
#pragma unroll
      for (int i = 0; i < 2; i++) { pk[2 * i] = pack2(ex2(sa[i][0] - n0), ex2(sa[i][1] - n0)); pk[2 * i + 1] = pack2(ex2(sa[i][2] - n1), ex2(sa[i][3] - n1)); }
      *(uint4*)(smem + OFF_P + (t & 1) * 2048 + tid * 16) = make_uint4(pk[0], pk[1], pk[2], pk[3]);
      const float al0 = ex2(m0 - n0), al1 = ex2(m1 - n1);
      if (tid < 32 && tq == 0) *(float2*)(s_sm + 192 + (t & 1) * 16 + 2 * g) = make_float2(al0, al1);
      nbar_arrive(4 + (t & 1), 256);
      m0 = n0; m1 = n1;
      l0 = l0 * al0 + (bflo(pk[0]) + bfhi(pk[0])) + (bflo(pk[2]) + bfhi(pk[2]));
      l1 = l1 * al1 + (bflo(pk[1]) + bfhi(pk[1])) + (bflo(pk[3]) + bfhi(pk[3]));
    }
    float lr[2] = {l0, l1};
    tred<1>(lr, lane, 1);
    lr[0] += __shfl_xor_sync(~0u, lr[0], 2);
    if (tq < 2) s_sm[128 + (g + 8 * tq) * 4 + warp] = lr[0];
    nbar(3, 128);
    if (warp == 0 && tq < 2) {
      const float4 a0 = *(const float4*)(s_sm + 128 + (g + 8 * tq) * 4);
      stx8(g_ml + (16 * rk + g + 8 * tq) * 64 + pr, make_uint2(fbits(tq ? m1 : m0), fbits((a0.x + a0.y) + (a0.z + a0.w))));
    }
    if (warp == 0) { __syncwarp(); if (lane == 0) CNT_ADD(96 + 32 * rk); }
    nbar(2, 288);
    if (tid == 0) asm volatile("red.relaxed.gpu.global.xor.b64 [%0], %1;" ::"l"(scr->cnt + 32 + 32 * rk), "l"(1ull << pr) : "memory");
  } else {
    float o[16][4] = {};
    const uint32_t vofs = (warp & 1) * 16384 + (lane & 15) * 128 + (((lane >> 4) ^ (lane & 7)) << 4);
    const int hf = (warp >> 1) & 1;
    uint32_t st = sb + hf * SLOT;
    auto pv = [&](const int t, auto np) {
      constexpr int npre = decltype(np)::value;
      uint32_t vf[4][8][4];
      const int n = 2 * t + hf;
      mbar_wait(bar0 + 8 * (FB_KV + n));
#pragma unroll
      for (int s = 0; s < npre; s++)
#pragma unroll
        for (int y = 0; y < 8; y++) ldsm_t(vf[s][y], st + (y >> 2) * 8192 + s * 2048 + (vofs ^ ((y & 3) << 5)));
      nbar(4 + (t & 1), 256);
      const float2 al = *(const float2*)(s_sm + 192 + (t & 1) * 16 + 2 * g);
      uint4 pf[4];
#pragma unroll
      for (int s = 0; s < 4; s++) pf[s] = *(const uint4*)(smem + OFF_P + (t & 1) * 2048 + s * 512 + lane * 16);
      if (t < 6) nbar_arrive(6 + (t & 1), 256);
#pragma unroll
      for (int s = npre; s < 4; s++)
#pragma unroll
        for (int y = 0; y < 8; y++) ldsm_t(vf[s][y], st + (y >> 2) * 8192 + s * 2048 + (vofs ^ ((y & 3) << 5)));
#pragma unroll
      for (int nt = 0; nt < 16; nt++) { o[nt][0] *= al.x; o[nt][1] *= al.x; o[nt][2] *= al.y; o[nt][3] *= al.y; }
#pragma unroll
      for (int s = 0; s < 4; s++) {
        const uint32_t pa[4] = {pf[s].x, pf[s].y, pf[s].z, pf[s].w};
#pragma unroll
        for (int y = 0; y < 8; y++) { mma16(o[2 * y], pa, vf[s][y][0], vf[s][y][1]); mma16(o[2 * y + 1], pa, vf[s][y][2], vf[s][y][3]); }
      }
      __syncwarp();
      arrive2(bar0 + 8 * (EB + NSLOT + n), rsb + OFF_BAR + 8 * (EB + NSLOT + n), lane == 0 && n < 14, lane == 0 && n < 16 - NSLOT);
      st = st + 2 * SLOT >= sb + NSLOT * SLOT ? st - (NSLOT - 2) * SLOT : st + 2 * SLOT;
    };
#pragma unroll 1
    for (int t = 0; t < 7; t++) pv(t, IC<NPRE0>());
    pv(7, IC<NPRE1>());
    uint4* po = g_xo + ((size_t)((16 * rk + (g & 6)) * 4 + warp - 4) * 64 + pr) * RS + (lane & 7);
    const bool odd = lane & 4;
#pragma unroll
    for (int e = 0; e < 2; e++)
#pragma unroll
      for (int j2 = 0; j2 < 2; j2++) {
        uint32_t c0[4], c1[4];
#pragma unroll
        for (int i = 0; i < 4; i++) {
          c0[i] = i ? pack2(o[8 * j2 + i][2 * e], o[8 * j2 + i][2 * e + 1]) : pack2t(o[8 * j2][2 * e], o[8 * j2][2 * e + 1], par);
          c1[i] = i ? pack2(o[8 * j2 + 4 + i][2 * e], o[8 * j2 + 4 + i][2 * e + 1]) : pack2t(o[8 * j2 + 4][2 * e], o[8 * j2 + 4][2 * e + 1], par);
          const uint32_t r = __shfl_xor_sync(~0u, odd ? c0[i] : c1[i], 4);
          if (odd) c0[i] = r; else c1[i] = r;
        }
        stx16(po + e * 8 * 4 * 64 * RS + 8 * j2, make_uint4(c0[0], c0[1], c0[2], c0[3]));
        stx16(po + (e * 8 + 1) * 4 * 64 * RS + 8 * j2, make_uint4(c1[0], c1[1], c1[2], c1[3]));
      }
    nbar_arrive(2, 288);
  }
  tail(smem, scr, x, out, par, epoch, warp);
}

static void launch(void* const* d_in, void* d_out) {
  static TMaps tms;
  static bool init = false;
  static void* scr = nullptr;
  if (!init) {
    void* fn = nullptr; cudaDriverEntryPointQueryResult qr;
    cudaGetDriverEntryPoint("cuTensorMapEncodeTiled", &fn, cudaEnableDefault, &qr);
    EncFn f = (EncFn)fn;
    const CUtensorMapSwizzle S32 = CU_TENSOR_MAP_SWIZZLE_32B, S64 = CU_TENSOR_MAP_SWIZZLE_64B, S128 = CU_TENSOR_MAP_SWIZZLE_128B;
    const CUtensorMapL2promotion P128 = CU_TENSOR_MAP_L2_PROMOTION_L2_128B, P256 = CU_TENSOR_MAP_L2_PROMOTION_L2_256B;
    enc3d(f, &tms.m[0], d_in[2], 64, 512, 64, 8192, 128, 64, 128, 1, S128, P128);
    enc3d(f, &tms.m[1], d_in[3], 64, 512, 64, 8192, 128, 64, 64, 2, S128, P256);
    enc3d(f, &tms.m[2], d_in[1], 64, SK, 8, 1024, 128, 64, 64, 2, S128, P256);
    enc3d(f, &tms.m[3], d_in[11], 3072, 256, 2, 6144, 256 * 6144, 16, 256, 2, S32, P128);
    enc3d(f, &tms.m[4], d_in[4], 64, 512, 64, 8192, 128, 64, 64, 2, S128, P256);
    enc3d(f, &tms.m[5], d_in[5], 512, 128, 32, 1024, 128 * 1024, 64, 128, 1, S128, P128);
    enc3d(f, &tms.m[6], d_in[7], 1792, 256, 2, 3584, 256 * 3584, 32, 256, 1, S64, P128);
    enc3d(f, &tms.m[7], d_in[8], 1792, 256, 2, 3584, 256 * 3584, 32, 256, 1, S64, P128);
    enc3d(f, &tms.m[8], d_in[9], 64, 1792, 8, 1024, 128, 64, 16, 8, S128, P256);
    cudaFuncSetAttribute(fused_kernel, cudaFuncAttributeMaxDynamicSharedMemorySize, SMEM_BYTES);
    cudaGetSymbolAddress(&scr, g_scr);
    init = true;
  }
  fused_kernel<<<NCTA, 384, SMEM_BYTES>>>((const bf16*)d_in[0], (const bf16*)d_in[10], (const bf16*)d_in[11], (bf16*)d_out, (Scratch*)scr, tms);
}

}

extern "C" void kernel_launch(void* const* d_in, const int* in_sizes, int n_in, void* d_out, int out_size) {
  static int big = -1;
  if (big < 0) big = v9::fits();
  if (big) v9::launch(d_in, d_out); else v8::launch(d_in, d_out);
}
```
